```python
import torch

def _softmax(x, axis=-1):
    return torch.softmax(x, dim=axis)

def _gelu(x):
    return torch.nn.functional.gelu(x, approximate='tanh')

def _silu(x):
    return torch.nn.functional.silu(x)

def _sigmoid(x):
    return torch.sigmoid(x)

def _layernorm(x, axis=-1, eps=1e-05):
    m = x.mean(dim=axis, keepdim=True)
    v = x.var(dim=axis, keepdim=True, unbiased=False)
    return (x - m) / torch.sqrt(v + eps)

def _scatter_add(tgt, idx, src, axis=0):
    return tgt.clone().index_add_(axis, idx, src)

def _segment_sum(src, seg, n):
    out = torch.zeros((n,) + src.shape[1:], dtype=src.dtype)
    return out.index_add_(0, seg, src)

def _pad(x, pw):
    flat = tuple((v for pair in reversed(pw) for v in pair))
    return torch.nn.functional.pad(x, flat)
kernel_name = 'standalone__conformer_family_zipformer__speech'

def setup_inputs():

    _w = lambda a: (lambda t: t.to(torch.bfloat16) if t.is_floating_point() else t)(torch.as_tensor(a))
    B, T, D, K, H = (2, 1000, 256, 15, 4)
    sc = 0.1
    return {'x': _w((lambda *s: torch.randn(*s, dtype=torch.bfloat16) * 0.8)(B, T, D)), 'w_ff1a': _w((lambda *s: torch.randn(*s, dtype=torch.bfloat16) * 0.8)(D, 4 * D) * sc), 'w_ff1b': _w((lambda *s: torch.randn(*s, dtype=torch.bfloat16) * 0.8)(4 * D, D) * sc), 'w_qkv': _w((lambda *s: torch.randn(*s, dtype=torch.bfloat16) * 0.8)(D, 3 * D) * sc), 'w_o': _w((lambda *s: torch.randn(*s, dtype=torch.bfloat16) * 1.6)(D, D) * sc), 'w_pw1': _w((lambda *s: torch.randn(*s, dtype=torch.bfloat16) * 1.6)(D, 2 * D) * sc), 'dw': _w((lambda *s: torch.randn(*s, dtype=torch.bfloat16) * 0.4)(K, D)), 'w_pw2': _w((lambda *s: torch.randn(*s, dtype=torch.bfloat16) * 0.4)(D, D) * sc), 'w_ff2a': _w((lambda *s: torch.randn(*s, dtype=torch.bfloat16) * 0.8)(D, 4 * D) * sc), 'w_ff2b': _w((lambda *s: torch.randn(*s, dtype=torch.bfloat16) * 0.8)(4 * D, D) * sc)}

def reference(x, w_ff1a, w_ff1b, w_qkv, w_o, w_pw1, dw, w_pw2, w_ff2a, w_ff2b):
    B, T, D = x.shape
    K = dw.shape[0]
    H = 4
    Dh = D // H
    h = _layernorm(x, axis=-1)
    h = _silu(h @ w_ff1a) @ w_ff1b
    x = x + 0.5 * h
    h = _layernorm(x, axis=-1)
    qkv = h @ w_qkv
    q = (lambda x, *d: x.permute(*d))(qkv[..., :D].reshape(B, T, H, Dh), 0, 2, 1, 3)
    k = (lambda x, *d: x.permute(*d))(qkv[..., D:2 * D].reshape(B, T, H, Dh), 0, 2, 1, 3)
    v = (lambda x, *d: x.permute(*d))(qkv[..., 2 * D:].reshape(B, T, H, Dh), 0, 2, 1, 3)
    scale = Dh ** (-0.5)
    scores = torch.einsum('bhqd,bhkd->bhqk', q, k) * scale
    p = _softmax(scores, axis=-1)
    att = torch.einsum('bhqk,bhkd->bhqd', p, v)
    att = (lambda x, *d: x.permute(*d))(att, 0, 2, 1, 3).reshape(B, T, D)
    x = x + att @ w_o
    h = _layernorm(x, axis=-1)
    h = h @ w_pw1
    a, b = (h[..., :D].clone(), h[..., D:].clone())
    h = a * _sigmoid(b)
    pad = K // 2
    hp = _pad(h, ((0, 0), (pad, pad), (0, 0)))
    c = torch.zeros_like(h)
    for i in range(K):
        c = c + hp[:, i:i + T, :] * dw[i][None, None, :]
    x = x + _silu(c) @ w_pw2
    h = _layernorm(x, axis=-1)
    h = _silu(h @ w_ff2a) @ w_ff2b
    x = x + 0.5 * h
    return _layernorm(x, axis=-1)
```

```cpp
#include <cuda_runtime.h>
#include <cuda_bf16.h>
#include <cuda.h>
#include <stdint.h>

namespace {

constexpr int T_SEQ = 1000;
constexpr int DM = 256;
constexpr int NCTA = 128;
constexpr int NSTAGE = 12;
constexpr uint32_t STAGE_BYTES = 16384;
constexpr uint32_t TILE_BYTES = 8192;
constexpr uint32_t SM_STG = NSTAGE * STAGE_BYTES;
constexpr uint32_t SM_BAR = SM_STG + 32768;
constexpr uint32_t SM_CS = SM_BAR + 256;
constexpr uint32_t SM_TOTAL = SM_BAR + 3072;
constexpr int CS_QKV = 0, CS_PW1 = 192, CS_FF2 = 320;
constexpr uint32_t SPIN_LIMIT = 1u << 22;
constexpr float LN_EPS = 1e-5f;
constexpr float SM_SCALE_LOG2 = 0.125f * 1.4426950408889634f;

enum { BAR_LN0 = 1, BAR_K, BAR_V, BAR_Q, BAR_MERGE, BAR_G, BAR_C, BAR_CS, BAR_WG1 };

struct Params {
  CUtensorMap m_ff1a, m_ff1b, m_qkv, m_o, m_pw1, m_pw2, m_ff2a, m_ff2b;
  const __nv_bfloat16 *x, *w_ff1b, *w_qkv, *w_o, *w_pw1, *dw, *w_pw2, *w_ff2a, *w_ff2b;
  __nv_bfloat16* out;
};

__device__ uint4 g_ag[5][NCTA][4][128];
__device__ uint4 g_st[4][NCTA][32];
__device__ uint4 g_rs[2][NCTA][3][4][128];
__device__ uint4 g_halo[NCTA][2][3][32];
__device__ uint4 g_kv[8][2][16][512];
__device__ uint32_t g_flag[8][32];
__device__ uint4 g_cs[576];
__device__ uint32_t g_epoch[NCTA];
#define PROF_MARK(i)

__device__ __forceinline__ void mbar_init(uint32_t bar, uint32_t cnt) {
  asm volatile("mbarrier.init.shared::cta.b64 [%0], %1;" :: "r"(bar), "r"(cnt) : "memory");
}
__device__ __forceinline__ void mbar_wait(uint32_t bar, uint32_t parity) {
  asm volatile("{\n.reg .pred p;\n.reg .u32 c;\nmov.u32 c, 0;\n"
               "WAIT_LOOP:\nmbarrier.try_wait.parity.shared::cta.b64 p, [%0], %1;\n@p bra WAIT_DONE;\n"
               "add.u32 c, c, 1;\nsetp.lt.u32 p, c, %2;\n@p bra WAIT_LOOP;\nWAIT_DONE:\n}"
               :: "r"(bar), "r"(parity), "n"(SPIN_LIMIT) : "memory");
}
__device__ __forceinline__ void mbar_arrive(uint32_t bar) {
  asm volatile("mbarrier.arrive.shared::cta.b64 _, [%0];" :: "r"(bar) : "memory");
}
__device__ __forceinline__ void mbar_expect(uint32_t bar, uint32_t bytes) {
  asm volatile("mbarrier.arrive.expect_tx.shared::cta.b64 _, [%0], %1;" :: "r"(bar), "r"(bytes) : "memory");
}
#define bar_sync(id, n) asm volatile("bar.sync %0, %1;" :: "n"((int)(id)), "n"(n) : "memory")
#define bar_arrive(id, n) asm volatile("bar.arrive %0, %1;" :: "n"((int)(id)), "n"(n) : "memory")
__device__ __forceinline__ void fence_async_smem() { asm volatile("fence.proxy.async.shared::cta;" ::: "memory"); }

__device__ __forceinline__ void st_vec(uint4* p, uint32_t a, uint32_t b, uint32_t c, uint32_t d) {
  asm volatile("{\n.reg .b128 v;\n.reg .b64 lo, hi;\nmov.b64 lo, {%1, %2};\nmov.b64 hi, {%3, %4};\nmov.b128 v, {lo, hi};\n"
               "st.relaxed.gpu.global.b128 [%0], v;\n}" :: "l"(p), "r"(a), "r"(b), "r"(c), "r"(d) : "memory");
}
__device__ __forceinline__ void ld_vec(const uint4* p, uint32_t& a, uint32_t& b, uint32_t& c, uint32_t& d) {
  asm volatile("{\n.reg .b128 v;\n.reg .b64 lo, hi;\nld.relaxed.gpu.global.b128 v, [%4];\nmov.b128 {lo, hi}, v;\n"
               "mov.b64 {%0, %1}, lo;\nmov.b64 {%2, %3}, hi;\n}" : "=r"(a), "=r"(b), "=r"(c), "=r"(d) : "l"(p) : "memory");
}
__device__ __forceinline__ void sts128(uint32_t a, uint32_t x, uint32_t y, uint32_t z, uint32_t w) {
  asm volatile("st.shared.v4.u32 [%0], {%1, %2, %3, %4};" :: "r"(a), "r"(x), "r"(y), "r"(z), "r"(w) : "memory");
}
__device__ __forceinline__ void lds128(uint32_t a, uint32_t& x, uint32_t& y, uint32_t& z, uint32_t& w) {
  asm volatile("ld.shared.v4.u32 {%0, %1, %2, %3}, [%4];" : "=r"(x), "=r"(y), "=r"(z), "=r"(w) : "r"(a) : "memory");
}
__device__ __forceinline__ uint32_t lds32(uint32_t a) {
  uint32_t x; asm volatile("ld.shared.u32 %0, [%1];" : "=r"(x) : "r"(a) : "memory"); return x;
}
__device__ __forceinline__ void sts32(uint32_t a, uint32_t x) { asm volatile("st.shared.u32 [%0], %1;" :: "r"(a), "r"(x) : "memory"); }
__device__ __forceinline__ float2 lds64f(uint32_t a) {
  float2 v; asm volatile("ld.shared.v2.f32 {%0, %1}, [%2];" : "=f"(v.x), "=f"(v.y) : "r"(a) : "memory"); return v;
}
__device__ __forceinline__ void stsm4(uint32_t a, const uint32_t* r) {
  asm volatile("stmatrix.sync.aligned.m8n8.x4.shared.b16 [%0], {%1, %2, %3, %4};" :: "r"(a), "r"(r[0]), "r"(r[1]), "r"(r[2]), "r"(r[3]) : "memory");
}
__device__ __forceinline__ void ldsm4(uint32_t a, uint32_t* r) {
  asm volatile("ldmatrix.sync.aligned.m8n8.x4.shared.b16 {%0, %1, %2, %3}, [%4];" : "=r"(r[0]), "=r"(r[1]), "=r"(r[2]), "=r"(r[3]) : "r"(a) : "memory");
}
__device__ __forceinline__ uint32_t pack2(float lo, float hi) {
  uint32_t r; asm("cvt.rn.bf16x2.f32 %0, %1, %2;" : "=r"(r) : "f"(hi), "f"(lo)); return r;
}
__device__ __forceinline__ float bf_lo(uint32_t w) { return __uint_as_float(w << 16); }
__device__ __forceinline__ float bf_hi(uint32_t w) { return __uint_as_float(w & 0xffff0000u); }
__device__ __forceinline__ float tanh_hw(float x) { float y; asm volatile("tanh.approx.f32 %0, %1;" : "=f"(y) : "f"(x)); return y; }
__device__ __forceinline__ float ex2_hw(float x) { float y; asm("ex2.approx.ftz.f32 %0, %1;" : "=f"(y) : "f"(x)); return y; }

__device__ __forceinline__ uint32_t here(uint32_t v) { asm volatile("" : "+r"(v)); return v; }

#define WG_FENCE() asm volatile("wgmma.fence.sync.aligned;" ::: "memory")
#define WG_COMMIT() asm volatile("wgmma.commit_group.sync.aligned;" ::: "memory")
#define WG_WAIT(n) asm volatile("wgmma.wait_group.sync.aligned %0;" :: "n"(n) : "memory")

template <int N> __device__ __forceinline__ void pin(float (&d)[N]) {
#pragma unroll
  for (int i = 0; i < N; i++) asm volatile("" : "+f"(d[i]) :: "memory");
}
template <int N> __device__ __forceinline__ void pin(uint32_t (&d)[N]) {
#pragma unroll
  for (int i = 0; i < N; i++) asm volatile("" : "+r"(d[i]) :: "memory");
}

__device__ __forceinline__ uint64_t mkdesc(uint32_t addr) {
  return (uint64_t)((addr & 0x3FFFF) >> 4) | (uint64_t(1) << 16) | (uint64_t(64) << 32) | (uint64_t(1) << 62);
}

#define WG_D32 "{%0, %1, %2, %3, %4, %5, %6, %7, %8, %9, %10, %11, %12, %13, %14, %15, %16, %17, %18, %19, %20, %21, %22, %23, %24, %25, %26, %27, %28, %29, %30, %31}"
template <int TB> __device__ __forceinline__ void wgmma64_acc(float (&d)[32], const uint32_t* a, uint64_t db) {
  asm volatile("wgmma.mma_async.sync.aligned.m64n64k16.f32.bf16.bf16 " WG_D32 ", {%32, %33, %34, %35}, %36, 1, 1, 1, %37;"
    : "+f"(d[0]), "+f"(d[1]), "+f"(d[2]), "+f"(d[3]), "+f"(d[4]), "+f"(d[5]), "+f"(d[6]), "+f"(d[7]),
      "+f"(d[8]), "+f"(d[9]), "+f"(d[10]), "+f"(d[11]), "+f"(d[12]), "+f"(d[13]), "+f"(d[14]), "+f"(d[15]),
      "+f"(d[16]), "+f"(d[17]), "+f"(d[18]), "+f"(d[19]), "+f"(d[20]), "+f"(d[21]), "+f"(d[22]), "+f"(d[23]),
      "+f"(d[24]), "+f"(d[25]), "+f"(d[26]), "+f"(d[27]), "+f"(d[28]), "+f"(d[29]), "+f"(d[30]), "+f"(d[31])
    : "r"(a[0]), "r"(a[1]), "r"(a[2]), "r"(a[3]), "l"(db), "n"(TB));
}
template <int TB> __device__ __forceinline__ void wgmma64_set(float (&d)[32], const uint32_t* a, uint64_t db) {
  asm volatile("wgmma.mma_async.sync.aligned.m64n64k16.f32.bf16.bf16 " WG_D32 ", {%32, %33, %34, %35}, %36, 0, 1, 1, %37;"
    : "=f"(d[0]), "=f"(d[1]), "=f"(d[2]), "=f"(d[3]), "=f"(d[4]), "=f"(d[5]), "=f"(d[6]), "=f"(d[7]),
      "=f"(d[8]), "=f"(d[9]), "=f"(d[10]), "=f"(d[11]), "=f"(d[12]), "=f"(d[13]), "=f"(d[14]), "=f"(d[15]),
      "=f"(d[16]), "=f"(d[17]), "=f"(d[18]), "=f"(d[19]), "=f"(d[20]), "=f"(d[21]), "=f"(d[22]), "=f"(d[23]),
      "=f"(d[24]), "=f"(d[25]), "=f"(d[26]), "=f"(d[27]), "=f"(d[28]), "=f"(d[29]), "=f"(d[30]), "=f"(d[31])
    : "r"(a[0]), "r"(a[1]), "r"(a[2]), "r"(a[3]), "l"(db), "n"(TB));
}

template <bool FIRST> __device__ __forceinline__ void mma_tile(float (&d)[32], const uint32_t (&a)[16], uint32_t tile) {
  const uint64_t db = mkdesc(tile);
  WG_FENCE();
#pragma unroll
  for (int s = 0; s < 4; s++) {
    if (FIRST && s == 0) wgmma64_set<1>(d, &a[0], db); else wgmma64_acc<1>(d, &a[4 * s], db + s * 128);
  }
  WG_COMMIT();
}

__device__ __forceinline__ void attn_scores(float (&S)[2][32], const uint32_t (&Q)[16], uint32_t base, uint32_t fill) {
  const uint32_t st = fill % NSTAGE;
  mbar_wait(base + SM_BAR + st * 8, (fill / NSTAGE) & 1);
  const uint64_t dk = mkdesc(base + st * STAGE_BYTES);
  WG_FENCE();
#pragma unroll
  for (int h = 0; h < 2; h++)
#pragma unroll
    for (int s = 0; s < 4; s++) {
      if (s == 0) wgmma64_set<0>(S[h], &Q[0], dk + h * 512); else wgmma64_acc<0>(S[h], &Q[4 * s], dk + h * 512 + s * 2);
    }
  WG_COMMIT();
}

struct Ring {
  uint32_t base, st, ph, rst;
  __device__ __forceinline__ uint32_t acquire() {
    mbar_wait(base + SM_BAR + st * 8, ph);
    const uint32_t a = base + st * STAGE_BYTES;
    if (++st == NSTAGE) { st = 0; ph ^= 1; }
    return a;
  }
  __device__ __forceinline__ void release() {
    if ((threadIdx.x & 31) == 0) mbar_arrive(base + SM_BAR + 96 + rst * 8);
    if (++rst == NSTAGE) rst = 0;
  }
  __device__ __forceinline__ void seek(uint32_t fill) { st = fill % NSTAGE; ph = (fill / NSTAGE) & 1; rst = st; }
};

__device__ __forceinline__ void publish(uint4* dst, const uint32_t (&a)[16], uint32_t tag) {
#pragma unroll
  for (int s = 0; s < 4; s++) st_vec(dst + s * 128, (a[4 * s] & ~1u) | tag, a[4 * s + 1], a[4 * s + 2], a[4 * s + 3]);
}
__device__ __forceinline__ void fetch(const uint4* src, uint32_t (&a)[16]) {
#pragma unroll
  for (int s = 0; s < 4; s++) ld_vec(src + s * 128, a[4 * s], a[4 * s + 1], a[4 * s + 2], a[4 * s + 3]);
}
__device__ __forceinline__ void confirm(const uint4* src, uint32_t (&a)[16], uint32_t tag) {
  uint32_t spin = 0;
  while (true) {
    const uint32_t bad = ((a[0] ^ tag) | (a[4] ^ tag) | (a[8] ^ tag) | (a[12] ^ tag)) & 1u;
    if (!__any_sync(0xffffffffu, bad)) break;
    if (++spin > SPIN_LIMIT) break;
    fetch(src, a);
  }
#pragma unroll
  for (int s = 0; s < 4; s++) a[4 * s] &= ~1u;
  pin(a);
}
__device__ __forceinline__ void pack_acc(const float (&d)[32], uint32_t (&a)[16]) {
#pragma unroll
  for (int i = 0; i < 16; i++) a[i] = pack2(d[2 * i], d[2 * i + 1]);
}
__device__ __forceinline__ void unpack_acc(const uint32_t (&a)[16], float (&d)[32], float scale) {
#pragma unroll
  for (int i = 0; i < 16; i++) { d[2 * i] = bf_lo(a[i]) * scale; d[2 * i + 1] = bf_hi(a[i]) * scale; }
}

__device__ __forceinline__ void res_store(uint32_t slot, const uint32_t (&a)[16]) {
#pragma unroll
  for (int s = 0; s < 4; s++) sts128(slot + s * 512, a[4 * s], a[4 * s + 1], a[4 * s + 2], a[4 * s + 3]);
}
__device__ __forceinline__ void res_load(uint32_t slot, float (&d)[32], float scale) {
  uint32_t a[16];
#pragma unroll
  for (int s = 0; s < 4; s++) lds128(slot + s * 512, a[4 * s], a[4 * s + 1], a[4 * s + 2], a[4 * s + 3]);
  unpack_acc(a, d, scale);
}

struct RowStat { float s0, q0, s1, q1; };
__device__ __forceinline__ RowStat stat_publish(const float (&d)[32], uint4* dst, uint32_t tag) {
  RowStat t = {0.f, 0.f, 0.f, 0.f};
#pragma unroll
  for (int j = 0; j < 8; j++) {
    t.s0 += d[4 * j] + d[4 * j + 1];
    t.q0 = fmaf(d[4 * j], d[4 * j], fmaf(d[4 * j + 1], d[4 * j + 1], t.q0));
    t.s1 += d[4 * j + 2] + d[4 * j + 3];
    t.q1 = fmaf(d[4 * j + 2], d[4 * j + 2], fmaf(d[4 * j + 3], d[4 * j + 3], t.q1));
  }
#pragma unroll
  for (int m = 1; m <= 2; m <<= 1) {
    t.s0 += __shfl_xor_sync(0xffffffffu, t.s0, m);
    t.q0 += __shfl_xor_sync(0xffffffffu, t.q0, m);
    t.s1 += __shfl_xor_sync(0xffffffffu, t.s1, m);
    t.q1 += __shfl_xor_sync(0xffffffffu, t.q1, m);
  }
  t.s0 = __uint_as_float(__float_as_uint(t.s0) & ~1u);
  if ((threadIdx.x & 3) == 0)
    st_vec(dst, __float_as_uint(t.s0) | tag, __float_as_uint(t.q0), __float_as_uint(t.s1), __float_as_uint(t.q1));
  return t;
}
struct RowNorm { float rs0, nm0, rs1, nm1; };
__device__ __forceinline__ RowNorm stat_gather(RowStat own, const uint4* grp, int r, uint32_t tag) {
  uint32_t v[3][4];
  uint32_t spin = 0;
  while (true) {
#pragma unroll
    for (int j = 0; j < 3; j++) ld_vec(grp + ((r + 1 + j) & 3) * 32, v[j][0], v[j][1], v[j][2], v[j][3]);
    const uint32_t bad = ((v[0][0] ^ tag) | (v[1][0] ^ tag) | (v[2][0] ^ tag)) & 1u;
    if (!__any_sync(0xffffffffu, bad)) break;
    if (++spin > SPIN_LIMIT) break;
  }
  const float s0 = (own.s0 + __uint_as_float(v[1][0] & ~1u)) + (__uint_as_float(v[0][0] & ~1u) + __uint_as_float(v[2][0] & ~1u));
  const float q0 = (own.q0 + __uint_as_float(v[1][1])) + (__uint_as_float(v[0][1]) + __uint_as_float(v[2][1]));
  const float s1 = (own.s1 + __uint_as_float(v[1][2])) + (__uint_as_float(v[0][2]) + __uint_as_float(v[2][2]));
  const float q1 = (own.q1 + __uint_as_float(v[1][3])) + (__uint_as_float(v[0][3]) + __uint_as_float(v[2][3]));
  const float m0 = s0 * (1.f / DM), m1 = s1 * (1.f / DM);
  RowNorm n;
  n.rs0 = rsqrtf(fmaxf(fmaf(-m0, m0, q0 * (1.f / DM)), 0.f) + LN_EPS);
  n.rs1 = rsqrtf(fmaxf(fmaf(-m1, m1, q1 * (1.f / DM)), 0.f) + LN_EPS);
  n.nm0 = -m0 * n.rs0;
  n.nm1 = -m1 * n.rs1;
  return n;
}
template <int J0, int J1> __device__ __forceinline__ void fold_ln(float (&d)[32], const RowNorm& n, uint32_t cs) {
#pragma unroll
  for (int j = J0; j < J1; j++) {
    const float2 c = lds64f(cs + j * 32);
    d[4 * j] = fmaf(d[4 * j], n.rs0, n.nm0 * c.x);
    d[4 * j + 1] = fmaf(d[4 * j + 1], n.rs0, n.nm0 * c.y);
    d[4 * j + 2] = fmaf(d[4 * j + 2], n.rs1, n.nm1 * c.x);
    d[4 * j + 3] = fmaf(d[4 * j + 3], n.rs1, n.nm1 * c.y);
  }
}
template <int J0, int J1> __device__ __forceinline__ void silu_part(float (&d)[32], uint32_t (&h)[16], const RowNorm& n, uint32_t cs) {
  fold_ln<J0, J1>(d, n, cs);
#pragma unroll
  for (int i = 2 * J0; i < 2 * J1; i++) {
    const float a = d[2 * i], b = d[2 * i + 1];
    h[i] = pack2(fmaf(a, tanh_hw(a), a), fmaf(b, tanh_hw(b), b));
  }
}

__device__ __forceinline__ void tma_tile(uint32_t base, uint32_t& n, const CUtensorMap* map, int x, int y) {
  const uint32_t f = n >> 1, st = f % NSTAGE, full = base + SM_BAR + st * 8;
  if ((n & 1) == 0) {
    if (f >= NSTAGE) mbar_wait(base + SM_BAR + 96 + st * 8, ((f / NSTAGE) - 1) & 1);
    mbar_expect(full, STAGE_BYTES);
  }
  asm volatile("cp.async.bulk.tensor.2d.shared::cluster.global.mbarrier::complete_tx::bytes [%0], [%1, {%3, %4}], [%2];"
               :: "r"(base + st * STAGE_BYTES + (n & 1) * TILE_BYTES), "l"(map), "r"(full), "r"(x), "r"(y) : "memory");
  n++;
}
__device__ __forceinline__ void tma_gemm_in(uint32_t base, uint32_t& n, const CUtensorMap* map, int r, int nb, int x0, int xs, int xm) {
#pragma unroll 1
  for (int i = 0; i < 4 * nb; i++) {
    int blk = i, kc = r;
    if (i >= nb) { blk = (i - nb) / 3; kc = (r + 1 + (i - nb) % 3) & 3; }
    tma_tile(base, n, map, (x0 + blk * xs) % xm, kc * 64);
  }
}
__device__ __forceinline__ void tma_ffn(uint32_t base, uint32_t& n, const CUtensorMap* ma, const CUtensorMap* mb, int r) {
  tma_gemm_in(base, n, ma, r, 4, 256 * r, 64, 1024);
#pragma unroll 1
  for (int i = 0; i < 16; i++) tma_tile(base, n, mb, ((r + 1 + (i >> 2)) & 3) * 64, 256 * r + (i & 3) * 64);
}
__device__ __forceinline__ void l2_prefetch(const void* p, uint32_t total, int b) {
  const uint32_t part = total / NCTA;
  asm volatile("cp.async.bulk.prefetch.L2.global [%0], %1;" :: "l"((const char*)p + (size_t)b * part), "r"(part) : "memory");
}

__global__ void __launch_bounds__(384, 1) conformer_kernel(const __grid_constant__ Params p) {
  extern __shared__ __align__(1024) uint8_t smem[];
  const uint32_t base = (uint32_t)__cvta_generic_to_shared(smem);
  const int tid = threadIdx.x, lane = tid & 31;
  const int cw = __shfl_sync(0xffffffffu, tid >> 5, 0), wg = cw >> 2, w = cw & 3;
  const int b = blockIdx.x, r = b & 3, tile = b >> 2, batch = tile >> 4, t = tile & 15;
  const uint32_t epoch = ((volatile uint32_t*)g_epoch)[b] + 1;
  PROF_MARK(0);

  if (tid == 256) {
    if (base & 1023) __trap();
    for (int i = 0; i < NSTAGE; i++) { mbar_init(base + SM_BAR + i * 8, 1); mbar_init(base + SM_BAR + 96 + i * 8, 4); }
    fence_async_smem();
  }
  if (wg == 1) { sts32(base + SM_CS + (CS_FF2 + tid - 128) * 4, 0); sts32(base + SM_CS + (CS_FF2 + tid) * 4, 0); }
  __syncthreads();

  if (wg == 2) {
    asm volatile("setmaxnreg.dec.sync.aligned.u32 40;");
    if (w == 0) {
      uint32_t n = 0;
      if (lane == 0) {
        tma_ffn(base, n, &p.m_ff1a, &p.m_ff1b, r);
        tma_gemm_in(base, n, &p.m_qkv, r, 3, 256 + 64 * r, 256, 768);
      }
      __syncwarp();
      const uint32_t* flag = &g_flag[batch * 4 + r][lane];
      uint32_t ready = 0;
#pragma unroll 1
      for (int i = 0; i < 16; i++) {
        const int kind = (i >> 1) & 1, blk = (i >> 2) * 2 + (i & 1);
        const uint32_t need = 3u << (kind * 16 + blk * 2);
        uint32_t spin = 0;
        while ((ready & need) != need) {
          uint32_t f;
          asm volatile("ld.acquire.gpu.global.u32 %0, [%1];" : "=r"(f) : "l"(flag) : "memory");
          ready = __ballot_sync(0xffffffffu, f == epoch);
          if (++spin > SPIN_LIMIT) break;
        }
        if (lane == 0) {
          const uint32_t f = 22 + i, st = f % NSTAGE, full = base + SM_BAR + st * 8;
          mbar_wait(base + SM_BAR + 96 + st * 8, ((f / NSTAGE) - 1) & 1);
          mbar_expect(full, STAGE_BYTES);
          asm volatile("fence.proxy.async.global;" ::: "memory");
          asm volatile("cp.async.bulk.shared::cluster.global.mbarrier::complete_tx::bytes [%0], [%1], %2, [%3];"
                       :: "r"(base + st * STAGE_BYTES), "l"(&g_kv[batch * 4 + r][kind][blk * 2][0]), "r"(STAGE_BYTES), "r"(full) : "memory");
        }
        __syncwarp();
      }
      if (lane == 0) {
        n = 76;
        tma_gemm_in(base, n, &p.m_o, r, 1, 64 * r, 0, 256);
#pragma unroll 1
        for (int i = 0; i < 8; i++) tma_tile(base, n, &p.m_pw1, (i & 1) * 256 + 64 * r, ((r + (i >> 1)) & 3) * 64);
        tma_gemm_in(base, n, &p.m_pw2, r, 1, 64 * r, 0, 256);
        tma_ffn(base, n, &p.m_ff2a, &p.m_ff2b, r);
      }
    } else if (w < 3) {
      const int kind = w - 1;
      if (kind == 0) bar_sync(BAR_K, 160); else bar_sync(BAR_V, 160);
      if (lane == 0) {
        asm volatile("cp.async.bulk.global.shared::cta.bulk_group [%0], [%1], %2;"
                     :: "l"(&g_kv[batch * 4 + r][kind][t][0]), "r"(base + SM_STG + kind * TILE_BYTES), "r"(TILE_BYTES) : "memory");
        asm volatile("cp.async.bulk.commit_group;\ncp.async.bulk.wait_group 0;" ::: "memory");
        asm volatile("st.release.gpu.global.u32 [%0], %1;" :: "l"(&g_flag[batch * 4 + r][kind * 16 + t]), "r"(epoch) : "memory");
      }
    } else if (lane == 0) {
      l2_prefetch(p.w_ff1b, 1024 * 256 * 2, b);
      l2_prefetch(p.w_o, 256 * 256 * 2, b);
      l2_prefetch(p.w_pw2, 256 * 256 * 2, b);
      l2_prefetch(p.w_ff2b, 1024 * 256 * 2, b);
    }
  } else {
    asm volatile("setmaxnreg.inc.sync.aligned.u32 232;");
    const uint32_t tag = epoch & 1;
    const int g = lane >> 2, q = lane & 3, th = tid & 127;
    const uint32_t stg = base + SM_STG;
    const uint32_t mrow = 16 * w + ((lane >> 3) & 1) * 8 + (lane & 7);
    const uint32_t maddr = stg + mrow * 128 + (((lane >> 4) ^ (lane & 7)) << 4);
    const size_t row0 = (size_t)batch * T_SEQ + t * 64;
    const int nvalid = T_SEQ - t * 64;

    uint32_t xres[16];
    {
      const int u = tid >> 2, row = ((u & 1) << 2) | ((u >> 1) & 3) | (u & ~7);
      const uint4* src = (const uint4*)(p.x + (row0 + row) * DM) + q;
      uint4 v[8];
#pragma unroll
      for (int i = 0; i < 8; i++) v[i] = row < nvalid ? __ldg(src + 4 * i) : make_uint4(0, 0, 0, 0);
      if (wg == 0) {
        const uint32_t* xs = (const uint32_t*)(p.x + (row0 + 16 * w + g) * DM + 64 * r) + q;
#pragma unroll
        for (int i = 0; i < 16; i++) xres[i] = (16 * w + g + (i & 1) * 8) < nvalid ? __ldg(xs + (i & 1) * 8 * (DM / 2) + (i >> 1) * 4) : 0u;
      }
      float s = 0.f, ss = 0.f;
#pragma unroll
      for (int i = 0; i < 8; i++) {
        const uint32_t e[4] = {v[i].x, v[i].y, v[i].z, v[i].w};
#pragma unroll
        for (int k = 0; k < 4; k++) {
          const float lo = bf_lo(e[k]), hi = bf_hi(e[k]);
          s += lo + hi;
          ss = fmaf(lo, lo, fmaf(hi, hi, ss));
        }
      }
      s += __shfl_xor_sync(0xffffffffu, s, 1); ss += __shfl_xor_sync(0xffffffffu, ss, 1);
      s += __shfl_xor_sync(0xffffffffu, s, 2); ss += __shfl_xor_sync(0xffffffffu, ss, 2);
      const float m = s * (1.f / DM), rs = rsqrtf(fmaxf(fmaf(-m, m, ss * (1.f / DM)), 0.f) + LN_EPS), nm = -m * rs;
#pragma unroll
      for (int i = 0; i < 8; i++) {
        const uint32_t e[4] = {v[i].x, v[i].y, v[i].z, v[i].w};
        uint32_t o[4];
#pragma unroll
        for (int k = 0; k < 4; k++) o[k] = pack2(fmaf(bf_lo(e[k]), rs, nm), fmaf(bf_hi(e[k]), rs, nm));
        const int ci = 4 * i + q;
        sts128(stg + (ci >> 3) * TILE_BYTES + row * 128 + (((ci & 7) ^ (row & 7)) << 4), o[0], o[1], o[2], o[3]);
      }
    }
    bar_sync(BAR_LN0, 256);
    PROF_MARK(1);

    Ring ring;
    ring.base = base;
    ring.seek(0);
    uint32_t A[4][16];
    RowStat own = {0.f, 0.f, 0.f, 0.f};
    const uint32_t csq = base + SM_CS + q * 8;
    const uint32_t res = stg + 3 * TILE_BYTES + w * 2048 + lane * 16;
    if (wg == 0) {
#pragma unroll
      for (int c = 0; c < 4; c++)
#pragma unroll
        for (int s = 0; s < 4; s++) ldsm4((maddr ^ (s << 5)) + ((r + c) & 3) * TILE_BYTES, &A[c][4 * s]);
      __syncwarp();
      res_store(res, xres);
    } else {
      if (b < 72) {
        const __nv_bfloat16* wp; int ld, col;
        if (b < 24) { wp = p.w_qkv; ld = 768; col = b * 32; }
        else if (b < 40) { wp = p.w_pw1; ld = 512; col = (b - 24) * 32; }
        else { wp = p.w_ff2a; ld = 1024; col = (b - 40) * 32; }
        const uint4* src = (const uint4*)(wp + (size_t)(th >> 2) * ld + col + q * 8);
        float c[8] = {0.f, 0.f, 0.f, 0.f, 0.f, 0.f, 0.f, 0.f};
#pragma unroll
        for (int i = 0; i < 8; i++) {
          const uint4 v = __ldg(src + i * 4 * ld);
          c[0] += bf_lo(v.x); c[1] += bf_hi(v.x); c[2] += bf_lo(v.y); c[3] += bf_hi(v.y);
          c[4] += bf_lo(v.z); c[5] += bf_hi(v.z); c[6] += bf_lo(v.w); c[7] += bf_hi(v.w);
        }
#pragma unroll
        for (int m = 4; m <= 16; m <<= 1)
#pragma unroll
          for (int k = 0; k < 8; k++) c[k] += __shfl_xor_sync(0xffffffffu, c[k], m);
        if (lane < 4) {
          const uint32_t a = base + SM_CS + w * 128 + lane * 32;
          sts128(a, __float_as_uint(c[0]), __float_as_uint(c[1]), __float_as_uint(c[2]), __float_as_uint(c[3]));
          sts128(a + 16, __float_as_uint(c[4]), __float_as_uint(c[5]), __float_as_uint(c[6]), __float_as_uint(c[7]));
        }
        bar_sync(BAR_WG1, 128);
        if (th < 8) {
          float o[4] = {0.f, 0.f, 0.f, 0.f};
#pragma unroll
          for (int k = 0; k < 4; k++) {
            uint32_t e[4];
            lds128(base + SM_CS + k * 128 + here(th) * 16, e[0], e[1], e[2], e[3]);
#pragma unroll
            for (int i = 0; i < 4; i++) o[i] += __uint_as_float(e[i]);
          }
          st_vec(&g_cs[b * 8 + th], (__float_as_uint(o[0]) & ~1u) | tag, __float_as_uint(o[1]), __float_as_uint(o[2]), __float_as_uint(o[3]));
        }
        bar_sync(BAR_WG1, 128);
      }
#pragma unroll 1
      for (int i = th; i < 144; i += 128) {
        int src;
        if (i < 48) src = ((64 + 16 * r + (i >> 4) * 64) % 192) + (i & 15);
        else if (i < 80) src = 192 + ((i - 48) >> 4) * 64 + 16 * r + (i & 15);
        else src = 320 + 64 * r + (i - 80);
        uint32_t e[4], spin = 0;
        do {
          ld_vec(&g_cs[src], e[0], e[1], e[2], e[3]);
          if (++spin > SPIN_LIMIT) break;
        } while ((e[0] ^ tag) & 1u);
        sts128(base + SM_CS + i * 16, e[0] & ~1u, e[1], e[2], e[3]);
      }
      bar_arrive(BAR_CS, 256);
    }

    const int grp = b & ~3;
#pragma unroll 1
    for (int pass = 0; pass < 2; pass++) {
      uint32_t Q[16];
      if (wg == 0) {
        float acc[4][32];
        uint32_t H[4][16];
        uint32_t s0, s1;
        s0 = ring.acquire();
        mma_tile<true>(acc[0], A[0], s0); mma_tile<true>(acc[1], A[0], s0 + TILE_BYTES);
        s0 = ring.acquire();
        mma_tile<true>(acc[2], A[0], s0); mma_tile<true>(acc[3], A[0], s0 + TILE_BYTES);
        RowNorm nrm = {0.5f, 0.f, 0.5f, 0.f};
        if (pass) {
#pragma unroll
          for (int c = 1; c < 4; c++) fetch(&g_ag[4][grp + ((r + c) & 3)][0][here(th)], A[c]);
#pragma unroll
          for (int c = 1; c < 4; c++) confirm(&g_ag[4][grp + ((r + c) & 3)][0][here(th)], A[c], tag);
        }
        PROF_MARK(2 + pass * 16);
        s0 = ring.acquire();
        mma_tile<false>(acc[0], A[1], s0); mma_tile<false>(acc[0], A[2], s0 + TILE_BYTES);
        WG_WAIT(2);
        ring.release(); ring.release();
        if (pass) {
          nrm = stat_gather(own, &g_st[2][grp][here(th) >> 2], r, tag);
          nrm.rs0 *= 0.5f; nrm.nm0 *= 0.5f; nrm.rs1 *= 0.5f; nrm.nm1 *= 0.5f;
        }
        const uint32_t cs = csq + CS_FF2 * 4;
        s0 = ring.acquire();
        mma_tile<false>(acc[0], A[3], s0); mma_tile<false>(acc[1], A[1], s0 + TILE_BYTES);
        s0 = ring.acquire();
        mma_tile<false>(acc[1], A[2], s0);
        WG_WAIT(2); pin(acc[0]);
        ring.release();
        silu_part<0, 4>(acc[0], H[0], nrm, cs);
        mma_tile<false>(acc[1], A[3], s0 + TILE_BYTES);
        silu_part<4, 8>(acc[0], H[0], nrm, cs);
        s0 = ring.acquire();
        mma_tile<false>(acc[2], A[1], s0); mma_tile<false>(acc[2], A[2], s0 + TILE_BYTES);
        WG_WAIT(2); pin(acc[1]);
        ring.release(); ring.release();
        silu_part<0, 4>(acc[1], H[1], nrm, cs + 256);
        s0 = ring.acquire();
        mma_tile<false>(acc[2], A[3], s0);
        silu_part<4, 8>(acc[1], H[1], nrm, cs + 256);
        mma_tile<false>(acc[3], A[1], s0 + TILE_BYTES);
        s0 = ring.acquire();
        mma_tile<false>(acc[3], A[2], s0);
        WG_WAIT(2); pin(acc[2]);
        ring.release();
        silu_part<0, 4>(acc[2], H[2], nrm, cs + 512);
        mma_tile<false>(acc[3], A[3], s0 + TILE_BYTES);
        silu_part<4, 8>(acc[2], H[2], nrm, cs + 512);
        pin(H[0]); pin(H[1]); pin(H[2]);
        s0 = ring.acquire();
        mma_tile<true>(acc[0], H[0], s0); mma_tile<false>(acc[0], H[1], s0 + TILE_BYTES);
        WG_WAIT(2); pin(acc[3]);
        ring.release(); ring.release();
        silu_part<0, 4>(acc[3], H[3], nrm, cs + 768);
        s0 = ring.acquire();
        mma_tile<false>(acc[0], H[2], s0);
        silu_part<4, 8>(acc[3], H[3], nrm, cs + 768);
        pin(H[3]);
        mma_tile<false>(acc[0], H[3], s0 + TILE_BYTES);
        PROF_MARK(3 + pass * 16);
        res_load(res, acc[3], 2.f);
        pin(acc[3]);
        uint4* rs_out = &g_rs[pass][grp][0][0][here(th)];
#pragma unroll
        for (int c = 1; c < 4; c++) {
          s0 = ring.acquire();
          if (c == 3) mma_tile<false>(acc[c], H[0], s0); else mma_tile<true>(acc[c], H[0], s0);
          mma_tile<false>(acc[c], H[1], s0 + TILE_BYTES);
          WG_WAIT(2); pin(acc[c - 1]);
          ring.release(); ring.release();
          uint32_t o[16];
          pack_acc(acc[c - 1], o);
          publish(rs_out + (((r + c) & 3) * 3 + (c - 1)) * 512, o, tag);
          s1 = ring.acquire();
          mma_tile<false>(acc[c], H[2], s1); mma_tile<false>(acc[c], H[3], s1 + TILE_BYTES);
        }
        {
          uint32_t P[3][16];
          const uint4* rs_in = &g_rs[pass][b][0][0][here(th)];
#pragma unroll
          for (int c = 0; c < 3; c++) fetch(rs_in + c * 512, P[c]);
          WG_WAIT(0); pin(acc[3]);
          ring.release(); ring.release();
          PROF_MARK(4 + pass * 16);
#pragma unroll
          for (int c = 0; c < 3; c++) {
            confirm(rs_in + c * 512, P[c], tag);
#pragma unroll
            for (int i = 0; i < 16; i++) { acc[3][2 * i] += bf_lo(P[c][i]); acc[3][2 * i + 1] += bf_hi(P[c][i]); }
          }
#pragma unroll
          for (int i = 0; i < 32; i++) acc[3][i] *= 0.5f;
        }
        PROF_MARK(5 + pass * 16);
        if (pass) {
          pack_acc(acc[3], A[0]);
          unpack_acc(A[0], acc[3], 1.f);
          own = stat_publish(acc[3], &g_st[3][b][here(th) >> 2], tag);
          const RowNorm fn = stat_gather(own, &g_st[3][grp][here(th) >> 2], r, tag);
#pragma unroll
          for (int i = 0; i < 16; i++) {
            const float rs = (i & 1) ? fn.rs1 : fn.rs0, nm = (i & 1) ? fn.nm1 : fn.nm0;
            A[0][i] = pack2(fmaf(acc[3][2 * i], rs, nm), fmaf(acc[3][2 * i + 1], rs, nm));
          }
#pragma unroll
          for (int s = 0; s < 4; s++) stsm4(here(maddr) ^ (s << 5), &A[0][4 * s]);
          __syncwarp();
#pragma unroll
          for (int i = 0; i < 4; i++) {
            const int row = 16 * w + 4 * i + (lane >> 3);
            uint4 v;
            lds128(stg + row * 128 + (((lane & 7) ^ (row & 7)) << 4), v.x, v.y, v.z, v.w);
            if (row < nvalid) *((uint4*)(p.out + (row0 + row) * DM + 64 * r) + (lane & 7)) = v;
          }
          if (tid == 0) g_epoch[b] = epoch;
          PROF_MARK(22);
          break;
        }
        pack_acc(acc[3], A[0]);
        publish(&g_ag[0][b][0][here(th)], A[0], tag);
        res_store(res, A[0]);
        s0 = ring.acquire();
        mma_tile<true>(acc[0], A[0], s0); mma_tile<true>(acc[1], A[0], s0 + TILE_BYTES);
        s0 = ring.acquire();
        mma_tile<true>(acc[2], A[0], s0);
        own = stat_publish(acc[3], &g_st[0][b][here(th) >> 2], tag);
#pragma unroll
        for (int c = 1; c < 4; c++) fetch(&g_ag[0][grp + ((r + c) & 3)][0][here(th)], A[c]);
#pragma unroll
        for (int c = 1; c < 4; c++) confirm(&g_ag[0][grp + ((r + c) & 3)][0][here(th)], A[c], tag);
        PROF_MARK(6);
        mma_tile<false>(acc[0], A[1], s0 + TILE_BYTES);
        s0 = ring.acquire();
        mma_tile<false>(acc[0], A[2], s0); mma_tile<false>(acc[0], A[3], s0 + TILE_BYTES);
        nrm = stat_gather(own, &g_st[0][grp][here(th) >> 2], r, tag);
        bar_sync(BAR_CS, 256);
        s0 = ring.acquire();
        mma_tile<false>(acc[1], A[1], s0); mma_tile<false>(acc[1], A[2], s0 + TILE_BYTES);
        WG_WAIT(2); pin(acc[0]);
        ring.release(); ring.release(); ring.release();
        fold_ln<0, 8>(acc[0], nrm, csq + CS_QKV * 4);
        pack_acc(acc[0], Q);
#pragma unroll
        for (int s = 0; s < 4; s++) stsm4(here(maddr) ^ (s << 5), &Q[4 * s]);
        fence_async_smem();
        bar_arrive(BAR_K, 160);
        s0 = ring.acquire();
        mma_tile<false>(acc[1], A[3], s0); mma_tile<false>(acc[2], A[1], s0 + TILE_BYTES);
        s0 = ring.acquire();
        mma_tile<false>(acc[2], A[2], s0);
        WG_WAIT(2); pin(acc[1]);
        ring.release();
        mma_tile<false>(acc[2], A[3], s0 + TILE_BYTES);
        fold_ln<0, 8>(acc[1], nrm, csq + CS_QKV * 4 + 256);
        pack_acc(acc[1], Q);
#pragma unroll
        for (int s = 0; s < 4; s++) stsm4((here(maddr) ^ (s << 5)) + TILE_BYTES, &Q[4 * s]);
        fence_async_smem();
        bar_arrive(BAR_V, 160);
        WG_WAIT(0); pin(acc[2]);
        ring.release(); ring.release();
        fold_ln<0, 8>(acc[2], nrm, csq + CS_QKV * 4 + 512);
        pack_acc(acc[2], Q);
#pragma unroll
        for (int s = 0; s < 4; s++) sts128(stg + 2 * TILE_BYTES + s * 2048 + here(th) * 16, Q[4 * s], Q[4 * s + 1], Q[4 * s + 2], Q[4 * s + 3]);
        bar_arrive(BAR_Q, 256);
      } else {
        bar_sync(BAR_Q, 256);
#pragma unroll
        for (int s = 0; s < 4; s++) lds128(stg + 2 * TILE_BYTES + s * 2048 + here(th) * 16, Q[4 * s], Q[4 * s + 1], Q[4 * s + 2], Q[4 * s + 3]);
      }
      PROF_MARK(7);

      float O[32];
      float m0 = -INFINITY, m1 = -INFINITY, l0 = 0.f, l1 = 0.f;
      {
#pragma unroll
        for (int i = 0; i < 32; i++) O[i] = 0.f;
        pin(Q);
        float S[2][32];
        attn_scores(S, Q, base, 22 + wg);
        PROF_MARK(8);
        WG_WAIT(0);
#pragma unroll 1
        for (int it = 0;; it++) {
          const uint32_t fk = 22 + 4 * it + wg, fv = fk + 2, sv = fv % NSTAGE;
          pin(S[0]); pin(S[1]); pin(O);
          if (lane == 0) {
            mbar_arrive(base + SM_BAR + 96 + (fk % NSTAGE) * 8);
            if (it) mbar_arrive(base + SM_BAR + 96 + ((fv - 4) % NSTAGE) * 8);
          }
          if (it == 3 && wg == 1) {
#pragma unroll
            for (int i = 20; i < 32; i++) S[1][i] = -INFINITY;
          }
          float n0 = m0, n1 = m1;
#pragma unroll
          for (int h = 0; h < 2; h++)
#pragma unroll
            for (int j = 0; j < 8; j++) {
              n0 = fmaxf(n0, fmaxf(S[h][4 * j], S[h][4 * j + 1]));
              n1 = fmaxf(n1, fmaxf(S[h][4 * j + 2], S[h][4 * j + 3]));
            }
          n0 = fmaxf(n0, __shfl_xor_sync(0xffffffffu, n0, 1)); n1 = fmaxf(n1, __shfl_xor_sync(0xffffffffu, n1, 1));
          n0 = fmaxf(n0, __shfl_xor_sync(0xffffffffu, n0, 2)); n1 = fmaxf(n1, __shfl_xor_sync(0xffffffffu, n1, 2));
          const float a0 = ex2_hw((m0 - n0) * SM_SCALE_LOG2), a1 = ex2_hw((m1 - n1) * SM_SCALE_LOG2);
          m0 = n0; m1 = n1;
          const float c0 = -n0 * SM_SCALE_LOG2, c1 = -n1 * SM_SCALE_LOG2;
          l0 *= a0; l1 *= a1;
          uint32_t P[2][16];
#pragma unroll
          for (int h = 0; h < 2; h++)
#pragma unroll
            for (int j = 0; j < 8; j++) {
              const float p0 = ex2_hw(fmaf(S[h][4 * j], SM_SCALE_LOG2, c0)), p1 = ex2_hw(fmaf(S[h][4 * j + 1], SM_SCALE_LOG2, c0));
              const float p2 = ex2_hw(fmaf(S[h][4 * j + 2], SM_SCALE_LOG2, c1)), p3 = ex2_hw(fmaf(S[h][4 * j + 3], SM_SCALE_LOG2, c1));
              l0 += p0 + p1; l1 += p2 + p3;
              P[h][2 * j] = pack2(p0, p1); P[h][2 * j + 1] = pack2(p2, p3);
            }
#pragma unroll
          for (int j = 0; j < 8; j++) { O[4 * j] *= a0; O[4 * j + 1] *= a0; O[4 * j + 2] *= a1; O[4 * j + 3] *= a1; }
          pin(P[0]); pin(P[1]); pin(O);
          mbar_wait(base + SM_BAR + sv * 8, (fv / NSTAGE) & 1);
          mma_tile<false>(O, P[0], base + sv * STAGE_BYTES);
          mma_tile<false>(O, P[1], base + sv * STAGE_BYTES + TILE_BYTES);
          if (it == 3) break;
          attn_scores(S, Q, base, fk + 4);
          WG_WAIT(0);
        }
        l0 += __shfl_xor_sync(0xffffffffu, l0, 1); l1 += __shfl_xor_sync(0xffffffffu, l1, 1);
        l0 += __shfl_xor_sync(0xffffffffu, l0, 2); l1 += __shfl_xor_sync(0xffffffffu, l1, 2);
        WG_WAIT(0); pin(O);
        if (lane == 0) mbar_arrive(base + SM_BAR + 96 + ((36 + wg) % NSTAGE) * 8);
      }
      PROF_MARK(9);

      uint32_t tap[15];
      {
        const uint32_t* dwp = (const uint32_t*)(p.dw + 64 * r) + lane;
#pragma unroll
        for (int k = 0; k < 15; k++) tap[k] = __ldg(dwp + (cw == 0 ? 14 - k : k) * (DM / 2));
      }

      if (wg == 1) {
#pragma unroll
        for (int i = 0; i < 8; i++)
          sts128(stg + i * 2048 + here(th) * 16, __float_as_uint(O[4 * i]), __float_as_uint(O[4 * i + 1]), __float_as_uint(O[4 * i + 2]), __float_as_uint(O[4 * i + 3]));
        sts128(stg + 8 * 2048 + here(th) * 16, __float_as_uint(m0), __float_as_uint(m1), __float_as_uint(l0), __float_as_uint(l1));
        bar_arrive(BAR_MERGE, 256);
      } else {
        float acc[2][32];
        uint32_t s0;
        ring.seek(38);
        bar_sync(BAR_MERGE, 256);
        {
          uint32_t e[4];
          lds128(stg + 8 * 2048 + here(th) * 16, e[0], e[1], e[2], e[3]);
          const float n0 = fmaxf(m0, __uint_as_float(e[0])), n1 = fmaxf(m1, __uint_as_float(e[1]));
          float a0 = ex2_hw((m0 - n0) * SM_SCALE_LOG2), a1 = ex2_hw((m1 - n1) * SM_SCALE_LOG2);
          float b0 = ex2_hw((__uint_as_float(e[0]) - n0) * SM_SCALE_LOG2), b1 = ex2_hw((__uint_as_float(e[1]) - n1) * SM_SCALE_LOG2);
          const float i0 = __fdividef(1.f, fmaf(a0, l0, b0 * __uint_as_float(e[2]))), i1 = __fdividef(1.f, fmaf(a1, l1, b1 * __uint_as_float(e[3])));
          a0 *= i0; b0 *= i0; a1 *= i1; b1 *= i1;
#pragma unroll
          for (int i = 0; i < 8; i++) {
            lds128(stg + i * 2048 + here(th) * 16, e[0], e[1], e[2], e[3]);
            A[0][2 * i] = pack2(fmaf(O[4 * i], a0, b0 * __uint_as_float(e[0])), fmaf(O[4 * i + 1], a0, b0 * __uint_as_float(e[1])));
            A[0][2 * i + 1] = pack2(fmaf(O[4 * i + 2], a1, b1 * __uint_as_float(e[2])), fmaf(O[4 * i + 3], a1, b1 * __uint_as_float(e[3])));
          }
        }
        publish(&g_ag[1][b][0][here(th)], A[0], tag);
        PROF_MARK(10);
        res_load(res, acc[0], 1.f);
        pin(acc[0]); pin(A[0]);
        s0 = ring.acquire();
        mma_tile<false>(acc[0], A[0], s0);
#pragma unroll
        for (int c = 1; c < 4; c++) fetch(&g_ag[1][grp + ((r + c) & 3)][0][here(th)], A[c]);
#pragma unroll
        for (int c = 1; c < 4; c++) confirm(&g_ag[1][grp + ((r + c) & 3)][0][here(th)], A[c], tag);
        PROF_MARK(11);
        mma_tile<false>(acc[0], A[1], s0 + TILE_BYTES);
        s0 = ring.acquire();
        mma_tile<false>(acc[0], A[2], s0); mma_tile<false>(acc[0], A[3], s0 + TILE_BYTES);
        WG_WAIT(0); pin(acc[0]);
        ring.release(); ring.release();
        pack_acc(acc[0], A[0]);
        publish(&g_ag[2][b][0][here(th)], A[0], tag);
        res_store(res, A[0]);
        PROF_MARK(12);
        own = stat_publish(acc[0], &g_st[1][b][here(th) >> 2], tag);
        s0 = ring.acquire();
        mma_tile<true>(acc[0], A[0], s0); mma_tile<true>(acc[1], A[0], s0 + TILE_BYTES);
#pragma unroll
        for (int c = 1; c < 4; c++) fetch(&g_ag[2][grp + ((r + c) & 3)][0][here(th)], A[c]);
#pragma unroll
        for (int c = 1; c < 4; c++) confirm(&g_ag[2][grp + ((r + c) & 3)][0][here(th)], A[c], tag);
        PROF_MARK(13);
#pragma unroll
        for (int c = 1; c < 4; c++) {
          s0 = ring.acquire();
          mma_tile<false>(acc[0], A[c], s0); mma_tile<false>(acc[1], A[c], s0 + TILE_BYTES);
        }
        RowNorm nrm = stat_gather(own, &g_st[1][grp][here(th) >> 2], r, tag);
        nrm.rs0 *= 0.5f; nrm.nm0 *= 0.5f; nrm.rs1 *= 0.5f; nrm.nm1 *= 0.5f;
        if (16 * w + g >= nvalid) { nrm.rs0 = 0.f; nrm.nm0 = 0.f; }
        if (16 * w + g + 8 >= nvalid) { nrm.rs1 = 0.f; nrm.nm1 = 0.f; }
        WG_WAIT(0); pin(acc[0]); pin(acc[1]);
        ring.release(); ring.release(); ring.release(); ring.release();
        fold_ln<0, 8>(acc[0], nrm, csq + CS_PW1 * 4);
        fold_ln<0, 8>(acc[1], nrm, csq + CS_PW1 * 4 + 256);
#pragma unroll
        for (int i = 0; i < 16; i++)
          A[0][i] = pack2(fmaf(acc[0][2 * i], tanh_hw(acc[1][2 * i]), acc[0][2 * i]), fmaf(acc[0][2 * i + 1], tanh_hw(acc[1][2 * i + 1]), acc[0][2 * i + 1]));
#pragma unroll
        for (int s = 0; s < 4; s++) stsm4((here(maddr) ^ (s << 5)) + TILE_BYTES, &A[0][4 * s]);
      }
      bar_sync(BAR_G, 256);
      PROF_MARK(14);

      {
        const int first = cw == 0 ? 14 : 8 * cw - 7, dir = cw == 0 ? -1 : 1;
        const uint32_t gcol = stg + TILE_BYTES + (lane & 3) * 4;
        uint32_t in[22];
#pragma unroll
        for (int i = 0; i < 15; i++) {
          const int row = first + dir * i;
          in[i] = lds32(gcol + row * 128 + (((lane >> 2) ^ (row & 7)) << 4));
        }
        const bool edge = cw == 0 || cw == 7;
        const bool nbr = cw == 0 ? t > 0 : t < 15;
        if (edge) {
          if (nbr) {
            uint4* dst = &g_halo[cw == 0 ? b - 4 : b + 4][cw == 0 ? 1 : 0][0][lane];
            st_vec(dst, epoch, in[14], in[13], in[12]);
            st_vec(dst + 32, epoch, in[11], in[10], in[9]);
            st_vec(dst + 64, epoch, in[8], 0u, 0u);
          }
        } else {
#pragma unroll
          for (int i = 15; i < 22; i++) {
            const int row = first + i;
            in[i] = lds32(gcol + row * 128 + (((lane >> 2) ^ (row & 7)) << 4));
          }
        }
        float cl[8], ch[8], tl[15], tv[15];
#pragma unroll
        for (int k = 0; k < 15; k++) { tl[k] = bf_lo(tap[k]); tv[k] = bf_hi(tap[k]); }
#pragma unroll
        for (int o = 0; o < 8; o++) { cl[o] = 0.f; ch[o] = 0.f; }
#pragma unroll
        for (int i = 0; i < 15; i++) {
          const float lo = bf_lo(in[i]), hi = bf_hi(in[i]);
#pragma unroll
          for (int o = 0; o < 8; o++)
            if (i - o >= 0) { cl[o] = fmaf(lo, tl[i - o], cl[o]); ch[o] = fmaf(hi, tv[i - o], ch[o]); }
        }
        if (edge) {
#pragma unroll
          for (int i = 15; i < 22; i++) in[i] = 0u;
          if (nbr) {
            const uint4* src = &g_halo[b][cw == 0 ? 0 : 1][0][lane];
            uint32_t e0, e1, e2, u0, u1, spin = 0;
            while (true) {
              ld_vec(src, e0, in[15], in[16], in[17]);
              ld_vec(src + 32, e1, in[18], in[19], in[20]);
              ld_vec(src + 64, e2, in[21], u0, u1);
              if (__all_sync(0xffffffffu, e0 == epoch && e1 == epoch && e2 == epoch)) break;
              if (++spin > SPIN_LIMIT) break;
            }
          }
        }
#pragma unroll
        for (int i = 15; i < 22; i++) {
          const float lo = bf_lo(in[i]), hi = bf_hi(in[i]);
#pragma unroll
          for (int o = 0; o < 8; o++)
            if (i - o <= 14) { cl[o] = fmaf(lo, tl[i - o], cl[o]); ch[o] = fmaf(hi, tv[i - o], ch[o]); }
        }
        const uint32_t ccol = stg + (lane & 3) * 4;
#pragma unroll
        for (int o = 0; o < 8; o++) {
          const float a = 0.5f * cl[o], c = 0.5f * ch[o];
          const int row = first + dir * (7 + o);
          sts32(ccol + row * 128 + (((lane >> 2) ^ (row & 7)) << 4), pack2(fmaf(a, tanh_hw(a), a), fmaf(c, tanh_hw(c), c)));
        }
      }
      if (wg == 1) {
        bar_arrive(BAR_C, 256);
        break;
      } else {
        float acc[32];
        uint32_t s0;
        res_load(res, acc, 1.f);
        bar_sync(BAR_C, 256);
#pragma unroll
        for (int s = 0; s < 4; s++) ldsm4(here(maddr) ^ (s << 5), &A[0][4 * s]);
        publish(&g_ag[3][b][0][here(th)], A[0], tag);
        PROF_MARK(15);
        pin(acc); pin(A[0]);
        s0 = ring.acquire();
        mma_tile<false>(acc, A[0], s0);
#pragma unroll
        for (int c = 1; c < 4; c++) fetch(&g_ag[3][grp + ((r + c) & 3)][0][here(th)], A[c]);
#pragma unroll
        for (int c = 1; c < 4; c++) confirm(&g_ag[3][grp + ((r + c) & 3)][0][here(th)], A[c], tag);
        PROF_MARK(16);
        mma_tile<false>(acc, A[1], s0 + TILE_BYTES);
        s0 = ring.acquire();
        mma_tile<false>(acc, A[2], s0); mma_tile<false>(acc, A[3], s0 + TILE_BYTES);
        WG_WAIT(0); pin(acc);
        ring.release(); ring.release();
        pack_acc(acc, A[0]);
        publish(&g_ag[4][b][0][here(th)], A[0], tag);
        res_store(res, A[0]);
        PROF_MARK(17);
        own = stat_publish(acc, &g_st[2][b][here(th) >> 2], tag);
      }
    }
  }
}

typedef CUresult (*EncodeFn)(CUtensorMap*, CUtensorMapDataType, cuuint32_t, void*, const cuuint64_t*, const cuuint64_t*,
                             const cuuint32_t*, const cuuint32_t*, CUtensorMapInterleave, CUtensorMapSwizzle,
                             CUtensorMapL2promotion, CUtensorMapFloatOOBfill);

void make_map(EncodeFn fn, CUtensorMap* m, const void* w, int rows, int cols) {
  const cuuint64_t dims[2] = {(cuuint64_t)cols, (cuuint64_t)rows};
  const cuuint64_t strides[1] = {(cuuint64_t)cols * 2};
  const cuuint32_t box[2] = {64, 64}, es[2] = {1, 1};
  fn(m, CU_TENSOR_MAP_DATA_TYPE_BFLOAT16, 2, const_cast<void*>(w), dims, strides, box, es, CU_TENSOR_MAP_INTERLEAVE_NONE,
     CU_TENSOR_MAP_SWIZZLE_128B, CU_TENSOR_MAP_L2_PROMOTION_L2_128B, CU_TENSOR_MAP_FLOAT_OOB_FILL_NONE);
}

}

extern "C" void kernel_launch(void* const* d_in, const int* in_sizes, int n_in, void* d_out, int out_size) {
  static EncodeFn fn = nullptr;
  if (!fn) {
    void* f = nullptr;
    cudaDriverEntryPointQueryResult st;
    cudaGetDriverEntryPoint("cuTensorMapEncodeTiled", &f, cudaEnableDefault, &st);
    fn = (EncodeFn)f;
    cudaFuncSetAttribute(conformer_kernel, cudaFuncAttributeMaxDynamicSharedMemorySize, SM_TOTAL);
  }
  typedef const __nv_bfloat16* W;
  Params p;
  make_map(fn, &p.m_ff1a, d_in[1], 256, 1024);
  make_map(fn, &p.m_ff1b, d_in[2], 1024, 256);
  make_map(fn, &p.m_qkv, d_in[3], 256, 768);
  make_map(fn, &p.m_o, d_in[4], 256, 256);
  make_map(fn, &p.m_pw1, d_in[5], 256, 512);
  make_map(fn, &p.m_pw2, d_in[7], 256, 256);
  make_map(fn, &p.m_ff2a, d_in[8], 256, 1024);
  make_map(fn, &p.m_ff2b, d_in[9], 1024, 256);
  p.x = (W)d_in[0]; p.w_ff1b = (W)d_in[2]; p.w_qkv = (W)d_in[3]; p.w_o = (W)d_in[4]; p.w_pw1 = (W)d_in[5];
  p.dw = (W)d_in[6]; p.w_pw2 = (W)d_in[7]; p.w_ff2a = (W)d_in[8]; p.w_ff2b = (W)d_in[9];
  p.out = (__nv_bfloat16*)d_out;

  cudaLaunchConfig_t cfg = {};
  cfg.gridDim = dim3(NCTA);
  cfg.blockDim = dim3(384);
  cfg.dynamicSmemBytes = SM_TOTAL;
  cfg.stream = cudaStreamPerThread;
  cudaLaunchAttribute at[1];
  at[0].id = cudaLaunchAttributeCooperative;
  at[0].val.cooperative = 1;
  cfg.attrs = at;
  cfg.numAttrs = 1;
  cudaLaunchKernelEx(&cfg, conformer_kernel, p);
}
```

```cpp
#include <cuda_runtime.h>
#include <cuda_bf16.h>
#include <cuda.h>
#include <stdint.h>

namespace {

constexpr int T_SEQ = 1000;
constexpr int DM = 256;
constexpr int NCTA = 128;
constexpr int NSTAGE = 12;
constexpr uint32_t STAGE_BYTES = 16384;
constexpr uint32_t TILE_BYTES = 8192;
constexpr uint32_t SM_BASE = 1024;
constexpr uint32_t SM_STG = NSTAGE * STAGE_BYTES;
constexpr uint32_t SM_FULL = SM_STG + 32768;
constexpr uint32_t SM_EMPTY = SM_FULL + 96;
constexpr uint32_t SM_XBAR = SM_FULL + 192;
constexpr uint32_t SM_EYE = SM_FULL + 256;
constexpr uint32_t SM_CS = SM_FULL + 768;
constexpr uint32_t SM_TOTAL = SM_FULL + 3072;
constexpr int CS_QKV = 0, CS_PW1 = 192, CS_FF2 = 320;
constexpr uint32_t SPIN_LIMIT = 1u << 16;
constexpr float LN_EPS = 1e-5f;
constexpr float SM_SCALE_LOG2 = 0.125f * 1.4426950408889634f;
constexpr uint32_t G_PITCH = 144;

constexpr int F_QKV = 16, F_SPARE = 22, F_KV = 24, F_WO = 40, F_PW1 = 42, F_PW2 = 46, F_TOTAL = 64;
enum { M_FF1A, M_FF1B, M_WKV, M_WQ, M_KV, M_WO, M_PW1, M_PW2, M_FF2A, M_FF2B, M_X, M_COUNT };
enum { BAR_K = 1, BAR_V, BAR_Q, BAR_MERGE, BAR_G, BAR_C, BAR_CS, BAR_WG1 };

struct Params {
  CUtensorMap map[M_COUNT];
  const __nv_bfloat16 *w_ff1b, *w_qkv, *w_o, *w_pw1, *dw, *w_pw2, *w_ff2a, *w_ff2b;
  __nv_bfloat16* out;
};

constexpr int X_AG0 = 0, X_AG1 = 512, X_RS = 1024, X_ST = 2560, X_HALO = 2592, X_SIZE = 4096;
__device__ __align__(1024) uint4 g_x[NCTA][X_SIZE];
__device__ __align__(1024) uint4 g_kv[8][2][16][512];
__device__ __align__(1024) uint32_t g_flag[8][32];
__device__ __align__(1024) uint4 g_cs[576];
__device__ uint32_t g_epoch[NCTA];
#define PROF_TIME(i)
#define PROF_MARK(i)

__device__ __forceinline__ void mbar_init(uint32_t bar, uint32_t cnt) {
  asm volatile("mbarrier.init.shared::cta.b64 [%0], %1;" :: "r"(bar), "r"(cnt) : "memory");
}
__device__ __forceinline__ void mbar_wait(uint32_t bar, uint32_t parity) {
  asm volatile("{\n.reg .pred p;\n.reg .u32 c;\nmov.u32 c, 0;\n"
               "WAIT_LOOP:\nmbarrier.try_wait.parity.shared::cta.b64 p, [%0], %1;\n@p bra WAIT_DONE;\n"
               "add.u32 c, c, 1;\nsetp.lt.u32 p, c, %2;\n@p bra WAIT_LOOP;\nWAIT_DONE:\n}"
               :: "r"(bar), "r"(parity), "n"(SPIN_LIMIT) : "memory");
}
__device__ __forceinline__ void mbar_arrive(uint32_t bar) {
  asm volatile("mbarrier.arrive.shared::cta.b64 _, [%0];" :: "r"(bar) : "memory");
}
#define bar_sync(id, n) asm volatile("bar.sync %0, %1;" :: "n"((int)(id)), "n"(n) : "memory")
#define bar_arrive(id, n) asm volatile("bar.arrive %0, %1;" :: "n"((int)(id)), "n"(n) : "memory")
__device__ __forceinline__ void fence_async_smem() { asm volatile("fence.proxy.async.shared::cta;" ::: "memory"); }

__device__ __forceinline__ void st_vec(uint4* p, uint32_t a, uint32_t b, uint32_t c, uint32_t d) {
  asm volatile("{\n.reg .b128 v;\n.reg .b64 lo, hi;\nmov.b64 lo, {%1, %2};\nmov.b64 hi, {%3, %4};\nmov.b128 v, {lo, hi};\n"
               "st.relaxed.gpu.global.b128 [%0], v;\n}" :: "l"(p), "r"(a), "r"(b), "r"(c), "r"(d) : "memory");
}
__device__ __forceinline__ void ld_vec(const uint4* p, uint32_t& a, uint32_t& b, uint32_t& c, uint32_t& d) {
  asm volatile("{\n.reg .b128 v;\n.reg .b64 lo, hi;\nld.relaxed.gpu.global.b128 v, [%4];\nmov.b128 {lo, hi}, v;\n"
               "mov.b64 {%0, %1}, lo;\nmov.b64 {%2, %3}, hi;\n}" : "=r"(a), "=r"(b), "=r"(c), "=r"(d) : "l"(p) : "memory");
}
__device__ __forceinline__ void sts128(uint32_t a, uint32_t x, uint32_t y, uint32_t z, uint32_t w) {
  asm volatile("st.shared.v4.u32 [%0], {%1, %2, %3, %4};" :: "r"(a), "r"(x), "r"(y), "r"(z), "r"(w) : "memory");
}
__device__ __forceinline__ void lds128(uint32_t a, uint32_t& x, uint32_t& y, uint32_t& z, uint32_t& w) {
  asm volatile("ld.shared.v4.u32 {%0, %1, %2, %3}, [%4];" : "=r"(x), "=r"(y), "=r"(z), "=r"(w) : "r"(a) : "memory");
}
__device__ __forceinline__ uint32_t lds32(uint32_t a) {
  uint32_t x; asm volatile("ld.shared.u32 %0, [%1];" : "=r"(x) : "r"(a) : "memory"); return x;
}
__device__ __forceinline__ void sts32(uint32_t a, uint32_t x) { asm volatile("st.shared.u32 [%0], %1;" :: "r"(a), "r"(x) : "memory"); }
__device__ __forceinline__ float2 lds64f(uint32_t a) {
  float2 v; asm volatile("ld.shared.v2.f32 {%0, %1}, [%2];" : "=f"(v.x), "=f"(v.y) : "r"(a) : "memory"); return v;
}
__device__ __forceinline__ void stsm4(uint32_t a, const uint32_t* r) {
  asm volatile("stmatrix.sync.aligned.m8n8.x4.shared.b16 [%0], {%1, %2, %3, %4};" :: "r"(a), "r"(r[0]), "r"(r[1]), "r"(r[2]), "r"(r[3]) : "memory");
}
__device__ __forceinline__ void ldsm4(uint32_t a, uint32_t* r) {
  asm volatile("ldmatrix.sync.aligned.m8n8.x4.shared.b16 {%0, %1, %2, %3}, [%4];" : "=r"(r[0]), "=r"(r[1]), "=r"(r[2]), "=r"(r[3]) : "r"(a) : "memory");
}
__device__ __forceinline__ uint32_t pack2(float lo, float hi) {
  uint32_t r; asm("cvt.rn.bf16x2.f32 %0, %1, %2;" : "=r"(r) : "f"(hi), "f"(lo)); return r;
}
__device__ __forceinline__ float bf_lo(uint32_t w) { return __uint_as_float(w << 16); }
__device__ __forceinline__ float bf_hi(uint32_t w) { return __uint_as_float(w & 0xffff0000u); }
__device__ __forceinline__ float tanh_hw(float x) { float y; asm volatile("tanh.approx.f32 %0, %1;" : "=f"(y) : "f"(x)); return y; }
__device__ __forceinline__ float rcp_hw(float x) { float y; asm("rcp.approx.ftz.f32 %0, %1;" : "=f"(y) : "f"(x)); return y; }
__device__ __forceinline__ float ex2_hw(float x) { float y; asm("ex2.approx.ftz.f32 %0, %1;" : "=f"(y) : "f"(x)); return y; }

__device__ __forceinline__ uint32_t here(uint32_t v) { asm volatile("" : "+r"(v)); return v; }

#define WG_FENCE() asm volatile("wgmma.fence.sync.aligned;" ::: "memory")
#define WG_COMMIT() asm volatile("wgmma.commit_group.sync.aligned;" ::: "memory")
#define WG_WAIT(n) asm volatile("wgmma.wait_group.sync.aligned %0;" :: "n"(n) : "memory")

template <int N> __device__ __forceinline__ void pin(float (&d)[N]) {
#pragma unroll
  for (int i = 0; i < N; i++) asm volatile("" : "+f"(d[i]) :: "memory");
}
template <int N> __device__ __forceinline__ void pin(uint32_t (&d)[N]) {
#pragma unroll
  for (int i = 0; i < N; i++) asm volatile("" : "+r"(d[i]) :: "memory");
}

__device__ __forceinline__ uint64_t mkdesc(uint32_t addr) {
  return (uint64_t)((addr & 0x3FFFF) >> 4) | (uint64_t(1) << 16) | (uint64_t(64) << 32) | (uint64_t(1) << 62);
}

#define WG_D32 "{%0, %1, %2, %3, %4, %5, %6, %7, %8, %9, %10, %11, %12, %13, %14, %15, %16, %17, %18, %19, %20, %21, %22, %23, %24, %25, %26, %27, %28, %29, %30, %31}"
template <int TB> __device__ __forceinline__ void wgmma64_acc(float (&d)[32], const uint32_t* a, uint64_t db) {
  asm volatile("wgmma.mma_async.sync.aligned.m64n64k16.f32.bf16.bf16 " WG_D32 ", {%32, %33, %34, %35}, %36, 1, 1, 1, %37;"
    : "+f"(d[0]), "+f"(d[1]), "+f"(d[2]), "+f"(d[3]), "+f"(d[4]), "+f"(d[5]), "+f"(d[6]), "+f"(d[7]),
      "+f"(d[8]), "+f"(d[9]), "+f"(d[10]), "+f"(d[11]), "+f"(d[12]), "+f"(d[13]), "+f"(d[14]), "+f"(d[15]),
      "+f"(d[16]), "+f"(d[17]), "+f"(d[18]), "+f"(d[19]), "+f"(d[20]), "+f"(d[21]), "+f"(d[22]), "+f"(d[23]),
      "+f"(d[24]), "+f"(d[25]), "+f"(d[26]), "+f"(d[27]), "+f"(d[28]), "+f"(d[29]), "+f"(d[30]), "+f"(d[31])
    : "r"(a[0]), "r"(a[1]), "r"(a[2]), "r"(a[3]), "l"(db), "n"(TB));
}
template <int TB> __device__ __forceinline__ void wgmma64_set(float (&d)[32], const uint32_t* a, uint64_t db) {
  asm volatile("wgmma.mma_async.sync.aligned.m64n64k16.f32.bf16.bf16 " WG_D32 ", {%32, %33, %34, %35}, %36, 0, 1, 1, %37;"
    : "=f"(d[0]), "=f"(d[1]), "=f"(d[2]), "=f"(d[3]), "=f"(d[4]), "=f"(d[5]), "=f"(d[6]), "=f"(d[7]),
      "=f"(d[8]), "=f"(d[9]), "=f"(d[10]), "=f"(d[11]), "=f"(d[12]), "=f"(d[13]), "=f"(d[14]), "=f"(d[15]),
      "=f"(d[16]), "=f"(d[17]), "=f"(d[18]), "=f"(d[19]), "=f"(d[20]), "=f"(d[21]), "=f"(d[22]), "=f"(d[23]),
      "=f"(d[24]), "=f"(d[25]), "=f"(d[26]), "=f"(d[27]), "=f"(d[28]), "=f"(d[29]), "=f"(d[30]), "=f"(d[31])
    : "r"(a[0]), "r"(a[1]), "r"(a[2]), "r"(a[3]), "l"(db), "n"(TB));
}

__device__ __forceinline__ void wgmma16_acc(float* d, const uint32_t* a, uint64_t db) {
  asm volatile("wgmma.mma_async.sync.aligned.m64n16k16.f32.bf16.bf16 {%0, %1, %2, %3, %4, %5, %6, %7}, {%8, %9, %10, %11}, %12, 1, 1, 1, 0;"
    : "+f"(d[0]), "+f"(d[1]), "+f"(d[2]), "+f"(d[3]), "+f"(d[4]), "+f"(d[5]), "+f"(d[6]), "+f"(d[7])
    : "r"(a[0]), "r"(a[1]), "r"(a[2]), "r"(a[3]), "l"(db));
}
__device__ __forceinline__ void hmma(float (&d)[4], const uint32_t* a, uint32_t b0, uint32_t b1) {
  asm("mma.sync.aligned.m16n8k16.row.col.f32.bf16.bf16.f32 {%0, %1, %2, %3}, {%4, %5, %6, %7}, {%8, %9}, {%0, %1, %2, %3};"
    : "+f"(d[0]), "+f"(d[1]), "+f"(d[2]), "+f"(d[3]) : "r"(a[0]), "r"(a[1]), "r"(a[2]), "r"(a[3]), "r"(b0), "r"(b1));
}

template <bool FIRST> __device__ __forceinline__ void mma_tile(float (&d)[32], const uint32_t (&a)[16], uint32_t tile) {
  const uint64_t db = mkdesc(tile);
  WG_FENCE();
#pragma unroll
  for (int s = 0; s < 4; s++) {
    if (FIRST && s == 0) wgmma64_set<1>(d, &a[0], db); else wgmma64_acc<1>(d, &a[4 * s], db + s * 128);
  }
  WG_COMMIT();
}
__device__ __forceinline__ void mma_add_half(float (&d)[32], const uint32_t (&a)[16]) {
  const uint64_t db = (uint64_t)((SM_BASE + SM_EYE) >> 4) | (uint64_t(8) << 16) | (uint64_t(8) << 32);
  WG_FENCE();
#pragma unroll
  for (int s = 0; s < 4; s++) wgmma16_acc(&d[8 * s], &a[4 * s], db);
  WG_COMMIT();
}
__device__ __forceinline__ void attn_scores(float (&S)[2][32], const uint32_t (&Q)[16], uint32_t st, uint32_t parity) {
  mbar_wait(SM_BASE + SM_FULL + st * 8, parity);
  const uint64_t dk = mkdesc(SM_BASE + st * STAGE_BYTES);
  WG_FENCE();
#pragma unroll
  for (int h = 0; h < 2; h++)
#pragma unroll
    for (int s = 0; s < 4; s++) {
      if (s == 0) wgmma64_set<0>(S[h], &Q[0], dk + h * 512); else wgmma64_acc<0>(S[h], &Q[4 * s], dk + h * 512 + s * 2);
    }
  WG_COMMIT();
}

__device__ constexpr uint32_t stage_addr(int f) { return SM_BASE + (f % NSTAGE) * STAGE_BYTES; }
#define ACQUIRE(f) mbar_wait(SM_BASE + SM_FULL + ((f) % NSTAGE) * 8, ((f) / NSTAGE) & 1)
#define RELEASE(f0, f1) do { if (lane == 0) { _Pragma("unroll") for (int f_ = (f0); f_ <= (f1); f_++) mbar_arrive(SM_BASE + SM_EMPTY + (f_ % NSTAGE) * 8); } } while (0)
#define LO(f) stage_addr(f)
#define HI(f) (stage_addr(f) + TILE_BYTES)

__device__ __forceinline__ void publish(uint4* dst, const uint32_t (&a)[16], uint32_t tag) {
#pragma unroll
  for (int s = 0; s < 4; s++) st_vec(dst + s * 128, (a[4 * s] & ~1u) | tag, a[4 * s + 1], a[4 * s + 2], a[4 * s + 3]);
}
__device__ __forceinline__ void fetch(const uint4* src, uint32_t (&a)[16]) {
#pragma unroll
  for (int s = 0; s < 4; s++) ld_vec(src + s * 128, a[4 * s], a[4 * s + 1], a[4 * s + 2], a[4 * s + 3]);
}
__device__ __forceinline__ uint32_t untag(uint32_t (&a)[16], uint32_t tag) {
  a[0] ^= tag; a[4] ^= tag; a[8] ^= tag; a[12] ^= tag;
  return a[0] | a[4] | a[8] | a[12];
}
__device__ __forceinline__ bool stale(uint32_t v) { return __any_sync(0xffffffffu, here(v) & 1u); }
__device__ __forceinline__ void confirm(const uint4* src, uint32_t (&a)[16], uint32_t tag) {
  uint32_t spin = 0;
  while (__builtin_expect(stale(untag(a, tag)), 0) && ++spin < SPIN_LIMIT) fetch(src, a);
  pin(a);
}
__device__ __forceinline__ void gather(uint32_t (&A)[4][16], uint32_t off, uint32_t tag) {
  const uint4* p1 = &g_x[0][0] + (off ^ (1 * X_SIZE));
  const uint4* p2 = &g_x[0][0] + (off ^ (2 * X_SIZE));
  const uint4* p3 = &g_x[0][0] + (off ^ (3 * X_SIZE));
  uint32_t spin = 0;
  do {
    fetch(p1, A[1]); fetch(p2, A[2]); fetch(p3, A[3]);
  } while (stale(untag(A[1], tag) | untag(A[2], tag) | untag(A[3], tag)) && ++spin < SPIN_LIMIT);
  pin(A[1]); pin(A[2]); pin(A[3]);
}
__device__ __forceinline__ void pack_acc(const float (&d)[32], uint32_t (&a)[16]) {
#pragma unroll
  for (int i = 0; i < 16; i++) a[i] = pack2(d[2 * i], d[2 * i + 1]);
}
__device__ __forceinline__ void res_store(uint32_t slot, const uint32_t (&a)[16]) {
#pragma unroll
  for (int s = 0; s < 4; s++) sts128(slot + s * 512, a[4 * s], a[4 * s + 1], a[4 * s + 2], a[4 * s + 3]);
}
__device__ __forceinline__ void res_load(uint32_t slot, float (&d)[32]) {
  uint32_t a[16];
#pragma unroll
  for (int s = 0; s < 4; s++) lds128(slot + s * 512, a[4 * s], a[4 * s + 1], a[4 * s + 2], a[4 * s + 3]);
#pragma unroll
  for (int i = 0; i < 16; i++) { d[2 * i] = bf_lo(a[i]); d[2 * i + 1] = bf_hi(a[i]); }
  pin(d);
}
__device__ __forceinline__ void tile_store(uint32_t maddr, const uint32_t (&a)[16]) {
#pragma unroll
  for (int s = 0; s < 4; s++) stsm4(maddr ^ (s << 5), &a[4 * s]);
}
__device__ __forceinline__ void tile_load(uint32_t maddr, uint32_t (&a)[16]) {
#pragma unroll
  for (int s = 0; s < 4; s++) ldsm4(maddr ^ (s << 5), &a[4 * s]);
}

struct RowAcc { float s[4], u[4], v[4]; };
__device__ __forceinline__ void row_acc(RowAcc& t, const uint32_t (&a)[16]) {
#pragma unroll
  for (int s = 0; s < 4; s++) {
    hmma(t.s, &a[4 * s], 0x3F803F80u, 0x3F803F80u);
    hmma(t.u, &a[4 * s], a[4 * s], a[4 * s + 2]);
    hmma(t.v, &a[4 * s], a[4 * s + 1], a[4 * s + 3]);
  }
}
__device__ __forceinline__ void stat_publish(const uint32_t (&a)[16], uint32_t b, uint32_t th, uint32_t tag) {
  RowAcc t = {};
  row_acc(t, a);
  const bool odd = th & 4;
  if ((th & 3) == ((th >> 3) & 3))
    st_vec(&g_x[b][X_ST + (th >> 2)], (__float_as_uint(t.s[0]) & ~1u) | tag, __float_as_uint(odd ? t.u[1] : t.u[0]),
           __float_as_uint(t.s[2]), __float_as_uint(odd ? t.v[3] : t.v[2]));
}
struct RowNorm { float rs0, nm0, rs1, nm1; };
__device__ __forceinline__ RowNorm row_norm(float s0, float q0, float s1, float q1, float scale) {
  const float m0 = s0 * (1.f / DM), m1 = s1 * (1.f / DM);
  RowNorm n;
  n.rs0 = scale * rsqrtf(fmaxf(fmaf(-m0, m0, q0 * (1.f / DM)), 0.f) + LN_EPS);
  n.rs1 = scale * rsqrtf(fmaxf(fmaf(-m1, m1, q1 * (1.f / DM)), 0.f) + LN_EPS);
  n.nm0 = -m0 * n.rs0;
  n.nm1 = -m1 * n.rs1;
  return n;
}
__device__ __forceinline__ RowNorm stat_gather(uint32_t b, uint32_t th, uint32_t tag, float scale) {
  const uint4* src = &g_x[b & ~3u][X_ST + (th >> 2)];
  uint32_t v[16], spin = 0;
  do {
#pragma unroll
    for (int j = 0; j < 4; j++) ld_vec(src + j * X_SIZE, v[4 * j], v[4 * j + 1], v[4 * j + 2], v[4 * j + 3]);
  } while (stale(untag(v, tag)) && ++spin < SPIN_LIMIT);
  float f[4];
#pragma unroll
  for (int i = 0; i < 4; i++)
    f[i] = (__uint_as_float(v[i]) + __uint_as_float(v[4 + i])) + (__uint_as_float(v[8 + i]) + __uint_as_float(v[12 + i]));
  return row_norm(f[0], f[1], f[2], f[3], scale);
}
template <int J0, int J1> __device__ __forceinline__ void fold_ln(float (&d)[32], const RowNorm& n, uint32_t cs) {
#pragma unroll
  for (int j = J0; j < J1; j++) {
    const float2 c = lds64f(cs + j * 32);
    d[4 * j] = fmaf(d[4 * j], n.rs0, n.nm0 * c.x);
    d[4 * j + 1] = fmaf(d[4 * j + 1], n.rs0, n.nm0 * c.y);
    d[4 * j + 2] = fmaf(d[4 * j + 2], n.rs1, n.nm1 * c.x);
    d[4 * j + 3] = fmaf(d[4 * j + 3], n.rs1, n.nm1 * c.y);
  }
}
template <int J0, int J1> __device__ __forceinline__ void silu_part(float (&d)[32], uint32_t (&h)[16], const RowNorm& n, uint32_t cs) {
  fold_ln<J0, J1>(d, n, cs);
#pragma unroll
  for (int i = 2 * J0; i < 2 * J1; i++) {
    const float a = d[2 * i], b = d[2 * i + 1];
    h[i] = pack2(fmaf(a, tanh_hw(a), a), fmaf(b, tanh_hw(b), b));
  }
}
template <int F> __device__ __forceinline__ void proj_residual(uint32_t (&A)[4][16], uint32_t xoff, uint32_t res, uint32_t r,
                                                               uint32_t tag_in, uint32_t tag_out, int lane) {
  float acc[32];
  publish(&g_x[0][X_AG1] + xoff, A[0], tag_in);
  res_load(res, acc);
  const uint32_t flip = (r & 1) * TILE_BYTES;
  ACQUIRE(F);
  mma_tile<false>(acc, A[0], LO(F) + flip);
  ACQUIRE(F + 1);
  gather(A, xoff + X_AG1, tag_in);
  PROF_MARK(F == F_WO ? 11 : 16);
  mma_tile<false>(acc, A[1], HI(F) - flip);
  mma_tile<false>(acc, A[2], LO(F + 1) + flip);
  mma_tile<false>(acc, A[3], HI(F + 1) - flip);
  WG_WAIT(0); pin(acc);
  pack_acc(acc, A[0]);
  publish(&g_x[0][X_AG0] + xoff, A[0], tag_out);
  RELEASE(F, F + 1);
  res_store(res, A[0]);
}

__device__ __forceinline__ uint32_t fill_entry(int f, int r, int bh) {
  int m, x = r, y, z = 0;
  if (f < F_QKV || f >= 48) {
    const int i = f & 15;
    m = f < F_QKV ? M_FF1A : M_FF2A;
    if (i < 8) {
      const int h = i < 2 ? i : (i >= 5), c = i < 2 ? 0 : i - 1 - 3 * h;
      x = 0; y = r ^ c; z = 4 * r + 2 * h;
    } else {
      m++; x = r ^ (((i >> 1) - 3) & 3); y = 4 * r + 2 * (i & 1);
    }
  } else if (f < F_KV) {
    const int i = f - F_QKV;
    if (i == 1 || i >= 5) { m = M_WQ; y = (r & 2) ^ (i == 1 ? 0 : 2); }
    else { m = M_WKV; y = r ^ (i ? i - 1 : 0); z = 1; }
  } else if (f < F_WO) {
    const int i = f - F_KV;
    m = M_KV; x = 0; y = bh * 32 + (i & 2) * 8 + (i >> 2) * 4 + (i & 1) * 2;
  } else if (f >= F_PW1 && f < F_PW2) {
    m = M_PW1; y = r ^ (f - F_PW1);
  } else {
    m = f < F_PW1 ? M_WO : M_PW2; y = (r & 2) ^ ((f & 1) * 2);
  }
  return m | (x << 4) | (y << 8) | (z << 16);
}
__device__ __forceinline__ void l2_prefetch(const void* p, uint32_t total, int b) {
  const uint32_t part = total / NCTA;
  asm volatile("cp.async.bulk.prefetch.L2.global [%0], %1;" :: "l"((const char*)p + (size_t)b * part), "r"(part) : "memory");
}

__global__ void __launch_bounds__(384, 1) conformer_kernel(const __grid_constant__ Params p) {
  extern __shared__ __align__(1024) uint8_t smem[];
  const int tid = threadIdx.x, lane = tid & 31;
  const int cw = __shfl_sync(0xffffffffu, tid >> 5, 0), wg = cw >> 2, w = cw & 3;
  const int b = blockIdx.x, r = b & 3, batch = b >> 6, t = (b >> 2) & 15;
  if ((uint32_t)__cvta_generic_to_shared(smem) != SM_BASE) return;
  PROF_MARK(0);
  PROF_TIME(30);

  if (cw == 8) {
    if (lane <= 2 * NSTAGE) mbar_init(SM_BASE + SM_FULL + lane * 8, (lane >= NSTAGE && lane < 2 * NSTAGE) ? 4 : 1);
    fence_async_smem();
    __syncwarp();
    asm volatile("{\n.reg .pred p;\nelect.sync _|p, 0xffffffff;\n"
                 "@p mbarrier.arrive.expect_tx.shared::cta.b64 _, [%1], 32768;\n"
                 "@p cp.async.bulk.tensor.4d.shared::cluster.global.mbarrier::complete_tx::bytes [%0], [%2, {0, %3, 0, %4}], [%1];\n}"
                 :: "r"(SM_BASE + SM_STG), "r"(SM_BASE + SM_XBAR), "l"(&p.map[M_X]), "r"(t * 64), "r"(batch) : "memory");
  } else if (wg == 1) {
    const int i = tid - 128;
    sts32(SM_BASE + SM_CS + (CS_FF2 + i) * 4, 0);
    sts32(SM_BASE + SM_CS + (CS_FF2 + 128 + i) * 4, 0);
    if (i < 96) sts32(SM_BASE + SM_EYE + i * 4, ((i & 32) == 0 && (i & 3) == ((i >> 3) & 3)) ? (0x3F00u << ((i & 4) * 4)) : 0u);
    fence_async_smem();
  }
  const uint32_t epoch = ((volatile uint32_t*)g_epoch)[b] + 1;
  if (cw == 8) bar_arrive(0, 384); else bar_sync(0, 384);

  if (wg == 2) {
    asm volatile("setmaxnreg.dec.sync.aligned.u32 40;");
    if (w == 0) {
      const uint32_t* flag = &g_flag[batch * 4 + r][lane];
      uint32_t ready = 0, entry = 0, st = 0, parity = 1;
#pragma unroll 1
      for (int f = 0; f < F_TOTAL; f++) {
        if ((f & 31) == 0) entry = fill_entry(f + lane, r, batch * 4 + r);
        const uint32_t e = __shfl_sync(0xffffffffu, entry, f & 31);
        if ((e & 15) == M_KV) {
          const uint32_t need = 3u << ((e >> 8) & 31);
          uint32_t spin = 0;
#pragma unroll 1
          while ((ready & need) != need && ++spin < SPIN_LIMIT) {
            uint32_t v;
            asm volatile("ld.relaxed.gpu.global.u32 %0, [%1];" : "=r"(v) : "l"(flag) : "memory");
            ready = __ballot_sync(0xffffffffu, v == epoch);
          }
        }
        mbar_wait(SM_BASE + SM_EMPTY + st * 8, parity);
        asm volatile("{\n.reg .pred p;\nelect.sync _|p, 0xffffffff;\n"
                     "@p mbarrier.arrive.expect_tx.shared::cta.b64 _, [%1], 16384;\n"
                     "@p cp.async.bulk.tensor.3d.shared::cluster.global.mbarrier::complete_tx::bytes [%0], [%2, {%3, %4, %5}], [%1];\n}"
                     :: "r"(SM_BASE + st * STAGE_BYTES), "r"(SM_BASE + SM_FULL + st * 8), "l"(&p.map[e & 15]),
                        "r"((e << 2) & 0x3C0), "r"((e >> 2) & 0x3FC0), "r"(e >> 16) : "memory");
        if (++st == NSTAGE) { st = 0; parity ^= 1; }
        if (f >= F_KV && f < F_WO) PROF_MARK(1 + f - F_KV);
      }
    } else if (w < 3) {
      const int kind = w - 1;
      if (kind == 0) bar_sync(BAR_K, 160); else bar_sync(BAR_V, 160);
      if (lane == 0) {
        asm volatile("cp.async.bulk.global.shared::cta.bulk_group [%0], [%1], %2;"
                     :: "l"(&g_kv[batch * 4 + r][kind][t][0]), "r"(SM_BASE + SM_STG + kind * TILE_BYTES), "r"(TILE_BYTES) : "memory");
        asm volatile("cp.async.bulk.commit_group;\ncp.async.bulk.wait_group 0;" ::: "memory");
        asm volatile("st.relaxed.gpu.global.u32 [%0], %1;" :: "l"(&g_flag[batch * 4 + r][kind * 16 + t]), "r"(epoch) : "memory");
      }
    } else {
      if (lane < M_COUNT) asm volatile("prefetch.tensormap [%0];" :: "l"(&p.map[lane]) : "memory");
      if (lane == 0) {
        l2_prefetch(p.w_ff1b, 1024 * 256 * 2, b);
        l2_prefetch(p.w_o, 256 * 256 * 2, b);
        l2_prefetch(p.w_pw2, 256 * 256 * 2, b);
        l2_prefetch(p.w_ff2b, 1024 * 256 * 2, b);
      }
    }
  } else {
    asm volatile("setmaxnreg.inc.sync.aligned.u32 232;");
    const uint32_t tag = epoch & 1;
    const int q = lane & 3, th = tid & 127;
    constexpr uint32_t stg = SM_BASE + SM_STG;
    const uint32_t mrow = 16 * w + (lane & 15);
    const uint32_t maddr = stg + mrow * 128 + (((lane >> 4) ^ (lane & 7)) << 4);
    const uint32_t csq = SM_BASE + SM_CS + q * 8;
    const uint32_t res = stg + 3 * TILE_BYTES + w * 2048 + lane * 16;
    const uint32_t xoff = b * X_SIZE + th;
    const int nvalid = T_SEQ - t * 64;

    uint32_t A[4][16];
    RowNorm nrm;
    if (wg == 0) {
      mbar_wait(SM_BASE + SM_XBAR, 0);
      PROF_MARK(1);
      RowAcc ra = {}, rb = {};
#pragma unroll
      for (int c = 0; c < 4; c++) {
        tile_load(maddr + (r ^ c) * TILE_BYTES, A[c]);
        row_acc((c & 1) ? rb : ra, A[c]);
      }
      __syncwarp();
      res_store(res, A[0]);
      const float s0 = ra.s[0] + rb.s[0], s1 = ra.s[2] + rb.s[2];
      const uint32_t m0 = pack2(s0 * (1.f / DM), s0 * (1.f / DM)), m1 = pack2(s1 * (1.f / DM), s1 * (1.f / DM));
#pragma unroll
      for (int c = 0; c < 4; c++) {
#pragma unroll
        for (int i = 0; i < 16; i++) asm("sub.rn.bf16x2 %0, %0, %1;" : "+r"(A[c][i]) : "r"((i & 1) ? m1 : m0));
        pin(A[c]);
      }
      const bool odd = lane & 4;
      const int src = (lane & 28) | (lane >> 3);
      const float q0 = __shfl_sync(0xffffffffu, odd ? ra.u[1] + rb.u[1] : ra.u[0] + rb.u[0], src);
      const float q1 = __shfl_sync(0xffffffffu, odd ? ra.v[3] + rb.v[3] : ra.v[2] + rb.v[2], src);
      nrm = row_norm(s0, q0, s1, q1, 0.5f);
      nrm.nm0 = 0.f; nrm.nm1 = 0.f;
    } else {
      if (b < 72) {
        const __nv_bfloat16* wp; int ld, col;
        if (b < 24) { wp = p.w_qkv; ld = 768; col = b * 32; }
        else if (b < 40) { wp = p.w_pw1; ld = 512; col = (b - 24) * 32; }
        else { wp = p.w_ff2a; ld = 1024; col = (b - 40) * 32; }
        const uint4* src = (const uint4*)(wp + (size_t)(th >> 2) * ld + col + q * 8);
        float c[8] = {0.f, 0.f, 0.f, 0.f, 0.f, 0.f, 0.f, 0.f};
#pragma unroll 1
        for (int h = 0; h < 2; h++) {
#pragma unroll
          for (int i = 0; i < 4; i++) {
            const uint4 v = __ldg(src + i * 4 * ld);
            c[0] += bf_lo(v.x); c[1] += bf_hi(v.x); c[2] += bf_lo(v.y); c[3] += bf_hi(v.y);
            c[4] += bf_lo(v.z); c[5] += bf_hi(v.z); c[6] += bf_lo(v.w); c[7] += bf_hi(v.w);
          }
          src += 16 * ld;
        }
#pragma unroll 1
        for (int m = 4; m <= 16; m <<= 1)
#pragma unroll
          for (int k = 0; k < 8; k++) c[k] += __shfl_xor_sync(0xffffffffu, c[k], m);
        if (lane < 4) {
          const uint32_t a = SM_BASE + SM_CS + w * 128 + lane * 32;
          sts128(a, __float_as_uint(c[0]), __float_as_uint(c[1]), __float_as_uint(c[2]), __float_as_uint(c[3]));
          sts128(a + 16, __float_as_uint(c[4]), __float_as_uint(c[5]), __float_as_uint(c[6]), __float_as_uint(c[7]));
        }
        bar_sync(BAR_WG1, 128);
        if (th < 8) {
          float o[4] = {0.f, 0.f, 0.f, 0.f};
#pragma unroll 1
          for (int k = 0; k < 4; k++) {
            uint32_t e[4];
            lds128(SM_BASE + SM_CS + k * 128 + th * 16, e[0], e[1], e[2], e[3]);
#pragma unroll
            for (int i = 0; i < 4; i++) o[i] += __uint_as_float(e[i]);
          }
          st_vec(&g_cs[b * 8 + th], (__float_as_uint(o[0]) & ~1u) | tag, __float_as_uint(o[1]), __float_as_uint(o[2]), __float_as_uint(o[3]));
        }
        bar_sync(BAR_WG1, 128);
      }
#pragma unroll 1
      for (int i = th; i < 144; i += 128) {
        int src;
        if (i < 48) src = ((64 + 16 * r + (i >> 4) * 64) % 192) + (i & 15);
        else if (i < 80) src = 192 + ((i - 48) >> 4) * 64 + 16 * r + (i & 15);
        else src = 320 + 64 * r + (i - 80);
        uint32_t e[4], spin = 0;
#pragma unroll 1
        do {
          ld_vec(&g_cs[src], e[0], e[1], e[2], e[3]);
        } while (((e[0] ^ tag) & 1u) && ++spin < SPIN_LIMIT);
        sts128(SM_BASE + SM_CS + i * 16, e[0] & ~1u, e[1], e[2], e[3]);
      }
      bar_arrive(BAR_CS, 256);
    }

#pragma unroll 1
    for (uint32_t pass = 0; pass < 2; pass++) {
      uint32_t Q[16];
      if (wg == 0) {
        float acc[4][32];
        uint32_t H[4][16];
        ACQUIRE(0);
        mma_tile<true>(acc[0], A[0], LO(0)); mma_tile<true>(acc[1], A[0], HI(0));
        ACQUIRE(1);
        mma_tile<true>(acc[2], A[0], LO(1)); mma_tile<true>(acc[3], A[0], HI(1));
        ACQUIRE(2); ACQUIRE(3);
        if (pass) gather(A, here(xoff) + X_AG0, tag);
        PROF_MARK(2 + pass * 16);
        mma_tile<false>(acc[0], A[1], LO(2)); mma_tile<false>(acc[0], A[2], LO(3));
        WG_WAIT(2);
        RELEASE(0, 1);
        if (pass) nrm = stat_gather(b, here(th), 1, 0.5f);
        const uint32_t cs = csq + CS_FF2 * 4;
        ACQUIRE(4);
        mma_tile<false>(acc[0], A[3], LO(4)); mma_tile<false>(acc[1], A[1], HI(2)); mma_tile<false>(acc[1], A[2], HI(3));
        WG_WAIT(2); pin(acc[0]);
        silu_part<0, 4>(acc[0], H[0], nrm, cs);
        mma_tile<false>(acc[1], A[3], HI(4));
        silu_part<4, 8>(acc[0], H[0], nrm, cs);
        ACQUIRE(5); ACQUIRE(6);
        mma_tile<false>(acc[2], A[1], LO(5)); mma_tile<false>(acc[2], A[2], LO(6));
        WG_WAIT(2); pin(acc[1]);
        RELEASE(2, 4);
        silu_part<0, 4>(acc[1], H[1], nrm, cs + 256);
        ACQUIRE(7);
        mma_tile<false>(acc[2], A[3], LO(7));
        silu_part<4, 8>(acc[1], H[1], nrm, cs + 256);
        mma_tile<false>(acc[3], A[1], HI(5)); mma_tile<false>(acc[3], A[2], HI(6));
        WG_WAIT(2); pin(acc[2]);
        silu_part<0, 4>(acc[2], H[2], nrm, cs + 512);
        mma_tile<false>(acc[3], A[3], HI(7));
        silu_part<4, 8>(acc[2], H[2], nrm, cs + 512);
        pin(H[0]); pin(H[1]); pin(H[2]);
        ACQUIRE(8);
        mma_tile<true>(acc[0], H[0], LO(8)); mma_tile<false>(acc[0], H[1], HI(8));
        WG_WAIT(2); pin(acc[3]);
        RELEASE(5, 7);
        silu_part<0, 4>(acc[3], H[3], nrm, cs + 768);
        ACQUIRE(9);
        mma_tile<false>(acc[0], H[2], LO(9));
        silu_part<4, 8>(acc[3], H[3], nrm, cs + 768);
        pin(H[3]);
        mma_tile<false>(acc[0], H[3], HI(9));
        PROF_MARK(3 + pass * 16);
        const uint32_t rtag = pass ^ 1;
        const uint4* rs_in = &g_x[0][X_RS] + here(xoff);
#pragma unroll
        for (int c = 1; c < 4; c++) {
          ACQUIRE(8 + 2 * c);
          mma_tile<true>(acc[c], H[0], LO(8 + 2 * c)); mma_tile<false>(acc[c], H[1], HI(8 + 2 * c));
          WG_WAIT(2); pin(acc[c - 1]);
          uint32_t o[16];
          pack_acc(acc[c - 1], o);
          publish(&g_x[0][X_RS + (c - 1) * 512] + (here(xoff) ^ (c * X_SIZE)), o, rtag);
          RELEASE(6 + 2 * c, 7 + 2 * c);
          if (c == 2) res_load(res, acc[0]);
          if (c == 3) { fetch(rs_in, A[1]); fetch(rs_in + 512, A[2]); }
          ACQUIRE(9 + 2 * c);
          mma_tile<false>(acc[c], H[2], LO(9 + 2 * c)); mma_tile<false>(acc[c], H[3], HI(9 + 2 * c));
        }
        fetch(rs_in + 1024, A[3]);
#pragma unroll
        for (int c = 1; c < 4; c++) {
          confirm(rs_in + (c - 1) * 512, A[c], rtag);
          mma_add_half(acc[0], A[c]);
        }
        PROF_MARK(4 + pass * 16);
        WG_WAIT(0); pin(acc[0]); pin(acc[3]);
#pragma unroll
        for (int i = 0; i < 16; i++) A[0][i] = pack2(fmaf(acc[3][2 * i], 0.5f, acc[0][2 * i]), fmaf(acc[3][2 * i + 1], 0.5f, acc[0][2 * i + 1]));
        if (pass) {
          PROF_MARK(21);
          stat_publish(A[0], b, here(th), 0);
          const RowNorm fn = stat_gather(b, here(th), 0, 1.f);
#pragma unroll
          for (int i = 0; i < 16; i++) {
            const float rs = (i & 1) ? fn.rs1 : fn.rs0, nm = (i & 1) ? fn.nm1 : fn.nm0;
            A[0][i] = pack2(fmaf(bf_lo(A[0][i]), rs, nm), fmaf(bf_hi(A[0][i]), rs, nm));
          }
          tile_store(here(maddr), A[0]);
          __syncwarp();
          const int row = 16 * w + (lane >> 3);
          uint4* dst = (uint4*)(p.out + ((size_t)batch * T_SEQ + t * 64 + row) * DM + 64 * r) + (lane & 7);
          const uint32_t src = stg + row * 128 + (((lane & 7) ^ (lane >> 3)) << 4);
#pragma unroll
          for (int i = 0; i < 4; i++) {
            uint4 v;
            lds128((src ^ ((i & 1) << 6)) + i * 512, v.x, v.y, v.z, v.w);
            if (row + 4 * i < nvalid) dst[i * 4 * (DM / 8)] = v;
          }
          if (tid == 0) g_epoch[b] = epoch;
          PROF_MARK(22);
          PROF_TIME(31);
          break;
        }
        publish(&g_x[0][X_AG0] + here(xoff), A[0], tag);
        PROF_MARK(5);
        RELEASE(14, 15);
        res_store(res, A[0]);
        stat_publish(A[0], b, here(th), 1);
        const uint32_t flip = (r & 1) * TILE_BYTES;
        ACQUIRE(F_QKV);
        mma_tile<true>(acc[0], A[0], LO(F_QKV)); mma_tile<true>(acc[1], A[0], HI(F_QKV));
        ACQUIRE(F_QKV + 1);
        mma_tile<true>(acc[2], A[0], LO(F_QKV + 1) + flip);
        ACQUIRE(F_QKV + 2); ACQUIRE(F_QKV + 3); ACQUIRE(F_QKV + 4);
        gather(A, here(xoff) + X_AG0, tag);
        PROF_MARK(6);
        mma_tile<false>(acc[0], A[1], LO(F_QKV + 2)); mma_tile<false>(acc[0], A[2], LO(F_QKV + 3)); mma_tile<false>(acc[0], A[3], LO(F_QKV + 4));
        mma_tile<false>(acc[1], A[1], HI(F_QKV + 2));
        nrm = stat_gather(b, here(th), 1, 1.f);
        bar_sync(BAR_CS, 256);
        mma_tile<false>(acc[1], A[2], HI(F_QKV + 3));
        WG_WAIT(2); pin(acc[0]);
        mma_tile<false>(acc[1], A[3], HI(F_QKV + 4));
        fold_ln<0, 8>(acc[0], nrm, csq + CS_QKV * 4);
        pack_acc(acc[0], Q);
        tile_store(here(maddr), Q);
        fence_async_smem();
        bar_arrive(BAR_K, 160);
        ACQUIRE(F_QKV + 5);
        mma_tile<false>(acc[2], A[1], HI(F_QKV + 1) - flip); mma_tile<false>(acc[2], A[2], LO(F_QKV + 5) + flip);
        WG_WAIT(2); pin(acc[1]);
        mma_tile<false>(acc[2], A[3], HI(F_QKV + 5) - flip);
        fold_ln<0, 8>(acc[1], nrm, csq + CS_QKV * 4 + 256);
        pack_acc(acc[1], Q);
        tile_store(here(maddr) + TILE_BYTES, Q);
        fence_async_smem();
        bar_arrive(BAR_V, 160);
        ACQUIRE(F_SPARE); ACQUIRE(F_SPARE + 1);
        WG_WAIT(0); pin(acc[2]);
        RELEASE(F_QKV, F_SPARE + 1);
        fold_ln<0, 8>(acc[2], nrm, csq + CS_QKV * 4 + 512);
        pack_acc(acc[2], Q);
        res_store(here(res) - TILE_BYTES, Q);
        bar_arrive(BAR_Q, 256);
      } else {
        bar_sync(BAR_Q, 256);
#pragma unroll
        for (int s = 0; s < 4; s++) lds128(res - TILE_BYTES + s * 512, Q[4 * s], Q[4 * s + 1], Q[4 * s + 2], Q[4 * s + 3]);
      }
      PROF_MARK(7);

      float O[32];
      float m0 = -INFINITY, m1 = -INFINITY, l0 = 0.f, l1 = 0.f;
      {
#pragma unroll
        for (int i = 0; i < 32; i++) O[i] = 0.f;
        pin(Q);
        float S[2][32];
        attn_scores(S, Q, wg, 0);
        PROF_MARK(8);
        WG_WAIT(0);
        uint32_t sk = wg;
#pragma unroll 1
        for (int it = 0;; it++) {
          pin(S[0]); pin(S[1]); pin(O);
          if (lane == 0) mbar_arrive(SM_BASE + SM_EMPTY + sk * 8);
          if (it == 3 && wg == 1) {
#pragma unroll
            for (int i = 20; i < 32; i++) S[1][i] = -INFINITY;
          }
          float n0 = m0, n1 = m1;
#pragma unroll
          for (int h = 0; h < 2; h++)
#pragma unroll
            for (int j = 0; j < 8; j++) {
              n0 = fmaxf(n0, fmaxf(S[h][4 * j], S[h][4 * j + 1]));
              n1 = fmaxf(n1, fmaxf(S[h][4 * j + 2], S[h][4 * j + 3]));
            }
          n0 = fmaxf(n0, __shfl_xor_sync(0xffffffffu, n0, 1)); n1 = fmaxf(n1, __shfl_xor_sync(0xffffffffu, n1, 1));
          n0 = fmaxf(n0, __shfl_xor_sync(0xffffffffu, n0, 2)); n1 = fmaxf(n1, __shfl_xor_sync(0xffffffffu, n1, 2));
          const float a0 = ex2_hw((m0 - n0) * SM_SCALE_LOG2), a1 = ex2_hw((m1 - n1) * SM_SCALE_LOG2);
          m0 = n0; m1 = n1;
          const float c0 = -n0 * SM_SCALE_LOG2, c1 = -n1 * SM_SCALE_LOG2;
          l0 *= a0; l1 *= a1;
          uint32_t P[2][16];
#pragma unroll
          for (int h = 0; h < 2; h++)
#pragma unroll
            for (int j = 0; j < 8; j++) {
              const float p0 = ex2_hw(fmaf(S[h][4 * j], SM_SCALE_LOG2, c0)), p1 = ex2_hw(fmaf(S[h][4 * j + 1], SM_SCALE_LOG2, c0));
              const float p2 = ex2_hw(fmaf(S[h][4 * j + 2], SM_SCALE_LOG2, c1)), p3 = ex2_hw(fmaf(S[h][4 * j + 3], SM_SCALE_LOG2, c1));
              l0 += p0 + p1; l1 += p2 + p3;
              P[h][2 * j] = pack2(p0, p1); P[h][2 * j + 1] = pack2(p2, p3);
            }
#pragma unroll
          for (int j = 0; j < 8; j++) { O[4 * j] *= a0; O[4 * j + 1] *= a0; O[4 * j + 2] *= a1; O[4 * j + 3] *= a1; }
          pin(P[0]); pin(P[1]); pin(O);
          const uint32_t sv = sk + 2;
          if (wg == 1) PROF_MARK(16 + it * 3);
          mbar_wait(SM_BASE + SM_FULL + sv * 8, it == 3);
          if (wg == 1) PROF_MARK(17 + it * 3);
          mma_tile<false>(O, P[0], SM_BASE + sv * STAGE_BYTES);
          mma_tile<false>(O, P[1], SM_BASE + sv * STAGE_BYTES + TILE_BYTES);
          if (it == 3) break;
          sk = it == 2 ? wg : sk + 4;
          attn_scores(S, Q, sk, it == 2);
          WG_WAIT(0);
          if (lane == 0) mbar_arrive(SM_BASE + SM_EMPTY + sv * 8);
          if (wg == 1) PROF_MARK(18 + it * 3);
        }
        l0 += __shfl_xor_sync(0xffffffffu, l0, 1); l1 += __shfl_xor_sync(0xffffffffu, l1, 1);
        l0 += __shfl_xor_sync(0xffffffffu, l0, 2); l1 += __shfl_xor_sync(0xffffffffu, l1, 2);
        WG_WAIT(0); pin(O);
        if (lane == 0) mbar_arrive(SM_BASE + SM_EMPTY + (wg + 2) * 8);
      }
      PROF_MARK(9);

      if (wg == 1) {
        const uint32_t mo = stg + here(th) * 16;
#pragma unroll
        for (int i = 0; i < 8; i++)
          sts128(mo + i * 2048, __float_as_uint(O[4 * i]), __float_as_uint(O[4 * i + 1]), __float_as_uint(O[4 * i + 2]), __float_as_uint(O[4 * i + 3]));
        sts128(mo + 8 * 2048, __float_as_uint(m0), __float_as_uint(m1), __float_as_uint(l0), __float_as_uint(l1));
        bar_arrive(BAR_MERGE, 256);
      } else {
        const uint32_t mo = stg + here(th) * 16;
        bar_sync(BAR_MERGE, 256);
        uint32_t e[4];
        lds128(mo + 8 * 2048, e[0], e[1], e[2], e[3]);
        const float n0 = fmaxf(m0, __uint_as_float(e[0])), n1 = fmaxf(m1, __uint_as_float(e[1]));
        float a0 = ex2_hw((m0 - n0) * SM_SCALE_LOG2), a1 = ex2_hw((m1 - n1) * SM_SCALE_LOG2);
        float b0 = ex2_hw((__uint_as_float(e[0]) - n0) * SM_SCALE_LOG2), b1 = ex2_hw((__uint_as_float(e[1]) - n1) * SM_SCALE_LOG2);
        const float i0 = rcp_hw(fmaf(a0, l0, b0 * __uint_as_float(e[2]))), i1 = rcp_hw(fmaf(a1, l1, b1 * __uint_as_float(e[3])));
        a0 *= i0; b0 *= i0; a1 *= i1; b1 *= i1;
#pragma unroll
        for (int i = 0; i < 8; i++) {
          lds128(mo + i * 2048, e[0], e[1], e[2], e[3]);
          A[0][2 * i] = pack2(fmaf(O[4 * i], a0, b0 * __uint_as_float(e[0])), fmaf(O[4 * i + 1], a0, b0 * __uint_as_float(e[1])));
          A[0][2 * i + 1] = pack2(fmaf(O[4 * i + 2], a1, b1 * __uint_as_float(e[2])), fmaf(O[4 * i + 3], a1, b1 * __uint_as_float(e[3])));
        }
        PROF_MARK(10);
        proj_residual<F_WO>(A, here(xoff), res, r, 1, tag ^ 1, lane);
        PROF_MARK(12);
      }

      const int dir = cw == 0 ? -1 : 1;
      uint32_t tap[15];
      {
        const uint32_t* dwp = (const uint32_t*)(p.dw + 64 * r) + lane + 7 * (DM / 2);
#pragma unroll
        for (int k = 0; k < 15; k++) tap[k] = __ldg(dwp + dir * (k - 7) * (DM / 2));
      }

      if (wg == 0) {
        float acc[2][32];
        stat_publish(A[0], b, here(th), 0);
        ACQUIRE(F_PW1);
        mma_tile<true>(acc[0], A[0], LO(F_PW1)); mma_tile<true>(acc[1], A[0], HI(F_PW1));
        ACQUIRE(F_PW1 + 1); ACQUIRE(F_PW1 + 2); ACQUIRE(F_PW1 + 3);
        gather(A, here(xoff) + X_AG0, tag ^ 1);
        PROF_MARK(13);
#pragma unroll
        for (int c = 1; c < 4; c++) mma_tile<false>(acc[1], A[c], HI(F_PW1 + c));
        mma_tile<false>(acc[0], A[1], LO(F_PW1 + 1));
        nrm = stat_gather(b, here(th), 0, 0.5f);
        const int row = 16 * w + (lane >> 2);
        if (row >= nvalid) { nrm.rs0 = 0.f; nrm.nm0 = 0.f; }
        if (row + 8 >= nvalid) { nrm.rs1 = 0.f; nrm.nm1 = 0.f; }
        mma_tile<false>(acc[0], A[2], LO(F_PW1 + 2)); mma_tile<false>(acc[0], A[3], LO(F_PW1 + 3));
        WG_WAIT(3); pin(acc[1]);
        fold_ln<0, 8>(acc[1], nrm, csq + CS_PW1 * 4 + 256);
#pragma unroll
        for (int i = 0; i < 32; i++) acc[1][i] = tanh_hw(acc[1][i]);
        WG_WAIT(0); pin(acc[0]);
        fold_ln<0, 8>(acc[0], nrm, csq + CS_PW1 * 4);
#pragma unroll
        for (int i = 0; i < 16; i++)
          A[0][i] = pack2(fmaf(acc[0][2 * i], acc[1][2 * i], acc[0][2 * i]), fmaf(acc[0][2 * i + 1], acc[1][2 * i + 1], acc[0][2 * i + 1]));
        const uint32_t ga = stg + TILE_BYTES + here(mrow) * G_PITCH + (lane >> 4) * 16;
#pragma unroll
        for (int s = 0; s < 4; s++) stsm4(ga + s * 32, &A[0][4 * s]);
        RELEASE(F_PW1, F_PW1 + 3);
      }
      bar_sync(BAR_G, 256);
      PROF_MARK(14);

      {
        const int first = cw == 0 ? 14 : 8 * cw - 7;
        const uint32_t gsrc = stg + TILE_BYTES + first * G_PITCH + lane * 4;
        uint32_t in[22];
#pragma unroll
        for (int i = 0; i < 15; i++) in[i] = lds32(gsrc + dir * i * (int)G_PITCH);
        const bool edge = cw == 0 || cw == 7;
        const bool nbr = cw == 0 ? t > 0 : t < 15;
        if (edge) {
          if (nbr) {
            uint4* dst = &g_x[b + 4 * dir][X_HALO + (cw == 0 ? 96 : 0) + lane];
            st_vec(dst, epoch, in[14], in[13], in[12]);
            st_vec(dst + 32, epoch, in[11], in[10], in[9]);
            st_vec(dst + 64, epoch, in[8], 0u, 0u);
          }
        } else {
#pragma unroll
          for (int i = 15; i < 22; i++) in[i] = lds32(gsrc + i * G_PITCH);
        }
        float cl[8], ch[8], tl[15], tv[15];
#pragma unroll
        for (int k = 0; k < 15; k++) { tl[k] = bf_lo(tap[k]); tv[k] = bf_hi(tap[k]); }
#pragma unroll
        for (int o = 0; o < 8; o++) { cl[o] = 0.f; ch[o] = 0.f; }
#pragma unroll
        for (int i = 0; i < 15; i++) {
          const float lo = bf_lo(in[i]), hi = bf_hi(in[i]);
#pragma unroll
          for (int o = 0; o < 8; o++)
            if (i - o >= 0) { cl[o] = fmaf(lo, tl[i - o], cl[o]); ch[o] = fmaf(hi, tv[i - o], ch[o]); }
        }
        if (edge) {
#pragma unroll
          for (int i = 15; i < 22; i++) in[i] = 0u;
          if (nbr) {
            const uint4* src = &g_x[b][X_HALO + (cw == 0 ? 0 : 96) + lane];
            uint32_t e0, e1, e2, u0, u1, spin = 0;
#pragma unroll 1
            do {
              ld_vec(src, e0, in[15], in[16], in[17]);
              ld_vec(src + 32, e1, in[18], in[19], in[20]);
              ld_vec(src + 64, e2, in[21], u0, u1);
            } while (__any_sync(0xffffffffu, ((e0 ^ epoch) | (e1 ^ epoch) | (e2 ^ epoch)) != 0) && ++spin < SPIN_LIMIT);
          }
        }
#pragma unroll
        for (int i = 15; i < 22; i++) {
          const float lo = bf_lo(in[i]), hi = bf_hi(in[i]);
#pragma unroll
          for (int o = 0; o < 8; o++)
            if (i - o <= 14) { cl[o] = fmaf(lo, tl[i - o], cl[o]); ch[o] = fmaf(hi, tv[i - o], ch[o]); }
        }
        const uint32_t fl = cw == 0 ? 7 : 0;
        const uint32_t cdst = (stg + cw * 1024 + lane * 4) ^ (fl * 144);
#pragma unroll
        for (int o = 0; o < 8; o++) {
          const float a = 0.5f * cl[o], c = 0.5f * ch[o];
          sts32(cdst ^ (o * 144), pack2(fmaf(a, tanh_hw(a), a), fmaf(c, tanh_hw(c), c)));
        }
      }
      if (wg == 1) {
        bar_arrive(BAR_C, 256);
        break;
      }
      bar_sync(BAR_C, 256);
      tile_load(here(maddr), A[0]);
      PROF_MARK(15);
      proj_residual<F_PW2>(A, here(xoff), res, r, 0, tag, lane);
      PROF_MARK(17);
      stat_publish(A[0], b, here(th), 1);
    }
  }
}

typedef CUresult (*EncodeFn)(CUtensorMap*, CUtensorMapDataType, cuuint32_t, void*, const cuuint64_t*, const cuuint64_t*,
                             const cuuint32_t*, const cuuint32_t*, CUtensorMapInterleave, CUtensorMapSwizzle,
                             CUtensorMapL2promotion, CUtensorMapFloatOOBfill);

void make_map(EncodeFn fn, CUtensorMap* m, const void* w, int rank, int d0, int d1, int d2, int d3, int s1, int s2, int s3,
              int b1, int b2, CUtensorMapSwizzle swz) {
  const cuuint64_t dims[4] = {(cuuint64_t)d0, (cuuint64_t)d1, (cuuint64_t)d2, (cuuint64_t)d3};
  const cuuint64_t strides[3] = {(cuuint64_t)s1, (cuuint64_t)s2, (cuuint64_t)s3};
  const cuuint32_t box[4] = {64, (cuuint32_t)b1, (cuuint32_t)b2, 1}, es[4] = {1, 1, 1, 1};
  fn(m, CU_TENSOR_MAP_DATA_TYPE_BFLOAT16, rank, const_cast<void*>(w), dims, strides, box, es, CU_TENSOR_MAP_INTERLEAVE_NONE,
     swz, CU_TENSOR_MAP_L2_PROMOTION_L2_128B, CU_TENSOR_MAP_FLOAT_OOB_FILL_NONE);
}

}

extern "C" void kernel_launch(void* const* d_in, const int* in_sizes, int n_in, void* d_out, int out_size) {
  static EncodeFn fn = nullptr;
  static void* kv = nullptr;
  if (!fn) {
    void* f = nullptr;
    cudaDriverEntryPointQueryResult st;
    cudaGetDriverEntryPoint("cuTensorMapEncodeTiled", &f, cudaEnableDefault, &st);
    fn = (EncodeFn)f;
    cudaGetSymbolAddress(&kv, g_kv);
    cudaFuncSetAttribute(conformer_kernel, cudaFuncAttributeMaxDynamicSharedMemorySize, SM_TOTAL);
  }
  typedef const __nv_bfloat16* W;
  const CUtensorMapSwizzle S = CU_TENSOR_MAP_SWIZZLE_128B;
  Params p;
  make_map(fn, &p.map[M_X], d_in[0], 4, 64, T_SEQ, 4, 2, 512, 128, T_SEQ * 512, 64, 4, S);
  make_map(fn, &p.map[M_FF1A], d_in[1], 3, 64, 256, 16, 1, 2048, 128, 0, 64, 2, S);
  make_map(fn, &p.map[M_FF1B], d_in[2], 3, 256, 1024, 1, 1, 512, 512 * 1024, 0, 128, 1, S);
  make_map(fn, &p.map[M_WKV], d_in[3], 3, 256, 256, 3, 1, 1536, 512, 0, 64, 2, S);
  make_map(fn, &p.map[M_WQ], d_in[3], 3, 256, 256, 3, 1, 1536, 512, 0, 128, 1, S);
  make_map(fn, &p.map[M_KV], kv, 3, 64, 16384, 1, 1, 128, 128 * 16384, 0, 128, 1, CU_TENSOR_MAP_SWIZZLE_NONE);
  make_map(fn, &p.map[M_WO], d_in[4], 3, 256, 256, 1, 1, 512, 512 * 256, 0, 128, 1, S);
  make_map(fn, &p.map[M_PW1], d_in[5], 3, 256, 256, 2, 1, 1024, 512, 0, 64, 2, S);
  make_map(fn, &p.map[M_PW2], d_in[7], 3, 256, 256, 1, 1, 512, 512 * 256, 0, 128, 1, S);
  make_map(fn, &p.map[M_FF2A], d_in[8], 3, 64, 256, 16, 1, 2048, 128, 0, 64, 2, S);
  make_map(fn, &p.map[M_FF2B], d_in[9], 3, 256, 1024, 1, 1, 512, 512 * 1024, 0, 128, 1, S);
  p.w_ff1b = (W)d_in[2]; p.w_qkv = (W)d_in[3]; p.w_o = (W)d_in[4]; p.w_pw1 = (W)d_in[5];
  p.dw = (W)d_in[6]; p.w_pw2 = (W)d_in[7]; p.w_ff2a = (W)d_in[8]; p.w_ff2b = (W)d_in[9];
  p.out = (__nv_bfloat16*)d_out;

  cudaLaunchConfig_t cfg = {};
  cfg.gridDim = dim3(NCTA);
  cfg.blockDim = dim3(384);
  cfg.dynamicSmemBytes = SM_TOTAL;
  cfg.stream = cudaStreamPerThread;
  cudaLaunchAttribute at[1];
  at[0].id = cudaLaunchAttributeCooperative;
  at[0].val.cooperative = 1;
  cfg.attrs = at;
  cfg.numAttrs = 1;
  cudaLaunchKernelEx(&cfg, conformer_kernel, p);
}
```

```cpp
#include <cuda_runtime.h>
#include <cuda_bf16.h>
#include <cuda.h>
#include <stdint.h>

namespace {

constexpr int T_SEQ = 1000;
constexpr int DM = 256;
constexpr int NCTA = 128;
constexpr int NSTAGE = 12;
constexpr uint32_t STAGE_BYTES = 16384;
constexpr uint32_t TILE_BYTES = 8192;
constexpr uint32_t SM_BASE = 1024;
constexpr uint32_t SM_STG = NSTAGE * STAGE_BYTES;
constexpr uint32_t SM_FULL = SM_STG + 32768;
constexpr uint32_t SM_EMPTY = SM_FULL + 96;
constexpr uint32_t SM_XBAR = SM_FULL + 192;
constexpr uint32_t SM_EYE = SM_FULL + 256;
constexpr uint32_t SM_CS = SM_FULL + 768;
constexpr uint32_t SM_TOTAL = SM_FULL + 3072;
constexpr int CS_FF2 = 0, CS_PW1 = 4, CS_QKV = 6;
constexpr uint32_t SPIN_LIMIT = 1u << 16;
constexpr float LN_EPS = 1e-5f;
constexpr float SM_SCALE_LOG2 = 0.125f * 1.4426950408889634f;
constexpr uint32_t G_PITCH = 144;

constexpr int F_QKV = 16, F_SPARE = 22, F_KV = 24, F_WO = 40, F_PW1 = 42, F_PW2 = 46, F_TOTAL = 64;
enum { M_FF1A, M_FF1B, M_WKV, M_WQ, M_KV, M_WO, M_PW1, M_PW2, M_FF2A, M_FF2B, M_X, M_COUNT };
enum { BAR_K = 1, BAR_V, BAR_Q, BAR_MERGE, BAR_G, BAR_C, BAR_CS, BAR_WG1, BAR_RDY, BAR_TURN0, BAR_TURN1 };

struct Params {
  CUtensorMap map[M_COUNT];
  const __nv_bfloat16 *w_ff1b, *w_qkv, *w_o, *w_pw1, *dw, *w_pw2, *w_ff2a, *w_ff2b;
  __nv_bfloat16* out;
  uint64_t ring[4];
};

constexpr int X_AG0 = 0, X_RS = 512, X_AG1 = X_RS, X_HALO = X_RS + 512, X_ST = 2048, X_CLEAR = 2176, X_SIZE = 4096;
constexpr uint32_t HALO_TAG = 0xFFFF0001u;
__device__ __align__(1024) uint4 g_x[NCTA][X_SIZE];
__device__ __align__(1024) uint4 g_kv[8][2][16][512];
__device__ __align__(1024) uint32_t g_flag[8][32];
__device__ __align__(1024) uint4 g_cs[576];
__device__ __align__(1024) uint32_t g_ready[NCTA];
__device__ uint32_t g_epoch[NCTA];
#define PROF_TIME(i)
#define PROF_MARK(i)

__device__ __forceinline__ void mbar_init(uint32_t bar, uint32_t cnt) {
  asm volatile("mbarrier.init.shared::cta.b64 [%0], %1;" :: "r"(bar), "r"(cnt) : "memory");
}
__device__ __forceinline__ void mbar_wait(uint32_t bar, uint32_t parity) {
  asm volatile("{\n.reg .pred p;\n.reg .u32 c;\nmov.u32 c, 0;\n"
               "WAIT_LOOP:\nmbarrier.try_wait.parity.shared::cta.b64 p, [%0], %1;\n@p bra WAIT_DONE;\n"
               "add.u32 c, c, 1;\nsetp.lt.u32 p, c, %2;\n@p bra WAIT_LOOP;\nWAIT_DONE:\n}"
               :: "r"(bar), "r"(parity), "n"(SPIN_LIMIT) : "memory");
}
__device__ __forceinline__ void mbar_arrive(uint32_t bar) {
  asm volatile("mbarrier.arrive.shared::cta.b64 _, [%0];" :: "r"(bar) : "memory");
}
#define bar_sync(id, n) asm volatile("bar.sync %0, %1;" :: "n"((int)(id)), "n"(n) : "memory")
#define bar_arrive(id, n) asm volatile("bar.arrive %0, %1;" :: "n"((int)(id)), "n"(n) : "memory")
__device__ __forceinline__ void fence_async_smem() { asm volatile("fence.proxy.async.shared::cta;" ::: "memory"); }

__device__ __forceinline__ void st_vec(uint4* p, uint32_t a, uint32_t b, uint32_t c, uint32_t d) {
  asm volatile("{\n.reg .b128 v;\n.reg .b64 lo, hi;\nmov.b64 lo, {%1, %2};\nmov.b64 hi, {%3, %4};\nmov.b128 v, {lo, hi};\n"
               "st.relaxed.gpu.global.b128 [%0], v;\n}" :: "l"(p), "r"(a), "r"(b), "r"(c), "r"(d) : "memory");
}
__device__ __forceinline__ void ld_vec(const uint4* p, uint32_t& a, uint32_t& b, uint32_t& c, uint32_t& d) {
  asm volatile("{\n.reg .b128 v;\n.reg .b64 lo, hi;\nld.relaxed.gpu.global.b128 v, [%4];\nmov.b128 {lo, hi}, v;\n"
               "mov.b64 {%0, %1}, lo;\nmov.b64 {%2, %3}, hi;\n}" : "=r"(a), "=r"(b), "=r"(c), "=r"(d) : "l"(p) : "memory");
}
__device__ __forceinline__ void sts128(uint32_t a, uint32_t x, uint32_t y, uint32_t z, uint32_t w) {
  asm volatile("st.shared.v4.u32 [%0], {%1, %2, %3, %4};" :: "r"(a), "r"(x), "r"(y), "r"(z), "r"(w) : "memory");
}
__device__ __forceinline__ void lds128(uint32_t a, uint32_t& x, uint32_t& y, uint32_t& z, uint32_t& w) {
  asm volatile("ld.shared.v4.u32 {%0, %1, %2, %3}, [%4];" : "=r"(x), "=r"(y), "=r"(z), "=r"(w) : "r"(a) : "memory");
}
__device__ __forceinline__ uint32_t lds32(uint32_t a) {
  uint32_t x; asm volatile("ld.shared.u32 %0, [%1];" : "=r"(x) : "r"(a) : "memory"); return x;
}
__device__ __forceinline__ void sts32(uint32_t a, uint32_t x) { asm volatile("st.shared.u32 [%0], %1;" :: "r"(a), "r"(x) : "memory"); }
__device__ __forceinline__ void sts64(uint32_t a, uint32_t x, uint32_t y) {
  asm volatile("st.shared.v2.u32 [%0], {%1, %2};" :: "r"(a), "r"(x), "r"(y) : "memory");
}
__device__ __forceinline__ void stsm4(uint32_t a, const uint32_t* r) {
  asm volatile("stmatrix.sync.aligned.m8n8.x4.shared.b16 [%0], {%1, %2, %3, %4};" :: "r"(a), "r"(r[0]), "r"(r[1]), "r"(r[2]), "r"(r[3]) : "memory");
}
__device__ __forceinline__ void ldsm4(uint32_t a, uint32_t* r) {
  asm volatile("ldmatrix.sync.aligned.m8n8.x4.shared.b16 {%0, %1, %2, %3}, [%4];" : "=r"(r[0]), "=r"(r[1]), "=r"(r[2]), "=r"(r[3]) : "r"(a) : "memory");
}
__device__ __forceinline__ uint32_t pack2(float lo, float hi) {
  uint32_t r; asm("cvt.rn.bf16x2.f32 %0, %1, %2;" : "=r"(r) : "f"(hi), "f"(lo)); return r;
}
__device__ __forceinline__ float bf_lo(uint32_t w) { return __uint_as_float(w << 16); }
__device__ __forceinline__ float bf_hi(uint32_t w) { return __uint_as_float(w & 0xffff0000u); }
__device__ __forceinline__ float tanh_hw(float x) { float y; asm volatile("tanh.approx.f32 %0, %1;" : "=f"(y) : "f"(x)); return y; }
__device__ __forceinline__ float rcp_hw(float x) { float y; asm("rcp.approx.ftz.f32 %0, %1;" : "=f"(y) : "f"(x)); return y; }
__device__ __forceinline__ float ex2_hw(float x) { float y; asm("ex2.approx.ftz.f32 %0, %1;" : "=f"(y) : "f"(x)); return y; }

__device__ __forceinline__ uint32_t here(uint32_t v) { asm volatile("" : "+r"(v)); return v; }

#define WG_FENCE() asm volatile("wgmma.fence.sync.aligned;" ::: "memory")
#define WG_COMMIT() asm volatile("wgmma.commit_group.sync.aligned;" ::: "memory")
#define WG_WAIT(n) asm volatile("wgmma.wait_group.sync.aligned %0;" :: "n"(n) : "memory")

template <int N> __device__ __forceinline__ void pin(float (&d)[N]) {
#pragma unroll
  for (int i = 0; i < N; i++) asm volatile("" : "+f"(d[i]) :: "memory");
}
template <int N> __device__ __forceinline__ void pin(uint32_t (&d)[N]) {
#pragma unroll
  for (int i = 0; i < N; i++) asm volatile("" : "+r"(d[i]) :: "memory");
}

#define WG_D32 "{%0, %1, %2, %3, %4, %5, %6, %7, %8, %9, %10, %11, %12, %13, %14, %15, %16, %17, %18, %19, %20, %21, %22, %23, %24, %25, %26, %27, %28, %29, %30, %31}"
template <int TB> __device__ __forceinline__ void wgmma64_acc(float (&d)[32], const uint32_t* a, uint64_t db) {
  asm volatile("wgmma.mma_async.sync.aligned.m64n64k16.f32.bf16.bf16 " WG_D32 ", {%32, %33, %34, %35}, %36, 1, 1, 1, %37;"
    : "+f"(d[0]), "+f"(d[1]), "+f"(d[2]), "+f"(d[3]), "+f"(d[4]), "+f"(d[5]), "+f"(d[6]), "+f"(d[7]),
      "+f"(d[8]), "+f"(d[9]), "+f"(d[10]), "+f"(d[11]), "+f"(d[12]), "+f"(d[13]), "+f"(d[14]), "+f"(d[15]),
      "+f"(d[16]), "+f"(d[17]), "+f"(d[18]), "+f"(d[19]), "+f"(d[20]), "+f"(d[21]), "+f"(d[22]), "+f"(d[23]),
      "+f"(d[24]), "+f"(d[25]), "+f"(d[26]), "+f"(d[27]), "+f"(d[28]), "+f"(d[29]), "+f"(d[30]), "+f"(d[31])
    : "r"(a[0]), "r"(a[1]), "r"(a[2]), "r"(a[3]), "l"(db), "n"(TB));
}
template <int TB> __device__ __forceinline__ void wgmma64_set(float (&d)[32], const uint32_t* a, uint64_t db) {
  asm volatile("wgmma.mma_async.sync.aligned.m64n64k16.f32.bf16.bf16 " WG_D32 ", {%32, %33, %34, %35}, %36, 0, 1, 1, %37;"
    : "=f"(d[0]), "=f"(d[1]), "=f"(d[2]), "=f"(d[3]), "=f"(d[4]), "=f"(d[5]), "=f"(d[6]), "=f"(d[7]),
      "=f"(d[8]), "=f"(d[9]), "=f"(d[10]), "=f"(d[11]), "=f"(d[12]), "=f"(d[13]), "=f"(d[14]), "=f"(d[15]),
      "=f"(d[16]), "=f"(d[17]), "=f"(d[18]), "=f"(d[19]), "=f"(d[20]), "=f"(d[21]), "=f"(d[22]), "=f"(d[23]),
      "=f"(d[24]), "=f"(d[25]), "=f"(d[26]), "=f"(d[27]), "=f"(d[28]), "=f"(d[29]), "=f"(d[30]), "=f"(d[31])
    : "r"(a[0]), "r"(a[1]), "r"(a[2]), "r"(a[3]), "l"(db), "n"(TB));
}

__device__ __forceinline__ void wgmma16_acc(float* d, const uint32_t* a, uint64_t db) {
  asm volatile("wgmma.mma_async.sync.aligned.m64n16k16.f32.bf16.bf16 {%0, %1, %2, %3, %4, %5, %6, %7}, {%8, %9, %10, %11}, %12, 1, 1, 1, 0;"
    : "+f"(d[0]), "+f"(d[1]), "+f"(d[2]), "+f"(d[3]), "+f"(d[4]), "+f"(d[5]), "+f"(d[6]), "+f"(d[7])
    : "r"(a[0]), "r"(a[1]), "r"(a[2]), "r"(a[3]), "l"(db));
}
__device__ __forceinline__ void hmma(float (&d)[4], const uint32_t* a, uint32_t b0, uint32_t b1) {
  asm("mma.sync.aligned.m16n8k16.row.col.f32.bf16.bf16.f32 {%0, %1, %2, %3}, {%4, %5, %6, %7}, {%8, %9}, {%0, %1, %2, %3};"
    : "+f"(d[0]), "+f"(d[1]), "+f"(d[2]), "+f"(d[3]) : "r"(a[0]), "r"(a[1]), "r"(a[2]), "r"(a[3]), "r"(b0), "r"(b1));
}

__device__ __forceinline__ void hmma8(float (&d)[4], const uint32_t* a, uint32_t b0) {
  asm("mma.sync.aligned.m16n8k8.row.col.f32.bf16.bf16.f32 {%0, %1, %2, %3}, {%4, %5}, {%6}, {%0, %1, %2, %3};"
    : "+f"(d[0]), "+f"(d[1]), "+f"(d[2]), "+f"(d[3]) : "r"(a[0]), "r"(a[1]), "r"(b0));
}

template <bool FIRST> __device__ __forceinline__ void mma_tile(float (&d)[32], const uint32_t (&a)[16], uint64_t db) {
  WG_FENCE();
#pragma unroll
  for (int s = 0; s < 4; s++) {
    if (FIRST && s == 0) wgmma64_set<1>(d, &a[0], db); else wgmma64_acc<1>(d, &a[4 * s], db + s * 128);
  }
  WG_COMMIT();
}
template <int ROW> __device__ __forceinline__ void mma_tile_fold(float (&d)[32], const uint32_t (&a)[16], uint64_t db, const uint32_t (&mu)[4]) {
  WG_FENCE();
#pragma unroll
  for (int s = 0; s < 4; s++) wgmma64_acc<1>(d, &a[4 * s], db + s * 128);
  wgmma64_acc<1>(d, mu, (uint64_t)((SM_BASE + SM_CS + ROW * 128) >> 4) | (uint64_t(1) << 16) | (uint64_t(1) << 62));
  WG_COMMIT();
}
__device__ __forceinline__ void mma_add_half(float (&d)[32], const uint32_t (&a)[16]) {
  const uint64_t db = (uint64_t)((SM_BASE + SM_EYE) >> 4) | (uint64_t(8) << 16) | (uint64_t(8) << 32);
  WG_FENCE();
#pragma unroll
  for (int s = 0; s < 4; s++) wgmma16_acc(&d[8 * s], &a[4 * s], db);
  WG_COMMIT();
}
#define ACQUIRE(f) mbar_wait(SM_BASE + SM_FULL + ((f) % NSTAGE) * 8, ((f) / NSTAGE) & 1)
template <int F, int N> __device__ __forceinline__ void acquire_n() {
  static_assert(F % NSTAGE + N <= NSTAGE, "stages must not wrap");
  uint32_t spin = 0, ok;
  do {
    ok = 1;
#pragma unroll
    for (int i = 0; i < N; i++)
      asm volatile("{\n.reg .pred p;\nmbarrier.try_wait.parity.shared::cta.b64 p, [%1], %2;\nselp.u32 %0, %0, 0, p;\n}"
                   : "+r"(ok) : "r"(SM_BASE + SM_FULL + (F % NSTAGE + i) * 8), "r"((F / NSTAGE) & 1) : "memory");
  } while (!ok && ++spin < SPIN_LIMIT);
}
#define RELEASE(f0, f1) do { if (lane == 0) { _Pragma("unroll") for (int f_ = (f0); f_ <= (f1); f_++) mbar_arrive(SM_BASE + SM_EMPTY + (f_ % NSTAGE) * 8); } } while (0)
#define LO(f) (p.ring[(f) / NSTAGE] + ((f) % NSTAGE) * 1024)
#define HI(f) (p.ring[(f) / NSTAGE] + ((f) % NSTAGE) * 1024 + 512)

__device__ __forceinline__ void publish(uint4* dst, uint32_t (&a)[16], uint32_t tag) {
#pragma unroll
  for (int s = 0; s < 4; s++) {
    a[4 * s] = (a[4 * s] & ~1u) | tag;
    st_vec(dst + s * 128, a[4 * s], a[4 * s + 1], a[4 * s + 2], a[4 * s + 3]);
  }
}
__device__ __forceinline__ void fetch(const uint4* src, uint32_t (&a)[16]) {
#pragma unroll
  for (int s = 0; s < 4; s++) ld_vec(src + s * 128, a[4 * s], a[4 * s + 1], a[4 * s + 2], a[4 * s + 3]);
}
__device__ __forceinline__ uint32_t miss(const uint32_t (&a)[16], uint32_t tag) {
  return (a[0] ^ tag) | (a[4] ^ tag) | (a[8] ^ tag) | (a[12] ^ tag);
}
__device__ __forceinline__ bool stale(uint32_t v) { return __any_sync(0xffffffffu, here(v) & 1u); }
__device__ __forceinline__ void confirm(const uint4* src, uint32_t (&a)[16], uint32_t tag) {
  uint32_t spin = 0;
  while (__builtin_expect(stale(miss(a, tag)), 0) && ++spin < SPIN_LIMIT) fetch(src, a);
}
__device__ __forceinline__ void gather(uint32_t (&A)[4][16], uint32_t off, uint32_t tag) {
  const uint4* p1 = &g_x[0][0] + (off ^ (1 * X_SIZE));
  const uint4* p2 = &g_x[0][0] + (off ^ (2 * X_SIZE));
  const uint4* p3 = &g_x[0][0] + (off ^ (3 * X_SIZE));
  uint32_t spin = 0;
  do {
    fetch(p1, A[1]); fetch(p2, A[2]); fetch(p3, A[3]);
  } while (stale(miss(A[1], tag) | miss(A[2], tag) | miss(A[3], tag)) && ++spin < SPIN_LIMIT);
}
__device__ __forceinline__ void pack_acc(const float (&d)[32], uint32_t (&a)[16]) {
#pragma unroll
  for (int i = 0; i < 16; i++) a[i] = pack2(d[2 * i], d[2 * i + 1]);
}
__device__ __forceinline__ void res_store(uint32_t slot, const uint32_t (&a)[16]) {
#pragma unroll
  for (int s = 0; s < 4; s++) sts128(slot + s * 512, a[4 * s], a[4 * s + 1], a[4 * s + 2], a[4 * s + 3]);
}
__device__ __forceinline__ void res_load(uint32_t slot, float (&d)[32]) {
  uint32_t a[16];
#pragma unroll
  for (int s = 0; s < 4; s++) lds128(slot + s * 512, a[4 * s], a[4 * s + 1], a[4 * s + 2], a[4 * s + 3]);
#pragma unroll
  for (int i = 0; i < 16; i++) { d[2 * i] = bf_lo(a[i]); d[2 * i + 1] = bf_hi(a[i]); }
  pin(d);
}
__device__ __forceinline__ void tile_store(uint32_t maddr, const uint32_t (&a)[16]) {
#pragma unroll
  for (int s = 0; s < 4; s++) stsm4(maddr ^ (s << 5), &a[4 * s]);
}
__device__ __forceinline__ void tile_load(uint32_t maddr, uint32_t (&a)[16]) {
#pragma unroll
  for (int s = 0; s < 4; s++) ldsm4(maddr ^ (s << 5), &a[4 * s]);
}

struct RowAcc { float s[4], u[4], v[4]; };
__device__ __forceinline__ void row_acc(RowAcc& t, const uint32_t (&a)[16]) {
#pragma unroll
  for (int s = 0; s < 8; s++) {
    if ((s & 1) == 0) hmma(t.s, &a[2 * s], 0x3F803F80u, 0x3F803F80u);
    hmma8(t.u, &a[2 * s], a[2 * s]);
    hmma8(t.v, &a[2 * s], a[2 * s + 1]);
  }
}
__device__ __forceinline__ void stat_publish(const uint32_t (&a)[16], uint32_t b, uint32_t th, uint32_t tag) {
  RowAcc t = {};
  row_acc(t, a);
  const bool odd = th & 4;
  if ((th & 3) == ((th >> 3) & 3))
    st_vec(&g_x[b][X_ST + (th >> 2)], (__float_as_uint(t.s[0]) & ~1u) | tag, __float_as_uint(odd ? t.u[1] : t.u[0]),
           __float_as_uint(t.s[2]), __float_as_uint(odd ? t.v[3] : t.v[2]));
}
struct RowNorm { float m0, rs0, m1, rs1; };
__device__ __forceinline__ RowNorm row_norm(float s0, float q0, float s1, float q1, float scale) {
  RowNorm n;
  n.m0 = s0 * (1.f / DM); n.m1 = s1 * (1.f / DM);
  n.rs0 = scale * rsqrtf(fmaxf(fmaf(-n.m0, n.m0, q0 * (1.f / DM)), 0.f) + LN_EPS);
  n.rs1 = scale * rsqrtf(fmaxf(fmaf(-n.m1, n.m1, q1 * (1.f / DM)), 0.f) + LN_EPS);
  return n;
}
__device__ __forceinline__ RowNorm stat_gather(uint32_t b, uint32_t th, uint32_t tag, float scale) {
  const uint4* src = &g_x[b & ~3u][X_ST + (th >> 2)];
  uint32_t v[16], spin = 0;
  do {
#pragma unroll
    for (int j = 0; j < 4; j++) ld_vec(src + j * X_SIZE, v[4 * j], v[4 * j + 1], v[4 * j + 2], v[4 * j + 3]);
  } while (stale(miss(v, tag)) && ++spin < SPIN_LIMIT);
  float f[4];
#pragma unroll
  for (int i = 0; i < 4; i++)
    f[i] = (__uint_as_float(v[i]) + __uint_as_float(v[4 + i])) + (__uint_as_float(v[8 + i]) + __uint_as_float(v[12 + i]));
  return row_norm(f[0], f[1], f[2], f[3], scale);
}
__device__ __forceinline__ void mean_frag(uint32_t (&mu)[4], const RowNorm& n, bool sel) {
  const float a = sel ? -n.m0 : 0.f, c = sel ? -n.m1 : 0.f;
  mu[0] = pack2(a, a); mu[1] = pack2(c, c);
  const float al = a - bf_lo(mu[0]), cl = c - bf_lo(mu[1]);
  mu[2] = pack2(al, al); mu[3] = pack2(cl, cl);
  pin(mu);
}
__device__ __forceinline__ void scale_pack(const float (&d)[32], uint32_t (&a)[16], float rs0, float rs1) {
#pragma unroll
  for (int i = 0; i < 16; i++) { const float rs = (i & 1) ? rs1 : rs0; a[i] = pack2(d[2 * i] * rs, d[2 * i + 1] * rs); }
}
template <int I0, int I1> __device__ __forceinline__ void silu_part(const float (&d)[32], uint32_t (&h)[16], float rs0, float rs1) {
#pragma unroll
  for (int i = I0; i < I1; i++) {
    const float rs = (i & 1) ? rs1 : rs0, a = d[2 * i] * rs, b = d[2 * i + 1] * rs;
    h[i] = pack2(fmaf(a, tanh_hw(a), a), fmaf(b, tanh_hw(b), b));
  }
}
template <int F, int N> __device__ __forceinline__ void send_residual(uint32_t (&a)[16], uint32_t xoff, uint32_t res, uint32_t tag) {
  const uint32_t exact[4] = {a[0], a[4], a[8], a[12]};
  publish(&g_x[0][X_AG0] + xoff, a, tag);
  acquire_n<F, N>();
  stat_publish(a, blockIdx.x, xoff & 127, tag);
  res_store(res, a);
#pragma unroll
  for (int s = 0; s < 4; s++) sts32(res + s * 512, exact[s]);
  pin(a);
}
template <int F, int NEXT> __device__ __forceinline__ void proj_residual(uint32_t (&A)[4][16], const Params& p, uint32_t xoff, uint32_t res,
                                                               uint32_t r, uint32_t tag, int lane) {
  float acc[32];
  publish(&g_x[0][X_AG1] + xoff, A[0], tag);
  acquire_n<F, 2>();
  res_load(res, acc);
  const uint32_t flip = (r & 1) * 512;
  mma_tile<false>(acc, A[0], flip + LO(F));
  gather(A, xoff + X_AG1, tag);
  PROF_MARK(F == F_WO ? 11 : 16);
  mma_tile<false>(acc, A[1], HI(F) - flip);
  mma_tile<false>(acc, A[2], flip + LO(F + 1));
  mma_tile<false>(acc, A[3], HI(F + 1) - flip);
  WG_WAIT(0); pin(acc);
  pack_acc(acc, A[0]);
  send_residual<F + 2, NEXT>(A[0], xoff, res, tag);
}

__device__ __forceinline__ uint32_t fill_entry(int f, int r, int bh) {
  int m, x = r, y, z = 0;
  if (f < F_QKV || f >= 48) {
    const int i = f & 15;
    m = f < F_QKV ? M_FF1A : M_FF2A;
    if (i < 8) {
      const int h = i < 2 ? i : (i >= 5), c = i < 2 ? 0 : i - 1 - 3 * h;
      x = 0; y = r ^ c; z = 4 * r + 2 * h;
    } else {
      m++; x = r ^ (((i >> 1) - 3) & 3); y = 4 * r + 2 * (i & 1);
    }
  } else if (f < F_KV) {
    const int i = f - F_QKV;
    if (i == 1 || i >= 5) { m = M_WQ; y = (r & 2) ^ (i == 1 ? 0 : 2); }
    else { m = M_WKV; y = r ^ (i ? i - 1 : 0); z = 1; }
  } else if (f < F_WO) {
    const int i = f - F_KV;
    m = M_KV; x = 0; y = bh * 32 + (i & 2) * 8 + (i >> 2) * 4 + (i & 1) * 2;
  } else if (f >= F_PW1 && f < F_PW2) {
    m = M_PW1; y = r ^ (f - F_PW1);
  } else {
    m = f < F_PW1 ? M_WO : M_PW2; y = (r & 2) ^ ((f & 1) * 2);
  }
  return m | (x << 4) | (y << 8) | (z << 16);
}
__device__ __forceinline__ void l2_prefetch(const void* p, uint32_t total, int b) {
  const uint32_t part = total / NCTA;
  asm volatile("cp.async.bulk.prefetch.L2.global [%0], %1;" :: "l"((const char*)p + (size_t)b * part), "r"(part) : "memory");
}

__global__ void __launch_bounds__(384, 1) conformer_kernel(const __grid_constant__ Params p) {
  extern __shared__ __align__(1024) uint8_t smem[];
  const int tid = threadIdx.x, lane = tid & 31;
  const int cw = __shfl_sync(0xffffffffu, tid >> 5, 0), wg = cw >> 2, w = cw & 3;
  const int b = blockIdx.x, r = b & 3, batch = b >> 6, t = (b >> 2) & 15;
  if ((uint32_t)__cvta_generic_to_shared(smem) != SM_BASE) return;
  PROF_MARK(0);
  PROF_TIME(30);

  if (cw == 8) {
    asm volatile("{\n.reg .pred p;\nelect.sync _|p, 0xffffffff;\n"
                 "@p prefetch.tensormap [%5];\n"
                 "@p mbarrier.init.shared::cta.b64 [%1], 1;\n"
                 "@p fence.proxy.async.shared::cta;\n"
                 "@p mbarrier.arrive.expect_tx.shared::cta.b64 _, [%1], 32768;\n"
                 "@p cp.async.bulk.tensor.4d.shared::cluster.global.mbarrier::complete_tx::bytes [%0], [%2, {0, %3, 0, %4}], [%1];\n}"
                 :: "r"(SM_BASE + SM_STG), "r"(SM_BASE + SM_XBAR), "l"(&p.map[M_X]), "r"(t * 64), "r"(batch), "l"(&p.map[M_FF1A]) : "memory");
    if (lane == 0) {
#pragma unroll
      for (int i = 0; i < NSTAGE; i++) { mbar_init(SM_BASE + SM_FULL + i * 8, 1); mbar_init(SM_BASE + SM_EMPTY + i * 8, 4); }
      fence_async_smem();
    }
    __syncwarp();
    bar_arrive(0, 288);
  } else if (wg < 2) {
    if (tid < 144) sts128(SM_BASE + SM_CS + tid * 16, 0, 0, 0, 0);
    if (tid >= 160) {
      const int i = tid - 160;
      sts32(SM_BASE + SM_EYE + i * 4, ((i & 32) == 0 && (i & 3) == ((i >> 3) & 3)) ? (0x3F00u << ((i & 4) * 4)) : 0u);
    }
    fence_async_smem();
    bar_sync(0, 288);
  }

  if (wg == 2) {
    asm volatile("setmaxnreg.dec.sync.aligned.u32 40;");
    if (w == 0) {
      const uint32_t* flag = &g_flag[batch * 4 + r][lane];
      uint32_t ready = 0, entry = 0, st = 0, parity = 1;
      const uint32_t prev = ((volatile uint32_t*)g_epoch)[b];
#pragma unroll 1
      for (int f = 0; f < F_TOTAL; f++) {
        if ((f & 31) == 0) entry = fill_entry(f + lane, r, batch * 4 + r);
        const uint32_t e = __shfl_sync(0xffffffffu, entry, f & 31);
        if ((e & 15) == M_KV) {
          const uint32_t need = 3u << ((e >> 8) & 31);
          uint32_t spin = 0;
#pragma unroll 1
          while ((ready & need) != need && ++spin < SPIN_LIMIT) {
            uint32_t v;
            asm volatile("ld.relaxed.gpu.global.u32 %0, [%1];" : "=r"(v) : "l"(flag) : "memory");
            ready = __ballot_sync(0xffffffffu, v - 1 == prev);
          }
        }
        mbar_wait(SM_BASE + SM_EMPTY + st * 8, parity);
        asm volatile("{\n.reg .pred p;\nelect.sync _|p, 0xffffffff;\n"
                     "@p mbarrier.arrive.expect_tx.shared::cta.b64 _, [%1], 16384;\n"
                     "@p cp.async.bulk.tensor.3d.shared::cluster.global.mbarrier::complete_tx::bytes [%0], [%2, {%3, %4, %5}], [%1];\n}"
                     :: "r"(SM_BASE + st * STAGE_BYTES), "r"(SM_BASE + SM_FULL + st * 8), "l"(&p.map[e & 15]),
                        "r"((e << 2) & 0x3C0), "r"((e >> 2) & 0x3FC0), "r"(e >> 16) : "memory");
        if (++st == NSTAGE) { st = 0; parity ^= 1; }
        if (f >= F_KV && f < F_WO) PROF_MARK(1 + f - F_KV);
      }
    } else if (w < 3) {
      const int kind = w - 1;
      const uint32_t epoch = ((volatile uint32_t*)g_epoch)[b] + 1;
      if (kind == 0) bar_sync(BAR_K, 160); else bar_sync(BAR_V, 160);
      if (lane == 0) {
        asm volatile("cp.async.bulk.global.shared::cta.bulk_group [%0], [%1], %2;"
                     :: "l"(&g_kv[batch * 4 + r][kind][t][0]), "r"(SM_BASE + SM_STG + kind * TILE_BYTES), "r"(TILE_BYTES) : "memory");
        asm volatile("cp.async.bulk.commit_group;\ncp.async.bulk.wait_group 0;" ::: "memory");
        asm volatile("st.relaxed.gpu.global.u32 [%0], %1;" :: "l"(&g_flag[batch * 4 + r][kind * 16 + t]), "r"(epoch) : "memory");
      }
    } else {
      if (lane < M_COUNT) asm volatile("prefetch.tensormap [%0];" :: "l"(&p.map[lane]) : "memory");
      if (lane == 0) {
        l2_prefetch(p.w_ff1b, 1024 * 256 * 2, b);
        l2_prefetch(p.w_o, 256 * 256 * 2, b);
        l2_prefetch(p.w_pw2, 256 * 256 * 2, b);
        l2_prefetch(p.w_ff2b, 1024 * 256 * 2, b);
      }
    }
  } else {
    asm volatile("setmaxnreg.inc.sync.aligned.u32 232;");
    const int q = lane & 3, th = tid & 127;
    constexpr uint32_t stg = SM_BASE + SM_STG;
    const uint32_t mrow = 16 * w + (lane & 15);
    const uint32_t maddr = stg + mrow * 128 + (((lane >> 4) ^ (lane & 7)) << 4);
    const uint32_t res = stg + 3 * TILE_BYTES + w * 2048 + lane * 16;
    const uint32_t xoff = b * X_SIZE + th;
    const int nvalid = T_SEQ - t * 64;

    uint32_t A[4][16];
    uint32_t mu[4] = {0u, 0u, 0u, 0u};
    float rs0, rs1;
    if (wg == 0) {
      mbar_wait(SM_BASE + SM_XBAR, 0);
      PROF_MARK(1);
      RowAcc ra = {}, rb = {};
#pragma unroll
      for (int c = 0; c < 4; c++) {
        tile_load(maddr + (r ^ c) * TILE_BYTES, A[c]);
        row_acc((c & 1) ? rb : ra, A[c]);
      }
      __syncwarp();
      res_store(res, A[0]);
      const float s0 = ra.s[0] + rb.s[0], s1 = ra.s[2] + rb.s[2];
      const uint32_t m0 = pack2(s0 * (1.f / DM), s0 * (1.f / DM)), m1 = pack2(s1 * (1.f / DM), s1 * (1.f / DM));
#pragma unroll
      for (int c = 0; c < 4; c++) {
#pragma unroll
        for (int i = 0; i < 16; i++) asm("sub.rn.bf16x2 %0, %0, %1;" : "+r"(A[c][i]) : "r"((i & 1) ? m1 : m0));
        pin(A[c]);
      }
      const bool odd = lane & 4;
      const int src = (lane & 28) | (lane >> 3);
      const float q0 = __shfl_sync(0xffffffffu, odd ? ra.u[1] + rb.u[1] : ra.u[0] + rb.u[0], src);
      const float q1 = __shfl_sync(0xffffffffu, odd ? ra.v[3] + rb.v[3] : ra.v[2] + rb.v[2], src);
      const RowNorm n = row_norm(s0, q0, s1, q1, 0.5f);
      rs0 = n.rs0; rs1 = n.rs1;
    } else {
      const uint32_t epoch = ((volatile uint32_t*)g_epoch)[b] + 1, tag = epoch & 1;
#pragma unroll 1
      for (int i = 0; i < X_CLEAR; i += 128) st_vec(&g_x[0][i] + xoff, 0u, 0u, 0u, 0u);
      if (b < 72) {
        const __nv_bfloat16* wp; int ld, col;
        if (b < 24) { wp = p.w_qkv; ld = 768; col = b * 32; }
        else if (b < 40) { wp = p.w_pw1; ld = 512; col = (b - 24) * 32; }
        else { wp = p.w_ff2a; ld = 1024; col = (b - 40) * 32; }
        const uint4* src = (const uint4*)(wp + (size_t)(th >> 2) * ld + col + q * 8);
        float c[8] = {0.f, 0.f, 0.f, 0.f, 0.f, 0.f, 0.f, 0.f};
#pragma unroll 1
        for (int h = 0; h < 2; h++) {
#pragma unroll
          for (int i = 0; i < 4; i++) {
            const uint4 v = __ldg(src + i * 4 * ld);
            c[0] += bf_lo(v.x); c[1] += bf_hi(v.x); c[2] += bf_lo(v.y); c[3] += bf_hi(v.y);
            c[4] += bf_lo(v.z); c[5] += bf_hi(v.z); c[6] += bf_lo(v.w); c[7] += bf_hi(v.w);
          }
          src += 16 * ld;
        }
#pragma unroll 1
        for (int m = 4; m <= 16; m <<= 1)
#pragma unroll
          for (int k = 0; k < 8; k++) c[k] += __shfl_xor_sync(0xffffffffu, c[k], m);
        if (lane < 4) {
          const uint32_t a = SM_BASE + SM_CS + 1792 + w * 128 + lane * 32;
          sts128(a, __float_as_uint(c[0]), __float_as_uint(c[1]), __float_as_uint(c[2]), __float_as_uint(c[3]));
          sts128(a + 16, __float_as_uint(c[4]), __float_as_uint(c[5]), __float_as_uint(c[6]), __float_as_uint(c[7]));
        }
        bar_sync(BAR_WG1, 128);
        if (th < 8) {
          float o[4] = {0.f, 0.f, 0.f, 0.f};
#pragma unroll 1
          for (int k = 0; k < 4; k++) {
            uint32_t e[4];
            lds128(SM_BASE + SM_CS + 1792 + k * 128 + th * 16, e[0], e[1], e[2], e[3]);
#pragma unroll
            for (int i = 0; i < 4; i++) o[i] += __uint_as_float(e[i]);
          }
          st_vec(&g_cs[b * 8 + th], (__float_as_uint(o[0]) & ~1u) | tag, __float_as_uint(o[1]), __float_as_uint(o[2]), __float_as_uint(o[3]));
        }
      }
      __threadfence();
      bar_sync(BAR_WG1, 128);
      if (th == 0) {
        asm volatile("st.relaxed.gpu.global.u32 [%0], %1;" :: "l"(&g_ready[b]), "r"(epoch) : "memory");
        uint32_t e[4], spin = 0;
#pragma unroll 1
        do {
          ld_vec((const uint4*)&g_ready[b & ~3], e[0], e[1], e[2], e[3]);
        } while ((e[0] != epoch || e[1] != epoch || e[2] != epoch || e[3] != epoch) && ++spin < SPIN_LIMIT);
        __threadfence();
      }
      __syncwarp();
      bar_arrive(BAR_RDY, 256);
#pragma unroll 1
      for (int i = th; i < 144; i += 128) {
        const int j = i >> 4;
        int src;
        if (j < CS_PW1) src = 320 + 64 * r + i;
        else if (j < CS_QKV) src = 192 + (j - CS_PW1) * 64 + 16 * r + (i & 15);
        else src = ((j - CS_QKV + 1) % 3) * 64 + 16 * r + (i & 15);
        uint32_t e[4], spin = 0;
#pragma unroll 1
        do {
          ld_vec(&g_cs[src], e[0], e[1], e[2], e[3]);
        } while (((e[0] ^ tag) & 1u) && ++spin < SPIN_LIMIT);
        const float c0 = __uint_as_float(e[0] & ~1u), c1 = __uint_as_float(e[1]), c2 = __uint_as_float(e[2]), c3 = __uint_as_float(e[3]);
        const uint32_t h0 = pack2(c0, c1), h1 = pack2(c2, c3);
        const uint32_t a = SM_BASE + SM_CS + j * 256 + (i & 15) * 8;
        sts64(a ^ ((a >> 3) & 0x70), h0, h1);
        sts64((a + 128) ^ (((a + 128) >> 3) & 0x70), pack2(c0 - bf_lo(h0), c1 - bf_hi(h0)), pack2(c2 - bf_lo(h1), c3 - bf_hi(h1)));
      }
      fence_async_smem();
      bar_arrive(BAR_CS, 256);
    }

#pragma unroll 1
    for (uint32_t pass = 0; pass < 2; pass++) {
      uint32_t Q[16];
      if (wg == 0) {
        float acc[4][32];
        uint32_t H[4][16];
        ACQUIRE(0);
        mma_tile<true>(acc[0], A[0], LO(0)); mma_tile<true>(acc[1], A[0], HI(0));
        ACQUIRE(1);
        mma_tile<true>(acc[2], A[0], LO(1)); mma_tile<true>(acc[3], A[0], HI(1));
        acquire_n<2, 3>();
        if (pass) gather(A, here(xoff) + X_AG0, 1);
        PROF_MARK(2 + pass * 16);
        mma_tile<false>(acc[0], A[1], LO(2)); mma_tile<false>(acc[0], A[2], LO(3));
        WG_WAIT(2);
        if (pass) {
          RELEASE(F_PW2, F_PW2 + 1);
          const RowNorm n = stat_gather(b, here(th), 1, 0.5f);
          rs0 = n.rs0; rs1 = n.rs1;
          mean_frag(mu, n, q == 0);
        }
        RELEASE(0, 1);
        mma_tile_fold<2 * CS_FF2>(acc[0], A[3], LO(4), mu);
        acquire_n<5, 3>();
        mma_tile<false>(acc[1], A[1], HI(2)); mma_tile<false>(acc[1], A[2], HI(3));
        WG_WAIT(2); pin(acc[0]);
        silu_part<0, 8>(acc[0], H[0], rs0, rs1);
        mma_tile_fold<2 * CS_FF2 + 2>(acc[1], A[3], HI(4), mu);
        silu_part<8, 16>(acc[0], H[0], rs0, rs1);
        mma_tile<false>(acc[2], A[1], LO(5)); mma_tile<false>(acc[2], A[2], LO(6));
        WG_WAIT(2); pin(acc[1]);
        RELEASE(2, 4);
        silu_part<0, 8>(acc[1], H[1], rs0, rs1);
        mma_tile_fold<2 * CS_FF2 + 4>(acc[2], A[3], LO(7), mu);
        silu_part<8, 16>(acc[1], H[1], rs0, rs1);
        mma_tile<false>(acc[3], A[1], HI(5)); mma_tile<false>(acc[3], A[2], HI(6));
        WG_WAIT(2); pin(acc[2]);
        silu_part<0, 8>(acc[2], H[2], rs0, rs1);
        mma_tile_fold<2 * CS_FF2 + 6>(acc[3], A[3], HI(7), mu);
        silu_part<8, 16>(acc[2], H[2], rs0, rs1);
        pin(H[0]); pin(H[1]); pin(H[2]);
        acquire_n<8, 2>();
        mma_tile<true>(acc[0], H[0], LO(8)); mma_tile<false>(acc[0], H[1], HI(8));
        WG_WAIT(2); pin(acc[3]);
        RELEASE(5, 7);
        silu_part<0, 8>(acc[3], H[3], rs0, rs1);
        mma_tile<false>(acc[0], H[2], LO(9));
        silu_part<8, 16>(acc[3], H[3], rs0, rs1);
        pin(H[3]);
        mma_tile<false>(acc[0], H[3], HI(9));
        PROF_MARK(3 + pass * 16);
        const uint32_t rtag = pass ^ 1;
        const uint4* rs_in = &g_x[0][X_RS] + here(xoff);
#pragma unroll
        for (int c = 1; c < 4; c++) {
          ACQUIRE(8 + 2 * c);
          mma_tile<true>(acc[c], H[0], LO(8 + 2 * c));
          if (c == 1 && !pass) bar_sync(BAR_RDY, 256);
          if (c == 3) fetch(rs_in, A[1]);
          mma_tile<false>(acc[c], H[1], HI(8 + 2 * c));
          WG_WAIT(2); pin(acc[c - 1]);
          uint32_t o[16];
          pack_acc(acc[c - 1], o);
          publish(&g_x[0][X_RS + (c - 1) * 512] + (here(xoff) ^ (c * X_SIZE)), o, rtag);
          ACQUIRE(9 + 2 * c);
          mma_tile<false>(acc[c], H[2], LO(9 + 2 * c));
          if (c == 1) RELEASE(8, 9);
          if (c == 2) res_load(res, acc[0]);
          mma_tile<false>(acc[c], H[3], HI(9 + 2 * c));
        }
        fetch(rs_in + 512, A[2]);
        confirm(rs_in, A[1], rtag);
        mma_add_half(acc[0], A[1]);
        WG_WAIT(1);
        fetch(rs_in + 1024, A[3]);
        confirm(rs_in + 512, A[2], rtag);
        mma_add_half(acc[0], A[2]);
        confirm(rs_in + 1024, A[3], rtag);
        mma_add_half(acc[0], A[3]);
        PROF_MARK(4 + pass * 16);
        WG_WAIT(0); pin(acc[0]); pin(acc[3]);
#pragma unroll
        for (int i = 0; i < 16; i++) A[0][i] = pack2(fmaf(acc[3][2 * i], 0.5f, acc[0][2 * i]), fmaf(acc[3][2 * i + 1], 0.5f, acc[0][2 * i + 1]));
        if (pass) {
          PROF_MARK(21);
          stat_publish(A[0], b, here(th), 0);
          const RowNorm fn = stat_gather(b, here(th), 0, 1.f);
          const float nm0 = -fn.m0 * fn.rs0, nm1 = -fn.m1 * fn.rs1;
#pragma unroll
          for (int i = 0; i < 16; i++) {
            const float rs = (i & 1) ? fn.rs1 : fn.rs0, nm = (i & 1) ? nm1 : nm0;
            A[0][i] = pack2(fmaf(bf_lo(A[0][i]), rs, nm), fmaf(bf_hi(A[0][i]), rs, nm));
          }
          tile_store(here(maddr), A[0]);
          __syncwarp();
          const int row = 16 * w + (lane >> 3);
          uint4* dst = (uint4*)(p.out + ((size_t)batch * T_SEQ + t * 64 + row) * DM + 64 * r) + (lane & 7);
          const uint32_t src = stg + row * 128 + (((lane & 7) ^ (lane >> 3)) << 4);
#pragma unroll
          for (int i = 0; i < 4; i++) {
            uint4 v;
            lds128((src ^ ((i & 1) << 6)) + i * 512, v.x, v.y, v.z, v.w);
            if (row + 4 * i < nvalid) dst[i * 4 * (DM / 8)] = v;
          }
          PROF_MARK(22);
          PROF_TIME(31);
          break;
        }
        send_residual<F_QKV, 6>(A[0], here(xoff), res, 1);
        PROF_MARK(5);
        const uint32_t flip = (r & 1) * 512;
        mma_tile<true>(acc[0], A[0], LO(F_QKV)); mma_tile<true>(acc[1], A[0], HI(F_QKV));
        mma_tile<true>(acc[2], A[0], flip + LO(F_QKV + 1));
        bar_sync(BAR_CS, 256);
        gather(A, here(xoff) + X_AG0, 1);
        PROF_MARK(6);
        mma_tile<false>(acc[0], A[1], LO(F_QKV + 2)); mma_tile<false>(acc[0], A[2], LO(F_QKV + 3));
        RELEASE(10, 15);
        {
          const RowNorm n = stat_gather(b, here(th), 1, 1.f);
          rs0 = n.rs0; rs1 = n.rs1;
          mean_frag(mu, n, q == 3);
        }
        mma_tile_fold<2 * CS_QKV - 6>(acc[0], A[3], LO(F_QKV + 4), mu);
        mma_tile<false>(acc[1], A[1], HI(F_QKV + 2)); mma_tile<false>(acc[1], A[2], HI(F_QKV + 3));
        WG_WAIT(2); pin(acc[0]);
        scale_pack(acc[0], Q, rs0, rs1);
        tile_store(here(maddr), Q);
        fence_async_smem();
        bar_arrive(BAR_K, 160);
        mma_tile_fold<2 * CS_QKV - 4>(acc[1], A[3], HI(F_QKV + 4), mu);
        mma_tile<false>(acc[2], A[1], HI(F_QKV + 1) - flip); mma_tile<false>(acc[2], A[2], flip + LO(F_QKV + 5));
        WG_WAIT(2); pin(acc[1]);
        scale_pack(acc[1], Q, rs0, rs1);
        tile_store(here(maddr) + TILE_BYTES, Q);
        fence_async_smem();
        bar_arrive(BAR_V, 160);
        mma_tile_fold<2 * CS_QKV - 2>(acc[2], A[3], HI(F_QKV + 5) - flip, mu);
        WG_WAIT(0); pin(acc[2]);
        scale_pack(acc[2], Q, rs0, rs1);
        res_store(here(res) - TILE_BYTES, Q);
        bar_arrive(BAR_Q, 256);
        acquire_n<F_SPARE, 2>();
        RELEASE(F_QKV, F_SPARE + 1);
      } else {
        bar_arrive(BAR_TURN0, 256);
        bar_sync(BAR_Q, 256);
#pragma unroll
        for (int s = 0; s < 4; s++) lds128(res - TILE_BYTES + s * 512, Q[4 * s], Q[4 * s + 1], Q[4 * s + 2], Q[4 * s + 3]);
      }
      PROF_MARK(7);

      float O[32];
      float m0 = -INFINITY, m1 = -INFINITY, l0 = 0.f, l1 = 0.f;
      {
        uint32_t P[2][16];
#pragma unroll
        for (int i = 0; i < 32; i++) O[i] = 0.f;
#pragma unroll
        for (int i = 0; i < 16; i++) { P[0][i] = 0u; P[1][i] = 0u; }
        pin(Q);
        uint32_t sk = wg, sv = wg;
#pragma unroll 1
        for (int it = 0; it < 4; it++) {
          float S[2][32];
          pin(P[0]); pin(P[1]); pin(O);
          mbar_wait(SM_BASE + SM_FULL + sk * 8, it == 3);
          if (wg == 0) bar_sync(BAR_TURN0, 256); else bar_sync(BAR_TURN1, 256);
          if (it == 0) PROF_MARK(8);
          const uint64_t dk = p.ring[2] + sk * 1024, dv = p.ring[2] + sv * 1024;
          WG_FENCE();
#pragma unroll
          for (int h = 0; h < 2; h++)
#pragma unroll
            for (int s = 0; s < 4; s++) {
              if (s == 0) wgmma64_set<0>(S[h], &Q[0], dk + h * 512); else wgmma64_acc<0>(S[h], &Q[4 * s], dk + h * 512 + s * 2);
            }
          WG_COMMIT();
          mma_tile<false>(O, P[0], dv);
          mma_tile<false>(O, P[1], dv + 512);
          if (wg == 0) bar_arrive(BAR_TURN1, 256); else if (it < 3) bar_arrive(BAR_TURN0, 256);
          WG_WAIT(2); pin(S[0]); pin(S[1]);
          if (wg == 1) PROF_MARK(16 + it * 2);
          if (it == 3 && wg == 1) {
#pragma unroll
            for (int i = 20; i < 32; i++) S[1][i] = -INFINITY;
          }
          float n0 = m0, n1 = m1;
#pragma unroll
          for (int h = 0; h < 2; h++)
#pragma unroll
            for (int j = 0; j < 8; j++) {
              n0 = fmaxf(n0, fmaxf(S[h][4 * j], S[h][4 * j + 1]));
              n1 = fmaxf(n1, fmaxf(S[h][4 * j + 2], S[h][4 * j + 3]));
            }
          n0 = fmaxf(n0, __shfl_xor_sync(0xffffffffu, n0, 1)); n1 = fmaxf(n1, __shfl_xor_sync(0xffffffffu, n1, 1));
          n0 = fmaxf(n0, __shfl_xor_sync(0xffffffffu, n0, 2)); n1 = fmaxf(n1, __shfl_xor_sync(0xffffffffu, n1, 2));
          const float a0 = ex2_hw((m0 - n0) * SM_SCALE_LOG2), a1 = ex2_hw((m1 - n1) * SM_SCALE_LOG2);
          m0 = n0; m1 = n1;
          const float c0 = -n0 * SM_SCALE_LOG2, c1 = -n1 * SM_SCALE_LOG2;
          l0 *= a0; l1 *= a1;
#pragma unroll
          for (int j = 0; j < 8; j++) {
            S[0][4 * j] = ex2_hw(fmaf(S[0][4 * j], SM_SCALE_LOG2, c0)); S[0][4 * j + 1] = ex2_hw(fmaf(S[0][4 * j + 1], SM_SCALE_LOG2, c0));
            S[0][4 * j + 2] = ex2_hw(fmaf(S[0][4 * j + 2], SM_SCALE_LOG2, c1)); S[0][4 * j + 3] = ex2_hw(fmaf(S[0][4 * j + 3], SM_SCALE_LOG2, c1));
            l0 += S[0][4 * j] + S[0][4 * j + 1]; l1 += S[0][4 * j + 2] + S[0][4 * j + 3];
          }
          pin(S[0]);
          mbar_wait(SM_BASE + SM_FULL + (sk + 2) * 8, it == 3);
          WG_WAIT(0); pin(O); pin(P[0]); pin(P[1]);
          if (lane == 0 && it < 3) {
            mbar_arrive(SM_BASE + SM_EMPTY + sk * 8);
            if (it) mbar_arrive(SM_BASE + SM_EMPTY + sv * 8);
          }
#pragma unroll
          for (int j = 0; j < 8; j++) {
            const float p0 = ex2_hw(fmaf(S[1][4 * j], SM_SCALE_LOG2, c0)), p1 = ex2_hw(fmaf(S[1][4 * j + 1], SM_SCALE_LOG2, c0));
            const float p2 = ex2_hw(fmaf(S[1][4 * j + 2], SM_SCALE_LOG2, c1)), p3 = ex2_hw(fmaf(S[1][4 * j + 3], SM_SCALE_LOG2, c1));
            l0 += p0 + p1; l1 += p2 + p3;
            P[1][2 * j] = pack2(p0, p1); P[1][2 * j + 1] = pack2(p2, p3);
            O[4 * j] *= a0; O[4 * j + 1] *= a0; O[4 * j + 2] *= a1; O[4 * j + 3] *= a1;
          }
          pack_acc(S[0], P[0]);
          sv = sk + 2;
          sk = it == 2 ? wg : sk + 4;
          if (wg == 1) PROF_MARK(17 + it * 2);
        }
        pin(P[0]); pin(P[1]); pin(O);
        mma_tile<false>(O, P[0], p.ring[2] + sv * 1024);
        mma_tile<false>(O, P[1], p.ring[2] + sv * 1024 + 512);
        l0 += __shfl_xor_sync(0xffffffffu, l0, 1); l1 += __shfl_xor_sync(0xffffffffu, l1, 1);
        l0 += __shfl_xor_sync(0xffffffffu, l0, 2); l1 += __shfl_xor_sync(0xffffffffu, l1, 2);
        WG_WAIT(0); pin(O);
      }
      PROF_MARK(9);

      if (wg == 1) {
        const uint32_t mo = stg + here(th) * 16;
#pragma unroll
        for (int i = 0; i < 8; i++)
          sts128(mo + i * 2048, __float_as_uint(O[4 * i]), __float_as_uint(O[4 * i + 1]), __float_as_uint(O[4 * i + 2]), __float_as_uint(O[4 * i + 3]));
        sts128(mo + 8 * 2048, __float_as_uint(m0), __float_as_uint(m1), __float_as_uint(l0), __float_as_uint(l1));
        bar_arrive(BAR_MERGE, 256);
      } else {
        const uint32_t mo = stg + here(th) * 16;
        bar_sync(BAR_MERGE, 256);
        uint32_t e[4];
        lds128(mo + 8 * 2048, e[0], e[1], e[2], e[3]);
        const float n0 = fmaxf(m0, __uint_as_float(e[0])), n1 = fmaxf(m1, __uint_as_float(e[1]));
        float a0 = ex2_hw((m0 - n0) * SM_SCALE_LOG2), a1 = ex2_hw((m1 - n1) * SM_SCALE_LOG2);
        float b0 = ex2_hw((__uint_as_float(e[0]) - n0) * SM_SCALE_LOG2), b1 = ex2_hw((__uint_as_float(e[1]) - n1) * SM_SCALE_LOG2);
        const float i0 = rcp_hw(fmaf(a0, l0, b0 * __uint_as_float(e[2]))), i1 = rcp_hw(fmaf(a1, l1, b1 * __uint_as_float(e[3])));
        a0 *= i0; b0 *= i0; a1 *= i1; b1 *= i1;
#pragma unroll
        for (int i = 0; i < 8; i++) {
          lds128(mo + i * 2048, e[0], e[1], e[2], e[3]);
          A[0][2 * i] = pack2(fmaf(O[4 * i], a0, b0 * __uint_as_float(e[0])), fmaf(O[4 * i + 1], a0, b0 * __uint_as_float(e[1])));
          A[0][2 * i + 1] = pack2(fmaf(O[4 * i + 2], a1, b1 * __uint_as_float(e[2])), fmaf(O[4 * i + 3], a1, b1 * __uint_as_float(e[3])));
        }
        PROF_MARK(10);
        proj_residual<F_WO, 4>(A, p, here(xoff), res, r, 0, lane);
        PROF_MARK(12);
      }

      const int dir = cw == 0 ? -1 : 1;
      uint32_t tap[15];
      {
        const uint32_t* dwp = (const uint32_t*)(p.dw + 64 * r) + lane + 7 * (DM / 2);
#pragma unroll
        for (int k = 0; k < 15; k++) tap[k] = __ldg(dwp + dir * (k - 7) * (DM / 2));
      }

      if (wg == 0) {
        float acc[2][32];
        mma_tile<true>(acc[0], A[0], LO(F_PW1)); mma_tile<true>(acc[1], A[0], HI(F_PW1));
        gather(A, here(xoff) + X_AG0, 0);
        PROF_MARK(13);
        mma_tile<false>(acc[1], A[1], HI(F_PW1 + 1)); mma_tile<false>(acc[1], A[2], HI(F_PW1 + 2));
        RELEASE(F_KV + 10, F_WO + 1);
        {
          const RowNorm n = stat_gather(b, here(th), 0, 0.5f);
          const int row = 16 * w + (lane >> 2);
          rs0 = row < nvalid ? n.rs0 : 0.f; rs1 = row + 8 < nvalid ? n.rs1 : 0.f;
          mean_frag(mu, n, q == 0);
        }
        mma_tile_fold<2 * CS_PW1 + 2>(acc[1], A[3], HI(F_PW1 + 3), mu);
        mma_tile<false>(acc[0], A[1], LO(F_PW1 + 1)); mma_tile<false>(acc[0], A[2], LO(F_PW1 + 2));
        WG_WAIT(2); pin(acc[1]);
#pragma unroll
        for (int i = 0; i < 16; i++) acc[1][i] = tanh_hw(acc[1][i] * ((i & 2) ? rs1 : rs0));
        mma_tile_fold<2 * CS_PW1>(acc[0], A[3], LO(F_PW1 + 3), mu);
#pragma unroll
        for (int i = 16; i < 32; i++) acc[1][i] = tanh_hw(acc[1][i] * ((i & 2) ? rs1 : rs0));
#pragma unroll
        for (int i = 0; i < 32; i++) { const float rs = (i & 2) ? rs1 : rs0; acc[1][i] = fmaf(acc[1][i], rs, rs); }
        pin(acc[1]);
        WG_WAIT(0); pin(acc[0]);
#pragma unroll
        for (int i = 0; i < 16; i++) A[0][i] = pack2(acc[0][2 * i] * acc[1][2 * i], acc[0][2 * i + 1] * acc[1][2 * i + 1]);
        const uint32_t ga = stg + TILE_BYTES + here(mrow) * G_PITCH + (lane >> 4) * 16;
#pragma unroll
        for (int s = 0; s < 4; s++) stsm4(ga + s * 32, &A[0][4 * s]);
        RELEASE(F_PW1, F_PW1 + 3);
      }
      bar_sync(BAR_G, 256);
      PROF_MARK(14);

      {
        const int first = cw == 0 ? 14 : 8 * cw - 7;
        const uint32_t gsrc = stg + TILE_BYTES + first * G_PITCH + lane * 4;
        uint32_t in[22];
#pragma unroll
        for (int i = 0; i < 15; i++) in[i] = lds32(gsrc + dir * i * (int)G_PITCH);
        const bool edge = cw == 0 || cw == 7;
        const bool nbr = cw == 0 ? t > 0 : t < 15;
        if (edge) {
          if (nbr) {
            uint4* dst = &g_x[b + 4 * dir][X_HALO + (cw == 0 ? 96 : 0) + lane];
            st_vec(dst, HALO_TAG, in[14], in[13], in[12]);
            st_vec(dst + 32, HALO_TAG, in[11], in[10], in[9]);
            st_vec(dst + 64, HALO_TAG, in[8], 0u, 0u);
          }
        } else {
#pragma unroll
          for (int i = 15; i < 22; i++) in[i] = lds32(gsrc + i * G_PITCH);
        }
        float cl[8], ch[8], tl[15], tv[15];
#pragma unroll
        for (int k = 0; k < 15; k++) { tl[k] = bf_lo(tap[k]); tv[k] = bf_hi(tap[k]); }
#pragma unroll
        for (int o = 0; o < 8; o++) { cl[o] = 0.f; ch[o] = 0.f; }
#pragma unroll
        for (int i = 0; i < 15; i++) {
          const float lo = bf_lo(in[i]), hi = bf_hi(in[i]);
#pragma unroll
          for (int o = 0; o < 8; o++)
            if (i - o >= 0) { cl[o] = fmaf(lo, tl[i - o], cl[o]); ch[o] = fmaf(hi, tv[i - o], ch[o]); }
        }
        if (edge) {
#pragma unroll
          for (int i = 15; i < 22; i++) in[i] = 0u;
          if (nbr) {
            const uint4* src = &g_x[b][X_HALO + (cw == 0 ? 0 : 96) + lane];
            uint32_t e0, e1, e2, u0, u1, spin = 0;
#pragma unroll 1
            do {
              ld_vec(src, e0, in[15], in[16], in[17]);
              ld_vec(src + 32, e1, in[18], in[19], in[20]);
              ld_vec(src + 64, e2, in[21], u0, u1);
            } while (__any_sync(0xffffffffu, ((e0 ^ HALO_TAG) | (e1 ^ HALO_TAG) | (e2 ^ HALO_TAG)) != 0) && ++spin < SPIN_LIMIT);
          }
        }
#pragma unroll
        for (int i = 15; i < 22; i++) {
          const float lo = bf_lo(in[i]), hi = bf_hi(in[i]);
#pragma unroll
          for (int o = 0; o < 8; o++)
            if (i - o <= 14) { cl[o] = fmaf(lo, tl[i - o], cl[o]); ch[o] = fmaf(hi, tv[i - o], ch[o]); }
        }
        const uint32_t fl = cw == 0 ? 7 : 0;
        const uint32_t cdst = (stg + cw * 1024 + lane * 4) ^ (fl * 144);
#pragma unroll
        for (int o = 0; o < 8; o++) {
          const float a = 0.5f * cl[o], c = 0.5f * ch[o];
          sts32(cdst ^ (o * 144), pack2(fmaf(a, tanh_hw(a), a), fmaf(c, tanh_hw(c), c)));
        }
      }
      if (wg == 1) {
        bar_arrive(BAR_C, 256);
        if (th == 0) ((volatile uint32_t*)g_epoch)[b] += 1;
        break;
      }
      bar_sync(BAR_C, 256);
      tile_load(here(maddr), A[0]);
      PROF_MARK(15);
      proj_residual<F_PW2, 1>(A, p, here(xoff), res, r, 1, lane);
      PROF_MARK(17);
    }
  }
}

typedef CUresult (*EncodeFn)(CUtensorMap*, CUtensorMapDataType, cuuint32_t, void*, const cuuint64_t*, const cuuint64_t*,
                             const cuuint32_t*, const cuuint32_t*, CUtensorMapInterleave, CUtensorMapSwizzle,
                             CUtensorMapL2promotion, CUtensorMapFloatOOBfill);

void make_map(EncodeFn fn, CUtensorMap* m, const void* w, int rank, int d0, int d1, int d2, int d3, int s1, int s2, int s3,
              int b1, int b2, CUtensorMapSwizzle swz) {
  const cuuint64_t dims[4] = {(cuuint64_t)d0, (cuuint64_t)d1, (cuuint64_t)d2, (cuuint64_t)d3};
  const cuuint64_t strides[3] = {(cuuint64_t)s1, (cuuint64_t)s2, (cuuint64_t)s3};
  const cuuint32_t box[4] = {64, (cuuint32_t)b1, (cuuint32_t)b2, 1}, es[4] = {1, 1, 1, 1};
  fn(m, CU_TENSOR_MAP_DATA_TYPE_BFLOAT16, rank, const_cast<void*>(w), dims, strides, box, es, CU_TENSOR_MAP_INTERLEAVE_NONE,
     swz, CU_TENSOR_MAP_L2_PROMOTION_L2_128B, CU_TENSOR_MAP_FLOAT_OOB_FILL_NONE);
}

}

extern "C" void kernel_launch(void* const* d_in, const int* in_sizes, int n_in, void* d_out, int out_size) {
  static EncodeFn fn = nullptr;
  static void* kv = nullptr;
  if (!fn) {
    void* f = nullptr;
    cudaDriverEntryPointQueryResult st;
    cudaGetDriverEntryPoint("cuTensorMapEncodeTiled", &f, cudaEnableDefault, &st);
    fn = (EncodeFn)f;
    cudaGetSymbolAddress(&kv, g_kv);
    cudaFuncSetAttribute(conformer_kernel, cudaFuncAttributeMaxDynamicSharedMemorySize, SM_TOTAL);
  }
  typedef const __nv_bfloat16* W;
  const CUtensorMapSwizzle S = CU_TENSOR_MAP_SWIZZLE_128B;
  Params p;
  make_map(fn, &p.map[M_X], d_in[0], 4, 64, T_SEQ, 4, 2, 512, 128, T_SEQ * 512, 64, 4, S);
  make_map(fn, &p.map[M_FF1A], d_in[1], 3, 64, 256, 16, 1, 2048, 128, 0, 64, 2, S);
  make_map(fn, &p.map[M_FF1B], d_in[2], 3, 256, 1024, 1, 1, 512, 512 * 1024, 0, 128, 1, S);
  make_map(fn, &p.map[M_WKV], d_in[3], 3, 256, 256, 3, 1, 1536, 512, 0, 64, 2, S);
  make_map(fn, &p.map[M_WQ], d_in[3], 3, 256, 256, 3, 1, 1536, 512, 0, 128, 1, S);
  make_map(fn, &p.map[M_KV], kv, 3, 64, 16384, 1, 1, 128, 128 * 16384, 0, 128, 1, CU_TENSOR_MAP_SWIZZLE_NONE);
  make_map(fn, &p.map[M_WO], d_in[4], 3, 256, 256, 1, 1, 512, 512 * 256, 0, 128, 1, S);
  make_map(fn, &p.map[M_PW1], d_in[5], 3, 256, 256, 2, 1, 1024, 512, 0, 64, 2, S);
  make_map(fn, &p.map[M_PW2], d_in[7], 3, 256, 256, 1, 1, 512, 512 * 256, 0, 128, 1, S);
  make_map(fn, &p.map[M_FF2A], d_in[8], 3, 64, 256, 16, 1, 2048, 128, 0, 64, 2, S);
  make_map(fn, &p.map[M_FF2B], d_in[9], 3, 256, 1024, 1, 1, 512, 512 * 1024, 0, 128, 1, S);
  p.w_ff1b = (W)d_in[2]; p.w_qkv = (W)d_in[3]; p.w_o = (W)d_in[4]; p.w_pw1 = (W)d_in[5];
  p.dw = (W)d_in[6]; p.w_pw2 = (W)d_in[7]; p.w_ff2a = (W)d_in[8]; p.w_ff2b = (W)d_in[9];
  p.out = (__nv_bfloat16*)d_out;
  for (int i = 0; i < 4; i++) p.ring[i] = (uint64_t)(SM_BASE >> 4) | (uint64_t(1) << 16) | (uint64_t(64) << 32) | (uint64_t(1) << 62);

  cudaLaunchConfig_t cfg = {};
  cfg.gridDim = dim3(NCTA);
  cfg.blockDim = dim3(384);
  cfg.dynamicSmemBytes = SM_TOTAL;
  cfg.stream = cudaStreamPerThread;
  cudaLaunchAttribute at[1];
  at[0].id = cudaLaunchAttributeCooperative;
  at[0].val.cooperative = 1;
  cfg.attrs = at;
  cfg.numAttrs = 1;
  cudaLaunchKernelEx(&cfg, conformer_kernel, p);
}
```

```cpp
#include <cuda_runtime.h>
#include <cuda_bf16.h>
#include <cuda.h>
#include <stdint.h>

namespace {

constexpr int T_SEQ = 1000;
constexpr int DM = 256;
constexpr int NCTA = 128;
constexpr int NSTAGE = 12;
constexpr uint32_t STAGE_BYTES = 16384;
constexpr uint32_t TILE_BYTES = 8192;
constexpr uint32_t SM_BASE = 1024;
constexpr uint32_t SM_STG = NSTAGE * STAGE_BYTES;
constexpr uint32_t SM_FULL = SM_STG + 32768;
constexpr uint32_t SM_EMPTY = SM_FULL + 96;
constexpr uint32_t SM_XBAR = SM_FULL + 192;
constexpr uint32_t SM_EYE = SM_FULL + 256;
constexpr uint32_t SM_CS = SM_FULL + 768;
constexpr uint32_t SM_TOTAL = SM_FULL + 3072;
constexpr int CS_FF2 = 0, CS_PW1 = 4, CS_QKV = 6;
constexpr uint32_t SPIN_LIMIT = 1u << 16;
constexpr float LN_EPS = 1e-5f;
constexpr float SM_SCALE_LOG2 = 0.125f * 1.4426950408889634f;
constexpr uint32_t G_PITCH = 144;

constexpr int F_QKV = 16, F_SPARE = 22, F_KV = 24, F_WO = 40, F_PW1 = 42, F_PW2 = 46, F_TOTAL = 64;
enum { M_FF1A, M_FF1B, M_WKV, M_WQ, M_KV, M_WO, M_PW1, M_PW2, M_FF2A, M_FF2B, M_X, M_COUNT };
enum { BAR_K = 1, BAR_V, BAR_Q, BAR_MERGE, BAR_G, BAR_C, BAR_CS, BAR_WG1, BAR_RDY, BAR_TURN0, BAR_TURN1 };

struct Params {
  CUtensorMap map[M_COUNT];
  const __nv_bfloat16 *w_ff1b, *w_qkv, *w_o, *w_pw1, *dw, *w_pw2, *w_ff2a, *w_ff2b;
  __nv_bfloat16* out;
};

constexpr int X_AG0 = 0, X_RS = 512, X_AG1 = X_RS, X_HALO = X_RS + 512, X_ST = 2048, X_CLEAR = 2176, X_SIZE = 4096;
constexpr uint32_t HALO_TAG = 0xFFFF0001u;
__device__ __align__(1024) uint4 g_x[NCTA][X_SIZE];
__device__ __align__(1024) uint4 g_kv[8][2][16][512];
__device__ __align__(1024) uint32_t g_flag[8][32];
__device__ __align__(1024) uint4 g_cs[576];
__device__ __align__(1024) uint32_t g_ready[NCTA];
__device__ uint32_t g_epoch[NCTA];
#define PROF_TIME(i)
#define PROF_MARK(i)

__device__ __forceinline__ void mbar_init(uint32_t bar, uint32_t cnt) {
  asm volatile("mbarrier.init.shared::cta.b64 [%0], %1;" :: "r"(bar), "r"(cnt) : "memory");
}
__device__ __forceinline__ void mbar_wait(uint32_t bar, uint32_t parity) {
  asm volatile("{\n.reg .pred p;\n.reg .u32 c;\nmov.u32 c, 0;\n"
               "WAIT_LOOP:\nmbarrier.try_wait.parity.shared::cta.b64 p, [%0], %1;\n@p bra WAIT_DONE;\n"
               "add.u32 c, c, 1;\nsetp.lt.u32 p, c, %2;\n@p bra WAIT_LOOP;\nWAIT_DONE:\n}"
               :: "r"(bar), "r"(parity), "n"(SPIN_LIMIT) : "memory");
}
__device__ __forceinline__ void mbar_arrive(uint32_t bar) {
  asm volatile("mbarrier.arrive.shared::cta.b64 _, [%0];" :: "r"(bar) : "memory");
}
#define bar_sync(id, n) asm volatile("bar.sync %0, %1;" :: "n"((int)(id)), "n"(n) : "memory")
#define bar_arrive(id, n) asm volatile("bar.arrive %0, %1;" :: "n"((int)(id)), "n"(n) : "memory")
__device__ __forceinline__ void fence_async_smem() { asm volatile("fence.proxy.async.shared::cta;" ::: "memory"); }

__device__ __forceinline__ void st_vec(uint4* p, uint32_t a, uint32_t b, uint32_t c, uint32_t d) {
  asm volatile("{\n.reg .b128 v;\n.reg .b64 lo, hi;\nmov.b64 lo, {%1, %2};\nmov.b64 hi, {%3, %4};\nmov.b128 v, {lo, hi};\n"
               "st.relaxed.gpu.global.b128 [%0], v;\n}" :: "l"(p), "r"(a), "r"(b), "r"(c), "r"(d) : "memory");
}
__device__ __forceinline__ void ld_vec(const uint4* p, uint32_t& a, uint32_t& b, uint32_t& c, uint32_t& d) {
  asm volatile("{\n.reg .b128 v;\n.reg .b64 lo, hi;\nld.relaxed.gpu.global.b128 v, [%4];\nmov.b128 {lo, hi}, v;\n"
               "mov.b64 {%0, %1}, lo;\nmov.b64 {%2, %3}, hi;\n}" : "=r"(a), "=r"(b), "=r"(c), "=r"(d) : "l"(p) : "memory");
}
__device__ __forceinline__ void sts128(uint32_t a, uint32_t x, uint32_t y, uint32_t z, uint32_t w) {
  asm volatile("st.shared.v4.u32 [%0], {%1, %2, %3, %4};" :: "r"(a), "r"(x), "r"(y), "r"(z), "r"(w) : "memory");
}
__device__ __forceinline__ void lds128(uint32_t a, uint32_t& x, uint32_t& y, uint32_t& z, uint32_t& w) {
  asm volatile("ld.shared.v4.u32 {%0, %1, %2, %3}, [%4];" : "=r"(x), "=r"(y), "=r"(z), "=r"(w) : "r"(a) : "memory");
}
__device__ __forceinline__ uint32_t lds32(uint32_t a) {
  uint32_t x; asm volatile("ld.shared.u32 %0, [%1];" : "=r"(x) : "r"(a) : "memory"); return x;
}
__device__ __forceinline__ void sts32(uint32_t a, uint32_t x) { asm volatile("st.shared.u32 [%0], %1;" :: "r"(a), "r"(x) : "memory"); }
__device__ __forceinline__ void sts64(uint32_t a, uint32_t x, uint32_t y) {
  asm volatile("st.shared.v2.u32 [%0], {%1, %2};" :: "r"(a), "r"(x), "r"(y) : "memory");
}
__device__ __forceinline__ void stsm4(uint32_t a, const uint32_t* r) {
  asm volatile("stmatrix.sync.aligned.m8n8.x4.shared.b16 [%0], {%1, %2, %3, %4};" :: "r"(a), "r"(r[0]), "r"(r[1]), "r"(r[2]), "r"(r[3]) : "memory");
}
__device__ __forceinline__ void ldsm4(uint32_t a, uint32_t* r) {
  asm volatile("ldmatrix.sync.aligned.m8n8.x4.shared.b16 {%0, %1, %2, %3}, [%4];" : "=r"(r[0]), "=r"(r[1]), "=r"(r[2]), "=r"(r[3]) : "r"(a) : "memory");
}
__device__ __forceinline__ uint32_t pack2(float lo, float hi) {
  uint32_t r; asm("cvt.rn.bf16x2.f32 %0, %1, %2;" : "=r"(r) : "f"(hi), "f"(lo)); return r;
}
__device__ __forceinline__ float bf_lo(uint32_t w) { return __uint_as_float(w << 16); }
__device__ __forceinline__ float bf_hi(uint32_t w) { return __uint_as_float(w & 0xffff0000u); }
__device__ __forceinline__ float tanh_hw(float x) { float y; asm volatile("tanh.approx.f32 %0, %1;" : "=f"(y) : "f"(x)); return y; }
__device__ __forceinline__ float rcp_hw(float x) { float y; asm("rcp.approx.ftz.f32 %0, %1;" : "=f"(y) : "f"(x)); return y; }
__device__ __forceinline__ float ex2_hw(float x) { float y; asm("ex2.approx.ftz.f32 %0, %1;" : "=f"(y) : "f"(x)); return y; }

__device__ __forceinline__ uint32_t here(uint32_t v) { asm volatile("" : "+r"(v)); return v; }

#define WG_FENCE() asm volatile("wgmma.fence.sync.aligned;" ::: "memory")
#define WG_COMMIT() asm volatile("wgmma.commit_group.sync.aligned;" ::: "memory")
#define WG_WAIT(n) asm volatile("wgmma.wait_group.sync.aligned %0;" :: "n"(n) : "memory")

template <int N> __device__ __forceinline__ void pin(float (&d)[N]) {
#pragma unroll
  for (int i = 0; i < N; i++) asm volatile("" : "+f"(d[i]) :: "memory");
}
template <int N> __device__ __forceinline__ void pin(uint32_t (&d)[N]) {
#pragma unroll
  for (int i = 0; i < N; i++) asm volatile("" : "+r"(d[i]) :: "memory");
}

#define WG_D32 "{%0, %1, %2, %3, %4, %5, %6, %7, %8, %9, %10, %11, %12, %13, %14, %15, %16, %17, %18, %19, %20, %21, %22, %23, %24, %25, %26, %27, %28, %29, %30, %31}"
template <int TB> __device__ __forceinline__ void wgmma64_acc(float (&d)[32], const uint32_t* a, uint64_t db) {
  asm volatile("wgmma.mma_async.sync.aligned.m64n64k16.f32.bf16.bf16 " WG_D32 ", {%32, %33, %34, %35}, %36, 1, 1, 1, %37;"
    : "+f"(d[0]), "+f"(d[1]), "+f"(d[2]), "+f"(d[3]), "+f"(d[4]), "+f"(d[5]), "+f"(d[6]), "+f"(d[7]),
      "+f"(d[8]), "+f"(d[9]), "+f"(d[10]), "+f"(d[11]), "+f"(d[12]), "+f"(d[13]), "+f"(d[14]), "+f"(d[15]),
      "+f"(d[16]), "+f"(d[17]), "+f"(d[18]), "+f"(d[19]), "+f"(d[20]), "+f"(d[21]), "+f"(d[22]), "+f"(d[23]),
      "+f"(d[24]), "+f"(d[25]), "+f"(d[26]), "+f"(d[27]), "+f"(d[28]), "+f"(d[29]), "+f"(d[30]), "+f"(d[31])
    : "r"(a[0]), "r"(a[1]), "r"(a[2]), "r"(a[3]), "l"(db), "n"(TB));
}
template <int TB> __device__ __forceinline__ void wgmma64_set(float (&d)[32], const uint32_t* a, uint64_t db) {
  asm volatile("wgmma.mma_async.sync.aligned.m64n64k16.f32.bf16.bf16 " WG_D32 ", {%32, %33, %34, %35}, %36, 0, 1, 1, %37;"
    : "=f"(d[0]), "=f"(d[1]), "=f"(d[2]), "=f"(d[3]), "=f"(d[4]), "=f"(d[5]), "=f"(d[6]), "=f"(d[7]),
      "=f"(d[8]), "=f"(d[9]), "=f"(d[10]), "=f"(d[11]), "=f"(d[12]), "=f"(d[13]), "=f"(d[14]), "=f"(d[15]),
      "=f"(d[16]), "=f"(d[17]), "=f"(d[18]), "=f"(d[19]), "=f"(d[20]), "=f"(d[21]), "=f"(d[22]), "=f"(d[23]),
      "=f"(d[24]), "=f"(d[25]), "=f"(d[26]), "=f"(d[27]), "=f"(d[28]), "=f"(d[29]), "=f"(d[30]), "=f"(d[31])
    : "r"(a[0]), "r"(a[1]), "r"(a[2]), "r"(a[3]), "l"(db), "n"(TB));
}

__device__ __forceinline__ void wgmma16_acc(float* d, const uint32_t* a, uint64_t db) {
  asm volatile("wgmma.mma_async.sync.aligned.m64n16k16.f32.bf16.bf16 {%0, %1, %2, %3, %4, %5, %6, %7}, {%8, %9, %10, %11}, %12, 1, 1, 1, 0;"
    : "+f"(d[0]), "+f"(d[1]), "+f"(d[2]), "+f"(d[3]), "+f"(d[4]), "+f"(d[5]), "+f"(d[6]), "+f"(d[7])
    : "r"(a[0]), "r"(a[1]), "r"(a[2]), "r"(a[3]), "l"(db));
}
__device__ __forceinline__ void hmma(float (&d)[4], const uint32_t* a, uint32_t b0, uint32_t b1) {
  asm("mma.sync.aligned.m16n8k16.row.col.f32.bf16.bf16.f32 {%0, %1, %2, %3}, {%4, %5, %6, %7}, {%8, %9}, {%0, %1, %2, %3};"
    : "+f"(d[0]), "+f"(d[1]), "+f"(d[2]), "+f"(d[3]) : "r"(a[0]), "r"(a[1]), "r"(a[2]), "r"(a[3]), "r"(b0), "r"(b1));
}

__device__ __forceinline__ void hmma8(float (&d)[4], const uint32_t* a, uint32_t b0) {
  asm("mma.sync.aligned.m16n8k8.row.col.f32.bf16.bf16.f32 {%0, %1, %2, %3}, {%4, %5}, {%6}, {%0, %1, %2, %3};"
    : "+f"(d[0]), "+f"(d[1]), "+f"(d[2]), "+f"(d[3]) : "r"(a[0]), "r"(a[1]), "r"(b0));
}

template <bool FIRST> __device__ __forceinline__ void mma_tile(float (&d)[32], const uint32_t (&a)[16], uint64_t db) {
  WG_FENCE();
#pragma unroll
  for (int s = 0; s < 4; s++) {
    if (FIRST && s == 0) wgmma64_set<1>(d, &a[0], db); else wgmma64_acc<1>(d, &a[4 * s], db + s * 128);
  }
  WG_COMMIT();
}
template <int ROW> __device__ __forceinline__ void mma_tile_fold(float (&d)[32], const uint32_t (&a)[16], uint64_t db, const uint32_t (&mu)[4]) {
  WG_FENCE();
#pragma unroll
  for (int s = 0; s < 4; s++) wgmma64_acc<1>(d, &a[4 * s], db + s * 128);
  wgmma64_acc<1>(d, mu, (uint64_t)((SM_BASE + SM_CS + ROW * 128) >> 4) | (uint64_t(1) << 16) | (uint64_t(1) << 62));
  WG_COMMIT();
}
__device__ __forceinline__ void mma_add_half(float (&d)[32], const uint32_t (&a)[16]) {
  const uint64_t db = (uint64_t)((SM_BASE + SM_EYE) >> 4) | (uint64_t(8) << 16) | (uint64_t(8) << 32);
  WG_FENCE();
#pragma unroll
  for (int s = 0; s < 4; s++) wgmma16_acc(&d[8 * s], &a[4 * s], db);
  WG_COMMIT();
}
#define ACQUIRE(f) mbar_wait(SM_BASE + SM_FULL + ((f) % NSTAGE) * 8, ((f) / NSTAGE) & 1)
template <int F, int N> __device__ __forceinline__ void acquire_n() {
  static_assert(F % NSTAGE + N <= NSTAGE, "stages must not wrap");
  uint32_t spin = 0, ok;
  do {
    ok = 1;
#pragma unroll
    for (int i = 0; i < N; i++)
      asm volatile("{\n.reg .pred p;\nmbarrier.try_wait.parity.shared::cta.b64 p, [%1], %2;\nselp.u32 %0, %0, 0, p;\n}"
                   : "+r"(ok) : "r"(SM_BASE + SM_FULL + (F % NSTAGE + i) * 8), "r"((F / NSTAGE) & 1) : "memory");
  } while (!ok && ++spin < SPIN_LIMIT);
}
#define RELEASE(f0, f1) do { if (lane == 0) { _Pragma("unroll") for (int f_ = (f0); f_ <= (f1); f_++) mbar_arrive(SM_BASE + SM_EMPTY + (f_ % NSTAGE) * 8); } } while (0)
constexpr uint64_t RING = (uint64_t)(SM_BASE >> 4) | (uint64_t(1) << 16) | (uint64_t(64) << 32) | (uint64_t(1) << 62);
#define LO(f) (RING + ((f) % NSTAGE) * 1024)
#define HI(f) (RING + ((f) % NSTAGE) * 1024 + 512)

__device__ __forceinline__ void publish(uint4* dst, uint32_t (&a)[16], uint32_t tag) {
#pragma unroll
  for (int s = 0; s < 4; s++) {
    a[4 * s] = (a[4 * s] & ~1u) | tag;
    st_vec(dst + s * 128, a[4 * s], a[4 * s + 1], a[4 * s + 2], a[4 * s + 3]);
  }
}
__device__ __forceinline__ void fetch(const uint4* src, uint32_t (&a)[16]) {
#pragma unroll
  for (int s = 0; s < 4; s++) ld_vec(src + s * 128, a[4 * s], a[4 * s + 1], a[4 * s + 2], a[4 * s + 3]);
}
__device__ __forceinline__ uint32_t miss(const uint32_t (&a)[16], uint32_t tag) {
  return (a[0] ^ tag) | (a[4] ^ tag) | (a[8] ^ tag) | (a[12] ^ tag);
}
__device__ __forceinline__ bool stale(uint32_t v) { return __any_sync(0xffffffffu, here(v) & 1u); }
__device__ __forceinline__ void confirm(const uint4* src, uint32_t (&a)[16], uint32_t tag) {
  uint32_t spin = 0;
  while (__builtin_expect(stale(miss(a, tag)), 0) && ++spin < SPIN_LIMIT) fetch(src, a);
}
__device__ __forceinline__ void gather(uint32_t (&A)[4][16], uint32_t off, uint32_t tag) {
  const uint4* p1 = &g_x[0][0] + (off ^ (1 * X_SIZE));
  const uint4* p2 = &g_x[0][0] + (off ^ (2 * X_SIZE));
  const uint4* p3 = &g_x[0][0] + (off ^ (3 * X_SIZE));
  uint32_t spin = 0;
  do {
    fetch(p1, A[1]); fetch(p2, A[2]); fetch(p3, A[3]);
  } while (stale(miss(A[1], tag) | miss(A[2], tag) | miss(A[3], tag)) && ++spin < SPIN_LIMIT);
}
__device__ __forceinline__ void pack_acc(const float (&d)[32], uint32_t (&a)[16]) {
#pragma unroll
  for (int i = 0; i < 16; i++) a[i] = pack2(d[2 * i], d[2 * i + 1]);
}
__device__ __forceinline__ void res_store(uint32_t slot, const uint32_t (&a)[16]) {
#pragma unroll
  for (int s = 0; s < 4; s++) sts128(slot + s * 512, a[4 * s], a[4 * s + 1], a[4 * s + 2], a[4 * s + 3]);
}
__device__ __forceinline__ void res_load(uint32_t slot, float (&d)[32]) {
  uint32_t a[16];
#pragma unroll
  for (int s = 0; s < 4; s++) lds128(slot + s * 512, a[4 * s], a[4 * s + 1], a[4 * s + 2], a[4 * s + 3]);
#pragma unroll
  for (int i = 0; i < 16; i++) { d[2 * i] = bf_lo(a[i]); d[2 * i + 1] = bf_hi(a[i]); }
  pin(d);
}
__device__ __forceinline__ void tile_store(uint32_t maddr, const uint32_t (&a)[16]) {
#pragma unroll
  for (int s = 0; s < 4; s++) stsm4(maddr ^ (s << 5), &a[4 * s]);
}
__device__ __forceinline__ void tile_load(uint32_t maddr, uint32_t (&a)[16]) {
#pragma unroll
  for (int s = 0; s < 4; s++) ldsm4(maddr ^ (s << 5), &a[4 * s]);
}

struct RowAcc { float s[4], u[4], v[4]; };
__device__ __forceinline__ void row_acc(RowAcc& t, const uint32_t (&a)[16]) {
#pragma unroll
  for (int s = 0; s < 8; s++) {
    if ((s & 1) == 0) hmma(t.s, &a[2 * s], 0x3F803F80u, 0x3F803F80u);
    hmma8(t.u, &a[2 * s], a[2 * s]);
    hmma8(t.v, &a[2 * s], a[2 * s + 1]);
  }
}
__device__ __forceinline__ void stat_publish(const uint32_t (&a)[16], uint32_t b, uint32_t th, uint32_t tag) {
  RowAcc t = {};
  row_acc(t, a);
  const bool odd = th & 4;
  if ((th & 3) == ((th >> 3) & 3))
    st_vec(&g_x[b][X_ST + (th >> 2)], (__float_as_uint(t.s[0]) & ~1u) | tag, __float_as_uint(odd ? t.u[1] : t.u[0]),
           __float_as_uint(t.s[2]), __float_as_uint(odd ? t.v[3] : t.v[2]));
}
struct RowNorm { float m0, rs0, m1, rs1; };
__device__ __forceinline__ RowNorm row_norm(float s0, float q0, float s1, float q1, float scale) {
  RowNorm n;
  n.m0 = s0 * (1.f / DM); n.m1 = s1 * (1.f / DM);
  n.rs0 = scale * rsqrtf(fmaxf(fmaf(-n.m0, n.m0, q0 * (1.f / DM)), 0.f) + LN_EPS);
  n.rs1 = scale * rsqrtf(fmaxf(fmaf(-n.m1, n.m1, q1 * (1.f / DM)), 0.f) + LN_EPS);
  return n;
}
__device__ __forceinline__ RowNorm stat_gather(uint32_t b, uint32_t th, uint32_t tag, float scale) {
  const uint4* src = &g_x[b & ~3u][X_ST + (th >> 2)];
  uint32_t v[16], spin = 0;
  do {
#pragma unroll
    for (int j = 0; j < 4; j++) ld_vec(src + j * X_SIZE, v[4 * j], v[4 * j + 1], v[4 * j + 2], v[4 * j + 3]);
  } while (stale(miss(v, tag)) && ++spin < SPIN_LIMIT);
  float f[4];
#pragma unroll
  for (int i = 0; i < 4; i++)
    f[i] = (__uint_as_float(v[i]) + __uint_as_float(v[4 + i])) + (__uint_as_float(v[8 + i]) + __uint_as_float(v[12 + i]));
  return row_norm(f[0], f[1], f[2], f[3], scale);
}
__device__ __forceinline__ void mean_frag(uint32_t (&mu)[4], const RowNorm& n, bool sel) {
  const float a = sel ? -n.m0 : 0.f, c = sel ? -n.m1 : 0.f;
  mu[0] = pack2(a, a); mu[1] = pack2(c, c);
  const float al = a - bf_lo(mu[0]), cl = c - bf_lo(mu[1]);
  mu[2] = pack2(al, al); mu[3] = pack2(cl, cl);
  pin(mu);
}
__device__ __forceinline__ void scale_pack(const float (&d)[32], uint32_t (&a)[16], float rs0, float rs1) {
#pragma unroll
  for (int i = 0; i < 16; i++) { const float rs = (i & 1) ? rs1 : rs0; a[i] = pack2(d[2 * i] * rs, d[2 * i + 1] * rs); }
}
template <int I0, int I1> __device__ __forceinline__ void silu_part(const float (&d)[32], uint32_t (&h)[16], float rs0, float rs1) {
#pragma unroll
  for (int i = I0; i < I1; i++) {
    const float rs = (i & 1) ? rs1 : rs0, a = d[2 * i] * rs, b = d[2 * i + 1] * rs;
    h[i] = pack2(fmaf(a, tanh_hw(a), a), fmaf(b, tanh_hw(b), b));
  }
}
template <int F, int N> __device__ __forceinline__ void send_residual(uint32_t (&a)[16], uint32_t xoff, uint32_t res, uint32_t tag) {
  const uint32_t exact[4] = {a[0], a[4], a[8], a[12]};
  publish(&g_x[0][X_AG0] + xoff, a, tag);
  acquire_n<F, N>();
  stat_publish(a, blockIdx.x, xoff & 127, tag);
  res_store(res, a);
#pragma unroll
  for (int s = 0; s < 4; s++) sts32(res + s * 512, exact[s]);
  pin(a);
}
template <int F, int NEXT> __device__ __forceinline__ void proj_residual(uint32_t (&A)[4][16], uint32_t xoff, uint32_t res,
                                                               uint32_t r, uint32_t tag, int lane) {
  float acc[32];
  publish(&g_x[0][X_AG1] + xoff, A[0], tag);
  acquire_n<F, 2>();
  res_load(res, acc);
  const uint32_t flip = (r & 1) * 512;
  mma_tile<false>(acc, A[0], flip + LO(F));
  gather(A, xoff + X_AG1, tag);
  PROF_MARK(F == F_WO ? 11 : 16);
  mma_tile<false>(acc, A[1], HI(F) - flip);
  mma_tile<false>(acc, A[2], flip + LO(F + 1));
  mma_tile<false>(acc, A[3], HI(F + 1) - flip);
  WG_WAIT(0); pin(acc);
  pack_acc(acc, A[0]);
  send_residual<F + 2, NEXT>(A[0], xoff, res, tag);
}

template <int R> __device__ __forceinline__ float row_max(const float (&S)[2][32], float m) {
  float t[8];
#pragma unroll
  for (int j = 0; j < 8; j++) t[j] = fmaxf(fmaxf(S[0][4 * j + R], S[0][4 * j + R + 1]), fmaxf(S[1][4 * j + R], S[1][4 * j + R + 1]));
  float n = fmaxf(fmaxf(fmaxf(t[0], t[1]), fmaxf(t[2], t[3])), fmaxf(fmaxf(t[4], t[5]), fmaxf(t[6], fmaxf(t[7], m))));
  n = fmaxf(n, __shfl_xor_sync(0xffffffffu, n, 1));
  return fmaxf(n, __shfl_xor_sync(0xffffffffu, n, 2));
}
template <int R> __device__ __forceinline__ float row_exp(float (&S)[2][32], float c) {
  float t0 = 0.f, t1 = 0.f;
#pragma unroll
  for (int h = 0; h < 2; h++)
#pragma unroll
    for (int j = 0; j < 8; j++) {
      S[h][4 * j + R] = ex2_hw(fmaf(S[h][4 * j + R], SM_SCALE_LOG2, c));
      S[h][4 * j + R + 1] = ex2_hw(fmaf(S[h][4 * j + R + 1], SM_SCALE_LOG2, c));
      t0 += S[h][4 * j + R]; t1 += S[h][4 * j + R + 1];
    }
  return t0 + t1;
}

__device__ __forceinline__ uint32_t fill_entry(int f, int r, int bh) {
  int m, x = r, y, z = 0;
  if (f < F_QKV || f >= 48) {
    const int i = f & 15;
    m = f < F_QKV ? M_FF1A : M_FF2A;
    if (i < 8) {
      const int h = i < 2 ? i : (i >= 5), c = i < 2 ? 0 : i - 1 - 3 * h;
      x = 0; y = r ^ c; z = 4 * r + 2 * h;
    } else {
      m++; x = r ^ (((i >> 1) - 3) & 3); y = 4 * r + 2 * (i & 1);
    }
  } else if (f < F_KV) {
    const int i = f - F_QKV;
    if (i == 1 || i >= 5) { m = M_WQ; y = (r & 2) ^ (i == 1 ? 0 : 2); }
    else { m = M_WKV; y = r ^ (i ? i - 1 : 0); z = 1; }
  } else if (f < F_WO) {
    const int i = f - F_KV;
    m = M_KV; x = 0; y = bh * 32 + (i & 2) * 8 + (i >> 2) * 4 + (i & 1) * 2;
  } else if (f >= F_PW1 && f < F_PW2) {
    m = M_PW1; y = r ^ (f - F_PW1);
  } else {
    m = f < F_PW1 ? M_WO : M_PW2; y = (r & 2) ^ ((f & 1) * 2);
  }
  return m | (x << 4) | (y << 8) | (z << 16);
}
__device__ __forceinline__ void l2_prefetch(const void* p, uint32_t total, int b) {
  const uint32_t part = total / NCTA;
  asm volatile("cp.async.bulk.prefetch.L2.global [%0], %1;" :: "l"((const char*)p + (size_t)b * part), "r"(part) : "memory");
}

__global__ void __launch_bounds__(384, 1) conformer_kernel(const __grid_constant__ Params p) {
  extern __shared__ __align__(1024) uint8_t smem[];
  const int tid = threadIdx.x, lane = tid & 31;
  const int cw = __shfl_sync(0xffffffffu, tid >> 5, 0), wg = cw >> 2, w = cw & 3;
  const int b = blockIdx.x, r = b & 3, batch = b >> 6, t = (b >> 2) & 15;
  if ((uint32_t)__cvta_generic_to_shared(smem) != SM_BASE) return;
  PROF_MARK(0);
  PROF_TIME(30);

  if (cw == 8) {
    asm volatile("{\n.reg .pred p;\nelect.sync _|p, 0xffffffff;\n"
                 "@p prefetch.tensormap [%5];\n"
                 "@p mbarrier.init.shared::cta.b64 [%1], 1;\n"
                 "@p fence.proxy.async.shared::cta;\n"
                 "@p mbarrier.arrive.expect_tx.shared::cta.b64 _, [%1], 32768;\n"
                 "@p cp.async.bulk.tensor.4d.shared::cluster.global.mbarrier::complete_tx::bytes [%0], [%2, {0, %3, 0, %4}], [%1];\n}"
                 :: "r"(SM_BASE + SM_STG), "r"(SM_BASE + SM_XBAR), "l"(&p.map[M_X]), "r"(t * 64), "r"(batch), "l"(&p.map[M_FF1A]) : "memory");
    if (lane == 0) {
#pragma unroll
      for (int i = 0; i < NSTAGE; i++) { mbar_init(SM_BASE + SM_FULL + i * 8, 1); mbar_init(SM_BASE + SM_EMPTY + i * 8, 4); }
      fence_async_smem();
    }
    __syncwarp();
    bar_arrive(0, 288);
  } else if (wg < 2) {
    if (tid < 144) sts128(SM_BASE + SM_CS + tid * 16, 0, 0, 0, 0);
    if (tid >= 160) {
      const int i = tid - 160;
      sts32(SM_BASE + SM_EYE + i * 4, ((i & 32) == 0 && (i & 3) == ((i >> 3) & 3)) ? (0x3F00u << ((i & 4) * 4)) : 0u);
    }
    fence_async_smem();
    bar_sync(0, 288);
  }

  if (wg == 2) {
    asm volatile("setmaxnreg.dec.sync.aligned.u32 40;");
    if (w == 0) {
      const uint32_t* flag = &g_flag[batch * 4 + r][lane];
      uint32_t ready = 0, entry = 0, st = 0, parity = 1;
      const uint32_t prev = ((volatile uint32_t*)g_epoch)[b];
#pragma unroll 1
      for (int f = 0; f < F_TOTAL; f++) {
        if ((f & 31) == 0) entry = fill_entry(f + lane, r, batch * 4 + r);
        const uint32_t e = __shfl_sync(0xffffffffu, entry, f & 31);
        if ((e & 15) == M_KV) {
          const uint32_t need = 3u << ((e >> 8) & 31);
          uint32_t spin = 0;
#pragma unroll 1
          while ((ready & need) != need && ++spin < SPIN_LIMIT) {
            uint32_t v;
            asm volatile("ld.relaxed.gpu.global.u32 %0, [%1];" : "=r"(v) : "l"(flag) : "memory");
            ready = __ballot_sync(0xffffffffu, v - 1 == prev);
          }
        }
        mbar_wait(SM_BASE + SM_EMPTY + st * 8, parity);
        asm volatile("{\n.reg .pred p;\nelect.sync _|p, 0xffffffff;\n"
                     "@p mbarrier.arrive.expect_tx.shared::cta.b64 _, [%1], 16384;\n"
                     "@p cp.async.bulk.tensor.3d.shared::cluster.global.mbarrier::complete_tx::bytes [%0], [%2, {%3, %4, %5}], [%1];\n}"
                     :: "r"(SM_BASE + st * STAGE_BYTES), "r"(SM_BASE + SM_FULL + st * 8), "l"(&p.map[e & 15]),
                        "r"((e << 2) & 0x3C0), "r"((e >> 2) & 0x3FC0), "r"(e >> 16) : "memory");
        if (++st == NSTAGE) { st = 0; parity ^= 1; }
        if (f == 0) PROF_MARK(1);
      }
    } else if (w < 3) {
      const int kind = w - 1;
      const uint32_t epoch = ((volatile uint32_t*)g_epoch)[b] + 1;
      if (kind == 0) bar_sync(BAR_K, 160); else bar_sync(BAR_V, 160);
      if (lane == 0) {
        asm volatile("cp.async.bulk.global.shared::cta.bulk_group [%0], [%1], %2;"
                     :: "l"(&g_kv[batch * 4 + r][kind][t][0]), "r"(SM_BASE + SM_STG + kind * TILE_BYTES), "r"(TILE_BYTES) : "memory");
        asm volatile("cp.async.bulk.commit_group;\ncp.async.bulk.wait_group 0;" ::: "memory");
        asm volatile("st.relaxed.gpu.global.u32 [%0], %1;" :: "l"(&g_flag[batch * 4 + r][kind * 16 + t]), "r"(epoch) : "memory");
      }
    } else {
      if (lane < M_COUNT) asm volatile("prefetch.tensormap [%0];" :: "l"(&p.map[lane]) : "memory");
      if (lane == 0) {
        l2_prefetch(p.w_ff1b, 1024 * 256 * 2, b);
        l2_prefetch(p.w_o, 256 * 256 * 2, b);
        l2_prefetch(p.w_pw2, 256 * 256 * 2, b);
        l2_prefetch(p.w_ff2b, 1024 * 256 * 2, b);
      }
    }
  } else {
    asm volatile("setmaxnreg.inc.sync.aligned.u32 232;");
    const int q = lane & 3, th = tid & 127;
    constexpr uint32_t stg = SM_BASE + SM_STG;
    const uint32_t mrow = 16 * w + (lane & 15);
    const uint32_t maddr = stg + mrow * 128 + (((lane >> 4) ^ (lane & 7)) << 4);
    const uint32_t res = stg + 3 * TILE_BYTES + w * 2048 + lane * 16;
    const uint32_t xoff = b * X_SIZE + th;
    const int nvalid = T_SEQ - t * 64;

    uint32_t A[4][16];
    uint32_t mu[4] = {0u, 0u, 0u, 0u};
    float rs0, rs1;
    if (wg == 0) {
      mbar_wait(SM_BASE + SM_XBAR, 0);
      PROF_MARK(1);
      RowAcc ra = {}, rb = {};
#pragma unroll
      for (int c = 0; c < 4; c++) {
        tile_load(maddr + (r ^ c) * TILE_BYTES, A[c]);
        row_acc((c & 1) ? rb : ra, A[c]);
      }
      __syncwarp();
      res_store(res, A[0]);
      const float s0 = ra.s[0] + rb.s[0], s1 = ra.s[2] + rb.s[2];
      const uint32_t m0 = pack2(s0 * (1.f / DM), s0 * (1.f / DM)), m1 = pack2(s1 * (1.f / DM), s1 * (1.f / DM));
#pragma unroll
      for (int c = 0; c < 4; c++) {
#pragma unroll
        for (int i = 0; i < 16; i++) asm("sub.rn.bf16x2 %0, %0, %1;" : "+r"(A[c][i]) : "r"((i & 1) ? m1 : m0));
        pin(A[c]);
      }
      const bool odd = lane & 4;
      const int src = (lane & 28) | (lane >> 3);
      const float q0 = __shfl_sync(0xffffffffu, odd ? ra.u[1] + rb.u[1] : ra.u[0] + rb.u[0], src);
      const float q1 = __shfl_sync(0xffffffffu, odd ? ra.v[3] + rb.v[3] : ra.v[2] + rb.v[2], src);
      const RowNorm n = row_norm(s0, q0, s1, q1, 0.5f);
      rs0 = n.rs0; rs1 = n.rs1;
    } else {
      const uint32_t epoch = ((volatile uint32_t*)g_epoch)[b] + 1, tag = epoch & 1;
#pragma unroll 1
      for (int i = 0; i < X_CLEAR; i += 128) st_vec(&g_x[0][i] + xoff, 0u, 0u, 0u, 0u);
      if (b < 72) {
        const __nv_bfloat16* wp; int ld, col;
        if (b < 24) { wp = p.w_qkv; ld = 768; col = b * 32; }
        else if (b < 40) { wp = p.w_pw1; ld = 512; col = (b - 24) * 32; }
        else { wp = p.w_ff2a; ld = 1024; col = (b - 40) * 32; }
        const uint4* src = (const uint4*)(wp + (size_t)(th >> 2) * ld + col + q * 8);
        float c[8] = {0.f, 0.f, 0.f, 0.f, 0.f, 0.f, 0.f, 0.f};
#pragma unroll 1
        for (int h = 0; h < 2; h++) {
#pragma unroll
          for (int i = 0; i < 4; i++) {
            const uint4 v = __ldg(src + i * 4 * ld);
            c[0] += bf_lo(v.x); c[1] += bf_hi(v.x); c[2] += bf_lo(v.y); c[3] += bf_hi(v.y);
            c[4] += bf_lo(v.z); c[5] += bf_hi(v.z); c[6] += bf_lo(v.w); c[7] += bf_hi(v.w);
          }
          src += 16 * ld;
        }
#pragma unroll 1
        for (int m = 4; m <= 16; m <<= 1)
#pragma unroll
          for (int k = 0; k < 8; k++) c[k] += __shfl_xor_sync(0xffffffffu, c[k], m);
        if (lane < 4) {
          const uint32_t a = SM_BASE + SM_CS + 1792 + w * 128 + lane * 32;
          sts128(a, __float_as_uint(c[0]), __float_as_uint(c[1]), __float_as_uint(c[2]), __float_as_uint(c[3]));
          sts128(a + 16, __float_as_uint(c[4]), __float_as_uint(c[5]), __float_as_uint(c[6]), __float_as_uint(c[7]));
        }
        bar_sync(BAR_WG1, 128);
        if (th < 8) {
          float o[4] = {0.f, 0.f, 0.f, 0.f};
#pragma unroll 1
          for (int k = 0; k < 4; k++) {
            uint32_t e[4];
            lds128(SM_BASE + SM_CS + 1792 + k * 128 + th * 16, e[0], e[1], e[2], e[3]);
#pragma unroll
            for (int i = 0; i < 4; i++) o[i] += __uint_as_float(e[i]);
          }
          st_vec(&g_cs[b * 8 + th], (__float_as_uint(o[0]) & ~1u) | tag, __float_as_uint(o[1]), __float_as_uint(o[2]), __float_as_uint(o[3]));
        }
      }
      PROF_MARK(1);
      __threadfence();
      PROF_MARK(2);
      bar_sync(BAR_WG1, 128);
      if (th == 0) {
        asm volatile("st.relaxed.gpu.global.u32 [%0], %1;" :: "l"(&g_ready[b]), "r"(epoch) : "memory");
        uint32_t e[4], spin = 0;
#pragma unroll 1
        do {
          ld_vec((const uint4*)&g_ready[b & ~3], e[0], e[1], e[2], e[3]);
        } while ((e[0] != epoch || e[1] != epoch || e[2] != epoch || e[3] != epoch) && ++spin < SPIN_LIMIT);
        __threadfence();
      }
      __syncwarp();
      bar_arrive(BAR_RDY, 256);
      PROF_MARK(3);
#pragma unroll 1
      for (int i = th; i < 144; i += 128) {
        const int j = i >> 4;
        int src;
        if (j < CS_PW1) src = 320 + 64 * r + i;
        else if (j < CS_QKV) src = 192 + (j - CS_PW1) * 64 + 16 * r + (i & 15);
        else src = ((j - CS_QKV + 1) % 3) * 64 + 16 * r + (i & 15);
        uint32_t e[4], spin = 0;
#pragma unroll 1
        do {
          ld_vec(&g_cs[src], e[0], e[1], e[2], e[3]);
        } while (((e[0] ^ tag) & 1u) && ++spin < SPIN_LIMIT);
        const float c0 = __uint_as_float(e[0] & ~1u), c1 = __uint_as_float(e[1]), c2 = __uint_as_float(e[2]), c3 = __uint_as_float(e[3]);
        const uint32_t h0 = pack2(c0, c1), h1 = pack2(c2, c3);
        const uint32_t a = SM_BASE + SM_CS + j * 256 + (i & 15) * 8;
        sts64(a ^ ((a >> 3) & 0x70), h0, h1);
        sts64((a + 128) ^ (((a + 128) >> 3) & 0x70), pack2(c0 - bf_lo(h0), c1 - bf_hi(h0)), pack2(c2 - bf_lo(h1), c3 - bf_hi(h1)));
      }
      fence_async_smem();
      bar_arrive(BAR_CS, 256);
      PROF_MARK(4);
    }

#pragma unroll 1
    for (uint32_t pass = 0; pass < 2; pass++) {
      uint32_t Q[16];
      if (wg == 0) {
        float acc[4][32];
        uint32_t H[4][16];
        ACQUIRE(0);
        mma_tile<true>(acc[0], A[0], LO(0)); mma_tile<true>(acc[1], A[0], HI(0));
        ACQUIRE(1);
        mma_tile<true>(acc[2], A[0], LO(1)); mma_tile<true>(acc[3], A[0], HI(1));
        acquire_n<2, 3>();
        if (pass) gather(A, here(xoff) + X_AG0, 1);
        PROF_MARK(2 + pass * 16);
        mma_tile<false>(acc[0], A[1], LO(2)); mma_tile<false>(acc[0], A[2], LO(3));
        WG_WAIT(2);
        if (pass) {
          RELEASE(F_PW2, F_PW2 + 1);
          const RowNorm n = stat_gather(b, here(th), 1, 0.5f);
          rs0 = n.rs0; rs1 = n.rs1;
          mean_frag(mu, n, q == 0);
        }
        RELEASE(0, 1);
        mma_tile_fold<2 * CS_FF2>(acc[0], A[3], LO(4), mu);
        acquire_n<5, 3>();
        mma_tile<false>(acc[1], A[1], HI(2)); mma_tile<false>(acc[1], A[2], HI(3));
        WG_WAIT(2); pin(acc[0]);
        silu_part<0, 8>(acc[0], H[0], rs0, rs1);
        mma_tile_fold<2 * CS_FF2 + 2>(acc[1], A[3], HI(4), mu);
        silu_part<8, 16>(acc[0], H[0], rs0, rs1);
        mma_tile<false>(acc[2], A[1], LO(5)); mma_tile<false>(acc[2], A[2], LO(6));
        WG_WAIT(2); pin(acc[1]);
        RELEASE(2, 4);
        silu_part<0, 8>(acc[1], H[1], rs0, rs1);
        mma_tile_fold<2 * CS_FF2 + 4>(acc[2], A[3], LO(7), mu);
        silu_part<8, 16>(acc[1], H[1], rs0, rs1);
        mma_tile<false>(acc[3], A[1], HI(5)); mma_tile<false>(acc[3], A[2], HI(6));
        WG_WAIT(2); pin(acc[2]);
        silu_part<0, 8>(acc[2], H[2], rs0, rs1);
        mma_tile_fold<2 * CS_FF2 + 6>(acc[3], A[3], HI(7), mu);
        silu_part<8, 16>(acc[2], H[2], rs0, rs1);
        pin(H[0]); pin(H[1]); pin(H[2]);
        acquire_n<8, 2>();
        mma_tile<true>(acc[0], H[0], LO(8)); mma_tile<false>(acc[0], H[1], HI(8));
        WG_WAIT(2); pin(acc[3]);
        RELEASE(5, 7);
        silu_part<0, 8>(acc[3], H[3], rs0, rs1);
        mma_tile<false>(acc[0], H[2], LO(9));
        silu_part<8, 16>(acc[3], H[3], rs0, rs1);
        pin(H[3]);
        mma_tile<false>(acc[0], H[3], HI(9));
        PROF_MARK(3 + pass * 16);
        const uint32_t rtag = pass ^ 1;
        const uint4* rs_in = &g_x[0][X_RS] + here(xoff);
#pragma unroll
        for (int c = 1; c < 4; c++) {
          ACQUIRE(8 + 2 * c);
          mma_tile<true>(acc[c], H[0], LO(8 + 2 * c));
          if (c == 1 && !pass) bar_sync(BAR_RDY, 256);
          if (c == 3) fetch(rs_in, A[1]);
          mma_tile<false>(acc[c], H[1], HI(8 + 2 * c));
          WG_WAIT(2); pin(acc[c - 1]);
          uint32_t o[16];
          pack_acc(acc[c - 1], o);
          publish(&g_x[0][X_RS + (c - 1) * 512] + (here(xoff) ^ (c * X_SIZE)), o, rtag);
          ACQUIRE(9 + 2 * c);
          mma_tile<false>(acc[c], H[2], LO(9 + 2 * c));
          if (c == 1) RELEASE(8, 9);
          if (c == 2) res_load(res, acc[0]);
          mma_tile<false>(acc[c], H[3], HI(9 + 2 * c));
        }
        fetch(rs_in + 512, A[2]);
        confirm(rs_in, A[1], rtag);
        mma_add_half(acc[0], A[1]);
        WG_WAIT(1);
        fetch(rs_in + 1024, A[3]);
        confirm(rs_in + 512, A[2], rtag);
        mma_add_half(acc[0], A[2]);
        confirm(rs_in + 1024, A[3], rtag);
        mma_add_half(acc[0], A[3]);
        PROF_MARK(4 + pass * 16);
        WG_WAIT(0); pin(acc[0]); pin(acc[3]);
#pragma unroll
        for (int i = 0; i < 16; i++) A[0][i] = pack2(fmaf(acc[3][2 * i], 0.5f, acc[0][2 * i]), fmaf(acc[3][2 * i + 1], 0.5f, acc[0][2 * i + 1]));
        if (pass) {
          PROF_MARK(21);
          stat_publish(A[0], b, here(th), 0);
          const RowNorm fn = stat_gather(b, here(th), 0, 1.f);
          const float nm0 = -fn.m0 * fn.rs0, nm1 = -fn.m1 * fn.rs1;
#pragma unroll
          for (int i = 0; i < 16; i++) {
            const float rs = (i & 1) ? fn.rs1 : fn.rs0, nm = (i & 1) ? nm1 : nm0;
            A[0][i] = pack2(fmaf(bf_lo(A[0][i]), rs, nm), fmaf(bf_hi(A[0][i]), rs, nm));
          }
          tile_store(here(maddr), A[0]);
          __syncwarp();
          const int row = 16 * w + (lane >> 3);
          uint4* dst = (uint4*)(p.out + ((size_t)batch * T_SEQ + t * 64 + row) * DM + 64 * r) + (lane & 7);
          const uint32_t src = stg + row * 128 + (((lane & 7) ^ (lane >> 3)) << 4);
#pragma unroll
          for (int i = 0; i < 4; i++) {
            uint4 v;
            lds128((src ^ ((i & 1) << 6)) + i * 512, v.x, v.y, v.z, v.w);
            if (row + 4 * i < nvalid) dst[i * 4 * (DM / 8)] = v;
          }
          PROF_MARK(22);
          PROF_TIME(31);
          break;
        }
        send_residual<F_QKV, 6>(A[0], here(xoff), res, 1);
        PROF_MARK(5);
        const uint32_t flip = (r & 1) * 512;
        mma_tile<true>(acc[0], A[0], LO(F_QKV)); mma_tile<true>(acc[1], A[0], HI(F_QKV));
        mma_tile<true>(acc[2], A[0], flip + LO(F_QKV + 1));
        bar_sync(BAR_CS, 256);
        gather(A, here(xoff) + X_AG0, 1);
        PROF_MARK(6);
        mma_tile<false>(acc[0], A[1], LO(F_QKV + 2)); mma_tile<false>(acc[0], A[2], LO(F_QKV + 3));
        RELEASE(10, 15);
        {
          const RowNorm n = stat_gather(b, here(th), 1, 1.f);
          rs0 = n.rs0; rs1 = n.rs1;
          mean_frag(mu, n, q == 3);
        }
        mma_tile_fold<2 * CS_QKV - 6>(acc[0], A[3], LO(F_QKV + 4), mu);
        mma_tile<false>(acc[1], A[1], HI(F_QKV + 2)); mma_tile<false>(acc[1], A[2], HI(F_QKV + 3));
        WG_WAIT(2); pin(acc[0]);
        scale_pack(acc[0], Q, rs0, rs1);
        tile_store(here(maddr), Q);
        fence_async_smem();
        bar_arrive(BAR_K, 160);
        mma_tile_fold<2 * CS_QKV - 4>(acc[1], A[3], HI(F_QKV + 4), mu);
        mma_tile<false>(acc[2], A[1], HI(F_QKV + 1) - flip); mma_tile<false>(acc[2], A[2], flip + LO(F_QKV + 5));
        WG_WAIT(2); pin(acc[1]);
        scale_pack(acc[1], Q, rs0, rs1);
        tile_store(here(maddr) + TILE_BYTES, Q);
        fence_async_smem();
        bar_arrive(BAR_V, 160);
        mma_tile_fold<2 * CS_QKV - 2>(acc[2], A[3], HI(F_QKV + 5) - flip, mu);
        WG_WAIT(0); pin(acc[2]);
        scale_pack(acc[2], Q, rs0, rs1);
        res_store(here(res) - TILE_BYTES, Q);
        bar_arrive(BAR_Q, 256);
        acquire_n<F_SPARE, 2>();
        RELEASE(F_QKV, F_SPARE + 1);
      } else {
        bar_arrive(BAR_TURN0, 256);
        bar_sync(BAR_Q, 256);
#pragma unroll
        for (int s = 0; s < 4; s++) lds128(res - TILE_BYTES + s * 512, Q[4 * s], Q[4 * s + 1], Q[4 * s + 2], Q[4 * s + 3]);
      }
      PROF_MARK(7);

      float O[32];
      float m0 = -INFINITY, m1 = -INFINITY, l0 = 0.f, l1 = 0.f;
      {
        uint32_t P[2][16];
#pragma unroll
        for (int i = 0; i < 32; i++) O[i] = 0.f;
#pragma unroll
        for (int i = 0; i < 16; i++) { P[0][i] = 0u; P[1][i] = 0u; }
        pin(Q);
        uint32_t sk = wg, sv = wg;
#pragma unroll 1
        for (int it = 0; it < 4; it++) {
          float S[2][32];
          pin(P[0]); pin(P[1]); pin(O);
          mbar_wait(SM_BASE + SM_FULL + sk * 8, it == 3);
          if (wg == 0) bar_sync(BAR_TURN0, 256); else bar_sync(BAR_TURN1, 256);
          const uint64_t dk = RING + sk * 1024, dv = RING + sv * 1024;
          WG_FENCE();
#pragma unroll
          for (int h = 0; h < 2; h++)
#pragma unroll
            for (int s = 0; s < 4; s++) {
              if (s == 0) wgmma64_set<0>(S[h], &Q[0], dk + h * 512); else wgmma64_acc<0>(S[h], &Q[4 * s], dk + h * 512 + s * 2);
            }
          WG_COMMIT();
          mma_tile<false>(O, P[0], dv);
          mma_tile<false>(O, P[1], dv + 512);
          if (wg == 0) bar_arrive(BAR_TURN1, 256); else if (it < 3) bar_arrive(BAR_TURN0, 256);
          WG_WAIT(2); pin(S[0]); pin(S[1]);
          if (it == 3 && wg == 1) {
#pragma unroll
            for (int i = 20; i < 32; i++) S[1][i] = -INFINITY;
          }
          const float n0 = row_max<0>(S, m0), n1 = row_max<2>(S, m1);
          const float a0 = ex2_hw((m0 - n0) * SM_SCALE_LOG2), a1 = ex2_hw((m1 - n1) * SM_SCALE_LOG2);
          m0 = n0; m1 = n1;
          l0 = fmaf(l0, a0, row_exp<0>(S, -n0 * SM_SCALE_LOG2));
          pin(S[0]); pin(S[1]);
          mbar_wait(SM_BASE + SM_FULL + (sk + 2) * 8, it == 3);
          WG_WAIT(0); pin(O); pin(P[0]); pin(P[1]);
          if (lane == 0 && it < 3) {
            mbar_arrive(SM_BASE + SM_EMPTY + sk * 8);
            if (it) mbar_arrive(SM_BASE + SM_EMPTY + sv * 8);
          }
          l1 = fmaf(l1, a1, row_exp<2>(S, -n1 * SM_SCALE_LOG2));
#pragma unroll
          for (int j = 0; j < 8; j++) { O[4 * j] *= a0; O[4 * j + 1] *= a0; O[4 * j + 2] *= a1; O[4 * j + 3] *= a1; }
          pack_acc(S[0], P[0]); pack_acc(S[1], P[1]);
          sv = sk + 2;
          sk = it == 2 ? wg : sk + 4;
        }
        pin(P[0]); pin(P[1]); pin(O);
        mma_tile<false>(O, P[0], RING + sv * 1024);
        mma_tile<false>(O, P[1], RING + sv * 1024 + 512);
        l0 += __shfl_xor_sync(0xffffffffu, l0, 1); l1 += __shfl_xor_sync(0xffffffffu, l1, 1);
        l0 += __shfl_xor_sync(0xffffffffu, l0, 2); l1 += __shfl_xor_sync(0xffffffffu, l1, 2);
        WG_WAIT(0); pin(O);
      }
      PROF_MARK(9);

      if (wg == 1) {
        const uint32_t mo = stg + here(th) * 16;
#pragma unroll
        for (int i = 0; i < 8; i++)
          sts128(mo + i * 2048, __float_as_uint(O[4 * i]), __float_as_uint(O[4 * i + 1]), __float_as_uint(O[4 * i + 2]), __float_as_uint(O[4 * i + 3]));
        sts128(mo + 8 * 2048, __float_as_uint(m0), __float_as_uint(m1), __float_as_uint(l0), __float_as_uint(l1));
        bar_arrive(BAR_MERGE, 256);
      } else {
        const uint32_t mo = stg + here(th) * 16;
        bar_sync(BAR_MERGE, 256);
        uint32_t e[4];
        lds128(mo + 8 * 2048, e[0], e[1], e[2], e[3]);
        const float n0 = fmaxf(m0, __uint_as_float(e[0])), n1 = fmaxf(m1, __uint_as_float(e[1]));
        float a0 = ex2_hw((m0 - n0) * SM_SCALE_LOG2), a1 = ex2_hw((m1 - n1) * SM_SCALE_LOG2);
        float b0 = ex2_hw((__uint_as_float(e[0]) - n0) * SM_SCALE_LOG2), b1 = ex2_hw((__uint_as_float(e[1]) - n1) * SM_SCALE_LOG2);
        const float i0 = rcp_hw(fmaf(a0, l0, b0 * __uint_as_float(e[2]))), i1 = rcp_hw(fmaf(a1, l1, b1 * __uint_as_float(e[3])));
        a0 *= i0; b0 *= i0; a1 *= i1; b1 *= i1;
#pragma unroll
        for (int i = 0; i < 8; i++) {
          lds128(mo + i * 2048, e[0], e[1], e[2], e[3]);
          A[0][2 * i] = pack2(fmaf(O[4 * i], a0, b0 * __uint_as_float(e[0])), fmaf(O[4 * i + 1], a0, b0 * __uint_as_float(e[1])));
          A[0][2 * i + 1] = pack2(fmaf(O[4 * i + 2], a1, b1 * __uint_as_float(e[2])), fmaf(O[4 * i + 3], a1, b1 * __uint_as_float(e[3])));
        }
        PROF_MARK(10);
        proj_residual<F_WO, 4>(A, here(xoff), res, r, 0, lane);
        PROF_MARK(12);
      }

      const int dir = cw == 0 ? -1 : 1;
      uint32_t tap[15];
      {
        const uint32_t* dwp = (const uint32_t*)(p.dw + 64 * r) + lane + 7 * (DM / 2);
#pragma unroll
        for (int k = 0; k < 15; k++) tap[k] = __ldg(dwp + dir * (k - 7) * (DM / 2));
      }

      if (wg == 0) {
        float acc[2][32];
        mma_tile<true>(acc[0], A[0], LO(F_PW1)); mma_tile<true>(acc[1], A[0], HI(F_PW1));
        gather(A, here(xoff) + X_AG0, 0);
        PROF_MARK(13);
        mma_tile<false>(acc[1], A[1], HI(F_PW1 + 1)); mma_tile<false>(acc[1], A[2], HI(F_PW1 + 2));
        RELEASE(F_KV + 10, F_WO + 1);
        {
          const RowNorm n = stat_gather(b, here(th), 0, 0.5f);
          const int row = 16 * w + (lane >> 2);
          rs0 = row < nvalid ? n.rs0 : 0.f; rs1 = row + 8 < nvalid ? n.rs1 : 0.f;
          mean_frag(mu, n, q == 0);
        }
        mma_tile_fold<2 * CS_PW1 + 2>(acc[1], A[3], HI(F_PW1 + 3), mu);
        mma_tile<false>(acc[0], A[1], LO(F_PW1 + 1)); mma_tile<false>(acc[0], A[2], LO(F_PW1 + 2));
        WG_WAIT(2); pin(acc[1]);
#pragma unroll
        for (int i = 0; i < 16; i++) acc[1][i] = tanh_hw(acc[1][i] * ((i & 2) ? rs1 : rs0));
        mma_tile_fold<2 * CS_PW1>(acc[0], A[3], LO(F_PW1 + 3), mu);
#pragma unroll
        for (int i = 16; i < 32; i++) acc[1][i] = tanh_hw(acc[1][i] * ((i & 2) ? rs1 : rs0));
#pragma unroll
        for (int i = 0; i < 32; i++) { const float rs = (i & 2) ? rs1 : rs0; acc[1][i] = fmaf(acc[1][i], rs, rs); }
        pin(acc[1]);
        WG_WAIT(0); pin(acc[0]);
#pragma unroll
        for (int i = 0; i < 16; i++) A[0][i] = pack2(acc[0][2 * i] * acc[1][2 * i], acc[0][2 * i + 1] * acc[1][2 * i + 1]);
        const uint32_t ga = stg + TILE_BYTES + here(mrow) * G_PITCH + (lane >> 4) * 16;
#pragma unroll
        for (int s = 0; s < 4; s++) stsm4(ga + s * 32, &A[0][4 * s]);
        RELEASE(F_PW1, F_PW1 + 3);
      }
      bar_sync(BAR_G, 256);
      PROF_MARK(14);

      {
        const int first = cw == 0 ? 14 : 8 * cw - 7;
        const uint32_t gsrc = stg + TILE_BYTES + first * G_PITCH + lane * 4;
        uint32_t in[22];
#pragma unroll
        for (int i = 0; i < 15; i++) in[i] = lds32(gsrc + dir * i * (int)G_PITCH);
        const bool edge = cw == 0 || cw == 7;
        const bool nbr = cw == 0 ? t > 0 : t < 15;
        if (edge) {
          if (nbr) {
            uint4* dst = &g_x[b + 4 * dir][X_HALO + (cw == 0 ? 96 : 0) + lane];
            st_vec(dst, HALO_TAG, in[14], in[13], in[12]);
            st_vec(dst + 32, HALO_TAG, in[11], in[10], in[9]);
            st_vec(dst + 64, HALO_TAG, in[8], 0u, 0u);
          }
        } else {
#pragma unroll
          for (int i = 15; i < 22; i++) in[i] = lds32(gsrc + i * G_PITCH);
        }
        float cl[8], ch[8], tl[15], tv[15];
#pragma unroll
        for (int k = 0; k < 15; k++) { tl[k] = bf_lo(tap[k]); tv[k] = bf_hi(tap[k]); }
#pragma unroll
        for (int o = 0; o < 8; o++) { cl[o] = 0.f; ch[o] = 0.f; }
#pragma unroll
        for (int i = 0; i < 15; i++) {
          const float lo = bf_lo(in[i]), hi = bf_hi(in[i]);
#pragma unroll
          for (int o = 0; o < 8; o++)
            if (i - o >= 0) { cl[o] = fmaf(lo, tl[i - o], cl[o]); ch[o] = fmaf(hi, tv[i - o], ch[o]); }
        }
        if (edge) {
#pragma unroll
          for (int i = 15; i < 22; i++) in[i] = 0u;
          if (nbr) {
            const uint4* src = &g_x[b][X_HALO + (cw == 0 ? 0 : 96) + lane];
            uint32_t e0, e1, e2, u0, u1, spin = 0;
#pragma unroll 1
            do {
              ld_vec(src, e0, in[15], in[16], in[17]);
              ld_vec(src + 32, e1, in[18], in[19], in[20]);
              ld_vec(src + 64, e2, in[21], u0, u1);
            } while (__any_sync(0xffffffffu, ((e0 ^ HALO_TAG) | (e1 ^ HALO_TAG) | (e2 ^ HALO_TAG)) != 0) && ++spin < SPIN_LIMIT);
          }
        }
#pragma unroll
        for (int i = 15; i < 22; i++) {
          const float lo = bf_lo(in[i]), hi = bf_hi(in[i]);
#pragma unroll
          for (int o = 0; o < 8; o++)
            if (i - o <= 14) { cl[o] = fmaf(lo, tl[i - o], cl[o]); ch[o] = fmaf(hi, tv[i - o], ch[o]); }
        }
        const uint32_t fl = cw == 0 ? 7 : 0;
        const uint32_t cdst = (stg + cw * 1024 + lane * 4) ^ (fl * 144);
#pragma unroll
        for (int o = 0; o < 8; o++) {
          const float a = 0.5f * cl[o], c = 0.5f * ch[o];
          sts32(cdst ^ (o * 144), pack2(fmaf(a, tanh_hw(a), a), fmaf(c, tanh_hw(c), c)));
        }
      }
      if (wg == 1) {
        bar_arrive(BAR_C, 256);
        if (th == 0) ((volatile uint32_t*)g_epoch)[b] += 1;
        break;
      }
      bar_sync(BAR_C, 256);
      tile_load(here(maddr), A[0]);
      PROF_MARK(15);
      proj_residual<F_PW2, 1>(A, here(xoff), res, r, 1, lane);
      PROF_MARK(17);
    }
  }
}

typedef CUresult (*EncodeFn)(CUtensorMap*, CUtensorMapDataType, cuuint32_t, void*, const cuuint64_t*, const cuuint64_t*,
                             const cuuint32_t*, const cuuint32_t*, CUtensorMapInterleave, CUtensorMapSwizzle,
                             CUtensorMapL2promotion, CUtensorMapFloatOOBfill);

void make_map(EncodeFn fn, CUtensorMap* m, const void* w, int rank, int d0, int d1, int d2, int d3, int s1, int s2, int s3,
              int b1, int b2, CUtensorMapSwizzle swz) {
  const cuuint64_t dims[4] = {(cuuint64_t)d0, (cuuint64_t)d1, (cuuint64_t)d2, (cuuint64_t)d3};
  const cuuint64_t strides[3] = {(cuuint64_t)s1, (cuuint64_t)s2, (cuuint64_t)s3};
  const cuuint32_t box[4] = {64, (cuuint32_t)b1, (cuuint32_t)b2, 1}, es[4] = {1, 1, 1, 1};
  fn(m, CU_TENSOR_MAP_DATA_TYPE_BFLOAT16, rank, const_cast<void*>(w), dims, strides, box, es, CU_TENSOR_MAP_INTERLEAVE_NONE,
     swz, CU_TENSOR_MAP_L2_PROMOTION_L2_128B, CU_TENSOR_MAP_FLOAT_OOB_FILL_NONE);
}

}

extern "C" void kernel_launch(void* const* d_in, const int* in_sizes, int n_in, void* d_out, int out_size) {
  static EncodeFn fn = nullptr;
  static void* kv = nullptr;
  if (!fn) {
    void* f = nullptr;
    cudaDriverEntryPointQueryResult st;
    cudaGetDriverEntryPoint("cuTensorMapEncodeTiled", &f, cudaEnableDefault, &st);
    fn = (EncodeFn)f;
    cudaGetSymbolAddress(&kv, g_kv);
    cudaFuncSetAttribute(conformer_kernel, cudaFuncAttributeMaxDynamicSharedMemorySize, SM_TOTAL);
  }
  typedef const __nv_bfloat16* W;
  const CUtensorMapSwizzle S = CU_TENSOR_MAP_SWIZZLE_128B;
  Params p;
  make_map(fn, &p.map[M_X], d_in[0], 4, 64, T_SEQ, 4, 2, 512, 128, T_SEQ * 512, 64, 4, S);
  make_map(fn, &p.map[M_FF1A], d_in[1], 3, 64, 256, 16, 1, 2048, 128, 0, 64, 2, S);
  make_map(fn, &p.map[M_FF1B], d_in[2], 3, 256, 1024, 1, 1, 512, 512 * 1024, 0, 128, 1, S);
  make_map(fn, &p.map[M_WKV], d_in[3], 3, 256, 256, 3, 1, 1536, 512, 0, 64, 2, S);
  make_map(fn, &p.map[M_WQ], d_in[3], 3, 256, 256, 3, 1, 1536, 512, 0, 128, 1, S);
  make_map(fn, &p.map[M_KV], kv, 3, 64, 16384, 1, 1, 128, 128 * 16384, 0, 128, 1, CU_TENSOR_MAP_SWIZZLE_NONE);
  make_map(fn, &p.map[M_WO], d_in[4], 3, 256, 256, 1, 1, 512, 512 * 256, 0, 128, 1, S);
  make_map(fn, &p.map[M_PW1], d_in[5], 3, 256, 256, 2, 1, 1024, 512, 0, 64, 2, S);
  make_map(fn, &p.map[M_PW2], d_in[7], 3, 256, 256, 1, 1, 512, 512 * 256, 0, 128, 1, S);
  make_map(fn, &p.map[M_FF2A], d_in[8], 3, 64, 256, 16, 1, 2048, 128, 0, 64, 2, S);
  make_map(fn, &p.map[M_FF2B], d_in[9], 3, 256, 1024, 1, 1, 512, 512 * 1024, 0, 128, 1, S);
  p.w_ff1b = (W)d_in[2]; p.w_qkv = (W)d_in[3]; p.w_o = (W)d_in[4]; p.w_pw1 = (W)d_in[5];
  p.dw = (W)d_in[6]; p.w_pw2 = (W)d_in[7]; p.w_ff2a = (W)d_in[8]; p.w_ff2b = (W)d_in[9];
  p.out = (__nv_bfloat16*)d_out;

  cudaLaunchConfig_t cfg = {};
  cfg.gridDim = dim3(NCTA);
  cfg.blockDim = dim3(384);
  cfg.dynamicSmemBytes = SM_TOTAL;
  cfg.stream = cudaStreamPerThread;
  cudaLaunchAttribute at[1];
  at[0].id = cudaLaunchAttributeCooperative;
  at[0].val.cooperative = 1;
  cfg.attrs = at;
  cfg.numAttrs = 1;
  cudaLaunchKernelEx(&cfg, conformer_kernel, p);
}
```

```cpp
#include <cuda_runtime.h>
#include <cuda_bf16.h>
#include <cuda.h>
#include <stdint.h>

namespace {

constexpr int T_SEQ = 1000;
constexpr int DM = 256;
constexpr int NCTA = 128;
constexpr int NSTAGE = 12;
constexpr uint32_t STAGE_BYTES = 16384;
constexpr uint32_t TILE_BYTES = 8192;
constexpr uint32_t SM_BASE = 1024;
constexpr uint32_t SM_STG = NSTAGE * STAGE_BYTES;
constexpr uint32_t SM_FULL = SM_STG + 32768;
constexpr uint32_t SM_EMPTY = SM_FULL + 96;
constexpr uint32_t SM_XBAR = SM_FULL + 192;
constexpr uint32_t SM_EYE = SM_FULL + 256;
constexpr uint32_t SM_ONE = SM_FULL + 640;
constexpr uint32_t SM_CS = SM_FULL + 768;
constexpr uint32_t SM_TOTAL = SM_FULL + 3072;
constexpr int CS_FF2 = 0, CS_PW1 = 4, CS_QKV = 6;
constexpr uint32_t SPIN_LIMIT = 1u << 16;
constexpr float LN_EPS = 1e-5f;
constexpr float SM_SCALE_LOG2 = 0.125f * 1.4426950408889634f;
constexpr uint32_t G_PITCH = 144;

constexpr int F_QKV = 16, F_SPARE = 22, F_KV = 24, F_WO = 40, F_PW1 = 42, F_PW2 = 46, F_TOTAL = 64;
enum { M_FF1A, M_FF1B, M_WKV, M_WQ, M_KV, M_WO, M_PW1, M_PW2, M_FF2A, M_FF2B, M_X, M_COUNT };
enum { BAR_K = 1, BAR_V, BAR_Q, BAR_MERGE, BAR_G, BAR_C, BAR_WG1, BAR_RDY, BAR_ST, BAR_ATT, BAR_INIT, BAR_RDY1 };

struct Params {
  CUtensorMap map[M_COUNT];
  const __nv_bfloat16 *w_ff1b, *w_qkv, *w_o, *w_pw1, *dw, *w_pw2, *w_ff2a, *w_ff2b;
  __nv_bfloat16* out;
};

constexpr int X_RS = 0, X_AG1 = X_RS, X_HALO = X_RS + 512, X_CLEAR = 1024, X_AG0 = 1536, X_ST = 2048, X_SIZE = 4096;
constexpr uint32_t HALO_TAG = 0xFFFF0001u;
__device__ __align__(1024) uint4 g_x[NCTA][X_SIZE];
__device__ __align__(1024) uint4 g_kv[8][2][16][512];
__device__ __align__(1024) uint32_t g_flag[8][32];
__device__ __align__(1024) uint4 g_cs[576];
__device__ __align__(1024) uint32_t g_ready[NCTA];
__device__ uint32_t g_epoch[NCTA];
#define PROF_TIME(i)
#define PROF_MARK(i)

__device__ __forceinline__ void mbar_init(uint32_t bar, uint32_t cnt) {
  asm volatile("mbarrier.init.shared::cta.b64 [%0], %1;" :: "r"(bar), "r"(cnt) : "memory");
}
__device__ __forceinline__ void mbar_wait(uint32_t bar, uint32_t parity) {
  asm volatile("{\n.reg .pred p;\n.reg .u32 c;\nmov.u32 c, 0;\n"
               "WAIT_LOOP:\nmbarrier.try_wait.parity.shared::cta.b64 p, [%0], %1;\n@p bra WAIT_DONE;\n"
               "add.u32 c, c, 1;\nsetp.lt.u32 p, c, %2;\n@p bra WAIT_LOOP;\nWAIT_DONE:\n}"
               :: "r"(bar), "r"(parity), "n"(SPIN_LIMIT) : "memory");
}
__device__ __forceinline__ void mbar_arrive(uint32_t bar) {
  asm volatile("mbarrier.arrive.shared::cta.b64 _, [%0];" :: "r"(bar) : "memory");
}
#define bar_sync(id, n) asm volatile("bar.sync %0, %1;" :: "n"((int)(id)), "n"(n) : "memory")
#define bar_arrive(id, n) asm volatile("bar.arrive %0, %1;" :: "n"((int)(id)), "n"(n) : "memory")
__device__ __forceinline__ void fence_async_smem() { asm volatile("fence.proxy.async.shared::cta;" ::: "memory"); }

__device__ __forceinline__ void st_vec(uint4* p, uint32_t a, uint32_t b, uint32_t c, uint32_t d) {
  asm volatile("{\n.reg .b128 v;\n.reg .b64 lo, hi;\nmov.b64 lo, {%1, %2};\nmov.b64 hi, {%3, %4};\nmov.b128 v, {lo, hi};\n"
               "st.relaxed.gpu.global.b128 [%0], v;\n}" :: "l"(p), "r"(a), "r"(b), "r"(c), "r"(d) : "memory");
}
__device__ __forceinline__ void ld_vec(const uint4* p, uint32_t& a, uint32_t& b, uint32_t& c, uint32_t& d) {
  asm volatile("{\n.reg .b128 v;\n.reg .b64 lo, hi;\nld.relaxed.gpu.global.b128 v, [%4];\nmov.b128 {lo, hi}, v;\n"
               "mov.b64 {%0, %1}, lo;\nmov.b64 {%2, %3}, hi;\n}" : "=r"(a), "=r"(b), "=r"(c), "=r"(d) : "l"(p) : "memory");
}
__device__ __forceinline__ void sts128(uint32_t a, uint32_t x, uint32_t y, uint32_t z, uint32_t w) {
  asm volatile("st.shared.v4.u32 [%0], {%1, %2, %3, %4};" :: "r"(a), "r"(x), "r"(y), "r"(z), "r"(w) : "memory");
}
__device__ __forceinline__ void lds128(uint32_t a, uint32_t& x, uint32_t& y, uint32_t& z, uint32_t& w) {
  asm volatile("ld.shared.v4.u32 {%0, %1, %2, %3}, [%4];" : "=r"(x), "=r"(y), "=r"(z), "=r"(w) : "r"(a) : "memory");
}
__device__ __forceinline__ uint32_t lds32(uint32_t a) {
  uint32_t x; asm volatile("ld.shared.u32 %0, [%1];" : "=r"(x) : "r"(a) : "memory"); return x;
}
__device__ __forceinline__ void sts32(uint32_t a, uint32_t x) { asm volatile("st.shared.u32 [%0], %1;" :: "r"(a), "r"(x) : "memory"); }
__device__ __forceinline__ void sts64(uint32_t a, uint32_t x, uint32_t y) {
  asm volatile("st.shared.v2.u32 [%0], {%1, %2};" :: "r"(a), "r"(x), "r"(y) : "memory");
}
__device__ __forceinline__ void stsm4(uint32_t a, const uint32_t* r) {
  asm volatile("stmatrix.sync.aligned.m8n8.x4.shared.b16 [%0], {%1, %2, %3, %4};" :: "r"(a), "r"(r[0]), "r"(r[1]), "r"(r[2]), "r"(r[3]) : "memory");
}
__device__ __forceinline__ void ldsm4(uint32_t a, uint32_t* r) {
  asm volatile("ldmatrix.sync.aligned.m8n8.x4.shared.b16 {%0, %1, %2, %3}, [%4];" : "=r"(r[0]), "=r"(r[1]), "=r"(r[2]), "=r"(r[3]) : "r"(a) : "memory");
}
__device__ __forceinline__ uint32_t pack2(float lo, float hi) {
  uint32_t r; asm("cvt.rn.bf16x2.f32 %0, %1, %2;" : "=r"(r) : "f"(hi), "f"(lo)); return r;
}
__device__ __forceinline__ float bf_lo(uint32_t w) { return __uint_as_float(w << 16); }
__device__ __forceinline__ float bf_hi(uint32_t w) { return __uint_as_float(w & 0xffff0000u); }
__device__ __forceinline__ float tanh_hw(float x) { float y; asm volatile("tanh.approx.f32 %0, %1;" : "=f"(y) : "f"(x)); return y; }
__device__ __forceinline__ float rcp_hw(float x) { float y; asm("rcp.approx.ftz.f32 %0, %1;" : "=f"(y) : "f"(x)); return y; }
__device__ __forceinline__ float ex2_hw(float x) { float y; asm("ex2.approx.ftz.f32 %0, %1;" : "=f"(y) : "f"(x)); return y; }

__device__ __forceinline__ uint32_t here(uint32_t v) { asm volatile("" : "+r"(v)); return v; }

#define SCHED() asm volatile("pmevent 1;" ::: "memory")
#define WG_FENCE() asm volatile("wgmma.fence.sync.aligned;" ::: "memory")
#define WG_COMMIT() asm volatile("wgmma.commit_group.sync.aligned;" ::: "memory")
#define WG_WAIT(n) asm volatile("wgmma.wait_group.sync.aligned %0;" :: "n"(n) : "memory")

template <int N> __device__ __forceinline__ void pin(float (&d)[N]) {
#pragma unroll
  for (int i = 0; i < N; i++) asm volatile("" : "+f"(d[i]) :: "memory");
}
template <int N> __device__ __forceinline__ void pin(uint32_t (&d)[N]) {
#pragma unroll
  for (int i = 0; i < N; i++) asm volatile("" : "+r"(d[i]) :: "memory");
}

#define WG_D32 "{%0, %1, %2, %3, %4, %5, %6, %7, %8, %9, %10, %11, %12, %13, %14, %15, %16, %17, %18, %19, %20, %21, %22, %23, %24, %25, %26, %27, %28, %29, %30, %31}"
template <int TB> __device__ __forceinline__ void wgmma64_acc(float (&d)[32], const uint32_t* a, uint64_t db) {
  asm volatile("wgmma.mma_async.sync.aligned.m64n64k16.f32.bf16.bf16 " WG_D32 ", {%32, %33, %34, %35}, %36, 1, 1, 1, %37;"
    : "+f"(d[0]), "+f"(d[1]), "+f"(d[2]), "+f"(d[3]), "+f"(d[4]), "+f"(d[5]), "+f"(d[6]), "+f"(d[7]),
      "+f"(d[8]), "+f"(d[9]), "+f"(d[10]), "+f"(d[11]), "+f"(d[12]), "+f"(d[13]), "+f"(d[14]), "+f"(d[15]),
      "+f"(d[16]), "+f"(d[17]), "+f"(d[18]), "+f"(d[19]), "+f"(d[20]), "+f"(d[21]), "+f"(d[22]), "+f"(d[23]),
      "+f"(d[24]), "+f"(d[25]), "+f"(d[26]), "+f"(d[27]), "+f"(d[28]), "+f"(d[29]), "+f"(d[30]), "+f"(d[31])
    : "r"(a[0]), "r"(a[1]), "r"(a[2]), "r"(a[3]), "l"(db), "n"(TB));
}
template <int TB> __device__ __forceinline__ void wgmma64_set(float (&d)[32], const uint32_t* a, uint64_t db) {
  asm volatile("wgmma.mma_async.sync.aligned.m64n64k16.f32.bf16.bf16 " WG_D32 ", {%32, %33, %34, %35}, %36, 0, 1, 1, %37;"
    : "=f"(d[0]), "=f"(d[1]), "=f"(d[2]), "=f"(d[3]), "=f"(d[4]), "=f"(d[5]), "=f"(d[6]), "=f"(d[7]),
      "=f"(d[8]), "=f"(d[9]), "=f"(d[10]), "=f"(d[11]), "=f"(d[12]), "=f"(d[13]), "=f"(d[14]), "=f"(d[15]),
      "=f"(d[16]), "=f"(d[17]), "=f"(d[18]), "=f"(d[19]), "=f"(d[20]), "=f"(d[21]), "=f"(d[22]), "=f"(d[23]),
      "=f"(d[24]), "=f"(d[25]), "=f"(d[26]), "=f"(d[27]), "=f"(d[28]), "=f"(d[29]), "=f"(d[30]), "=f"(d[31])
    : "r"(a[0]), "r"(a[1]), "r"(a[2]), "r"(a[3]), "l"(db), "n"(TB));
}

__device__ __forceinline__ void wgmma72_acc(float (&d)[36], const uint32_t* a, uint64_t db) {
  asm volatile("wgmma.mma_async.sync.aligned.m64n72k16.f32.bf16.bf16 {%0, %1, %2, %3, %4, %5, %6, %7, %8, %9, %10, %11, %12, %13, %14, %15, %16, %17, %18, %19, %20, %21, %22, %23, %24, %25, %26, %27, %28, %29, %30, %31, %32, %33, %34, %35}, {%36, %37, %38, %39}, %40, 1, 1, 1, 1;"
    : "+f"(d[0]), "+f"(d[1]), "+f"(d[2]), "+f"(d[3]), "+f"(d[4]), "+f"(d[5]), "+f"(d[6]), "+f"(d[7]), "+f"(d[8]),
      "+f"(d[9]), "+f"(d[10]), "+f"(d[11]), "+f"(d[12]), "+f"(d[13]), "+f"(d[14]), "+f"(d[15]), "+f"(d[16]), "+f"(d[17]),
      "+f"(d[18]), "+f"(d[19]), "+f"(d[20]), "+f"(d[21]), "+f"(d[22]), "+f"(d[23]), "+f"(d[24]), "+f"(d[25]), "+f"(d[26]),
      "+f"(d[27]), "+f"(d[28]), "+f"(d[29]), "+f"(d[30]), "+f"(d[31]), "+f"(d[32]), "+f"(d[33]), "+f"(d[34]), "+f"(d[35])
    : "r"(a[0]), "r"(a[1]), "r"(a[2]), "r"(a[3]), "l"(db));
}
__device__ __forceinline__ void wgmma16_acc(float* d, const uint32_t* a, uint64_t db) {
  asm volatile("wgmma.mma_async.sync.aligned.m64n16k16.f32.bf16.bf16 {%0, %1, %2, %3, %4, %5, %6, %7}, {%8, %9, %10, %11}, %12, 1, 1, 1, 0;"
    : "+f"(d[0]), "+f"(d[1]), "+f"(d[2]), "+f"(d[3]), "+f"(d[4]), "+f"(d[5]), "+f"(d[6]), "+f"(d[7])
    : "r"(a[0]), "r"(a[1]), "r"(a[2]), "r"(a[3]), "l"(db));
}
__device__ __forceinline__ void hmma(float (&d)[4], const uint32_t* a, uint32_t b0, uint32_t b1) {
  asm("mma.sync.aligned.m16n8k16.row.col.f32.bf16.bf16.f32 {%0, %1, %2, %3}, {%4, %5, %6, %7}, {%8, %9}, {%0, %1, %2, %3};"
    : "+f"(d[0]), "+f"(d[1]), "+f"(d[2]), "+f"(d[3]) : "r"(a[0]), "r"(a[1]), "r"(a[2]), "r"(a[3]), "r"(b0), "r"(b1));
}

__device__ __forceinline__ void hmma8(float (&d)[4], const uint32_t* a, uint32_t b0) {
  asm("mma.sync.aligned.m16n8k8.row.col.f32.bf16.bf16.f32 {%0, %1, %2, %3}, {%4, %5}, {%6}, {%0, %1, %2, %3};"
    : "+f"(d[0]), "+f"(d[1]), "+f"(d[2]), "+f"(d[3]) : "r"(a[0]), "r"(a[1]), "r"(b0));
}

template <bool FIRST> __device__ __forceinline__ void mma_tile(float (&d)[32], const uint32_t (&a)[16], uint64_t db) {
  WG_FENCE();
#pragma unroll
  for (int s = 0; s < 4; s++) {
    if (FIRST && s == 0) wgmma64_set<1>(d, &a[0], db); else wgmma64_acc<1>(d, &a[4 * s], db + s * 128);
  }
  WG_COMMIT();
}
template <int ROW> __device__ __forceinline__ void mma_tile_fold(float (&d)[32], const uint32_t (&a)[16], uint64_t db, const uint32_t (&mu)[4]) {
  WG_FENCE();
#pragma unroll
  for (int s = 0; s < 4; s++) wgmma64_acc<1>(d, &a[4 * s], db + s * 128);
  wgmma64_acc<1>(d, mu, (uint64_t)((SM_BASE + SM_CS + ROW * 128) >> 4) | (uint64_t(1) << 16) | (uint64_t(1) << 62));
  WG_COMMIT();
}
__device__ __forceinline__ void mma_add_half(float (&d)[32], const uint32_t (&a)[16]) {
  const uint64_t db = (uint64_t)((SM_BASE + SM_EYE) >> 4) | (uint64_t(8) << 16) | (uint64_t(8) << 32);
  WG_FENCE();
#pragma unroll
  for (int s = 0; s < 4; s++) wgmma16_acc(&d[8 * s], &a[4 * s], db);
  WG_COMMIT();
}
#define ACQUIRE(f) mbar_wait(SM_BASE + SM_FULL + ((f) % NSTAGE) * 8, ((f) / NSTAGE) & 1)
template <int F, int N> __device__ __forceinline__ void acquire_n() {
  static_assert(F % NSTAGE + N <= NSTAGE, "stages must not wrap");
  uint32_t spin = 0, ok;
  do {
    ok = 1;
#pragma unroll
    for (int i = 0; i < N; i++)
      asm volatile("{\n.reg .pred p;\nmbarrier.try_wait.parity.shared::cta.b64 p, [%1], %2;\nselp.u32 %0, %0, 0, p;\n}"
                   : "+r"(ok) : "r"(SM_BASE + SM_FULL + (F % NSTAGE + i) * 8), "r"((F / NSTAGE) & 1) : "memory");
  } while (!ok && ++spin < SPIN_LIMIT);
}
#define RELEASE(f0, f1) do { if (lane == 0) { _Pragma("unroll") for (int f_ = (f0); f_ <= (f1); f_++) mbar_arrive(SM_BASE + SM_EMPTY + (f_ % NSTAGE) * 8); } } while (0)
constexpr uint64_t RING = (uint64_t)(SM_BASE >> 4) | (uint64_t(1) << 16) | (uint64_t(64) << 32) | (uint64_t(1) << 62);
#define LO(f) (RING + ((f) % NSTAGE) * 1024)
#define HI(f) (RING + ((f) % NSTAGE) * 1024 + 512)

__device__ __forceinline__ void publish(uint4* dst, uint32_t (&a)[16], uint32_t tag) {
#pragma unroll
  for (int s = 0; s < 4; s++) {
    a[4 * s] = (a[4 * s] & ~1u) | tag;
    st_vec(dst + s * 128, a[4 * s], a[4 * s + 1], a[4 * s + 2], a[4 * s + 3]);
  }
}
__device__ __forceinline__ void fetch(const uint4* src, uint32_t (&a)[16]) {
#pragma unroll
  for (int s = 0; s < 4; s++) ld_vec(src + s * 128, a[4 * s], a[4 * s + 1], a[4 * s + 2], a[4 * s + 3]);
}
__device__ __forceinline__ uint32_t miss(const uint32_t (&a)[16], uint32_t tag) {
  return (a[0] ^ tag) | (a[4] ^ tag) | (a[8] ^ tag) | (a[12] ^ tag);
}
__device__ __forceinline__ bool stale(uint32_t v) { return __any_sync(0xffffffffu, here(v) & 1u); }
__device__ __forceinline__ void confirm(const uint4* src, uint32_t (&a)[16], uint32_t tag) {
  uint32_t spin = 0;
  while (__builtin_expect(stale(miss(a, tag)), 0) && ++spin < SPIN_LIMIT) fetch(src, a);
}
__device__ __forceinline__ void gather(uint32_t (&A)[4][16], uint32_t off, uint32_t tag) {
  const uint4* p1 = &g_x[0][0] + (off ^ (1 * X_SIZE));
  const uint4* p2 = &g_x[0][0] + (off ^ (2 * X_SIZE));
  const uint4* p3 = &g_x[0][0] + (off ^ (3 * X_SIZE));
  uint32_t spin = 0;
  do {
    fetch(p1, A[1]); fetch(p2, A[2]); fetch(p3, A[3]);
  } while (stale(miss(A[1], tag) | miss(A[2], tag) | miss(A[3], tag)) && ++spin < SPIN_LIMIT);
}
__device__ __forceinline__ void pack_acc(const float (&d)[32], uint32_t (&a)[16]) {
#pragma unroll
  for (int i = 0; i < 16; i++) a[i] = pack2(d[2 * i], d[2 * i + 1]);
}
__device__ __forceinline__ void res_store(uint32_t slot, const uint32_t (&a)[16]) {
#pragma unroll
  for (int s = 0; s < 4; s++) sts128(slot + s * 512, a[4 * s], a[4 * s + 1], a[4 * s + 2], a[4 * s + 3]);
}
__device__ __forceinline__ void res_load(uint32_t slot, float (&d)[32]) {
  uint32_t a[16];
#pragma unroll
  for (int s = 0; s < 4; s++) lds128(slot + s * 512, a[4 * s], a[4 * s + 1], a[4 * s + 2], a[4 * s + 3]);
#pragma unroll
  for (int i = 0; i < 16; i++) { d[2 * i] = bf_lo(a[i]); d[2 * i + 1] = bf_hi(a[i]); }
  pin(d);
}
__device__ __forceinline__ void tile_store(uint32_t maddr, const uint32_t (&a)[16]) {
#pragma unroll
  for (int s = 0; s < 4; s++) stsm4(maddr ^ (s << 5), &a[4 * s]);
}
__device__ __forceinline__ void tile_load(uint32_t maddr, uint32_t (&a)[16]) {
#pragma unroll
  for (int s = 0; s < 4; s++) ldsm4(maddr ^ (s << 5), &a[4 * s]);
}

struct RowAcc { float s[4], u[4], v[4]; };
__device__ __forceinline__ void row_acc(RowAcc& t, const uint32_t (&a)[16]) {
#pragma unroll
  for (int s = 0; s < 8; s++) {
    if ((s & 1) == 0) hmma(t.s, &a[2 * s], 0x3F803F80u, 0x3F803F80u);
    hmma8(t.u, &a[2 * s], a[2 * s]);
    hmma8(t.v, &a[2 * s], a[2 * s + 1]);
  }
}
__device__ __forceinline__ void stat_publish(const uint32_t (&a)[16], uint32_t b, uint32_t th, uint32_t tag) {
  RowAcc t = {};
  row_acc(t, a);
  const bool odd = th & 4;
  if ((th & 3) == ((th >> 3) & 3))
    st_vec(&g_x[b][X_ST + (th >> 2)], (__float_as_uint(t.s[0]) & ~1u) | tag, __float_as_uint(odd ? t.u[1] : t.u[0]),
           __float_as_uint(t.s[2]), __float_as_uint(odd ? t.v[3] : t.v[2]));
}
struct RowNorm { float m0, rs0, m1, rs1; };
__device__ __forceinline__ RowNorm row_norm(float s0, float q0, float s1, float q1, float scale) {
  RowNorm n;
  n.m0 = s0 * (1.f / DM); n.m1 = s1 * (1.f / DM);
  n.rs0 = scale * rsqrtf(fmaxf(fmaf(-n.m0, n.m0, q0 * (1.f / DM)), 0.f) + LN_EPS);
  n.rs1 = scale * rsqrtf(fmaxf(fmaf(-n.m1, n.m1, q1 * (1.f / DM)), 0.f) + LN_EPS);
  return n;
}
__device__ __forceinline__ RowNorm stat_gather(uint32_t b, uint32_t th, uint32_t tag, float scale) {
  const uint4* src = &g_x[b & ~3u][X_ST + (th >> 2)];
  uint32_t v[16], spin = 0;
  do {
#pragma unroll
    for (int j = 0; j < 4; j++) ld_vec(src + j * X_SIZE, v[4 * j], v[4 * j + 1], v[4 * j + 2], v[4 * j + 3]);
  } while (stale(miss(v, tag)) && ++spin < SPIN_LIMIT);
  float f[4];
#pragma unroll
  for (int i = 0; i < 4; i++)
    f[i] = (__uint_as_float(v[i]) + __uint_as_float(v[4 + i])) + (__uint_as_float(v[8 + i]) + __uint_as_float(v[12 + i]));
  return row_norm(f[0], f[1], f[2], f[3], scale);
}
constexpr uint32_t SM_NORM = SM_BASE + SM_STG + 2 * TILE_BYTES + 4096;
__device__ __forceinline__ void norm_produce(uint32_t th, uint32_t tag, float scale, uint32_t qsel) {
  const RowNorm n = stat_gather(blockIdx.x, th, tag, scale);
  const bool sel = (th & 3) == qsel;
  const float a = sel ? -n.m0 : 0.f, c = sel ? -n.m1 : 0.f;
  const uint32_t ah = pack2(a, a), ch = pack2(c, c);
  const float al = a - bf_lo(ah), cl = c - bf_lo(ch);
  sts128(SM_NORM + th * 16, ah, ch, pack2(al, al), pack2(cl, cl));
  sts64(SM_NORM + 2048 + th * 8, __float_as_uint(n.rs0), __float_as_uint(n.rs1));
  bar_arrive(BAR_ST, 256);
}
__device__ __forceinline__ void norm_consume(uint32_t th, uint32_t (&mu)[4], float& rs0, float& rs1) {
  bar_sync(BAR_ST, 256);
  lds128(SM_NORM + th * 16, mu[0], mu[1], mu[2], mu[3]);
  asm volatile("ld.shared.v2.f32 {%0, %1}, [%2];" : "=f"(rs0), "=f"(rs1) : "r"(SM_NORM + 2048 + th * 8) : "memory");
}
__device__ __forceinline__ void scale_pack(const float (&d)[32], uint32_t (&a)[16], float rs0, float rs1) {
#pragma unroll
  for (int i = 0; i < 16; i++) { const float rs = (i & 1) ? rs1 : rs0; a[i] = pack2(d[2 * i] * rs, d[2 * i + 1] * rs); }
}
template <int I0, int I1> __device__ __forceinline__ void silu_part(const float (&d)[32], uint32_t (&h)[16], float rs0, float rs1) {
#pragma unroll
  for (int i = I0; i < I1; i++) {
    const float rs = (i & 1) ? rs1 : rs0, a = d[2 * i] * rs, b = d[2 * i + 1] * rs;
    h[i] = pack2(fmaf(a, tanh_hw(a), a), fmaf(b, tanh_hw(b), b));
  }
}
template <int F, int N> __device__ __forceinline__ void send_residual(uint32_t (&a)[16], uint32_t xoff, uint32_t res, uint32_t tag) {
  const uint32_t exact[4] = {a[0], a[4], a[8], a[12]};
  publish(&g_x[0][X_AG0] + xoff, a, tag);
  acquire_n<F, N>();
  stat_publish(a, blockIdx.x, xoff & 127, tag);
  res_store(res, a);
#pragma unroll
  for (int s = 0; s < 4; s++) sts32(res + s * 512, exact[s]);
  pin(a);
}
template <int F, int NEXT> __device__ __forceinline__ void proj_residual(uint32_t (&A)[4][16], uint32_t xoff, uint32_t res,
                                                               uint32_t r, uint32_t tag, int lane) {
  float acc[32];
  publish(&g_x[0][X_AG1] + xoff, A[0], tag);
  acquire_n<F, 2>();
  res_load(res, acc);
  const uint32_t flip = (r & 1) * 512;
  mma_tile<false>(acc, A[0], flip + LO(F));
  gather(A, xoff + X_AG1, tag);
  PROF_MARK(F == F_WO ? 11 : 16);
  mma_tile<false>(acc, A[1], HI(F) - flip);
  mma_tile<false>(acc, A[2], flip + LO(F + 1));
  mma_tile<false>(acc, A[3], HI(F + 1) - flip);
  WG_WAIT(0); pin(acc);
  pack_acc(acc, A[0]);
  send_residual<F + 2, NEXT>(A[0], xoff, res, tag);
}

__device__ __forceinline__ void qk_tile(float (&S)[32], const uint32_t (&Q)[16], uint64_t dk) {
#pragma unroll
  for (int s = 0; s < 4; s++) {
    if (s == 0) wgmma64_set<0>(S, &Q[0], dk); else wgmma64_acc<0>(S, &Q[4 * s], dk + s * 2);
  }
}
__device__ __forceinline__ void qk_shift(float (&S)[32], const uint32_t (&nm)[4]) { wgmma64_acc<0>(S, nm, (uint64_t)((SM_BASE + SM_ONE) >> 4)); }
constexpr uint64_t V_STEP = uint64_t(1) - (uint64_t(1) << 16);
constexpr uint64_t RING_V = RING - (uint64_t(1) << 16) + ((uint64_t)((SM_STG + 2 * TILE_BYTES) >> 4) << 16);
__device__ __forceinline__ void pv_tile(float (&O)[36], const uint32_t (&P)[16], uint64_t dv, uint64_t pad) {
#pragma unroll
  for (int s = 0; s < 4; s++) wgmma72_acc(O, &P[4 * s], dv + s * 128 * V_STEP + (s < 2 ? 0 : (s - 1) * pad));
}
__device__ __forceinline__ void attn_step(const float (&Sc)[32], float (&Sn)[32], uint32_t (&Pc)[16], uint32_t (&Pp)[16], float (&O)[36],
                                          const uint32_t (&Q)[16], const uint32_t (&nm)[4], uint64_t dk, uint64_t dv) {
  WG_FENCE();
  qk_tile(Sn, Q, dk);
  qk_shift(Sn, nm);
  pv_tile(O, Pp, dv, 0);
  WG_COMMIT();
  SCHED();
#pragma unroll
  for (int i = 0; i < 16; i++) Pc[i] = pack2(ex2_hw(Sc[2 * i]), ex2_hw(Sc[2 * i + 1]));
  pin(Pc);
  SCHED();
}
template <int R> __device__ __forceinline__ float tile_max(const float (&S)[32]) {
  float t[4];
#pragma unroll
  for (int j = 0; j < 4; j++) t[j] = fmaxf(fmaxf(S[8 * j + R], S[8 * j + R + 1]), fmaxf(S[8 * j + R + 4], S[8 * j + R + 5]));
  float n = fmaxf(fmaxf(t[0], t[1]), fmaxf(t[2], t[3]));
  n = fmaxf(n, __shfl_xor_sync(0xffffffffu, n, 1));
  return fmaxf(n, __shfl_xor_sync(0xffffffffu, n, 2));
}
__device__ __forceinline__ void attention_exact(float (&O)[36], const uint32_t (&Q)[16], int bh, int lane) {
  const char* kb = (const char*)&g_kv[bh][0][0][0];
  const char* vb = (const char*)&g_kv[bh][1][0][0];
  const int g = lane >> 2, q = lane & 3;
  float m0 = -INFINITY, m1 = -INFINITY, l0 = 0.f, l1 = 0.f;
  float o[8][4] = {};
#pragma unroll 1
  for (int k0 = 0; k0 < T_SEQ; k0 += 8) {
    float s[4] = {0.f, 0.f, 0.f, 0.f};
#pragma unroll
    for (int c = 0; c < 8; c++) hmma8(s, &Q[2 * c], __ldcg((const uint32_t*)(kb + (k0 + g) * 128 + ((c ^ g) << 4) + q * 4)));
    float n0 = fmaxf(s[0], s[1]), n1 = fmaxf(s[2], s[3]);
    n0 = fmaxf(n0, __shfl_xor_sync(0xffffffffu, n0, 1)); n1 = fmaxf(n1, __shfl_xor_sync(0xffffffffu, n1, 1));
    n0 = fmaxf(m0, fmaxf(n0, __shfl_xor_sync(0xffffffffu, n0, 2))); n1 = fmaxf(m1, fmaxf(n1, __shfl_xor_sync(0xffffffffu, n1, 2)));
    const float a0 = ex2_hw(m0 - n0), a1 = ex2_hw(m1 - n1);
    m0 = n0; m1 = n1;
    const uint32_t pp[2] = {pack2(ex2_hw(s[0] - n0), ex2_hw(s[1] - n0)), pack2(ex2_hw(s[2] - n1), ex2_hw(s[3] - n1))};
    l0 = fmaf(l0, a0, bf_lo(pp[0]) + bf_hi(pp[0])); l1 = fmaf(l1, a1, bf_lo(pp[1]) + bf_hi(pp[1]));
#pragma unroll
    for (int j = 0; j < 8; j++) {
      const uint32_t v0 = __ldcg((const uint16_t*)(vb + (k0 + 2 * q) * 128 + ((j ^ (2 * q)) << 4) + g * 2));
      const uint32_t v1 = __ldcg((const uint16_t*)(vb + (k0 + 2 * q + 1) * 128 + ((j ^ (2 * q + 1)) << 4) + g * 2));
      o[j][0] *= a0; o[j][1] *= a0; o[j][2] *= a1; o[j][3] *= a1;
      hmma8(o[j], pp, v0 | (v1 << 16));
    }
  }
  l0 += __shfl_xor_sync(0xffffffffu, l0, 1); l1 += __shfl_xor_sync(0xffffffffu, l1, 1);
  O[32] = l0 + __shfl_xor_sync(0xffffffffu, l0, 2); O[34] = l1 + __shfl_xor_sync(0xffffffffu, l1, 2);
#pragma unroll
  for (int i = 0; i < 32; i++) O[i] = o[i >> 2][i & 3];
}

__device__ __forceinline__ uint32_t fill_entry(int f, int r, int bh) {
  int m, x = r, y, z = 0;
  if (f < F_QKV || f >= 48) {
    const int i = f & 15;
    m = f < F_QKV ? M_FF1A : M_FF2A;
    if (i < 8) {
      const int h = i < 2 ? i : (i >= 5), c = i < 2 ? 0 : i - 1 - 3 * h;
      x = 0; y = r ^ c; z = 4 * r + 2 * h;
    } else {
      m++; x = r ^ (((i >> 1) - 3) & 3); y = 4 * r + 2 * (i & 1);
    }
  } else if (f < F_KV) {
    const int i = f - F_QKV;
    if (i == 1 || i >= 5) { m = M_WQ; y = (r & 2) ^ (i == 1 ? 0 : 2); }
    else { m = M_WKV; y = r ^ (i ? i - 1 : 0); z = 1; }
  } else if (f < F_WO) {
    const int i = f - F_KV;
    m = M_KV; x = 0; y = bh * 32 + (i & 2) * 8 + (i >> 2) * 4 + (i & 1) * 2;
  } else if (f >= F_PW1 && f < F_PW2) {
    m = M_PW1; y = r ^ (f - F_PW1);
  } else {
    m = f < F_PW1 ? M_WO : M_PW2; y = (r & 2) ^ ((f & 1) * 2);
  }
  return m | (x << 4) | (y << 8) | (z << 16);
}
__device__ __forceinline__ void tma_fill(uint32_t st, const CUtensorMap* map, uint32_t x, uint32_t y, uint32_t z) {
  asm volatile("{\n.reg .pred p;\nelect.sync _|p, 0xffffffff;\n"
               "@p mbarrier.arrive.expect_tx.shared::cta.b64 _, [%1], 16384;\n"
               "@p cp.async.bulk.tensor.3d.shared::cluster.global.mbarrier::complete_tx::bytes [%0], [%2, {%3, %4, %5}], [%1];\n}"
               :: "r"(SM_BASE + st * STAGE_BYTES), "r"(SM_BASE + SM_FULL + st * 8), "l"(map), "r"(x), "r"(y), "r"(z) : "memory");
}
__device__ __forceinline__ void l2_prefetch(const void* p, uint32_t total, int b) {
  const uint32_t part = total / NCTA;
  asm volatile("cp.async.bulk.prefetch.L2.global [%0], %1;" :: "l"((const char*)p + (size_t)b * part), "r"(part) : "memory");
}

__global__ void __launch_bounds__(384, 1) conformer_kernel(const __grid_constant__ Params p) {
  extern __shared__ __align__(1024) uint8_t smem[];
  const int tid = threadIdx.x, lane = tid & 31;
  const int cw = __shfl_sync(0xffffffffu, tid >> 5, 0), wg = cw >> 2, w = cw & 3;
  const int b = blockIdx.x, r = b & 3, batch = b >> 6, t = (b >> 2) & 15;
  if ((uint32_t)__cvta_generic_to_shared(smem) != SM_BASE) return;
  PROF_MARK(0);
  PROF_TIME(30);

  if (cw == 8) {
    if (lane == 0) {
      asm volatile("prefetch.tensormap [%0];" :: "l"(&p.map[M_X]) : "memory");
      asm volatile("prefetch.tensormap [%0];" :: "l"(&p.map[M_FF1A]) : "memory");
      mbar_init(SM_BASE + SM_XBAR, 1);
#pragma unroll
      for (int i = 0; i < NSTAGE; i++) mbar_init(SM_BASE + SM_FULL + i * 8, 1);
      fence_async_smem();
    }
    __syncwarp();
    asm volatile("{\n.reg .pred p;\nelect.sync _|p, 0xffffffff;\n"
                 "@p mbarrier.arrive.expect_tx.shared::cta.b64 _, [%1], 32768;\n"
                 "@p cp.async.bulk.tensor.4d.shared::cluster.global.mbarrier::complete_tx::bytes [%0], [%2, {0, %3, 0, %4}], [%1];\n}"
                 :: "r"(SM_BASE + SM_STG), "r"(SM_BASE + SM_XBAR), "l"(&p.map[M_X]), "r"(t * 64), "r"(batch) : "memory");
    bar_arrive(0, 352);
  } else if (cw == 9) {
    if (lane == 0) {
#pragma unroll
      for (int i = 0; i < NSTAGE; i++) mbar_init(SM_BASE + SM_EMPTY + i * 8, 4);
    }
    __syncwarp();
    bar_arrive(0, 352);
    bar_arrive(BAR_INIT, 64);
  } else if (cw != 10) {
    if (tid < 144) sts128(SM_BASE + SM_CS + tid * 16, 0, 0, 0, 0);
    if (wg == 1) {
      const int i = tid - 128;
      sts32(SM_BASE + SM_EYE + i * 4, i >= 96 ? 0x3F803F80u : ((i & 32) == 0 && (i & 3) == ((i >> 3) & 3)) ? (0x3F00u << ((i & 4) * 4)) : 0u);
    }
    fence_async_smem();
    bar_sync(0, 352);
  }

  if (wg == 2) {
    asm volatile("setmaxnreg.dec.sync.aligned.u32 40;");
    if (w == 0) {
#pragma unroll 1
      for (int f = 0; f < 8; f++)
        tma_fill(f, &p.map[M_FF1A], 0, (r ^ ((0xE790u >> (2 * f)) & 3)) * 64, 4 * r + ((0xE2u >> f) & 1) * 2);
      PROF_MARK(1);
      const uint32_t* flag = &g_flag[batch * 4 + r][lane];
      const uint32_t prev = ((volatile uint32_t*)g_epoch)[b];
      uint32_t entry[2], ready = 0, st = 8, parity = 1;
#pragma unroll 1
      for (int i = 0; i < 2; i++) { entry[1] = fill_entry(i * 32 + lane, r, batch * 4 + r); if (i == 0) entry[0] = entry[1]; }
      bar_sync(BAR_INIT, 64);
#pragma unroll 1
      for (int f = 8; f < F_TOTAL; f++) {
        const uint32_t e = __shfl_sync(0xffffffffu, f < 32 ? entry[0] : entry[1], f);
        if ((e & 15) == M_KV) {
          const uint32_t need = 3u << ((e >> 8) & 31);
          uint32_t spin = 0;
#pragma unroll 1
          while ((ready & need) != need && ++spin < SPIN_LIMIT) {
            uint32_t v;
            asm volatile("ld.relaxed.gpu.global.u32 %0, [%1];" : "=r"(v) : "l"(flag) : "memory");
            ready = __ballot_sync(0xffffffffu, v - 1 == prev);
          }
        }
        mbar_wait(SM_BASE + SM_EMPTY + st * 8, parity);
        tma_fill(st, &p.map[e & 15], (e << 2) & 0x3C0, (e >> 2) & 0x3FC0, e >> 16);
        if (++st == NSTAGE) { st = 0; parity ^= 1; }
      }
    } else if (w < 3) {
      const int kind = w - 1;
      const uint32_t epoch = ((volatile uint32_t*)g_epoch)[b] + 1;
      if (kind == 0) bar_sync(BAR_K, 160); else bar_sync(BAR_V, 160);
      if (lane == 0) {
        asm volatile("cp.async.bulk.global.shared::cta.bulk_group [%0], [%1], %2;"
                     :: "l"(&g_kv[batch * 4 + r][kind][t][0]), "r"(SM_BASE + SM_STG + kind * TILE_BYTES), "r"(TILE_BYTES) : "memory");
        asm volatile("cp.async.bulk.commit_group;\ncp.async.bulk.wait_group 0;" ::: "memory");
        asm volatile("st.relaxed.gpu.global.u32 [%0], %1;" :: "l"(&g_flag[batch * 4 + r][kind * 16 + t]), "r"(epoch) : "memory");
      }
    } else {
      const uint32_t epoch = ((volatile uint32_t*)g_epoch)[b] + 1;
      if (lane < M_COUNT) asm volatile("prefetch.tensormap [%0];" :: "l"(&p.map[lane]) : "memory");
      if (lane == 0) {
        l2_prefetch(p.w_ff1b, 1024 * 256 * 2, b);
#pragma unroll 1
        for (int i = 0; i < 11; i++) {
          mbar_wait(SM_BASE + SM_FULL + (i >> 1) * 8, 0);
          asm volatile("cp.async.bulk.global.shared::cta.bulk_group [%0], [%1], 1536;"
                       :: "l"(&g_x[b][X_CLEAR + i * 96]), "r"(SM_BASE + SM_CS) : "memory");
        }
        asm volatile("cp.async.bulk.commit_group;\ncp.async.bulk.wait_group 0;" ::: "memory");
        asm volatile("st.relaxed.gpu.global.u32 [%0], %1;" :: "l"(&g_ready[b]), "r"(epoch) : "memory");
        l2_prefetch(p.w_o, 256 * 256 * 2, b);
        l2_prefetch(p.w_pw2, 256 * 256 * 2, b);
        l2_prefetch(p.w_ff2b, 1024 * 256 * 2, b);
        uint32_t e[4], spin = 0;
#pragma unroll 1
        do {
          ld_vec((const uint4*)&g_ready[b & ~3], e[0], e[1], e[2], e[3]);
        } while ((e[0] != epoch || e[1] != epoch || e[2] != epoch || e[3] != epoch) && ++spin < SPIN_LIMIT);
      }
      __syncwarp();
      bar_arrive(BAR_RDY, 160);
      bar_arrive(BAR_RDY1, 160);
    }
  } else {
    asm volatile("setmaxnreg.inc.sync.aligned.u32 232;");
    const int q = lane & 3, th = tid & 127;
    constexpr uint32_t stg = SM_BASE + SM_STG;
    const uint32_t mrow = 16 * w + (lane & 15);
    const uint32_t maddr = stg + mrow * 128 + (((lane >> 4) ^ (lane & 7)) << 4);
    const uint32_t res = stg + 3 * TILE_BYTES + w * 2048 + lane * 16;
    const uint32_t xoff = b * X_SIZE + th;
    const int nvalid = T_SEQ - t * 64, row0 = 16 * w + (lane >> 2);

    uint32_t A[4][16];
    uint32_t mu[4] = {0u, 0u, 0u, 0u};
    float rs0, rs1;
    if (wg == 0) {
      mbar_wait(SM_BASE + SM_XBAR, 0);
      PROF_MARK(1);
      RowAcc ra = {}, rb = {};
#pragma unroll
      for (int c = 0; c < 4; c++) {
        tile_load(maddr + (r ^ c) * TILE_BYTES, A[c]);
        row_acc((c & 1) ? rb : ra, A[c]);
      }
      __syncwarp();
      res_store(res, A[0]);
      const float s0 = ra.s[0] + rb.s[0], s1 = ra.s[2] + rb.s[2];
      const uint32_t m0 = pack2(s0 * (1.f / DM), s0 * (1.f / DM)), m1 = pack2(s1 * (1.f / DM), s1 * (1.f / DM));
#pragma unroll
      for (int c = 0; c < 4; c++) {
#pragma unroll
        for (int i = 0; i < 16; i++) asm("sub.rn.bf16x2 %0, %0, %1;" : "+r"(A[c][i]) : "r"((i & 1) ? m1 : m0));
        pin(A[c]);
      }
      const bool odd = lane & 4;
      const int src = (lane & 28) | (lane >> 3);
      const float q0 = __shfl_sync(0xffffffffu, odd ? ra.u[1] + rb.u[1] : ra.u[0] + rb.u[0], src);
      const float q1 = __shfl_sync(0xffffffffu, odd ? ra.v[3] + rb.v[3] : ra.v[2] + rb.v[2], src);
      const RowNorm n = row_norm(s0, q0, s1, q1, 0.5f);
      rs0 = n.rs0; rs1 = n.rs1;
    } else {
      const uint32_t epoch = ((volatile uint32_t*)g_epoch)[b] + 1, tag = epoch & 1;
      mbar_wait(SM_BASE + SM_XBAR, 0);
      if (b < 72) {
        const __nv_bfloat16* wp; int ld, col;
        if (b < 24) { wp = p.w_qkv; ld = 768; col = b * 32; }
        else if (b < 40) { wp = p.w_pw1; ld = 512; col = (b - 24) * 32; }
        else { wp = p.w_ff2a; ld = 1024; col = (b - 40) * 32; }
        const uint4* src = (const uint4*)(wp + (size_t)(th >> 2) * ld + col + q * 8);
        float c[8] = {0.f, 0.f, 0.f, 0.f, 0.f, 0.f, 0.f, 0.f};
#pragma unroll 1
        for (int h = 0; h < 2; h++) {
#pragma unroll
          for (int i = 0; i < 4; i++) {
            const uint4 v = __ldg(src + i * 4 * ld);
            c[0] += bf_lo(v.x); c[1] += bf_hi(v.x); c[2] += bf_lo(v.y); c[3] += bf_hi(v.y);
            c[4] += bf_lo(v.z); c[5] += bf_hi(v.z); c[6] += bf_lo(v.w); c[7] += bf_hi(v.w);
          }
          src += 16 * ld;
        }
#pragma unroll 1
        for (int m = 4; m <= 16; m <<= 1)
#pragma unroll
          for (int k = 0; k < 8; k++) c[k] += __shfl_xor_sync(0xffffffffu, c[k], m);
        if (lane < 4) {
          const uint32_t a = SM_BASE + SM_CS + 1792 + w * 128 + lane * 32;
          sts128(a, __float_as_uint(c[0]), __float_as_uint(c[1]), __float_as_uint(c[2]), __float_as_uint(c[3]));
          sts128(a + 16, __float_as_uint(c[4]), __float_as_uint(c[5]), __float_as_uint(c[6]), __float_as_uint(c[7]));
        }
        bar_sync(BAR_WG1, 128);
        if (th < 8) {
          float o[4] = {0.f, 0.f, 0.f, 0.f};
#pragma unroll 1
          for (int k = 0; k < 4; k++) {
            uint32_t e[4];
            lds128(SM_BASE + SM_CS + 1792 + k * 128 + th * 16, e[0], e[1], e[2], e[3]);
#pragma unroll
            for (int i = 0; i < 4; i++) o[i] += __uint_as_float(e[i]);
          }
          st_vec(&g_cs[b * 8 + th], (__float_as_uint(o[0]) & ~1u) | tag, __float_as_uint(o[1]), __float_as_uint(o[2]), __float_as_uint(o[3]));
        }
      }
      PROF_MARK(1);
      bar_sync(BAR_RDY1, 160);
      PROF_MARK(3);
#pragma unroll 1
      for (int i = th; i < 144; i += 128) {
        const int j = i >> 4;
        int src;
        if (j < CS_PW1) src = 320 + 64 * r + i;
        else if (j < CS_QKV) src = 192 + (j - CS_PW1) * 64 + 16 * r + (i & 15);
        else src = ((j - CS_QKV + 1) % 3) * 64 + 16 * r + (i & 15);
        uint32_t e[4], spin = 0;
#pragma unroll 1
        do {
          ld_vec(&g_cs[src], e[0], e[1], e[2], e[3]);
        } while (((e[0] ^ tag) & 1u) && ++spin < SPIN_LIMIT);
        const float c0 = __uint_as_float(e[0] & ~1u), c1 = __uint_as_float(e[1]), c2 = __uint_as_float(e[2]), c3 = __uint_as_float(e[3]);
        const uint32_t h0 = pack2(c0, c1), h1 = pack2(c2, c3);
        const uint32_t a = SM_BASE + SM_CS + j * 256 + (i & 15) * 8;
        sts64(a ^ ((a >> 3) & 0x70), h0, h1);
        sts64((a + 128) ^ (((a + 128) >> 3) & 0x70), pack2(c0 - bf_lo(h0), c1 - bf_hi(h0)), pack2(c2 - bf_lo(h1), c3 - bf_hi(h1)));
      }
      fence_async_smem();
      PROF_MARK(4);
      norm_produce(th, 1, 1.f, 3);
    }

#pragma unroll 1
    for (uint32_t pass = 0; pass < 2; pass++) {
      uint32_t Q[16];
      if (wg == 0) {
        float acc[4][32];
        uint32_t H[4][16];
        ACQUIRE(0);
        mma_tile<true>(acc[0], A[0], LO(0)); mma_tile<true>(acc[1], A[0], HI(0));
        ACQUIRE(1);
        mma_tile<true>(acc[2], A[0], LO(1)); mma_tile<true>(acc[3], A[0], HI(1));
        acquire_n<2, 3>();
        if (pass) gather(A, here(xoff) + X_AG0, 1);
        PROF_MARK(2 + pass * 16);
        mma_tile<false>(acc[0], A[1], LO(2)); mma_tile<false>(acc[0], A[2], LO(3));
        WG_WAIT(2);
        if (pass) {
          RELEASE(F_PW2, F_PW2 + 1);
          norm_consume(here(th), mu, rs0, rs1);
        }
        RELEASE(0, 1);
        mma_tile_fold<2 * CS_FF2>(acc[0], A[3], LO(4), mu);
        acquire_n<5, 3>();
        mma_tile<false>(acc[1], A[1], HI(2)); mma_tile<false>(acc[1], A[2], HI(3));
        WG_WAIT(2); pin(acc[0]);
        silu_part<0, 8>(acc[0], H[0], rs0, rs1);
        mma_tile_fold<2 * CS_FF2 + 2>(acc[1], A[3], HI(4), mu);
        silu_part<8, 16>(acc[0], H[0], rs0, rs1);
        mma_tile<false>(acc[2], A[1], LO(5)); mma_tile<false>(acc[2], A[2], LO(6));
        WG_WAIT(2); pin(acc[1]);
        RELEASE(2, 4);
        silu_part<0, 8>(acc[1], H[1], rs0, rs1);
        mma_tile_fold<2 * CS_FF2 + 4>(acc[2], A[3], LO(7), mu);
        silu_part<8, 16>(acc[1], H[1], rs0, rs1);
        mma_tile<false>(acc[3], A[1], HI(5)); mma_tile<false>(acc[3], A[2], HI(6));
        WG_WAIT(2); pin(acc[2]);
        silu_part<0, 8>(acc[2], H[2], rs0, rs1);
        mma_tile_fold<2 * CS_FF2 + 6>(acc[3], A[3], HI(7), mu);
        silu_part<8, 16>(acc[2], H[2], rs0, rs1);
        pin(H[0]); pin(H[1]); pin(H[2]);
        acquire_n<8, 2>();
        mma_tile<true>(acc[0], H[0], LO(8)); mma_tile<false>(acc[0], H[1], HI(8));
        WG_WAIT(2); pin(acc[3]);
        RELEASE(5, 7);
        silu_part<0, 8>(acc[3], H[3], rs0, rs1);
        mma_tile<false>(acc[0], H[2], LO(9));
        silu_part<8, 16>(acc[3], H[3], rs0, rs1);
        pin(H[3]);
        mma_tile<false>(acc[0], H[3], HI(9));
        PROF_MARK(3 + pass * 16);
        const uint32_t rtag = pass ^ 1;
        const uint4* rs_in = &g_x[0][X_RS] + here(xoff);
#pragma unroll
        for (int c = 1; c < 4; c++) {
          ACQUIRE(8 + 2 * c);
          mma_tile<true>(acc[c], H[0], LO(8 + 2 * c));
          if (c == 3 && !pass) bar_sync(BAR_RDY, 160);
          if (c == 3) fetch(rs_in, A[1]);
          mma_tile<false>(acc[c], H[1], HI(8 + 2 * c));
          WG_WAIT(2); pin(acc[c - 1]);
          uint32_t o[16];
          pack_acc(acc[c - 1], o);
          publish(&g_x[0][X_RS + (c - 1) * 512] + (here(xoff) ^ (c * X_SIZE)), o, rtag);
          ACQUIRE(9 + 2 * c);
          mma_tile<false>(acc[c], H[2], LO(9 + 2 * c));
          if (c == 1) RELEASE(8, 9);
          if (c == 2) res_load(res, acc[0]);
          mma_tile<false>(acc[c], H[3], HI(9 + 2 * c));
        }
        fetch(rs_in + 512, A[2]);
        confirm(rs_in, A[1], rtag);
        mma_add_half(acc[0], A[1]);
        WG_WAIT(1);
        fetch(rs_in + 1024, A[3]);
        confirm(rs_in + 512, A[2], rtag);
        mma_add_half(acc[0], A[2]);
        confirm(rs_in + 1024, A[3], rtag);
        mma_add_half(acc[0], A[3]);
        PROF_MARK(4 + pass * 16);
        WG_WAIT(0); pin(acc[0]); pin(acc[3]);
#pragma unroll
        for (int i = 0; i < 16; i++) A[0][i] = pack2(fmaf(acc[3][2 * i], 0.5f, acc[0][2 * i]), fmaf(acc[3][2 * i + 1], 0.5f, acc[0][2 * i + 1]));
        if (pass) {
          PROF_MARK(21);
          stat_publish(A[0], b, here(th), 0);
          const RowNorm fn = stat_gather(b, here(th), 0, 1.f);
          const float nm0 = -fn.m0 * fn.rs0, nm1 = -fn.m1 * fn.rs1;
#pragma unroll
          for (int i = 0; i < 16; i++) {
            const float rs = (i & 1) ? fn.rs1 : fn.rs0, nm = (i & 1) ? nm1 : nm0;
            A[0][i] = pack2(fmaf(bf_lo(A[0][i]), rs, nm), fmaf(bf_hi(A[0][i]), rs, nm));
          }
          tile_store(here(maddr), A[0]);
          __syncwarp();
          const int row = 16 * w + (lane >> 3);
          uint4* dst = (uint4*)(p.out + ((size_t)batch * T_SEQ + t * 64 + row) * DM + 64 * r) + (lane & 7);
          const uint32_t src = stg + row * 128 + (((lane & 7) ^ (lane >> 3)) << 4);
#pragma unroll
          for (int i = 0; i < 4; i++) {
            uint4 v;
            lds128((src ^ ((i & 1) << 6)) + i * 512, v.x, v.y, v.z, v.w);
            if (row + 4 * i < nvalid) dst[i * 4 * (DM / 8)] = v;
          }
          PROF_MARK(22);
          PROF_TIME(31);
          break;
        }
        send_residual<F_QKV, 6>(A[0], here(xoff), res, 1);
        PROF_MARK(5);
        const uint32_t flip = (r & 1) * 512;
        mma_tile<true>(acc[0], A[0], LO(F_QKV)); mma_tile<true>(acc[1], A[0], HI(F_QKV));
        mma_tile<true>(acc[2], A[0], flip + LO(F_QKV + 1));
        gather(A, here(xoff) + X_AG0, 1);
        PROF_MARK(6);
        mma_tile<false>(acc[0], A[1], LO(F_QKV + 2)); mma_tile<false>(acc[0], A[2], LO(F_QKV + 3));
        RELEASE(10, 15);
        norm_consume(here(th), mu, rs0, rs1);
        if (row0 >= nvalid) rs0 = 0.f;
        if (row0 + 8 >= nvalid) rs1 = 0.f;
        mma_tile_fold<2 * CS_QKV - 6>(acc[0], A[3], LO(F_QKV + 4), mu);
        mma_tile<false>(acc[1], A[1], HI(F_QKV + 2)); mma_tile<false>(acc[1], A[2], HI(F_QKV + 3));
        WG_WAIT(2); pin(acc[0]);
        scale_pack(acc[0], Q, rs0, rs1);
        tile_store(here(maddr), Q);
        fence_async_smem();
        bar_arrive(BAR_K, 160);
        mma_tile_fold<2 * CS_QKV - 4>(acc[1], A[3], HI(F_QKV + 4), mu);
        mma_tile<false>(acc[2], A[1], HI(F_QKV + 1) - flip); mma_tile<false>(acc[2], A[2], flip + LO(F_QKV + 5));
        WG_WAIT(2); pin(acc[1]);
        scale_pack(acc[1], Q, rs0, rs1);
        tile_store(here(maddr) + TILE_BYTES, Q);
        fence_async_smem();
        bar_arrive(BAR_V, 160);
        mma_tile_fold<2 * CS_QKV - 2>(acc[2], A[3], HI(F_QKV + 5) - flip, mu);
        WG_WAIT(0); pin(acc[2]);
        scale_pack(acc[2], Q, rs0 * SM_SCALE_LOG2, rs1 * SM_SCALE_LOG2);
        res_store(here(res) - TILE_BYTES, Q);
        bar_arrive(BAR_Q, 256);
        acquire_n<F_SPARE, 2>();
        RELEASE(F_QKV, F_SPARE + 1);
      } else {
        bar_sync(BAR_Q, 256);
#pragma unroll
        for (int s = 0; s < 4; s++) lds128(res - TILE_BYTES + s * 512, Q[4 * s], Q[4 * s + 1], Q[4 * s + 2], Q[4 * s + 3]);
        if (w < 2) {
          const uint32_t v = w ? 0u : 0x3F803F80u;
#pragma unroll
          for (int s = 0; s < 4; s++) sts128(res - TILE_BYTES + s * 512, v, v, v, v);
          fence_async_smem();
        }
      }
      bar_sync(BAR_ATT, 256);
      PROF_MARK(7);

      float O[36];
      {
        float S[2][32];
        uint32_t P[2][16], nm[4];
        pin(Q);
        WG_FENCE();
        qk_tile(S[0], Q, RING + (SM_STG >> 4));
        WG_COMMIT();
#pragma unroll
        for (int i = 0; i < 36; i++) O[i] = 0.f;
#pragma unroll
        for (int i = 0; i < 16; i++) P[1][i] = 0u;
        WG_WAIT(0); pin(S[0]);
        const float m0 = tile_max<0>(S[0]), m1 = tile_max<2>(S[0]);
        nm[0] = pack2(q ? 0.f : -m0, 0.f); nm[1] = pack2(q ? 0.f : -m1, 0.f); nm[2] = 0u; nm[3] = 0u;
        pin(nm); pin(O); pin(P[1]);
        uint32_t sk = wg, sv = wg;
        mbar_wait(SM_BASE + SM_FULL + sk * 8, 0);
        PROF_MARK(8);
        WG_FENCE();
        qk_tile(S[0], Q, RING + sk * 1024);
        qk_shift(S[0], nm);
        WG_COMMIT();
        WG_WAIT(0); pin(S[0]);
#pragma unroll 1
        for (int it = 0; it < 4; it++) {
          attn_step(S[0], S[1], P[0], P[1], O, Q, nm, RING + sk * 1024 + 512, RING_V + (sv * 1024 + 512) * V_STEP);
          const uint32_t sn = it >= 2 ? wg : sk + 4;
          mbar_wait(SM_BASE + SM_FULL + sn * 8, it >= 2);
          mbar_wait(SM_BASE + SM_FULL + (sk + 2) * 8, it == 3);
          WG_WAIT(0); pin(O); pin(S[1]); pin(P[1]);
          if (lane == 0 && it < 3) {
            mbar_arrive(SM_BASE + SM_EMPTY + sk * 8);
            if (it) mbar_arrive(SM_BASE + SM_EMPTY + sv * 8);
          }
          sv = sk + 2; sk = sn;
          attn_step(S[1], S[0], P[1], P[0], O, Q, nm, RING + sk * 1024, RING_V + (sv * 1024) * V_STEP);
          WG_WAIT(0); pin(O); pin(S[0]); pin(P[0]);
        }
        WG_FENCE();
        pv_tile(O, P[1], RING_V + (sv * 1024 + 512) * V_STEP, (uint64_t)wg << 22);
        WG_COMMIT();
        WG_WAIT(0); pin(O);
      }
      PROF_MARK(9);

      if (wg == 1) {
        const uint32_t mo = stg + here(th) * 16;
#pragma unroll
        for (int i = 0; i < 9; i++)
          sts128(mo + i * 2048 + (i >> 3) * 4096, __float_as_uint(O[4 * i]), __float_as_uint(O[4 * i + 1]), __float_as_uint(O[4 * i + 2]), __float_as_uint(O[4 * i + 3]));
        bar_arrive(BAR_MERGE, 256);
        norm_produce(here(th), 0, 0.5f, 0);
      } else {
        const uint32_t mo = stg + here(th) * 16;
        bar_sync(BAR_MERGE, 256);
#pragma unroll
        for (int i = 8; i >= 0; i--) {
          uint32_t e[4];
          lds128(mo + i * 2048 + (i >> 3) * 4096, e[0], e[1], e[2], e[3]);
#pragma unroll
          for (int k = 0; k < 4; k++) O[4 * i + k] += __uint_as_float(e[k]);
        }
        const bool safe = O[32] > 0x1p-60f && O[32] < 0x1p60f && O[34] > 0x1p-60f && O[34] < 0x1p60f;
        if (__builtin_expect(__any_sync(0xffffffffu, !safe), 0)) attention_exact(O, Q, batch * 4 + r, lane);
        const float i0 = rcp_hw(O[32]), i1 = rcp_hw(O[34]);
#pragma unroll
        for (int i = 0; i < 16; i++) { const float v = (i & 1) ? i1 : i0; A[0][i] = pack2(O[2 * i] * v, O[2 * i + 1] * v); }
        PROF_MARK(10);
        proj_residual<F_WO, 4>(A, here(xoff), res, r, 0, lane);
        PROF_MARK(12);
      }

      const int dir = cw == 0 ? -1 : 1;
      uint32_t tap[15];
      {
        const uint32_t* dwp = (const uint32_t*)(p.dw + 64 * r) + lane + 7 * (DM / 2);
#pragma unroll
        for (int k = 0; k < 15; k++) tap[k] = __ldg(dwp + dir * (k - 7) * (DM / 2));
      }

      if (wg == 0) {
        float acc[2][32];
        mma_tile<true>(acc[0], A[0], LO(F_PW1)); mma_tile<true>(acc[1], A[0], HI(F_PW1));
        gather(A, here(xoff) + X_AG0, 0);
        PROF_MARK(13);
        mma_tile<false>(acc[1], A[1], HI(F_PW1 + 1)); mma_tile<false>(acc[1], A[2], HI(F_PW1 + 2));
        RELEASE(F_KV + 10, F_WO + 1);
        norm_consume(here(th), mu, rs0, rs1);
        if (row0 >= nvalid) rs0 = 0.f;
        if (row0 + 8 >= nvalid) rs1 = 0.f;
        mma_tile_fold<2 * CS_PW1 + 2>(acc[1], A[3], HI(F_PW1 + 3), mu);
        mma_tile<false>(acc[0], A[1], LO(F_PW1 + 1)); mma_tile<false>(acc[0], A[2], LO(F_PW1 + 2));
        WG_WAIT(2); pin(acc[1]);
#pragma unroll
        for (int i = 0; i < 16; i++) acc[1][i] = tanh_hw(acc[1][i] * ((i & 2) ? rs1 : rs0));
        mma_tile_fold<2 * CS_PW1>(acc[0], A[3], LO(F_PW1 + 3), mu);
#pragma unroll
        for (int i = 16; i < 32; i++) acc[1][i] = tanh_hw(acc[1][i] * ((i & 2) ? rs1 : rs0));
#pragma unroll
        for (int i = 0; i < 32; i++) { const float rs = (i & 2) ? rs1 : rs0; acc[1][i] = fmaf(acc[1][i], rs, rs); }
        pin(acc[1]);
        WG_WAIT(0); pin(acc[0]);
#pragma unroll
        for (int i = 0; i < 16; i++) A[0][i] = pack2(acc[0][2 * i] * acc[1][2 * i], acc[0][2 * i + 1] * acc[1][2 * i + 1]);
        const uint32_t ga = stg + TILE_BYTES + here(mrow) * G_PITCH + (lane >> 4) * 16;
#pragma unroll
        for (int s = 0; s < 4; s++) stsm4(ga + s * 32, &A[0][4 * s]);
        RELEASE(F_PW1, F_PW1 + 3);
      }
      bar_sync(BAR_G, 256);
      PROF_MARK(14);

      {
        const int first = cw == 0 ? 14 : 8 * cw - 7;
        const uint32_t gsrc = stg + TILE_BYTES + first * G_PITCH + lane * 4;
        uint32_t in[22];
#pragma unroll
        for (int i = 0; i < 15; i++) in[i] = lds32(gsrc + dir * i * (int)G_PITCH);
        const bool edge = cw == 0 || cw == 7;
        const bool nbr = cw == 0 ? t > 0 : t < 15;
        if (edge) {
          if (nbr) {
            uint4* dst = &g_x[b + 4 * dir][X_HALO + (cw == 0 ? 96 : 0) + lane];
            st_vec(dst, HALO_TAG, in[14], in[13], in[12]);
            st_vec(dst + 32, HALO_TAG, in[11], in[10], in[9]);
            st_vec(dst + 64, HALO_TAG, in[8], 0u, 0u);
          }
        } else {
#pragma unroll
          for (int i = 15; i < 22; i++) in[i] = lds32(gsrc + i * G_PITCH);
        }
        float cl[8], ch[8], tl[15], tv[15];
#pragma unroll
        for (int k = 0; k < 15; k++) { tl[k] = bf_lo(tap[k]); tv[k] = bf_hi(tap[k]); }
#pragma unroll
        for (int o = 0; o < 8; o++) { cl[o] = 0.f; ch[o] = 0.f; }
#pragma unroll
        for (int i = 0; i < 15; i++) {
          const float lo = bf_lo(in[i]), hi = bf_hi(in[i]);
#pragma unroll
          for (int o = 0; o < 8; o++)
            if (i - o >= 0) { cl[o] = fmaf(lo, tl[i - o], cl[o]); ch[o] = fmaf(hi, tv[i - o], ch[o]); }
        }
        if (edge) {
#pragma unroll
          for (int i = 15; i < 22; i++) in[i] = 0u;
          if (nbr) {
            const uint4* src = &g_x[b][X_HALO + (cw == 0 ? 0 : 96) + lane];
            uint32_t e0, e1, e2, u0, u1, spin = 0;
#pragma unroll 1
            do {
              ld_vec(src, e0, in[15], in[16], in[17]);
              ld_vec(src + 32, e1, in[18], in[19], in[20]);
              ld_vec(src + 64, e2, in[21], u0, u1);
            } while (__any_sync(0xffffffffu, ((e0 ^ HALO_TAG) | (e1 ^ HALO_TAG) | (e2 ^ HALO_TAG)) != 0) && ++spin < SPIN_LIMIT);
          }
        }
#pragma unroll
        for (int i = 15; i < 22; i++) {
          const float lo = bf_lo(in[i]), hi = bf_hi(in[i]);
#pragma unroll
          for (int o = 0; o < 8; o++)
            if (i - o <= 14) { cl[o] = fmaf(lo, tl[i - o], cl[o]); ch[o] = fmaf(hi, tv[i - o], ch[o]); }
        }
        const uint32_t fl = cw == 0 ? 7 : 0;
        const uint32_t cdst = (stg + cw * 1024 + lane * 4) ^ (fl * 144);
#pragma unroll
        for (int o = 0; o < 8; o++) {
          const float a = 0.5f * cl[o], c = 0.5f * ch[o];
          sts32(cdst ^ (o * 144), pack2(fmaf(a, tanh_hw(a), a), fmaf(c, tanh_hw(c), c)));
        }
      }
      if (wg == 1) {
        bar_arrive(BAR_C, 256);
        norm_produce(here(th), 1, 0.5f, 0);
        if (th == 0) ((volatile uint32_t*)g_epoch)[b] += 1;
        break;
      }
      bar_sync(BAR_C, 256);
      tile_load(here(maddr), A[0]);
      PROF_MARK(15);
      proj_residual<F_PW2, 1>(A, here(xoff), res, r, 1, lane);
      PROF_MARK(17);
    }
  }
}

typedef CUresult (*EncodeFn)(CUtensorMap*, CUtensorMapDataType, cuuint32_t, void*, const cuuint64_t*, const cuuint64_t*,
                             const cuuint32_t*, const cuuint32_t*, CUtensorMapInterleave, CUtensorMapSwizzle,
                             CUtensorMapL2promotion, CUtensorMapFloatOOBfill);

void make_map(EncodeFn fn, CUtensorMap* m, const void* w, int rank, int d0, int d1, int d2, int d3, int s1, int s2, int s3,
              int b1, int b2, CUtensorMapSwizzle swz) {
  const cuuint64_t dims[4] = {(cuuint64_t)d0, (cuuint64_t)d1, (cuuint64_t)d2, (cuuint64_t)d3};
  const cuuint64_t strides[3] = {(cuuint64_t)s1, (cuuint64_t)s2, (cuuint64_t)s3};
  const cuuint32_t box[4] = {64, (cuuint32_t)b1, (cuuint32_t)b2, 1}, es[4] = {1, 1, 1, 1};
  fn(m, CU_TENSOR_MAP_DATA_TYPE_BFLOAT16, rank, const_cast<void*>(w), dims, strides, box, es, CU_TENSOR_MAP_INTERLEAVE_NONE,
     swz, CU_TENSOR_MAP_L2_PROMOTION_L2_128B, CU_TENSOR_MAP_FLOAT_OOB_FILL_NONE);
}

}

extern "C" void kernel_launch(void* const* d_in, const int* in_sizes, int n_in, void* d_out, int out_size) {
  static EncodeFn fn = nullptr;
  static void* kv = nullptr;
  if (!fn) {
    void* f = nullptr;
    cudaDriverEntryPointQueryResult st;
    cudaGetDriverEntryPoint("cuTensorMapEncodeTiled", &f, cudaEnableDefault, &st);
    fn = (EncodeFn)f;
    cudaGetSymbolAddress(&kv, g_kv);
    cudaFuncSetAttribute(conformer_kernel, cudaFuncAttributeMaxDynamicSharedMemorySize, SM_TOTAL);
  }
  typedef const __nv_bfloat16* W;
  const CUtensorMapSwizzle S = CU_TENSOR_MAP_SWIZZLE_128B;
  Params p;
  make_map(fn, &p.map[M_X], d_in[0], 4, 64, T_SEQ, 4, 2, 512, 128, T_SEQ * 512, 64, 4, S);
  make_map(fn, &p.map[M_FF1A], d_in[1], 3, 64, 256, 16, 1, 2048, 128, 0, 64, 2, S);
  make_map(fn, &p.map[M_FF1B], d_in[2], 3, 256, 1024, 1, 1, 512, 512 * 1024, 0, 128, 1, S);
  make_map(fn, &p.map[M_WKV], d_in[3], 3, 256, 256, 3, 1, 1536, 512, 0, 64, 2, S);
  make_map(fn, &p.map[M_WQ], d_in[3], 3, 256, 256, 3, 1, 1536, 512, 0, 128, 1, S);
  make_map(fn, &p.map[M_KV], kv, 3, 64, 16384, 1, 1, 128, 128 * 16384, 0, 128, 1, CU_TENSOR_MAP_SWIZZLE_NONE);
  make_map(fn, &p.map[M_WO], d_in[4], 3, 256, 256, 1, 1, 512, 512 * 256, 0, 128, 1, S);
  make_map(fn, &p.map[M_PW1], d_in[5], 3, 256, 256, 2, 1, 1024, 512, 0, 64, 2, S);
  make_map(fn, &p.map[M_PW2], d_in[7], 3, 256, 256, 1, 1, 512, 512 * 256, 0, 128, 1, S);
  make_map(fn, &p.map[M_FF2A], d_in[8], 3, 64, 256, 16, 1, 2048, 128, 0, 64, 2, S);
  make_map(fn, &p.map[M_FF2B], d_in[9], 3, 256, 1024, 1, 1, 512, 512 * 1024, 0, 128, 1, S);
  p.w_ff1b = (W)d_in[2]; p.w_qkv = (W)d_in[3]; p.w_o = (W)d_in[4]; p.w_pw1 = (W)d_in[5];
  p.dw = (W)d_in[6]; p.w_pw2 = (W)d_in[7]; p.w_ff2a = (W)d_in[8]; p.w_ff2b = (W)d_in[9];
  p.out = (__nv_bfloat16*)d_out;

  cudaLaunchConfig_t cfg = {};
  cfg.gridDim = dim3(NCTA);
  cfg.blockDim = dim3(384);
  cfg.dynamicSmemBytes = SM_TOTAL;
  cfg.stream = cudaStreamPerThread;
  cudaLaunchAttribute at[1];
  at[0].id = cudaLaunchAttributeCooperative;
  at[0].val.cooperative = 1;
  cfg.attrs = at;
  cfg.numAttrs = 1;
  cudaLaunchKernelEx(&cfg, conformer_kernel, p);
}
```

```cpp
#include <cuda_runtime.h>
#include <cuda_bf16.h>
#include <cuda.h>
#include <stdint.h>

namespace {

constexpr int T_SEQ = 1000;
constexpr int DM = 256;
constexpr int NCTA = 128;
constexpr int NSTAGE = 12;
constexpr uint32_t STAGE_BYTES = 16384;
constexpr uint32_t TILE_BYTES = 8192;
constexpr uint32_t SM_BASE = 1024;
constexpr uint32_t SM_STG = NSTAGE * STAGE_BYTES;
constexpr uint32_t SM_FULL = SM_STG + 32768;
constexpr uint32_t SM_EMPTY = SM_FULL + 96;
constexpr uint32_t SM_XBAR = SM_FULL + 192;
constexpr uint32_t SM_EYE = SM_FULL + 256;
constexpr uint32_t SM_ONE = SM_FULL + 640;
constexpr uint32_t SM_CS = SM_FULL + 768;
constexpr uint32_t SM_TOTAL = SM_FULL + 3072;
constexpr int CS_FF2 = 0, CS_PW1 = 4, CS_QKV = 6;
constexpr uint32_t SPIN_LIMIT = 1u << 16;
constexpr float LN_EPS = 1e-5f;
constexpr float SM_SCALE_LOG2 = 0.125f * 1.4426950408889634f;
constexpr uint32_t G_PITCH = 144;

constexpr int F_QKV = 16, F_SPARE = 22, F_KV = 24, F_WO = 40, F_PW1 = 42, F_PW2 = 46, F_TOTAL = 64;
enum { M_FF1A, M_FF1B, M_WKV, M_WQ, M_KV, M_WO, M_PW1, M_PW2, M_FF2A, M_FF2B, M_X, M_COUNT };
enum { BAR_K = 1, BAR_V, BAR_Q, BAR_MERGE, BAR_G, BAR_C, BAR_WG1, BAR_RDY, BAR_ST, BAR_ATT, BAR_INIT, BAR_RDY1, BAR_X };

struct Params {
  CUtensorMap map[M_COUNT];
  const __nv_bfloat16 *w_ff1b, *w_qkv, *w_o, *w_pw1, *dw, *w_pw2, *w_ff2a, *w_ff2b;
  __nv_bfloat16* out;
};

constexpr int X_RS = 0, X_AG1 = X_RS, X_HALO = X_RS + 512, X_CLEAR = 1024, X_AG0 = 1536, X_ST = 2048, X_SIZE = 4096;
constexpr uint32_t HALO_TAG = 0xFFFF0001u;
__device__ __align__(1024) uint4 g_x[NCTA][X_SIZE];
__device__ __align__(1024) uint4 g_kv[8][2][16][512];
__device__ __align__(1024) uint32_t g_flag[8][32];
__device__ __align__(1024) uint4 g_cs[576];
__device__ __align__(1024) uint32_t g_ready[NCTA];
__device__ uint32_t g_epoch[NCTA];
#define PROF_TIME(i)
#define PROF_MARK(i)

__device__ __forceinline__ void mbar_init(uint32_t bar, uint32_t cnt) {
  asm volatile("mbarrier.init.shared::cta.b64 [%0], %1;" :: "r"(bar), "r"(cnt) : "memory");
}
__device__ __forceinline__ void mbar_wait(uint32_t bar, uint32_t parity) {
  asm volatile("{\n.reg .pred p;\n.reg .u32 c;\nmov.u32 c, 0;\n"
               "WAIT_LOOP:\nmbarrier.try_wait.parity.shared::cta.b64 p, [%0], %1;\n@p bra WAIT_DONE;\n"
               "add.u32 c, c, 1;\nsetp.lt.u32 p, c, %2;\n@p bra WAIT_LOOP;\nWAIT_DONE:\n}"
               :: "r"(bar), "r"(parity), "n"(SPIN_LIMIT) : "memory");
}
__device__ __forceinline__ void mbar_arrive(uint32_t bar) {
  asm volatile("mbarrier.arrive.shared::cta.b64 _, [%0];" :: "r"(bar) : "memory");
}
#define bar_sync(id, n) asm volatile("bar.sync %0, %1;" :: "n"((int)(id)), "n"(n) : "memory")
#define bar_arrive(id, n) asm volatile("bar.arrive %0, %1;" :: "n"((int)(id)), "n"(n) : "memory")
__device__ __forceinline__ void fence_async_smem() { asm volatile("fence.proxy.async.shared::cta;" ::: "memory"); }

__device__ __forceinline__ void st_vec(uint4* p, uint32_t a, uint32_t b, uint32_t c, uint32_t d) {
  asm volatile("{\n.reg .b128 v;\n.reg .b64 lo, hi;\nmov.b64 lo, {%1, %2};\nmov.b64 hi, {%3, %4};\nmov.b128 v, {lo, hi};\n"
               "st.relaxed.gpu.global.b128 [%0], v;\n}" :: "l"(p), "r"(a), "r"(b), "r"(c), "r"(d) : "memory");
}
__device__ __forceinline__ void ld_vec(const uint4* p, uint32_t& a, uint32_t& b, uint32_t& c, uint32_t& d) {
  asm volatile("{\n.reg .b128 v;\n.reg .b64 lo, hi;\nld.relaxed.gpu.global.b128 v, [%4];\nmov.b128 {lo, hi}, v;\n"
               "mov.b64 {%0, %1}, lo;\nmov.b64 {%2, %3}, hi;\n}" : "=r"(a), "=r"(b), "=r"(c), "=r"(d) : "l"(p) : "memory");
}
__device__ __forceinline__ void sts128(uint32_t a, uint32_t x, uint32_t y, uint32_t z, uint32_t w) {
  asm volatile("st.shared.v4.u32 [%0], {%1, %2, %3, %4};" :: "r"(a), "r"(x), "r"(y), "r"(z), "r"(w) : "memory");
}
__device__ __forceinline__ void lds128(uint32_t a, uint32_t& x, uint32_t& y, uint32_t& z, uint32_t& w) {
  asm volatile("ld.shared.v4.u32 {%0, %1, %2, %3}, [%4];" : "=r"(x), "=r"(y), "=r"(z), "=r"(w) : "r"(a) : "memory");
}
__device__ __forceinline__ uint32_t lds32(uint32_t a) {
  uint32_t x; asm volatile("ld.shared.u32 %0, [%1];" : "=r"(x) : "r"(a) : "memory"); return x;
}
__device__ __forceinline__ void sts32(uint32_t a, uint32_t x) { asm volatile("st.shared.u32 [%0], %1;" :: "r"(a), "r"(x) : "memory"); }
__device__ __forceinline__ void sts64(uint32_t a, uint32_t x, uint32_t y) {
  asm volatile("st.shared.v2.u32 [%0], {%1, %2};" :: "r"(a), "r"(x), "r"(y) : "memory");
}
__device__ __forceinline__ void stsm4(uint32_t a, const uint32_t* r) {
  asm volatile("stmatrix.sync.aligned.m8n8.x4.shared.b16 [%0], {%1, %2, %3, %4};" :: "r"(a), "r"(r[0]), "r"(r[1]), "r"(r[2]), "r"(r[3]) : "memory");
}
__device__ __forceinline__ void ldsm4(uint32_t a, uint32_t* r) {
  asm volatile("ldmatrix.sync.aligned.m8n8.x4.shared.b16 {%0, %1, %2, %3}, [%4];" : "=r"(r[0]), "=r"(r[1]), "=r"(r[2]), "=r"(r[3]) : "r"(a) : "memory");
}
__device__ __forceinline__ uint32_t pack2(float lo, float hi) {
  uint32_t r; asm("cvt.rn.bf16x2.f32 %0, %1, %2;" : "=r"(r) : "f"(hi), "f"(lo)); return r;
}
__device__ __forceinline__ float bf_lo(uint32_t w) { return __uint_as_float(w << 16); }
__device__ __forceinline__ float bf_hi(uint32_t w) { return __uint_as_float(w & 0xffff0000u); }
__device__ __forceinline__ float tanh_hw(float x) { float y; asm volatile("tanh.approx.f32 %0, %1;" : "=f"(y) : "f"(x)); return y; }
__device__ __forceinline__ float rcp_hw(float x) { float y; asm("rcp.approx.ftz.f32 %0, %1;" : "=f"(y) : "f"(x)); return y; }
__device__ __forceinline__ float ex2_hw(float x) { float y; asm("ex2.approx.ftz.f32 %0, %1;" : "=f"(y) : "f"(x)); return y; }

__device__ __forceinline__ uint32_t here(uint32_t v) { asm volatile("" : "+r"(v)); return v; }

#define SCHED() asm volatile("pmevent 1;" ::: "memory")
#define WG_FENCE() asm volatile("wgmma.fence.sync.aligned;" ::: "memory")
#define WG_COMMIT() asm volatile("wgmma.commit_group.sync.aligned;" ::: "memory")
#define WG_WAIT(n) asm volatile("wgmma.wait_group.sync.aligned %0;" :: "n"(n) : "memory")

template <int N> __device__ __forceinline__ void pin(float (&d)[N]) {
#pragma unroll
  for (int i = 0; i < N; i++) asm volatile("" : "+f"(d[i]) :: "memory");
}
template <int N> __device__ __forceinline__ void pin(uint32_t (&d)[N]) {
#pragma unroll
  for (int i = 0; i < N; i++) asm volatile("" : "+r"(d[i]) :: "memory");
}

#define WG_D32 "{%0, %1, %2, %3, %4, %5, %6, %7, %8, %9, %10, %11, %12, %13, %14, %15, %16, %17, %18, %19, %20, %21, %22, %23, %24, %25, %26, %27, %28, %29, %30, %31}"
template <int TB> __device__ __forceinline__ void wgmma64_acc(float (&d)[32], const uint32_t* a, uint64_t db) {
  asm volatile("wgmma.mma_async.sync.aligned.m64n64k16.f32.bf16.bf16 " WG_D32 ", {%32, %33, %34, %35}, %36, 1, 1, 1, %37;"
    : "+f"(d[0]), "+f"(d[1]), "+f"(d[2]), "+f"(d[3]), "+f"(d[4]), "+f"(d[5]), "+f"(d[6]), "+f"(d[7]),
      "+f"(d[8]), "+f"(d[9]), "+f"(d[10]), "+f"(d[11]), "+f"(d[12]), "+f"(d[13]), "+f"(d[14]), "+f"(d[15]),
      "+f"(d[16]), "+f"(d[17]), "+f"(d[18]), "+f"(d[19]), "+f"(d[20]), "+f"(d[21]), "+f"(d[22]), "+f"(d[23]),
      "+f"(d[24]), "+f"(d[25]), "+f"(d[26]), "+f"(d[27]), "+f"(d[28]), "+f"(d[29]), "+f"(d[30]), "+f"(d[31])
    : "r"(a[0]), "r"(a[1]), "r"(a[2]), "r"(a[3]), "l"(db), "n"(TB));
}
template <int TB> __device__ __forceinline__ void wgmma64_set(float (&d)[32], const uint32_t* a, uint64_t db) {
  asm volatile("wgmma.mma_async.sync.aligned.m64n64k16.f32.bf16.bf16 " WG_D32 ", {%32, %33, %34, %35}, %36, 0, 1, 1, %37;"
    : "=f"(d[0]), "=f"(d[1]), "=f"(d[2]), "=f"(d[3]), "=f"(d[4]), "=f"(d[5]), "=f"(d[6]), "=f"(d[7]),
      "=f"(d[8]), "=f"(d[9]), "=f"(d[10]), "=f"(d[11]), "=f"(d[12]), "=f"(d[13]), "=f"(d[14]), "=f"(d[15]),
      "=f"(d[16]), "=f"(d[17]), "=f"(d[18]), "=f"(d[19]), "=f"(d[20]), "=f"(d[21]), "=f"(d[22]), "=f"(d[23]),
      "=f"(d[24]), "=f"(d[25]), "=f"(d[26]), "=f"(d[27]), "=f"(d[28]), "=f"(d[29]), "=f"(d[30]), "=f"(d[31])
    : "r"(a[0]), "r"(a[1]), "r"(a[2]), "r"(a[3]), "l"(db), "n"(TB));
}

__device__ __forceinline__ void wgmma72_acc(float (&d)[36], const uint32_t* a, uint64_t db) {
  asm volatile("wgmma.mma_async.sync.aligned.m64n72k16.f32.bf16.bf16 {%0, %1, %2, %3, %4, %5, %6, %7, %8, %9, %10, %11, %12, %13, %14, %15, %16, %17, %18, %19, %20, %21, %22, %23, %24, %25, %26, %27, %28, %29, %30, %31, %32, %33, %34, %35}, {%36, %37, %38, %39}, %40, 1, 1, 1, 1;"
    : "+f"(d[0]), "+f"(d[1]), "+f"(d[2]), "+f"(d[3]), "+f"(d[4]), "+f"(d[5]), "+f"(d[6]), "+f"(d[7]), "+f"(d[8]),
      "+f"(d[9]), "+f"(d[10]), "+f"(d[11]), "+f"(d[12]), "+f"(d[13]), "+f"(d[14]), "+f"(d[15]), "+f"(d[16]), "+f"(d[17]),
      "+f"(d[18]), "+f"(d[19]), "+f"(d[20]), "+f"(d[21]), "+f"(d[22]), "+f"(d[23]), "+f"(d[24]), "+f"(d[25]), "+f"(d[26]),
      "+f"(d[27]), "+f"(d[28]), "+f"(d[29]), "+f"(d[30]), "+f"(d[31]), "+f"(d[32]), "+f"(d[33]), "+f"(d[34]), "+f"(d[35])
    : "r"(a[0]), "r"(a[1]), "r"(a[2]), "r"(a[3]), "l"(db));
}
__device__ __forceinline__ void wgmma16_acc(float* d, const uint32_t* a, uint64_t db) {
  asm volatile("wgmma.mma_async.sync.aligned.m64n16k16.f32.bf16.bf16 {%0, %1, %2, %3, %4, %5, %6, %7}, {%8, %9, %10, %11}, %12, 1, 1, 1, 0;"
    : "+f"(d[0]), "+f"(d[1]), "+f"(d[2]), "+f"(d[3]), "+f"(d[4]), "+f"(d[5]), "+f"(d[6]), "+f"(d[7])
    : "r"(a[0]), "r"(a[1]), "r"(a[2]), "r"(a[3]), "l"(db));
}
__device__ __forceinline__ void hmma(float (&d)[4], const uint32_t* a, uint32_t b0, uint32_t b1) {
  asm("mma.sync.aligned.m16n8k16.row.col.f32.bf16.bf16.f32 {%0, %1, %2, %3}, {%4, %5, %6, %7}, {%8, %9}, {%0, %1, %2, %3};"
    : "+f"(d[0]), "+f"(d[1]), "+f"(d[2]), "+f"(d[3]) : "r"(a[0]), "r"(a[1]), "r"(a[2]), "r"(a[3]), "r"(b0), "r"(b1));
}

__device__ __forceinline__ void hmma8(float (&d)[4], const uint32_t* a, uint32_t b0) {
  asm("mma.sync.aligned.m16n8k8.row.col.f32.bf16.bf16.f32 {%0, %1, %2, %3}, {%4, %5}, {%6}, {%0, %1, %2, %3};"
    : "+f"(d[0]), "+f"(d[1]), "+f"(d[2]), "+f"(d[3]) : "r"(a[0]), "r"(a[1]), "r"(b0));
}

template <bool FIRST> __device__ __forceinline__ void mma_tile(float (&d)[32], const uint32_t (&a)[16], uint64_t db) {
  WG_FENCE();
#pragma unroll
  for (int s = 0; s < 4; s++) {
    if (FIRST && s == 0) wgmma64_set<1>(d, &a[0], db); else wgmma64_acc<1>(d, &a[4 * s], db + s * 128);
  }
  WG_COMMIT();
}
template <int ROW> __device__ __forceinline__ void mma_tile_fold(float (&d)[32], const uint32_t (&a)[16], uint64_t db, const uint32_t (&mu)[4]) {
  WG_FENCE();
#pragma unroll
  for (int s = 0; s < 4; s++) wgmma64_acc<1>(d, &a[4 * s], db + s * 128);
  wgmma64_acc<1>(d, mu, (uint64_t)((SM_BASE + SM_CS + ROW * 128) >> 4) | (uint64_t(1) << 16) | (uint64_t(1) << 62));
  WG_COMMIT();
}
__device__ __forceinline__ void mma_add_half(float (&d)[32], const uint32_t (&a)[16]) {
  const uint64_t db = (uint64_t)((SM_BASE + SM_EYE) >> 4) | (uint64_t(8) << 16) | (uint64_t(8) << 32);
  WG_FENCE();
#pragma unroll
  for (int s = 0; s < 4; s++) wgmma16_acc(&d[8 * s], &a[4 * s], db);
  WG_COMMIT();
}
#define ACQUIRE(f) mbar_wait(SM_BASE + SM_FULL + ((f) % NSTAGE) * 8, ((f) / NSTAGE) & 1)
template <int F, int N> __device__ __forceinline__ void acquire_n() {
  static_assert(F % NSTAGE + N <= NSTAGE, "stages must not wrap");
  uint32_t spin = 0, ok;
  do {
    ok = 1;
#pragma unroll
    for (int i = 0; i < N; i++)
      asm volatile("{\n.reg .pred p;\nmbarrier.try_wait.parity.shared::cta.b64 p, [%1], %2;\nselp.u32 %0, %0, 0, p;\n}"
                   : "+r"(ok) : "r"(SM_BASE + SM_FULL + (F % NSTAGE + i) * 8), "r"((F / NSTAGE) & 1) : "memory");
  } while (!ok && ++spin < SPIN_LIMIT);
}
#define RELEASE(f0, f1) do { if (lane == 0) { _Pragma("unroll") for (int f_ = (f0); f_ <= (f1); f_++) mbar_arrive(SM_BASE + SM_EMPTY + (f_ % NSTAGE) * 8); } } while (0)
constexpr uint64_t RING = (uint64_t)(SM_BASE >> 4) | (uint64_t(1) << 16) | (uint64_t(64) << 32) | (uint64_t(1) << 62);
#define LO(f) (RING + ((f) % NSTAGE) * 1024)
#define HI(f) (RING + ((f) % NSTAGE) * 1024 + 512)

__device__ __forceinline__ uint32_t clock_now() { uint32_t c; asm volatile("mov.u32 %0, %%clock;" : "=r"(c) :: "memory"); return c; }
__device__ __forceinline__ void publish(uint4* dst, uint32_t (&a)[16], uint32_t tag) {
#pragma unroll
  for (int s = 0; s < 4; s++) a[4 * s] = (a[4 * s] & ~1u) | tag;
  pin(a);
  SCHED();
#pragma unroll
  for (int s = 0; s < 4; s++) st_vec(dst + s * 128, a[4 * s], a[4 * s + 1], a[4 * s + 2], a[4 * s + 3]);
  SCHED();
}
__device__ __forceinline__ void fetch(const uint4* src, uint32_t (&a)[16]) {
#pragma unroll
  for (int s = 0; s < 4; s++) ld_vec(src + s * 128, a[4 * s], a[4 * s + 1], a[4 * s + 2], a[4 * s + 3]);
}
__device__ __forceinline__ uint32_t miss(const uint32_t (&a)[16], uint32_t tag) {
  return (a[0] ^ tag) | (a[4] ^ tag) | (a[8] ^ tag) | (a[12] ^ tag);
}
__device__ __forceinline__ bool stale(uint32_t v) { return __any_sync(0xffffffffu, here(v) & 1u); }
__device__ __forceinline__ void confirm(const uint4* src, uint32_t (&a)[16], uint32_t tag) {
  uint32_t spin = 0;
  while (__builtin_expect(stale(miss(a, tag)), 0) && ++spin < SPIN_LIMIT) fetch(src, a);
}
constexpr uint32_t GATHER_DELAY = 400;
__device__ __forceinline__ void gather_start(uint32_t (&A)[4][16], uint32_t off, uint32_t sent) {
  const uint4* p1 = &g_x[0][0] + (off ^ (1 * X_SIZE));
  const uint4* p2 = &g_x[0][0] + (off ^ (2 * X_SIZE));
  const uint4* p3 = &g_x[0][0] + (off ^ (3 * X_SIZE));
  while (clock_now() - sent < GATHER_DELAY) {}
  fetch(p1, A[1]); fetch(p2, A[2]); fetch(p3, A[3]);
  SCHED();
}
template <int C> __device__ __forceinline__ void gather_wait(uint32_t (&A)[4][16], uint32_t off, uint32_t tag) {
  SCHED();
  confirm(&g_x[0][0] + (here(off) ^ (C * X_SIZE)), A[C], tag);
}
__device__ __forceinline__ void pack_acc(const float (&d)[32], uint32_t (&a)[16]) {
#pragma unroll
  for (int i = 0; i < 16; i++) a[i] = pack2(d[2 * i], d[2 * i + 1]);
}
__device__ __forceinline__ void res_store(uint32_t slot, const uint32_t (&a)[16]) {
#pragma unroll
  for (int s = 0; s < 4; s++) sts128(slot + s * 512, a[4 * s], a[4 * s + 1], a[4 * s + 2], a[4 * s + 3]);
}
__device__ __forceinline__ void res_load(uint32_t slot, float (&d)[32]) {
  uint32_t a[16];
#pragma unroll
  for (int s = 0; s < 4; s++) lds128(slot + s * 512, a[4 * s], a[4 * s + 1], a[4 * s + 2], a[4 * s + 3]);
#pragma unroll
  for (int i = 0; i < 16; i++) { d[2 * i] = bf_lo(a[i]); d[2 * i + 1] = bf_hi(a[i]); }
  pin(d);
}
__device__ __forceinline__ void tile_store(uint32_t maddr, const uint32_t (&a)[16]) {
#pragma unroll
  for (int s = 0; s < 4; s++) stsm4(maddr ^ (s << 5), &a[4 * s]);
}
__device__ __forceinline__ void tile_load(uint32_t maddr, uint32_t (&a)[16]) {
#pragma unroll
  for (int s = 0; s < 4; s++) ldsm4(maddr ^ (s << 5), &a[4 * s]);
}

struct RowAcc { float s[4], u[4], v[4]; };
__device__ __forceinline__ void row_acc(RowAcc& t, const uint32_t (&a)[16]) {
#pragma unroll
  for (int s = 0; s < 8; s++) {
    if ((s & 1) == 0) hmma(t.s, &a[2 * s], 0x3F803F80u, 0x3F803F80u);
    hmma8(t.u, &a[2 * s], a[2 * s]);
    hmma8(t.v, &a[2 * s], a[2 * s + 1]);
  }
}
__device__ __forceinline__ void stat_publish(const uint32_t (&a)[16], uint32_t b, uint32_t th, uint32_t tag) {
  RowAcc t = {};
  row_acc(t, a);
  const bool odd = th & 4;
  if ((th & 3) == ((th >> 3) & 3))
    st_vec(&g_x[b][X_ST + (th >> 2)], (__float_as_uint(t.s[0]) & ~1u) | tag, __float_as_uint(odd ? t.u[1] : t.u[0]),
           __float_as_uint(t.s[2]), __float_as_uint(odd ? t.v[3] : t.v[2]));
}
struct RowNorm { float m0, rs0, m1, rs1; };
__device__ __forceinline__ RowNorm row_norm(float s0, float q0, float s1, float q1, float scale) {
  RowNorm n;
  n.m0 = s0 * (1.f / DM); n.m1 = s1 * (1.f / DM);
  n.rs0 = scale * rsqrtf(fmaxf(fmaf(-n.m0, n.m0, q0 * (1.f / DM)), 0.f) + LN_EPS);
  n.rs1 = scale * rsqrtf(fmaxf(fmaf(-n.m1, n.m1, q1 * (1.f / DM)), 0.f) + LN_EPS);
  return n;
}
__device__ __forceinline__ RowNorm stat_gather(uint32_t b, uint32_t th, uint32_t tag, float scale) {
  const uint4* src = &g_x[b & ~3u][X_ST + (th >> 2)];
  uint32_t v[16], spin = 0;
  do {
#pragma unroll
    for (int j = 0; j < 4; j++) ld_vec(src + j * X_SIZE, v[4 * j], v[4 * j + 1], v[4 * j + 2], v[4 * j + 3]);
  } while (stale(miss(v, tag)) && ++spin < SPIN_LIMIT);
  float f[4];
#pragma unroll
  for (int i = 0; i < 4; i++)
    f[i] = (__uint_as_float(v[i]) + __uint_as_float(v[4 + i])) + (__uint_as_float(v[8 + i]) + __uint_as_float(v[12 + i]));
  return row_norm(f[0], f[1], f[2], f[3], scale);
}
constexpr uint32_t SM_NORM = SM_BASE + SM_STG + 2 * TILE_BYTES + 4096;
__device__ __forceinline__ void norm_produce(const RowNorm& n, uint32_t th, uint32_t qsel) {
  const bool sel = (th & 3) == qsel;
  const float a = sel ? -n.m0 : 0.f, c = sel ? -n.m1 : 0.f;
  const uint32_t ah = pack2(a, a), ch = pack2(c, c);
  const float al = a - bf_lo(ah), cl = c - bf_lo(ch);
  sts128(SM_NORM + th * 16, ah, ch, pack2(al, al), pack2(cl, cl));
  sts64(SM_NORM + 2048 + th * 8, __float_as_uint(n.rs0), __float_as_uint(n.rs1));
  bar_arrive(BAR_ST, 256);
}
__device__ __forceinline__ void norm_consume(uint32_t th, uint32_t (&mu)[4], float& rs0, float& rs1) {
  bar_sync(BAR_ST, 256);
  lds128(SM_NORM + th * 16, mu[0], mu[1], mu[2], mu[3]);
  asm volatile("ld.shared.v2.f32 {%0, %1}, [%2];" : "=f"(rs0), "=f"(rs1) : "r"(SM_NORM + 2048 + th * 8) : "memory");
}
__device__ __forceinline__ void scale_pack(const float (&d)[32], uint32_t (&a)[16], float rs0, float rs1) {
#pragma unroll
  for (int i = 0; i < 16; i++) { const float rs = (i & 1) ? rs1 : rs0; a[i] = pack2(d[2 * i] * rs, d[2 * i + 1] * rs); }
}
template <int I0, int I1> __device__ __forceinline__ void silu_part(const float (&d)[32], uint32_t (&h)[16], float rs0, float rs1) {
  if (I0) SCHED();
#pragma unroll
  for (int i = I0; i < I1; i++) {
    const float rs = (i & 1) ? rs1 : rs0, a = d[2 * i] * rs, b = d[2 * i + 1] * rs;
    h[i] = pack2(fmaf(a, tanh_hw(a), a), fmaf(b, tanh_hw(b), b));
    asm volatile("" : "+r"(h[i]));
  }
  SCHED();
}
template <int F, int N> __device__ __forceinline__ uint32_t send_residual(uint32_t (&a)[16], uint32_t xoff, uint32_t res, uint32_t tag) {
  const uint32_t exact[4] = {a[0], a[4], a[8], a[12]};
  publish(&g_x[0][X_AG0] + xoff, a, tag);
  const uint32_t sent = clock_now();
  stat_publish(a, blockIdx.x, xoff & 127, tag);
  res_store(res, a);
#pragma unroll
  for (int s = 0; s < 4; s++) sts32(res + s * 512, exact[s]);
  acquire_n<F, N>();
  return sent;
}
template <int F, int NEXT> __device__ __forceinline__ uint32_t proj_residual(uint32_t (&A)[4][16], uint32_t xoff, uint32_t res,
                                                                             uint32_t r, uint32_t tag) {
  float acc[32];
  publish(&g_x[0][X_AG1] + xoff, A[0], tag);
  const uint32_t sent = clock_now();
  acquire_n<F, 2>();
  res_load(res, acc);
  const uint32_t flip = (r & 1) * 512;
  mma_tile<false>(acc, A[0], flip + LO(F));
  gather_start(A, xoff + X_AG1, sent);
  gather_wait<1>(A, xoff + X_AG1, tag);
  mma_tile<false>(acc, A[1], HI(F) - flip);
  gather_wait<2>(A, xoff + X_AG1, tag);
  mma_tile<false>(acc, A[2], flip + LO(F + 1));
  gather_wait<3>(A, xoff + X_AG1, tag);
  PROF_MARK(F == F_WO ? 11 : 16);
  mma_tile<false>(acc, A[3], HI(F + 1) - flip);
  WG_WAIT(0); pin(acc);
  pack_acc(acc, A[0]);
  return send_residual<F + 2, NEXT>(A[0], xoff, res, tag);
}

__device__ __forceinline__ void qk_tile(float (&S)[32], const uint32_t (&Q)[16], uint64_t dk) {
#pragma unroll
  for (int s = 0; s < 4; s++) {
    if (s == 0) wgmma64_set<0>(S, &Q[0], dk); else wgmma64_acc<0>(S, &Q[4 * s], dk + s * 2);
  }
}
__device__ __forceinline__ void qk_shift(float (&S)[32], const uint32_t (&nm)[4]) { wgmma64_acc<0>(S, nm, (uint64_t)((SM_BASE + SM_ONE) >> 4)); }
constexpr uint64_t V_STEP = uint64_t(1) - (uint64_t(1) << 16);
constexpr uint64_t RING_V = RING - (uint64_t(1) << 16) + ((uint64_t)((SM_STG + 2 * TILE_BYTES) >> 4) << 16);
__device__ __forceinline__ void pv_tile(float (&O)[36], const uint32_t (&P)[16], uint64_t dv, uint64_t pad) {
#pragma unroll
  for (int s = 0; s < 4; s++) wgmma72_acc(O, &P[4 * s], dv + s * 128 * V_STEP + (s < 2 ? 0 : (s - 1) * pad));
}
__device__ __forceinline__ void attn_step(const float (&Sc)[32], float (&Sn)[32], uint32_t (&Pc)[16], uint32_t (&Pp)[16], float (&O)[36],
                                          const uint32_t (&Q)[16], const uint32_t (&nm)[4], uint64_t dk, uint64_t dv) {
  WG_FENCE();
  qk_tile(Sn, Q, dk);
  qk_shift(Sn, nm);
  pv_tile(O, Pp, dv, 0);
  WG_COMMIT();
  SCHED();
#pragma unroll
  for (int i = 0; i < 16; i++) Pc[i] = pack2(ex2_hw(Sc[2 * i]), ex2_hw(Sc[2 * i + 1]));
  pin(Pc);
  SCHED();
}
template <int R> __device__ __forceinline__ float tile_max(const float (&S)[32]) {
  float t[4];
#pragma unroll
  for (int j = 0; j < 4; j++) t[j] = fmaxf(fmaxf(S[8 * j + R], S[8 * j + R + 1]), fmaxf(S[8 * j + R + 4], S[8 * j + R + 5]));
  float n = fmaxf(fmaxf(t[0], t[1]), fmaxf(t[2], t[3]));
  n = fmaxf(n, __shfl_xor_sync(0xffffffffu, n, 1));
  return fmaxf(n, __shfl_xor_sync(0xffffffffu, n, 2));
}
__device__ __forceinline__ void attention_exact(float (&O)[36], const uint32_t (&Q)[16], int bh, int lane) {
  const char* kb = (const char*)&g_kv[bh][0][0][0];
  const char* vb = (const char*)&g_kv[bh][1][0][0];
  const int g = lane >> 2, q = lane & 3;
  float m0 = -INFINITY, m1 = -INFINITY, l0 = 0.f, l1 = 0.f;
  float o[8][4] = {};
#pragma unroll 1
  for (int k0 = 0; k0 < T_SEQ; k0 += 8) {
    float s[4] = {0.f, 0.f, 0.f, 0.f};
#pragma unroll
    for (int c = 0; c < 8; c++) hmma8(s, &Q[2 * c], __ldcg((const uint32_t*)(kb + (k0 + g) * 128 + ((c ^ g) << 4) + q * 4)));
    float n0 = fmaxf(s[0], s[1]), n1 = fmaxf(s[2], s[3]);
    n0 = fmaxf(n0, __shfl_xor_sync(0xffffffffu, n0, 1)); n1 = fmaxf(n1, __shfl_xor_sync(0xffffffffu, n1, 1));
    n0 = fmaxf(m0, fmaxf(n0, __shfl_xor_sync(0xffffffffu, n0, 2))); n1 = fmaxf(m1, fmaxf(n1, __shfl_xor_sync(0xffffffffu, n1, 2)));
    const float a0 = ex2_hw(m0 - n0), a1 = ex2_hw(m1 - n1);
    m0 = n0; m1 = n1;
    const uint32_t pp[2] = {pack2(ex2_hw(s[0] - n0), ex2_hw(s[1] - n0)), pack2(ex2_hw(s[2] - n1), ex2_hw(s[3] - n1))};
    l0 = fmaf(l0, a0, bf_lo(pp[0]) + bf_hi(pp[0])); l1 = fmaf(l1, a1, bf_lo(pp[1]) + bf_hi(pp[1]));
#pragma unroll
    for (int j = 0; j < 8; j++) {
      const uint32_t v0 = __ldcg((const uint16_t*)(vb + (k0 + 2 * q) * 128 + ((j ^ (2 * q)) << 4) + g * 2));
      const uint32_t v1 = __ldcg((const uint16_t*)(vb + (k0 + 2 * q + 1) * 128 + ((j ^ (2 * q + 1)) << 4) + g * 2));
      o[j][0] *= a0; o[j][1] *= a0; o[j][2] *= a1; o[j][3] *= a1;
      hmma8(o[j], pp, v0 | (v1 << 16));
    }
  }
  l0 += __shfl_xor_sync(0xffffffffu, l0, 1); l1 += __shfl_xor_sync(0xffffffffu, l1, 1);
  O[32] = l0 + __shfl_xor_sync(0xffffffffu, l0, 2); O[34] = l1 + __shfl_xor_sync(0xffffffffu, l1, 2);
#pragma unroll
  for (int i = 0; i < 32; i++) O[i] = o[i >> 2][i & 3];
}

__device__ __forceinline__ uint32_t fill_entry(int f, int r, int bh) {
  int m, x = r, y, z = 0;
  if (f < F_QKV || f >= 48) {
    const int i = f & 15;
    m = f < F_QKV ? M_FF1A : M_FF2A;
    if (i < 8) {
      const int h = i < 2 ? i : (i >= 5), c = i < 2 ? 0 : i - 1 - 3 * h;
      x = 0; y = r ^ c; z = 4 * r + 2 * h;
    } else {
      m++; x = r ^ (((i >> 1) - 3) & 3); y = 4 * r + 2 * (i & 1);
    }
  } else if (f < F_KV) {
    const int i = f - F_QKV;
    if (i == 1 || i >= 5) { m = M_WQ; y = (r & 2) ^ (i == 1 ? 0 : 2); }
    else { m = M_WKV; y = r ^ (i ? i - 1 : 0); z = 1; }
  } else if (f < F_WO) {
    const int i = f - F_KV;
    m = M_KV; x = 0; y = bh * 32 + (i & 2) * 8 + (i >> 2) * 4 + (i & 1) * 2;
  } else if (f >= F_PW1 && f < F_PW2) {
    m = M_PW1; y = r ^ (f - F_PW1);
  } else {
    m = f < F_PW1 ? M_WO : M_PW2; y = (r & 2) ^ ((f & 1) * 2);
  }
  return m | (x << 4) | (y << 8) | (z << 16);
}
__device__ __forceinline__ void tma_fill(uint32_t st, const CUtensorMap* map, uint32_t x, uint32_t y, uint32_t z) {
  asm volatile("{\n.reg .pred p;\nelect.sync _|p, 0xffffffff;\n"
               "@p mbarrier.arrive.expect_tx.shared::cta.b64 _, [%1], 16384;\n"
               "@p cp.async.bulk.tensor.3d.shared::cluster.global.mbarrier::complete_tx::bytes [%0], [%2, {%3, %4, %5}], [%1];\n}"
               :: "r"(SM_BASE + st * STAGE_BYTES), "r"(SM_BASE + SM_FULL + st * 8), "l"(map), "r"(x), "r"(y), "r"(z) : "memory");
}
__device__ __forceinline__ void l2_prefetch(const void* p, uint32_t total, int b) {
  const uint32_t part = total / NCTA;
  asm volatile("cp.async.bulk.prefetch.L2.global [%0], %1;" :: "l"((const char*)p + (size_t)b * part), "r"(part) : "memory");
}

__global__ void __launch_bounds__(384, 1) conformer_kernel(const __grid_constant__ Params p) {
  extern __shared__ __align__(1024) uint8_t smem[];
  const int tid = threadIdx.x, lane = tid & 31;
  const int cw = __shfl_sync(0xffffffffu, tid >> 5, 0), wg = cw >> 2, w = cw & 3;
  const int b = blockIdx.x, r = b & 3, batch = b >> 6, t = (b >> 2) & 15;
  if ((uint32_t)__cvta_generic_to_shared(smem) != SM_BASE) return;
  PROF_MARK(0);
  PROF_TIME(30);

  if (cw == 8) {
    if (lane == 0) {
      asm volatile("prefetch.tensormap [%0];" :: "l"(&p.map[M_X]) : "memory");
      asm volatile("prefetch.tensormap [%0];" :: "l"(&p.map[M_FF1A]) : "memory");
      mbar_init(SM_BASE + SM_XBAR, 1);
#pragma unroll
      for (int i = 0; i < NSTAGE; i++) mbar_init(SM_BASE + SM_FULL + i * 8, 1);
      fence_async_smem();
    }
    __syncwarp();
    asm volatile("{\n.reg .pred p;\nelect.sync _|p, 0xffffffff;\n"
                 "@p mbarrier.arrive.expect_tx.shared::cta.b64 _, [%1], 32768;\n"
                 "@p cp.async.bulk.tensor.4d.shared::cluster.global.mbarrier::complete_tx::bytes [%0], [%2, {0, %3, 0, %4}], [%1];\n}"
                 :: "r"(SM_BASE + SM_STG), "r"(SM_BASE + SM_XBAR), "l"(&p.map[M_X]), "r"(t * 64), "r"(batch) : "memory");
    bar_arrive(0, 320);
  } else if (cw == 9) {
    if (lane == 0) {
#pragma unroll
      for (int i = 0; i < NSTAGE; i++) mbar_init(SM_BASE + SM_EMPTY + i * 8, 4);
    }
    __syncwarp();
    bar_arrive(0, 320);
    bar_arrive(BAR_INIT, 64);
  } else if (wg < 2) {
    if (tid < 144) sts128(SM_BASE + SM_CS + tid * 16, 0, 0, 0, 0);
    if (wg == 1) {
      const int i = tid - 128;
      sts32(SM_BASE + SM_EYE + i * 4, i >= 96 ? 0x3F803F80u : ((i & 32) == 0 && (i & 3) == ((i >> 3) & 3)) ? (0x3F00u << ((i & 4) * 4)) : 0u);
    }
    fence_async_smem();
    bar_sync(0, 320);
  }

  if (wg == 2) {
    asm volatile("setmaxnreg.dec.sync.aligned.u32 40;");
    if (w == 0) {
#pragma unroll 1
      for (int f = 0; f < 8; f++)
        tma_fill(f, &p.map[M_FF1A], 0, (r ^ ((0xE790u >> (2 * f)) & 3)) * 64, 4 * r + ((0xE2u >> f) & 1) * 2);
      PROF_MARK(1);
      const uint32_t* flag = &g_flag[batch * 4 + r][lane];
      const uint32_t prev = ((volatile uint32_t*)g_epoch)[b];
      uint32_t entry[2], ready = 0, st = 8, parity = 1;
#pragma unroll 1
      for (int i = 0; i < 2; i++) { entry[1] = fill_entry(i * 32 + lane, r, batch * 4 + r); if (i == 0) entry[0] = entry[1]; }
      bar_sync(BAR_INIT, 64);
#pragma unroll 1
      for (int f = 8; f < F_TOTAL; f++) {
        const uint32_t e = __shfl_sync(0xffffffffu, f < 32 ? entry[0] : entry[1], f);
        if ((e & 15) == M_KV) {
          const uint32_t need = 3u << ((e >> 8) & 31);
          uint32_t spin = 0;
#pragma unroll 1
          while ((ready & need) != need && ++spin < SPIN_LIMIT) {
            uint32_t v;
            asm volatile("ld.relaxed.gpu.global.u32 %0, [%1];" : "=r"(v) : "l"(flag) : "memory");
            ready = __ballot_sync(0xffffffffu, v - 1 == prev);
          }
        }
        mbar_wait(SM_BASE + SM_EMPTY + st * 8, parity);
        tma_fill(st, &p.map[e & 15], (e << 2) & 0x3C0, (e >> 2) & 0x3FC0, e >> 16);
        if (++st == NSTAGE) { st = 0; parity ^= 1; }
      }
    } else if (w < 3) {
      const int kind = w - 1;
      const uint32_t epoch = ((volatile uint32_t*)g_epoch)[b] + 1;
      if (kind == 0) {
        bar_sync(BAR_K, 160);
      } else {
        uint32_t v, spin = 0;
#pragma unroll 1
        do {
          __nanosleep(50);
          asm volatile("ld.relaxed.gpu.global.u32 %0, [%1];" : "=r"(v) : "l"(&g_ready[(b & ~3) + (lane & 3)]) : "memory");
        } while (__any_sync(0xffffffffu, v != epoch) && ++spin < SPIN_LIMIT);
        __threadfence();
        bar_arrive(BAR_RDY, 160);
        bar_arrive(BAR_RDY1, 160);
        bar_sync(BAR_V, 160);
      }
      if (lane == 0) {
        asm volatile("cp.async.bulk.global.shared::cta.bulk_group [%0], [%1], %2;"
                     :: "l"(&g_kv[batch * 4 + r][kind][t][0]), "r"(SM_BASE + SM_STG + kind * TILE_BYTES), "r"(TILE_BYTES) : "memory");
        asm volatile("cp.async.bulk.commit_group;\ncp.async.bulk.wait_group 0;" ::: "memory");
        asm volatile("st.relaxed.gpu.global.u32 [%0], %1;" :: "l"(&g_flag[batch * 4 + r][kind * 16 + t]), "r"(epoch) : "memory");
      }
    } else {
      const uint32_t epoch = ((volatile uint32_t*)g_epoch)[b] + 1;
      if (lane < M_COUNT) asm volatile("prefetch.tensormap [%0];" :: "l"(&p.map[lane]) : "memory");
      if (lane == 0) l2_prefetch(p.w_ff1b, 1024 * 256 * 2, b);
#pragma unroll 1
      for (int i = 0; i < 33; i++) {
        st_vec(&g_x[b][X_CLEAR + i * 32 + lane], 0u, 0u, 0u, 0u);
        __nanosleep(20);
      }
      __threadfence();
      __syncwarp();
      if (lane == 0) {
        asm volatile("st.relaxed.gpu.global.u32 [%0], %1;" :: "l"(&g_ready[b]), "r"(epoch) : "memory");
        l2_prefetch(p.w_o, 256 * 256 * 2, b);
        l2_prefetch(p.w_pw2, 256 * 256 * 2, b);
        l2_prefetch(p.w_ff2b, 1024 * 256 * 2, b);
      }
    }
  } else {
    asm volatile("setmaxnreg.inc.sync.aligned.u32 232;");
    const int q = lane & 3, th = tid & 127;
    constexpr uint32_t stg = SM_BASE + SM_STG;
    const uint32_t mrow = 16 * w + (lane & 15);
    const uint32_t maddr = stg + mrow * 128 + (((lane >> 4) ^ (lane & 7)) << 4);
    const uint32_t res = stg + 3 * TILE_BYTES + w * 2048 + lane * 16;
    const uint32_t xoff = b * X_SIZE + th;
    const int nvalid = T_SEQ - t * 64, row0 = 16 * w + (lane >> 2);

    uint32_t A[4][16];
    uint32_t sent = 0;
    mbar_wait(SM_BASE + SM_XBAR, 0);
    PROF_MARK(1);
#pragma unroll
    for (int c = 0; c < 4; c++) tile_load(maddr + (r ^ c) * TILE_BYTES, A[c]);
    if (wg == 0) {
      float sa[4] = {0.f, 0.f, 0.f, 0.f}, sb[4] = {0.f, 0.f, 0.f, 0.f};
#pragma unroll
      for (int i = 0; i < 16; i++) hmma((i & 1) ? sb : sa, &A[i >> 2][4 * (i & 3)], 0x3F803F80u, 0x3F803F80u);
      bar_arrive(BAR_X, 256);
      const float s0 = (sa[0] + sb[0]) * (1.f / DM), s1 = (sa[2] + sb[2]) * (1.f / DM);
      const uint32_t m0 = pack2(s0, s0), m1 = pack2(s1, s1);
#pragma unroll
      for (int c = 0; c < 4; c++) {
#pragma unroll
        for (int i = 0; i < 16; i++) asm("sub.rn.bf16x2 %0, %0, %1;" : "+r"(A[c][i]) : "r"((i & 1) ? m1 : m0));
        pin(A[c]);
      }
    } else {
      const uint32_t epoch = ((volatile uint32_t*)g_epoch)[b] + 1, tag = epoch & 1;
      {
        RowAcc ra = {};
#pragma unroll
        for (int c = 0; c < 4; c++) row_acc(ra, A[c]);
        const bool odd = lane & 4;
        const int src = (lane & 28) | (lane >> 3);
        const float q0 = __shfl_sync(0xffffffffu, odd ? ra.u[1] : ra.u[0], src);
        const float q1 = __shfl_sync(0xffffffffu, odd ? ra.v[3] : ra.v[2], src);
        bar_sync(BAR_X, 256);
        res_store(res, A[0]);
        norm_produce(row_norm(ra.s[0], q0, ra.s[2], q1, 0.5f), th, 4);
      }
      if (b < 72) {
        const __nv_bfloat16* wp; int ld, col;
        if (b < 24) { wp = p.w_qkv; ld = 768; col = b * 32; }
        else if (b < 40) { wp = p.w_pw1; ld = 512; col = (b - 24) * 32; }
        else { wp = p.w_ff2a; ld = 1024; col = (b - 40) * 32; }
        const uint4* src = (const uint4*)(wp + (size_t)(th >> 2) * ld + col + q * 8);
        float c[8] = {0.f, 0.f, 0.f, 0.f, 0.f, 0.f, 0.f, 0.f};
#pragma unroll
        for (int i = 0; i < 8; i++) {
          const uint4 v = __ldg(src + i * 4 * ld);
          c[0] += bf_lo(v.x); c[1] += bf_hi(v.x); c[2] += bf_lo(v.y); c[3] += bf_hi(v.y);
          c[4] += bf_lo(v.z); c[5] += bf_hi(v.z); c[6] += bf_lo(v.w); c[7] += bf_hi(v.w);
        }
#pragma unroll 1
        for (int m = 4; m <= 16; m <<= 1)
#pragma unroll
          for (int k = 0; k < 8; k++) c[k] += __shfl_xor_sync(0xffffffffu, c[k], m);
        if (lane < 4) {
          const uint32_t a = SM_BASE + SM_CS + 1792 + w * 128 + lane * 32;
          sts128(a, __float_as_uint(c[0]), __float_as_uint(c[1]), __float_as_uint(c[2]), __float_as_uint(c[3]));
          sts128(a + 16, __float_as_uint(c[4]), __float_as_uint(c[5]), __float_as_uint(c[6]), __float_as_uint(c[7]));
        }
        bar_sync(BAR_WG1, 128);
        if (th < 8) {
          float o[4] = {0.f, 0.f, 0.f, 0.f};
#pragma unroll 1
          for (int k = 0; k < 4; k++) {
            uint32_t e[4];
            lds128(SM_BASE + SM_CS + 1792 + k * 128 + th * 16, e[0], e[1], e[2], e[3]);
#pragma unroll
            for (int i = 0; i < 4; i++) o[i] += __uint_as_float(e[i]);
          }
          st_vec(&g_cs[b * 8 + th], (__float_as_uint(o[0]) & ~1u) | tag, __float_as_uint(o[1]), __float_as_uint(o[2]), __float_as_uint(o[3]));
        }
      }
      bar_sync(BAR_WG1, 128);
      PROF_MARK(2);
#pragma unroll 1
      for (int i = th; i < 144; i += 128) {
        const int j = i >> 4;
        int src;
        if (j < CS_PW1) src = 320 + 64 * r + i;
        else if (j < CS_QKV) src = 192 + (j - CS_PW1) * 64 + 16 * r + (i & 15);
        else src = ((j - CS_QKV + 1) % 3) * 64 + 16 * r + (i & 15);
        uint32_t e[4], spin = 0;
#pragma unroll 1
        do {
          ld_vec(&g_cs[src], e[0], e[1], e[2], e[3]);
        } while (((e[0] ^ tag) & 1u) && ++spin < SPIN_LIMIT);
        const float c0 = __uint_as_float(e[0] & ~1u), c1 = __uint_as_float(e[1]), c2 = __uint_as_float(e[2]), c3 = __uint_as_float(e[3]);
        const uint32_t h0 = pack2(c0, c1), h1 = pack2(c2, c3);
        const uint32_t a = SM_BASE + SM_CS + j * 256 + (i & 15) * 8;
        sts64(a ^ ((a >> 3) & 0x70), h0, h1);
        sts64((a + 128) ^ (((a + 128) >> 3) & 0x70), pack2(c0 - bf_lo(h0), c1 - bf_hi(h0)), pack2(c2 - bf_lo(h1), c3 - bf_hi(h1)));
      }
      fence_async_smem();
      PROF_MARK(4);
      bar_sync(BAR_RDY1, 160);
      norm_produce(stat_gather(b, th, 1, 1.f), th, 3);
    }

#pragma unroll 1
    for (uint32_t pass = 0; pass < 2; pass++) {
      uint32_t Q[16];
      if (wg == 0) {
        float acc[4][32];
        uint32_t H[4][16];
        ACQUIRE(0);
        mma_tile<true>(acc[0], A[0], LO(0)); mma_tile<true>(acc[1], A[0], HI(0));
        ACQUIRE(1);
        mma_tile<true>(acc[2], A[0], LO(1)); mma_tile<true>(acc[3], A[0], HI(1));
        acquire_n<2, 3>();
        if (pass) { gather_start(A, here(xoff) + X_AG0, sent); gather_wait<1>(A, xoff + X_AG0, 1); }
        mma_tile<false>(acc[0], A[1], LO(2));
        if (pass) gather_wait<2>(A, xoff + X_AG0, 1);
        mma_tile<false>(acc[0], A[2], LO(3));
        WG_WAIT(2);
        uint32_t mu[4];
        float rs0, rs1;
        norm_consume(here(th), mu, rs0, rs1);
        if (pass) { gather_wait<3>(A, xoff + X_AG0, 1); RELEASE(F_PW2, F_PW2 + 1); }
        PROF_MARK(2 + pass * 16);
        mma_tile_fold<2 * CS_FF2>(acc[0], A[3], LO(4), mu);
        RELEASE(0, 1);
        mma_tile<false>(acc[1], A[1], HI(2));
        acquire_n<5, 3>();
        mma_tile<false>(acc[1], A[2], HI(3));
        WG_WAIT(2); pin(acc[0]);
        silu_part<0, 8>(acc[0], H[0], rs0, rs1);
        mma_tile_fold<2 * CS_FF2 + 2>(acc[1], A[3], HI(4), mu);
        silu_part<8, 16>(acc[0], H[0], rs0, rs1);
        mma_tile<false>(acc[2], A[1], LO(5)); mma_tile<false>(acc[2], A[2], LO(6));
        WG_WAIT(2); pin(acc[1]);
        RELEASE(2, 4);
        silu_part<0, 8>(acc[1], H[1], rs0, rs1);
        mma_tile_fold<2 * CS_FF2 + 4>(acc[2], A[3], LO(7), mu);
        silu_part<8, 16>(acc[1], H[1], rs0, rs1);
        mma_tile<false>(acc[3], A[1], HI(5));
        acquire_n<8, 2>();
        mma_tile<false>(acc[3], A[2], HI(6));
        WG_WAIT(2); pin(acc[2]);
        silu_part<0, 8>(acc[2], H[2], rs0, rs1);
        mma_tile_fold<2 * CS_FF2 + 6>(acc[3], A[3], HI(7), mu);
        silu_part<8, 16>(acc[2], H[2], rs0, rs1);
        mma_tile<true>(acc[0], H[0], LO(8));
        acquire_n<10, 2>();
        mma_tile<false>(acc[0], H[1], HI(8));
        WG_WAIT(2); pin(acc[3]);
        RELEASE(5, 7);
        silu_part<0, 8>(acc[3], H[3], rs0, rs1);
        mma_tile<false>(acc[0], H[2], LO(9));
        silu_part<8, 16>(acc[3], H[3], rs0, rs1);
        mma_tile<false>(acc[0], H[3], HI(9));
        PROF_MARK(3 + pass * 16);
        const uint32_t rtag = pass ^ 1;
        const uint4* rs_in = &g_x[0][X_RS] + here(xoff);
#pragma unroll
        for (int c = 1; c < 4; c++) {
          mma_tile<true>(acc[c], H[0], LO(8 + 2 * c));
          uint4* rs_out = &g_x[0][X_RS + (c - 1) * 512] + (here(xoff) ^ (c * X_SIZE));
          if (c == 3) { if (!pass) bar_sync(BAR_RDY, 160); fetch(rs_in, A[1]); }
          SCHED();
          mma_tile<false>(acc[c], H[1], HI(8 + 2 * c));
          WG_WAIT(2); pin(acc[c - 1]);
          uint32_t o[16];
          pack_acc(acc[c - 1], o);
          publish(rs_out, o, rtag);
          mma_tile<false>(acc[c], H[2], LO(9 + 2 * c));
          SCHED();
          if (c == 1) { RELEASE(8, 9); acquire_n<12, 2>(); }
          if (c == 2) { res_load(res, acc[0]); acquire_n<14, 2>(); }
          if (c == 3) confirm(rs_in, A[1], rtag);
          mma_tile<false>(acc[c], H[3], HI(9 + 2 * c));
          SCHED();
        }
        fetch(rs_in + 512, A[2]);
        mma_add_half(acc[0], A[1]);
        WG_WAIT(1);
        SCHED();
        fetch(rs_in + 1024, A[3]);
        SCHED();
        confirm(rs_in + 512, A[2], rtag);
        mma_add_half(acc[0], A[2]);
        SCHED();
        confirm(rs_in + 1024, A[3], rtag);
        mma_add_half(acc[0], A[3]);
        PROF_MARK(4 + pass * 16);
        WG_WAIT(0); pin(acc[0]); pin(acc[3]);
#pragma unroll
        for (int i = 0; i < 16; i++) A[0][i] = pack2(fmaf(acc[3][2 * i], 0.5f, acc[0][2 * i]), fmaf(acc[3][2 * i + 1], 0.5f, acc[0][2 * i + 1]));
        if (pass) {
          PROF_MARK(21);
          stat_publish(A[0], b, here(th), 0);
          const RowNorm fn = stat_gather(b, here(th), 0, 1.f);
          const float nm0 = -fn.m0 * fn.rs0, nm1 = -fn.m1 * fn.rs1;
#pragma unroll
          for (int i = 0; i < 16; i++) {
            const float rs = (i & 1) ? fn.rs1 : fn.rs0, nm = (i & 1) ? nm1 : nm0;
            A[0][i] = pack2(fmaf(bf_lo(A[0][i]), rs, nm), fmaf(bf_hi(A[0][i]), rs, nm));
          }
          tile_store(here(maddr), A[0]);
          __syncwarp();
          const int row = 16 * w + (lane >> 3);
          uint4* dst = (uint4*)(p.out + ((size_t)batch * T_SEQ + t * 64 + row) * DM + 64 * r) + (lane & 7);
          const uint32_t src = stg + row * 128 + (((lane & 7) ^ (lane >> 3)) << 4);
#pragma unroll
          for (int i = 0; i < 4; i++) {
            uint4 v;
            lds128((src ^ ((i & 1) << 6)) + i * 512, v.x, v.y, v.z, v.w);
            if (row + 4 * i < nvalid) dst[i * 4 * (DM / 8)] = v;
          }
          PROF_MARK(22);
          PROF_TIME(31);
          break;
        }
        sent = send_residual<F_QKV, 6>(A[0], here(xoff), res, 1);
        PROF_MARK(5);
        const uint32_t flip = (r & 1) * 512;
        mma_tile<true>(acc[0], A[0], LO(F_QKV)); mma_tile<true>(acc[1], A[0], HI(F_QKV));
        mma_tile<true>(acc[2], A[0], flip + LO(F_QKV + 1));
        gather_start(A, here(xoff) + X_AG0, sent);
        gather_wait<1>(A, xoff + X_AG0, 1);
        mma_tile<false>(acc[0], A[1], LO(F_QKV + 2));
        gather_wait<2>(A, xoff + X_AG0, 1);
        mma_tile<false>(acc[0], A[2], LO(F_QKV + 3));
        norm_consume(here(th), mu, rs0, rs1);
        if (row0 >= nvalid) rs0 = 0.f;
        if (row0 + 8 >= nvalid) rs1 = 0.f;
        gather_wait<3>(A, xoff + X_AG0, 1);
        PROF_MARK(6);
        mma_tile_fold<2 * CS_QKV - 6>(acc[0], A[3], LO(F_QKV + 4), mu);
        RELEASE(10, 15);
        mma_tile<false>(acc[1], A[1], HI(F_QKV + 2)); mma_tile<false>(acc[1], A[2], HI(F_QKV + 3));
        WG_WAIT(2); pin(acc[0]);
        scale_pack(acc[0], Q, rs0, rs1);
        tile_store(here(maddr), Q);
        fence_async_smem();
        bar_arrive(BAR_K, 160);
        mma_tile_fold<2 * CS_QKV - 4>(acc[1], A[3], HI(F_QKV + 4), mu);
        mma_tile<false>(acc[2], A[1], HI(F_QKV + 1) - flip); mma_tile<false>(acc[2], A[2], flip + LO(F_QKV + 5));
        WG_WAIT(2); pin(acc[1]);
        scale_pack(acc[1], Q, rs0, rs1);
        tile_store(here(maddr) + TILE_BYTES, Q);
        fence_async_smem();
        bar_arrive(BAR_V, 160);
        mma_tile_fold<2 * CS_QKV - 2>(acc[2], A[3], HI(F_QKV + 5) - flip, mu);
        WG_WAIT(0); pin(acc[2]);
        scale_pack(acc[2], Q, rs0 * SM_SCALE_LOG2, rs1 * SM_SCALE_LOG2);
        res_store(here(res) - TILE_BYTES, Q);
        bar_arrive(BAR_Q, 256);
        acquire_n<F_SPARE, 2>();
        RELEASE(F_QKV, F_SPARE + 1);
      } else {
        bar_sync(BAR_Q, 256);
#pragma unroll
        for (int s = 0; s < 4; s++) lds128(res - TILE_BYTES + s * 512, Q[4 * s], Q[4 * s + 1], Q[4 * s + 2], Q[4 * s + 3]);
        if (w < 2) {
          const uint32_t v = w ? 0u : 0x3F803F80u;
#pragma unroll
          for (int s = 0; s < 4; s++) sts128(res - TILE_BYTES + s * 512, v, v, v, v);
          fence_async_smem();
        }
      }
      bar_sync(BAR_ATT, 256);
      PROF_MARK(7);

      float O[36];
      {
        float S[2][32];
        uint32_t P[2][16], nm[4];
        pin(Q);
        WG_FENCE();
        qk_tile(S[0], Q, RING + (SM_STG >> 4));
        WG_COMMIT();
#pragma unroll
        for (int i = 0; i < 36; i++) O[i] = 0.f;
#pragma unroll
        for (int i = 0; i < 16; i++) P[1][i] = 0u;
        WG_WAIT(0); pin(S[0]);
        const float m0 = tile_max<0>(S[0]), m1 = tile_max<2>(S[0]);
        nm[0] = pack2(q ? 0.f : -m0, 0.f); nm[1] = pack2(q ? 0.f : -m1, 0.f); nm[2] = 0u; nm[3] = 0u;
        pin(nm); pin(O); pin(P[1]);
        uint32_t sk = wg, sv = wg;
        mbar_wait(SM_BASE + SM_FULL + sk * 8, 0);
        PROF_MARK(8);
        WG_FENCE();
        qk_tile(S[0], Q, RING + sk * 1024);
        qk_shift(S[0], nm);
        WG_COMMIT();
        WG_WAIT(0); pin(S[0]);
#pragma unroll 1
        for (int it = 0; it < 4; it++) {
          attn_step(S[0], S[1], P[0], P[1], O, Q, nm, RING + sk * 1024 + 512, RING_V + (sv * 1024 + 512) * V_STEP);
          const uint32_t sn = it >= 2 ? wg : sk + 4;
          mbar_wait(SM_BASE + SM_FULL + sn * 8, it >= 2);
          mbar_wait(SM_BASE + SM_FULL + (sk + 2) * 8, it == 3);
          WG_WAIT(0); pin(O); pin(S[1]); pin(P[1]);
          if (lane == 0 && it < 3) {
            mbar_arrive(SM_BASE + SM_EMPTY + sk * 8);
            if (it) mbar_arrive(SM_BASE + SM_EMPTY + sv * 8);
          }
          sv = sk + 2; sk = sn;
          attn_step(S[1], S[0], P[1], P[0], O, Q, nm, RING + sk * 1024, RING_V + (sv * 1024) * V_STEP);
          WG_WAIT(0); pin(O); pin(S[0]); pin(P[0]);
        }
        WG_FENCE();
        pv_tile(O, P[1], RING_V + (sv * 1024 + 512) * V_STEP, (uint64_t)wg << 22);
        WG_COMMIT();
        WG_WAIT(0); pin(O);
      }
      PROF_MARK(9);

      if (wg == 1) {
        const uint32_t mo = stg + here(th) * 16;
#pragma unroll
        for (int i = 0; i < 9; i++)
          sts128(mo + i * 2048 + (i >> 3) * 4096, __float_as_uint(O[4 * i]), __float_as_uint(O[4 * i + 1]), __float_as_uint(O[4 * i + 2]), __float_as_uint(O[4 * i + 3]));
        bar_arrive(BAR_MERGE, 256);
        norm_produce(stat_gather(b, here(th), 0, 0.5f), here(th), 0);
      } else {
        const uint32_t mo = stg + here(th) * 16;
        bar_sync(BAR_MERGE, 256);
#pragma unroll
        for (int i = 8; i >= 0; i--) {
          uint32_t e[4];
          lds128(mo + i * 2048 + (i >> 3) * 4096, e[0], e[1], e[2], e[3]);
#pragma unroll
          for (int k = 0; k < 4; k++) O[4 * i + k] += __uint_as_float(e[k]);
        }
        const bool safe = O[32] > 0x1p-60f && O[32] < 0x1p60f && O[34] > 0x1p-60f && O[34] < 0x1p60f;
        if (__builtin_expect(__any_sync(0xffffffffu, !safe), 0)) attention_exact(O, Q, batch * 4 + r, lane);
        const float i0 = rcp_hw(O[32]), i1 = rcp_hw(O[34]);
#pragma unroll
        for (int i = 0; i < 16; i++) { const float v = (i & 1) ? i1 : i0; A[0][i] = pack2(O[2 * i] * v, O[2 * i + 1] * v); }
        PROF_MARK(10);
        sent = proj_residual<F_WO, 4>(A, here(xoff), res, r, 0);
        PROF_MARK(12);
      }

      const int dir = cw == 0 ? -1 : 1;
      uint32_t tap[15];
      {
        const uint32_t* dwp = (const uint32_t*)(p.dw + 64 * r) + lane + 7 * (DM / 2);
#pragma unroll
        for (int k = 0; k < 15; k++) tap[k] = __ldg(dwp + dir * (k - 7) * (DM / 2));
      }

      if (wg == 0) {
        float acc[2][32];
        mma_tile<true>(acc[0], A[0], LO(F_PW1)); mma_tile<true>(acc[1], A[0], HI(F_PW1));
        gather_start(A, here(xoff) + X_AG0, sent);
        gather_wait<1>(A, xoff + X_AG0, 0);
        mma_tile<false>(acc[1], A[1], HI(F_PW1 + 1));
        gather_wait<2>(A, xoff + X_AG0, 0);
        mma_tile<false>(acc[1], A[2], HI(F_PW1 + 2));
        uint32_t mu[4];
        float rs0, rs1;
        norm_consume(here(th), mu, rs0, rs1);
        if (row0 >= nvalid) rs0 = 0.f;
        if (row0 + 8 >= nvalid) rs1 = 0.f;
        gather_wait<3>(A, xoff + X_AG0, 0);
        PROF_MARK(13);
        mma_tile_fold<2 * CS_PW1 + 2>(acc[1], A[3], HI(F_PW1 + 3), mu);
        RELEASE(F_KV + 10, F_WO + 1);
        mma_tile<false>(acc[0], A[1], LO(F_PW1 + 1)); mma_tile<false>(acc[0], A[2], LO(F_PW1 + 2));
        WG_WAIT(2); pin(acc[1]);
#pragma unroll
        for (int i = 0; i < 16; i++) acc[1][i] = tanh_hw(acc[1][i] * ((i & 2) ? rs1 : rs0));
        SCHED();
        mma_tile_fold<2 * CS_PW1>(acc[0], A[3], LO(F_PW1 + 3), mu);
        SCHED();
#pragma unroll
        for (int i = 16; i < 32; i++) acc[1][i] = tanh_hw(acc[1][i] * ((i & 2) ? rs1 : rs0));
#pragma unroll
        for (int i = 0; i < 32; i++) { const float rs = (i & 2) ? rs1 : rs0; acc[1][i] = fmaf(acc[1][i], rs, rs); }
        pin(acc[1]);
        SCHED();
        WG_WAIT(0); pin(acc[0]);
#pragma unroll
        for (int i = 0; i < 16; i++) A[0][i] = pack2(acc[0][2 * i] * acc[1][2 * i], acc[0][2 * i + 1] * acc[1][2 * i + 1]);
        const uint32_t ga = stg + TILE_BYTES + here(mrow) * G_PITCH + (lane >> 4) * 16;
#pragma unroll
        for (int s = 0; s < 4; s++) stsm4(ga + s * 32, &A[0][4 * s]);
        RELEASE(F_PW1, F_PW1 + 3);
      }
      bar_sync(BAR_G, 256);
      PROF_MARK(14);

      {
        const int first = cw == 0 ? 14 : 8 * cw - 7;
        const uint32_t gsrc = stg + TILE_BYTES + first * G_PITCH + lane * 4;
        uint32_t in[22];
#pragma unroll
        for (int i = 0; i < 15; i++) in[i] = lds32(gsrc + dir * i * (int)G_PITCH);
        const bool edge = cw == 0 || cw == 7;
        const bool nbr = cw == 0 ? t > 0 : t < 15;
        if (edge) {
          if (nbr) {
            uint4* dst = &g_x[b + 4 * dir][X_HALO + (cw == 0 ? 96 : 0) + lane];
            st_vec(dst, HALO_TAG, in[14], in[13], in[12]);
            st_vec(dst + 32, HALO_TAG, in[11], in[10], in[9]);
            st_vec(dst + 64, HALO_TAG, in[8], 0u, 0u);
          }
        } else {
#pragma unroll
          for (int i = 15; i < 22; i++) in[i] = lds32(gsrc + i * G_PITCH);
        }
        float cl[8], ch[8], tl[15], tv[15];
#pragma unroll
        for (int k = 0; k < 15; k++) { tl[k] = bf_lo(tap[k]); tv[k] = bf_hi(tap[k]); }
#pragma unroll
        for (int o = 0; o < 8; o++) { cl[o] = 0.f; ch[o] = 0.f; }
#pragma unroll
        for (int i = 0; i < 15; i++) {
          const float lo = bf_lo(in[i]), hi = bf_hi(in[i]);
#pragma unroll
          for (int o = 0; o < 8; o++)
            if (i - o >= 0) { cl[o] = fmaf(lo, tl[i - o], cl[o]); ch[o] = fmaf(hi, tv[i - o], ch[o]); }
        }
        if (edge) {
#pragma unroll
          for (int i = 15; i < 22; i++) in[i] = 0u;
          if (nbr) {
            const uint4* src = &g_x[b][X_HALO + (cw == 0 ? 0 : 96) + lane];
            uint32_t e0, e1, e2, u0, u1, spin = 0;
#pragma unroll 1
            do {
              ld_vec(src, e0, in[15], in[16], in[17]);
              ld_vec(src + 32, e1, in[18], in[19], in[20]);
              ld_vec(src + 64, e2, in[21], u0, u1);
            } while (__any_sync(0xffffffffu, ((e0 ^ HALO_TAG) | (e1 ^ HALO_TAG) | (e2 ^ HALO_TAG)) != 0) && ++spin < SPIN_LIMIT);
          }
        }
#pragma unroll
        for (int i = 15; i < 22; i++) {
          const float lo = bf_lo(in[i]), hi = bf_hi(in[i]);
#pragma unroll
          for (int o = 0; o < 8; o++)
            if (i - o <= 14) { cl[o] = fmaf(lo, tl[i - o], cl[o]); ch[o] = fmaf(hi, tv[i - o], ch[o]); }
        }
        const uint32_t fl = cw == 0 ? 7 : 0;
        const uint32_t cdst = (stg + cw * 1024 + lane * 4) ^ (fl * 144);
#pragma unroll
        for (int o = 0; o < 8; o++) {
          const float a = 0.5f * cl[o], c = 0.5f * ch[o];
          sts32(cdst ^ (o * 144), pack2(fmaf(a, tanh_hw(a), a), fmaf(c, tanh_hw(c), c)));
        }
      }
      if (wg == 1) {
        bar_arrive(BAR_C, 256);
        norm_produce(stat_gather(b, here(th), 1, 0.5f), here(th), 0);
        if (th == 0) ((volatile uint32_t*)g_epoch)[b] += 1;
        break;
      }
      bar_sync(BAR_C, 256);
      tile_load(here(maddr), A[0]);
      PROF_MARK(15);
      sent = proj_residual<F_PW2, 1>(A, here(xoff), res, r, 1);
      PROF_MARK(17);
    }
  }
}

typedef CUresult (*EncodeFn)(CUtensorMap*, CUtensorMapDataType, cuuint32_t, void*, const cuuint64_t*, const cuuint64_t*,
                             const cuuint32_t*, const cuuint32_t*, CUtensorMapInterleave, CUtensorMapSwizzle,
                             CUtensorMapL2promotion, CUtensorMapFloatOOBfill);

void make_map(EncodeFn fn, CUtensorMap* m, const void* w, int rank, int d0, int d1, int d2, int d3, int s1, int s2, int s3,
              int b1, int b2, CUtensorMapSwizzle swz) {
  const cuuint64_t dims[4] = {(cuuint64_t)d0, (cuuint64_t)d1, (cuuint64_t)d2, (cuuint64_t)d3};
  const cuuint64_t strides[3] = {(cuuint64_t)s1, (cuuint64_t)s2, (cuuint64_t)s3};
  const cuuint32_t box[4] = {64, (cuuint32_t)b1, (cuuint32_t)b2, 1}, es[4] = {1, 1, 1, 1};
  fn(m, CU_TENSOR_MAP_DATA_TYPE_BFLOAT16, rank, const_cast<void*>(w), dims, strides, box, es, CU_TENSOR_MAP_INTERLEAVE_NONE,
     swz, CU_TENSOR_MAP_L2_PROMOTION_L2_128B, CU_TENSOR_MAP_FLOAT_OOB_FILL_NONE);
}

}

extern "C" void kernel_launch(void* const* d_in, const int* in_sizes, int n_in, void* d_out, int out_size) {
  static EncodeFn fn = nullptr;
  static void* kv = nullptr;
  if (!fn) {
    void* f = nullptr;
    cudaDriverEntryPointQueryResult st;
    cudaGetDriverEntryPoint("cuTensorMapEncodeTiled", &f, cudaEnableDefault, &st);
    fn = (EncodeFn)f;
    cudaGetSymbolAddress(&kv, g_kv);
    cudaFuncSetAttribute(conformer_kernel, cudaFuncAttributeMaxDynamicSharedMemorySize, SM_TOTAL);
  }
  typedef const __nv_bfloat16* W;
  const CUtensorMapSwizzle S = CU_TENSOR_MAP_SWIZZLE_128B;
  Params p;
  make_map(fn, &p.map[M_X], d_in[0], 4, 64, T_SEQ, 4, 2, 512, 128, T_SEQ * 512, 64, 4, S);
  make_map(fn, &p.map[M_FF1A], d_in[1], 3, 64, 256, 16, 1, 2048, 128, 0, 64, 2, S);
  make_map(fn, &p.map[M_FF1B], d_in[2], 3, 256, 1024, 1, 1, 512, 512 * 1024, 0, 128, 1, S);
  make_map(fn, &p.map[M_WKV], d_in[3], 3, 256, 256, 3, 1, 1536, 512, 0, 64, 2, S);
  make_map(fn, &p.map[M_WQ], d_in[3], 3, 256, 256, 3, 1, 1536, 512, 0, 128, 1, S);
  make_map(fn, &p.map[M_KV], kv, 3, 64, 16384, 1, 1, 128, 128 * 16384, 0, 128, 1, CU_TENSOR_MAP_SWIZZLE_NONE);
  make_map(fn, &p.map[M_WO], d_in[4], 3, 256, 256, 1, 1, 512, 512 * 256, 0, 128, 1, S);
  make_map(fn, &p.map[M_PW1], d_in[5], 3, 256, 256, 2, 1, 1024, 512, 0, 64, 2, S);
  make_map(fn, &p.map[M_PW2], d_in[7], 3, 256, 256, 1, 1, 512, 512 * 256, 0, 128, 1, S);
  make_map(fn, &p.map[M_FF2A], d_in[8], 3, 64, 256, 16, 1, 2048, 128, 0, 64, 2, S);
  make_map(fn, &p.map[M_FF2B], d_in[9], 3, 256, 1024, 1, 1, 512, 512 * 1024, 0, 128, 1, S);
  p.w_ff1b = (W)d_in[2]; p.w_qkv = (W)d_in[3]; p.w_o = (W)d_in[4]; p.w_pw1 = (W)d_in[5];
  p.dw = (W)d_in[6]; p.w_pw2 = (W)d_in[7]; p.w_ff2a = (W)d_in[8]; p.w_ff2b = (W)d_in[9];
  p.out = (__nv_bfloat16*)d_out;

  cudaLaunchConfig_t cfg = {};
  cfg.gridDim = dim3(NCTA);
  cfg.blockDim = dim3(384);
  cfg.dynamicSmemBytes = SM_TOTAL;
  cfg.stream = cudaStreamPerThread;
  cudaLaunchAttribute at[1];
  at[0].id = cudaLaunchAttributeCooperative;
  at[0].val.cooperative = 1;
  cfg.attrs = at;
  cfg.numAttrs = 1;
  cudaLaunchKernelEx(&cfg, conformer_kernel, p);
}
```

```cpp
#include <cuda_runtime.h>
#include <cuda_bf16.h>
#include <cuda.h>
#include <stdint.h>

namespace {

constexpr int T_SEQ = 1000;
constexpr int DM = 256;
constexpr int NCTA = 128;
constexpr int NSTAGE = 12;
constexpr uint32_t STAGE_BYTES = 16384;
constexpr uint32_t TILE_BYTES = 8192;
constexpr uint32_t SM_BASE = 1024;
constexpr uint32_t SM_STG = NSTAGE * STAGE_BYTES;
constexpr uint32_t SM_FULL = SM_STG + 32768;
constexpr uint32_t SM_EMPTY = SM_FULL + 96;
constexpr uint32_t SM_XBAR = SM_FULL + 192;
constexpr uint32_t SM_EYE = SM_FULL + 256;
constexpr uint32_t SM_ONE = SM_FULL + 640;
constexpr uint32_t SM_CS = SM_FULL + 768;
constexpr uint32_t SM_TOTAL = SM_FULL + 3072;
constexpr int CS_FF2 = 0, CS_PW1 = 4, CS_QKV = 6;
constexpr uint32_t SPIN_LIMIT = 1u << 16;
constexpr float LN_EPS = 1e-5f;
constexpr float SM_SCALE_LOG2 = 0.125f * 1.4426950408889634f;
constexpr uint32_t G_PITCH = 144;

constexpr int F_QKV = 16, F_SPARE = 22, F_KV = 24, F_WO = 40, F_PW1 = 42, F_PW2 = 46, F_TOTAL = 64;
enum { M_FF1A, M_FF1B, M_QKV, M_KV, M_WO, M_PW1, M_PW2, M_FF2A, M_FF2B, M_X, M_COUNT };
enum { BAR_K = 1, BAR_V, BAR_Q, BAR_MERGE, BAR_G, BAR_C, BAR_WG1, BAR_RDY, BAR_ST, BAR_ATT, BAR_INIT, BAR_RDY1, BAR_X };

struct Params {
  CUtensorMap map[M_COUNT];
  const __nv_bfloat16 *w_ff1b, *w_qkv, *w_o, *w_pw1, *dw, *w_pw2, *w_ff2a, *w_ff2b;
  __nv_bfloat16* out;
};

constexpr int X_RS = 0, X_AG1 = X_RS, X_HALO = X_RS + 512, X_CLEAR = 1024, X_AG0 = 1536, X_ST = 2048, X_SIZE = 4096;
constexpr uint32_t HALO_TAG = 0xFFFF0001u;
__device__ __align__(1024) uint4 g_x[NCTA][X_SIZE];
__device__ __align__(1024) uint4 g_kv[8][2][16][512];
__device__ __align__(1024) uint32_t g_flag[8][32];
__device__ __align__(1024) uint4 g_cs[576];
__device__ __align__(1024) uint32_t g_ready[NCTA];
__device__ uint32_t g_epoch[NCTA];
#define PROF_TIME(i)
#define PROF_MARK(i)

__device__ __forceinline__ void mbar_init(uint32_t bar, uint32_t cnt) {
  asm volatile("mbarrier.init.shared::cta.b64 [%0], %1;" :: "r"(bar), "r"(cnt) : "memory");
}
__device__ __forceinline__ void mbar_wait(uint32_t bar, uint32_t parity) {
  asm volatile("{\n.reg .pred p;\n.reg .u32 c;\nmov.u32 c, 0;\n"
               "WAIT_LOOP:\nmbarrier.try_wait.parity.shared::cta.b64 p, [%0], %1;\n@p bra WAIT_DONE;\n"
               "add.u32 c, c, 1;\nsetp.lt.u32 p, c, %2;\n@p bra WAIT_LOOP;\nWAIT_DONE:\n}"
               :: "r"(bar), "r"(parity), "n"(SPIN_LIMIT) : "memory");
}
__device__ __forceinline__ void mbar_arrive(uint32_t bar) {
  asm volatile("mbarrier.arrive.shared::cta.b64 _, [%0];" :: "r"(bar) : "memory");
}
#define bar_sync(id, n) asm volatile("bar.sync %0, %1;" :: "n"((int)(id)), "n"(n) : "memory")
#define bar_arrive(id, n) asm volatile("bar.arrive %0, %1;" :: "n"((int)(id)), "n"(n) : "memory")
__device__ __forceinline__ void fence_async_smem() { asm volatile("fence.proxy.async.shared::cta;" ::: "memory"); }

__device__ __forceinline__ void st_vec(uint4* p, uint32_t a, uint32_t b, uint32_t c, uint32_t d) {
  asm volatile("{\n.reg .b128 v;\n.reg .b64 lo, hi;\nmov.b64 lo, {%1, %2};\nmov.b64 hi, {%3, %4};\nmov.b128 v, {lo, hi};\n"
               "st.relaxed.gpu.global.b128 [%0], v;\n}" :: "l"(p), "r"(a), "r"(b), "r"(c), "r"(d) : "memory");
}
__device__ __forceinline__ void ld_vec(const uint4* p, uint32_t& a, uint32_t& b, uint32_t& c, uint32_t& d) {
  asm volatile("{\n.reg .b128 v;\n.reg .b64 lo, hi;\nld.relaxed.gpu.global.b128 v, [%4];\nmov.b128 {lo, hi}, v;\n"
               "mov.b64 {%0, %1}, lo;\nmov.b64 {%2, %3}, hi;\n}" : "=r"(a), "=r"(b), "=r"(c), "=r"(d) : "l"(p) : "memory");
}
__device__ __forceinline__ void sts128(uint32_t a, uint32_t x, uint32_t y, uint32_t z, uint32_t w) {
  asm volatile("st.shared.v4.u32 [%0], {%1, %2, %3, %4};" :: "r"(a), "r"(x), "r"(y), "r"(z), "r"(w) : "memory");
}
__device__ __forceinline__ void lds128(uint32_t a, uint32_t& x, uint32_t& y, uint32_t& z, uint32_t& w) {
  asm volatile("ld.shared.v4.u32 {%0, %1, %2, %3}, [%4];" : "=r"(x), "=r"(y), "=r"(z), "=r"(w) : "r"(a) : "memory");
}
__device__ __forceinline__ uint32_t lds32(uint32_t a) {
  uint32_t x; asm volatile("ld.shared.u32 %0, [%1];" : "=r"(x) : "r"(a) : "memory"); return x;
}
__device__ __forceinline__ void sts32(uint32_t a, uint32_t x) { asm volatile("st.shared.u32 [%0], %1;" :: "r"(a), "r"(x) : "memory"); }
__device__ __forceinline__ void sts64(uint32_t a, uint32_t x, uint32_t y) {
  asm volatile("st.shared.v2.u32 [%0], {%1, %2};" :: "r"(a), "r"(x), "r"(y) : "memory");
}
__device__ __forceinline__ void stsm4(uint32_t a, const uint32_t* r) {
  asm volatile("stmatrix.sync.aligned.m8n8.x4.shared.b16 [%0], {%1, %2, %3, %4};" :: "r"(a), "r"(r[0]), "r"(r[1]), "r"(r[2]), "r"(r[3]) : "memory");
}
__device__ __forceinline__ void ldsm4(uint32_t a, uint32_t* r) {
  asm volatile("ldmatrix.sync.aligned.m8n8.x4.shared.b16 {%0, %1, %2, %3}, [%4];" : "=r"(r[0]), "=r"(r[1]), "=r"(r[2]), "=r"(r[3]) : "r"(a) : "memory");
}
__device__ __forceinline__ uint32_t pack2(float lo, float hi) {
  uint32_t r; asm("cvt.rn.bf16x2.f32 %0, %1, %2;" : "=r"(r) : "f"(hi), "f"(lo)); return r;
}
__device__ __forceinline__ float bf_lo(uint32_t w) { return __uint_as_float(w << 16); }
__device__ __forceinline__ float bf_hi(uint32_t w) { return __uint_as_float(w & 0xffff0000u); }
__device__ __forceinline__ float tanh_hw(float x) { float y; asm volatile("tanh.approx.f32 %0, %1;" : "=f"(y) : "f"(x)); return y; }
__device__ __forceinline__ float rcp_hw(float x) { float y; asm("rcp.approx.ftz.f32 %0, %1;" : "=f"(y) : "f"(x)); return y; }
__device__ __forceinline__ float ex2_hw(float x) { float y; asm("ex2.approx.ftz.f32 %0, %1;" : "=f"(y) : "f"(x)); return y; }

__device__ __forceinline__ uint32_t here(uint32_t v) { asm volatile("" : "+r"(v)); return v; }

#define SCHED() asm volatile("pmevent 1;" ::: "memory")
#define WG_FENCE() asm volatile("wgmma.fence.sync.aligned;" ::: "memory")
#define WG_COMMIT() asm volatile("wgmma.commit_group.sync.aligned;" ::: "memory")
#define WG_WAIT(n) asm volatile("wgmma.wait_group.sync.aligned %0;" :: "n"(n) : "memory")

template <int N> __device__ __forceinline__ void pin(float (&d)[N]) {
#pragma unroll
  for (int i = 0; i < N; i++) asm volatile("" : "+f"(d[i]) :: "memory");
}
template <int N> __device__ __forceinline__ void pin(uint32_t (&d)[N]) {
#pragma unroll
  for (int i = 0; i < N; i++) asm volatile("" : "+r"(d[i]) :: "memory");
}

#define WG_D32 "{%0, %1, %2, %3, %4, %5, %6, %7, %8, %9, %10, %11, %12, %13, %14, %15, %16, %17, %18, %19, %20, %21, %22, %23, %24, %25, %26, %27, %28, %29, %30, %31}"
template <int TB> __device__ __forceinline__ void wgmma64_acc(float (&d)[32], const uint32_t* a, uint64_t db) {
  asm volatile("wgmma.mma_async.sync.aligned.m64n64k16.f32.bf16.bf16 " WG_D32 ", {%32, %33, %34, %35}, %36, 1, 1, 1, %37;"
    : "+f"(d[0]), "+f"(d[1]), "+f"(d[2]), "+f"(d[3]), "+f"(d[4]), "+f"(d[5]), "+f"(d[6]), "+f"(d[7]),
      "+f"(d[8]), "+f"(d[9]), "+f"(d[10]), "+f"(d[11]), "+f"(d[12]), "+f"(d[13]), "+f"(d[14]), "+f"(d[15]),
      "+f"(d[16]), "+f"(d[17]), "+f"(d[18]), "+f"(d[19]), "+f"(d[20]), "+f"(d[21]), "+f"(d[22]), "+f"(d[23]),
      "+f"(d[24]), "+f"(d[25]), "+f"(d[26]), "+f"(d[27]), "+f"(d[28]), "+f"(d[29]), "+f"(d[30]), "+f"(d[31])
    : "r"(a[0]), "r"(a[1]), "r"(a[2]), "r"(a[3]), "l"(db), "n"(TB));
}
__device__ __forceinline__ void wgmma64_reuse(float (&d)[32], const uint32_t* a, uint64_t db, uint32_t zero) {
  asm volatile("{\n.reg .pred p;\nsetp.ne.u32 p, %37, 0;\nwgmma.mma_async.sync.aligned.m64n64k16.f32.bf16.bf16 " WG_D32 ", {%32, %33, %34, %35}, %36, p, 1, 1, 1;\n}"
    : "+f"(d[0]), "+f"(d[1]), "+f"(d[2]), "+f"(d[3]), "+f"(d[4]), "+f"(d[5]), "+f"(d[6]), "+f"(d[7]),
      "+f"(d[8]), "+f"(d[9]), "+f"(d[10]), "+f"(d[11]), "+f"(d[12]), "+f"(d[13]), "+f"(d[14]), "+f"(d[15]),
      "+f"(d[16]), "+f"(d[17]), "+f"(d[18]), "+f"(d[19]), "+f"(d[20]), "+f"(d[21]), "+f"(d[22]), "+f"(d[23]),
      "+f"(d[24]), "+f"(d[25]), "+f"(d[26]), "+f"(d[27]), "+f"(d[28]), "+f"(d[29]), "+f"(d[30]), "+f"(d[31])
    : "r"(a[0]), "r"(a[1]), "r"(a[2]), "r"(a[3]), "l"(db), "r"(zero));
}
template <int TB> __device__ __forceinline__ void wgmma64_set(float (&d)[32], const uint32_t* a, uint64_t db) {
  asm volatile("wgmma.mma_async.sync.aligned.m64n64k16.f32.bf16.bf16 " WG_D32 ", {%32, %33, %34, %35}, %36, 0, 1, 1, %37;"
    : "=f"(d[0]), "=f"(d[1]), "=f"(d[2]), "=f"(d[3]), "=f"(d[4]), "=f"(d[5]), "=f"(d[6]), "=f"(d[7]),
      "=f"(d[8]), "=f"(d[9]), "=f"(d[10]), "=f"(d[11]), "=f"(d[12]), "=f"(d[13]), "=f"(d[14]), "=f"(d[15]),
      "=f"(d[16]), "=f"(d[17]), "=f"(d[18]), "=f"(d[19]), "=f"(d[20]), "=f"(d[21]), "=f"(d[22]), "=f"(d[23]),
      "=f"(d[24]), "=f"(d[25]), "=f"(d[26]), "=f"(d[27]), "=f"(d[28]), "=f"(d[29]), "=f"(d[30]), "=f"(d[31])
    : "r"(a[0]), "r"(a[1]), "r"(a[2]), "r"(a[3]), "l"(db), "n"(TB));
}

__device__ __forceinline__ void wgmma72_acc(float (&d)[36], const uint32_t* a, uint64_t db) {
  asm volatile("wgmma.mma_async.sync.aligned.m64n72k16.f32.bf16.bf16 {%0, %1, %2, %3, %4, %5, %6, %7, %8, %9, %10, %11, %12, %13, %14, %15, %16, %17, %18, %19, %20, %21, %22, %23, %24, %25, %26, %27, %28, %29, %30, %31, %32, %33, %34, %35}, {%36, %37, %38, %39}, %40, 1, 1, 1, 1;"
    : "+f"(d[0]), "+f"(d[1]), "+f"(d[2]), "+f"(d[3]), "+f"(d[4]), "+f"(d[5]), "+f"(d[6]), "+f"(d[7]), "+f"(d[8]),
      "+f"(d[9]), "+f"(d[10]), "+f"(d[11]), "+f"(d[12]), "+f"(d[13]), "+f"(d[14]), "+f"(d[15]), "+f"(d[16]), "+f"(d[17]),
      "+f"(d[18]), "+f"(d[19]), "+f"(d[20]), "+f"(d[21]), "+f"(d[22]), "+f"(d[23]), "+f"(d[24]), "+f"(d[25]), "+f"(d[26]),
      "+f"(d[27]), "+f"(d[28]), "+f"(d[29]), "+f"(d[30]), "+f"(d[31]), "+f"(d[32]), "+f"(d[33]), "+f"(d[34]), "+f"(d[35])
    : "r"(a[0]), "r"(a[1]), "r"(a[2]), "r"(a[3]), "l"(db));
}
__device__ __forceinline__ void wgmma16_acc(float* d, const uint32_t* a, uint64_t db) {
  asm volatile("wgmma.mma_async.sync.aligned.m64n16k16.f32.bf16.bf16 {%0, %1, %2, %3, %4, %5, %6, %7}, {%8, %9, %10, %11}, %12, 1, 1, 1, 0;"
    : "+f"(d[0]), "+f"(d[1]), "+f"(d[2]), "+f"(d[3]), "+f"(d[4]), "+f"(d[5]), "+f"(d[6]), "+f"(d[7])
    : "r"(a[0]), "r"(a[1]), "r"(a[2]), "r"(a[3]), "l"(db));
}
__device__ __forceinline__ void hmma(float (&d)[4], const uint32_t* a, uint32_t b0, uint32_t b1) {
  asm("mma.sync.aligned.m16n8k16.row.col.f32.bf16.bf16.f32 {%0, %1, %2, %3}, {%4, %5, %6, %7}, {%8, %9}, {%0, %1, %2, %3};"
    : "+f"(d[0]), "+f"(d[1]), "+f"(d[2]), "+f"(d[3]) : "r"(a[0]), "r"(a[1]), "r"(a[2]), "r"(a[3]), "r"(b0), "r"(b1));
}

__device__ __forceinline__ void hmma8(float (&d)[4], const uint32_t* a, uint32_t b0) {
  asm("mma.sync.aligned.m16n8k8.row.col.f32.bf16.bf16.f32 {%0, %1, %2, %3}, {%4, %5}, {%6}, {%0, %1, %2, %3};"
    : "+f"(d[0]), "+f"(d[1]), "+f"(d[2]), "+f"(d[3]) : "r"(a[0]), "r"(a[1]), "r"(b0));
}

template <bool FIRST> __device__ __forceinline__ void mma_tile(float (&d)[32], const uint32_t (&a)[16], uint64_t db) {
  WG_FENCE();
#pragma unroll
  for (int s = 0; s < 4; s++) {
    if (FIRST && s == 0) wgmma64_set<1>(d, &a[0], db); else wgmma64_acc<1>(d, &a[4 * s], db + s * 128);
  }
  WG_COMMIT();
}
__device__ __forceinline__ void mma_tile_reuse(float (&d)[32], const uint32_t (&a)[16], uint64_t db) {
  WG_FENCE();
  wgmma64_reuse(d, &a[0], db, blockIdx.y);
#pragma unroll
  for (int s = 1; s < 4; s++) wgmma64_acc<1>(d, &a[4 * s], db + s * 128);
  WG_COMMIT();
}
template <int ROW> __device__ __forceinline__ void mma_tile_fold(float (&d)[32], const uint32_t (&a)[16], uint64_t db, const uint32_t (&mu)[4]) {
  WG_FENCE();
#pragma unroll
  for (int s = 0; s < 4; s++) wgmma64_acc<1>(d, &a[4 * s], db + s * 128);
  wgmma64_acc<1>(d, mu, (uint64_t)((SM_BASE + SM_CS + ROW * 128) >> 4) | (uint64_t(1) << 16) | (uint64_t(1) << 62));
  WG_COMMIT();
}
__device__ __forceinline__ void mma_add_half(float (&d)[32], const uint32_t (&a)[16]) {
  const uint64_t db = (uint64_t)((SM_BASE + SM_EYE) >> 4) | (uint64_t(8) << 16) | (uint64_t(8) << 32);
  WG_FENCE();
#pragma unroll
  for (int s = 0; s < 4; s++) wgmma16_acc(&d[8 * s], &a[4 * s], db);
  WG_COMMIT();
}
#define ACQUIRE(f) mbar_wait(SM_BASE + SM_FULL + ((f) % NSTAGE) * 8, ((f) / NSTAGE) & 1)
template <int F, int N> __device__ __forceinline__ void acquire_n() {
  static_assert(F % NSTAGE + N <= NSTAGE, "stages must not wrap");
  uint32_t spin = 0, ok;
  do {
    ok = 1;
#pragma unroll
    for (int i = 0; i < N; i++)
      asm volatile("{\n.reg .pred p;\nmbarrier.try_wait.parity.shared::cta.b64 p, [%1], %2;\nselp.u32 %0, %0, 0, p;\n}"
                   : "+r"(ok) : "r"(SM_BASE + SM_FULL + (F % NSTAGE + i) * 8), "r"((F / NSTAGE) & 1) : "memory");
  } while (!ok && ++spin < SPIN_LIMIT);
}
#define RELEASE(f0, f1) do { if (lane == 0) { _Pragma("unroll") for (int f_ = (f0); f_ <= (f1); f_++) mbar_arrive(SM_BASE + SM_EMPTY + (f_ % NSTAGE) * 8); } } while (0)
constexpr uint64_t RING = (uint64_t)(SM_BASE >> 4) | (uint64_t(1) << 16) | (uint64_t(64) << 32) | (uint64_t(1) << 62);
#define LO(f) (RING + ((f) % NSTAGE) * 1024)
#define HI(f) (RING + ((f) % NSTAGE) * 1024 + 512)

__device__ __forceinline__ uint32_t clock_now() { uint32_t c; asm volatile("mov.u32 %0, %%clock;" : "=r"(c) :: "memory"); return c; }
__device__ __forceinline__ void publish(uint4* dst, uint32_t (&a)[16], uint32_t tag) {
#pragma unroll
  for (int s = 0; s < 4; s++) a[4 * s] = (a[4 * s] & ~1u) | tag;
  pin(a);
  SCHED();
#pragma unroll
  for (int s = 0; s < 4; s++) st_vec(dst + s * 128, a[4 * s], a[4 * s + 1], a[4 * s + 2], a[4 * s + 3]);
  SCHED();
}
__device__ __forceinline__ void fetch(const uint4* src, uint32_t (&a)[16]) {
#pragma unroll
  for (int s = 0; s < 4; s++) ld_vec(src + s * 128, a[4 * s], a[4 * s + 1], a[4 * s + 2], a[4 * s + 3]);
}
__device__ __forceinline__ uint32_t miss(const uint32_t (&a)[16], uint32_t tag) {
  return (a[0] ^ tag) | (a[4] ^ tag) | (a[8] ^ tag) | (a[12] ^ tag);
}
__device__ __forceinline__ bool stale(uint32_t v) { return __any_sync(0xffffffffu, here(v) & 1u); }
__device__ __forceinline__ void confirm(const uint4* src, uint32_t (&a)[16], uint32_t tag) {
  uint32_t spin = 0;
  while (__builtin_expect(stale(miss(a, tag)), 0) && ++spin < SPIN_LIMIT) fetch(src, a);
}
constexpr uint32_t GATHER_DELAY = 400;
template <int C0, int C1> __device__ __forceinline__ void gather_wait(uint32_t (&A)[4][16], uint32_t off, uint32_t tag) {
  uint32_t spin = 0;
  while (__builtin_expect(stale(miss(A[C0], tag) | miss(A[C1], tag)), 0) && ++spin < SPIN_LIMIT) {
#pragma unroll
    for (int c = C0; c <= C1; c++) fetch(&g_x[0][0] + (here(off) ^ (c * X_SIZE)), A[c]);
  }
}
template <int C> __device__ __forceinline__ void gather_first(uint32_t (&A)[4][16], uint32_t off, uint32_t tag, uint32_t sent) {
  const uint4* p1 = &g_x[0][0] + (off ^ (1 * X_SIZE));
  const uint4* p2 = &g_x[0][0] + (off ^ (2 * X_SIZE));
  const uint4* p3 = &g_x[0][0] + (off ^ (3 * X_SIZE));
  while (clock_now() - sent < GATHER_DELAY) {}
  fetch(p1, A[1]); fetch(p2, A[2]); fetch(p3, A[3]);
  gather_wait<1, C>(A, off, tag);
}
template <int C> __device__ __forceinline__ void gather_rest(uint32_t (&A)[4][16], uint32_t off, uint32_t tag) {
  SCHED();
  gather_wait<C + 1, 3>(A, off, tag);
}
__device__ __forceinline__ void pack_acc(const float (&d)[32], uint32_t (&a)[16]) {
#pragma unroll
  for (int i = 0; i < 16; i++) a[i] = pack2(d[2 * i], d[2 * i + 1]);
}
__device__ __forceinline__ void res_store(uint32_t slot, const uint32_t (&a)[16]) {
#pragma unroll
  for (int s = 0; s < 4; s++) sts128(slot + s * 512, a[4 * s], a[4 * s + 1], a[4 * s + 2], a[4 * s + 3]);
}
__device__ __forceinline__ void res_load(uint32_t slot, float (&d)[32]) {
  uint32_t a[16];
#pragma unroll
  for (int s = 0; s < 4; s++) lds128(slot + s * 512, a[4 * s], a[4 * s + 1], a[4 * s + 2], a[4 * s + 3]);
#pragma unroll
  for (int i = 0; i < 16; i++) { d[2 * i] = bf_lo(a[i]); d[2 * i + 1] = bf_hi(a[i]); }
  pin(d);
}
__device__ __forceinline__ void tile_store(uint32_t maddr, const uint32_t (&a)[16]) {
#pragma unroll
  for (int s = 0; s < 4; s++) stsm4(maddr ^ (s << 5), &a[4 * s]);
}
__device__ __forceinline__ void tile_load(uint32_t maddr, uint32_t (&a)[16]) {
#pragma unroll
  for (int s = 0; s < 4; s++) ldsm4(maddr ^ (s << 5), &a[4 * s]);
}

struct RowAcc { float s[4], u[4], v[4]; };
__device__ __forceinline__ void row_acc(RowAcc& t, const uint32_t (&a)[16]) {
#pragma unroll
  for (int s = 0; s < 8; s++) {
    if ((s & 1) == 0) hmma(t.s, &a[2 * s], 0x3F803F80u, 0x3F803F80u);
    hmma8(t.u, &a[2 * s], a[2 * s]);
    hmma8(t.v, &a[2 * s], a[2 * s + 1]);
  }
}
__device__ __forceinline__ void stat_publish(const uint32_t (&a)[16], uint32_t b, uint32_t th, uint32_t tag) {
  RowAcc t = {};
  row_acc(t, a);
  const bool odd = th & 4;
  if ((th & 3) == ((th >> 3) & 3))
    st_vec(&g_x[b][X_ST + (th >> 2)], (__float_as_uint(t.s[0]) & ~1u) | tag, __float_as_uint(odd ? t.u[1] : t.u[0]),
           __float_as_uint(t.s[2]), __float_as_uint(odd ? t.v[3] : t.v[2]));
}
struct RowNorm { float m0, rs0, m1, rs1; };
__device__ __forceinline__ RowNorm row_norm(float s0, float q0, float s1, float q1, float scale) {
  RowNorm n;
  n.m0 = s0 * (1.f / DM); n.m1 = s1 * (1.f / DM);
  n.rs0 = scale * rsqrtf(fmaxf(fmaf(-n.m0, n.m0, q0 * (1.f / DM)), 0.f) + LN_EPS);
  n.rs1 = scale * rsqrtf(fmaxf(fmaf(-n.m1, n.m1, q1 * (1.f / DM)), 0.f) + LN_EPS);
  return n;
}
__device__ __forceinline__ RowNorm stat_gather(uint32_t b, uint32_t th, uint32_t tag, float scale) {
  const uint4* src = &g_x[b & ~3u][X_ST + (th >> 2)];
  uint32_t v[16], spin = 0;
  do {
#pragma unroll
    for (int j = 0; j < 4; j++) ld_vec(src + j * X_SIZE, v[4 * j], v[4 * j + 1], v[4 * j + 2], v[4 * j + 3]);
  } while (stale(miss(v, tag)) && ++spin < SPIN_LIMIT);
  float f[4];
#pragma unroll
  for (int i = 0; i < 4; i++)
    f[i] = (__uint_as_float(v[i]) + __uint_as_float(v[4 + i])) + (__uint_as_float(v[8 + i]) + __uint_as_float(v[12 + i]));
  return row_norm(f[0], f[1], f[2], f[3], scale);
}
constexpr uint32_t SM_NORM = SM_BASE + SM_STG + 2 * TILE_BYTES + 4096;
__device__ __forceinline__ void norm_produce(const RowNorm& n, uint32_t th, uint32_t qsel) {
  const bool sel = (th & 3) == qsel;
  const float a = sel ? -n.m0 : 0.f, c = sel ? -n.m1 : 0.f;
  const uint32_t ah = pack2(a, a), ch = pack2(c, c);
  const float al = a - bf_lo(ah), cl = c - bf_lo(ch);
  sts128(SM_NORM + th * 16, ah, ch, pack2(al, al), pack2(cl, cl));
  sts64(SM_NORM + 2048 + th * 8, __float_as_uint(n.rs0), __float_as_uint(n.rs1));
  bar_arrive(BAR_ST, 256);
}
__device__ __forceinline__ void norm_consume(uint32_t th, uint32_t (&mu)[4], float& rs0, float& rs1) {
  bar_sync(BAR_ST, 256);
  lds128(SM_NORM + th * 16, mu[0], mu[1], mu[2], mu[3]);
  asm volatile("ld.shared.v2.f32 {%0, %1}, [%2];" : "=f"(rs0), "=f"(rs1) : "r"(SM_NORM + 2048 + th * 8) : "memory");
}
__device__ __forceinline__ void scale_pack(const float (&d)[32], uint32_t (&a)[16], float rs0, float rs1) {
#pragma unroll
  for (int i = 0; i < 16; i++) { const float rs = (i & 1) ? rs1 : rs0; a[i] = pack2(d[2 * i] * rs, d[2 * i + 1] * rs); }
}
template <int S> __device__ __forceinline__ void silu_seg(float (&acc)[4][32], float (&tn)[2][4], uint32_t (&H)[4][16], float rs0, float rs1) {
  if (S >= 2) {
    const float* h = &acc[(S - 2) >> 3][4 * ((S - 2) & 7)];
    const float* v = tn[S & 1];
    uint32_t* o = &H[(S - 2) >> 3][2 * ((S - 2) & 7)];
    o[0] = pack2(fmaf(h[0], v[0], h[0]), fmaf(h[1], v[1], h[1]));
    o[1] = pack2(fmaf(h[2], v[2], h[2]), fmaf(h[3], v[3], h[3]));
    asm volatile("" : "+r"(o[0]), "+r"(o[1]));
  }
  if (S >= 1 && S <= 32) {
#pragma unroll
    for (int k = 0; k < 4; k++) tn[(S - 1) & 1][k] = tanh_hw(acc[((S - 1) >> 3) & 3][4 * ((S - 1) & 7) + k]);
  }
  if (S < 32) {
    float* h = &acc[(S >> 3) & 3][4 * (S & 7)];
    h[0] *= rs0; h[1] *= rs0; h[2] *= rs1; h[3] *= rs1;
    asm volatile("" : "+f"(h[0]), "+f"(h[1]), "+f"(h[2]), "+f"(h[3]));
  }
  SCHED();
}
template <int S0, int S1> __device__ __forceinline__ void silu_segs(float (&acc)[4][32], float (&tn)[2][4], uint32_t (&H)[4][16], float rs0, float rs1) {
  silu_seg<S0>(acc, tn, H, rs0, rs1);
  if constexpr (S0 + 1 < S1) silu_segs<S0 + 1, S1>(acc, tn, H, rs0, rs1);
}
template <int HALF> __device__ __forceinline__ void send_half(uint4* dst, const float (&d)[32], uint32_t tag) {
  uint32_t o[8];
#pragma unroll
  for (int i = 0; i < 8; i++) o[i] = pack2(d[16 * HALF + 2 * i], d[16 * HALF + 2 * i + 1]);
  o[0] = (o[0] & ~1u) | tag; o[4] = (o[4] & ~1u) | tag;
  pin(o);
  SCHED();
  st_vec(dst + HALF * 256, o[0], o[1], o[2], o[3]);
  st_vec(dst + HALF * 256 + 128, o[4], o[5], o[6], o[7]);
  SCHED();
}
template <int F, int N> __device__ __forceinline__ uint32_t send_residual(uint32_t (&a)[16], uint32_t xoff, uint32_t res, uint32_t tag) {
  const uint32_t exact[4] = {a[0], a[4], a[8], a[12]};
  publish(&g_x[0][X_AG0] + xoff, a, tag);
  const uint32_t sent = clock_now();
  stat_publish(a, blockIdx.x, xoff & 127, tag);
  res_store(res, a);
#pragma unroll
  for (int s = 0; s < 4; s++) sts32(res + s * 512, exact[s]);
  acquire_n<F, N>();
  return sent;
}
template <int F, int NEXT> __device__ __forceinline__ uint32_t proj_residual(uint32_t (&A)[4][16], uint32_t xoff, uint32_t res, uint32_t tag) {
  float acc[32];
  publish(&g_x[0][X_AG1] + xoff, A[0], tag);
  const uint32_t sent = clock_now();
  acquire_n<F, 2>();
  res_load(res, acc);
  mma_tile<false>(acc, A[0], LO(F));
  gather_first<2>(A, xoff + X_AG1, tag, sent);
  mma_tile<false>(acc, A[1], HI(F));
  mma_tile<false>(acc, A[2], LO(F + 1));
  gather_rest<2>(A, xoff + X_AG1, tag);
  PROF_MARK(F == F_WO ? 11 : 16);
  mma_tile<false>(acc, A[3], HI(F + 1));
  WG_WAIT(0); pin(acc);
  pack_acc(acc, A[0]);
  return send_residual<F + 2, NEXT>(A[0], xoff, res, tag);
}

__device__ __forceinline__ void qk_tile(float (&S)[32], const uint32_t (&Q)[16], uint64_t dk) {
#pragma unroll
  for (int s = 0; s < 4; s++) {
    if (s == 0) wgmma64_set<0>(S, &Q[0], dk); else wgmma64_acc<0>(S, &Q[4 * s], dk + s * 2);
  }
}
__device__ __forceinline__ void qk_shift(float (&S)[32], const uint32_t (&nm)[4]) { wgmma64_acc<0>(S, nm, (uint64_t)((SM_BASE + SM_ONE) >> 4)); }
constexpr uint64_t V_STEP = uint64_t(1) - (uint64_t(1) << 16);
constexpr uint64_t RING_V = RING - (uint64_t(1) << 16) + ((uint64_t)((SM_STG + 2 * TILE_BYTES) >> 4) << 16);
__device__ __forceinline__ void pv_tile(float (&O)[36], const uint32_t (&P)[16], uint64_t dv, uint64_t pad) {
#pragma unroll
  for (int s = 0; s < 4; s++) wgmma72_acc(O, &P[4 * s], dv + s * 128 * V_STEP + (s < 2 ? 0 : (s - 1) * pad));
}
__device__ __forceinline__ void attn_step(const float (&Sc)[32], float (&Sn)[32], uint32_t (&Pc)[16], uint32_t (&Pp)[16], float (&O)[36],
                                          const uint32_t (&Q)[16], const uint32_t (&nm)[4], uint64_t dk, uint64_t dv) {
  WG_FENCE();
  qk_tile(Sn, Q, dk);
  qk_shift(Sn, nm);
  pv_tile(O, Pp, dv, 0);
  WG_COMMIT();
  SCHED();
#pragma unroll
  for (int i = 0; i < 16; i++) Pc[i] = pack2(ex2_hw(Sc[2 * i]), ex2_hw(Sc[2 * i + 1]));
  pin(Pc);
  SCHED();
}
template <int R> __device__ __forceinline__ float tile_max(const float (&S)[32]) {
  float t[4];
#pragma unroll
  for (int j = 0; j < 4; j++) t[j] = fmaxf(fmaxf(S[8 * j + R], S[8 * j + R + 1]), fmaxf(S[8 * j + R + 4], S[8 * j + R + 5]));
  float n = fmaxf(fmaxf(t[0], t[1]), fmaxf(t[2], t[3]));
  n = fmaxf(n, __shfl_xor_sync(0xffffffffu, n, 1));
  return fmaxf(n, __shfl_xor_sync(0xffffffffu, n, 2));
}
__device__ __forceinline__ void attention_exact(float (&O)[36], const uint32_t (&Q)[16], int bh, int lane) {
  const char* kb = (const char*)&g_kv[bh][0][0][0];
  const char* vb = (const char*)&g_kv[bh][1][0][0];
  const int g = lane >> 2, q = lane & 3;
  float m0 = -INFINITY, m1 = -INFINITY, l0 = 0.f, l1 = 0.f;
  float o[8][4] = {};
#pragma unroll 1
  for (int k0 = 0; k0 < T_SEQ; k0 += 8) {
    float s[4] = {0.f, 0.f, 0.f, 0.f};
#pragma unroll
    for (int c = 0; c < 8; c++) hmma8(s, &Q[2 * c], __ldcg((const uint32_t*)(kb + (k0 + g) * 128 + ((c ^ g) << 4) + q * 4)));
    float n0 = fmaxf(s[0], s[1]), n1 = fmaxf(s[2], s[3]);
    n0 = fmaxf(n0, __shfl_xor_sync(0xffffffffu, n0, 1)); n1 = fmaxf(n1, __shfl_xor_sync(0xffffffffu, n1, 1));
    n0 = fmaxf(m0, fmaxf(n0, __shfl_xor_sync(0xffffffffu, n0, 2))); n1 = fmaxf(m1, fmaxf(n1, __shfl_xor_sync(0xffffffffu, n1, 2)));
    const float a0 = ex2_hw(m0 - n0), a1 = ex2_hw(m1 - n1);
    m0 = n0; m1 = n1;
    const uint32_t pp[2] = {pack2(ex2_hw(s[0] - n0), ex2_hw(s[1] - n0)), pack2(ex2_hw(s[2] - n1), ex2_hw(s[3] - n1))};
    l0 = fmaf(l0, a0, bf_lo(pp[0]) + bf_hi(pp[0])); l1 = fmaf(l1, a1, bf_lo(pp[1]) + bf_hi(pp[1]));
#pragma unroll
    for (int j = 0; j < 8; j++) {
      const uint32_t v0 = __ldcg((const uint16_t*)(vb + (k0 + 2 * q) * 128 + ((j ^ (2 * q)) << 4) + g * 2));
      const uint32_t v1 = __ldcg((const uint16_t*)(vb + (k0 + 2 * q + 1) * 128 + ((j ^ (2 * q + 1)) << 4) + g * 2));
      o[j][0] *= a0; o[j][1] *= a0; o[j][2] *= a1; o[j][3] *= a1;
      hmma8(o[j], pp, v0 | (v1 << 16));
    }
  }
  l0 += __shfl_xor_sync(0xffffffffu, l0, 1); l1 += __shfl_xor_sync(0xffffffffu, l1, 1);
  O[32] = l0 + __shfl_xor_sync(0xffffffffu, l0, 2); O[34] = l1 + __shfl_xor_sync(0xffffffffu, l1, 2);
#pragma unroll
  for (int i = 0; i < 32; i++) O[i] = o[i >> 2][i & 3];
}

__device__ __forceinline__ uint32_t fill_entry(int f, int r, int bh) {
  int m, x = r, y, dx = 0;
  if (f < F_QKV || f >= 48) {
    const int i = f & 15;
    m = f < F_QKV ? M_FF1A : M_FF2A;
    if (i < 8) { x = 4 * r + ((0xE2u >> i) & 1) * 2; y = r ^ ((0xE790u >> (2 * i)) & 3); dx = 1; }
    else { m++; x = r ^ (((i >> 1) - 3) & 3); y = 4 * r + 2 * (i & 1); }
  } else if (f < F_KV) {
    const int i = f - F_QKV;
    m = M_QKV;
    if (i == 1 || i >= 5) { y = r ^ (i == 1 ? 0 : 2); }
    else { x = 4 + r; y = r ^ (i ? i - 1 : 0); dx = 4; }
  } else if (f < F_WO) {
    const int i = f - F_KV;
    m = M_KV; x = 0; y = bh * 32 + (i & 2) * 8 + (i >> 2) * 4 + (i & 1) * 2;
  } else if (f >= F_PW1 && f < F_PW2) {
    m = M_PW1; y = r ^ (f - F_PW1); dx = 4;
  } else {
    m = f < F_PW1 ? M_WO : M_PW2; y = r ^ ((f & 1) * 2);
  }
  return m | (x << 4) | (y << 8) | (dx << 16);
}
__device__ __forceinline__ void tma_fill(uint32_t st, const CUtensorMap* map, uint32_t x, uint32_t y, uint32_t x2, uint32_t y2) {
  asm volatile("{\n.reg .pred p;\nelect.sync _|p, 0xffffffff;\n"
               "@p mbarrier.arrive.expect_tx.shared::cta.b64 _, [%1], 16384;\n"
               "@p cp.async.bulk.tensor.2d.shared::cluster.global.mbarrier::complete_tx::bytes [%0], [%2, {%3, %4}], [%1];\n"
               "@p cp.async.bulk.tensor.2d.shared::cluster.global.mbarrier::complete_tx::bytes [%0 + 8192], [%2, {%5, %6}], [%1];\n}"
               :: "r"(SM_BASE + st * STAGE_BYTES), "r"(SM_BASE + SM_FULL + st * 8), "l"(map), "r"(x), "r"(y), "r"(x2), "r"(y2) : "memory");
}
__device__ __forceinline__ void l2_prefetch(const void* p, uint32_t total, int b) {
  const uint32_t part = total / NCTA;
  asm volatile("cp.async.bulk.prefetch.L2.global [%0], %1;" :: "l"((const char*)p + (size_t)b * part), "r"(part) : "memory");
}

__global__ void __launch_bounds__(384, 1) conformer_kernel(const __grid_constant__ Params p) {
  extern __shared__ __align__(1024) uint8_t smem[];
  const int tid = threadIdx.x, lane = tid & 31;
  const int cw = __shfl_sync(0xffffffffu, tid >> 5, 0), wg = cw >> 2, w = cw & 3;
  const int b = blockIdx.x, r = b & 3, batch = b >> 6, t = (b >> 2) & 15;
  if ((uint32_t)__cvta_generic_to_shared(smem) != SM_BASE) return;
  PROF_MARK(0);
  PROF_TIME(30);

  if (cw == 8) {
    if (lane == 0) {
      asm volatile("prefetch.tensormap [%0];" :: "l"(&p.map[M_X]) : "memory");
      asm volatile("prefetch.tensormap [%0];" :: "l"(&p.map[M_FF1A]) : "memory");
      mbar_init(SM_BASE + SM_XBAR, 1);
#pragma unroll
      for (int i = 0; i < NSTAGE; i++) mbar_init(SM_BASE + SM_FULL + i * 8, 1);
      fence_async_smem();
    }
    __syncwarp();
    asm volatile("{\n.reg .pred p;\nelect.sync _|p, 0xffffffff;\n"
                 "@p mbarrier.arrive.expect_tx.shared::cta.b64 _, [%1], 32768;\n"
                 "@p cp.async.bulk.tensor.4d.shared::cluster.global.mbarrier::complete_tx::bytes [%0], [%2, {0, %3, 0, %4}], [%1];\n}"
                 :: "r"(SM_BASE + SM_STG), "r"(SM_BASE + SM_XBAR), "l"(&p.map[M_X]), "r"(t * 64), "r"(batch) : "memory");
    bar_arrive(0, 320);
  } else if (cw == 9) {
    if (lane == 0) {
#pragma unroll
      for (int i = 0; i < NSTAGE; i++) mbar_init(SM_BASE + SM_EMPTY + i * 8, 4);
    }
    __syncwarp();
    bar_arrive(0, 320);
    bar_arrive(BAR_INIT, 64);
  } else if (wg < 2) {
    if (tid < 144) sts128(SM_BASE + SM_CS + tid * 16, 0, 0, 0, 0);
    if (wg == 1) {
      const int i = tid - 128;
      sts32(SM_BASE + SM_EYE + i * 4, i >= 96 ? 0x3F803F80u : ((i & 32) == 0 && (i & 3) == ((i >> 3) & 3)) ? (0x3F00u << ((i & 4) * 4)) : 0u);
    }
    fence_async_smem();
    bar_sync(0, 320);
  }

  if (wg == 2) {
    asm volatile("setmaxnreg.dec.sync.aligned.u32 40;");
    if (w == 0) {
#pragma unroll 1
      for (int f = 0; f < 8; f++) {
        const uint32_t x = 256 * r + ((0xE2u >> f) & 1) * 128, y = (r ^ ((0xE790u >> (2 * f)) & 3)) * 64;
        tma_fill(f, &p.map[M_FF1A], x, y, x + 64, y);
      }
      PROF_MARK(1);
      const uint32_t* flag = &g_flag[batch * 4 + r][lane];
      const uint32_t prev = ((volatile uint32_t*)g_epoch)[b];
      uint32_t entry[2], ready = 0, st = 8, parity = 1;
#pragma unroll 1
      for (int i = 0; i < 2; i++) { entry[1] = fill_entry(i * 32 + lane, r, batch * 4 + r); if (i == 0) entry[0] = entry[1]; }
      bar_sync(BAR_INIT, 64);
#pragma unroll 1
      for (int f = 8; f < F_TOTAL; f++) {
        const uint32_t e = __shfl_sync(0xffffffffu, f < 32 ? entry[0] : entry[1], f);
        if ((e & 15) == M_KV) {
          const uint32_t need = 3u << ((e >> 8) & 31);
          uint32_t spin = 0;
#pragma unroll 1
          while ((ready & need) != need && ++spin < SPIN_LIMIT) {
            uint32_t v;
            asm volatile("ld.relaxed.gpu.global.u32 %0, [%1];" : "=r"(v) : "l"(flag) : "memory");
            ready = __ballot_sync(0xffffffffu, v - 1 == prev);
          }
        }
        mbar_wait(SM_BASE + SM_EMPTY + st * 8, parity);
        const uint32_t x = (e << 2) & 0x3C0, y = (e >> 2) & 0x3FC0, dx = (e >> 16) << 6;
        tma_fill(st, &p.map[e & 15], x, y, x + dx, dx ? y : y ^ 64);
        if (++st == NSTAGE) { st = 0; parity ^= 1; }
      }
    } else if (w < 3) {
      const int kind = w - 1;
      const uint32_t epoch = ((volatile uint32_t*)g_epoch)[b] + 1;
      if (kind == 0) {
        bar_sync(BAR_K, 160);
      } else {
        uint32_t v, spin = 0;
#pragma unroll 1
        do {
          asm volatile("ld.relaxed.gpu.global.u32 %0, [%1];" : "=r"(v) : "l"(&g_ready[(b & ~3) + (lane & 3)]) : "memory");
        } while (__any_sync(0xffffffffu, v != epoch) && ++spin < SPIN_LIMIT);
        bar_arrive(BAR_RDY, 160);
        bar_arrive(BAR_RDY1, 160);
        bar_sync(BAR_V, 160);
      }
      if (lane == 0) {
        asm volatile("cp.async.bulk.global.shared::cta.bulk_group [%0], [%1], %2;"
                     :: "l"(&g_kv[batch * 4 + r][kind][t][0]), "r"(SM_BASE + SM_STG + kind * TILE_BYTES), "r"(TILE_BYTES) : "memory");
        asm volatile("cp.async.bulk.commit_group;\ncp.async.bulk.wait_group 0;" ::: "memory");
        asm volatile("st.relaxed.gpu.global.u32 [%0], %1;" :: "l"(&g_flag[batch * 4 + r][kind * 16 + t]), "r"(epoch) : "memory");
      }
    } else {
      const uint32_t epoch = ((volatile uint32_t*)g_epoch)[b] + 1;
      if (lane < M_COUNT) asm volatile("prefetch.tensormap [%0];" :: "l"(&p.map[lane]) : "memory");
      if (lane == 0) l2_prefetch(p.w_ff1b, 1024 * 256 * 2, b);
#pragma unroll 1
      for (int i = 0; i < 33; i++) {
        const uint32_t t0 = clock_now();
        st_vec(&g_x[b][X_CLEAR + i * 32 + lane], 0u, 0u, 0u, 0u);
        while (clock_now() - t0 < 40) {}
      }
      asm volatile("fence.acq_rel.gpu;" ::: "memory");
      __syncwarp();
      if (lane == 0) {
        asm volatile("st.relaxed.gpu.global.u32 [%0], %1;" :: "l"(&g_ready[b]), "r"(epoch) : "memory");
        l2_prefetch(p.w_o, 256 * 256 * 2, b);
        l2_prefetch(p.w_pw2, 256 * 256 * 2, b);
        l2_prefetch(p.w_ff2b, 1024 * 256 * 2, b);
      }
    }
  } else {
    asm volatile("setmaxnreg.inc.sync.aligned.u32 232;");
    const int q = lane & 3, th = tid & 127;
    constexpr uint32_t stg = SM_BASE + SM_STG;
    const uint32_t mrow = 16 * w + (lane & 15);
    const uint32_t maddr = stg + mrow * 128 + (((lane >> 4) ^ (lane & 7)) << 4);
    const uint32_t res = stg + 3 * TILE_BYTES + w * 2048 + lane * 16;
    const uint32_t xoff = b * X_SIZE + th;
    const int nvalid = T_SEQ - t * 64, row0 = 16 * w + (lane >> 2);

    uint32_t A[4][16];
    uint32_t sent = 0;
    mbar_wait(SM_BASE + SM_XBAR, 0);
    PROF_MARK(1);
#pragma unroll
    for (int c = 0; c < 4; c++) tile_load(maddr + (r ^ c) * TILE_BYTES, A[c]);
    if (wg == 0) {
      float sa[4] = {0.f, 0.f, 0.f, 0.f}, sb[4] = {0.f, 0.f, 0.f, 0.f};
#pragma unroll
      for (int i = 0; i < 16; i++) hmma((i & 1) ? sb : sa, &A[i >> 2][4 * (i & 3)], 0x3F803F80u, 0x3F803F80u);
      bar_arrive(BAR_X, 256);
      const float s0 = (sa[0] + sb[0]) * (1.f / DM), s1 = (sa[2] + sb[2]) * (1.f / DM);
      const uint32_t m0 = pack2(s0, s0), m1 = pack2(s1, s1);
#pragma unroll
      for (int c = 0; c < 4; c++) {
#pragma unroll
        for (int i = 0; i < 16; i++) asm("sub.rn.bf16x2 %0, %0, %1;" : "+r"(A[c][i]) : "r"((i & 1) ? m1 : m0));
        pin(A[c]);
      }
    } else {
      const uint32_t epoch = ((volatile uint32_t*)g_epoch)[b] + 1, tag = epoch & 1;
      uint4 cv[8];
      if (b < 72) {
        const __nv_bfloat16* wp; int ld, col;
        if (b < 24) { wp = p.w_qkv; ld = 768; col = b * 32; }
        else if (b < 40) { wp = p.w_pw1; ld = 512; col = (b - 24) * 32; }
        else { wp = p.w_ff2a; ld = 1024; col = (b - 40) * 32; }
        const uint4* src = (const uint4*)(wp + (size_t)(th >> 2) * ld + col + q * 8);
#pragma unroll
        for (int i = 0; i < 8; i++) cv[i] = __ldg(src + i * 4 * ld);
      }
      {
        RowAcc ra[4] = {};
#pragma unroll
        for (int c = 0; c < 4; c++) row_acc(ra[c], A[c]);
        const bool odd = lane & 4;
        const int src = (lane & 28) | (lane >> 3);
        float f[4] = {0.f, 0.f, 0.f, 0.f};
#pragma unroll
        for (int c = 0; c < 4; c++) { f[0] += ra[c].s[0]; f[1] += odd ? ra[c].u[1] : ra[c].u[0]; f[2] += ra[c].s[2]; f[3] += odd ? ra[c].v[3] : ra[c].v[2]; }
        const float q0 = __shfl_sync(0xffffffffu, f[1], src), q1 = __shfl_sync(0xffffffffu, f[3], src);
        bar_sync(BAR_X, 256);
        res_store(res, A[0]);
        norm_produce(row_norm(f[0], q0, f[2], q1, 0.5f), th, 4);
      }
      PROF_MARK(5);
      if (b < 72) {
        float c[8] = {0.f, 0.f, 0.f, 0.f, 0.f, 0.f, 0.f, 0.f};
#pragma unroll
        for (int i = 0; i < 8; i++) {
          const uint4 v = cv[i];
          c[0] += bf_lo(v.x); c[1] += bf_hi(v.x); c[2] += bf_lo(v.y); c[3] += bf_hi(v.y);
          c[4] += bf_lo(v.z); c[5] += bf_hi(v.z); c[6] += bf_lo(v.w); c[7] += bf_hi(v.w);
        }
#pragma unroll 1
        for (int m = 4; m <= 16; m <<= 1)
#pragma unroll
          for (int k = 0; k < 8; k++) c[k] += __shfl_xor_sync(0xffffffffu, c[k], m);
        if (lane < 4) {
          const uint32_t a = SM_BASE + SM_CS + 1792 + w * 128 + lane * 32;
          sts128(a, __float_as_uint(c[0]), __float_as_uint(c[1]), __float_as_uint(c[2]), __float_as_uint(c[3]));
          sts128(a + 16, __float_as_uint(c[4]), __float_as_uint(c[5]), __float_as_uint(c[6]), __float_as_uint(c[7]));
        }
        bar_sync(BAR_WG1, 128);
        if (th < 8) {
          float o[4] = {0.f, 0.f, 0.f, 0.f};
#pragma unroll 1
          for (int k = 0; k < 4; k++) {
            uint32_t e[4];
            lds128(SM_BASE + SM_CS + 1792 + k * 128 + th * 16, e[0], e[1], e[2], e[3]);
#pragma unroll
            for (int i = 0; i < 4; i++) o[i] += __uint_as_float(e[i]);
          }
          st_vec(&g_cs[b * 8 + th], (__float_as_uint(o[0]) & ~1u) | tag, __float_as_uint(o[1]), __float_as_uint(o[2]), __float_as_uint(o[3]));
        }
      }
      bar_sync(BAR_WG1, 128);
      PROF_MARK(2);
#pragma unroll 1
      for (int i = th; i < 144; i += 128) {
        const int j = i >> 4;
        int src;
        if (j < CS_PW1) src = 320 + 64 * r + i;
        else if (j < CS_QKV) src = 192 + (j - CS_PW1) * 64 + 16 * r + (i & 15);
        else src = ((j - CS_QKV + 1) % 3) * 64 + 16 * r + (i & 15);
        uint32_t e[4], spin = 0;
#pragma unroll 1
        do {
          ld_vec(&g_cs[src], e[0], e[1], e[2], e[3]);
        } while (((e[0] ^ tag) & 1u) && ++spin < SPIN_LIMIT);
        const float c0 = __uint_as_float(e[0] & ~1u), c1 = __uint_as_float(e[1]), c2 = __uint_as_float(e[2]), c3 = __uint_as_float(e[3]);
        const uint32_t h0 = pack2(c0, c1), h1 = pack2(c2, c3);
        const uint32_t a = SM_BASE + SM_CS + j * 256 + (i & 15) * 8;
        sts64(a ^ ((a >> 3) & 0x70), h0, h1);
        sts64((a + 128) ^ (((a + 128) >> 3) & 0x70), pack2(c0 - bf_lo(h0), c1 - bf_hi(h0)), pack2(c2 - bf_lo(h1), c3 - bf_hi(h1)));
      }
      fence_async_smem();
      PROF_MARK(4);
      bar_sync(BAR_RDY1, 160);
      norm_produce(stat_gather(b, th, 1, 1.f), th, 3);
    }

#pragma unroll 1
    for (uint32_t pass = 0; pass < 2; pass++) {
      uint32_t Q[16];
      if (wg == 0) {
        float acc[4][32];
        uint32_t H[4][16];
        ACQUIRE(0);
        mma_tile<true>(acc[0], A[0], LO(0)); mma_tile<true>(acc[1], A[0], HI(0));
        ACQUIRE(1);
        mma_tile<true>(acc[2], A[0], LO(1)); mma_tile<true>(acc[3], A[0], HI(1));
        acquire_n<2, 3>();
        if (pass) gather_first<1>(A, here(xoff) + X_AG0, 1, sent);
        mma_tile<false>(acc[0], A[1], LO(2)); mma_tile<false>(acc[1], A[1], HI(2));
        WG_WAIT(2);
        uint32_t mu[4];
        float rs0, rs1, tn[2][4];
        norm_consume(here(th), mu, rs0, rs1);
        if (pass) { gather_rest<1>(A, xoff + X_AG0, 1); RELEASE(F_PW2, F_PW2 + 1); }
        PROF_MARK(2 + pass * 16);
        mma_tile<false>(acc[0], A[2], LO(3));
        mma_tile_fold<2 * CS_FF2>(acc[0], A[3], LO(4), mu);
        RELEASE(0, 1);
        acquire_n<5, 3>();
        mma_tile<false>(acc[1], A[2], HI(3));
#define SEGS(a, b) silu_segs<a, b>(acc, tn, H, rs0, rs1)
        WG_WAIT(1); pin(acc[0]);
        SEGS(0, 1);
        mma_tile_fold<2 * CS_FF2 + 2>(acc[1], A[3], HI(4), mu);
        SEGS(1, 4);
        mma_tile<false>(acc[2], A[1], LO(5));
        SEGS(4, 6);
        mma_tile<false>(acc[2], A[2], LO(6));
        SEGS(6, 8);
        WG_WAIT(2); pin(acc[1]);
        RELEASE(2, 4);
        SEGS(8, 9);
        mma_tile_fold<2 * CS_FF2 + 4>(acc[2], A[3], LO(7), mu);
        SEGS(9, 12);
        mma_tile<false>(acc[3], A[1], HI(5));
        acquire_n<8, 2>();
        SEGS(12, 14);
        mma_tile<false>(acc[3], A[2], HI(6));
        SEGS(14, 16);
        WG_WAIT(2); pin(acc[2]);
        SEGS(16, 17);
        mma_tile_fold<2 * CS_FF2 + 6>(acc[3], A[3], HI(7), mu);
        SEGS(17, 20);
        mma_tile_reuse(acc[1], H[0], LO(8));
        acquire_n<10, 2>();
        SEGS(20, 22);
        mma_tile<false>(acc[1], H[1], HI(8));
        SEGS(22, 24);
        WG_WAIT(2); pin(acc[3]);
        RELEASE(5, 7);
        SEGS(24, 26);
        mma_tile<false>(acc[1], H[2], LO(9));
        SEGS(26, 28);
        mma_tile_reuse(acc[2], H[0], LO(10));
        SEGS(28, 31);
        mma_tile<false>(acc[2], H[1], HI(10));
        SEGS(31, 34);
#undef SEGS
        PROF_MARK(3 + pass * 16);
        const uint32_t rtag = here(pass ^ 1);
        const uint4* rs_in = &g_x[0][X_RS] + here(xoff);
        mma_tile<false>(acc[1], H[3], HI(9));
        mma_tile<false>(acc[2], H[2], LO(11));
        acquire_n<12, 2>();
        uint4* rs_out = &g_x[0][X_RS] + (here(xoff) ^ (1 * X_SIZE));
        mma_tile<false>(acc[2], H[3], HI(11));
        WG_WAIT(2); pin(acc[1]);
        send_half<0>(rs_out, acc[1], rtag);
        mma_tile_reuse(acc[3], H[0], LO(12));
        SCHED();
        send_half<1>(rs_out, acc[1], rtag);
        mma_tile<false>(acc[3], H[1], HI(12));
        rs_out = &g_x[0][X_RS + 512] + (here(xoff) ^ (2 * X_SIZE));
        WG_WAIT(2); pin(acc[2]);
        send_half<0>(rs_out, acc[2], rtag);
        mma_tile<false>(acc[3], H[2], LO(13));
        SCHED();
        send_half<1>(rs_out, acc[2], rtag);
        mma_tile<false>(acc[3], H[3], HI(13));
        RELEASE(8, 9);
        acquire_n<14, 2>();
        mma_tile_reuse(acc[1], H[0], LO(14));
        rs_out = &g_x[0][X_RS + 1024] + (here(xoff) ^ (3 * X_SIZE));
        if (!pass) bar_sync(BAR_RDY, 160);
        fetch(rs_in, A[1]);
        SCHED();
        mma_tile<false>(acc[1], H[1], HI(14));
        WG_WAIT(2); pin(acc[3]);
        send_half<0>(rs_out, acc[3], rtag);
        send_half<1>(rs_out, acc[3], rtag);
        mma_tile<false>(acc[1], H[2], LO(15)); mma_tile<false>(acc[1], H[3], HI(15));
        SCHED();
        res_load(res, acc[2]);
        confirm(rs_in, A[1], rtag);
        mma_add_half(acc[2], A[1]);
        PROF_MARK(44);
        fetch(rs_in + 512, A[2]);
        fetch(rs_in + 1024, A[3]);
        confirm(rs_in + 512, A[2], rtag);
        mma_add_half(acc[2], A[2]);
        SCHED();
        confirm(rs_in + 1024, A[3], rtag);
        mma_add_half(acc[2], A[3]);
        PROF_MARK(4 + pass * 16);
        WG_WAIT(0); pin(acc[2]); pin(acc[1]);
#pragma unroll
        for (int i = 0; i < 16; i++) A[0][i] = pack2(fmaf(acc[1][2 * i], 0.5f, acc[2][2 * i]), fmaf(acc[1][2 * i + 1], 0.5f, acc[2][2 * i + 1]));
        if (pass) {
          PROF_MARK(21);
          stat_publish(A[0], b, here(th), 0);
          const RowNorm fn = stat_gather(b, here(th), 0, 1.f);
          const float nm0 = -fn.m0 * fn.rs0, nm1 = -fn.m1 * fn.rs1;
#pragma unroll
          for (int i = 0; i < 16; i++) {
            const float rs = (i & 1) ? fn.rs1 : fn.rs0, nm = (i & 1) ? nm1 : nm0;
            A[0][i] = pack2(fmaf(bf_lo(A[0][i]), rs, nm), fmaf(bf_hi(A[0][i]), rs, nm));
          }
          tile_store(here(maddr), A[0]);
          __syncwarp();
          const int row = 16 * w + (lane >> 3);
          uint4* dst = (uint4*)(p.out + ((size_t)batch * T_SEQ + t * 64 + row) * DM + 64 * r) + (lane & 7);
          const uint32_t src = stg + row * 128 + (((lane & 7) ^ (lane >> 3)) << 4);
#pragma unroll
          for (int i = 0; i < 4; i++) {
            uint4 v;
            lds128((src ^ ((i & 1) << 6)) + i * 512, v.x, v.y, v.z, v.w);
            if (row + 4 * i < nvalid) dst[i * 4 * (DM / 8)] = v;
          }
          PROF_MARK(22);
          PROF_TIME(31);
          break;
        }
        sent = send_residual<F_QKV, 6>(A[0], here(xoff), res, 1);
        PROF_MARK(5);
        mma_tile<true>(acc[0], A[0], LO(F_QKV)); mma_tile<true>(acc[1], A[0], HI(F_QKV));
        mma_tile<true>(acc[2], A[0], LO(F_QKV + 1));
        gather_first<1>(A, here(xoff) + X_AG0, 1, sent);
        mma_tile<false>(acc[0], A[1], LO(F_QKV + 2)); mma_tile<false>(acc[1], A[1], HI(F_QKV + 2));
        norm_consume(here(th), mu, rs0, rs1);
        if (row0 >= nvalid) rs0 = 0.f;
        if (row0 + 8 >= nvalid) rs1 = 0.f;
        gather_rest<1>(A, xoff + X_AG0, 1);
        PROF_MARK(6);
        mma_tile<false>(acc[0], A[2], LO(F_QKV + 3));
        mma_tile_fold<2 * CS_QKV - 6>(acc[0], A[3], LO(F_QKV + 4), mu);
        RELEASE(10, 15);
        mma_tile<false>(acc[1], A[2], HI(F_QKV + 3));
        mma_tile_fold<2 * CS_QKV - 4>(acc[1], A[3], HI(F_QKV + 4), mu);
        WG_WAIT(2); pin(acc[0]);
        scale_pack(acc[0], Q, rs0, rs1);
        tile_store(here(maddr), Q);
        fence_async_smem();
        bar_arrive(BAR_K, 160);
        mma_tile<false>(acc[2], A[1], HI(F_QKV + 1)); mma_tile<false>(acc[2], A[2], LO(F_QKV + 5));
        WG_WAIT(2); pin(acc[1]);
        scale_pack(acc[1], Q, rs0, rs1);
        tile_store(here(maddr) + TILE_BYTES, Q);
        fence_async_smem();
        bar_arrive(BAR_V, 160);
        mma_tile_fold<2 * CS_QKV - 2>(acc[2], A[3], HI(F_QKV + 5), mu);
        WG_WAIT(0); pin(acc[2]);
        scale_pack(acc[2], Q, rs0 * SM_SCALE_LOG2, rs1 * SM_SCALE_LOG2);
        res_store(here(res) - TILE_BYTES, Q);
        bar_arrive(BAR_Q, 256);
        acquire_n<F_SPARE, 2>();
        RELEASE(F_QKV, F_SPARE + 1);
      } else {
        bar_sync(BAR_Q, 256);
#pragma unroll
        for (int s = 0; s < 4; s++) lds128(res - TILE_BYTES + s * 512, Q[4 * s], Q[4 * s + 1], Q[4 * s + 2], Q[4 * s + 3]);
        if (w < 2) {
          const uint32_t v = w ? 0u : 0x3F803F80u;
#pragma unroll
          for (int s = 0; s < 4; s++) sts128(res - TILE_BYTES + s * 512, v, v, v, v);
          fence_async_smem();
        }
      }
      bar_sync(BAR_ATT, 256);
      PROF_MARK(7);

      float O[36];
      {
        float S[2][32];
        uint32_t P[2][16], nm[4];
        pin(Q);
        WG_FENCE();
        qk_tile(S[0], Q, RING + (SM_STG >> 4));
        WG_COMMIT();
#pragma unroll
        for (int i = 0; i < 36; i++) O[i] = 0.f;
#pragma unroll
        for (int i = 0; i < 16; i++) P[1][i] = 0u;
        WG_WAIT(0); pin(S[0]);
        const float m0 = tile_max<0>(S[0]), m1 = tile_max<2>(S[0]);
        nm[0] = pack2(q ? 0.f : -m0, 0.f); nm[1] = pack2(q ? 0.f : -m1, 0.f); nm[2] = 0u; nm[3] = 0u;
        pin(nm); pin(O); pin(P[1]);
        uint32_t sk = wg, sv = wg;
        mbar_wait(SM_BASE + SM_FULL + sk * 8, 0);
        PROF_MARK(8);
        WG_FENCE();
        qk_tile(S[0], Q, RING + sk * 1024);
        qk_shift(S[0], nm);
        WG_COMMIT();
        WG_WAIT(0); pin(S[0]);
#pragma unroll 1
        for (int it = 0; it < 4; it++) {
          attn_step(S[0], S[1], P[0], P[1], O, Q, nm, RING + sk * 1024 + 512, RING_V + (sv * 1024 + 512) * V_STEP);
          const uint32_t sn = it >= 2 ? wg : sk + 4;
          mbar_wait(SM_BASE + SM_FULL + sn * 8, it >= 2);
          mbar_wait(SM_BASE + SM_FULL + (sk + 2) * 8, it == 3);
          WG_WAIT(0); pin(O); pin(S[1]); pin(P[1]);
          if (lane == 0 && it < 3) {
            mbar_arrive(SM_BASE + SM_EMPTY + sk * 8);
            if (it) mbar_arrive(SM_BASE + SM_EMPTY + sv * 8);
          }
          sv = sk + 2; sk = sn;
          attn_step(S[1], S[0], P[1], P[0], O, Q, nm, RING + sk * 1024, RING_V + (sv * 1024) * V_STEP);
          WG_WAIT(0); pin(O); pin(S[0]); pin(P[0]);
        }
        WG_FENCE();
        pv_tile(O, P[1], RING_V + (sv * 1024 + 512) * V_STEP, (uint64_t)wg << 22);
        WG_COMMIT();
        WG_WAIT(0); pin(O);
      }
      PROF_MARK(9);

      if (wg == 1) {
        const uint32_t mo = stg + here(th) * 16;
#pragma unroll
        for (int i = 0; i < 9; i++)
          sts128(mo + i * 2048 + (i >> 3) * 4096, __float_as_uint(O[4 * i]), __float_as_uint(O[4 * i + 1]), __float_as_uint(O[4 * i + 2]), __float_as_uint(O[4 * i + 3]));
        bar_arrive(BAR_MERGE, 256);
        norm_produce(stat_gather(b, here(th), 0, 0.5f), here(th), 0);
      } else {
        const uint32_t mo = stg + here(th) * 16;
        bar_sync(BAR_MERGE, 256);
#pragma unroll
        for (int i = 8; i >= 0; i--) {
          uint32_t e[4];
          lds128(mo + i * 2048 + (i >> 3) * 4096, e[0], e[1], e[2], e[3]);
#pragma unroll
          for (int k = 0; k < 4; k++) O[4 * i + k] += __uint_as_float(e[k]);
        }
        const bool safe = O[32] > 0x1p-60f && O[32] < 0x1p60f && O[34] > 0x1p-60f && O[34] < 0x1p60f;
        if (__builtin_expect(__any_sync(0xffffffffu, !safe), 0)) attention_exact(O, Q, batch * 4 + r, lane);
        const float i0 = rcp_hw(O[32]), i1 = rcp_hw(O[34]);
#pragma unroll
        for (int i = 0; i < 16; i++) { const float v = (i & 1) ? i1 : i0; A[0][i] = pack2(O[2 * i] * v, O[2 * i + 1] * v); }
        PROF_MARK(10);
        sent = proj_residual<F_WO, 4>(A, here(xoff), res, 0);
        PROF_MARK(12);
      }

      const int dir = cw == 0 ? -1 : 1;
      uint32_t tap[15];
      {
        const uint32_t* dwp = (const uint32_t*)(p.dw + 64 * r) + lane + 7 * (DM / 2);
#pragma unroll
        for (int k = 0; k < 15; k++) tap[k] = __ldg(dwp + dir * (k - 7) * (DM / 2));
      }

      if (wg == 0) {
        float acc[2][32];
        mma_tile<true>(acc[0], A[0], LO(F_PW1)); mma_tile<true>(acc[1], A[0], HI(F_PW1));
        gather_first<1>(A, here(xoff) + X_AG0, 0, sent);
        mma_tile<false>(acc[1], A[1], HI(F_PW1 + 1)); mma_tile<false>(acc[0], A[1], LO(F_PW1 + 1));
        uint32_t mu[4];
        float rs0, rs1;
        norm_consume(here(th), mu, rs0, rs1);
        if (row0 >= nvalid) rs0 = 0.f;
        if (row0 + 8 >= nvalid) rs1 = 0.f;
        gather_rest<1>(A, xoff + X_AG0, 0);
        PROF_MARK(13);
        mma_tile<false>(acc[1], A[2], HI(F_PW1 + 2));
        mma_tile_fold<2 * CS_PW1 + 2>(acc[1], A[3], HI(F_PW1 + 3), mu);
        RELEASE(F_KV + 10, F_WO + 1);
        mma_tile<false>(acc[0], A[2], LO(F_PW1 + 2));
        mma_tile_fold<2 * CS_PW1>(acc[0], A[3], LO(F_PW1 + 3), mu);
        WG_WAIT(2); pin(acc[1]);
#pragma unroll
        for (int i = 0; i < 32; i++) acc[1][i] = tanh_hw(acc[1][i] * ((i & 2) ? rs1 : rs0));
#pragma unroll
        for (int i = 0; i < 32; i++) { const float rs = (i & 2) ? rs1 : rs0; acc[1][i] = fmaf(acc[1][i], rs, rs); }
        pin(acc[1]);
        SCHED();
        WG_WAIT(0); pin(acc[0]);
#pragma unroll
        for (int i = 0; i < 16; i++) A[0][i] = pack2(acc[0][2 * i] * acc[1][2 * i], acc[0][2 * i + 1] * acc[1][2 * i + 1]);
        const uint32_t ga = stg + TILE_BYTES + here(mrow) * G_PITCH + (lane >> 4) * 16;
#pragma unroll
        for (int s = 0; s < 4; s++) stsm4(ga + s * 32, &A[0][4 * s]);
        RELEASE(F_PW1, F_PW1 + 3);
      }
      bar_sync(BAR_G, 256);
      PROF_MARK(14);

      {
        const int first = cw == 0 ? 14 : 8 * cw - 7;
        const uint32_t gsrc = stg + TILE_BYTES + first * G_PITCH + lane * 4;
        uint32_t in[22];
#pragma unroll
        for (int i = 0; i < 15; i++) in[i] = lds32(gsrc + dir * i * (int)G_PITCH);
        const bool edge = cw == 0 || cw == 7;
        const bool nbr = cw == 0 ? t > 0 : t < 15;
        if (edge) {
          if (nbr) {
            uint4* dst = &g_x[b + 4 * dir][X_HALO + (cw == 0 ? 96 : 0) + lane];
            st_vec(dst, HALO_TAG, in[14], in[13], in[12]);
            st_vec(dst + 32, HALO_TAG, in[11], in[10], in[9]);
            st_vec(dst + 64, HALO_TAG, in[8], 0u, 0u);
          }
        } else {
#pragma unroll
          for (int i = 15; i < 22; i++) in[i] = lds32(gsrc + i * G_PITCH);
        }
        float cl[8], ch[8], tl[15], tv[15];
#pragma unroll
        for (int k = 0; k < 15; k++) { tl[k] = bf_lo(tap[k]); tv[k] = bf_hi(tap[k]); }
#pragma unroll
        for (int o = 0; o < 8; o++) { cl[o] = 0.f; ch[o] = 0.f; }
#pragma unroll
        for (int i = 0; i < 15; i++) {
          const float lo = bf_lo(in[i]), hi = bf_hi(in[i]);
#pragma unroll
          for (int o = 0; o < 8; o++)
            if (i - o >= 0) { cl[o] = fmaf(lo, tl[i - o], cl[o]); ch[o] = fmaf(hi, tv[i - o], ch[o]); }
        }
        if (edge) {
#pragma unroll
          for (int i = 15; i < 22; i++) in[i] = 0u;
          if (nbr) {
            const uint4* src = &g_x[b][X_HALO + (cw == 0 ? 0 : 96) + lane];
            uint32_t e0, e1, e2, u0, u1, spin = 0;
#pragma unroll 1
            do {
              ld_vec(src, e0, in[15], in[16], in[17]);
              ld_vec(src + 32, e1, in[18], in[19], in[20]);
              ld_vec(src + 64, e2, in[21], u0, u1);
            } while (__any_sync(0xffffffffu, ((e0 ^ HALO_TAG) | (e1 ^ HALO_TAG) | (e2 ^ HALO_TAG)) != 0) && ++spin < SPIN_LIMIT);
          }
        }
#pragma unroll
        for (int i = 15; i < 22; i++) {
          const float lo = bf_lo(in[i]), hi = bf_hi(in[i]);
#pragma unroll
          for (int o = 0; o < 8; o++)
            if (i - o <= 14) { cl[o] = fmaf(lo, tl[i - o], cl[o]); ch[o] = fmaf(hi, tv[i - o], ch[o]); }
        }
        const uint32_t fl = cw == 0 ? 7 : 0;
        const uint32_t cdst = (stg + cw * 1024 + lane * 4) ^ (fl * 144);
#pragma unroll
        for (int o = 0; o < 8; o++) {
          const float a = 0.5f * cl[o], c = 0.5f * ch[o];
          sts32(cdst ^ (o * 144), pack2(fmaf(a, tanh_hw(a), a), fmaf(c, tanh_hw(c), c)));
        }
      }
      if (wg == 1) {
        bar_arrive(BAR_C, 256);
        norm_produce(stat_gather(b, here(th), 1, 0.5f), here(th), 0);
        if (th == 0) ((volatile uint32_t*)g_epoch)[b] += 1;
        break;
      }
      bar_sync(BAR_C, 256);
      tile_load(here(maddr), A[0]);
      PROF_MARK(15);
      sent = proj_residual<F_PW2, 1>(A, here(xoff), res, 1);
      PROF_MARK(17);
    }
  }
}

typedef CUresult (*EncodeFn)(CUtensorMap*, CUtensorMapDataType, cuuint32_t, void*, const cuuint64_t*, const cuuint64_t*,
                             const cuuint32_t*, const cuuint32_t*, CUtensorMapInterleave, CUtensorMapSwizzle,
                             CUtensorMapL2promotion, CUtensorMapFloatOOBfill);

void make_map(EncodeFn fn, CUtensorMap* m, const void* w, int rows, int cols, CUtensorMapSwizzle swz) {
  const cuuint64_t dims[2] = {(cuuint64_t)cols, (cuuint64_t)rows}, strides[1] = {(cuuint64_t)cols * 2};
  const cuuint32_t box[2] = {64, 64}, es[2] = {1, 1};
  fn(m, CU_TENSOR_MAP_DATA_TYPE_BFLOAT16, 2, const_cast<void*>(w), dims, strides, box, es, CU_TENSOR_MAP_INTERLEAVE_NONE,
     swz, CU_TENSOR_MAP_L2_PROMOTION_L2_128B, CU_TENSOR_MAP_FLOAT_OOB_FILL_NONE);
}

}

extern "C" void kernel_launch(void* const* d_in, const int* in_sizes, int n_in, void* d_out, int out_size) {
  static EncodeFn fn = nullptr;
  static void* kv = nullptr;
  if (!fn) {
    void* f = nullptr;
    cudaDriverEntryPointQueryResult st;
    cudaGetDriverEntryPoint("cuTensorMapEncodeTiled", &f, cudaEnableDefault, &st);
    fn = (EncodeFn)f;
    cudaGetSymbolAddress(&kv, g_kv);
    cudaFuncSetAttribute(conformer_kernel, cudaFuncAttributeMaxDynamicSharedMemorySize, SM_TOTAL);
  }
  typedef const __nv_bfloat16* W;
  const CUtensorMapSwizzle S = CU_TENSOR_MAP_SWIZZLE_128B;
  Params p;
  {
    const cuuint64_t dims[4] = {64, T_SEQ, 4, 2}, strides[3] = {512, 128, T_SEQ * 512};
    const cuuint32_t box[4] = {64, 64, 4, 1}, es[4] = {1, 1, 1, 1};
    fn(&p.map[M_X], CU_TENSOR_MAP_DATA_TYPE_BFLOAT16, 4, d_in[0], dims, strides, box, es, CU_TENSOR_MAP_INTERLEAVE_NONE, S,
       CU_TENSOR_MAP_L2_PROMOTION_L2_128B, CU_TENSOR_MAP_FLOAT_OOB_FILL_NONE);
  }
  make_map(fn, &p.map[M_FF1A], d_in[1], 256, 1024, S);
  make_map(fn, &p.map[M_FF1B], d_in[2], 1024, 256, S);
  make_map(fn, &p.map[M_QKV], d_in[3], 256, 768, S);
  make_map(fn, &p.map[M_KV], kv, 16384, 64, CU_TENSOR_MAP_SWIZZLE_NONE);
  make_map(fn, &p.map[M_WO], d_in[4], 256, 256, S);
  make_map(fn, &p.map[M_PW1], d_in[5], 256, 512, S);
  make_map(fn, &p.map[M_PW2], d_in[7], 256, 256, S);
  make_map(fn, &p.map[M_FF2A], d_in[8], 256, 1024, S);
  make_map(fn, &p.map[M_FF2B], d_in[9], 1024, 256, S);
  p.w_ff1b = (W)d_in[2]; p.w_qkv = (W)d_in[3]; p.w_o = (W)d_in[4]; p.w_pw1 = (W)d_in[5];
  p.dw = (W)d_in[6]; p.w_pw2 = (W)d_in[7]; p.w_ff2a = (W)d_in[8]; p.w_ff2b = (W)d_in[9];
  p.out = (__nv_bfloat16*)d_out;

  cudaLaunchConfig_t cfg = {};
  cfg.gridDim = dim3(NCTA);
  cfg.blockDim = dim3(384);
  cfg.dynamicSmemBytes = SM_TOTAL;
  cfg.stream = cudaStreamPerThread;
  cudaLaunchAttribute at[1];
  at[0].id = cudaLaunchAttributeCooperative;
  at[0].val.cooperative = 1;
  cfg.attrs = at;
  cfg.numAttrs = 1;
  cudaLaunchKernelEx(&cfg, conformer_kernel, p);
}
```

```cpp
#include <cuda_runtime.h>
#include <cuda_bf16.h>
#include <cuda.h>
#include <stdint.h>

namespace {

constexpr int T_SEQ = 1000;
constexpr int DM = 256;
constexpr int NCTA = 128;
constexpr int NSTAGE = 12;
constexpr uint32_t STAGE_BYTES = 16384;
constexpr uint32_t TILE_BYTES = 8192;
constexpr uint32_t SM_BASE = 1024;
constexpr uint32_t SM_STG = NSTAGE * STAGE_BYTES;
constexpr uint32_t SM_FULL = SM_STG + 32768;
constexpr uint32_t SM_EMPTY = SM_FULL + 96;
constexpr uint32_t SM_XBAR = SM_FULL + 192;
constexpr uint32_t SM_EYE = SM_FULL + 256;
constexpr uint32_t SM_ONE = SM_FULL + 640;
constexpr uint32_t SM_CS = SM_FULL + 768;
constexpr uint32_t SM_TOTAL = SM_FULL + 3072;
constexpr int CS_FF2 = 0, CS_PW1 = 4, CS_QKV = 6;
constexpr uint32_t SPIN_LIMIT = 1u << 16;
constexpr float LN_EPS = 1e-5f;
constexpr float SM_SCALE_LOG2 = 0.125f * 1.4426950408889634f;
constexpr uint32_t G_PITCH = 144;

constexpr int F_QKV = 16, F_SPARE = 22, F_KV = 24, F_WO = 40, F_PW1 = 42, F_PW2 = 46, F_TOTAL = 64;
enum { M_FF1A, M_FF1B, M_QKV, M_KV, M_WO, M_PW1, M_PW2, M_FF2A, M_FF2B, M_X, M_COUNT };
enum { BAR_K = 1, BAR_V, BAR_Q, BAR_MERGE, BAR_G, BAR_C, BAR_WG1, BAR_RDY, BAR_ST, BAR_ATT, BAR_INIT, BAR_RDY1, BAR_X, BAR_RES };

struct Params {
  CUtensorMap map[M_COUNT];
  const __nv_bfloat16 *w_ff1b, *w_qkv, *w_o, *w_pw1, *w_pw2, *w_ff2a, *w_ff2b;
};

constexpr int X_RS = 0, X_AG1 = X_RS, X_HALO = X_RS + 512, X_CLEAR = 1024, X_AG0 = 1536, X_ST = 2048, X_SIZE = 4096;
constexpr uint32_t HALO_TAG = 0xFFFF0001u;
struct Scratch {
  uint4 x[NCTA][X_SIZE];
  uint4 kv[8][2][16][512];
  uint4 cs[576];
  uint32_t flag[8][32];
  uint32_t ready[NCTA];
  uint32_t epoch[NCTA];
};
constexpr size_t X_ALIGN = 4 * X_SIZE * sizeof(uint4);
__device__ uint8_t g_scratch[sizeof(Scratch) + X_ALIGN];
#define PROF_TIME(i)
#define PROF_MARK(i)

__device__ __forceinline__ void mbar_init(uint32_t bar, uint32_t cnt) {
  asm volatile("mbarrier.init.shared::cta.b64 [%0], %1;" :: "r"(bar), "r"(cnt) : "memory");
}
__device__ __forceinline__ void mbar_wait(uint32_t bar, uint32_t parity) {
  asm volatile("{\n.reg .pred p;\n.reg .u32 c;\nmov.u32 c, 0;\n"
               "WAIT_LOOP:\nmbarrier.try_wait.parity.shared::cta.b64 p, [%0], %1;\n@p bra WAIT_DONE;\n"
               "add.u32 c, c, 1;\nsetp.lt.u32 p, c, %2;\n@p bra WAIT_LOOP;\nWAIT_DONE:\n}"
               :: "r"(bar), "r"(parity), "n"(SPIN_LIMIT) : "memory");
}
__device__ __forceinline__ void mbar_arrive(uint32_t bar) {
  asm volatile("mbarrier.arrive.shared::cta.b64 _, [%0];" :: "r"(bar) : "memory");
}
#define bar_sync(id, n) asm volatile("bar.sync %0, %1;" :: "n"((int)(id)), "n"(n) : "memory")
#define bar_arrive(id, n) asm volatile("bar.arrive %0, %1;" :: "n"((int)(id)), "n"(n) : "memory")
__device__ __forceinline__ void fence_async_smem() { asm volatile("fence.proxy.async.shared::cta;" ::: "memory"); }

__device__ __forceinline__ void st_vec(uint4* p, uint32_t a, uint32_t b, uint32_t c, uint32_t d) {
  asm volatile("{\n.reg .b128 v;\n.reg .b64 lo, hi;\nmov.b64 lo, {%1, %2};\nmov.b64 hi, {%3, %4};\nmov.b128 v, {lo, hi};\n"
               "st.relaxed.gpu.global.b128 [%0], v;\n}" :: "l"(p), "r"(a), "r"(b), "r"(c), "r"(d) : "memory");
}
__device__ __forceinline__ void ld_vec(const uint4* p, uint32_t& a, uint32_t& b, uint32_t& c, uint32_t& d) {
  asm volatile("{\n.reg .b128 v;\n.reg .b64 lo, hi;\nld.relaxed.gpu.global.b128 v, [%4];\nmov.b128 {lo, hi}, v;\n"
               "mov.b64 {%0, %1}, lo;\nmov.b64 {%2, %3}, hi;\n}" : "=r"(a), "=r"(b), "=r"(c), "=r"(d) : "l"(p) : "memory");
}
__device__ __forceinline__ void sts128(uint32_t a, uint32_t x, uint32_t y, uint32_t z, uint32_t w) {
  asm volatile("st.shared.v4.u32 [%0], {%1, %2, %3, %4};" :: "r"(a), "r"(x), "r"(y), "r"(z), "r"(w) : "memory");
}
__device__ __forceinline__ void lds128(uint32_t a, uint32_t& x, uint32_t& y, uint32_t& z, uint32_t& w) {
  asm volatile("ld.shared.v4.u32 {%0, %1, %2, %3}, [%4];" : "=r"(x), "=r"(y), "=r"(z), "=r"(w) : "r"(a) : "memory");
}
__device__ __forceinline__ uint32_t lds32(uint32_t a) {
  uint32_t x; asm volatile("ld.shared.u32 %0, [%1];" : "=r"(x) : "r"(a) : "memory"); return x;
}
__device__ __forceinline__ void sts32(uint32_t a, uint32_t x) { asm volatile("st.shared.u32 [%0], %1;" :: "r"(a), "r"(x) : "memory"); }
__device__ __forceinline__ void sts64(uint32_t a, uint32_t x, uint32_t y) {
  asm volatile("st.shared.v2.u32 [%0], {%1, %2};" :: "r"(a), "r"(x), "r"(y) : "memory");
}
__device__ __forceinline__ void stsm4(uint32_t a, const uint32_t* r) {
  asm volatile("stmatrix.sync.aligned.m8n8.x4.shared.b16 [%0], {%1, %2, %3, %4};" :: "r"(a), "r"(r[0]), "r"(r[1]), "r"(r[2]), "r"(r[3]) : "memory");
}
__device__ __forceinline__ void ldsm4(uint32_t a, uint32_t* r) {
  asm volatile("ldmatrix.sync.aligned.m8n8.x4.shared.b16 {%0, %1, %2, %3}, [%4];" : "=r"(r[0]), "=r"(r[1]), "=r"(r[2]), "=r"(r[3]) : "r"(a) : "memory");
}
__device__ __forceinline__ uint32_t pack2(float lo, float hi) {
  uint32_t r; asm("cvt.rn.bf16x2.f32 %0, %1, %2;" : "=r"(r) : "f"(hi), "f"(lo)); return r;
}
__device__ __forceinline__ float bf_lo(uint32_t w) { return __uint_as_float(w << 16); }
__device__ __forceinline__ float bf_hi(uint32_t w) { return __uint_as_float(w & 0xffff0000u); }
__device__ __forceinline__ float tanh_hw(float x) { float y; asm volatile("tanh.approx.f32 %0, %1;" : "=f"(y) : "f"(x)); return y; }
__device__ __forceinline__ float rcp_hw(float x) { float y; asm("rcp.approx.ftz.f32 %0, %1;" : "=f"(y) : "f"(x)); return y; }
__device__ __forceinline__ float ex2_hw(float x) { float y; asm("ex2.approx.ftz.f32 %0, %1;" : "=f"(y) : "f"(x)); return y; }

__device__ __forceinline__ uint32_t here(uint32_t v) { asm volatile("" : "+r"(v)); return v; }

#define SCHED() asm volatile("pmevent 1;" ::: "memory")
#define WG_FENCE() asm volatile("wgmma.fence.sync.aligned;" ::: "memory")
#define WG_COMMIT() asm volatile("wgmma.commit_group.sync.aligned;" ::: "memory")
#define WG_WAIT(n) asm volatile("wgmma.wait_group.sync.aligned %0;" :: "n"(n) : "memory")

template <int N> __device__ __forceinline__ void pin(float (&d)[N]) {
#pragma unroll
  for (int i = 0; i < N; i++) asm volatile("" : "+f"(d[i]) :: "memory");
}
template <int N> __device__ __forceinline__ void pin(uint32_t (&d)[N]) {
#pragma unroll
  for (int i = 0; i < N; i++) asm volatile("" : "+r"(d[i]) :: "memory");
}

#define WG_D32 "{%0, %1, %2, %3, %4, %5, %6, %7, %8, %9, %10, %11, %12, %13, %14, %15, %16, %17, %18, %19, %20, %21, %22, %23, %24, %25, %26, %27, %28, %29, %30, %31}"
template <int TB> __device__ __forceinline__ void wgmma64_acc(float (&d)[32], const uint32_t* a, uint64_t db) {
  asm volatile("wgmma.mma_async.sync.aligned.m64n64k16.f32.bf16.bf16 " WG_D32 ", {%32, %33, %34, %35}, %36, 1, 1, 1, %37;"
    : "+f"(d[0]), "+f"(d[1]), "+f"(d[2]), "+f"(d[3]), "+f"(d[4]), "+f"(d[5]), "+f"(d[6]), "+f"(d[7]),
      "+f"(d[8]), "+f"(d[9]), "+f"(d[10]), "+f"(d[11]), "+f"(d[12]), "+f"(d[13]), "+f"(d[14]), "+f"(d[15]),
      "+f"(d[16]), "+f"(d[17]), "+f"(d[18]), "+f"(d[19]), "+f"(d[20]), "+f"(d[21]), "+f"(d[22]), "+f"(d[23]),
      "+f"(d[24]), "+f"(d[25]), "+f"(d[26]), "+f"(d[27]), "+f"(d[28]), "+f"(d[29]), "+f"(d[30]), "+f"(d[31])
    : "r"(a[0]), "r"(a[1]), "r"(a[2]), "r"(a[3]), "l"(db), "n"(TB));
}
__device__ __forceinline__ void wgmma64_reuse(float (&d)[32], const uint32_t* a, uint64_t db, uint32_t zero) {
  asm volatile("{\n.reg .pred p;\nsetp.ne.u32 p, %37, 0;\nwgmma.mma_async.sync.aligned.m64n64k16.f32.bf16.bf16 " WG_D32 ", {%32, %33, %34, %35}, %36, p, 1, 1, 1;\n}"
    : "+f"(d[0]), "+f"(d[1]), "+f"(d[2]), "+f"(d[3]), "+f"(d[4]), "+f"(d[5]), "+f"(d[6]), "+f"(d[7]),
      "+f"(d[8]), "+f"(d[9]), "+f"(d[10]), "+f"(d[11]), "+f"(d[12]), "+f"(d[13]), "+f"(d[14]), "+f"(d[15]),
      "+f"(d[16]), "+f"(d[17]), "+f"(d[18]), "+f"(d[19]), "+f"(d[20]), "+f"(d[21]), "+f"(d[22]), "+f"(d[23]),
      "+f"(d[24]), "+f"(d[25]), "+f"(d[26]), "+f"(d[27]), "+f"(d[28]), "+f"(d[29]), "+f"(d[30]), "+f"(d[31])
    : "r"(a[0]), "r"(a[1]), "r"(a[2]), "r"(a[3]), "l"(db), "r"(zero));
}
template <int TB> __device__ __forceinline__ void wgmma64_set(float (&d)[32], const uint32_t* a, uint64_t db) {
  asm volatile("wgmma.mma_async.sync.aligned.m64n64k16.f32.bf16.bf16 " WG_D32 ", {%32, %33, %34, %35}, %36, 0, 1, 1, %37;"
    : "=f"(d[0]), "=f"(d[1]), "=f"(d[2]), "=f"(d[3]), "=f"(d[4]), "=f"(d[5]), "=f"(d[6]), "=f"(d[7]),
      "=f"(d[8]), "=f"(d[9]), "=f"(d[10]), "=f"(d[11]), "=f"(d[12]), "=f"(d[13]), "=f"(d[14]), "=f"(d[15]),
      "=f"(d[16]), "=f"(d[17]), "=f"(d[18]), "=f"(d[19]), "=f"(d[20]), "=f"(d[21]), "=f"(d[22]), "=f"(d[23]),
      "=f"(d[24]), "=f"(d[25]), "=f"(d[26]), "=f"(d[27]), "=f"(d[28]), "=f"(d[29]), "=f"(d[30]), "=f"(d[31])
    : "r"(a[0]), "r"(a[1]), "r"(a[2]), "r"(a[3]), "l"(db), "n"(TB));
}

__device__ __forceinline__ void wgmma72_acc(float (&d)[36], const uint32_t* a, uint64_t db) {
  asm volatile("wgmma.mma_async.sync.aligned.m64n72k16.f32.bf16.bf16 {%0, %1, %2, %3, %4, %5, %6, %7, %8, %9, %10, %11, %12, %13, %14, %15, %16, %17, %18, %19, %20, %21, %22, %23, %24, %25, %26, %27, %28, %29, %30, %31, %32, %33, %34, %35}, {%36, %37, %38, %39}, %40, 1, 1, 1, 1;"
    : "+f"(d[0]), "+f"(d[1]), "+f"(d[2]), "+f"(d[3]), "+f"(d[4]), "+f"(d[5]), "+f"(d[6]), "+f"(d[7]), "+f"(d[8]),
      "+f"(d[9]), "+f"(d[10]), "+f"(d[11]), "+f"(d[12]), "+f"(d[13]), "+f"(d[14]), "+f"(d[15]), "+f"(d[16]), "+f"(d[17]),
      "+f"(d[18]), "+f"(d[19]), "+f"(d[20]), "+f"(d[21]), "+f"(d[22]), "+f"(d[23]), "+f"(d[24]), "+f"(d[25]), "+f"(d[26]),
      "+f"(d[27]), "+f"(d[28]), "+f"(d[29]), "+f"(d[30]), "+f"(d[31]), "+f"(d[32]), "+f"(d[33]), "+f"(d[34]), "+f"(d[35])
    : "r"(a[0]), "r"(a[1]), "r"(a[2]), "r"(a[3]), "l"(db));
}
__device__ __forceinline__ void wgmma16_acc(float* d, const uint32_t* a, uint64_t db) {
  asm volatile("wgmma.mma_async.sync.aligned.m64n16k16.f32.bf16.bf16 {%0, %1, %2, %3, %4, %5, %6, %7}, {%8, %9, %10, %11}, %12, 1, 1, 1, 0;"
    : "+f"(d[0]), "+f"(d[1]), "+f"(d[2]), "+f"(d[3]), "+f"(d[4]), "+f"(d[5]), "+f"(d[6]), "+f"(d[7])
    : "r"(a[0]), "r"(a[1]), "r"(a[2]), "r"(a[3]), "l"(db));
}
__device__ __forceinline__ void hmma(float (&d)[4], const uint32_t* a, uint32_t b0, uint32_t b1) {
  asm("mma.sync.aligned.m16n8k16.row.col.f32.bf16.bf16.f32 {%0, %1, %2, %3}, {%4, %5, %6, %7}, {%8, %9}, {%0, %1, %2, %3};"
    : "+f"(d[0]), "+f"(d[1]), "+f"(d[2]), "+f"(d[3]) : "r"(a[0]), "r"(a[1]), "r"(a[2]), "r"(a[3]), "r"(b0), "r"(b1));
}

__device__ __forceinline__ void hmma8(float (&d)[4], const uint32_t* a, uint32_t b0) {
  asm("mma.sync.aligned.m16n8k8.row.col.f32.bf16.bf16.f32 {%0, %1, %2, %3}, {%4, %5}, {%6}, {%0, %1, %2, %3};"
    : "+f"(d[0]), "+f"(d[1]), "+f"(d[2]), "+f"(d[3]) : "r"(a[0]), "r"(a[1]), "r"(b0));
}

template <bool FIRST> __device__ __forceinline__ void mma_tile(float (&d)[32], const uint32_t (&a)[16], uint64_t db) {
  WG_FENCE();
#pragma unroll
  for (int s = 0; s < 4; s++) {
    if (FIRST && s == 0) wgmma64_set<1>(d, &a[0], db); else wgmma64_acc<1>(d, &a[4 * s], db + s * 128);
  }
  WG_COMMIT();
}
__device__ __forceinline__ void mma_tile_reuse(float (&d)[32], const uint32_t (&a)[16], uint64_t db) {
  WG_FENCE();
  wgmma64_reuse(d, &a[0], db, blockIdx.y);
#pragma unroll
  for (int s = 1; s < 4; s++) wgmma64_acc<1>(d, &a[4 * s], db + s * 128);
  WG_COMMIT();
}
template <int ROW> __device__ __forceinline__ void mma_tile_fold(float (&d)[32], const uint32_t (&a)[16], uint64_t db, const uint32_t (&mu)[4]) {
  WG_FENCE();
#pragma unroll
  for (int s = 0; s < 4; s++) wgmma64_acc<1>(d, &a[4 * s], db + s * 128);
  wgmma64_acc<1>(d, mu, (uint64_t)((SM_BASE + SM_CS + ROW * 128) >> 4) | (uint64_t(1) << 16) | (uint64_t(1) << 62));
  WG_COMMIT();
}
__device__ __forceinline__ void mma_add_half(float (&d)[32], const uint32_t (&a)[16]) {
  const uint64_t db = (uint64_t)((SM_BASE + SM_EYE) >> 4) | (uint64_t(8) << 16) | (uint64_t(8) << 32);
  WG_FENCE();
#pragma unroll
  for (int s = 0; s < 4; s++) wgmma16_acc(&d[8 * s], &a[4 * s], db);
  WG_COMMIT();
}
#define ACQUIRE(f) mbar_wait(SM_BASE + SM_FULL + ((f) % NSTAGE) * 8, ((f) / NSTAGE) & 1)
template <int F, int N> __device__ __forceinline__ void acquire_n() {
  static_assert(F % NSTAGE + N <= NSTAGE, "stages must not wrap");
  uint32_t spin = 0, ok;
  do {
    ok = 1;
#pragma unroll
    for (int i = 0; i < N; i++)
      asm volatile("{\n.reg .pred p;\nmbarrier.try_wait.parity.shared::cta.b64 p, [%1], %2;\nselp.u32 %0, %0, 0, p;\n}"
                   : "+r"(ok) : "r"(SM_BASE + SM_FULL + (F % NSTAGE + i) * 8), "r"((F / NSTAGE) & 1) : "memory");
  } while (!ok && ++spin < SPIN_LIMIT);
}
#define RELEASE(f0, f1) do { if (lane == 0) { _Pragma("unroll") for (int f_ = (f0); f_ <= (f1); f_++) mbar_arrive(SM_BASE + SM_EMPTY + (f_ % NSTAGE) * 8); } } while (0)
constexpr uint64_t RING = (uint64_t)(SM_BASE >> 4) | (uint64_t(1) << 16) | (uint64_t(64) << 32) | (uint64_t(1) << 62);
#define LO(f) (RING + ((f) % NSTAGE) * 1024)
#define HI(f) (RING + ((f) % NSTAGE) * 1024 + 512)

template <int C> __device__ __forceinline__ uint4* peer(uint4* p) {
  asm volatile("" : "+l"(p));
  return (uint4*)((uintptr_t)p ^ (C * X_SIZE * sizeof(uint4)));
}
__device__ __forceinline__ uint32_t clock_now() { uint32_t c; asm volatile("mov.u32 %0, %%clock;" : "=r"(c) :: "memory"); return c; }
__device__ __forceinline__ void publish(uint4* dst, uint32_t (&a)[16], uint32_t tag) {
#pragma unroll
  for (int s = 0; s < 4; s++) a[4 * s] = (a[4 * s] & ~1u) | tag;
  pin(a);
  SCHED();
#pragma unroll
  for (int s = 0; s < 4; s++) st_vec(dst + s * 128, a[4 * s], a[4 * s + 1], a[4 * s + 2], a[4 * s + 3]);
  SCHED();
}
__device__ __forceinline__ void fetch(const uint4* src, uint32_t (&a)[16]) {
#pragma unroll
  for (int s = 0; s < 4; s++) ld_vec(src + s * 128, a[4 * s], a[4 * s + 1], a[4 * s + 2], a[4 * s + 3]);
}
__device__ __forceinline__ uint32_t miss(const uint32_t (&a)[16], uint32_t tag) {
  return (a[0] ^ tag) | (a[4] ^ tag) | (a[8] ^ tag) | (a[12] ^ tag);
}
__device__ __forceinline__ bool stale(uint32_t v) { return __any_sync(0xffffffffu, here(v) & 1u); }
__device__ __forceinline__ void confirm(const uint4* src, uint32_t (&a)[16], uint32_t tag) {
  uint32_t spin = 0;
  while (__builtin_expect(stale(miss(a, tag)), 0) && ++spin < SPIN_LIMIT) fetch(src, a);
}
constexpr uint32_t GATHER_DELAY = 400;
template <int C0, int C1, int SLOT> __device__ __forceinline__ void gather_wait(uint32_t (&A)[4][16], uint4* xp, uint32_t tag) {
  uint32_t spin = 0;
  while (__builtin_expect(stale(miss(A[C0], tag) | miss(A[C1], tag)), 0) && ++spin < SPIN_LIMIT) {
    fetch(peer<C0>(xp) + SLOT, A[C0]);
    if (C1 != C0) fetch(peer<C1>(xp) + SLOT, A[C1]);
  }
}
template <int C, int SLOT> __device__ __forceinline__ void gather_first(uint32_t (&A)[4][16], uint4* xp, uint32_t tag, uint32_t sent) {
  while (clock_now() - sent < GATHER_DELAY) {}
  fetch(peer<1>(xp) + SLOT, A[1]); fetch(peer<2>(xp) + SLOT, A[2]); fetch(peer<3>(xp) + SLOT, A[3]);
  gather_wait<1, C, SLOT>(A, xp, tag);
}
template <int C, int SLOT> __device__ __forceinline__ void gather_rest(uint32_t (&A)[4][16], uint4* xp, uint32_t tag) {
  SCHED();
  gather_wait<C + 1, 3, SLOT>(A, xp, tag);
}
__device__ __forceinline__ void pack_acc(const float (&d)[32], uint32_t (&a)[16]) {
#pragma unroll
  for (int i = 0; i < 16; i++) a[i] = pack2(d[2 * i], d[2 * i + 1]);
}
__device__ __forceinline__ void res_store(uint32_t slot, const uint32_t (&a)[16]) {
#pragma unroll
  for (int s = 0; s < 4; s++) sts128(slot + s * 512, a[4 * s], a[4 * s + 1], a[4 * s + 2], a[4 * s + 3]);
}
__device__ __forceinline__ void res_load(uint32_t slot, float (&d)[32]) {
  uint32_t a[16];
#pragma unroll
  for (int s = 0; s < 4; s++) lds128(slot + s * 512, a[4 * s], a[4 * s + 1], a[4 * s + 2], a[4 * s + 3]);
#pragma unroll
  for (int i = 0; i < 16; i++) { d[2 * i] = bf_lo(a[i]); d[2 * i + 1] = bf_hi(a[i]); }
  pin(d);
}
__device__ __forceinline__ void tile_store(uint32_t maddr, const uint32_t (&a)[16]) {
#pragma unroll
  for (int s = 0; s < 4; s++) stsm4(maddr ^ (s << 5), &a[4 * s]);
}
__device__ __forceinline__ void tile_load(uint32_t maddr, uint32_t (&a)[16]) {
#pragma unroll
  for (int s = 0; s < 4; s++) ldsm4(maddr ^ (s << 5), &a[4 * s]);
}

struct RowAcc { float s[4], u[2][4], v[2][4]; };
__device__ __forceinline__ void row_acc(RowAcc& t, const uint32_t (&a)[16]) {
#pragma unroll
  for (int s = 0; s < 8; s++) {
    if ((s & 1) == 0) hmma(t.s, &a[2 * s], 0x3F803F80u, 0x3F803F80u);
    hmma8(t.u[s & 1], &a[2 * s], a[2 * s]);
    hmma8(t.v[s & 1], &a[2 * s], a[2 * s + 1]);
  }
}
__device__ __forceinline__ float2 row_squares(const RowAcc& t, bool odd) {
  return make_float2(odd ? t.u[0][1] + t.u[1][1] : t.u[0][0] + t.u[1][0], odd ? t.v[0][3] + t.v[1][3] : t.v[0][2] + t.v[1][2]);
}
__device__ __forceinline__ void stat_publish(const uint32_t (&a)[16], Scratch* sc, uint32_t th, uint32_t tag) {
  RowAcc t = {};
  row_acc(t, a);
  const float2 q = row_squares(t, th & 4);
  if ((th & 3) == ((th >> 3) & 3))
    st_vec(&sc->x[blockIdx.x][X_ST + (th >> 2)], (__float_as_uint(t.s[0]) & ~1u) | tag, __float_as_uint(q.x), __float_as_uint(t.s[2]), __float_as_uint(q.y));
}
struct RowNorm { float m0, rs0, m1, rs1; };
__device__ __forceinline__ RowNorm row_norm(float s0, float q0, float s1, float q1, float scale) {
  RowNorm n;
  n.m0 = s0 * (1.f / DM); n.m1 = s1 * (1.f / DM);
  n.rs0 = scale * rsqrtf(fmaxf(fmaf(-n.m0, n.m0, q0 * (1.f / DM)), 0.f) + LN_EPS);
  n.rs1 = scale * rsqrtf(fmaxf(fmaf(-n.m1, n.m1, q1 * (1.f / DM)), 0.f) + LN_EPS);
  return n;
}
__device__ __forceinline__ RowNorm stat_gather(Scratch* sc, uint32_t th, uint32_t tag, float scale) {
  const uint4* src = &sc->x[blockIdx.x & ~3u][X_ST + (th >> 2)];
  uint32_t v[16], spin = 0;
  do {
#pragma unroll
    for (int j = 0; j < 4; j++) ld_vec(src + j * X_SIZE, v[4 * j], v[4 * j + 1], v[4 * j + 2], v[4 * j + 3]);
  } while (stale(miss(v, tag)) && ++spin < SPIN_LIMIT);
  float f[4];
#pragma unroll
  for (int i = 0; i < 4; i++)
    f[i] = (__uint_as_float(v[i]) + __uint_as_float(v[4 + i])) + (__uint_as_float(v[8 + i]) + __uint_as_float(v[12 + i]));
  return row_norm(f[0], f[1], f[2], f[3], scale);
}
constexpr uint32_t SM_NORM = SM_BASE + SM_STG + 2 * TILE_BYTES + 4096;
__device__ __forceinline__ void norm_produce(const RowNorm& n, uint32_t th, uint32_t qsel) {
  const bool sel = (th & 3) == qsel;
  const float a = sel ? -n.m0 : 0.f, c = sel ? -n.m1 : 0.f;
  const uint32_t ah = pack2(a, a), ch = pack2(c, c);
  const float al = a - bf_lo(ah), cl = c - bf_lo(ch);
  sts128(SM_NORM + th * 16, ah, ch, pack2(al, al), pack2(cl, cl));
  sts64(SM_NORM + 2048 + th * 8, __float_as_uint(n.rs0), __float_as_uint(n.rs1));
  bar_arrive(BAR_ST, 256);
}
__device__ __forceinline__ void norm_duty(Scratch* sc, uint32_t th, uint32_t res, uint32_t tag, float scale, uint32_t qsel) {
  uint32_t a[16];
  bar_sync(BAR_RES, 256);
#pragma unroll
  for (int s = 0; s < 4; s++) lds128(res + s * 512, a[4 * s], a[4 * s + 1], a[4 * s + 2], a[4 * s + 3]);
  stat_publish(a, sc, th, tag);
  norm_produce(stat_gather(sc, th, tag, scale), th, qsel);
}
__device__ __forceinline__ void norm_consume(uint32_t th, uint32_t (&mu)[4], float& rs0, float& rs1) {
  bar_sync(BAR_ST, 256);
  lds128(SM_NORM + th * 16, mu[0], mu[1], mu[2], mu[3]);
  asm volatile("ld.shared.v2.f32 {%0, %1}, [%2];" : "=f"(rs0), "=f"(rs1) : "r"(SM_NORM + 2048 + th * 8) : "memory");
}
__device__ __forceinline__ void scale_pack(const float (&d)[32], uint32_t (&a)[16], float rs0, float rs1) {
#pragma unroll
  for (int i = 0; i < 16; i++) { const float rs = (i & 1) ? rs1 : rs0; a[i] = pack2(d[2 * i] * rs, d[2 * i + 1] * rs); }
}
template <int S> __device__ __forceinline__ void silu_seg(float (&acc)[4][32], float (&tn)[2][4], uint32_t (&H)[4][16], float rs0, float rs1) {
  if (S >= 2) {
    const float* h = &acc[(S - 2) >> 3][4 * ((S - 2) & 7)];
    const float* v = tn[S & 1];
    uint32_t* o = &H[(S - 2) >> 3][2 * ((S - 2) & 7)];
    o[0] = pack2(fmaf(h[0], v[0], h[0]), fmaf(h[1], v[1], h[1]));
    o[1] = pack2(fmaf(h[2], v[2], h[2]), fmaf(h[3], v[3], h[3]));
    asm volatile("" : "+r"(o[0]), "+r"(o[1]));
  }
  if (S >= 1 && S <= 32) {
#pragma unroll
    for (int k = 0; k < 4; k++) tn[(S - 1) & 1][k] = tanh_hw(acc[((S - 1) >> 3) & 3][4 * ((S - 1) & 7) + k]);
  }
  if (S < 32) {
    float* h = &acc[(S >> 3) & 3][4 * (S & 7)];
    h[0] *= rs0; h[1] *= rs0; h[2] *= rs1; h[3] *= rs1;
    asm volatile("" : "+f"(h[0]), "+f"(h[1]), "+f"(h[2]), "+f"(h[3]));
  }
  SCHED();
}
template <int S0, int S1> __device__ __forceinline__ void silu_segs(float (&acc)[4][32], float (&tn)[2][4], uint32_t (&H)[4][16], float rs0, float rs1) {
  silu_seg<S0>(acc, tn, H, rs0, rs1);
  if constexpr (S0 + 1 < S1) silu_segs<S0 + 1, S1>(acc, tn, H, rs0, rs1);
}
template <int HALF> __device__ __forceinline__ void send_half(uint4* dst, const float (&d)[32], uint32_t tag) {
  uint32_t o[8];
#pragma unroll
  for (int i = 0; i < 8; i++) o[i] = pack2(d[16 * HALF + 2 * i], d[16 * HALF + 2 * i + 1]);
  o[0] = (o[0] & ~1u) | tag; o[4] = (o[4] & ~1u) | tag;
  pin(o);
  SCHED();
  st_vec(dst + HALF * 256, o[0], o[1], o[2], o[3]);
  st_vec(dst + HALF * 256 + 128, o[4], o[5], o[6], o[7]);
  SCHED();
}
__device__ __forceinline__ uint32_t send_residual(uint32_t (&a)[16], uint4* xp, uint32_t res, uint32_t tag) {
  const uint32_t exact[4] = {a[0], a[4], a[8], a[12]};
  publish(xp + X_AG0, a, tag);
  const uint32_t sent = clock_now();
  res_store(res, a);
#pragma unroll
  for (int s = 0; s < 4; s++) sts32(res + s * 512, exact[s]);
  bar_arrive(BAR_RES, 256);
  return sent;
}
template <int F, int N> __device__ __forceinline__ uint32_t proj_residual(uint32_t (&A)[4][16], uint4* xp, uint32_t res, uint32_t tag) {
  float acc[32];
  publish(xp + X_AG1, A[0], tag);
  const uint32_t sent = clock_now();
  acquire_n<F, N>();
  res_load(res, acc);
  mma_tile<false>(acc, A[0], LO(F));
  gather_first<2, X_AG1>(A, xp, tag, sent);
  mma_tile<false>(acc, A[1], HI(F));
  mma_tile<false>(acc, A[2], LO(F + 1));
  gather_rest<2, X_AG1>(A, xp, tag);
  PROF_MARK(F == F_WO ? 11 : 16);
  mma_tile<false>(acc, A[3], HI(F + 1));
  WG_WAIT(0); pin(acc);
  pack_acc(acc, A[0]);
  return send_residual(A[0], xp, res, tag);
}

__device__ __forceinline__ void qk_tile(float (&S)[32], const uint32_t (&Q)[16], uint64_t dk) {
#pragma unroll
  for (int s = 0; s < 4; s++) {
    if (s == 0) wgmma64_set<0>(S, &Q[0], dk); else wgmma64_acc<0>(S, &Q[4 * s], dk + s * 2);
  }
}
__device__ __forceinline__ void qk_shift(float (&S)[32], const uint32_t (&nm)[4]) { wgmma64_acc<0>(S, nm, (uint64_t)((SM_BASE + SM_ONE) >> 4)); }
constexpr uint64_t V_STEP = uint64_t(1) - (uint64_t(1) << 16);
constexpr uint64_t RING_V = RING - (uint64_t(1) << 16) + ((uint64_t)((SM_STG + 2 * TILE_BYTES) >> 4) << 16);
__device__ __forceinline__ void pv_tile(float (&O)[36], const uint32_t (&P)[16], uint64_t dv, uint64_t pad) {
#pragma unroll
  for (int s = 0; s < 4; s++) wgmma72_acc(O, &P[4 * s], dv + s * 128 * V_STEP + (s < 2 ? 0 : (s - 1) * pad));
}
__device__ __forceinline__ void attn_step(const float (&Sc)[32], float (&Sn)[32], uint32_t (&Pc)[16], uint32_t (&Pp)[16], float (&O)[36],
                                          const uint32_t (&Q)[16], const uint32_t (&nm)[4], uint64_t dk, uint64_t dv) {
  WG_FENCE();
  qk_tile(Sn, Q, dk);
  qk_shift(Sn, nm);
  pv_tile(O, Pp, dv, 0);
  WG_COMMIT();
  SCHED();
#pragma unroll
  for (int i = 0; i < 16; i++) Pc[i] = pack2(ex2_hw(Sc[2 * i]), ex2_hw(Sc[2 * i + 1]));
  pin(Pc);
  SCHED();
}
template <int R> __device__ __forceinline__ float tile_max(const float (&S)[32]) {
  float t[4];
#pragma unroll
  for (int j = 0; j < 4; j++) t[j] = fmaxf(fmaxf(S[8 * j + R], S[8 * j + R + 1]), fmaxf(S[8 * j + R + 4], S[8 * j + R + 5]));
  float n = fmaxf(fmaxf(t[0], t[1]), fmaxf(t[2], t[3]));
  n = fmaxf(n, __shfl_xor_sync(0xffffffffu, n, 1));
  return fmaxf(n, __shfl_xor_sync(0xffffffffu, n, 2));
}
__device__ __forceinline__ void attention_exact(float (&O)[36], const uint32_t (&Q)[16], const Scratch* sc, int bh, int lane) {
  const char* kb = (const char*)&sc->kv[bh][0][0][0];
  const char* vb = (const char*)&sc->kv[bh][1][0][0];
  const int g = lane >> 2, q = lane & 3;
  float m0 = -INFINITY, m1 = -INFINITY, l0 = 0.f, l1 = 0.f;
  float o[8][4] = {};
#pragma unroll 1
  for (int k0 = 0; k0 < T_SEQ; k0 += 8) {
    float s[4] = {0.f, 0.f, 0.f, 0.f};
#pragma unroll
    for (int c = 0; c < 8; c++) hmma8(s, &Q[2 * c], __ldcg((const uint32_t*)(kb + (k0 + g) * 128 + ((c ^ g) << 4) + q * 4)));
    float n0 = fmaxf(s[0], s[1]), n1 = fmaxf(s[2], s[3]);
    n0 = fmaxf(n0, __shfl_xor_sync(0xffffffffu, n0, 1)); n1 = fmaxf(n1, __shfl_xor_sync(0xffffffffu, n1, 1));
    n0 = fmaxf(m0, fmaxf(n0, __shfl_xor_sync(0xffffffffu, n0, 2))); n1 = fmaxf(m1, fmaxf(n1, __shfl_xor_sync(0xffffffffu, n1, 2)));
    const float a0 = ex2_hw(m0 - n0), a1 = ex2_hw(m1 - n1);
    m0 = n0; m1 = n1;
    const uint32_t pp[2] = {pack2(ex2_hw(s[0] - n0), ex2_hw(s[1] - n0)), pack2(ex2_hw(s[2] - n1), ex2_hw(s[3] - n1))};
    l0 = fmaf(l0, a0, bf_lo(pp[0]) + bf_hi(pp[0])); l1 = fmaf(l1, a1, bf_lo(pp[1]) + bf_hi(pp[1]));
#pragma unroll
    for (int j = 0; j < 8; j++) {
      const uint32_t v0 = __ldcg((const uint16_t*)(vb + (k0 + 2 * q) * 128 + ((j ^ (2 * q)) << 4) + g * 2));
      const uint32_t v1 = __ldcg((const uint16_t*)(vb + (k0 + 2 * q + 1) * 128 + ((j ^ (2 * q + 1)) << 4) + g * 2));
      o[j][0] *= a0; o[j][1] *= a0; o[j][2] *= a1; o[j][3] *= a1;
      hmma8(o[j], pp, v0 | (v1 << 16));
    }
  }
  l0 += __shfl_xor_sync(0xffffffffu, l0, 1); l1 += __shfl_xor_sync(0xffffffffu, l1, 1);
  O[32] = l0 + __shfl_xor_sync(0xffffffffu, l0, 2); O[34] = l1 + __shfl_xor_sync(0xffffffffu, l1, 2);
#pragma unroll
  for (int i = 0; i < 32; i++) O[i] = o[i >> 2][i & 3];
}

__device__ __forceinline__ uint32_t fill_entry(int f, int r, int bh) {
  int m, x = r, y, dx = 0;
  if (f < F_QKV || f >= 48) {
    const int i = f & 15;
    m = f < F_QKV ? M_FF1A : M_FF2A;
    if (i < 8) { x = 4 * r + ((0xE2u >> i) & 1) * 2; y = r ^ ((0xE790u >> (2 * i)) & 3); dx = 1; }
    else { m++; x = r ^ (((i >> 1) - 3) & 3); y = 4 * r + 2 * (i & 1); }
  } else if (f < F_KV) {
    const int i = f - F_QKV;
    m = M_QKV;
    if (i == 1 || i >= 5) { y = r ^ (i == 1 ? 0 : 2); }
    else { x = 4 + r; y = r ^ (i ? i - 1 : 0); dx = 4; }
  } else if (f < F_WO) {
    const int i = f - F_KV;
    m = M_KV; x = 0; y = bh * 32 + (i & 2) * 8 + (i >> 2) * 4 + (i & 1) * 2;
  } else if (f >= F_PW1 && f < F_PW2) {
    m = M_PW1; y = r ^ (f - F_PW1); dx = 4;
  } else {
    m = f < F_PW1 ? M_WO : M_PW2; y = r ^ ((f & 1) * 2);
  }
  return m | (x << 4) | (y << 8) | (dx << 16);
}
__device__ __forceinline__ void tma_fill(uint32_t st, const CUtensorMap* map, uint32_t x, uint32_t y, uint32_t x2, uint32_t y2) {
  asm volatile("{\n.reg .pred p;\nelect.sync _|p, 0xffffffff;\n"
               "@p mbarrier.arrive.expect_tx.shared::cta.b64 _, [%1], 16384;\n"
               "@p cp.async.bulk.tensor.2d.shared::cluster.global.mbarrier::complete_tx::bytes [%0], [%2, {%3, %4}], [%1];\n"
               "@p cp.async.bulk.tensor.2d.shared::cluster.global.mbarrier::complete_tx::bytes [%0 + 8192], [%2, {%5, %6}], [%1];\n}"
               :: "r"(SM_BASE + st * STAGE_BYTES), "r"(SM_BASE + SM_FULL + st * 8), "l"(map), "r"(x), "r"(y), "r"(x2), "r"(y2) : "memory");
}
__device__ __forceinline__ void l2_prefetch(const void* p, uint32_t total, int b) {
  const uint32_t part = total / NCTA;
  asm volatile("cp.async.bulk.prefetch.L2.global [%0], %1;" :: "l"((const char*)p + (size_t)b * part), "r"(part) : "memory");
}

__global__ void __launch_bounds__(384, 1) conformer_kernel(Scratch* __restrict__ sc, __nv_bfloat16* __restrict__ out,
                                                           const __nv_bfloat16* __restrict__ dw, const __grid_constant__ Params p) {
  extern __shared__ __align__(1024) uint8_t smem[];
  const int tid = threadIdx.x, lane = tid & 31;
  const int cw = __shfl_sync(0xffffffffu, tid >> 5, 0), wg = cw >> 2, w = cw & 3;
  const int b = blockIdx.x, r = b & 3, batch = b >> 6, t = (b >> 2) & 15;
  if ((uint32_t)__cvta_generic_to_shared(smem) != SM_BASE) return;
  PROF_MARK(0);
  PROF_TIME(30);

  if (cw == 8) {
    if (lane == 0) {
      asm volatile("prefetch.tensormap [%0];" :: "l"(&p.map[M_X]) : "memory");
      asm volatile("prefetch.tensormap [%0];" :: "l"(&p.map[M_FF1A]) : "memory");
      mbar_init(SM_BASE + SM_XBAR, 1);
#pragma unroll
      for (int i = 0; i < NSTAGE; i++) mbar_init(SM_BASE + SM_FULL + i * 8, 1);
      fence_async_smem();
    }
    __syncwarp();
    asm volatile("{\n.reg .pred p;\nelect.sync _|p, 0xffffffff;\n"
                 "@p mbarrier.arrive.expect_tx.shared::cta.b64 _, [%1], 32768;\n"
                 "@p cp.async.bulk.tensor.4d.shared::cluster.global.mbarrier::complete_tx::bytes [%0], [%2, {0, %3, 0, %4}], [%1];\n}"
                 :: "r"(SM_BASE + SM_STG), "r"(SM_BASE + SM_XBAR), "l"(&p.map[M_X]), "r"(t * 64), "r"(batch) : "memory");
    bar_arrive(0, 320);
#pragma unroll 1
    for (int f = 0; f < 8; f++) {
      const uint32_t x = 256 * r + ((0xE2u >> f) & 1) * 128, y = (r ^ ((0xE790u >> (2 * f)) & 3)) * 64;
      tma_fill(f, &p.map[M_FF1A], x, y, x + 64, y);
    }
    PROF_MARK(1);
  } else if (cw == 9) {
    if (lane == 0) {
#pragma unroll
      for (int i = 0; i < NSTAGE; i++) mbar_init(SM_BASE + SM_EMPTY + i * 8, 4);
    }
    __syncwarp();
    bar_arrive(0, 320);
    bar_arrive(BAR_INIT, 64);
  } else if (wg < 2) {
    if (tid < 144) sts128(SM_BASE + SM_CS + tid * 16, 0, 0, 0, 0);
    if (wg == 1) {
      const int i = tid - 128;
      sts32(SM_BASE + SM_EYE + i * 4, i >= 96 ? 0x3F803F80u : ((i & 32) == 0 && (i & 3) == ((i >> 3) & 3)) ? (0x3F00u << ((i & 4) * 4)) : 0u);
    }
    fence_async_smem();
    bar_sync(0, 320);
  }

  if (wg == 2) {
    asm volatile("setmaxnreg.dec.sync.aligned.u32 40;");
    if (cw == 8) {
      const uint32_t* flag = &sc->flag[batch * 4 + r][lane];
      const uint32_t prev = ((volatile uint32_t*)sc->epoch)[b];
      uint32_t entry[2], ready = 0, st = 8, parity = 1;
#pragma unroll 1
      for (int i = 0; i < 2; i++) { entry[1] = fill_entry(i * 32 + lane, r, batch * 4 + r); if (i == 0) entry[0] = entry[1]; }
      bar_sync(BAR_INIT, 64);
#pragma unroll 1
      for (int f = 8; f < F_TOTAL; f++) {
        const uint32_t e = __shfl_sync(0xffffffffu, f < 32 ? entry[0] : entry[1], f);
        if ((e & 15) == M_KV) {
          const uint32_t need = 3u << ((e >> 8) & 31);
          uint32_t spin = 0;
#pragma unroll 1
          while ((ready & need) != need && ++spin < SPIN_LIMIT) {
            uint32_t v;
            asm volatile("ld.relaxed.gpu.global.u32 %0, [%1];" : "=r"(v) : "l"(flag) : "memory");
            ready = __ballot_sync(0xffffffffu, v - 1 == prev);
          }
        }
        mbar_wait(SM_BASE + SM_EMPTY + st * 8, parity);
        const uint32_t x = (e << 2) & 0x3C0, y = (e >> 2) & 0x3FC0, dx = (e >> 16) << 6;
        tma_fill(st, &p.map[e & 15], x, y, x + dx, dx ? y : y ^ 64);
        if (++st == NSTAGE) { st = 0; parity ^= 1; }
      }
    } else if (here(cw) != 11) {
      const int kind = w - 1;
      const uint32_t epoch = ((volatile uint32_t*)sc->epoch)[b] + 1;
      if (kind == 0) {
        bar_sync(BAR_K, 160);
      } else {
        uint32_t v, spin = 0;
#pragma unroll 1
        do {
          asm volatile("ld.relaxed.gpu.global.u32 %0, [%1];" : "=r"(v) : "l"(&sc->ready[(b & ~3) + (lane & 3)]) : "memory");
        } while (__any_sync(0xffffffffu, v != epoch) && ++spin < SPIN_LIMIT);
        bar_arrive(BAR_RDY, 160);
        bar_arrive(BAR_RDY1, 160);
        bar_sync(BAR_V, 160);
      }
      if (lane == 0) {
        asm volatile("cp.async.bulk.global.shared::cta.bulk_group [%0], [%1], %2;"
                     :: "l"(&sc->kv[batch * 4 + r][kind][t][0]), "r"(SM_BASE + SM_STG + kind * TILE_BYTES), "r"(TILE_BYTES) : "memory");
        asm volatile("cp.async.bulk.commit_group;\ncp.async.bulk.wait_group 0;" ::: "memory");
        asm volatile("st.relaxed.gpu.global.u32 [%0], %1;" :: "l"(&sc->flag[batch * 4 + r][kind * 16 + t]), "r"(epoch) : "memory");
      }
    } else {
      const uint32_t epoch = ((volatile uint32_t*)sc->epoch)[b] + 1;
      if (lane == 0) {
        asm volatile("prefetch.tensormap [%0];" :: "l"(&p.map[M_FF1B]) : "memory");
        l2_prefetch(p.w_ff1b, 1024 * 256 * 2, b);
      }
#pragma unroll 1
      for (uint4* dst = &sc->x[b][X_CLEAR + lane]; dst < &sc->x[b][X_ST + 32]; dst += 32) {
        const uint32_t t0 = clock_now();
        st_vec(dst, 0u, 0u, 0u, 0u);
        while (clock_now() - t0 < 24) {}
      }
      asm volatile("fence.acq_rel.gpu;" ::: "memory");
      __syncwarp();
      if (lane == 0) {
        asm volatile("st.relaxed.gpu.global.u32 [%0], %1;" :: "l"(&sc->ready[b]), "r"(epoch) : "memory");
        l2_prefetch(p.w_o, 256 * 256 * 2, b);
        l2_prefetch(p.w_pw2, 256 * 256 * 2, b);
        l2_prefetch(p.w_ff2b, 1024 * 256 * 2, b);
#pragma unroll
        for (int i = M_QKV; i < M_X; i++) asm volatile("prefetch.tensormap [%0];" :: "l"(&p.map[i]) : "memory");
      }
    }
  } else {
    asm volatile("setmaxnreg.inc.sync.aligned.u32 232;");
    const int q = lane & 3, th = tid & 127;
    constexpr uint32_t stg = SM_BASE + SM_STG;
    const uint32_t mrow = 16 * w + (lane & 15);
    const uint32_t maddr = stg + mrow * 128 + (((lane >> 4) ^ (lane & 7)) << 4);
    const uint32_t res = stg + 3 * TILE_BYTES + w * 2048 + lane * 16;
    uint4* const xp = &sc->x[b][th];
    const int nvalid = T_SEQ - t * 64, row0 = 16 * w + (lane >> 2);

    uint32_t A[4][16];
    uint32_t sent = 0;
    mbar_wait(SM_BASE + SM_XBAR, 0);
    PROF_MARK(1);
#pragma unroll
    for (int c = 0; c < 4; c++) tile_load(maddr + (r ^ c) * TILE_BYTES, A[c]);
    if (wg == 0) {
      float sa[4] = {0.f, 0.f, 0.f, 0.f}, sb[4] = {0.f, 0.f, 0.f, 0.f};
#pragma unroll
      for (int i = 0; i < 16; i++) hmma((i & 1) ? sb : sa, &A[i >> 2][4 * (i & 3)], 0x3F803F80u, 0x3F803F80u);
      bar_arrive(BAR_X, 256);
      const float s0 = (sa[0] + sb[0]) * (1.f / DM), s1 = (sa[2] + sb[2]) * (1.f / DM);
      const uint32_t m0 = pack2(s0, s0), m1 = pack2(s1, s1);
#pragma unroll
      for (int c = 0; c < 4; c++) {
#pragma unroll
        for (int i = 0; i < 16; i++) asm("sub.rn.bf16x2 %0, %0, %1;" : "+r"(A[c][i]) : "r"((i & 1) ? m1 : m0));
        pin(A[c]);
      }
    } else {
      const uint32_t epoch = ((volatile uint32_t*)sc->epoch)[b] + 1, tag = epoch & 1;
      uint4 cv[8];
      if (b < 72) {
        const __nv_bfloat16* wp; int ld, col;
        if (b < 24) { wp = p.w_qkv; ld = 768; col = b * 32; }
        else if (b < 40) { wp = p.w_pw1; ld = 512; col = (b - 24) * 32; }
        else { wp = p.w_ff2a; ld = 1024; col = (b - 40) * 32; }
        const uint4* src = (const uint4*)(wp + (size_t)(th >> 2) * ld + col + q * 8);
#pragma unroll
        for (int i = 0; i < 8; i++) cv[i] = __ldg(src + i * 4 * ld);
      }
      {
        RowAcc ra[2] = {};
#pragma unroll
        for (int c = 0; c < 4; c++) row_acc(ra[c & 1], A[c]);
        const float2 qa = row_squares(ra[0], lane & 4), qb = row_squares(ra[1], lane & 4);
        const int src = (lane & 28) | (lane >> 3);
        const float q0 = __shfl_sync(0xffffffffu, qa.x + qb.x, src), q1 = __shfl_sync(0xffffffffu, qa.y + qb.y, src);
        bar_sync(BAR_X, 256);
        res_store(res, A[0]);
        norm_produce(row_norm(ra[0].s[0] + ra[1].s[0], q0, ra[0].s[2] + ra[1].s[2], q1, 0.5f), th, 4);
      }
      PROF_MARK(5);
      if (b < 72) {
        float c[8] = {0.f, 0.f, 0.f, 0.f, 0.f, 0.f, 0.f, 0.f};
#pragma unroll
        for (int i = 0; i < 8; i++) {
          const uint4 v = cv[i];
          c[0] += bf_lo(v.x); c[1] += bf_hi(v.x); c[2] += bf_lo(v.y); c[3] += bf_hi(v.y);
          c[4] += bf_lo(v.z); c[5] += bf_hi(v.z); c[6] += bf_lo(v.w); c[7] += bf_hi(v.w);
        }
#pragma unroll 1
        for (int m = 4; m <= 16; m <<= 1)
#pragma unroll
          for (int k = 0; k < 8; k++) c[k] += __shfl_xor_sync(0xffffffffu, c[k], m);
        if (lane < 4) {
          const uint32_t a = SM_BASE + SM_CS + 1792 + w * 128 + lane * 32;
          sts128(a, __float_as_uint(c[0]), __float_as_uint(c[1]), __float_as_uint(c[2]), __float_as_uint(c[3]));
          sts128(a + 16, __float_as_uint(c[4]), __float_as_uint(c[5]), __float_as_uint(c[6]), __float_as_uint(c[7]));
        }
        bar_sync(BAR_WG1, 128);
        if (th < 8) {
          float o[4] = {0.f, 0.f, 0.f, 0.f};
#pragma unroll 1
          for (int k = 0; k < 4; k++) {
            uint32_t e[4];
            lds128(SM_BASE + SM_CS + 1792 + k * 128 + th * 16, e[0], e[1], e[2], e[3]);
#pragma unroll
            for (int i = 0; i < 4; i++) o[i] += __uint_as_float(e[i]);
          }
          st_vec(&sc->cs[b * 8 + th], (__float_as_uint(o[0]) & ~1u) | tag, __float_as_uint(o[1]), __float_as_uint(o[2]), __float_as_uint(o[3]));
        }
      }
      bar_sync(BAR_WG1, 128);
      PROF_MARK(2);
#pragma unroll 1
      for (int i = th; i < 144; i += 128) {
        const int j = i >> 4;
        int src;
        if (j < CS_PW1) src = 320 + 64 * r + i;
        else if (j < CS_QKV) src = 192 + (j - CS_PW1) * 64 + 16 * r + (i & 15);
        else src = ((j - CS_QKV + 1) % 3) * 64 + 16 * r + (i & 15);
        uint32_t e[4], spin = 0;
#pragma unroll 1
        do {
          ld_vec(&sc->cs[src], e[0], e[1], e[2], e[3]);
        } while (((e[0] ^ tag) & 1u) && ++spin < SPIN_LIMIT);
        const float c0 = __uint_as_float(e[0] & ~1u), c1 = __uint_as_float(e[1]), c2 = __uint_as_float(e[2]), c3 = __uint_as_float(e[3]);
        const uint32_t h0 = pack2(c0, c1), h1 = pack2(c2, c3);
        const uint32_t a = SM_BASE + SM_CS + j * 256 + (i & 15) * 8;
        sts64(a ^ ((a >> 3) & 0x70), h0, h1);
        sts64((a + 128) ^ (((a + 128) >> 3) & 0x70), pack2(c0 - bf_lo(h0), c1 - bf_hi(h0)), pack2(c2 - bf_lo(h1), c3 - bf_hi(h1)));
      }
      fence_async_smem();
      PROF_MARK(4);
      bar_sync(BAR_RDY1, 160);
      norm_duty(sc, th, res, 1, 1.f, 3);
    }

#pragma unroll 1
    for (uint32_t pass = 0; pass < 2; pass++) {
      uint32_t Q[16];
      if (wg == 0) {
        float acc[4][32];
        uint32_t H[4][16];
        ACQUIRE(0);
        mma_tile<true>(acc[0], A[0], LO(0)); mma_tile<true>(acc[1], A[0], HI(0));
        ACQUIRE(1);
        mma_tile<true>(acc[2], A[0], LO(1)); mma_tile<true>(acc[3], A[0], HI(1));
        acquire_n<2, 3>();
        if (pass) gather_first<1, X_AG0>(A, xp, 1, sent);
        mma_tile<false>(acc[0], A[1], LO(2)); mma_tile<false>(acc[1], A[1], HI(2));
        if (pass) { gather_rest<1, X_AG0>(A, xp, 1); RELEASE(F_PW2, F_PW2 + 1); }
        PROF_MARK(2 + pass * 16);
        mma_tile<false>(acc[0], A[2], LO(3));
        WG_WAIT(3);
        uint32_t mu[4];
        float rs0, rs1, tn[2][4];
        norm_consume(here(th), mu, rs0, rs1);
        mma_tile_fold<2 * CS_FF2>(acc[0], A[3], LO(4), mu);
        RELEASE(0, 1);
        acquire_n<5, 3>();
        mma_tile<false>(acc[1], A[2], HI(3));
#define SEGS(a, b) silu_segs<a, b>(acc, tn, H, rs0, rs1)
        WG_WAIT(1); pin(acc[0]);
        SEGS(0, 1);
        mma_tile_fold<2 * CS_FF2 + 2>(acc[1], A[3], HI(4), mu);
        SEGS(1, 4);
        mma_tile<false>(acc[2], A[1], LO(5));
        SEGS(4, 6);
        mma_tile<false>(acc[2], A[2], LO(6));
        SEGS(6, 8);
        WG_WAIT(2); pin(acc[1]);
        RELEASE(2, 4);
        SEGS(8, 9);
        mma_tile_fold<2 * CS_FF2 + 4>(acc[2], A[3], LO(7), mu);
        SEGS(9, 12);
        mma_tile<false>(acc[3], A[1], HI(5));
        acquire_n<8, 2>();
        SEGS(12, 14);
        mma_tile<false>(acc[3], A[2], HI(6));
        SEGS(14, 16);
        WG_WAIT(2); pin(acc[2]);
        SEGS(16, 17);
        mma_tile_fold<2 * CS_FF2 + 6>(acc[3], A[3], HI(7), mu);
        SEGS(17, 20);
        mma_tile_reuse(acc[1], H[0], LO(8));
        acquire_n<10, 2>();
        SEGS(20, 22);
        mma_tile<false>(acc[1], H[1], HI(8));
        SEGS(22, 24);
        WG_WAIT(2); pin(acc[3]);
        RELEASE(5, 7);
        SEGS(24, 26);
        mma_tile<false>(acc[1], H[2], LO(9));
        SEGS(26, 28);
        mma_tile_reuse(acc[2], H[0], LO(10));
        SEGS(28, 31);
        mma_tile<false>(acc[2], H[1], HI(10));
        SEGS(31, 34);
#undef SEGS
        PROF_MARK(3 + pass * 16);
        const uint32_t rtag = here(pass ^ 1);
        const uint4* rs_in = xp + X_RS;
        mma_tile<false>(acc[1], H[3], HI(9));
        mma_tile<false>(acc[2], H[2], LO(11));
        acquire_n<12, 2>();
        uint4* rs_out = peer<1>(xp) + X_RS;
        mma_tile<false>(acc[2], H[3], HI(11));
        WG_WAIT(2); pin(acc[1]);
        send_half<0>(rs_out, acc[1], rtag);
        mma_tile_reuse(acc[3], H[0], LO(12));
        SCHED();
        send_half<1>(rs_out, acc[1], rtag);
        mma_tile<false>(acc[3], H[1], HI(12));
        rs_out = peer<2>(xp) + X_RS + 512;
        WG_WAIT(2); pin(acc[2]);
        send_half<0>(rs_out, acc[2], rtag);
        mma_tile<false>(acc[3], H[2], LO(13));
        SCHED();
        send_half<1>(rs_out, acc[2], rtag);
        mma_tile<false>(acc[3], H[3], HI(13));
        RELEASE(8, 9);
        acquire_n<14, 2>();
        mma_tile_reuse(acc[1], H[0], LO(14));
        rs_out = peer<3>(xp) + X_RS + 1024;
        if (!pass) bar_sync(BAR_RDY, 160);
        fetch(rs_in, A[1]);
        SCHED();
        mma_tile<false>(acc[1], H[1], HI(14));
        WG_WAIT(2); pin(acc[3]);
        send_half<0>(rs_out, acc[3], rtag);
        send_half<1>(rs_out, acc[3], rtag);
        mma_tile<false>(acc[1], H[2], LO(15)); mma_tile<false>(acc[1], H[3], HI(15));
        SCHED();
        res_load(res, acc[2]);
        confirm(rs_in, A[1], rtag);
        mma_add_half(acc[2], A[1]);
        PROF_MARK(44);
        fetch(rs_in + 512, A[2]);
        fetch(rs_in + 1024, A[3]);
        confirm(rs_in + 512, A[2], rtag);
        mma_add_half(acc[2], A[2]);
        SCHED();
        confirm(rs_in + 1024, A[3], rtag);
        mma_add_half(acc[2], A[3]);
        PROF_MARK(4 + pass * 16);
        WG_WAIT(0); pin(acc[2]); pin(acc[1]);
#pragma unroll
        for (int i = 0; i < 16; i++) A[0][i] = pack2(fmaf(acc[1][2 * i], 0.5f, acc[2][2 * i]), fmaf(acc[1][2 * i + 1], 0.5f, acc[2][2 * i + 1]));
        if (pass) {
          PROF_MARK(21);
          stat_publish(A[0], sc, here(th), 0);
          const RowNorm fn = stat_gather(sc, here(th), 0, 1.f);
          const float nm0 = -fn.m0 * fn.rs0, nm1 = -fn.m1 * fn.rs1;
#pragma unroll
          for (int i = 0; i < 16; i++) {
            const float rs = (i & 1) ? fn.rs1 : fn.rs0, nm = (i & 1) ? nm1 : nm0;
            A[0][i] = pack2(fmaf(bf_lo(A[0][i]), rs, nm), fmaf(bf_hi(A[0][i]), rs, nm));
          }
          tile_store(here(maddr), A[0]);
          __syncwarp();
          const int row = 16 * w + (lane >> 3);
          uint4* dst = (uint4*)(out + ((size_t)batch * T_SEQ + t * 64 + row) * DM + 64 * r) + (lane & 7);
          const uint32_t src = stg + row * 128 + (((lane & 7) ^ (lane >> 3)) << 4);
#pragma unroll
          for (int i = 0; i < 4; i++) {
            uint4 v;
            lds128((src ^ ((i & 1) << 6)) + i * 512, v.x, v.y, v.z, v.w);
            if (row + 4 * i < nvalid) dst[i * 4 * (DM / 8)] = v;
          }
          PROF_MARK(22);
          PROF_TIME(31);
          break;
        }
        sent = send_residual(A[0], xp, res, 1);
        PROF_MARK(5);
        acquire_n<F_QKV, 6>();
        mma_tile<true>(acc[0], A[0], LO(F_QKV)); mma_tile<true>(acc[1], A[0], HI(F_QKV));
        mma_tile<true>(acc[2], A[0], LO(F_QKV + 1));
        gather_first<1, X_AG0>(A, xp, 1, sent);
        mma_tile<false>(acc[0], A[1], LO(F_QKV + 2)); mma_tile<false>(acc[1], A[1], HI(F_QKV + 2));
        gather_rest<1, X_AG0>(A, xp, 1);
        PROF_MARK(6);
        mma_tile<false>(acc[0], A[2], LO(F_QKV + 3));
        norm_consume(here(th), mu, rs0, rs1);
        if (row0 >= nvalid) rs0 = 0.f;
        if (row0 + 8 >= nvalid) rs1 = 0.f;
        mma_tile_fold<2 * CS_QKV - 6>(acc[0], A[3], LO(F_QKV + 4), mu);
        RELEASE(10, 15);
        mma_tile<false>(acc[1], A[2], HI(F_QKV + 3));
        mma_tile_fold<2 * CS_QKV - 4>(acc[1], A[3], HI(F_QKV + 4), mu);
        WG_WAIT(2); pin(acc[0]);
        scale_pack(acc[0], Q, rs0, rs1);
        tile_store(here(maddr), Q);
        fence_async_smem();
        bar_arrive(BAR_K, 160);
        mma_tile<false>(acc[2], A[1], HI(F_QKV + 1)); mma_tile<false>(acc[2], A[2], LO(F_QKV + 5));
        WG_WAIT(2); pin(acc[1]);
        scale_pack(acc[1], Q, rs0, rs1);
        tile_store(here(maddr) + TILE_BYTES, Q);
        fence_async_smem();
        bar_arrive(BAR_V, 160);
        mma_tile_fold<2 * CS_QKV - 2>(acc[2], A[3], HI(F_QKV + 5), mu);
        WG_WAIT(0); pin(acc[2]);
        scale_pack(acc[2], Q, rs0 * SM_SCALE_LOG2, rs1 * SM_SCALE_LOG2);
        res_store(here(res) - TILE_BYTES, Q);
        bar_arrive(BAR_Q, 256);
        acquire_n<F_SPARE, 2>();
        RELEASE(F_QKV, F_SPARE + 1);
      } else {
        bar_sync(BAR_Q, 256);
#pragma unroll
        for (int s = 0; s < 4; s++) lds128(res - TILE_BYTES + s * 512, Q[4 * s], Q[4 * s + 1], Q[4 * s + 2], Q[4 * s + 3]);
        if (w < 2) {
          const uint32_t v = w ? 0u : 0x3F803F80u;
#pragma unroll
          for (int s = 0; s < 4; s++) sts128(res - TILE_BYTES + s * 512, v, v, v, v);
          fence_async_smem();
        }
      }
      bar_sync(BAR_ATT, 256);
      PROF_MARK(7);

      const int dir = cw == 0 ? -1 : 1;
      uint32_t tap[15];
      {
        const uint32_t* dwp = (const uint32_t*)(dw + 64 * r) + lane + 7 * (DM / 2);
#pragma unroll
        for (int k = 0; k < 15; k++) tap[k] = __ldg(dwp + dir * (k - 7) * (DM / 2));
      }

      float O[36];
      {
        float S[2][32];
        uint32_t P[2][16], nm[4];
        pin(Q);
        WG_FENCE();
        qk_tile(S[0], Q, RING + (SM_STG >> 4));
        WG_COMMIT();
#pragma unroll
        for (int i = 0; i < 36; i++) O[i] = 0.f;
#pragma unroll
        for (int i = 0; i < 16; i++) P[1][i] = 0u;
        WG_WAIT(0); pin(S[0]);
        const float m0 = tile_max<0>(S[0]), m1 = tile_max<2>(S[0]);
        nm[0] = pack2(q ? 0.f : -m0, 0.f); nm[1] = pack2(q ? 0.f : -m1, 0.f); nm[2] = 0u; nm[3] = 0u;
#pragma unroll
        for (int k = 0; k < 15; k++) asm("mul.rn.bf16x2 %0, %0, %1;" : "+r"(tap[k]) : "r"(0x3F003F00u));
        pin(nm); pin(O); pin(P[1]); pin(tap);
        uint32_t sk = wg, sv = wg;
        mbar_wait(SM_BASE + SM_FULL + sk * 8, 0);
        PROF_MARK(8);
        WG_FENCE();
        qk_tile(S[0], Q, RING + sk * 1024);
        qk_shift(S[0], nm);
        WG_COMMIT();
        WG_WAIT(0); pin(S[0]);
#pragma unroll 1
        for (int it = 0; it < 4; it++) {
          attn_step(S[0], S[1], P[0], P[1], O, Q, nm, RING + sk * 1024 + 512, RING_V + (sv * 1024 + 512) * V_STEP);
          const uint32_t sn = it >= 2 ? wg : sk + 4;
          mbar_wait(SM_BASE + SM_FULL + sn * 8, it >= 2);
          mbar_wait(SM_BASE + SM_FULL + (sk + 2) * 8, it == 3);
          WG_WAIT(0); pin(O); pin(S[1]); pin(P[1]);
          if (lane == 0 && it < 3) {
            mbar_arrive(SM_BASE + SM_EMPTY + sk * 8);
            if (it) mbar_arrive(SM_BASE + SM_EMPTY + sv * 8);
          }
          sv = sk + 2; sk = sn;
          attn_step(S[1], S[0], P[1], P[0], O, Q, nm, RING + sk * 1024, RING_V + (sv * 1024) * V_STEP);
          WG_WAIT(0); pin(O); pin(S[0]); pin(P[0]);
        }
        WG_FENCE();
        pv_tile(O, P[1], RING_V + (sv * 1024 + 512) * V_STEP, (uint64_t)wg << 22);
        WG_COMMIT();
        WG_WAIT(0); pin(O);
      }
      PROF_MARK(9);

      if (wg == 1) {
        const uint32_t mo = stg + here(th) * 16;
#pragma unroll
        for (int i = 0; i < 9; i++)
          sts128(mo + i * 2048 + (i >> 3) * 4096, __float_as_uint(O[4 * i]), __float_as_uint(O[4 * i + 1]), __float_as_uint(O[4 * i + 2]), __float_as_uint(O[4 * i + 3]));
        bar_arrive(BAR_MERGE, 256);
        norm_duty(sc, here(th), res, 0, 0.5f, 0);
      } else {
        const uint32_t mo = stg + here(th) * 16;
        bar_sync(BAR_MERGE, 256);
#pragma unroll
        for (int i = 8; i >= 0; i--) {
          uint32_t e[4];
          lds128(mo + i * 2048 + (i >> 3) * 4096, e[0], e[1], e[2], e[3]);
#pragma unroll
          for (int k = 0; k < 4; k++) O[4 * i + k] += __uint_as_float(e[k]);
        }
        const bool safe = O[32] > 0x1p-60f && O[32] < 0x1p60f && O[34] > 0x1p-60f && O[34] < 0x1p60f;
        if (__builtin_expect(__any_sync(0xffffffffu, !safe), 0)) attention_exact(O, Q, sc, batch * 4 + r, lane);
        const float i0 = rcp_hw(O[32]), i1 = rcp_hw(O[34]);
#pragma unroll
        for (int i = 0; i < 16; i++) { const float v = (i & 1) ? i1 : i0; A[0][i] = pack2(O[2 * i] * v, O[2 * i + 1] * v); }
        PROF_MARK(10);
        sent = proj_residual<F_WO, 6>(A, xp, res, 0);
        PROF_MARK(12);
        float acc[2][32];
        mma_tile<true>(acc[0], A[0], LO(F_PW1)); mma_tile<true>(acc[1], A[0], HI(F_PW1));
        gather_first<1, X_AG0>(A, xp, 0, sent);
        mma_tile<false>(acc[1], A[1], HI(F_PW1 + 1)); mma_tile<false>(acc[0], A[1], LO(F_PW1 + 1));
        gather_rest<1, X_AG0>(A, xp, 0);
        PROF_MARK(13);
        mma_tile<false>(acc[1], A[2], HI(F_PW1 + 2));
        uint32_t mu[4];
        float rs0, rs1;
        norm_consume(here(th), mu, rs0, rs1);
        if (row0 >= nvalid) rs0 = 0.f;
        if (row0 + 8 >= nvalid) rs1 = 0.f;
        mma_tile_fold<2 * CS_PW1 + 2>(acc[1], A[3], HI(F_PW1 + 3), mu);
        RELEASE(F_KV + 10, F_WO + 1);
        mma_tile<false>(acc[0], A[2], LO(F_PW1 + 2));
        mma_tile_fold<2 * CS_PW1>(acc[0], A[3], LO(F_PW1 + 3), mu);
        WG_WAIT(2); pin(acc[1]);
#pragma unroll
        for (int i = 0; i < 32; i++) acc[1][i] = tanh_hw(acc[1][i] * ((i & 2) ? rs1 : rs0));
#pragma unroll
        for (int i = 0; i < 32; i++) { const float rs = (i & 2) ? rs1 : rs0; acc[1][i] = fmaf(acc[1][i], rs, rs); }
        pin(acc[1]);
        SCHED();
        WG_WAIT(0); pin(acc[0]);
#pragma unroll
        for (int i = 0; i < 16; i++) A[0][i] = pack2(acc[0][2 * i] * acc[1][2 * i], acc[0][2 * i + 1] * acc[1][2 * i + 1]);
        const uint32_t ga = stg + TILE_BYTES + here(mrow) * G_PITCH + (lane >> 4) * 16;
#pragma unroll
        for (int s = 0; s < 4; s++) stsm4(ga + s * 32, &A[0][4 * s]);
        RELEASE(F_PW1, F_PW1 + 3);
      }
      bar_sync(BAR_G, 256);
      PROF_MARK(14);

      {
        const int first = cw == 0 ? 14 : 8 * cw - 7;
        const uint32_t gsrc = stg + TILE_BYTES + first * G_PITCH + lane * 4;
        uint32_t in[22];
#pragma unroll
        for (int i = 0; i < 15; i++) in[i] = lds32(gsrc + dir * i * (int)G_PITCH);
        const bool edge = cw == 0 || cw == 7;
        const bool nbr = cw == 0 ? t > 0 : t < 15;
        if (edge) {
          if (nbr) {
            uint4* dst = &sc->x[b + 4 * dir][X_HALO + (cw == 0 ? 96 : 0) + lane];
            st_vec(dst, HALO_TAG, in[14], in[13], in[12]);
            st_vec(dst + 32, HALO_TAG, in[11], in[10], in[9]);
            st_vec(dst + 64, HALO_TAG, in[8], 0u, 0u);
          }
        } else {
#pragma unroll
          for (int i = 15; i < 22; i++) in[i] = lds32(gsrc + i * G_PITCH);
        }
        uint32_t cv[8];
#pragma unroll
        for (int i = 0; i < 15; i++)
#pragma unroll
          for (int o = 0; o < 8; o++) {
            if (i == o) asm("mul.rn.bf16x2 %0, %1, %2;" : "=r"(cv[o]) : "r"(in[i]), "r"(tap[0]));
            if (i > o) asm("fma.rn.bf16x2 %0, %1, %2, %0;" : "+r"(cv[o]) : "r"(in[i]), "r"(tap[i - o]));
          }
        pin(cv);
        if (edge) {
#pragma unroll
          for (int i = 15; i < 22; i++) in[i] = 0u;
          if (nbr) {
            const uint4* src = &sc->x[b][X_HALO + (cw == 0 ? 0 : 96) + lane];
            uint32_t e0, e1, e2, u0, u1, spin = 0;
#pragma unroll 1
            do {
              ld_vec(src, e0, in[15], in[16], in[17]);
              ld_vec(src + 32, e1, in[18], in[19], in[20]);
              ld_vec(src + 64, e2, in[21], u0, u1);
            } while (__any_sync(0xffffffffu, ((e0 ^ HALO_TAG) | (e1 ^ HALO_TAG) | (e2 ^ HALO_TAG)) != 0) && ++spin < SPIN_LIMIT);
          }
        }
#pragma unroll
        for (int i = 15; i < 22; i++)
#pragma unroll
          for (int o = 0; o < 8; o++)
            if (i - o <= 14) asm("fma.rn.bf16x2 %0, %1, %2, %0;" : "+r"(cv[o]) : "r"(in[i]), "r"(tap[i - o]));
        const uint32_t fl = cw == 0 ? 7 : 0;
        const uint32_t cdst = (stg + cw * 1024 + lane * 4) ^ (fl * 144);
#pragma unroll
        for (int o = 0; o < 8; o++) {
          const float a = bf_lo(cv[o]), c = bf_hi(cv[o]);
          sts32(cdst ^ (o * 144), pack2(fmaf(a, tanh_hw(a), a), fmaf(c, tanh_hw(c), c)));
        }
      }
      if (wg == 1) {
        bar_arrive(BAR_C, 256);
        norm_duty(sc, here(th), res, 1, 0.5f, 0);
        if (th == 0) ((volatile uint32_t*)sc->epoch)[b] += 1;
        break;
      }
      bar_sync(BAR_C, 256);
      tile_load(here(maddr), A[0]);
      PROF_MARK(15);
      sent = proj_residual<F_PW2, 2>(A, xp, res, 1);
      PROF_MARK(17);
    }
  }
}

typedef CUresult (*EncodeFn)(CUtensorMap*, CUtensorMapDataType, cuuint32_t, void*, const cuuint64_t*, const cuuint64_t*,
                             const cuuint32_t*, const cuuint32_t*, CUtensorMapInterleave, CUtensorMapSwizzle,
                             CUtensorMapL2promotion, CUtensorMapFloatOOBfill);

void make_map(EncodeFn fn, CUtensorMap* m, const void* w, int rows, int cols, CUtensorMapSwizzle swz) {
  const cuuint64_t dims[2] = {(cuuint64_t)cols, (cuuint64_t)rows}, strides[1] = {(cuuint64_t)cols * 2};
  const cuuint32_t box[2] = {64, 64}, es[2] = {1, 1};
  fn(m, CU_TENSOR_MAP_DATA_TYPE_BFLOAT16, 2, const_cast<void*>(w), dims, strides, box, es, CU_TENSOR_MAP_INTERLEAVE_NONE,
     swz, CU_TENSOR_MAP_L2_PROMOTION_L2_128B, CU_TENSOR_MAP_FLOAT_OOB_FILL_NONE);
}

}

extern "C" void kernel_launch(void* const* d_in, const int* in_sizes, int n_in, void* d_out, int out_size) {
  static EncodeFn fn = nullptr;
  static Scratch* sc = nullptr;
  if (!fn) {
    void* f = nullptr;
    cudaDriverEntryPointQueryResult st;
    cudaGetDriverEntryPoint("cuTensorMapEncodeTiled", &f, cudaEnableDefault, &st);
    fn = (EncodeFn)f;
    void* raw = nullptr;
    cudaGetSymbolAddress(&raw, g_scratch);
    sc = (Scratch*)(((uintptr_t)raw + X_ALIGN - 1) & ~(uintptr_t)(X_ALIGN - 1));
    cudaFuncSetAttribute(conformer_kernel, cudaFuncAttributeMaxDynamicSharedMemorySize, SM_TOTAL);
  }
  typedef const __nv_bfloat16* W;
  const CUtensorMapSwizzle S = CU_TENSOR_MAP_SWIZZLE_128B;
  Params p;
  {
    const cuuint64_t dims[4] = {64, T_SEQ, 4, 2}, strides[3] = {512, 128, T_SEQ * 512};
    const cuuint32_t box[4] = {64, 64, 4, 1}, es[4] = {1, 1, 1, 1};
    fn(&p.map[M_X], CU_TENSOR_MAP_DATA_TYPE_BFLOAT16, 4, d_in[0], dims, strides, box, es, CU_TENSOR_MAP_INTERLEAVE_NONE, S,
       CU_TENSOR_MAP_L2_PROMOTION_L2_128B, CU_TENSOR_MAP_FLOAT_OOB_FILL_NONE);
  }
  make_map(fn, &p.map[M_FF1A], d_in[1], 256, 1024, S);
  make_map(fn, &p.map[M_FF1B], d_in[2], 1024, 256, S);
  make_map(fn, &p.map[M_QKV], d_in[3], 256, 768, S);
  make_map(fn, &p.map[M_KV], sc->kv, 16384, 64, CU_TENSOR_MAP_SWIZZLE_NONE);
  make_map(fn, &p.map[M_WO], d_in[4], 256, 256, S);
  make_map(fn, &p.map[M_PW1], d_in[5], 256, 512, S);
  make_map(fn, &p.map[M_PW2], d_in[7], 256, 256, S);
  make_map(fn, &p.map[M_FF2A], d_in[8], 256, 1024, S);
  make_map(fn, &p.map[M_FF2B], d_in[9], 1024, 256, S);
  p.w_ff1b = (W)d_in[2]; p.w_qkv = (W)d_in[3]; p.w_o = (W)d_in[4]; p.w_pw1 = (W)d_in[5];
  p.w_pw2 = (W)d_in[7]; p.w_ff2a = (W)d_in[8]; p.w_ff2b = (W)d_in[9];

  cudaLaunchConfig_t cfg = {};
  cfg.gridDim = dim3(NCTA);
  cfg.blockDim = dim3(384);
  cfg.dynamicSmemBytes = SM_TOTAL;
  cfg.stream = cudaStreamPerThread;
  cudaLaunchAttribute at[1];
  at[0].id = cudaLaunchAttributeCooperative;
  at[0].val.cooperative = 1;
  cfg.attrs = at;
  cfg.numAttrs = 1;
  cudaLaunchKernelEx(&cfg, conformer_kernel, sc, (__nv_bfloat16*)d_out, (W)d_in[6], p);
}
```

```cpp
#include <cuda_runtime.h>
#include <cuda_bf16.h>
#include <cuda.h>
#include <stdint.h>

namespace {

constexpr int T_SEQ = 1000;
constexpr int DM = 256;
constexpr int NCTA = 128;
constexpr int NSTAGE = 12;
constexpr uint32_t STAGE_BYTES = 16384;
constexpr uint32_t TILE_BYTES = 8192;
constexpr uint32_t SM_BASE = 1024;
constexpr uint32_t SM_STG = NSTAGE * STAGE_BYTES;
constexpr uint32_t SM_FULL = SM_STG + 32768;
constexpr uint32_t SM_EMPTY = SM_FULL + 96;
constexpr uint32_t SM_XBAR = SM_FULL + 192;
constexpr uint32_t SM_EYE = SM_FULL + 256;
constexpr uint32_t SM_ONE = SM_FULL + 640;
constexpr uint32_t SM_CS = SM_FULL + 768;
constexpr uint32_t SM_TOTAL = SM_FULL + 3072;
constexpr int CS_FF2 = 0, CS_PW1 = 4, CS_QKV = 6;
constexpr uint32_t SPIN_LIMIT = 1u << 16;
constexpr float LN_EPS = 1e-5f;
constexpr float SM_SCALE_LOG2 = 0.125f * 1.4426950408889634f;
constexpr uint32_t G_PITCH = 144;

constexpr int F_QKV = 16, F_SPARE = 22, F_KV = 24, F_WO = 40, F_PW1 = 42, F_PW2 = 46, F_TOTAL = 64;
enum { M_FF1A, M_FF1B, M_QKV, M_KV, M_WO, M_PW1, M_PW2, M_FF2A, M_FF2B, M_X, M_COUNT };
enum { BAR_K = 1, BAR_V, BAR_Q, BAR_MERGE, BAR_G, BAR_C, BAR_WG1, BAR_RDY, BAR_ST, BAR_ATT, BAR_INIT, BAR_RDY1, BAR_X, BAR_RES };

struct Params {
  CUtensorMap map[M_COUNT];
  const __nv_bfloat16 *w_ff1b, *w_qkv, *w_o, *w_pw1, *w_pw2, *w_ff2a, *w_ff2b;
};

constexpr int X_RS = 0, X_AG1 = X_RS, X_HALO = X_RS + 512, X_CLEAR = 1024, X_AG0 = 1536, X_ST = 2048, X_SIZE = 4096;
constexpr uint32_t HALO_TAG = 0xFFFF0001u;
struct Scratch {
  uint4 x[NCTA][X_SIZE];
  uint4 kv[8][2][16][512];
  uint4 cs[576];
  uint32_t flag[8][32];
  uint32_t ready[NCTA];
  uint32_t epoch[NCTA];
};
constexpr size_t X_ALIGN = 4 * X_SIZE * sizeof(uint4);
__device__ uint8_t g_scratch[sizeof(Scratch) + X_ALIGN];
#define PROF_TIME(i)
#define PROF_MARK(i)

__device__ __forceinline__ void mbar_init(uint32_t bar, uint32_t cnt) {
  asm volatile("mbarrier.init.shared::cta.b64 [%0], %1;" :: "r"(bar), "r"(cnt) : "memory");
}
__device__ __forceinline__ void mbar_wait(uint32_t bar, uint32_t parity) {
  asm volatile("{\n.reg .pred p;\n.reg .u32 c;\nmov.u32 c, 0;\n"
               "WAIT_LOOP:\nmbarrier.try_wait.parity.shared::cta.b64 p, [%0], %1;\n@p bra WAIT_DONE;\n"
               "add.u32 c, c, 1;\nsetp.lt.u32 p, c, %2;\n@p bra WAIT_LOOP;\nWAIT_DONE:\n}"
               :: "r"(bar), "r"(parity), "n"(SPIN_LIMIT) : "memory");
}
__device__ __forceinline__ void mbar_arrive(uint32_t bar) {
  asm volatile("mbarrier.arrive.shared::cta.b64 _, [%0];" :: "r"(bar) : "memory");
}
#define bar_sync(id, n) asm volatile("bar.sync %0, %1;" :: "n"((int)(id)), "n"(n) : "memory")
#define bar_arrive(id, n) asm volatile("bar.arrive %0, %1;" :: "n"((int)(id)), "n"(n) : "memory")
__device__ __forceinline__ void fence_async_smem() { asm volatile("fence.proxy.async.shared::cta;" ::: "memory"); }

__device__ __forceinline__ void st_vec(uint4* p, uint32_t a, uint32_t b, uint32_t c, uint32_t d) {
  asm volatile("{\n.reg .b128 v;\n.reg .b64 lo, hi;\nmov.b64 lo, {%1, %2};\nmov.b64 hi, {%3, %4};\nmov.b128 v, {lo, hi};\n"
               "st.relaxed.gpu.global.b128 [%0], v;\n}" :: "l"(p), "r"(a), "r"(b), "r"(c), "r"(d) : "memory");
}
__device__ __forceinline__ void ld_vec(const uint4* p, uint32_t& a, uint32_t& b, uint32_t& c, uint32_t& d) {
  asm volatile("{\n.reg .b128 v;\n.reg .b64 lo, hi;\nld.relaxed.gpu.global.b128 v, [%4];\nmov.b128 {lo, hi}, v;\n"
               "mov.b64 {%0, %1}, lo;\nmov.b64 {%2, %3}, hi;\n}" : "=r"(a), "=r"(b), "=r"(c), "=r"(d) : "l"(p) : "memory");
}
__device__ __forceinline__ void sts128(uint32_t a, uint32_t x, uint32_t y, uint32_t z, uint32_t w) {
  asm volatile("st.shared.v4.u32 [%0], {%1, %2, %3, %4};" :: "r"(a), "r"(x), "r"(y), "r"(z), "r"(w) : "memory");
}
__device__ __forceinline__ void lds128(uint32_t a, uint32_t& x, uint32_t& y, uint32_t& z, uint32_t& w) {
  asm volatile("ld.shared.v4.u32 {%0, %1, %2, %3}, [%4];" : "=r"(x), "=r"(y), "=r"(z), "=r"(w) : "r"(a) : "memory");
}
__device__ __forceinline__ uint32_t lds32(uint32_t a) {
  uint32_t x; asm volatile("ld.shared.u32 %0, [%1];" : "=r"(x) : "r"(a) : "memory"); return x;
}
__device__ __forceinline__ void sts32(uint32_t a, uint32_t x) { asm volatile("st.shared.u32 [%0], %1;" :: "r"(a), "r"(x) : "memory"); }
__device__ __forceinline__ void sts64(uint32_t a, uint32_t x, uint32_t y) {
  asm volatile("st.shared.v2.u32 [%0], {%1, %2};" :: "r"(a), "r"(x), "r"(y) : "memory");
}
__device__ __forceinline__ void stsm4(uint32_t a, const uint32_t* r) {
  asm volatile("stmatrix.sync.aligned.m8n8.x4.shared.b16 [%0], {%1, %2, %3, %4};" :: "r"(a), "r"(r[0]), "r"(r[1]), "r"(r[2]), "r"(r[3]) : "memory");
}
__device__ __forceinline__ void ldsm4(uint32_t a, uint32_t* r) {
  asm volatile("ldmatrix.sync.aligned.m8n8.x4.shared.b16 {%0, %1, %2, %3}, [%4];" : "=r"(r[0]), "=r"(r[1]), "=r"(r[2]), "=r"(r[3]) : "r"(a) : "memory");
}
__device__ __forceinline__ uint32_t pack2(float lo, float hi) {
  uint32_t r; asm("cvt.rn.bf16x2.f32 %0, %1, %2;" : "=r"(r) : "f"(hi), "f"(lo)); return r;
}
__device__ __forceinline__ float bf_lo(uint32_t w) { return __uint_as_float(w << 16); }
__device__ __forceinline__ float bf_hi(uint32_t w) { return __uint_as_float(w & 0xffff0000u); }
__device__ __forceinline__ float tanh_hw(float x) { float y; asm volatile("tanh.approx.f32 %0, %1;" : "=f"(y) : "f"(x)); return y; }
__device__ __forceinline__ float rcp_hw(float x) { float y; asm("rcp.approx.ftz.f32 %0, %1;" : "=f"(y) : "f"(x)); return y; }
__device__ __forceinline__ float ex2_hw(float x) { float y; asm("ex2.approx.ftz.f32 %0, %1;" : "=f"(y) : "f"(x)); return y; }

__device__ __forceinline__ uint32_t here(uint32_t v) { asm volatile("" : "+r"(v)); return v; }

#define SCHED() asm volatile("pmevent 1;" ::: "memory")
#define WG_FENCE() asm volatile("wgmma.fence.sync.aligned;" ::: "memory")
#define WG_COMMIT() asm volatile("wgmma.commit_group.sync.aligned;" ::: "memory")
#define WG_WAIT(n) asm volatile("wgmma.wait_group.sync.aligned %0;" :: "n"(n) : "memory")

template <int N> __device__ __forceinline__ void pin(float (&d)[N]) {
#pragma unroll
  for (int i = 0; i < N; i++) asm volatile("" : "+f"(d[i]) :: "memory");
}
template <int N> __device__ __forceinline__ void pin(uint32_t (&d)[N]) {
#pragma unroll
  for (int i = 0; i < N; i++) asm volatile("" : "+r"(d[i]) :: "memory");
}

#define WG_D32 "{%0, %1, %2, %3, %4, %5, %6, %7, %8, %9, %10, %11, %12, %13, %14, %15, %16, %17, %18, %19, %20, %21, %22, %23, %24, %25, %26, %27, %28, %29, %30, %31}"
template <int TB> __device__ __forceinline__ void wgmma64_acc(float (&d)[32], const uint32_t* a, uint64_t db) {
  asm volatile("wgmma.mma_async.sync.aligned.m64n64k16.f32.bf16.bf16 " WG_D32 ", {%32, %33, %34, %35}, %36, 1, 1, 1, %37;"
    : "+f"(d[0]), "+f"(d[1]), "+f"(d[2]), "+f"(d[3]), "+f"(d[4]), "+f"(d[5]), "+f"(d[6]), "+f"(d[7]),
      "+f"(d[8]), "+f"(d[9]), "+f"(d[10]), "+f"(d[11]), "+f"(d[12]), "+f"(d[13]), "+f"(d[14]), "+f"(d[15]),
      "+f"(d[16]), "+f"(d[17]), "+f"(d[18]), "+f"(d[19]), "+f"(d[20]), "+f"(d[21]), "+f"(d[22]), "+f"(d[23]),
      "+f"(d[24]), "+f"(d[25]), "+f"(d[26]), "+f"(d[27]), "+f"(d[28]), "+f"(d[29]), "+f"(d[30]), "+f"(d[31])
    : "r"(a[0]), "r"(a[1]), "r"(a[2]), "r"(a[3]), "l"(db), "n"(TB));
}
__device__ __forceinline__ void wgmma64_reuse(float (&d)[32], const uint32_t* a, uint64_t db, uint32_t zero) {
  asm volatile("{\n.reg .pred p;\nsetp.ne.u32 p, %37, 0;\nwgmma.mma_async.sync.aligned.m64n64k16.f32.bf16.bf16 " WG_D32 ", {%32, %33, %34, %35}, %36, p, 1, 1, 1;\n}"
    : "+f"(d[0]), "+f"(d[1]), "+f"(d[2]), "+f"(d[3]), "+f"(d[4]), "+f"(d[5]), "+f"(d[6]), "+f"(d[7]),
      "+f"(d[8]), "+f"(d[9]), "+f"(d[10]), "+f"(d[11]), "+f"(d[12]), "+f"(d[13]), "+f"(d[14]), "+f"(d[15]),
      "+f"(d[16]), "+f"(d[17]), "+f"(d[18]), "+f"(d[19]), "+f"(d[20]), "+f"(d[21]), "+f"(d[22]), "+f"(d[23]),
      "+f"(d[24]), "+f"(d[25]), "+f"(d[26]), "+f"(d[27]), "+f"(d[28]), "+f"(d[29]), "+f"(d[30]), "+f"(d[31])
    : "r"(a[0]), "r"(a[1]), "r"(a[2]), "r"(a[3]), "l"(db), "r"(zero));
}
template <int TB> __device__ __forceinline__ void wgmma64_set(float (&d)[32], const uint32_t* a, uint64_t db) {
  asm volatile("wgmma.mma_async.sync.aligned.m64n64k16.f32.bf16.bf16 " WG_D32 ", {%32, %33, %34, %35}, %36, 0, 1, 1, %37;"
    : "=f"(d[0]), "=f"(d[1]), "=f"(d[2]), "=f"(d[3]), "=f"(d[4]), "=f"(d[5]), "=f"(d[6]), "=f"(d[7]),
      "=f"(d[8]), "=f"(d[9]), "=f"(d[10]), "=f"(d[11]), "=f"(d[12]), "=f"(d[13]), "=f"(d[14]), "=f"(d[15]),
      "=f"(d[16]), "=f"(d[17]), "=f"(d[18]), "=f"(d[19]), "=f"(d[20]), "=f"(d[21]), "=f"(d[22]), "=f"(d[23]),
      "=f"(d[24]), "=f"(d[25]), "=f"(d[26]), "=f"(d[27]), "=f"(d[28]), "=f"(d[29]), "=f"(d[30]), "=f"(d[31])
    : "r"(a[0]), "r"(a[1]), "r"(a[2]), "r"(a[3]), "l"(db), "n"(TB));
}

__device__ __forceinline__ void wgmma72_acc(float (&d)[36], const uint32_t* a, uint64_t db) {
  asm volatile("wgmma.mma_async.sync.aligned.m64n72k16.f32.bf16.bf16 {%0, %1, %2, %3, %4, %5, %6, %7, %8, %9, %10, %11, %12, %13, %14, %15, %16, %17, %18, %19, %20, %21, %22, %23, %24, %25, %26, %27, %28, %29, %30, %31, %32, %33, %34, %35}, {%36, %37, %38, %39}, %40, 1, 1, 1, 1;"
    : "+f"(d[0]), "+f"(d[1]), "+f"(d[2]), "+f"(d[3]), "+f"(d[4]), "+f"(d[5]), "+f"(d[6]), "+f"(d[7]), "+f"(d[8]),
      "+f"(d[9]), "+f"(d[10]), "+f"(d[11]), "+f"(d[12]), "+f"(d[13]), "+f"(d[14]), "+f"(d[15]), "+f"(d[16]), "+f"(d[17]),
      "+f"(d[18]), "+f"(d[19]), "+f"(d[20]), "+f"(d[21]), "+f"(d[22]), "+f"(d[23]), "+f"(d[24]), "+f"(d[25]), "+f"(d[26]),
      "+f"(d[27]), "+f"(d[28]), "+f"(d[29]), "+f"(d[30]), "+f"(d[31]), "+f"(d[32]), "+f"(d[33]), "+f"(d[34]), "+f"(d[35])
    : "r"(a[0]), "r"(a[1]), "r"(a[2]), "r"(a[3]), "l"(db));
}
__device__ __forceinline__ void wgmma16_acc(float* d, const uint32_t* a, uint64_t db) {
  asm volatile("wgmma.mma_async.sync.aligned.m64n16k16.f32.bf16.bf16 {%0, %1, %2, %3, %4, %5, %6, %7}, {%8, %9, %10, %11}, %12, 1, 1, 1, 0;"
    : "+f"(d[0]), "+f"(d[1]), "+f"(d[2]), "+f"(d[3]), "+f"(d[4]), "+f"(d[5]), "+f"(d[6]), "+f"(d[7])
    : "r"(a[0]), "r"(a[1]), "r"(a[2]), "r"(a[3]), "l"(db));
}
__device__ __forceinline__ void hmma(float (&d)[4], const uint32_t* a, uint32_t b0, uint32_t b1) {
  asm("mma.sync.aligned.m16n8k16.row.col.f32.bf16.bf16.f32 {%0, %1, %2, %3}, {%4, %5, %6, %7}, {%8, %9}, {%0, %1, %2, %3};"
    : "+f"(d[0]), "+f"(d[1]), "+f"(d[2]), "+f"(d[3]) : "r"(a[0]), "r"(a[1]), "r"(a[2]), "r"(a[3]), "r"(b0), "r"(b1));
}

__device__ __forceinline__ void hmma8(float (&d)[4], const uint32_t* a, uint32_t b0) {
  asm("mma.sync.aligned.m16n8k8.row.col.f32.bf16.bf16.f32 {%0, %1, %2, %3}, {%4, %5}, {%6}, {%0, %1, %2, %3};"
    : "+f"(d[0]), "+f"(d[1]), "+f"(d[2]), "+f"(d[3]) : "r"(a[0]), "r"(a[1]), "r"(b0));
}

template <bool FIRST> __device__ __forceinline__ void mma_tile(float (&d)[32], const uint32_t (&a)[16], uint64_t db) {
  WG_FENCE();
#pragma unroll
  for (int s = 0; s < 4; s++) {
    if (FIRST && s == 0) wgmma64_set<1>(d, &a[0], db); else wgmma64_acc<1>(d, &a[4 * s], db + s * 128);
  }
  WG_COMMIT();
}
__device__ __forceinline__ void mma_tile_reuse(float (&d)[32], const uint32_t (&a)[16], uint64_t db) {
  WG_FENCE();
  wgmma64_reuse(d, &a[0], db, blockIdx.y);
#pragma unroll
  for (int s = 1; s < 4; s++) wgmma64_acc<1>(d, &a[4 * s], db + s * 128);
  WG_COMMIT();
}
template <int ROW> __device__ __forceinline__ void mma_tile_fold(float (&d)[32], const uint32_t (&a)[16], uint64_t db, const uint32_t (&mu)[4]) {
  WG_FENCE();
#pragma unroll
  for (int s = 0; s < 4; s++) wgmma64_acc<1>(d, &a[4 * s], db + s * 128);
  wgmma64_acc<1>(d, mu, (uint64_t)((SM_BASE + SM_CS + ROW * 128) >> 4) | (uint64_t(1) << 16) | (uint64_t(1) << 62));
  WG_COMMIT();
}
__device__ __forceinline__ void mma_add_half(float (&d)[32], const uint32_t (&a)[16]) {
  const uint64_t db = (uint64_t)((SM_BASE + SM_EYE) >> 4) | (uint64_t(8) << 16) | (uint64_t(8) << 32);
  WG_FENCE();
#pragma unroll
  for (int s = 0; s < 4; s++) wgmma16_acc(&d[8 * s], &a[4 * s], db);
  WG_COMMIT();
}
#define ACQUIRE(f) mbar_wait(SM_BASE + SM_FULL + ((f) % NSTAGE) * 8, ((f) / NSTAGE) & 1)
template <int F, int N> __device__ __forceinline__ void acquire_n() {
  static_assert(F % NSTAGE + N <= NSTAGE, "stages must not wrap");
  uint32_t spin = 0, ok;
  do {
    ok = 1;
#pragma unroll
    for (int i = 0; i < N; i++)
      asm volatile("{\n.reg .pred p;\nmbarrier.try_wait.parity.shared::cta.b64 p, [%1], %2;\nselp.u32 %0, %0, 0, p;\n}"
                   : "+r"(ok) : "r"(SM_BASE + SM_FULL + (F % NSTAGE + i) * 8), "r"((F / NSTAGE) & 1) : "memory");
  } while (!ok && ++spin < SPIN_LIMIT);
}
#define RELEASE(f0, f1) do { if (lane == 0) { _Pragma("unroll") for (int f_ = (f0); f_ <= (f1); f_++) mbar_arrive(SM_BASE + SM_EMPTY + (f_ % NSTAGE) * 8); } } while (0)
constexpr uint64_t RING = (uint64_t)(SM_BASE >> 4) | (uint64_t(1) << 16) | (uint64_t(64) << 32) | (uint64_t(1) << 62);
#define LO(f) (RING + ((f) % NSTAGE) * 1024)
#define HI(f) (RING + ((f) % NSTAGE) * 1024 + 512)

template <int C> __device__ __forceinline__ uint4* peer(uint4* p) {
  asm volatile("" : "+l"(p));
  return (uint4*)((uintptr_t)p ^ (C * X_SIZE * sizeof(uint4)));
}
__device__ __forceinline__ uint32_t clock_now() { uint32_t c; asm volatile("mov.u32 %0, %%clock;" : "=r"(c) :: "memory"); return c; }
__device__ __forceinline__ void publish(uint4* dst, uint32_t (&a)[16], uint32_t tag) {
#pragma unroll
  for (int s = 0; s < 4; s++) a[4 * s] = (a[4 * s] & ~1u) | tag;
  pin(a);
  SCHED();
#pragma unroll
  for (int s = 0; s < 4; s++) st_vec(dst + s * 128, a[4 * s], a[4 * s + 1], a[4 * s + 2], a[4 * s + 3]);
  SCHED();
}
__device__ __forceinline__ void fetch(const uint4* src, uint32_t (&a)[16]) {
#pragma unroll
  for (int s = 0; s < 4; s++) ld_vec(src + s * 128, a[4 * s], a[4 * s + 1], a[4 * s + 2], a[4 * s + 3]);
}
__device__ __forceinline__ uint32_t miss(const uint32_t (&a)[16], uint32_t tag) {
  return (a[0] ^ tag) | (a[4] ^ tag) | (a[8] ^ tag) | (a[12] ^ tag);
}
__device__ __forceinline__ bool stale(uint32_t v) { return __any_sync(0xffffffffu, here(v) & 1u); }
__device__ __forceinline__ void confirm(const uint4* src, uint32_t (&a)[16], uint32_t tag) {
  uint32_t spin = 0;
  while (__builtin_expect(stale(miss(a, tag)), 0) && ++spin < SPIN_LIMIT) fetch(src, a);
}
constexpr uint32_t GATHER_DELAY = 400;
template <int C0, int C1, int SLOT> __device__ __forceinline__ void gather_wait(uint32_t (&A)[4][16], uint4* xp, uint32_t tag) {
  uint32_t spin = 0;
  while (__builtin_expect(stale(miss(A[C0], tag) | miss(A[C1], tag)), 0) && ++spin < SPIN_LIMIT) {
    fetch(peer<C0>(xp) + SLOT, A[C0]);
    if (C1 != C0) fetch(peer<C1>(xp) + SLOT, A[C1]);
  }
}
template <int C, int SLOT> __device__ __forceinline__ void gather_first(uint32_t (&A)[4][16], uint4* xp, uint32_t tag, uint32_t sent) {
  while (clock_now() - sent < GATHER_DELAY) {}
  fetch(peer<1>(xp) + SLOT, A[1]); fetch(peer<2>(xp) + SLOT, A[2]); fetch(peer<3>(xp) + SLOT, A[3]);
  gather_wait<1, C, SLOT>(A, xp, tag);
}
template <int C, int SLOT> __device__ __forceinline__ void gather_rest(uint32_t (&A)[4][16], uint4* xp, uint32_t tag) {
  SCHED();
  gather_wait<C + 1, 3, SLOT>(A, xp, tag);
}
__device__ __forceinline__ void pack_acc(const float (&d)[32], uint32_t (&a)[16]) {
#pragma unroll
  for (int i = 0; i < 16; i++) a[i] = pack2(d[2 * i], d[2 * i + 1]);
}
__device__ __forceinline__ void res_store(uint32_t slot, const uint32_t (&a)[16]) {
#pragma unroll
  for (int s = 0; s < 4; s++) sts128(slot + s * 512, a[4 * s], a[4 * s + 1], a[4 * s + 2], a[4 * s + 3]);
}
__device__ __forceinline__ void res_load(uint32_t slot, float (&d)[32]) {
  uint32_t a[16];
#pragma unroll
  for (int s = 0; s < 4; s++) lds128(slot + s * 512, a[4 * s], a[4 * s + 1], a[4 * s + 2], a[4 * s + 3]);
#pragma unroll
  for (int i = 0; i < 16; i++) { d[2 * i] = bf_lo(a[i]); d[2 * i + 1] = bf_hi(a[i]); }
  pin(d);
}
__device__ __forceinline__ void tile_store(uint32_t maddr, const uint32_t (&a)[16]) {
#pragma unroll
  for (int s = 0; s < 4; s++) stsm4(maddr ^ (s << 5), &a[4 * s]);
}
__device__ __forceinline__ void tile_load(uint32_t maddr, uint32_t (&a)[16]) {
#pragma unroll
  for (int s = 0; s < 4; s++) ldsm4(maddr ^ (s << 5), &a[4 * s]);
}

struct RowAcc { float s[4], u[2][4], v[2][4]; };
__device__ __forceinline__ void row_acc(RowAcc& t, const uint32_t (&a)[16]) {
#pragma unroll
  for (int s = 0; s < 8; s++) {
    if ((s & 1) == 0) hmma(t.s, &a[2 * s], 0x3F803F80u, 0x3F803F80u);
    hmma8(t.u[s & 1], &a[2 * s], a[2 * s]);
    hmma8(t.v[s & 1], &a[2 * s], a[2 * s + 1]);
  }
}
__device__ __forceinline__ float2 row_squares(const RowAcc& t, bool odd) {
  return make_float2(odd ? t.u[0][1] + t.u[1][1] : t.u[0][0] + t.u[1][0], odd ? t.v[0][3] + t.v[1][3] : t.v[0][2] + t.v[1][2]);
}
__device__ __forceinline__ void stat_publish(const uint32_t (&a)[16], Scratch* sc, uint32_t th, uint32_t tag) {
  RowAcc t = {};
  row_acc(t, a);
  const float2 q = row_squares(t, th & 4);
  if ((th & 3) == ((th >> 3) & 3))
    st_vec(&sc->x[blockIdx.x][X_ST + (th >> 2)], (__float_as_uint(t.s[0]) & ~1u) | tag, __float_as_uint(q.x), __float_as_uint(t.s[2]), __float_as_uint(q.y));
}
struct RowNorm { float m0, rs0, m1, rs1; };
__device__ __forceinline__ RowNorm row_norm(float s0, float q0, float s1, float q1, float scale) {
  RowNorm n;
  n.m0 = s0 * (1.f / DM); n.m1 = s1 * (1.f / DM);
  n.rs0 = scale * rsqrtf(fmaxf(fmaf(-n.m0, n.m0, q0 * (1.f / DM)), 0.f) + LN_EPS);
  n.rs1 = scale * rsqrtf(fmaxf(fmaf(-n.m1, n.m1, q1 * (1.f / DM)), 0.f) + LN_EPS);
  return n;
}
__device__ __forceinline__ RowNorm stat_gather(Scratch* sc, uint32_t th, uint32_t tag, float scale) {
  const uint4* src = &sc->x[blockIdx.x & ~3u][X_ST + (th >> 2)];
  uint32_t v[16], spin = 0;
  do {
#pragma unroll
    for (int j = 0; j < 4; j++) ld_vec(src + j * X_SIZE, v[4 * j], v[4 * j + 1], v[4 * j + 2], v[4 * j + 3]);
  } while (stale(miss(v, tag)) && ++spin < SPIN_LIMIT);
  float f[4];
#pragma unroll
  for (int i = 0; i < 4; i++)
    f[i] = (__uint_as_float(v[i]) + __uint_as_float(v[4 + i])) + (__uint_as_float(v[8 + i]) + __uint_as_float(v[12 + i]));
  return row_norm(f[0], f[1], f[2], f[3], scale);
}
constexpr uint32_t SM_NORM = SM_BASE + SM_STG + 2 * TILE_BYTES + 4096;
__device__ __forceinline__ void norm_produce(const RowNorm& n, uint32_t th, uint32_t qsel) {
  const bool sel = (th & 3) == qsel;
  const float a = sel ? -n.m0 : 0.f, c = sel ? -n.m1 : 0.f;
  const uint32_t ah = pack2(a, a), ch = pack2(c, c);
  const float al = a - bf_lo(ah), cl = c - bf_lo(ch);
  sts128(SM_NORM + th * 16, ah, ch, pack2(al, al), pack2(cl, cl));
  sts64(SM_NORM + 2048 + th * 8, __float_as_uint(n.rs0), __float_as_uint(n.rs1));
  bar_arrive(BAR_ST, 256);
}
__device__ __forceinline__ void norm_duty(Scratch* sc, uint32_t th, uint32_t tag, float scale, uint32_t qsel) {
  bar_sync(BAR_RES, 256);
  norm_produce(stat_gather(sc, th, tag, scale), th, qsel);
}
__device__ __forceinline__ void norm_consume(uint32_t th, uint32_t (&mu)[4], float& rs0, float& rs1) {
  bar_sync(BAR_ST, 256);
  lds128(SM_NORM + th * 16, mu[0], mu[1], mu[2], mu[3]);
  asm volatile("ld.shared.v2.f32 {%0, %1}, [%2];" : "=f"(rs0), "=f"(rs1) : "r"(SM_NORM + 2048 + th * 8) : "memory");
}
__device__ __forceinline__ void scale_pack(const float (&d)[32], uint32_t (&a)[16], float rs0, float rs1) {
#pragma unroll
  for (int i = 0; i < 16; i++) { const float rs = (i & 1) ? rs1 : rs0; a[i] = pack2(d[2 * i] * rs, d[2 * i + 1] * rs); }
}
template <int S> __device__ __forceinline__ void silu_seg(float (&acc)[4][32], float (&tn)[2][4], uint32_t (&H)[4][16], float rs0, float rs1) {
  if (S >= 2) {
    const float* h = &acc[(S - 2) >> 3][4 * ((S - 2) & 7)];
    const float* v = tn[S & 1];
    uint32_t* o = &H[(S - 2) >> 3][2 * ((S - 2) & 7)];
    o[0] = pack2(fmaf(h[0], v[0], h[0]), fmaf(h[1], v[1], h[1]));
    o[1] = pack2(fmaf(h[2], v[2], h[2]), fmaf(h[3], v[3], h[3]));
    asm volatile("" : "+r"(o[0]), "+r"(o[1]));
  }
  if (S >= 1 && S <= 32) {
#pragma unroll
    for (int k = 0; k < 4; k++) tn[(S - 1) & 1][k] = tanh_hw(acc[((S - 1) >> 3) & 3][4 * ((S - 1) & 7) + k]);
  }
  if (S < 32) {
    float* h = &acc[(S >> 3) & 3][4 * (S & 7)];
    h[0] *= rs0; h[1] *= rs0; h[2] *= rs1; h[3] *= rs1;
    asm volatile("" : "+f"(h[0]), "+f"(h[1]), "+f"(h[2]), "+f"(h[3]));
  }
  SCHED();
}
template <int S0, int S1> __device__ __forceinline__ void silu_segs(float (&acc)[4][32], float (&tn)[2][4], uint32_t (&H)[4][16], float rs0, float rs1) {
  silu_seg<S0>(acc, tn, H, rs0, rs1);
  if constexpr (S0 + 1 < S1) silu_segs<S0 + 1, S1>(acc, tn, H, rs0, rs1);
}
template <int HALF> __device__ __forceinline__ void send_half(uint4* dst, const float (&d)[32], uint32_t tag) {
  uint32_t o[8];
#pragma unroll
  for (int i = 0; i < 8; i++) o[i] = pack2(d[16 * HALF + 2 * i], d[16 * HALF + 2 * i + 1]);
  o[0] = (o[0] & ~1u) | tag; o[4] = (o[4] & ~1u) | tag;
  pin(o);
  SCHED();
  st_vec(dst + HALF * 256, o[0], o[1], o[2], o[3]);
  st_vec(dst + HALF * 256 + 128, o[4], o[5], o[6], o[7]);
  SCHED();
}
__device__ __forceinline__ uint32_t send_residual(uint32_t (&a)[16], Scratch* sc, uint4* xp, uint32_t res, uint32_t tag) {
  const uint32_t exact[4] = {a[0], a[4], a[8], a[12]};
  publish(xp + X_AG0, a, tag);
  const uint32_t sent = clock_now();
  stat_publish(a, sc, threadIdx.x, tag);
  res_store(res, a);
#pragma unroll
  for (int s = 0; s < 4; s++) sts32(res + s * 512, exact[s]);
  bar_arrive(BAR_RES, 256);
  return sent;
}
template <int F, int N> __device__ __forceinline__ uint32_t proj_residual(uint32_t (&A)[4][16], Scratch* sc, uint4* xp, uint32_t res, uint32_t tag) {
  float acc[32];
  publish(xp + X_AG1, A[0], tag);
  const uint32_t sent = clock_now();
  acquire_n<F, N>();
  if (F == F_PW2) acquire_n<0, 5>();
  res_load(res, acc);
  mma_tile<false>(acc, A[0], LO(F));
  gather_first<2, X_AG1>(A, xp, tag, sent);
  mma_tile<false>(acc, A[1], HI(F));
  mma_tile<false>(acc, A[2], LO(F + 1));
  gather_rest<2, X_AG1>(A, xp, tag);
  PROF_MARK(F == F_WO ? 11 : 16);
  mma_tile<false>(acc, A[3], HI(F + 1));
  WG_WAIT(0); pin(acc);
  pack_acc(acc, A[0]);
  return send_residual(A[0], sc, xp, res, tag);
}

__device__ __forceinline__ void qk_tile(float (&S)[32], const uint32_t (&Q)[16], uint64_t dk) {
#pragma unroll
  for (int s = 0; s < 4; s++) {
    if (s == 0) wgmma64_set<0>(S, &Q[0], dk); else wgmma64_acc<0>(S, &Q[4 * s], dk + s * 2);
  }
}
__device__ __forceinline__ void qk_shift(float (&S)[32], const uint32_t (&nm)[4]) { wgmma64_acc<0>(S, nm, (uint64_t)((SM_BASE + SM_ONE) >> 4)); }
constexpr uint64_t V_STEP = uint64_t(1) - (uint64_t(1) << 16);
constexpr uint64_t RING_V = RING - (uint64_t(1) << 16) + ((uint64_t)((SM_STG + 2 * TILE_BYTES) >> 4) << 16);
__device__ __forceinline__ void pv_tile(float (&O)[36], const uint32_t (&P)[16], uint64_t dv, uint64_t pad) {
#pragma unroll
  for (int s = 0; s < 4; s++) wgmma72_acc(O, &P[4 * s], dv + s * 128 * V_STEP + (s < 2 ? 0 : (s - 1) * pad));
}
__device__ __forceinline__ void attn_step(const float (&Sc)[32], float (&Sn)[32], uint32_t (&Pc)[16], uint32_t (&Pp)[16], float (&O)[36],
                                          const uint32_t (&Q)[16], const uint32_t (&nm)[4], uint64_t dk, uint64_t dv) {
  WG_FENCE();
  qk_tile(Sn, Q, dk);
  qk_shift(Sn, nm);
  pv_tile(O, Pp, dv, 0);
  WG_COMMIT();
  SCHED();
#pragma unroll
  for (int i = 0; i < 16; i++) Pc[i] = pack2(ex2_hw(Sc[2 * i]), ex2_hw(Sc[2 * i + 1]));
  pin(Pc);
  SCHED();
}
template <int R> __device__ __forceinline__ float tile_max(const float (&S)[32]) {
  float t[4];
#pragma unroll
  for (int j = 0; j < 4; j++) t[j] = fmaxf(fmaxf(S[8 * j + R], S[8 * j + R + 1]), fmaxf(S[8 * j + R + 4], S[8 * j + R + 5]));
  float n = fmaxf(fmaxf(t[0], t[1]), fmaxf(t[2], t[3]));
  n = fmaxf(n, __shfl_xor_sync(0xffffffffu, n, 1));
  return fmaxf(n, __shfl_xor_sync(0xffffffffu, n, 2));
}
__device__ __forceinline__ void attention_exact(float (&O)[36], const uint32_t (&Q)[16], const Scratch* sc, int bh, int lane) {
  const char* kb = (const char*)&sc->kv[bh][0][0][0];
  const char* vb = (const char*)&sc->kv[bh][1][0][0];
  const int g = lane >> 2, q = lane & 3;
  float m0 = -INFINITY, m1 = -INFINITY, l0 = 0.f, l1 = 0.f;
  float o[8][4] = {};
#pragma unroll 1
  for (int k0 = 0; k0 < T_SEQ; k0 += 8) {
    float s[4] = {0.f, 0.f, 0.f, 0.f};
#pragma unroll
    for (int c = 0; c < 8; c++) hmma8(s, &Q[2 * c], __ldcg((const uint32_t*)(kb + (k0 + g) * 128 + ((c ^ g) << 4) + q * 4)));
    float n0 = fmaxf(s[0], s[1]), n1 = fmaxf(s[2], s[3]);
    n0 = fmaxf(n0, __shfl_xor_sync(0xffffffffu, n0, 1)); n1 = fmaxf(n1, __shfl_xor_sync(0xffffffffu, n1, 1));
    n0 = fmaxf(m0, fmaxf(n0, __shfl_xor_sync(0xffffffffu, n0, 2))); n1 = fmaxf(m1, fmaxf(n1, __shfl_xor_sync(0xffffffffu, n1, 2)));
    const float a0 = ex2_hw(m0 - n0), a1 = ex2_hw(m1 - n1);
    m0 = n0; m1 = n1;
    const uint32_t pp[2] = {pack2(ex2_hw(s[0] - n0), ex2_hw(s[1] - n0)), pack2(ex2_hw(s[2] - n1), ex2_hw(s[3] - n1))};
    l0 = fmaf(l0, a0, bf_lo(pp[0]) + bf_hi(pp[0])); l1 = fmaf(l1, a1, bf_lo(pp[1]) + bf_hi(pp[1]));
#pragma unroll
    for (int j = 0; j < 8; j++) {
      const uint32_t v0 = __ldcg((const uint16_t*)(vb + (k0 + 2 * q) * 128 + ((j ^ (2 * q)) << 4) + g * 2));
      const uint32_t v1 = __ldcg((const uint16_t*)(vb + (k0 + 2 * q + 1) * 128 + ((j ^ (2 * q + 1)) << 4) + g * 2));
      o[j][0] *= a0; o[j][1] *= a0; o[j][2] *= a1; o[j][3] *= a1;
      hmma8(o[j], pp, v0 | (v1 << 16));
    }
  }
  l0 += __shfl_xor_sync(0xffffffffu, l0, 1); l1 += __shfl_xor_sync(0xffffffffu, l1, 1);
  O[32] = l0 + __shfl_xor_sync(0xffffffffu, l0, 2); O[34] = l1 + __shfl_xor_sync(0xffffffffu, l1, 2);
#pragma unroll
  for (int i = 0; i < 32; i++) O[i] = o[i >> 2][i & 3];
}

__device__ __forceinline__ uint32_t fill_entry(int f, int r, int bh) {
  int m, x = r, y, dx = 0;
  if (f < F_QKV || f >= 48) {
    const int i = f & 15;
    m = f < F_QKV ? M_FF1A : M_FF2A;
    if (i < 8) { x = 4 * r + ((0xE2u >> i) & 1) * 2; y = r ^ ((0xE790u >> (2 * i)) & 3); dx = 1; }
    else { m++; x = r ^ (((i >> 1) - 3) & 3); y = 4 * r + 2 * (i & 1); }
  } else if (f < F_KV) {
    const int i = f - F_QKV;
    m = M_QKV;
    if (i == 1 || i >= 5) { y = r ^ (i == 1 ? 0 : 2); }
    else { x = 4 + r; y = r ^ (i ? i - 1 : 0); dx = 4; }
  } else if (f < F_WO) {
    const int i = f - F_KV;
    m = M_KV; x = 0; y = bh * 32 + (i & 2) * 8 + (i >> 2) * 4 + (i & 1) * 2;
  } else if (f >= F_PW1 && f < F_PW2) {
    m = M_PW1; y = r ^ (f - F_PW1); dx = 4;
  } else {
    m = f < F_PW1 ? M_WO : M_PW2; y = r ^ ((f & 1) * 2);
  }
  return m | (x << 4) | (y << 8) | (dx << 16);
}
__device__ __forceinline__ void tma_fill(uint32_t st, const CUtensorMap* map, uint32_t x, uint32_t y, uint32_t x2, uint32_t y2) {
  asm volatile("{\n.reg .pred p;\nelect.sync _|p, 0xffffffff;\n"
               "@p mbarrier.arrive.expect_tx.shared::cta.b64 _, [%1], 16384;\n"
               "@p cp.async.bulk.tensor.2d.shared::cluster.global.mbarrier::complete_tx::bytes [%0], [%2, {%3, %4}], [%1];\n"
               "@p cp.async.bulk.tensor.2d.shared::cluster.global.mbarrier::complete_tx::bytes [%0 + 8192], [%2, {%5, %6}], [%1];\n}"
               :: "r"(SM_BASE + st * STAGE_BYTES), "r"(SM_BASE + SM_FULL + st * 8), "l"(map), "r"(x), "r"(y), "r"(x2), "r"(y2) : "memory");
}
__device__ __forceinline__ void l2_prefetch(const void* p, uint32_t total, int b) {
  const uint32_t part = total / NCTA;
  asm volatile("cp.async.bulk.prefetch.L2.global [%0], %1;" :: "l"((const char*)p + (size_t)b * part), "r"(part) : "memory");
}

__global__ void __launch_bounds__(384, 1) conformer_kernel(Scratch* __restrict__ sc, __nv_bfloat16* __restrict__ out,
                                                           const __nv_bfloat16* __restrict__ dw, const __grid_constant__ Params p) {
  extern __shared__ __align__(1024) uint8_t smem[];
  const int tid = threadIdx.x, lane = tid & 31;
  const int cw = __shfl_sync(0xffffffffu, tid >> 5, 0), wg = cw >> 2, w = cw & 3;
  const int b = blockIdx.x, r = b & 3, batch = b >> 6, t = (b >> 2) & 15;
  if ((uint32_t)__cvta_generic_to_shared(smem) != SM_BASE) return;
  PROF_MARK(0);
  PROF_TIME(30);

  if (cw == 8) {
    if (lane == 0) {
      asm volatile("prefetch.tensormap [%0];" :: "l"(&p.map[M_X]) : "memory");
      asm volatile("prefetch.tensormap [%0];" :: "l"(&p.map[M_FF1A]) : "memory");
      mbar_init(SM_BASE + SM_XBAR, 1);
#pragma unroll
      for (int i = 0; i < NSTAGE; i++) mbar_init(SM_BASE + SM_FULL + i * 8, 1);
      fence_async_smem();
    }
    __syncwarp();
    asm volatile("{\n.reg .pred p;\nelect.sync _|p, 0xffffffff;\n"
                 "@p mbarrier.arrive.expect_tx.shared::cta.b64 _, [%1], 32768;\n"
                 "@p cp.async.bulk.tensor.4d.shared::cluster.global.mbarrier::complete_tx::bytes [%0], [%2, {0, %3, 0, %4}], [%1];\n}"
                 :: "r"(SM_BASE + SM_STG), "r"(SM_BASE + SM_XBAR), "l"(&p.map[M_X]), "r"(t * 64), "r"(batch) : "memory");
    bar_arrive(0, 320);
#pragma unroll 1
    for (int f = 0; f < 8; f++) {
      const uint32_t x = 256 * r + ((0xE2u >> f) & 1) * 128, y = (r ^ ((0xE790u >> (2 * f)) & 3)) * 64;
      tma_fill(f, &p.map[M_FF1A], x, y, x + 64, y);
    }
    PROF_MARK(1);
  } else if (cw == 9) {
    if (lane == 0) {
#pragma unroll
      for (int i = 0; i < NSTAGE; i++) mbar_init(SM_BASE + SM_EMPTY + i * 8, 4);
    }
    __syncwarp();
    bar_arrive(0, 320);
    bar_arrive(BAR_INIT, 64);
  } else if (wg < 2) {
    if (tid < 144) sts128(SM_BASE + SM_CS + tid * 16, 0, 0, 0, 0);
    if (wg == 1) {
      const int i = tid - 128;
      sts32(SM_BASE + SM_EYE + i * 4, i >= 96 ? 0x3F803F80u : ((i & 32) == 0 && (i & 3) == ((i >> 3) & 3)) ? (0x3F00u << ((i & 4) * 4)) : 0u);
    }
    fence_async_smem();
    bar_sync(0, 320);
  }

  if (wg == 2) {
    asm volatile("setmaxnreg.dec.sync.aligned.u32 40;");
    if (cw == 8) {
      const uint32_t* flag = &sc->flag[batch * 4 + r][lane];
      const uint32_t prev = ((volatile uint32_t*)sc->epoch)[b];
      uint32_t entry[2], ready = 0, st = 8, parity = 1;
#pragma unroll 1
      for (int i = 0; i < 2; i++) { entry[1] = fill_entry(i * 32 + lane, r, batch * 4 + r); if (i == 0) entry[0] = entry[1]; }
      bar_sync(BAR_INIT, 64);
#pragma unroll 1
      for (int f = 8; f < F_TOTAL; f++) {
        const uint32_t e = __shfl_sync(0xffffffffu, f < 32 ? entry[0] : entry[1], f);
        if ((e & 15) == M_KV) {
          const uint32_t need = 3u << ((e >> 8) & 31);
          uint32_t spin = 0;
#pragma unroll 1
          while ((ready & need) != need && ++spin < SPIN_LIMIT) {
            uint32_t v;
            asm volatile("ld.relaxed.gpu.global.u32 %0, [%1];" : "=r"(v) : "l"(flag) : "memory");
            ready = __ballot_sync(0xffffffffu, v - 1 == prev);
          }
        }
        if (f == F_KV) PROF_MARK(8);
        mbar_wait(SM_BASE + SM_EMPTY + st * 8, parity);
        const uint32_t x = (e << 2) & 0x3C0, y = (e >> 2) & 0x3FC0, dx = (e >> 16) << 6;
        tma_fill(st, &p.map[e & 15], x, y, x + dx, dx ? y : y ^ 64);
        if (++st == NSTAGE) { st = 0; parity ^= 1; }
      }
    } else if (here(cw) != 11) {
      const int kind = w - 1;
      const uint32_t epoch = ((volatile uint32_t*)sc->epoch)[b] + 1;
      if (kind == 0) {
        bar_sync(BAR_K, 160);
      } else {
        uint32_t v, spin = 0;
#pragma unroll 1
        do {
          asm volatile("ld.relaxed.gpu.global.u32 %0, [%1];" : "=r"(v) : "l"(&sc->ready[(b & ~3) + (lane & 3)]) : "memory");
        } while (__any_sync(0xffffffffu, v != epoch) && ++spin < SPIN_LIMIT);
        bar_arrive(BAR_RDY, 160);
        bar_arrive(BAR_RDY1, 160);
        bar_sync(BAR_V, 160);
      }
      if (lane == 0) {
        asm volatile("cp.async.bulk.global.shared::cta.bulk_group [%0], [%1], %2;"
                     :: "l"(&sc->kv[batch * 4 + r][kind][t][0]), "r"(SM_BASE + SM_STG + kind * TILE_BYTES), "r"(TILE_BYTES) : "memory");
        asm volatile("cp.async.bulk.commit_group;\ncp.async.bulk.wait_group 0;" ::: "memory");
        asm volatile("st.relaxed.gpu.global.u32 [%0], %1;" :: "l"(&sc->flag[batch * 4 + r][kind * 16 + t]), "r"(epoch) : "memory");
      }
    } else {
      const uint32_t epoch = ((volatile uint32_t*)sc->epoch)[b] + 1;
      if (lane == 0) {
        asm volatile("prefetch.tensormap [%0];" :: "l"(&p.map[M_FF1B]) : "memory");
        l2_prefetch(p.w_ff1b, 1024 * 256 * 2, b);
      }
#pragma unroll 1
      for (uint4* dst = &sc->x[b][X_CLEAR + lane]; dst < &sc->x[b][X_ST + 32]; dst += 32) {
        const uint32_t t0 = clock_now();
        st_vec(dst, 0u, 0u, 0u, 0u);
        while (clock_now() - t0 < 24) {}
      }
      asm volatile("fence.acq_rel.gpu;" ::: "memory");
      __syncwarp();
      if (lane == 0) {
        asm volatile("st.relaxed.gpu.global.u32 [%0], %1;" :: "l"(&sc->ready[b]), "r"(epoch) : "memory");
        l2_prefetch(p.w_o, 256 * 256 * 2, b);
        l2_prefetch(p.w_pw2, 256 * 256 * 2, b);
        l2_prefetch(p.w_ff2b, 1024 * 256 * 2, b);
#pragma unroll
        for (int i = M_QKV; i < M_X; i++) asm volatile("prefetch.tensormap [%0];" :: "l"(&p.map[i]) : "memory");
      }
    }
  } else {
    asm volatile("setmaxnreg.inc.sync.aligned.u32 232;");
    const int q = lane & 3, th = tid & 127;
    constexpr uint32_t stg = SM_BASE + SM_STG;
    const uint32_t mrow = 16 * w + (lane & 15);
    const uint32_t maddr = stg + mrow * 128 + (((lane >> 4) ^ (lane & 7)) << 4);
    const uint32_t res = stg + 3 * TILE_BYTES + w * 2048 + lane * 16;
    uint4* const xp = &sc->x[b][th];
    const int nvalid = T_SEQ - t * 64, row0 = 16 * w + (lane >> 2);

    uint32_t A[4][16];
    uint32_t sent = 0;
    mbar_wait(SM_BASE + SM_XBAR, 0);
    PROF_MARK(1);
#pragma unroll
    for (int c = 0; c < 4; c++) tile_load(maddr + (r ^ c) * TILE_BYTES, A[c]);
    if (wg == 0) {
      float sa[4] = {0.f, 0.f, 0.f, 0.f}, sb[4] = {0.f, 0.f, 0.f, 0.f};
#pragma unroll
      for (int i = 0; i < 16; i++) hmma((i & 1) ? sb : sa, &A[i >> 2][4 * (i & 3)], 0x3F803F80u, 0x3F803F80u);
      bar_arrive(BAR_X, 256);
      const float s0 = (sa[0] + sb[0]) * (1.f / DM), s1 = (sa[2] + sb[2]) * (1.f / DM);
      const uint32_t m0 = pack2(s0, s0), m1 = pack2(s1, s1);
#pragma unroll
      for (int c = 0; c < 4; c++) {
#pragma unroll
        for (int i = 0; i < 16; i++) asm("sub.rn.bf16x2 %0, %0, %1;" : "+r"(A[c][i]) : "r"((i & 1) ? m1 : m0));
        pin(A[c]);
      }
    } else {
      const uint32_t epoch = ((volatile uint32_t*)sc->epoch)[b] + 1, tag = epoch & 1;
      uint4 cv[8];
      if (b < 72) {
        const __nv_bfloat16* wp; int ld, col;
        if (b < 24) { wp = p.w_qkv; ld = 768; col = b * 32; }
        else if (b < 40) { wp = p.w_pw1; ld = 512; col = (b - 24) * 32; }
        else { wp = p.w_ff2a; ld = 1024; col = (b - 40) * 32; }
        const uint4* src = (const uint4*)(wp + (size_t)(th >> 2) * ld + col + q * 8);
#pragma unroll
        for (int i = 0; i < 8; i++) cv[i] = __ldg(src + i * 4 * ld);
      }
      {
        RowAcc ra[2] = {};
#pragma unroll
        for (int c = 0; c < 4; c++) row_acc(ra[c & 1], A[c]);
        const float2 qa = row_squares(ra[0], lane & 4), qb = row_squares(ra[1], lane & 4);
        const int src = (lane & 28) | (lane >> 3);
        const float q0 = __shfl_sync(0xffffffffu, qa.x + qb.x, src), q1 = __shfl_sync(0xffffffffu, qa.y + qb.y, src);
        bar_sync(BAR_X, 256);
        res_store(res, A[0]);
        norm_produce(row_norm(ra[0].s[0] + ra[1].s[0], q0, ra[0].s[2] + ra[1].s[2], q1, 0.5f), th, 4);
      }
      PROF_MARK(5);
      if (b < 72) {
        float c[8] = {0.f, 0.f, 0.f, 0.f, 0.f, 0.f, 0.f, 0.f};
#pragma unroll
        for (int i = 0; i < 8; i++) {
          const uint4 v = cv[i];
          c[0] += bf_lo(v.x); c[1] += bf_hi(v.x); c[2] += bf_lo(v.y); c[3] += bf_hi(v.y);
          c[4] += bf_lo(v.z); c[5] += bf_hi(v.z); c[6] += bf_lo(v.w); c[7] += bf_hi(v.w);
        }
#pragma unroll 1
        for (int m = 4; m <= 16; m <<= 1)
#pragma unroll
          for (int k = 0; k < 8; k++) c[k] += __shfl_xor_sync(0xffffffffu, c[k], m);
        if (lane < 4) {
          const uint32_t a = SM_BASE + SM_CS + 1792 + w * 128 + lane * 32;
          sts128(a, __float_as_uint(c[0]), __float_as_uint(c[1]), __float_as_uint(c[2]), __float_as_uint(c[3]));
          sts128(a + 16, __float_as_uint(c[4]), __float_as_uint(c[5]), __float_as_uint(c[6]), __float_as_uint(c[7]));
        }
        bar_sync(BAR_WG1, 128);
        if (th < 8) {
          float o[4] = {0.f, 0.f, 0.f, 0.f};
#pragma unroll 1
          for (int k = 0; k < 4; k++) {
            uint32_t e[4];
            lds128(SM_BASE + SM_CS + 1792 + k * 128 + th * 16, e[0], e[1], e[2], e[3]);
#pragma unroll
            for (int i = 0; i < 4; i++) o[i] += __uint_as_float(e[i]);
          }
          st_vec(&sc->cs[b * 8 + th], (__float_as_uint(o[0]) & ~1u) | tag, __float_as_uint(o[1]), __float_as_uint(o[2]), __float_as_uint(o[3]));
        }
      }
      bar_sync(BAR_WG1, 128);
      PROF_MARK(2);
#pragma unroll 1
      for (int i = th; i < 144; i += 128) {
        const int j = i >> 4;
        int src;
        if (j < CS_PW1) src = 320 + 64 * r + i;
        else if (j < CS_QKV) src = 192 + (j - CS_PW1) * 64 + 16 * r + (i & 15);
        else src = ((j - CS_QKV + 1) % 3) * 64 + 16 * r + (i & 15);
        uint32_t e[4], spin = 0;
#pragma unroll 1
        do {
          ld_vec(&sc->cs[src], e[0], e[1], e[2], e[3]);
        } while (((e[0] ^ tag) & 1u) && ++spin < SPIN_LIMIT);
        const float c0 = __uint_as_float(e[0] & ~1u), c1 = __uint_as_float(e[1]), c2 = __uint_as_float(e[2]), c3 = __uint_as_float(e[3]);
        const uint32_t h0 = pack2(c0, c1), h1 = pack2(c2, c3);
        const uint32_t a = SM_BASE + SM_CS + j * 256 + (i & 15) * 8;
        sts64(a ^ ((a >> 3) & 0x70), h0, h1);
        sts64((a + 128) ^ (((a + 128) >> 3) & 0x70), pack2(c0 - bf_lo(h0), c1 - bf_hi(h0)), pack2(c2 - bf_lo(h1), c3 - bf_hi(h1)));
      }
      fence_async_smem();
      PROF_MARK(4);
      bar_sync(BAR_RDY1, 160);
      norm_duty(sc, th, 1, 1.f, 3);
    }

#pragma unroll 1
    for (uint32_t pass = 0; pass < 2; pass++) {
      uint32_t Q[16];
      if (wg == 0) {
        float acc[4][32];
        uint32_t H[4][16];
        if (!pass) ACQUIRE(0);
        mma_tile<true>(acc[0], A[0], LO(0)); mma_tile<true>(acc[1], A[0], HI(0));
        if (!pass) ACQUIRE(1);
        mma_tile<true>(acc[2], A[0], LO(1)); mma_tile<true>(acc[3], A[0], HI(1));
        if (pass) gather_first<1, X_AG0>(A, xp, 1, sent); else acquire_n<2, 3>();
        mma_tile<false>(acc[0], A[1], LO(2)); mma_tile<false>(acc[1], A[1], HI(2));
        if (pass) { gather_rest<1, X_AG0>(A, xp, 1); RELEASE(F_PW2, F_PW2 + 1); }
        PROF_MARK(2 + pass * 16);
        mma_tile<false>(acc[0], A[2], LO(3));
        WG_WAIT(3);
        uint32_t mu[4];
        float rs0, rs1, tn[2][4];
        norm_consume(here(th), mu, rs0, rs1);
        mma_tile_fold<2 * CS_FF2>(acc[0], A[3], LO(4), mu);
        RELEASE(0, 1);
        acquire_n<5, 3>();
        mma_tile<false>(acc[1], A[2], HI(3));
#define SEGS(a, b) silu_segs<a, b>(acc, tn, H, rs0, rs1)
        WG_WAIT(1); pin(acc[0]);
        SEGS(0, 1);
        mma_tile_fold<2 * CS_FF2 + 2>(acc[1], A[3], HI(4), mu);
        SEGS(1, 4);
        mma_tile<false>(acc[2], A[1], LO(5));
        SEGS(4, 6);
        mma_tile<false>(acc[2], A[2], LO(6));
        SEGS(6, 8);
        WG_WAIT(2); pin(acc[1]);
        RELEASE(2, 4);
        SEGS(8, 9);
        mma_tile_fold<2 * CS_FF2 + 4>(acc[2], A[3], LO(7), mu);
        SEGS(9, 12);
        mma_tile<false>(acc[3], A[1], HI(5));
        acquire_n<8, 2>();
        SEGS(12, 14);
        mma_tile<false>(acc[3], A[2], HI(6));
        SEGS(14, 16);
        WG_WAIT(2); pin(acc[2]);
        SEGS(16, 17);
        mma_tile_fold<2 * CS_FF2 + 6>(acc[3], A[3], HI(7), mu);
        SEGS(17, 20);
        mma_tile_reuse(acc[1], H[0], LO(8));
        acquire_n<10, 2>();
        SEGS(20, 22);
        mma_tile<false>(acc[1], H[1], HI(8));
        SEGS(22, 24);
        WG_WAIT(2); pin(acc[3]);
        RELEASE(5, 7);
        SEGS(24, 26);
        mma_tile<false>(acc[1], H[2], LO(9));
        SEGS(26, 28);
        mma_tile_reuse(acc[2], H[0], LO(10));
        SEGS(28, 31);
        mma_tile<false>(acc[2], H[1], HI(10));
        SEGS(31, 34);
#undef SEGS
        PROF_MARK(3 + pass * 16);
        const uint32_t rtag = here(pass ^ 1);
        const uint4* rs_in = xp + X_RS;
        mma_tile<false>(acc[1], H[3], HI(9));
        mma_tile<false>(acc[2], H[2], LO(11));
        acquire_n<12, 2>();
        uint4* rs_out = peer<1>(xp) + X_RS;
        mma_tile<false>(acc[2], H[3], HI(11));
        WG_WAIT(2); pin(acc[1]);
        send_half<0>(rs_out, acc[1], rtag);
        mma_tile_reuse(acc[3], H[0], LO(12));
        SCHED();
        send_half<1>(rs_out, acc[1], rtag);
        mma_tile<false>(acc[3], H[1], HI(12));
        rs_out = peer<2>(xp) + X_RS + 512;
        WG_WAIT(2); pin(acc[2]);
        send_half<0>(rs_out, acc[2], rtag);
        mma_tile<false>(acc[3], H[2], LO(13));
        SCHED();
        send_half<1>(rs_out, acc[2], rtag);
        mma_tile<false>(acc[3], H[3], HI(13));
        RELEASE(8, 9);
        acquire_n<14, 2>();
        mma_tile_reuse(acc[1], H[0], LO(14));
        rs_out = peer<3>(xp) + X_RS + 1024;
        if (!pass) bar_sync(BAR_RDY, 160);
        fetch(rs_in, A[1]);
        SCHED();
        mma_tile<false>(acc[1], H[1], HI(14));
        WG_WAIT(2); pin(acc[3]);
        send_half<0>(rs_out, acc[3], rtag);
        send_half<1>(rs_out, acc[3], rtag);
        mma_tile<false>(acc[1], H[2], LO(15)); mma_tile<false>(acc[1], H[3], HI(15));
        SCHED();
        res_load(res, acc[2]);
        if (!pass) acquire_n<F_QKV, 6>();
        confirm(rs_in, A[1], rtag);
        mma_add_half(acc[2], A[1]);
        PROF_MARK(44);
        fetch(rs_in + 512, A[2]);
        fetch(rs_in + 1024, A[3]);
        confirm(rs_in + 512, A[2], rtag);
        mma_add_half(acc[2], A[2]);
        SCHED();
        confirm(rs_in + 1024, A[3], rtag);
        mma_add_half(acc[2], A[3]);
        PROF_MARK(4 + pass * 16);
        WG_WAIT(0); pin(acc[2]); pin(acc[1]);
#pragma unroll
        for (int i = 0; i < 16; i++) A[0][i] = pack2(fmaf(acc[1][2 * i], 0.5f, acc[2][2 * i]), fmaf(acc[1][2 * i + 1], 0.5f, acc[2][2 * i + 1]));
        if (pass) {
          PROF_MARK(21);
          stat_publish(A[0], sc, here(th), 0);
          const RowNorm fn = stat_gather(sc, here(th), 0, 1.f);
          const float nm0 = -fn.m0 * fn.rs0, nm1 = -fn.m1 * fn.rs1;
#pragma unroll
          for (int i = 0; i < 16; i++) {
            const float rs = (i & 1) ? fn.rs1 : fn.rs0, nm = (i & 1) ? nm1 : nm0;
            A[0][i] = pack2(fmaf(bf_lo(A[0][i]), rs, nm), fmaf(bf_hi(A[0][i]), rs, nm));
          }
          tile_store(here(maddr), A[0]);
          __syncwarp();
          const int row = 16 * w + (lane >> 3);
          uint4* dst = (uint4*)(out + ((size_t)batch * T_SEQ + t * 64 + row) * DM + 64 * r) + (lane & 7);
          const uint32_t src = stg + row * 128 + (((lane & 7) ^ (lane >> 3)) << 4);
#pragma unroll
          for (int i = 0; i < 4; i++) {
            uint4 v;
            lds128((src ^ ((i & 1) << 6)) + i * 512, v.x, v.y, v.z, v.w);
            if (row + 4 * i < nvalid) dst[i * 4 * (DM / 8)] = v;
          }
          PROF_MARK(22);
          PROF_TIME(31);
          break;
        }
        sent = send_residual(A[0], sc, xp, res, 1);
        PROF_MARK(5);
        mma_tile<true>(acc[0], A[0], LO(F_QKV)); mma_tile<true>(acc[1], A[0], HI(F_QKV));
        mma_tile<true>(acc[2], A[0], LO(F_QKV + 1));
        gather_first<1, X_AG0>(A, xp, 1, sent);
        mma_tile<false>(acc[0], A[1], LO(F_QKV + 2)); mma_tile<false>(acc[1], A[1], HI(F_QKV + 2));
        gather_rest<1, X_AG0>(A, xp, 1);
        PROF_MARK(6);
        mma_tile<false>(acc[0], A[2], LO(F_QKV + 3));
        norm_consume(here(th), mu, rs0, rs1);
        if (row0 >= nvalid) rs0 = 0.f;
        if (row0 + 8 >= nvalid) rs1 = 0.f;
        mma_tile_fold<2 * CS_QKV - 6>(acc[0], A[3], LO(F_QKV + 4), mu);
        RELEASE(10, 15);
        mma_tile<false>(acc[1], A[2], HI(F_QKV + 3));
        mma_tile_fold<2 * CS_QKV - 4>(acc[1], A[3], HI(F_QKV + 4), mu);
        WG_WAIT(2); pin(acc[0]);
        scale_pack(acc[0], Q, rs0, rs1);
        tile_store(here(maddr), Q);
        fence_async_smem();
        bar_arrive(BAR_K, 160);
        mma_tile<false>(acc[2], A[1], HI(F_QKV + 1)); mma_tile<false>(acc[2], A[2], LO(F_QKV + 5));
        WG_WAIT(2); pin(acc[1]);
        scale_pack(acc[1], Q, rs0, rs1);
        tile_store(here(maddr) + TILE_BYTES, Q);
        fence_async_smem();
        bar_arrive(BAR_V, 160);
        mma_tile_fold<2 * CS_QKV - 2>(acc[2], A[3], HI(F_QKV + 5), mu);
        WG_WAIT(0); pin(acc[2]);
        scale_pack(acc[2], Q, rs0 * SM_SCALE_LOG2, rs1 * SM_SCALE_LOG2);
        res_store(here(res) - TILE_BYTES, Q);
        bar_arrive(BAR_Q, 256);
        acquire_n<F_SPARE, 2>();
        RELEASE(F_QKV, F_SPARE + 1);
      } else {
        bar_sync(BAR_Q, 256);
#pragma unroll
        for (int s = 0; s < 4; s++) lds128(res - TILE_BYTES + s * 512, Q[4 * s], Q[4 * s + 1], Q[4 * s + 2], Q[4 * s + 3]);
        if (w < 2) {
          const uint32_t v = w ? 0u : 0x3F803F80u;
#pragma unroll
          for (int s = 0; s < 4; s++) sts128(res - TILE_BYTES + s * 512, v, v, v, v);
          fence_async_smem();
        }
      }
      bar_sync(BAR_ATT, 256);
      PROF_MARK(7);

      const int dir = cw == 0 ? -1 : 1;
      uint32_t tap[15];
      {
        const uint32_t* dwp = (const uint32_t*)(dw + 64 * r) + lane + 7 * (DM / 2);
#pragma unroll
        for (int k = 0; k < 15; k++) tap[k] = __ldg(dwp + dir * (k - 7) * (DM / 2));
      }

      float O[36];
      {
        float S[2][32];
        uint32_t P[2][16], nm[4];
        pin(Q);
        WG_FENCE();
        qk_tile(S[0], Q, RING + (SM_STG >> 4));
        WG_COMMIT();
#pragma unroll
        for (int i = 0; i < 36; i++) O[i] = 0.f;
#pragma unroll
        for (int i = 0; i < 16; i++) P[1][i] = 0u;
        WG_WAIT(0); pin(S[0]);
        const float m0 = tile_max<0>(S[0]), m1 = tile_max<2>(S[0]);
        nm[0] = pack2(q ? 0.f : -m0, 0.f); nm[1] = pack2(q ? 0.f : -m1, 0.f); nm[2] = 0u; nm[3] = 0u;
#pragma unroll
        for (int k = 0; k < 15; k++) asm("mul.rn.bf16x2 %0, %0, %1;" : "+r"(tap[k]) : "r"(0x3F003F00u));
        pin(nm); pin(O); pin(P[1]); pin(tap);
        uint32_t sk = wg, sv = wg;
        mbar_wait(SM_BASE + SM_FULL + sk * 8, 0);
        PROF_MARK(8);
        WG_FENCE();
        qk_tile(S[0], Q, RING + sk * 1024);
        qk_shift(S[0], nm);
        WG_COMMIT();
        WG_WAIT(0); pin(S[0]);
#pragma unroll 1
        for (int it = 0; it < 4; it++) {
          attn_step(S[0], S[1], P[0], P[1], O, Q, nm, RING + sk * 1024 + 512, RING_V + (sv * 1024 + 512) * V_STEP);
          const uint32_t sn = it >= 2 ? wg : sk + 4;
          mbar_wait(SM_BASE + SM_FULL + sn * 8, it >= 2);
          mbar_wait(SM_BASE + SM_FULL + (sk + 2) * 8, it == 3);
          WG_WAIT(0); pin(O); pin(S[1]); pin(P[1]);
          if (lane == 0 && it < 3) {
            mbar_arrive(SM_BASE + SM_EMPTY + sk * 8);
            if (it) mbar_arrive(SM_BASE + SM_EMPTY + sv * 8);
          }
          sv = sk + 2; sk = sn;
          attn_step(S[1], S[0], P[1], P[0], O, Q, nm, RING + sk * 1024, RING_V + (sv * 1024) * V_STEP);
          WG_WAIT(0); pin(O); pin(S[0]); pin(P[0]);
        }
        WG_FENCE();
        pv_tile(O, P[1], RING_V + (sv * 1024 + 512) * V_STEP, (uint64_t)wg << 22);
        WG_COMMIT();
        WG_WAIT(0); pin(O);
      }
      PROF_MARK(9);

      if (wg == 1) {
        const uint32_t mo = stg + here(th) * 16;
#pragma unroll
        for (int i = 0; i < 9; i++)
          sts128(mo + i * 2048 + (i >> 3) * 4096, __float_as_uint(O[4 * i]), __float_as_uint(O[4 * i + 1]), __float_as_uint(O[4 * i + 2]), __float_as_uint(O[4 * i + 3]));
        bar_arrive(BAR_MERGE, 256);
        norm_duty(sc, here(th), 0, 0.5f, 0);
      } else {
        const uint32_t mo = stg + here(th) * 16;
        bar_sync(BAR_MERGE, 256);
#pragma unroll
        for (int i = 8; i >= 0; i--) {
          uint32_t e[4];
          lds128(mo + i * 2048 + (i >> 3) * 4096, e[0], e[1], e[2], e[3]);
#pragma unroll
          for (int k = 0; k < 4; k++) O[4 * i + k] += __uint_as_float(e[k]);
        }
        const bool safe = O[32] > 0x1p-60f && O[32] < 0x1p60f && O[34] > 0x1p-60f && O[34] < 0x1p60f;
        if (__builtin_expect(__any_sync(0xffffffffu, !safe), 0)) attention_exact(O, Q, sc, batch * 4 + r, lane);
        const float i0 = rcp_hw(O[32]), i1 = rcp_hw(O[34]);
#pragma unroll
        for (int i = 0; i < 16; i++) { const float v = (i & 1) ? i1 : i0; A[0][i] = pack2(O[2 * i] * v, O[2 * i + 1] * v); }
        PROF_MARK(10);
        sent = proj_residual<F_WO, 6>(A, sc, xp, res, 0);
        PROF_MARK(12);
        float acc[2][32];
        mma_tile<true>(acc[0], A[0], LO(F_PW1)); mma_tile<true>(acc[1], A[0], HI(F_PW1));
        gather_first<1, X_AG0>(A, xp, 0, sent);
        mma_tile<false>(acc[1], A[1], HI(F_PW1 + 1)); mma_tile<false>(acc[0], A[1], LO(F_PW1 + 1));
        gather_rest<1, X_AG0>(A, xp, 0);
        PROF_MARK(13);
        mma_tile<false>(acc[1], A[2], HI(F_PW1 + 2));
        uint32_t mu[4];
        float rs0, rs1;
        norm_consume(here(th), mu, rs0, rs1);
        if (row0 >= nvalid) rs0 = 0.f;
        if (row0 + 8 >= nvalid) rs1 = 0.f;
        mma_tile_fold<2 * CS_PW1 + 2>(acc[1], A[3], HI(F_PW1 + 3), mu);
        RELEASE(F_KV + 10, F_WO + 1);
        mma_tile<false>(acc[0], A[2], LO(F_PW1 + 2));
        mma_tile_fold<2 * CS_PW1>(acc[0], A[3], LO(F_PW1 + 3), mu);
        WG_WAIT(2); pin(acc[1]);
#pragma unroll
        for (int i = 0; i < 32; i++) acc[1][i] = tanh_hw(acc[1][i] * ((i & 2) ? rs1 : rs0));
#pragma unroll
        for (int i = 0; i < 32; i++) { const float rs = (i & 2) ? rs1 : rs0; acc[1][i] = fmaf(acc[1][i], rs, rs); }
        pin(acc[1]);
        SCHED();
        WG_WAIT(0); pin(acc[0]);
#pragma unroll
        for (int i = 0; i < 16; i++) A[0][i] = pack2(acc[0][2 * i] * acc[1][2 * i], acc[0][2 * i + 1] * acc[1][2 * i + 1]);
        const uint32_t ga = stg + TILE_BYTES + here(mrow) * G_PITCH + (lane >> 4) * 16;
#pragma unroll
        for (int s = 0; s < 4; s++) stsm4(ga + s * 32, &A[0][4 * s]);
        RELEASE(F_PW1, F_PW1 + 3);
      }
      bar_sync(BAR_G, 256);
      PROF_MARK(14);

      {
        const int first = cw == 0 ? 14 : 8 * cw - 7;
        const uint32_t gsrc = stg + TILE_BYTES + first * G_PITCH + lane * 4;
        uint32_t in[22];
#pragma unroll
        for (int i = 0; i < 15; i++) in[i] = lds32(gsrc + dir * i * (int)G_PITCH);
        const bool edge = cw == 0 || cw == 7;
        const bool nbr = cw == 0 ? t > 0 : t < 15;
        if (edge) {
          if (nbr) {
            uint4* dst = &sc->x[b + 4 * dir][X_HALO + (cw == 0 ? 96 : 0) + lane];
            st_vec(dst, HALO_TAG, in[14], in[13], in[12]);
            st_vec(dst + 32, HALO_TAG, in[11], in[10], in[9]);
            st_vec(dst + 64, HALO_TAG, in[8], 0u, 0u);
          }
        } else {
#pragma unroll
          for (int i = 15; i < 22; i++) in[i] = lds32(gsrc + i * G_PITCH);
        }
        uint32_t cv[8];
#pragma unroll
        for (int i = 0; i < 15; i++)
#pragma unroll
          for (int o = 0; o < 8; o++) {
            if (i == o) asm("mul.rn.bf16x2 %0, %1, %2;" : "=r"(cv[o]) : "r"(in[i]), "r"(tap[0]));
            if (i > o) asm("fma.rn.bf16x2 %0, %1, %2, %0;" : "+r"(cv[o]) : "r"(in[i]), "r"(tap[i - o]));
          }
        pin(cv);
        PROF_MARK(45);
        if (edge) {
#pragma unroll
          for (int i = 15; i < 22; i++) in[i] = 0u;
          if (nbr) {
            const uint4* src = &sc->x[b][X_HALO + (cw == 0 ? 0 : 96) + lane];
            uint32_t e0, e1, e2, u0, u1, spin = 0;
#pragma unroll 1
            do {
              ld_vec(src, e0, in[15], in[16], in[17]);
              ld_vec(src + 32, e1, in[18], in[19], in[20]);
              ld_vec(src + 64, e2, in[21], u0, u1);
            } while (__any_sync(0xffffffffu, ((e0 ^ HALO_TAG) | (e1 ^ HALO_TAG) | (e2 ^ HALO_TAG)) != 0) && ++spin < SPIN_LIMIT);
          }
        }
#pragma unroll
        for (int i = 15; i < 22; i++)
#pragma unroll
          for (int o = 0; o < 8; o++)
            if (i - o <= 14) asm("fma.rn.bf16x2 %0, %1, %2, %0;" : "+r"(cv[o]) : "r"(in[i]), "r"(tap[i - o]));
        PROF_MARK(46);
        const uint32_t fl = cw == 0 ? 7 : 0;
        const uint32_t cdst = (stg + cw * 1024 + lane * 4) ^ (fl * 144);
#pragma unroll
        for (int o = 0; o < 8; o++) {
          const float a = bf_lo(cv[o]), c = bf_hi(cv[o]);
          sts32(cdst ^ (o * 144), pack2(fmaf(a, tanh_hw(a), a), fmaf(c, tanh_hw(c), c)));
        }
      }
      if (wg == 1) {
        bar_arrive(BAR_C, 256);
        norm_duty(sc, here(th), 1, 0.5f, 0);
        if (th == 0) ((volatile uint32_t*)sc->epoch)[b] += 1;
        break;
      }
      bar_sync(BAR_C, 256);
      tile_load(here(maddr), A[0]);
      PROF_MARK(15);
      sent = proj_residual<F_PW2, 2>(A, sc, xp, res, 1);
      PROF_MARK(17);
    }
  }
}

typedef CUresult (*EncodeFn)(CUtensorMap*, CUtensorMapDataType, cuuint32_t, void*, const cuuint64_t*, const cuuint64_t*,
                             const cuuint32_t*, const cuuint32_t*, CUtensorMapInterleave, CUtensorMapSwizzle,
                             CUtensorMapL2promotion, CUtensorMapFloatOOBfill);

void make_map(EncodeFn fn, CUtensorMap* m, const void* w, int rows, int cols, CUtensorMapSwizzle swz) {
  const cuuint64_t dims[2] = {(cuuint64_t)cols, (cuuint64_t)rows}, strides[1] = {(cuuint64_t)cols * 2};
  const cuuint32_t box[2] = {64, 64}, es[2] = {1, 1};
  fn(m, CU_TENSOR_MAP_DATA_TYPE_BFLOAT16, 2, const_cast<void*>(w), dims, strides, box, es, CU_TENSOR_MAP_INTERLEAVE_NONE,
     swz, CU_TENSOR_MAP_L2_PROMOTION_L2_128B, CU_TENSOR_MAP_FLOAT_OOB_FILL_NONE);
}

}

extern "C" void kernel_launch(void* const* d_in, const int* in_sizes, int n_in, void* d_out, int out_size) {
  static EncodeFn fn = nullptr;
  static Scratch* sc = nullptr;
  if (!fn) {
    void* f = nullptr;
    cudaDriverEntryPointQueryResult st;
    cudaGetDriverEntryPoint("cuTensorMapEncodeTiled", &f, cudaEnableDefault, &st);
    fn = (EncodeFn)f;
    void* raw = nullptr;
    cudaGetSymbolAddress(&raw, g_scratch);
    sc = (Scratch*)(((uintptr_t)raw + X_ALIGN - 1) & ~(uintptr_t)(X_ALIGN - 1));
    cudaFuncSetAttribute(conformer_kernel, cudaFuncAttributeMaxDynamicSharedMemorySize, SM_TOTAL);
  }
  typedef const __nv_bfloat16* W;
  const CUtensorMapSwizzle S = CU_TENSOR_MAP_SWIZZLE_128B;
  Params p;
  {
    const cuuint64_t dims[4] = {64, T_SEQ, 4, 2}, strides[3] = {512, 128, T_SEQ * 512};
    const cuuint32_t box[4] = {64, 64, 4, 1}, es[4] = {1, 1, 1, 1};
    fn(&p.map[M_X], CU_TENSOR_MAP_DATA_TYPE_BFLOAT16, 4, d_in[0], dims, strides, box, es, CU_TENSOR_MAP_INTERLEAVE_NONE, S,
       CU_TENSOR_MAP_L2_PROMOTION_L2_128B, CU_TENSOR_MAP_FLOAT_OOB_FILL_NONE);
  }
  make_map(fn, &p.map[M_FF1A], d_in[1], 256, 1024, S);
  make_map(fn, &p.map[M_FF1B], d_in[2], 1024, 256, S);
  make_map(fn, &p.map[M_QKV], d_in[3], 256, 768, S);
  make_map(fn, &p.map[M_KV], sc->kv, 16384, 64, CU_TENSOR_MAP_SWIZZLE_NONE);
  make_map(fn, &p.map[M_WO], d_in[4], 256, 256, S);
  make_map(fn, &p.map[M_PW1], d_in[5], 256, 512, S);
  make_map(fn, &p.map[M_PW2], d_in[7], 256, 256, S);
  make_map(fn, &p.map[M_FF2A], d_in[8], 256, 1024, S);
  make_map(fn, &p.map[M_FF2B], d_in[9], 1024, 256, S);
  p.w_ff1b = (W)d_in[2]; p.w_qkv = (W)d_in[3]; p.w_o = (W)d_in[4]; p.w_pw1 = (W)d_in[5];
  p.w_pw2 = (W)d_in[7]; p.w_ff2a = (W)d_in[8]; p.w_ff2b = (W)d_in[9];

  cudaLaunchConfig_t cfg = {};
  cfg.gridDim = dim3(NCTA);
  cfg.blockDim = dim3(384);
  cfg.dynamicSmemBytes = SM_TOTAL;
  cfg.stream = cudaStreamPerThread;
  cudaLaunchAttribute at[1];
  at[0].id = cudaLaunchAttributeCooperative;
  at[0].val.cooperative = 1;
  cfg.attrs = at;
  cfg.numAttrs = 1;
  cudaLaunchKernelEx(&cfg, conformer_kernel, sc, (__nv_bfloat16*)d_out, (W)d_in[6], p);
}
```

```cpp
#include <cuda_runtime.h>
#include <cuda_bf16.h>
#include <cuda.h>
#include <stdint.h>

namespace {

constexpr int T_SEQ = 1000;
constexpr int DM = 256;
constexpr int NCTA = 128;
constexpr int NSTAGE = 12;
constexpr uint32_t STAGE_BYTES = 16384;
constexpr uint32_t TILE_BYTES = 8192;
constexpr uint32_t SM_BASE = 1024;
constexpr uint32_t SM_STG = NSTAGE * STAGE_BYTES;
constexpr uint32_t SM_FULL = SM_STG + 32768;
constexpr uint32_t SM_EMPTY = SM_FULL + 96;
constexpr uint32_t SM_XBAR = SM_FULL + 192;
constexpr uint32_t SM_EYE = SM_FULL + 256;
constexpr uint32_t SM_ONE = SM_FULL + 640;
constexpr uint32_t SM_CS = SM_FULL + 768;
constexpr uint32_t SM_TOTAL = SM_FULL + 3072;
constexpr int CS_FF2 = 0, CS_PW1 = 4, CS_QKV = 6;
constexpr uint32_t SPIN_LIMIT = 1u << 16;
constexpr float LN_EPS = 1e-5f;
constexpr float SM_SCALE_LOG2 = 0.125f * 1.4426950408889634f;
constexpr uint32_t G_PITCH = 144;

constexpr int F_QKV = 16, F_SPARE = 22, F_KV = 24, F_WO = 40, F_PW1 = 42, F_PW2 = 46, F_TOTAL = 64;
enum { M_FF1A, M_FF1B, M_QKV, M_KV, M_WO, M_PW1, M_PW2, M_FF2A, M_FF2B, M_X, M_COUNT };
enum { BAR_K = 1, BAR_V, BAR_Q, BAR_MERGE, BAR_G, BAR_C, BAR_WG1, BAR_RDY, BAR_ST, BAR_ATT, BAR_INIT, BAR_RDY1, BAR_X, BAR_RES };

struct Params {
  CUtensorMap map[M_COUNT];
  const __nv_bfloat16 *w_ff1b, *w_qkv, *w_o, *w_pw1, *w_pw2, *w_ff2a, *w_ff2b;
};

constexpr int X_RS = 0, X_AG1 = X_RS, X_HALO = X_RS + 512, X_CLEAR = 1024, X_AG0 = 1536, X_ST = 2048, X_SIZE = 4096;
constexpr uint32_t HALO_TAG = 0xFFFF0001u;
struct Scratch {
  uint4 x[NCTA][X_SIZE];
  uint4 kv[8][2][16][512];
  uint4 cs[576];
  uint32_t flag[8][32][32];
  uint32_t ready[NCTA][32];
  uint32_t epoch[NCTA];
};
constexpr size_t X_ALIGN = 4 * X_SIZE * sizeof(uint4);
__device__ uint8_t g_scratch[sizeof(Scratch) + X_ALIGN];
#define PROF_TIME(i)
#define PROF_MARK(i)

__device__ __forceinline__ void mbar_init(uint32_t bar, uint32_t cnt) {
  asm volatile("mbarrier.init.shared::cta.b64 [%0], %1;" :: "r"(bar), "r"(cnt) : "memory");
}
__device__ __forceinline__ void mbar_wait(uint32_t bar, uint32_t parity) {
  asm volatile("{\n.reg .pred p;\n.reg .u32 c;\nmov.u32 c, 0;\n"
               "WAIT_LOOP:\nmbarrier.try_wait.parity.shared::cta.b64 p, [%0], %1;\n@p bra WAIT_DONE;\n"
               "add.u32 c, c, 1;\nsetp.lt.u32 p, c, %2;\n@p bra WAIT_LOOP;\nWAIT_DONE:\n}"
               :: "r"(bar), "r"(parity), "n"(SPIN_LIMIT) : "memory");
}
__device__ __forceinline__ void mbar_arrive(uint32_t bar) {
  asm volatile("mbarrier.arrive.shared::cta.b64 _, [%0];" :: "r"(bar) : "memory");
}
#define bar_sync(id, n) asm volatile("bar.sync %0, %1;" :: "n"((int)(id)), "n"(n) : "memory")
#define bar_arrive(id, n) asm volatile("bar.arrive %0, %1;" :: "n"((int)(id)), "n"(n) : "memory")
__device__ __forceinline__ void fence_async_smem() { asm volatile("fence.proxy.async.shared::cta;" ::: "memory"); }

__device__ __forceinline__ void st_vec(uint4* p, uint32_t a, uint32_t b, uint32_t c, uint32_t d) {
  asm volatile("{\n.reg .b128 v;\n.reg .b64 lo, hi;\nmov.b64 lo, {%1, %2};\nmov.b64 hi, {%3, %4};\nmov.b128 v, {lo, hi};\n"
               "st.relaxed.gpu.global.b128 [%0], v;\n}" :: "l"(p), "r"(a), "r"(b), "r"(c), "r"(d) : "memory");
}
__device__ __forceinline__ void ld_vec(const uint4* p, uint32_t& a, uint32_t& b, uint32_t& c, uint32_t& d) {
  asm volatile("{\n.reg .b128 v;\n.reg .b64 lo, hi;\nld.relaxed.gpu.global.b128 v, [%4];\nmov.b128 {lo, hi}, v;\n"
               "mov.b64 {%0, %1}, lo;\nmov.b64 {%2, %3}, hi;\n}" : "=r"(a), "=r"(b), "=r"(c), "=r"(d) : "l"(p) : "memory");
}
__device__ __forceinline__ void sts128(uint32_t a, uint32_t x, uint32_t y, uint32_t z, uint32_t w) {
  asm volatile("st.shared.v4.u32 [%0], {%1, %2, %3, %4};" :: "r"(a), "r"(x), "r"(y), "r"(z), "r"(w) : "memory");
}
__device__ __forceinline__ void lds128(uint32_t a, uint32_t& x, uint32_t& y, uint32_t& z, uint32_t& w) {
  asm volatile("ld.shared.v4.u32 {%0, %1, %2, %3}, [%4];" : "=r"(x), "=r"(y), "=r"(z), "=r"(w) : "r"(a) : "memory");
}
__device__ __forceinline__ uint32_t lds32(uint32_t a) {
  uint32_t x; asm volatile("ld.shared.u32 %0, [%1];" : "=r"(x) : "r"(a) : "memory"); return x;
}
__device__ __forceinline__ void sts32(uint32_t a, uint32_t x) { asm volatile("st.shared.u32 [%0], %1;" :: "r"(a), "r"(x) : "memory"); }
__device__ __forceinline__ void sts64(uint32_t a, uint32_t x, uint32_t y) {
  asm volatile("st.shared.v2.u32 [%0], {%1, %2};" :: "r"(a), "r"(x), "r"(y) : "memory");
}
__device__ __forceinline__ void stsm4(uint32_t a, const uint32_t* r) {
  asm volatile("stmatrix.sync.aligned.m8n8.x4.shared.b16 [%0], {%1, %2, %3, %4};" :: "r"(a), "r"(r[0]), "r"(r[1]), "r"(r[2]), "r"(r[3]) : "memory");
}
__device__ __forceinline__ void ldsm4(uint32_t a, uint32_t* r) {
  asm volatile("ldmatrix.sync.aligned.m8n8.x4.shared.b16 {%0, %1, %2, %3}, [%4];" : "=r"(r[0]), "=r"(r[1]), "=r"(r[2]), "=r"(r[3]) : "r"(a) : "memory");
}
__device__ __forceinline__ uint32_t pack2(float lo, float hi) {
  uint32_t r; asm("cvt.rn.bf16x2.f32 %0, %1, %2;" : "=r"(r) : "f"(hi), "f"(lo)); return r;
}
__device__ __forceinline__ float bf_lo(uint32_t w) { return __uint_as_float(w << 16); }
__device__ __forceinline__ float bf_hi(uint32_t w) { return __uint_as_float(w & 0xffff0000u); }
__device__ __forceinline__ float tanh_hw(float x) { float y; asm volatile("tanh.approx.f32 %0, %1;" : "=f"(y) : "f"(x)); return y; }
__device__ __forceinline__ float rcp_hw(float x) { float y; asm("rcp.approx.ftz.f32 %0, %1;" : "=f"(y) : "f"(x)); return y; }
__device__ __forceinline__ float ex2_hw(float x) { float y; asm("ex2.approx.ftz.f32 %0, %1;" : "=f"(y) : "f"(x)); return y; }

__device__ __forceinline__ uint32_t here(uint32_t v) { asm volatile("" : "+r"(v)); return v; }

#define SCHED() asm volatile("pmevent 1;" ::: "memory")
#define WG_FENCE() asm volatile("wgmma.fence.sync.aligned;" ::: "memory")
#define WG_COMMIT() asm volatile("wgmma.commit_group.sync.aligned;" ::: "memory")
#define WG_WAIT(n) asm volatile("wgmma.wait_group.sync.aligned %0;" :: "n"(n) : "memory")

template <int N> __device__ __forceinline__ void pin(float (&d)[N]) {
#pragma unroll
  for (int i = 0; i < N; i++) asm volatile("" : "+f"(d[i]) :: "memory");
}
template <int N> __device__ __forceinline__ void pin(uint32_t (&d)[N]) {
#pragma unroll
  for (int i = 0; i < N; i++) asm volatile("" : "+r"(d[i]) :: "memory");
}

#define WG_D32 "{%0, %1, %2, %3, %4, %5, %6, %7, %8, %9, %10, %11, %12, %13, %14, %15, %16, %17, %18, %19, %20, %21, %22, %23, %24, %25, %26, %27, %28, %29, %30, %31}"
template <int TB> __device__ __forceinline__ void wgmma64_acc(float (&d)[32], const uint32_t* a, uint64_t db) {
  asm volatile("wgmma.mma_async.sync.aligned.m64n64k16.f32.bf16.bf16 " WG_D32 ", {%32, %33, %34, %35}, %36, 1, 1, 1, %37;"
    : "+f"(d[0]), "+f"(d[1]), "+f"(d[2]), "+f"(d[3]), "+f"(d[4]), "+f"(d[5]), "+f"(d[6]), "+f"(d[7]),
      "+f"(d[8]), "+f"(d[9]), "+f"(d[10]), "+f"(d[11]), "+f"(d[12]), "+f"(d[13]), "+f"(d[14]), "+f"(d[15]),
      "+f"(d[16]), "+f"(d[17]), "+f"(d[18]), "+f"(d[19]), "+f"(d[20]), "+f"(d[21]), "+f"(d[22]), "+f"(d[23]),
      "+f"(d[24]), "+f"(d[25]), "+f"(d[26]), "+f"(d[27]), "+f"(d[28]), "+f"(d[29]), "+f"(d[30]), "+f"(d[31])
    : "r"(a[0]), "r"(a[1]), "r"(a[2]), "r"(a[3]), "l"(db), "n"(TB));
}
__device__ __forceinline__ void wgmma64_reuse(float (&d)[32], const uint32_t* a, uint64_t db, uint32_t zero) {
  asm volatile("{\n.reg .pred p;\nsetp.ne.u32 p, %37, 0;\nwgmma.mma_async.sync.aligned.m64n64k16.f32.bf16.bf16 " WG_D32 ", {%32, %33, %34, %35}, %36, p, 1, 1, 1;\n}"
    : "+f"(d[0]), "+f"(d[1]), "+f"(d[2]), "+f"(d[3]), "+f"(d[4]), "+f"(d[5]), "+f"(d[6]), "+f"(d[7]),
      "+f"(d[8]), "+f"(d[9]), "+f"(d[10]), "+f"(d[11]), "+f"(d[12]), "+f"(d[13]), "+f"(d[14]), "+f"(d[15]),
      "+f"(d[16]), "+f"(d[17]), "+f"(d[18]), "+f"(d[19]), "+f"(d[20]), "+f"(d[21]), "+f"(d[22]), "+f"(d[23]),
      "+f"(d[24]), "+f"(d[25]), "+f"(d[26]), "+f"(d[27]), "+f"(d[28]), "+f"(d[29]), "+f"(d[30]), "+f"(d[31])
    : "r"(a[0]), "r"(a[1]), "r"(a[2]), "r"(a[3]), "l"(db), "r"(zero));
}
template <int TB> __device__ __forceinline__ void wgmma64_set(float (&d)[32], const uint32_t* a, uint64_t db) {
  asm volatile("wgmma.mma_async.sync.aligned.m64n64k16.f32.bf16.bf16 " WG_D32 ", {%32, %33, %34, %35}, %36, 0, 1, 1, %37;"
    : "=f"(d[0]), "=f"(d[1]), "=f"(d[2]), "=f"(d[3]), "=f"(d[4]), "=f"(d[5]), "=f"(d[6]), "=f"(d[7]),
      "=f"(d[8]), "=f"(d[9]), "=f"(d[10]), "=f"(d[11]), "=f"(d[12]), "=f"(d[13]), "=f"(d[14]), "=f"(d[15]),
      "=f"(d[16]), "=f"(d[17]), "=f"(d[18]), "=f"(d[19]), "=f"(d[20]), "=f"(d[21]), "=f"(d[22]), "=f"(d[23]),
      "=f"(d[24]), "=f"(d[25]), "=f"(d[26]), "=f"(d[27]), "=f"(d[28]), "=f"(d[29]), "=f"(d[30]), "=f"(d[31])
    : "r"(a[0]), "r"(a[1]), "r"(a[2]), "r"(a[3]), "l"(db), "n"(TB));
}

__device__ __forceinline__ void wgmma72_acc(float (&d)[36], const uint32_t* a, uint64_t db) {
  asm volatile("wgmma.mma_async.sync.aligned.m64n72k16.f32.bf16.bf16 {%0, %1, %2, %3, %4, %5, %6, %7, %8, %9, %10, %11, %12, %13, %14, %15, %16, %17, %18, %19, %20, %21, %22, %23, %24, %25, %26, %27, %28, %29, %30, %31, %32, %33, %34, %35}, {%36, %37, %38, %39}, %40, 1, 1, 1, 1;"
    : "+f"(d[0]), "+f"(d[1]), "+f"(d[2]), "+f"(d[3]), "+f"(d[4]), "+f"(d[5]), "+f"(d[6]), "+f"(d[7]), "+f"(d[8]),
      "+f"(d[9]), "+f"(d[10]), "+f"(d[11]), "+f"(d[12]), "+f"(d[13]), "+f"(d[14]), "+f"(d[15]), "+f"(d[16]), "+f"(d[17]),
      "+f"(d[18]), "+f"(d[19]), "+f"(d[20]), "+f"(d[21]), "+f"(d[22]), "+f"(d[23]), "+f"(d[24]), "+f"(d[25]), "+f"(d[26]),
      "+f"(d[27]), "+f"(d[28]), "+f"(d[29]), "+f"(d[30]), "+f"(d[31]), "+f"(d[32]), "+f"(d[33]), "+f"(d[34]), "+f"(d[35])
    : "r"(a[0]), "r"(a[1]), "r"(a[2]), "r"(a[3]), "l"(db));
}
__device__ __forceinline__ void wgmma16_acc(float* d, const uint32_t* a, uint64_t db) {
  asm volatile("wgmma.mma_async.sync.aligned.m64n16k16.f32.bf16.bf16 {%0, %1, %2, %3, %4, %5, %6, %7}, {%8, %9, %10, %11}, %12, 1, 1, 1, 0;"
    : "+f"(d[0]), "+f"(d[1]), "+f"(d[2]), "+f"(d[3]), "+f"(d[4]), "+f"(d[5]), "+f"(d[6]), "+f"(d[7])
    : "r"(a[0]), "r"(a[1]), "r"(a[2]), "r"(a[3]), "l"(db));
}
__device__ __forceinline__ void hmma(float (&d)[4], const uint32_t* a, uint32_t b0, uint32_t b1) {
  asm("mma.sync.aligned.m16n8k16.row.col.f32.bf16.bf16.f32 {%0, %1, %2, %3}, {%4, %5, %6, %7}, {%8, %9}, {%0, %1, %2, %3};"
    : "+f"(d[0]), "+f"(d[1]), "+f"(d[2]), "+f"(d[3]) : "r"(a[0]), "r"(a[1]), "r"(a[2]), "r"(a[3]), "r"(b0), "r"(b1));
}

__device__ __forceinline__ void hmma8(float (&d)[4], const uint32_t* a, uint32_t b0) {
  asm("mma.sync.aligned.m16n8k8.row.col.f32.bf16.bf16.f32 {%0, %1, %2, %3}, {%4, %5}, {%6}, {%0, %1, %2, %3};"
    : "+f"(d[0]), "+f"(d[1]), "+f"(d[2]), "+f"(d[3]) : "r"(a[0]), "r"(a[1]), "r"(b0));
}

template <bool FIRST> __device__ __forceinline__ void mma_tile(float (&d)[32], const uint32_t (&a)[16], uint64_t db) {
  WG_FENCE();
#pragma unroll
  for (int s = 0; s < 4; s++) {
    if (FIRST && s == 0) wgmma64_set<1>(d, &a[0], db); else wgmma64_acc<1>(d, &a[4 * s], db + s * 128);
  }
  WG_COMMIT();
}
__device__ __forceinline__ void mma_tile_reuse(float (&d)[32], const uint32_t (&a)[16], uint64_t db) {
  WG_FENCE();
  wgmma64_reuse(d, &a[0], db, blockIdx.y);
#pragma unroll
  for (int s = 1; s < 4; s++) wgmma64_acc<1>(d, &a[4 * s], db + s * 128);
  WG_COMMIT();
}
template <int ROW> __device__ __forceinline__ void mma_tile_fold(float (&d)[32], const uint32_t (&a)[16], uint64_t db, const uint32_t (&mu)[4]) {
  WG_FENCE();
#pragma unroll
  for (int s = 0; s < 4; s++) wgmma64_acc<1>(d, &a[4 * s], db + s * 128);
  wgmma64_acc<1>(d, mu, (uint64_t)((SM_BASE + SM_CS + ROW * 128) >> 4) | (uint64_t(1) << 16) | (uint64_t(1) << 62));
  WG_COMMIT();
}
__device__ __forceinline__ void mma_add_half(float (&d)[32], const uint32_t (&a)[16]) {
  const uint64_t db = (uint64_t)((SM_BASE + SM_EYE) >> 4) | (uint64_t(8) << 16) | (uint64_t(8) << 32);
  WG_FENCE();
#pragma unroll
  for (int s = 0; s < 4; s++) wgmma16_acc(&d[8 * s], &a[4 * s], db);
  WG_COMMIT();
}
#define ACQUIRE(f) mbar_wait(SM_BASE + SM_FULL + ((f) % NSTAGE) * 8, ((f) / NSTAGE) & 1)
template <int F, int N> __device__ __forceinline__ void acquire_n() {
  static_assert(F % NSTAGE + N <= NSTAGE, "stages must not wrap");
  uint32_t spin = 0, ok;
  do {
    ok = 1;
#pragma unroll
    for (int i = 0; i < N; i++)
      asm volatile("{\n.reg .pred p;\nmbarrier.try_wait.parity.shared::cta.b64 p, [%1], %2;\nselp.u32 %0, %0, 0, p;\n}"
                   : "+r"(ok) : "r"(SM_BASE + SM_FULL + (F % NSTAGE + i) * 8), "r"((F / NSTAGE) & 1) : "memory");
  } while (!ok && ++spin < SPIN_LIMIT);
}
#define RELEASE(f0, f1) do { if (lane == 0) { _Pragma("unroll") for (int f_ = (f0); f_ <= (f1); f_++) mbar_arrive(SM_BASE + SM_EMPTY + (f_ % NSTAGE) * 8); } } while (0)
constexpr uint64_t RING = (uint64_t)(SM_BASE >> 4) | (uint64_t(1) << 16) | (uint64_t(64) << 32) | (uint64_t(1) << 62);
#define LO(f) (RING + ((f) % NSTAGE) * 1024)
#define HI(f) (RING + ((f) % NSTAGE) * 1024 + 512)

template <int C> __device__ __forceinline__ uint4* peer(uint4* p) {
  asm volatile("" : "+l"(p));
  return (uint4*)((uintptr_t)p ^ (C * X_SIZE * sizeof(uint4)));
}
__device__ __forceinline__ uint32_t clock_now() { uint32_t c; asm volatile("mov.u32 %0, %%clock;" : "=r"(c) :: "memory"); return c; }
__device__ __forceinline__ void publish(uint4* dst, uint32_t (&a)[16], uint32_t tag) {
#pragma unroll
  for (int s = 0; s < 4; s++) a[4 * s] = (a[4 * s] & ~1u) | tag;
  pin(a);
  SCHED();
#pragma unroll
  for (int s = 0; s < 4; s++) st_vec(dst + s * 128, a[4 * s], a[4 * s + 1], a[4 * s + 2], a[4 * s + 3]);
  SCHED();
}
__device__ __forceinline__ void fetch(const uint4* src, uint32_t (&a)[16]) {
#pragma unroll
  for (int s = 0; s < 4; s++) ld_vec(src + s * 128, a[4 * s], a[4 * s + 1], a[4 * s + 2], a[4 * s + 3]);
}
__device__ __forceinline__ uint32_t miss(const uint32_t (&a)[16], uint32_t tag) {
  return (a[0] ^ tag) | (a[4] ^ tag) | (a[8] ^ tag) | (a[12] ^ tag);
}
__device__ __forceinline__ bool stale(uint32_t v) { return __any_sync(0xffffffffu, here(v) & 1u); }
__device__ __forceinline__ void confirm(const uint4* src, uint32_t (&a)[16], uint32_t tag) {
  uint32_t spin = 0;
  while (__builtin_expect(stale(miss(a, tag)), 0) && ++spin < SPIN_LIMIT) fetch(src, a);
}
constexpr uint32_t GATHER_DELAY = 400;
template <int C0, int C1, int SLOT> __device__ __forceinline__ void gather_wait(uint32_t (&A)[4][16], uint4* xp, uint32_t tag) {
  uint32_t spin = 0;
  while (__builtin_expect(stale(miss(A[C0], tag) | miss(A[C1], tag)), 0) && ++spin < SPIN_LIMIT) {
    fetch(peer<C0>(xp) + SLOT, A[C0]);
    if (C1 != C0) fetch(peer<C1>(xp) + SLOT, A[C1]);
  }
}
template <int C, int SLOT> __device__ __forceinline__ void gather_first(uint32_t (&A)[4][16], uint4* xp, uint32_t tag, uint32_t sent) {
  while (clock_now() - sent < GATHER_DELAY) {}
  fetch(peer<1>(xp) + SLOT, A[1]); fetch(peer<2>(xp) + SLOT, A[2]); fetch(peer<3>(xp) + SLOT, A[3]);
  gather_wait<1, C, SLOT>(A, xp, tag);
}
template <int C, int SLOT> __device__ __forceinline__ void gather_rest(uint32_t (&A)[4][16], uint4* xp, uint32_t tag) {
  SCHED();
  gather_wait<C + 1, 3, SLOT>(A, xp, tag);
}
__device__ __forceinline__ void pack_acc(const float (&d)[32], uint32_t (&a)[16]) {
#pragma unroll
  for (int i = 0; i < 16; i++) a[i] = pack2(d[2 * i], d[2 * i + 1]);
}
__device__ __forceinline__ void res_store(uint32_t slot, const uint32_t (&a)[16]) {
#pragma unroll
  for (int s = 0; s < 4; s++) sts128(slot + s * 512, a[4 * s], a[4 * s + 1], a[4 * s + 2], a[4 * s + 3]);
}
__device__ __forceinline__ void res_load(uint32_t slot, float (&d)[32]) {
  uint32_t a[16];
#pragma unroll
  for (int s = 0; s < 4; s++) lds128(slot + s * 512, a[4 * s], a[4 * s + 1], a[4 * s + 2], a[4 * s + 3]);
#pragma unroll
  for (int i = 0; i < 16; i++) { d[2 * i] = bf_lo(a[i]); d[2 * i + 1] = bf_hi(a[i]); }
  pin(d);
}
__device__ __forceinline__ void tile_store(uint32_t maddr, const uint32_t (&a)[16]) {
#pragma unroll
  for (int s = 0; s < 4; s++) stsm4(maddr ^ (s << 5), &a[4 * s]);
}
__device__ __forceinline__ void tile_load(uint32_t maddr, uint32_t (&a)[16]) {
#pragma unroll
  for (int s = 0; s < 4; s++) ldsm4(maddr ^ (s << 5), &a[4 * s]);
}

struct RowAcc { float s[4], u[2][4], v[2][4]; };
__device__ __forceinline__ void row_acc(RowAcc& t, const uint32_t (&a)[16]) {
#pragma unroll
  for (int s = 0; s < 8; s++) {
    if ((s & 1) == 0) hmma(t.s, &a[2 * s], 0x3F803F80u, 0x3F803F80u);
    hmma8(t.u[s & 1], &a[2 * s], a[2 * s]);
    hmma8(t.v[s & 1], &a[2 * s], a[2 * s + 1]);
  }
}
__device__ __forceinline__ float2 row_squares(const RowAcc& t, bool odd) {
  return make_float2(odd ? t.u[0][1] + t.u[1][1] : t.u[0][0] + t.u[1][0], odd ? t.v[0][3] + t.v[1][3] : t.v[0][2] + t.v[1][2]);
}
__device__ __forceinline__ void stat_publish(const uint32_t (&a)[16], Scratch* sc, uint32_t th, uint32_t tag) {
  RowAcc t = {};
  row_acc(t, a);
  const float2 q = row_squares(t, th & 4);
  if ((th & 3) == ((th >> 3) & 3))
    st_vec(&sc->x[blockIdx.x][X_ST + (th >> 2)], (__float_as_uint(t.s[0]) & ~1u) | tag, __float_as_uint(q.x), __float_as_uint(t.s[2]), __float_as_uint(q.y));
}
struct RowNorm { float m0, rs0, m1, rs1; };
__device__ __forceinline__ RowNorm row_norm(float s0, float q0, float s1, float q1, float scale) {
  RowNorm n;
  n.m0 = s0 * (1.f / DM); n.m1 = s1 * (1.f / DM);
  n.rs0 = scale * rsqrtf(fmaxf(fmaf(-n.m0, n.m0, q0 * (1.f / DM)), 0.f) + LN_EPS);
  n.rs1 = scale * rsqrtf(fmaxf(fmaf(-n.m1, n.m1, q1 * (1.f / DM)), 0.f) + LN_EPS);
  return n;
}
__device__ __forceinline__ RowNorm stat_gather(Scratch* sc, uint32_t th, uint32_t tag, float scale) {
  const uint4* src = &sc->x[blockIdx.x & ~3u][X_ST + (th >> 2)];
  uint32_t v[16], spin = 0;
  do {
#pragma unroll
    for (int j = 0; j < 4; j++) ld_vec(src + j * X_SIZE, v[4 * j], v[4 * j + 1], v[4 * j + 2], v[4 * j + 3]);
  } while (stale(miss(v, tag)) && ++spin < SPIN_LIMIT);
  float f[4];
#pragma unroll
  for (int i = 0; i < 4; i++)
    f[i] = (__uint_as_float(v[i]) + __uint_as_float(v[4 + i])) + (__uint_as_float(v[8 + i]) + __uint_as_float(v[12 + i]));
  return row_norm(f[0], f[1], f[2], f[3], scale);
}
constexpr uint32_t SM_NORM = SM_BASE + SM_STG + 2 * TILE_BYTES + 4096;
__device__ __forceinline__ void norm_produce(const RowNorm& n, uint32_t th, uint32_t qsel) {
  const bool sel = (th & 3) == qsel;
  const float a = sel ? -n.m0 : 0.f, c = sel ? -n.m1 : 0.f;
  const uint32_t ah = pack2(a, a), ch = pack2(c, c);
  const float al = a - bf_lo(ah), cl = c - bf_lo(ch);
  sts128(SM_NORM + th * 16, ah, ch, pack2(al, al), pack2(cl, cl));
  sts64(SM_NORM + 2048 + th * 8, __float_as_uint(n.rs0), __float_as_uint(n.rs1));
  bar_arrive(BAR_ST, 256);
}
__device__ __forceinline__ void norm_duty(Scratch* sc, uint32_t th, uint32_t tag, float scale, uint32_t qsel) {
  bar_sync(BAR_RES, 256);
  norm_produce(stat_gather(sc, th, tag, scale), th, qsel);
}
__device__ __forceinline__ void norm_consume(uint32_t th, uint32_t (&mu)[4], float& rs0, float& rs1) {
  bar_sync(BAR_ST, 256);
  lds128(SM_NORM + th * 16, mu[0], mu[1], mu[2], mu[3]);
  asm volatile("ld.shared.v2.f32 {%0, %1}, [%2];" : "=f"(rs0), "=f"(rs1) : "r"(SM_NORM + 2048 + th * 8) : "memory");
}
__device__ __forceinline__ void scale_pack(const float (&d)[32], uint32_t (&a)[16], float rs0, float rs1) {
#pragma unroll
  for (int i = 0; i < 16; i++) { const float rs = (i & 1) ? rs1 : rs0; a[i] = pack2(d[2 * i] * rs, d[2 * i + 1] * rs); }
}
template <int S> __device__ __forceinline__ void silu_seg(float (&acc)[4][32], float (&tn)[2][4], uint32_t (&H)[4][16], float rs0, float rs1) {
  if (S >= 2) {
    const float* h = &acc[(S - 2) >> 3][4 * ((S - 2) & 7)];
    const float* v = tn[S & 1];
    uint32_t* o = &H[(S - 2) >> 3][2 * ((S - 2) & 7)];
    o[0] = pack2(fmaf(h[0], v[0], h[0]), fmaf(h[1], v[1], h[1]));
    o[1] = pack2(fmaf(h[2], v[2], h[2]), fmaf(h[3], v[3], h[3]));
    asm volatile("" : "+r"(o[0]), "+r"(o[1]));
  }
  if (S >= 1 && S <= 32) {
#pragma unroll
    for (int k = 0; k < 4; k++) tn[(S - 1) & 1][k] = tanh_hw(acc[((S - 1) >> 3) & 3][4 * ((S - 1) & 7) + k]);
  }
  if (S < 32) {
    float* h = &acc[(S >> 3) & 3][4 * (S & 7)];
    h[0] *= rs0; h[1] *= rs0; h[2] *= rs1; h[3] *= rs1;
    asm volatile("" : "+f"(h[0]), "+f"(h[1]), "+f"(h[2]), "+f"(h[3]));
  }
  SCHED();
}
template <int S0, int S1> __device__ __forceinline__ void silu_segs(float (&acc)[4][32], float (&tn)[2][4], uint32_t (&H)[4][16], float rs0, float rs1) {
  silu_seg<S0>(acc, tn, H, rs0, rs1);
  if constexpr (S0 + 1 < S1) silu_segs<S0 + 1, S1>(acc, tn, H, rs0, rs1);
}
template <int HALF> __device__ __forceinline__ void send_half(uint4* dst, const float (&d)[32], uint32_t tag) {
  uint32_t o[8];
#pragma unroll
  for (int i = 0; i < 8; i++) o[i] = pack2(d[16 * HALF + 2 * i], d[16 * HALF + 2 * i + 1]);
  o[0] = (o[0] & ~1u) | tag; o[4] = (o[4] & ~1u) | tag;
  pin(o);
  SCHED();
  st_vec(dst + HALF * 256, o[0], o[1], o[2], o[3]);
  st_vec(dst + HALF * 256 + 128, o[4], o[5], o[6], o[7]);
  SCHED();
}
__device__ __forceinline__ uint32_t send_residual(uint32_t (&a)[16], Scratch* sc, uint4* xp, uint32_t res, uint32_t tag) {
  const uint32_t exact[4] = {a[0], a[4], a[8], a[12]};
  publish(xp + X_AG0, a, tag);
  const uint32_t sent = clock_now();
  stat_publish(a, sc, threadIdx.x, tag);
  res_store(res, a);
#pragma unroll
  for (int s = 0; s < 4; s++) sts32(res + s * 512, exact[s]);
  bar_arrive(BAR_RES, 256);
  return sent;
}
template <int F, int N> __device__ __forceinline__ uint32_t proj_residual(uint32_t (&A)[4][16], Scratch* sc, uint4* xp, uint32_t res, uint32_t tag) {
  float acc[32];
  publish(xp + X_AG1, A[0], tag);
  const uint32_t sent = clock_now();
  acquire_n<F, N>();
  if (F == F_PW2) acquire_n<0, 5>();
  res_load(res, acc);
  mma_tile<false>(acc, A[0], LO(F));
  gather_first<2, X_AG1>(A, xp, tag, sent);
  mma_tile<false>(acc, A[1], HI(F));
  mma_tile<false>(acc, A[2], LO(F + 1));
  gather_rest<2, X_AG1>(A, xp, tag);
  PROF_MARK(F == F_WO ? 11 : 16);
  mma_tile<false>(acc, A[3], HI(F + 1));
  WG_WAIT(0); pin(acc);
  pack_acc(acc, A[0]);
  return send_residual(A[0], sc, xp, res, tag);
}

__device__ __forceinline__ void qk_tile(float (&S)[32], const uint32_t (&Q)[16], uint64_t dk) {
#pragma unroll
  for (int s = 0; s < 4; s++) {
    if (s == 0) wgmma64_set<0>(S, &Q[0], dk); else wgmma64_acc<0>(S, &Q[4 * s], dk + s * 2);
  }
}
__device__ __forceinline__ void qk_shift(float (&S)[32], const uint32_t (&nm)[4]) { wgmma64_acc<0>(S, nm, (uint64_t)((SM_BASE + SM_ONE) >> 4)); }
constexpr uint64_t V_STEP = uint64_t(1) - (uint64_t(1) << 16);
constexpr uint64_t RING_V = RING - (uint64_t(1) << 16) + ((uint64_t)((SM_STG + 2 * TILE_BYTES) >> 4) << 16);
__device__ __forceinline__ void pv_tile(float (&O)[36], const uint32_t (&P)[16], uint64_t dv, uint64_t pad) {
#pragma unroll
  for (int s = 0; s < 4; s++) wgmma72_acc(O, &P[4 * s], dv + s * 128 * V_STEP + (s < 2 ? 0 : (s - 1) * pad));
}
__device__ __forceinline__ void attn_step(const float (&Sc)[32], float (&Sn)[32], uint32_t (&Pc)[16], uint32_t (&Pp)[16], float (&O)[36],
                                          const uint32_t (&Q)[16], const uint32_t (&nm)[4], uint64_t dk, uint64_t dv) {
  WG_FENCE();
  qk_tile(Sn, Q, dk);
  qk_shift(Sn, nm);
  pv_tile(O, Pp, dv, 0);
  WG_COMMIT();
  SCHED();
#pragma unroll
  for (int i = 0; i < 16; i++) Pc[i] = pack2(ex2_hw(Sc[2 * i]), ex2_hw(Sc[2 * i + 1]));
  pin(Pc);
  SCHED();
}
template <int R> __device__ __forceinline__ float tile_max(const float (&S)[32]) {
  float t[4];
#pragma unroll
  for (int j = 0; j < 4; j++) t[j] = fmaxf(fmaxf(S[8 * j + R], S[8 * j + R + 1]), fmaxf(S[8 * j + R + 4], S[8 * j + R + 5]));
  float n = fmaxf(fmaxf(t[0], t[1]), fmaxf(t[2], t[3]));
  n = fmaxf(n, __shfl_xor_sync(0xffffffffu, n, 1));
  return fmaxf(n, __shfl_xor_sync(0xffffffffu, n, 2));
}
__device__ __forceinline__ void attention_exact(float (&O)[36], const uint32_t (&Q)[16], const Scratch* sc, int bh, int lane) {
  const char* kb = (const char*)&sc->kv[bh][0][0][0];
  const char* vb = (const char*)&sc->kv[bh][1][0][0];
  const int g = lane >> 2, q = lane & 3;
  float m0 = -INFINITY, m1 = -INFINITY, l0 = 0.f, l1 = 0.f;
  float o[8][4] = {};
#pragma unroll 1
  for (int k0 = 0; k0 < T_SEQ; k0 += 8) {
    float s[4] = {0.f, 0.f, 0.f, 0.f};
#pragma unroll
    for (int c = 0; c < 8; c++) hmma8(s, &Q[2 * c], __ldcg((const uint32_t*)(kb + (k0 + g) * 128 + ((c ^ g) << 4) + q * 4)));
    float n0 = fmaxf(s[0], s[1]), n1 = fmaxf(s[2], s[3]);
    n0 = fmaxf(n0, __shfl_xor_sync(0xffffffffu, n0, 1)); n1 = fmaxf(n1, __shfl_xor_sync(0xffffffffu, n1, 1));
    n0 = fmaxf(m0, fmaxf(n0, __shfl_xor_sync(0xffffffffu, n0, 2))); n1 = fmaxf(m1, fmaxf(n1, __shfl_xor_sync(0xffffffffu, n1, 2)));
    const float a0 = ex2_hw(m0 - n0), a1 = ex2_hw(m1 - n1);
    m0 = n0; m1 = n1;
    const uint32_t pp[2] = {pack2(ex2_hw(s[0] - n0), ex2_hw(s[1] - n0)), pack2(ex2_hw(s[2] - n1), ex2_hw(s[3] - n1))};
    l0 = fmaf(l0, a0, bf_lo(pp[0]) + bf_hi(pp[0])); l1 = fmaf(l1, a1, bf_lo(pp[1]) + bf_hi(pp[1]));
#pragma unroll
    for (int j = 0; j < 8; j++) {
      const uint32_t v0 = __ldcg((const uint16_t*)(vb + (k0 + 2 * q) * 128 + ((j ^ (2 * q)) << 4) + g * 2));
      const uint32_t v1 = __ldcg((const uint16_t*)(vb + (k0 + 2 * q + 1) * 128 + ((j ^ (2 * q + 1)) << 4) + g * 2));
      o[j][0] *= a0; o[j][1] *= a0; o[j][2] *= a1; o[j][3] *= a1;
      hmma8(o[j], pp, v0 | (v1 << 16));
    }
  }
  l0 += __shfl_xor_sync(0xffffffffu, l0, 1); l1 += __shfl_xor_sync(0xffffffffu, l1, 1);
  O[32] = l0 + __shfl_xor_sync(0xffffffffu, l0, 2); O[34] = l1 + __shfl_xor_sync(0xffffffffu, l1, 2);
#pragma unroll
  for (int i = 0; i < 32; i++) O[i] = o[i >> 2][i & 3];
}

__device__ __forceinline__ uint32_t fill_entry(int f, int r, int bh) {
  int m, x = r, y, dx = 0;
  if (f < F_QKV || f >= 48) {
    const int i = f & 15;
    m = f < F_QKV ? M_FF1A : M_FF2A;
    if (i < 8) { x = 4 * r + ((0xE2u >> i) & 1) * 2; y = r ^ ((0xE790u >> (2 * i)) & 3); dx = 1; }
    else { m++; x = r ^ (((i >> 1) - 3) & 3); y = 4 * r + 2 * (i & 1); }
  } else if (f < F_KV) {
    const int i = f - F_QKV;
    m = M_QKV;
    if (i == 1 || i >= 5) { y = r ^ (i == 1 ? 0 : 2); }
    else { x = 4 + r; y = r ^ (i ? i - 1 : 0); dx = 4; }
  } else if (f < F_WO) {
    const int i = f - F_KV;
    m = M_KV; x = 0; y = bh * 32 + (i & 2) * 8 + (i >> 2) * 4 + (i & 1) * 2;
  } else if (f >= F_PW1 && f < F_PW2) {
    m = M_PW1; y = r ^ (f - F_PW1); dx = 4;
  } else {
    m = f < F_PW1 ? M_WO : M_PW2; y = r ^ ((f & 1) * 2);
  }
  return m | (x << 4) | (y << 8) | (dx << 16);
}
__device__ __forceinline__ void tma_fill(uint32_t st, const CUtensorMap* map, uint32_t x, uint32_t y, uint32_t x2, uint32_t y2) {
  asm volatile("{\n.reg .pred p;\nelect.sync _|p, 0xffffffff;\n"
               "@p mbarrier.arrive.expect_tx.shared::cta.b64 _, [%1], 16384;\n"
               "@p cp.async.bulk.tensor.2d.shared::cluster.global.mbarrier::complete_tx::bytes [%0], [%2, {%3, %4}], [%1];\n"
               "@p cp.async.bulk.tensor.2d.shared::cluster.global.mbarrier::complete_tx::bytes [%0 + 8192], [%2, {%5, %6}], [%1];\n}"
               :: "r"(SM_BASE + st * STAGE_BYTES), "r"(SM_BASE + SM_FULL + st * 8), "l"(map), "r"(x), "r"(y), "r"(x2), "r"(y2) : "memory");
}
__device__ __forceinline__ void l2_prefetch(const void* p, uint32_t total, int b) {
  const uint32_t part = total / NCTA;
  asm volatile("cp.async.bulk.prefetch.L2.global [%0], %1;" :: "l"((const char*)p + (size_t)b * part), "r"(part) : "memory");
}

__global__ void __launch_bounds__(384, 1) conformer_kernel(Scratch* __restrict__ sc, __nv_bfloat16* __restrict__ out,
                                                           const __nv_bfloat16* __restrict__ dw, const __grid_constant__ Params p) {
  extern __shared__ __align__(1024) uint8_t smem[];
  const int tid = threadIdx.x, lane = tid & 31;
  const int cw = __shfl_sync(0xffffffffu, tid >> 5, 0), wg = cw >> 2, w = cw & 3;
  const int b = blockIdx.x, r = b & 3, batch = b >> 6, t = (b >> 2) & 15;
  if ((uint32_t)__cvta_generic_to_shared(smem) != SM_BASE) return;
  PROF_MARK(0);
  PROF_TIME(30);

  if (cw == 8) {
    if (lane == 0) {
      asm volatile("prefetch.tensormap [%0];" :: "l"(&p.map[M_X]) : "memory");
      asm volatile("prefetch.tensormap [%0];" :: "l"(&p.map[M_FF1A]) : "memory");
      mbar_init(SM_BASE + SM_XBAR, 1);
#pragma unroll
      for (int i = 0; i < NSTAGE; i++) mbar_init(SM_BASE + SM_FULL + i * 8, 1);
      fence_async_smem();
    }
    __syncwarp();
    asm volatile("{\n.reg .pred p;\nelect.sync _|p, 0xffffffff;\n"
                 "@p mbarrier.arrive.expect_tx.shared::cta.b64 _, [%1], 32768;\n"
                 "@p cp.async.bulk.tensor.4d.shared::cluster.global.mbarrier::complete_tx::bytes [%0], [%2, {0, %3, 0, %4}], [%1];\n}"
                 :: "r"(SM_BASE + SM_STG), "r"(SM_BASE + SM_XBAR), "l"(&p.map[M_X]), "r"(t * 64), "r"(batch) : "memory");
    bar_arrive(0, 320);
    PROF_MARK(9);
#pragma unroll 1
    for (int f = 0; f < 8; f++) {
      const uint32_t x = 256 * r + ((0xE2u >> f) & 1) * 128, y = (r ^ ((0xE790u >> (2 * f)) & 3)) * 64;
      tma_fill(f, &p.map[M_FF1A], x, y, x + 64, y);
    }
    PROF_MARK(1);
  } else if (cw == 9) {
    if (lane == 0) {
#pragma unroll
      for (int i = 0; i < NSTAGE; i++) mbar_init(SM_BASE + SM_EMPTY + i * 8, 4);
    }
    __syncwarp();
    bar_arrive(0, 320);
    bar_arrive(BAR_INIT, 64);
  } else if (wg < 2) {
    if (tid < 144) sts128(SM_BASE + SM_CS + tid * 16, 0, 0, 0, 0);
    if (wg == 1) {
      const int i = tid - 128;
      sts32(SM_BASE + SM_EYE + i * 4, i >= 96 ? 0x3F803F80u : ((i & 32) == 0 && (i & 3) == ((i >> 3) & 3)) ? (0x3F00u << ((i & 4) * 4)) : 0u);
    }
    fence_async_smem();
    bar_sync(0, 320);
  }

  if (wg == 2) {
    asm volatile("setmaxnreg.dec.sync.aligned.u32 40;");
    if (cw == 8) {
      const uint32_t* flag = sc->flag[batch * 4 + r][lane];
      const uint32_t prev = ((volatile uint32_t*)sc->epoch)[b];
      uint32_t entry[2], ready = 0, st = 8, parity = 1;
#pragma unroll 1
      for (int i = 0; i < 2; i++) { entry[1] = fill_entry(i * 32 + lane, r, batch * 4 + r); if (i == 0) entry[0] = entry[1]; }
      bar_sync(BAR_INIT, 64);
#pragma unroll 1
      for (int f = 8; f < F_TOTAL; f++) {
        const uint32_t e = __shfl_sync(0xffffffffu, f < 32 ? entry[0] : entry[1], f);
        if ((e & 15) == M_KV) {
          const uint32_t need = 3u << ((e >> 8) & 31);
          uint32_t spin = 0;
#pragma unroll 1
          while ((ready & need) != need && ++spin < SPIN_LIMIT) {
            uint32_t v;
            asm volatile("ld.relaxed.gpu.global.u32 %0, [%1];" : "=r"(v) : "l"(flag) : "memory");
            ready = __ballot_sync(0xffffffffu, v - 1 == prev);
          }
        }
        if (f == F_KV) PROF_MARK(8);
        mbar_wait(SM_BASE + SM_EMPTY + st * 8, parity);
        const uint32_t x = (e << 2) & 0x3C0, y = (e >> 2) & 0x3FC0, dx = (e >> 16) << 6;
        tma_fill(st, &p.map[e & 15], x, y, x + dx, dx ? y : y ^ 64);
        if (++st == NSTAGE) { st = 0; parity ^= 1; }
      }
    } else if (here(cw) != 11) {
      const int kind = w - 1;
      const uint32_t epoch = ((volatile uint32_t*)sc->epoch)[b] + 1;
      if (kind == 0) {
        bar_sync(BAR_K, 160);
      } else {
        uint32_t v, spin = 0;
#pragma unroll 1
        do {
          asm volatile("ld.relaxed.gpu.global.u32 %0, [%1];" : "=r"(v) : "l"(sc->ready[(b & ~3) + (lane & 3)]) : "memory");
        } while (__any_sync(0xffffffffu, v != epoch) && ++spin < SPIN_LIMIT);
        bar_arrive(BAR_RDY, 160);
        bar_arrive(BAR_RDY1, 160);
        bar_sync(BAR_V, 160);
      }
      if (lane == 0) {
        asm volatile("cp.async.bulk.global.shared::cta.bulk_group [%0], [%1], %2;"
                     :: "l"(&sc->kv[batch * 4 + r][kind][t][0]), "r"(SM_BASE + SM_STG + kind * TILE_BYTES), "r"(TILE_BYTES) : "memory");
        asm volatile("cp.async.bulk.commit_group;\ncp.async.bulk.wait_group 0;" ::: "memory");
        asm volatile("st.relaxed.gpu.global.u32 [%0], %1;" :: "l"(sc->flag[batch * 4 + r][kind * 16 + t]), "r"(epoch) : "memory");
      }
    } else {
      const uint32_t epoch = ((volatile uint32_t*)sc->epoch)[b] + 1;
      if (lane == 0) {
        asm volatile("prefetch.tensormap [%0];" :: "l"(&p.map[M_FF1B]) : "memory");
        l2_prefetch(p.w_ff1b, 1024 * 256 * 2, b);
      }
#pragma unroll 1
      for (uint4* dst = &sc->x[b][X_CLEAR + lane]; dst < &sc->x[b][X_ST + 32]; dst += 32) {
        const uint32_t t0 = clock_now();
        st_vec(dst, 0u, 0u, 0u, 0u);
        while (clock_now() - t0 < 24) {}
      }
      asm volatile("fence.acq_rel.gpu;" ::: "memory");
      __syncwarp();
      if (lane == 0) {
        asm volatile("st.relaxed.gpu.global.u32 [%0], %1;" :: "l"(sc->ready[b]), "r"(epoch) : "memory");
        l2_prefetch(p.w_o, 256 * 256 * 2, b);
        l2_prefetch(p.w_pw2, 256 * 256 * 2, b);
        l2_prefetch(p.w_ff2b, 1024 * 256 * 2, b);
#pragma unroll
        for (int i = M_QKV; i < M_X; i++) asm volatile("prefetch.tensormap [%0];" :: "l"(&p.map[i]) : "memory");
      }
    }
  } else {
    asm volatile("setmaxnreg.inc.sync.aligned.u32 232;");
    const int q = lane & 3, th = tid & 127;
    constexpr uint32_t stg = SM_BASE + SM_STG;
    const uint32_t mrow = 16 * w + (lane & 15);
    const uint32_t maddr = stg + mrow * 128 + (((lane >> 4) ^ (lane & 7)) << 4);
    const uint32_t res = stg + 3 * TILE_BYTES + w * 2048 + lane * 16;
    uint4* const xp = &sc->x[b][th];
    const int nvalid = T_SEQ - t * 64, row0 = 16 * w + (lane >> 2);

    uint32_t A[4][16];
    uint32_t sent = 0;
    mbar_wait(SM_BASE + SM_XBAR, 0);
    PROF_MARK(1);
#pragma unroll
    for (int c = 0; c < 4; c++) tile_load(maddr + (r ^ c) * TILE_BYTES, A[c]);
    if (wg == 0) {
      float sa[4] = {0.f, 0.f, 0.f, 0.f}, sb[4] = {0.f, 0.f, 0.f, 0.f};
#pragma unroll
      for (int i = 0; i < 16; i++) hmma((i & 1) ? sb : sa, &A[i >> 2][4 * (i & 3)], 0x3F803F80u, 0x3F803F80u);
      bar_arrive(BAR_X, 256);
      const float s0 = (sa[0] + sb[0]) * (1.f / DM), s1 = (sa[2] + sb[2]) * (1.f / DM);
      const uint32_t m0 = pack2(s0, s0), m1 = pack2(s1, s1);
#pragma unroll
      for (int c = 0; c < 4; c++) {
#pragma unroll
        for (int i = 0; i < 16; i++) asm("sub.rn.bf16x2 %0, %0, %1;" : "+r"(A[c][i]) : "r"((i & 1) ? m1 : m0));
        pin(A[c]);
      }
    } else {
      const uint32_t epoch = ((volatile uint32_t*)sc->epoch)[b] + 1, tag = epoch & 1;
      {
        RowAcc ra[2] = {};
#pragma unroll
        for (int c = 0; c < 4; c++) row_acc(ra[c & 1], A[c]);
        const float2 qa = row_squares(ra[0], lane & 4), qb = row_squares(ra[1], lane & 4);
        const int src = (lane & 28) | (lane >> 3);
        const float q0 = __shfl_sync(0xffffffffu, qa.x + qb.x, src), q1 = __shfl_sync(0xffffffffu, qa.y + qb.y, src);
        bar_sync(BAR_X, 256);
        res_store(res, A[0]);
        norm_produce(row_norm(ra[0].s[0] + ra[1].s[0], q0, ra[0].s[2] + ra[1].s[2], q1, 0.5f), th, 4);
      }
      PROF_MARK(5);
      SCHED();
      uint4 cv[8];
      if (b < 72) {
        const __nv_bfloat16* wp; int ld, col;
        if (b < 24) { wp = p.w_qkv; ld = 768; col = b * 32; }
        else if (b < 40) { wp = p.w_pw1; ld = 512; col = (b - 24) * 32; }
        else { wp = p.w_ff2a; ld = 1024; col = (b - 40) * 32; }
        const uint4* src = (const uint4*)(wp + (size_t)(th >> 2) * ld + col + q * 8);
#pragma unroll
        for (int i = 0; i < 8; i++) cv[i] = __ldg(src + i * 4 * ld);
      }
      if (b < 72) {
        float c[8] = {0.f, 0.f, 0.f, 0.f, 0.f, 0.f, 0.f, 0.f};
#pragma unroll
        for (int i = 0; i < 8; i++) {
          const uint4 v = cv[i];
          c[0] += bf_lo(v.x); c[1] += bf_hi(v.x); c[2] += bf_lo(v.y); c[3] += bf_hi(v.y);
          c[4] += bf_lo(v.z); c[5] += bf_hi(v.z); c[6] += bf_lo(v.w); c[7] += bf_hi(v.w);
        }
#pragma unroll 1
        for (int m = 4; m <= 16; m <<= 1)
#pragma unroll
          for (int k = 0; k < 8; k++) c[k] += __shfl_xor_sync(0xffffffffu, c[k], m);
        if (lane < 4) {
          const uint32_t a = SM_BASE + SM_CS + 1792 + w * 128 + lane * 32;
          sts128(a, __float_as_uint(c[0]), __float_as_uint(c[1]), __float_as_uint(c[2]), __float_as_uint(c[3]));
          sts128(a + 16, __float_as_uint(c[4]), __float_as_uint(c[5]), __float_as_uint(c[6]), __float_as_uint(c[7]));
        }
        bar_sync(BAR_WG1, 128);
        if (th < 8) {
          float o[4] = {0.f, 0.f, 0.f, 0.f};
#pragma unroll 1
          for (int k = 0; k < 4; k++) {
            uint32_t e[4];
            lds128(SM_BASE + SM_CS + 1792 + k * 128 + th * 16, e[0], e[1], e[2], e[3]);
#pragma unroll
            for (int i = 0; i < 4; i++) o[i] += __uint_as_float(e[i]);
          }
          st_vec(&sc->cs[b * 8 + th], (__float_as_uint(o[0]) & ~1u) | tag, __float_as_uint(o[1]), __float_as_uint(o[2]), __float_as_uint(o[3]));
        }
      }
      bar_sync(BAR_WG1, 128);
      PROF_MARK(2);
#pragma unroll 1
      for (int i = th; i < 144; i += 128) {
        const int j = i >> 4;
        int src;
        if (j < CS_PW1) src = 320 + 64 * r + i;
        else if (j < CS_QKV) src = 192 + (j - CS_PW1) * 64 + 16 * r + (i & 15);
        else src = ((j - CS_QKV + 1) % 3) * 64 + 16 * r + (i & 15);
        uint32_t e[4], spin = 0;
#pragma unroll 1
        do {
          ld_vec(&sc->cs[src], e[0], e[1], e[2], e[3]);
        } while (((e[0] ^ tag) & 1u) && ++spin < SPIN_LIMIT);
        const float c0 = __uint_as_float(e[0] & ~1u), c1 = __uint_as_float(e[1]), c2 = __uint_as_float(e[2]), c3 = __uint_as_float(e[3]);
        const uint32_t h0 = pack2(c0, c1), h1 = pack2(c2, c3);
        const uint32_t a = SM_BASE + SM_CS + j * 256 + (i & 15) * 8;
        sts64(a ^ ((a >> 3) & 0x70), h0, h1);
        sts64((a + 128) ^ (((a + 128) >> 3) & 0x70), pack2(c0 - bf_lo(h0), c1 - bf_hi(h0)), pack2(c2 - bf_lo(h1), c3 - bf_hi(h1)));
      }
      fence_async_smem();
      PROF_MARK(4);
      bar_sync(BAR_RDY1, 160);
      norm_duty(sc, th, 1, 1.f, 3);
    }

#pragma unroll 1
    for (uint32_t pass = 0; pass < 2; pass++) {
      uint32_t Q[16];
      if (wg == 0) {
        float acc[4][32];
        uint32_t H[4][16];
        if (!pass) ACQUIRE(0);
        mma_tile<true>(acc[0], A[0], LO(0)); mma_tile<true>(acc[1], A[0], HI(0));
        if (!pass) ACQUIRE(1);
        mma_tile<true>(acc[2], A[0], LO(1)); mma_tile<true>(acc[3], A[0], HI(1));
        if (pass) gather_first<1, X_AG0>(A, xp, 1, sent); else acquire_n<2, 3>();
        mma_tile<false>(acc[0], A[1], LO(2)); mma_tile<false>(acc[1], A[1], HI(2));
        if (pass) { gather_rest<1, X_AG0>(A, xp, 1); RELEASE(F_PW2, F_PW2 + 1); }
        PROF_MARK(2 + pass * 16);
        mma_tile<false>(acc[0], A[2], LO(3));
        WG_WAIT(3);
        uint32_t mu[4];
        float rs0, rs1, tn[2][4];
        norm_consume(here(th), mu, rs0, rs1);
        mma_tile_fold<2 * CS_FF2>(acc[0], A[3], LO(4), mu);
        RELEASE(0, 1);
        acquire_n<5, 3>();
        mma_tile<false>(acc[1], A[2], HI(3));
#define SEGS(a, b) silu_segs<a, b>(acc, tn, H, rs0, rs1)
        WG_WAIT(1); pin(acc[0]);
        SEGS(0, 1);
        mma_tile_fold<2 * CS_FF2 + 2>(acc[1], A[3], HI(4), mu);
        SEGS(1, 4);
        mma_tile<false>(acc[2], A[1], LO(5));
        SEGS(4, 6);
        mma_tile<false>(acc[2], A[2], LO(6));
        SEGS(6, 8);
        WG_WAIT(2); pin(acc[1]);
        RELEASE(2, 4);
        SEGS(8, 9);
        mma_tile_fold<2 * CS_FF2 + 4>(acc[2], A[3], LO(7), mu);
        SEGS(9, 12);
        mma_tile<false>(acc[3], A[1], HI(5));
        acquire_n<8, 2>();
        SEGS(12, 14);
        mma_tile<false>(acc[3], A[2], HI(6));
        SEGS(14, 16);
        WG_WAIT(2); pin(acc[2]);
        SEGS(16, 17);
        mma_tile_fold<2 * CS_FF2 + 6>(acc[3], A[3], HI(7), mu);
        SEGS(17, 20);
        mma_tile_reuse(acc[1], H[0], LO(8));
        acquire_n<10, 2>();
        SEGS(20, 22);
        mma_tile<false>(acc[1], H[1], HI(8));
        SEGS(22, 24);
        WG_WAIT(2); pin(acc[3]);
        RELEASE(5, 7);
        SEGS(24, 26);
        mma_tile<false>(acc[1], H[2], LO(9));
        SEGS(26, 28);
        mma_tile_reuse(acc[2], H[0], LO(10));
        SEGS(28, 31);
        mma_tile<false>(acc[2], H[1], HI(10));
        SEGS(31, 34);
#undef SEGS
        PROF_MARK(3 + pass * 16);
        const uint32_t rtag = here(pass ^ 1);
        const uint4* rs_in = xp + X_RS;
        mma_tile<false>(acc[1], H[3], HI(9));
        mma_tile<false>(acc[2], H[2], LO(11));
        acquire_n<12, 2>();
        uint4* rs_out = peer<1>(xp) + X_RS;
        mma_tile<false>(acc[2], H[3], HI(11));
        WG_WAIT(2); pin(acc[1]);
        send_half<0>(rs_out, acc[1], rtag);
        mma_tile_reuse(acc[3], H[0], LO(12));
        SCHED();
        send_half<1>(rs_out, acc[1], rtag);
        mma_tile<false>(acc[3], H[1], HI(12));
        rs_out = peer<2>(xp) + X_RS + 512;
        WG_WAIT(2); pin(acc[2]);
        send_half<0>(rs_out, acc[2], rtag);
        mma_tile<false>(acc[3], H[2], LO(13));
        SCHED();
        send_half<1>(rs_out, acc[2], rtag);
        mma_tile<false>(acc[3], H[3], HI(13));
        RELEASE(8, 11);
        acquire_n<14, 2>();
        mma_tile_reuse(acc[1], H[0], LO(14));
        rs_out = peer<3>(xp) + X_RS + 1024;
        if (!pass) bar_sync(BAR_RDY, 160);
        fetch(rs_in, A[1]);
        SCHED();
        mma_tile<false>(acc[1], H[1], HI(14));
        WG_WAIT(2); pin(acc[3]);
        send_half<0>(rs_out, acc[3], rtag);
        send_half<1>(rs_out, acc[3], rtag);
        mma_tile<false>(acc[1], H[2], LO(15)); mma_tile<false>(acc[1], H[3], HI(15));
        SCHED();
        res_load(res, acc[2]);
        if (!pass) acquire_n<F_QKV, 6>();
        confirm(rs_in, A[1], rtag);
        mma_add_half(acc[2], A[1]);
        PROF_MARK(44);
        fetch(rs_in + 512, A[2]);
        fetch(rs_in + 1024, A[3]);
        confirm(rs_in + 512, A[2], rtag);
        mma_add_half(acc[2], A[2]);
        SCHED();
        confirm(rs_in + 1024, A[3], rtag);
        mma_add_half(acc[2], A[3]);
        PROF_MARK(4 + pass * 16);
        WG_WAIT(0); pin(acc[2]); pin(acc[1]);
#pragma unroll
        for (int i = 0; i < 16; i++) A[0][i] = pack2(fmaf(acc[1][2 * i], 0.5f, acc[2][2 * i]), fmaf(acc[1][2 * i + 1], 0.5f, acc[2][2 * i + 1]));
        if (pass) {
          PROF_MARK(21);
          stat_publish(A[0], sc, here(th), 0);
          const RowNorm fn = stat_gather(sc, here(th), 0, 1.f);
          const float nm0 = -fn.m0 * fn.rs0, nm1 = -fn.m1 * fn.rs1;
#pragma unroll
          for (int i = 0; i < 16; i++) {
            const float rs = (i & 1) ? fn.rs1 : fn.rs0, nm = (i & 1) ? nm1 : nm0;
            A[0][i] = pack2(fmaf(bf_lo(A[0][i]), rs, nm), fmaf(bf_hi(A[0][i]), rs, nm));
          }
          tile_store(here(maddr), A[0]);
          __syncwarp();
          const int row = 16 * w + (lane >> 3);
          uint4* dst = (uint4*)(out + ((size_t)batch * T_SEQ + t * 64 + row) * DM + 64 * r) + (lane & 7);
          const uint32_t src = stg + row * 128 + (((lane & 7) ^ (lane >> 3)) << 4);
#pragma unroll
          for (int i = 0; i < 4; i++) {
            uint4 v;
            lds128((src ^ ((i & 1) << 6)) + i * 512, v.x, v.y, v.z, v.w);
            if (row + 4 * i < nvalid) dst[i * 4 * (DM / 8)] = v;
          }
          PROF_MARK(22);
          PROF_TIME(31);
          break;
        }
        sent = send_residual(A[0], sc, xp, res, 1);
        PROF_MARK(5);
        mma_tile<true>(acc[0], A[0], LO(F_QKV)); mma_tile<true>(acc[1], A[0], HI(F_QKV));
        mma_tile<true>(acc[2], A[0], LO(F_QKV + 1));
        gather_first<1, X_AG0>(A, xp, 1, sent);
        mma_tile<false>(acc[0], A[1], LO(F_QKV + 2)); mma_tile<false>(acc[1], A[1], HI(F_QKV + 2));
        gather_rest<1, X_AG0>(A, xp, 1);
        PROF_MARK(6);
        mma_tile<false>(acc[0], A[2], LO(F_QKV + 3));
        norm_consume(here(th), mu, rs0, rs1);
        if (row0 >= nvalid) rs0 = 0.f;
        if (row0 + 8 >= nvalid) rs1 = 0.f;
        mma_tile_fold<2 * CS_QKV - 6>(acc[0], A[3], LO(F_QKV + 4), mu);
        RELEASE(12, 15);
        mma_tile<false>(acc[1], A[2], HI(F_QKV + 3));
        mma_tile_fold<2 * CS_QKV - 4>(acc[1], A[3], HI(F_QKV + 4), mu);
        WG_WAIT(2); pin(acc[0]);
        scale_pack(acc[0], Q, rs0, rs1);
        tile_store(here(maddr), Q);
        fence_async_smem();
        bar_arrive(BAR_K, 160);
        mma_tile<false>(acc[2], A[1], HI(F_QKV + 1)); mma_tile<false>(acc[2], A[2], LO(F_QKV + 5));
        WG_WAIT(2); pin(acc[1]);
        scale_pack(acc[1], Q, rs0, rs1);
        tile_store(here(maddr) + TILE_BYTES, Q);
        fence_async_smem();
        bar_arrive(BAR_V, 160);
        mma_tile_fold<2 * CS_QKV - 2>(acc[2], A[3], HI(F_QKV + 5), mu);
        WG_WAIT(0); pin(acc[2]);
        scale_pack(acc[2], Q, rs0 * SM_SCALE_LOG2, rs1 * SM_SCALE_LOG2);
        res_store(here(res) - TILE_BYTES, Q);
        bar_arrive(BAR_Q, 256);
        acquire_n<F_SPARE, 2>();
        RELEASE(F_QKV, F_SPARE + 1);
      } else {
        bar_sync(BAR_Q, 256);
#pragma unroll
        for (int s = 0; s < 4; s++) lds128(res - TILE_BYTES + s * 512, Q[4 * s], Q[4 * s + 1], Q[4 * s + 2], Q[4 * s + 3]);
        if (w < 2) {
          const uint32_t v = w ? 0u : 0x3F803F80u;
#pragma unroll
          for (int s = 0; s < 4; s++) sts128(res - TILE_BYTES + s * 512, v, v, v, v);
          fence_async_smem();
        }
      }
      bar_sync(BAR_ATT, 256);
      PROF_MARK(7);

      const int dir = cw == 0 ? -1 : 1;
      uint32_t tap[15];
      {
        const uint32_t* dwp = (const uint32_t*)(dw + 64 * r) + lane + 7 * (DM / 2);
#pragma unroll
        for (int k = 0; k < 15; k++) tap[k] = __ldg(dwp + dir * (k - 7) * (DM / 2));
      }

      float O[36];
      {
        float S[2][32];
        uint32_t P[2][16], nm[4];
        pin(Q);
        WG_FENCE();
        qk_tile(S[0], Q, RING + (SM_STG >> 4));
        WG_COMMIT();
#pragma unroll
        for (int i = 0; i < 36; i++) O[i] = 0.f;
#pragma unroll
        for (int i = 0; i < 16; i++) P[1][i] = 0u;
        WG_WAIT(0); pin(S[0]);
        const float m0 = tile_max<0>(S[0]), m1 = tile_max<2>(S[0]);
        nm[0] = pack2(q ? 0.f : -m0, 0.f); nm[1] = pack2(q ? 0.f : -m1, 0.f); nm[2] = 0u; nm[3] = 0u;
#pragma unroll
        for (int k = 0; k < 15; k++) asm("mul.rn.bf16x2 %0, %0, %1;" : "+r"(tap[k]) : "r"(0x3F003F00u));
        pin(nm); pin(O); pin(P[1]); pin(tap);
        uint32_t sk = wg, sv = wg;
        mbar_wait(SM_BASE + SM_FULL + sk * 8, 0);
        PROF_MARK(8);
        WG_FENCE();
        qk_tile(S[0], Q, RING + sk * 1024);
        qk_shift(S[0], nm);
        WG_COMMIT();
        WG_WAIT(0); pin(S[0]);
#pragma unroll 1
        for (int it = 0; it < 4; it++) {
          attn_step(S[0], S[1], P[0], P[1], O, Q, nm, RING + sk * 1024 + 512, RING_V + (sv * 1024 + 512) * V_STEP);
          const uint32_t sn = it == 2 ? wg : sk + (it == 3 ? 2 : 4);
          mbar_wait(SM_BASE + SM_FULL + sn * 8, it >= 2);
          mbar_wait(SM_BASE + SM_FULL + (sk + 2) * 8, it == 3);
          WG_WAIT(0); pin(O); pin(S[1]); pin(P[1]);
          if (lane == 0) {
            mbar_arrive(SM_BASE + SM_EMPTY + sk * 8);
            if (it) mbar_arrive(SM_BASE + SM_EMPTY + sv * 8);
          }
          sv = sk + 2; sk = sn;
          attn_step(S[1], S[0], P[1], P[0], O, Q, nm, RING + sk * 1024, RING_V + (sv * 1024) * V_STEP);
          WG_WAIT(0); pin(O); pin(S[0]); pin(P[0]);
        }
        WG_FENCE();
        pv_tile(O, P[1], RING_V + (sv * 1024 + 512) * V_STEP, (uint64_t)wg << 22);
        WG_COMMIT();
        WG_WAIT(0); pin(O);
      }
      PROF_MARK(9);

      if (wg == 1) {
        const uint32_t mo = stg + here(th) * 16;
#pragma unroll
        for (int i = 0; i < 9; i++)
          sts128(mo + i * 2048 + (i >> 3) * 4096, __float_as_uint(O[4 * i]), __float_as_uint(O[4 * i + 1]), __float_as_uint(O[4 * i + 2]), __float_as_uint(O[4 * i + 3]));
        bar_arrive(BAR_MERGE, 256);
        norm_duty(sc, here(th), 0, 0.5f, 0);
      } else {
        const uint32_t mo = stg + here(th) * 16;
        bar_sync(BAR_MERGE, 256);
#pragma unroll
        for (int i = 8; i >= 0; i--) {
          uint32_t e[4];
          lds128(mo + i * 2048 + (i >> 3) * 4096, e[0], e[1], e[2], e[3]);
#pragma unroll
          for (int k = 0; k < 4; k++) O[4 * i + k] += __uint_as_float(e[k]);
        }
        const bool safe = O[32] > 0x1p-60f && O[32] < 0x1p60f && O[34] > 0x1p-60f && O[34] < 0x1p60f;
        if (__builtin_expect(__any_sync(0xffffffffu, !safe), 0)) attention_exact(O, Q, sc, batch * 4 + r, lane);
        const float i0 = rcp_hw(O[32]), i1 = rcp_hw(O[34]);
#pragma unroll
        for (int i = 0; i < 16; i++) { const float v = (i & 1) ? i1 : i0; A[0][i] = pack2(O[2 * i] * v, O[2 * i + 1] * v); }
        PROF_MARK(10);
        sent = proj_residual<F_WO, 6>(A, sc, xp, res, 0);
        PROF_MARK(12);
        float acc[2][32];
        mma_tile<true>(acc[0], A[0], LO(F_PW1)); mma_tile<true>(acc[1], A[0], HI(F_PW1));
        gather_first<1, X_AG0>(A, xp, 0, sent);
        mma_tile<false>(acc[1], A[1], HI(F_PW1 + 1)); mma_tile<false>(acc[0], A[1], LO(F_PW1 + 1));
        gather_rest<1, X_AG0>(A, xp, 0);
        PROF_MARK(13);
        mma_tile<false>(acc[1], A[2], HI(F_PW1 + 2));
        uint32_t mu[4];
        float rs0, rs1;
        norm_consume(here(th), mu, rs0, rs1);
        if (row0 >= nvalid) rs0 = 0.f;
        if (row0 + 8 >= nvalid) rs1 = 0.f;
        mma_tile_fold<2 * CS_PW1 + 2>(acc[1], A[3], HI(F_PW1 + 3), mu);
        RELEASE(F_KV + 14, F_WO + 1);
        mma_tile<false>(acc[0], A[2], LO(F_PW1 + 2));
        mma_tile_fold<2 * CS_PW1>(acc[0], A[3], LO(F_PW1 + 3), mu);
        WG_WAIT(2); pin(acc[1]);
#pragma unroll
        for (int i = 0; i < 32; i++) acc[1][i] = tanh_hw(acc[1][i] * ((i & 2) ? rs1 : rs0));
#pragma unroll
        for (int i = 0; i < 32; i++) { const float rs = (i & 2) ? rs1 : rs0; acc[1][i] = fmaf(acc[1][i], rs, rs); }
        pin(acc[1]);
        SCHED();
        WG_WAIT(0); pin(acc[0]);
#pragma unroll
        for (int i = 0; i < 16; i++) A[0][i] = pack2(acc[0][2 * i] * acc[1][2 * i], acc[0][2 * i + 1] * acc[1][2 * i + 1]);
        const uint32_t ga = stg + TILE_BYTES + here(mrow) * G_PITCH + (lane >> 4) * 16;
#pragma unroll
        for (int s = 0; s < 4; s++) stsm4(ga + s * 32, &A[0][4 * s]);
        RELEASE(F_PW1, F_PW1 + 3);
      }
      bar_sync(BAR_G, 256);
      PROF_MARK(14);

      {
        const int first = cw == 0 ? 14 : 8 * cw - 7;
        const uint32_t gsrc = stg + TILE_BYTES + first * G_PITCH + lane * 4;
        uint32_t in[22];
#pragma unroll
        for (int i = 0; i < 15; i++) in[i] = lds32(gsrc + dir * i * (int)G_PITCH);
        const bool edge = cw == 0 || cw == 7;
        const bool nbr = cw == 0 ? t > 0 : t < 15;
        if (edge) {
          if (nbr) {
            uint4* dst = &sc->x[b + 4 * dir][X_HALO + (cw == 0 ? 96 : 0) + lane];
            st_vec(dst, HALO_TAG, in[14], in[13], in[12]);
            st_vec(dst + 32, HALO_TAG, in[11], in[10], in[9]);
            st_vec(dst + 64, HALO_TAG, in[8], 0u, 0u);
          }
        } else {
#pragma unroll
          for (int i = 15; i < 22; i++) in[i] = lds32(gsrc + i * G_PITCH);
        }
        uint32_t cv[8];
#pragma unroll
        for (int i = 0; i < 15; i++)
#pragma unroll
          for (int o = 0; o < 8; o++) {
            if (i == o) asm("mul.rn.bf16x2 %0, %1, %2;" : "=r"(cv[o]) : "r"(in[i]), "r"(tap[0]));
            if (i > o) asm("fma.rn.bf16x2 %0, %1, %2, %0;" : "+r"(cv[o]) : "r"(in[i]), "r"(tap[i - o]));
          }
        pin(cv);
        PROF_MARK(45);
        if (edge) {
#pragma unroll
          for (int i = 15; i < 22; i++) in[i] = 0u;
          if (nbr) {
            const uint4* src = &sc->x[b][X_HALO + (cw == 0 ? 0 : 96) + lane];
            uint32_t e0, e1, e2, u0, u1, spin = 0;
#pragma unroll 1
            do {
              ld_vec(src, e0, in[15], in[16], in[17]);
              ld_vec(src + 32, e1, in[18], in[19], in[20]);
              ld_vec(src + 64, e2, in[21], u0, u1);
            } while (__any_sync(0xffffffffu, ((e0 ^ HALO_TAG) | (e1 ^ HALO_TAG) | (e2 ^ HALO_TAG)) != 0) && ++spin < SPIN_LIMIT);
          }
        }
#pragma unroll
        for (int i = 15; i < 22; i++)
#pragma unroll
          for (int o = 0; o < 8; o++)
            if (i - o <= 14) asm("fma.rn.bf16x2 %0, %1, %2, %0;" : "+r"(cv[o]) : "r"(in[i]), "r"(tap[i - o]));
        PROF_MARK(46);
        const uint32_t fl = cw == 0 ? 7 : 0;
        const uint32_t cdst = (stg + cw * 1024 + lane * 4) ^ (fl * 144);
#pragma unroll
        for (int o = 0; o < 8; o++) {
          const float a = bf_lo(cv[o]), c = bf_hi(cv[o]);
          sts32(cdst ^ (o * 144), pack2(fmaf(a, tanh_hw(a), a), fmaf(c, tanh_hw(c), c)));
        }
      }
      if (wg == 1) {
        bar_arrive(BAR_C, 256);
        norm_duty(sc, here(th), 1, 0.5f, 0);
        if (th == 0) ((volatile uint32_t*)sc->epoch)[b] += 1;
        break;
      }
      bar_sync(BAR_C, 256);
      tile_load(here(maddr), A[0]);
      PROF_MARK(15);
      sent = proj_residual<F_PW2, 2>(A, sc, xp, res, 1);
      PROF_MARK(17);
    }
  }
}

typedef CUresult (*EncodeFn)(CUtensorMap*, CUtensorMapDataType, cuuint32_t, void*, const cuuint64_t*, const cuuint64_t*,
                             const cuuint32_t*, const cuuint32_t*, CUtensorMapInterleave, CUtensorMapSwizzle,
                             CUtensorMapL2promotion, CUtensorMapFloatOOBfill);

void make_map(EncodeFn fn, CUtensorMap* m, const void* w, int rows, int cols, CUtensorMapSwizzle swz) {
  const cuuint64_t dims[2] = {(cuuint64_t)cols, (cuuint64_t)rows}, strides[1] = {(cuuint64_t)cols * 2};
  const cuuint32_t box[2] = {64, 64}, es[2] = {1, 1};
  fn(m, CU_TENSOR_MAP_DATA_TYPE_BFLOAT16, 2, const_cast<void*>(w), dims, strides, box, es, CU_TENSOR_MAP_INTERLEAVE_NONE,
     swz, CU_TENSOR_MAP_L2_PROMOTION_L2_128B, CU_TENSOR_MAP_FLOAT_OOB_FILL_NONE);
}

}

extern "C" void kernel_launch(void* const* d_in, const int* in_sizes, int n_in, void* d_out, int out_size) {
  static EncodeFn fn = nullptr;
  static Scratch* sc = nullptr;
  if (!fn) {
    void* f = nullptr;
    cudaDriverEntryPointQueryResult st;
    cudaGetDriverEntryPoint("cuTensorMapEncodeTiled", &f, cudaEnableDefault, &st);
    fn = (EncodeFn)f;
    void* raw = nullptr;
    cudaGetSymbolAddress(&raw, g_scratch);
    sc = (Scratch*)(((uintptr_t)raw + X_ALIGN - 1) & ~(uintptr_t)(X_ALIGN - 1));
    cudaFuncSetAttribute(conformer_kernel, cudaFuncAttributeMaxDynamicSharedMemorySize, SM_TOTAL);
  }
  typedef const __nv_bfloat16* W;
  const CUtensorMapSwizzle S = CU_TENSOR_MAP_SWIZZLE_128B;
  Params p;
  {
    const cuuint64_t dims[4] = {64, T_SEQ, 4, 2}, strides[3] = {512, 128, T_SEQ * 512};
    const cuuint32_t box[4] = {64, 64, 4, 1}, es[4] = {1, 1, 1, 1};
    fn(&p.map[M_X], CU_TENSOR_MAP_DATA_TYPE_BFLOAT16, 4, d_in[0], dims, strides, box, es, CU_TENSOR_MAP_INTERLEAVE_NONE, S,
       CU_TENSOR_MAP_L2_PROMOTION_L2_128B, CU_TENSOR_MAP_FLOAT_OOB_FILL_NONE);
  }
  make_map(fn, &p.map[M_FF1A], d_in[1], 256, 1024, S);
  make_map(fn, &p.map[M_FF1B], d_in[2], 1024, 256, S);
  make_map(fn, &p.map[M_QKV], d_in[3], 256, 768, S);
  make_map(fn, &p.map[M_KV], sc->kv, 16384, 64, CU_TENSOR_MAP_SWIZZLE_NONE);
  make_map(fn, &p.map[M_WO], d_in[4], 256, 256, S);
  make_map(fn, &p.map[M_PW1], d_in[5], 256, 512, S);
  make_map(fn, &p.map[M_PW2], d_in[7], 256, 256, S);
  make_map(fn, &p.map[M_FF2A], d_in[8], 256, 1024, S);
  make_map(fn, &p.map[M_FF2B], d_in[9], 1024, 256, S);
  p.w_ff1b = (W)d_in[2]; p.w_qkv = (W)d_in[3]; p.w_o = (W)d_in[4]; p.w_pw1 = (W)d_in[5];
  p.w_pw2 = (W)d_in[7]; p.w_ff2a = (W)d_in[8]; p.w_ff2b = (W)d_in[9];

  cudaLaunchConfig_t cfg = {};
  cfg.gridDim = dim3(NCTA);
  cfg.blockDim = dim3(384);
  cfg.dynamicSmemBytes = SM_TOTAL;
  cfg.stream = cudaStreamPerThread;
  cudaLaunchAttribute at[1];
  at[0].id = cudaLaunchAttributeCooperative;
  at[0].val.cooperative = 1;
  cfg.attrs = at;
  cfg.numAttrs = 1;
  cudaLaunchKernelEx(&cfg, conformer_kernel, sc, (__nv_bfloat16*)d_out, (W)d_in[6], p);
}
```

```cpp
#include <cuda_runtime.h>
#include <cuda_bf16.h>
#include <cuda.h>
#include <stdint.h>

namespace {

constexpr int T_SEQ = 1000;
constexpr int DM = 256;
constexpr int NCTA = 128;
constexpr int NSTAGE = 12;
constexpr uint32_t STAGE_BYTES = 16384;
constexpr uint32_t TILE_BYTES = 8192;
constexpr uint32_t SM_BASE = 1024;
constexpr uint32_t SM_STG = NSTAGE * STAGE_BYTES;
constexpr uint32_t SM_FULL = SM_STG + 32768;
constexpr uint32_t SM_EMPTY = SM_FULL + 96;
constexpr uint32_t SM_XBAR = SM_FULL + 192;
constexpr uint32_t SM_EYE = SM_FULL + 256;
constexpr uint32_t SM_ONE = SM_FULL + 640;
constexpr uint32_t SM_CS = SM_FULL + 768;
constexpr uint32_t SM_TOTAL = SM_FULL + 3072;
constexpr int CS_FF2 = 0, CS_PW1 = 4, CS_QKV = 6;
constexpr uint32_t SPIN_LIMIT = 1u << 16;
constexpr float LN_EPS = 1e-5f;
constexpr float SM_SCALE_LOG2 = 0.125f * 1.4426950408889634f;
constexpr uint32_t G_PITCH = 144;

constexpr int F_QKV = 16, F_SPARE = 22, F_KV = 24, F_WO = 40, F_PW1 = 42, F_PW2 = 46, F_TOTAL = 64;
enum { M_FF1A, M_FF1B, M_QKV, M_KV, M_WO, M_PW1, M_PW2, M_FF2A, M_FF2B, M_X, M_COUNT };
enum { BAR_K = 1, BAR_V, BAR_Q, BAR_MERGE, BAR_G, BAR_C, BAR_WG1, BAR_RDY, BAR_ST, BAR_ATT, BAR_INIT, BAR_RDY1, BAR_X, BAR_RES };

struct Params {
  CUtensorMap map[M_COUNT];
  const __nv_bfloat16 *w_ff1b, *w_qkv, *w_o, *w_pw1, *w_pw2, *w_ff2a, *w_ff2b;
};

constexpr int X_RS = 0, X_AG1 = X_RS, X_HALO = X_RS + 512, X_CLEAR = 1024, X_AG0 = 1536, X_ST = 2048, X_SIZE = 4096;
constexpr uint32_t HALO_TAG = 0xFFFF0001u;
struct Scratch {
  uint4 x[NCTA][X_SIZE];
  uint4 kv[8][2][16][512];
  uint4 cs[576];
  uint32_t flag[8][32][32];
  uint32_t ready[NCTA][32];
  uint32_t epoch[NCTA];
};
constexpr size_t X_ALIGN = 4 * X_SIZE * sizeof(uint4);
__device__ uint8_t g_scratch[sizeof(Scratch) + X_ALIGN];
#define PROF_TIME(i)
#define PROF_MARK(i)

__device__ __forceinline__ void mbar_init(uint32_t bar, uint32_t cnt) {
  asm volatile("mbarrier.init.shared::cta.b64 [%0], %1;" :: "r"(bar), "r"(cnt) : "memory");
}
__device__ __forceinline__ void mbar_wait(uint32_t bar, uint32_t parity) {
  asm volatile("{\n.reg .pred p;\n.reg .u32 c;\nmov.u32 c, 0;\n"
               "WAIT_LOOP:\nmbarrier.try_wait.parity.shared::cta.b64 p, [%0], %1;\n@p bra WAIT_DONE;\n"
               "add.u32 c, c, 1;\nsetp.lt.u32 p, c, %2;\n@p bra WAIT_LOOP;\nWAIT_DONE:\n}"
               :: "r"(bar), "r"(parity), "n"(SPIN_LIMIT) : "memory");
}
__device__ __forceinline__ void mbar_arrive(uint32_t bar) {
  asm volatile("mbarrier.arrive.shared::cta.b64 _, [%0];" :: "r"(bar) : "memory");
}
#define bar_sync(id, n) asm volatile("bar.sync %0, %1;" :: "n"((int)(id)), "n"(n) : "memory")
#define bar_arrive(id, n) asm volatile("bar.arrive %0, %1;" :: "n"((int)(id)), "n"(n) : "memory")
__device__ __forceinline__ void fence_async_smem() { asm volatile("fence.proxy.async.shared::cta;" ::: "memory"); }

__device__ __forceinline__ void st_vec(uint4* p, uint32_t a, uint32_t b, uint32_t c, uint32_t d) {
  asm volatile("{\n.reg .b128 v;\n.reg .b64 lo, hi;\nmov.b64 lo, {%1, %2};\nmov.b64 hi, {%3, %4};\nmov.b128 v, {lo, hi};\n"
               "st.relaxed.gpu.global.b128 [%0], v;\n}" :: "l"(p), "r"(a), "r"(b), "r"(c), "r"(d) : "memory");
}
__device__ __forceinline__ void ld_vec(const uint4* p, uint32_t& a, uint32_t& b, uint32_t& c, uint32_t& d) {
  asm volatile("{\n.reg .b128 v;\n.reg .b64 lo, hi;\nld.relaxed.gpu.global.b128 v, [%4];\nmov.b128 {lo, hi}, v;\n"
               "mov.b64 {%0, %1}, lo;\nmov.b64 {%2, %3}, hi;\n}" : "=r"(a), "=r"(b), "=r"(c), "=r"(d) : "l"(p) : "memory");
}
__device__ __forceinline__ void sts128(uint32_t a, uint32_t x, uint32_t y, uint32_t z, uint32_t w) {
  asm volatile("st.shared.v4.u32 [%0], {%1, %2, %3, %4};" :: "r"(a), "r"(x), "r"(y), "r"(z), "r"(w) : "memory");
}
__device__ __forceinline__ void lds128(uint32_t a, uint32_t& x, uint32_t& y, uint32_t& z, uint32_t& w) {
  asm volatile("ld.shared.v4.u32 {%0, %1, %2, %3}, [%4];" : "=r"(x), "=r"(y), "=r"(z), "=r"(w) : "r"(a) : "memory");
}
__device__ __forceinline__ uint32_t lds32(uint32_t a) {
  uint32_t x; asm volatile("ld.shared.u32 %0, [%1];" : "=r"(x) : "r"(a) : "memory"); return x;
}
__device__ __forceinline__ void sts32(uint32_t a, uint32_t x) { asm volatile("st.shared.u32 [%0], %1;" :: "r"(a), "r"(x) : "memory"); }
__device__ __forceinline__ void sts64(uint32_t a, uint32_t x, uint32_t y) {
  asm volatile("st.shared.v2.u32 [%0], {%1, %2};" :: "r"(a), "r"(x), "r"(y) : "memory");
}
__device__ __forceinline__ void stsm4(uint32_t a, const uint32_t* r) {
  asm volatile("stmatrix.sync.aligned.m8n8.x4.shared.b16 [%0], {%1, %2, %3, %4};" :: "r"(a), "r"(r[0]), "r"(r[1]), "r"(r[2]), "r"(r[3]) : "memory");
}
__device__ __forceinline__ void ldsm4(uint32_t a, uint32_t* r) {
  asm volatile("ldmatrix.sync.aligned.m8n8.x4.shared.b16 {%0, %1, %2, %3}, [%4];" : "=r"(r[0]), "=r"(r[1]), "=r"(r[2]), "=r"(r[3]) : "r"(a) : "memory");
}
__device__ __forceinline__ uint32_t pack2(float lo, float hi) {
  uint32_t r; asm("cvt.rn.bf16x2.f32 %0, %1, %2;" : "=r"(r) : "f"(hi), "f"(lo)); return r;
}
__device__ __forceinline__ float bf_lo(uint32_t w) { return __uint_as_float(w << 16); }
__device__ __forceinline__ float bf_hi(uint32_t w) { return __uint_as_float(w & 0xffff0000u); }
__device__ __forceinline__ float tanh_hw(float x) { float y; asm volatile("tanh.approx.f32 %0, %1;" : "=f"(y) : "f"(x)); return y; }
__device__ __forceinline__ float rcp_hw(float x) { float y; asm("rcp.approx.ftz.f32 %0, %1;" : "=f"(y) : "f"(x)); return y; }
__device__ __forceinline__ float ex2_hw(float x) { float y; asm("ex2.approx.ftz.f32 %0, %1;" : "=f"(y) : "f"(x)); return y; }

__device__ __forceinline__ uint32_t here(uint32_t v) { asm volatile("" : "+r"(v)); return v; }

#define SCHED() asm volatile("pmevent 1;" ::: "memory")
#define WG_FENCE() asm volatile("wgmma.fence.sync.aligned;" ::: "memory")
#define WG_COMMIT() asm volatile("wgmma.commit_group.sync.aligned;" ::: "memory")
#define WG_WAIT(n) asm volatile("wgmma.wait_group.sync.aligned %0;" :: "n"(n) : "memory")

template <int N> __device__ __forceinline__ void pin(float (&d)[N]) {
#pragma unroll
  for (int i = 0; i < N; i++) asm volatile("" : "+f"(d[i]) :: "memory");
}
template <int N> __device__ __forceinline__ void pin(uint32_t (&d)[N]) {
#pragma unroll
  for (int i = 0; i < N; i++) asm volatile("" : "+r"(d[i]) :: "memory");
}

#define WG_D32 "{%0, %1, %2, %3, %4, %5, %6, %7, %8, %9, %10, %11, %12, %13, %14, %15, %16, %17, %18, %19, %20, %21, %22, %23, %24, %25, %26, %27, %28, %29, %30, %31}"
template <int TB> __device__ __forceinline__ void wgmma64_acc(float (&d)[32], const uint32_t* a, uint64_t db) {
  asm volatile("wgmma.mma_async.sync.aligned.m64n64k16.f32.bf16.bf16 " WG_D32 ", {%32, %33, %34, %35}, %36, 1, 1, 1, %37;"
    : "+f"(d[0]), "+f"(d[1]), "+f"(d[2]), "+f"(d[3]), "+f"(d[4]), "+f"(d[5]), "+f"(d[6]), "+f"(d[7]),
      "+f"(d[8]), "+f"(d[9]), "+f"(d[10]), "+f"(d[11]), "+f"(d[12]), "+f"(d[13]), "+f"(d[14]), "+f"(d[15]),
      "+f"(d[16]), "+f"(d[17]), "+f"(d[18]), "+f"(d[19]), "+f"(d[20]), "+f"(d[21]), "+f"(d[22]), "+f"(d[23]),
      "+f"(d[24]), "+f"(d[25]), "+f"(d[26]), "+f"(d[27]), "+f"(d[28]), "+f"(d[29]), "+f"(d[30]), "+f"(d[31])
    : "r"(a[0]), "r"(a[1]), "r"(a[2]), "r"(a[3]), "l"(db), "n"(TB));
}
__device__ __forceinline__ void wgmma64_reuse(float (&d)[32], const uint32_t* a, uint64_t db, uint32_t zero) {
  asm volatile("{\n.reg .pred p;\nsetp.ne.u32 p, %37, 0;\nwgmma.mma_async.sync.aligned.m64n64k16.f32.bf16.bf16 " WG_D32 ", {%32, %33, %34, %35}, %36, p, 1, 1, 1;\n}"
    : "+f"(d[0]), "+f"(d[1]), "+f"(d[2]), "+f"(d[3]), "+f"(d[4]), "+f"(d[5]), "+f"(d[6]), "+f"(d[7]),
      "+f"(d[8]), "+f"(d[9]), "+f"(d[10]), "+f"(d[11]), "+f"(d[12]), "+f"(d[13]), "+f"(d[14]), "+f"(d[15]),
      "+f"(d[16]), "+f"(d[17]), "+f"(d[18]), "+f"(d[19]), "+f"(d[20]), "+f"(d[21]), "+f"(d[22]), "+f"(d[23]),
      "+f"(d[24]), "+f"(d[25]), "+f"(d[26]), "+f"(d[27]), "+f"(d[28]), "+f"(d[29]), "+f"(d[30]), "+f"(d[31])
    : "r"(a[0]), "r"(a[1]), "r"(a[2]), "r"(a[3]), "l"(db), "r"(zero));
}
template <int TB> __device__ __forceinline__ void wgmma64_set(float (&d)[32], const uint32_t* a, uint64_t db) {
  asm volatile("wgmma.mma_async.sync.aligned.m64n64k16.f32.bf16.bf16 " WG_D32 ", {%32, %33, %34, %35}, %36, 0, 1, 1, %37;"
    : "=f"(d[0]), "=f"(d[1]), "=f"(d[2]), "=f"(d[3]), "=f"(d[4]), "=f"(d[5]), "=f"(d[6]), "=f"(d[7]),
      "=f"(d[8]), "=f"(d[9]), "=f"(d[10]), "=f"(d[11]), "=f"(d[12]), "=f"(d[13]), "=f"(d[14]), "=f"(d[15]),
      "=f"(d[16]), "=f"(d[17]), "=f"(d[18]), "=f"(d[19]), "=f"(d[20]), "=f"(d[21]), "=f"(d[22]), "=f"(d[23]),
      "=f"(d[24]), "=f"(d[25]), "=f"(d[26]), "=f"(d[27]), "=f"(d[28]), "=f"(d[29]), "=f"(d[30]), "=f"(d[31])
    : "r"(a[0]), "r"(a[1]), "r"(a[2]), "r"(a[3]), "l"(db), "n"(TB));
}

__device__ __forceinline__ void wgmma72_acc(float (&d)[36], const uint32_t* a, uint64_t db) {
  asm volatile("wgmma.mma_async.sync.aligned.m64n72k16.f32.bf16.bf16 {%0, %1, %2, %3, %4, %5, %6, %7, %8, %9, %10, %11, %12, %13, %14, %15, %16, %17, %18, %19, %20, %21, %22, %23, %24, %25, %26, %27, %28, %29, %30, %31, %32, %33, %34, %35}, {%36, %37, %38, %39}, %40, 1, 1, 1, 1;"
    : "+f"(d[0]), "+f"(d[1]), "+f"(d[2]), "+f"(d[3]), "+f"(d[4]), "+f"(d[5]), "+f"(d[6]), "+f"(d[7]), "+f"(d[8]),
      "+f"(d[9]), "+f"(d[10]), "+f"(d[11]), "+f"(d[12]), "+f"(d[13]), "+f"(d[14]), "+f"(d[15]), "+f"(d[16]), "+f"(d[17]),
      "+f"(d[18]), "+f"(d[19]), "+f"(d[20]), "+f"(d[21]), "+f"(d[22]), "+f"(d[23]), "+f"(d[24]), "+f"(d[25]), "+f"(d[26]),
      "+f"(d[27]), "+f"(d[28]), "+f"(d[29]), "+f"(d[30]), "+f"(d[31]), "+f"(d[32]), "+f"(d[33]), "+f"(d[34]), "+f"(d[35])
    : "r"(a[0]), "r"(a[1]), "r"(a[2]), "r"(a[3]), "l"(db));
}
__device__ __forceinline__ void wgmma16_acc(float* d, const uint32_t* a, uint64_t db) {
  asm volatile("wgmma.mma_async.sync.aligned.m64n16k16.f32.bf16.bf16 {%0, %1, %2, %3, %4, %5, %6, %7}, {%8, %9, %10, %11}, %12, 1, 1, 1, 0;"
    : "+f"(d[0]), "+f"(d[1]), "+f"(d[2]), "+f"(d[3]), "+f"(d[4]), "+f"(d[5]), "+f"(d[6]), "+f"(d[7])
    : "r"(a[0]), "r"(a[1]), "r"(a[2]), "r"(a[3]), "l"(db));
}
__device__ __forceinline__ void hmma(float (&d)[4], const uint32_t* a, uint32_t b0, uint32_t b1) {
  asm("mma.sync.aligned.m16n8k16.row.col.f32.bf16.bf16.f32 {%0, %1, %2, %3}, {%4, %5, %6, %7}, {%8, %9}, {%0, %1, %2, %3};"
    : "+f"(d[0]), "+f"(d[1]), "+f"(d[2]), "+f"(d[3]) : "r"(a[0]), "r"(a[1]), "r"(a[2]), "r"(a[3]), "r"(b0), "r"(b1));
}

__device__ __forceinline__ void hmma8(float (&d)[4], const uint32_t* a, uint32_t b0) {
  asm("mma.sync.aligned.m16n8k8.row.col.f32.bf16.bf16.f32 {%0, %1, %2, %3}, {%4, %5}, {%6}, {%0, %1, %2, %3};"
    : "+f"(d[0]), "+f"(d[1]), "+f"(d[2]), "+f"(d[3]) : "r"(a[0]), "r"(a[1]), "r"(b0));
}

template <bool FIRST> __device__ __forceinline__ void mma_tile(float (&d)[32], const uint32_t (&a)[16], uint64_t db) {
  WG_FENCE();
#pragma unroll
  for (int s = 0; s < 4; s++) {
    if (FIRST && s == 0) wgmma64_set<1>(d, &a[0], db); else wgmma64_acc<1>(d, &a[4 * s], db + s * 128);
  }
  WG_COMMIT();
}
__device__ __forceinline__ void mma_tile_reuse(float (&d)[32], const uint32_t (&a)[16], uint64_t db) {
  WG_FENCE();
  wgmma64_reuse(d, &a[0], db, blockIdx.y);
#pragma unroll
  for (int s = 1; s < 4; s++) wgmma64_acc<1>(d, &a[4 * s], db + s * 128);
  WG_COMMIT();
}
template <int ROW> __device__ __forceinline__ void mma_tile_fold(float (&d)[32], const uint32_t (&a)[16], uint64_t db, const uint32_t (&mu)[4]) {
  WG_FENCE();
#pragma unroll
  for (int s = 0; s < 4; s++) wgmma64_acc<1>(d, &a[4 * s], db + s * 128);
  wgmma64_acc<1>(d, mu, (uint64_t)((SM_BASE + SM_CS + ROW * 128) >> 4) | (uint64_t(1) << 16) | (uint64_t(1) << 62));
  WG_COMMIT();
}
__device__ __forceinline__ void mma_add_half(float (&d)[32], const uint32_t (&a)[16]) {
  const uint64_t db = (uint64_t)((SM_BASE + SM_EYE) >> 4) | (uint64_t(8) << 16) | (uint64_t(8) << 32);
  WG_FENCE();
#pragma unroll
  for (int s = 0; s < 4; s++) wgmma16_acc(&d[8 * s], &a[4 * s], db);
  WG_COMMIT();
}
#define ACQUIRE(f) mbar_wait(SM_BASE + SM_FULL + ((f) % NSTAGE) * 8, ((f) / NSTAGE) & 1)
template <int F, int N> __device__ __forceinline__ void acquire_n() {
  static_assert(F % NSTAGE + N <= NSTAGE, "stages must not wrap");
  uint32_t spin = 0, ok;
  do {
    ok = 1;
#pragma unroll
    for (int i = 0; i < N; i++)
      asm volatile("{\n.reg .pred p;\nmbarrier.try_wait.parity.shared::cta.b64 p, [%1], %2;\nselp.u32 %0, %0, 0, p;\n}"
                   : "+r"(ok) : "r"(SM_BASE + SM_FULL + (F % NSTAGE + i) * 8), "r"((F / NSTAGE) & 1) : "memory");
  } while (!ok && ++spin < SPIN_LIMIT);
}
#define RELEASE(f0, f1) do { if (lane == 0) { _Pragma("unroll") for (int f_ = (f0); f_ <= (f1); f_++) mbar_arrive(SM_BASE + SM_EMPTY + (f_ % NSTAGE) * 8); } } while (0)
constexpr uint64_t RING = (uint64_t)(SM_BASE >> 4) | (uint64_t(1) << 16) | (uint64_t(64) << 32) | (uint64_t(1) << 62);
#define LO(f) (RING + ((f) % NSTAGE) * 1024)
#define HI(f) (RING + ((f) % NSTAGE) * 1024 + 512)

template <int C> __device__ __forceinline__ uint4* peer(uint4* p) {
  asm volatile("" : "+l"(p));
  return (uint4*)((uintptr_t)p ^ (C * X_SIZE * sizeof(uint4)));
}
__device__ __forceinline__ uint32_t clock_now() { uint32_t c; asm volatile("mov.u32 %0, %%clock;" : "=r"(c) :: "memory"); return c; }
__device__ __forceinline__ void publish(uint4* dst, uint32_t (&a)[16], uint32_t tag) {
#pragma unroll
  for (int s = 0; s < 4; s++) a[4 * s] = (a[4 * s] & ~1u) | tag;
  pin(a);
  SCHED();
#pragma unroll
  for (int s = 0; s < 4; s++) st_vec(dst + s * 128, a[4 * s], a[4 * s + 1], a[4 * s + 2], a[4 * s + 3]);
  SCHED();
}
__device__ __forceinline__ void fetch(const uint4* src, uint32_t (&a)[16]) {
#pragma unroll
  for (int s = 0; s < 4; s++) ld_vec(src + s * 128, a[4 * s], a[4 * s + 1], a[4 * s + 2], a[4 * s + 3]);
}
__device__ __forceinline__ uint32_t miss(const uint32_t (&a)[16], uint32_t tag) {
  return (a[0] ^ tag) | (a[4] ^ tag) | (a[8] ^ tag) | (a[12] ^ tag);
}
__device__ __forceinline__ bool stale(uint32_t v) { return __any_sync(0xffffffffu, here(v) & 1u); }
__device__ __forceinline__ void confirm(const uint4* src, uint32_t (&a)[16], uint32_t tag) {
  uint32_t spin = 0;
  while (__builtin_expect(stale(miss(a, tag)), 0) && ++spin < SPIN_LIMIT) fetch(src, a);
}
constexpr uint32_t GATHER_DELAY = 400;
template <int C0, int C1, int SLOT> __device__ __forceinline__ void gather_wait(uint32_t (&A)[4][16], uint4* xp, uint32_t tag) {
  uint32_t spin = 0;
  while (__builtin_expect(stale(miss(A[C0], tag) | miss(A[C1], tag)), 0) && ++spin < SPIN_LIMIT) {
    fetch(peer<C0>(xp) + SLOT, A[C0]);
    if (C1 != C0) fetch(peer<C1>(xp) + SLOT, A[C1]);
  }
}
template <int C, int SLOT> __device__ __forceinline__ void gather_first(uint32_t (&A)[4][16], uint4* xp, uint32_t tag, uint32_t sent) {
  while (clock_now() - sent < GATHER_DELAY) {}
  fetch(peer<1>(xp) + SLOT, A[1]); fetch(peer<2>(xp) + SLOT, A[2]); fetch(peer<3>(xp) + SLOT, A[3]);
  gather_wait<1, C, SLOT>(A, xp, tag);
}
template <int C, int SLOT> __device__ __forceinline__ void gather_rest(uint32_t (&A)[4][16], uint4* xp, uint32_t tag) {
  SCHED();
  gather_wait<C + 1, 3, SLOT>(A, xp, tag);
}
__device__ __forceinline__ void pack_acc(const float (&d)[32], uint32_t (&a)[16]) {
#pragma unroll
  for (int i = 0; i < 16; i++) a[i] = pack2(d[2 * i], d[2 * i + 1]);
}
__device__ __forceinline__ void res_store(uint32_t slot, const uint32_t (&a)[16]) {
#pragma unroll
  for (int s = 0; s < 4; s++) sts128(slot + s * 512, a[4 * s], a[4 * s + 1], a[4 * s + 2], a[4 * s + 3]);
}
__device__ __forceinline__ void res_load(uint32_t slot, float (&d)[32]) {
  uint32_t a[16];
#pragma unroll
  for (int s = 0; s < 4; s++) lds128(slot + s * 512, a[4 * s], a[4 * s + 1], a[4 * s + 2], a[4 * s + 3]);
#pragma unroll
  for (int i = 0; i < 16; i++) { d[2 * i] = bf_lo(a[i]); d[2 * i + 1] = bf_hi(a[i]); }
  pin(d);
}
__device__ __forceinline__ void tile_store(uint32_t maddr, const uint32_t (&a)[16]) {
#pragma unroll
  for (int s = 0; s < 4; s++) stsm4(maddr ^ (s << 5), &a[4 * s]);
}
__device__ __forceinline__ void tile_load(uint32_t maddr, uint32_t (&a)[16]) {
#pragma unroll
  for (int s = 0; s < 4; s++) ldsm4(maddr ^ (s << 5), &a[4 * s]);
}

struct RowAcc { float s[4], u[2][4], v[2][4]; };
__device__ __forceinline__ void row_acc(RowAcc& t, const uint32_t (&a)[16]) {
#pragma unroll
  for (int s = 0; s < 8; s++) {
    if ((s & 1) == 0) hmma(t.s, &a[2 * s], 0x3F803F80u, 0x3F803F80u);
    hmma8(t.u[s & 1], &a[2 * s], a[2 * s]);
    hmma8(t.v[s & 1], &a[2 * s], a[2 * s + 1]);
  }
}
__device__ __forceinline__ float2 row_squares(const RowAcc& t, bool odd) {
  return make_float2(odd ? t.u[0][1] + t.u[1][1] : t.u[0][0] + t.u[1][0], odd ? t.v[0][3] + t.v[1][3] : t.v[0][2] + t.v[1][2]);
}
__device__ __forceinline__ void stat_publish(const uint32_t (&a)[16], Scratch* sc, uint32_t th, uint32_t tag) {
  RowAcc t = {};
  row_acc(t, a);
  const float2 q = row_squares(t, th & 4);
  if ((th & 3) == ((th >> 3) & 3))
    st_vec(&sc->x[blockIdx.x][X_ST + (th >> 2)], (__float_as_uint(t.s[0]) & ~1u) | tag, __float_as_uint(q.x), __float_as_uint(t.s[2]), __float_as_uint(q.y));
}
struct RowNorm { float m0, rs0, m1, rs1; };
__device__ __forceinline__ RowNorm row_norm(float s0, float q0, float s1, float q1, float scale) {
  RowNorm n;
  n.m0 = s0 * (1.f / DM); n.m1 = s1 * (1.f / DM);
  n.rs0 = scale * rsqrtf(fmaxf(fmaf(-n.m0, n.m0, q0 * (1.f / DM)), 0.f) + LN_EPS);
  n.rs1 = scale * rsqrtf(fmaxf(fmaf(-n.m1, n.m1, q1 * (1.f / DM)), 0.f) + LN_EPS);
  return n;
}
__device__ __forceinline__ RowNorm stat_gather(Scratch* sc, uint32_t th, uint32_t tag, float scale) {
  const uint4* src = &sc->x[blockIdx.x & ~3u][X_ST + (th >> 2)];
  uint32_t v[16], spin = 0;
  do {
#pragma unroll
    for (int j = 0; j < 4; j++) ld_vec(src + j * X_SIZE, v[4 * j], v[4 * j + 1], v[4 * j + 2], v[4 * j + 3]);
  } while (stale(miss(v, tag)) && ++spin < SPIN_LIMIT);
  float f[4];
#pragma unroll
  for (int i = 0; i < 4; i++)
    f[i] = (__uint_as_float(v[i]) + __uint_as_float(v[4 + i])) + (__uint_as_float(v[8 + i]) + __uint_as_float(v[12 + i]));
  return row_norm(f[0], f[1], f[2], f[3], scale);
}
constexpr uint32_t SM_NORM = SM_BASE + SM_STG + 2 * TILE_BYTES + 4096;
__device__ __forceinline__ void norm_produce(const RowNorm& n, uint32_t th, uint32_t qsel) {
  const bool sel = (th & 3) == qsel;
  const float a = sel ? -n.m0 : 0.f, c = sel ? -n.m1 : 0.f;
  const uint32_t ah = pack2(a, a), ch = pack2(c, c);
  const float al = a - bf_lo(ah), cl = c - bf_lo(ch);
  sts128(SM_NORM + th * 16, ah, ch, pack2(al, al), pack2(cl, cl));
  sts64(SM_NORM + 2048 + th * 8, __float_as_uint(n.rs0), __float_as_uint(n.rs1));
  bar_arrive(BAR_ST, 256);
}
__device__ __forceinline__ void norm_duty(Scratch* sc, uint32_t th, uint32_t tag, float scale, uint32_t qsel) {
  bar_sync(BAR_RES, 256);
  norm_produce(stat_gather(sc, th, tag, scale), th, qsel);
}
__device__ __forceinline__ void norm_consume(uint32_t th, uint32_t (&mu)[4], float& rs0, float& rs1) {
  bar_sync(BAR_ST, 256);
  lds128(SM_NORM + th * 16, mu[0], mu[1], mu[2], mu[3]);
  asm volatile("ld.shared.v2.f32 {%0, %1}, [%2];" : "=f"(rs0), "=f"(rs1) : "r"(SM_NORM + 2048 + th * 8) : "memory");
}
__device__ __forceinline__ void scale_pack(const float (&d)[32], uint32_t (&a)[16], float rs0, float rs1) {
#pragma unroll
  for (int i = 0; i < 16; i++) { const float rs = (i & 1) ? rs1 : rs0; a[i] = pack2(d[2 * i] * rs, d[2 * i + 1] * rs); }
}
template <int S> __device__ __forceinline__ void silu_seg(float (&acc)[4][32], float (&tn)[2][4], uint32_t (&H)[4][16], float rs0, float rs1) {
  if (S >= 2) {
    const float* h = &acc[(S - 2) >> 3][4 * ((S - 2) & 7)];
    const float* v = tn[S & 1];
    uint32_t* o = &H[(S - 2) >> 3][2 * ((S - 2) & 7)];
    o[0] = pack2(fmaf(h[0], v[0], h[0]), fmaf(h[1], v[1], h[1]));
    o[1] = pack2(fmaf(h[2], v[2], h[2]), fmaf(h[3], v[3], h[3]));
    asm volatile("" : "+r"(o[0]), "+r"(o[1]));
  }
  if (S >= 1 && S <= 32) {
#pragma unroll
    for (int k = 0; k < 4; k++) tn[(S - 1) & 1][k] = tanh_hw(acc[((S - 1) >> 3) & 3][4 * ((S - 1) & 7) + k]);
  }
  if (S < 32) {
    float* h = &acc[(S >> 3) & 3][4 * (S & 7)];
    h[0] *= rs0; h[1] *= rs0; h[2] *= rs1; h[3] *= rs1;
    asm volatile("" : "+f"(h[0]), "+f"(h[1]), "+f"(h[2]), "+f"(h[3]));
  }
  SCHED();
}
template <int S0, int S1> __device__ __forceinline__ void silu_segs(float (&acc)[4][32], float (&tn)[2][4], uint32_t (&H)[4][16], float rs0, float rs1) {
  silu_seg<S0>(acc, tn, H, rs0, rs1);
  if constexpr (S0 + 1 < S1) silu_segs<S0 + 1, S1>(acc, tn, H, rs0, rs1);
}
template <int HALF> __device__ __forceinline__ void send_half(uint4* dst, const float (&d)[32], uint32_t tag) {
  uint32_t o[8];
#pragma unroll
  for (int i = 0; i < 8; i++) o[i] = pack2(d[16 * HALF + 2 * i], d[16 * HALF + 2 * i + 1]);
  o[0] = (o[0] & ~1u) | tag; o[4] = (o[4] & ~1u) | tag;
  pin(o);
  SCHED();
  st_vec(dst + HALF * 256, o[0], o[1], o[2], o[3]);
  st_vec(dst + HALF * 256 + 128, o[4], o[5], o[6], o[7]);
  SCHED();
}
__device__ __forceinline__ uint32_t send_residual(uint32_t (&a)[16], Scratch* sc, uint4* xp, uint32_t res, uint32_t tag) {
  const uint32_t exact[4] = {a[0], a[4], a[8], a[12]};
  publish(xp + X_AG0, a, tag);
  const uint32_t sent = clock_now();
  stat_publish(a, sc, threadIdx.x, tag);
  res_store(res, a);
#pragma unroll
  for (int s = 0; s < 4; s++) sts32(res + s * 512, exact[s]);
  bar_arrive(BAR_RES, 256);
  return sent;
}
template <int F, int N> __device__ __forceinline__ uint32_t proj_residual(uint32_t (&A)[4][16], Scratch* sc, uint4* xp, uint32_t res, uint32_t tag) {
  float acc[32];
  publish(xp + X_AG1, A[0], tag);
  const uint32_t sent = clock_now();
  acquire_n<F, N>();
  if (F == F_PW2) acquire_n<0, 5>();
  res_load(res, acc);
  mma_tile<false>(acc, A[0], LO(F));
  gather_first<2, X_AG1>(A, xp, tag, sent);
  mma_tile<false>(acc, A[1], HI(F));
  mma_tile<false>(acc, A[2], LO(F + 1));
  gather_rest<2, X_AG1>(A, xp, tag);
  PROF_MARK(F == F_WO ? 11 : 16);
  mma_tile<false>(acc, A[3], HI(F + 1));
  WG_WAIT(0); pin(acc);
  pack_acc(acc, A[0]);
  return send_residual(A[0], sc, xp, res, tag);
}

__device__ __forceinline__ void qk_tile(float (&S)[32], const uint32_t (&Q)[16], uint64_t dk) {
#pragma unroll
  for (int s = 0; s < 4; s++) {
    if (s == 0) wgmma64_set<0>(S, &Q[0], dk); else wgmma64_acc<0>(S, &Q[4 * s], dk + s * 2);
  }
}
__device__ __forceinline__ void qk_shift(float (&S)[32], const uint32_t (&nm)[4]) { wgmma64_acc<0>(S, nm, (uint64_t)((SM_BASE + SM_ONE) >> 4)); }
constexpr uint64_t V_STEP = uint64_t(1) - (uint64_t(1) << 16);
constexpr uint64_t RING_V = RING - (uint64_t(1) << 16) + ((uint64_t)((SM_STG + 2 * TILE_BYTES) >> 4) << 16);
__device__ __forceinline__ void pv_tile(float (&O)[36], const uint32_t (&P)[16], uint64_t dv, uint64_t pad) {
#pragma unroll
  for (int s = 0; s < 4; s++) wgmma72_acc(O, &P[4 * s], dv + s * 128 * V_STEP + (s < 2 ? 0 : (s - 1) * pad));
}
__device__ __forceinline__ void attn_step(const float (&Sc)[32], float (&Sn)[32], uint32_t (&Pc)[16], uint32_t (&Pp)[16], float (&O)[36],
                                          const uint32_t (&Q)[16], const uint32_t (&nm)[4], uint64_t dk, uint64_t dv) {
  WG_FENCE();
  qk_tile(Sn, Q, dk);
  qk_shift(Sn, nm);
  pv_tile(O, Pp, dv, 0);
  WG_COMMIT();
  SCHED();
#pragma unroll
  for (int i = 0; i < 16; i++) Pc[i] = pack2(ex2_hw(Sc[2 * i]), ex2_hw(Sc[2 * i + 1]));
  pin(Pc);
  SCHED();
}
template <int R> __device__ __forceinline__ float tile_max(const float (&S)[32]) {
  float t[4];
#pragma unroll
  for (int j = 0; j < 4; j++) t[j] = fmaxf(fmaxf(S[8 * j + R], S[8 * j + R + 1]), fmaxf(S[8 * j + R + 4], S[8 * j + R + 5]));
  float n = fmaxf(fmaxf(t[0], t[1]), fmaxf(t[2], t[3]));
  n = fmaxf(n, __shfl_xor_sync(0xffffffffu, n, 1));
  return fmaxf(n, __shfl_xor_sync(0xffffffffu, n, 2));
}
__device__ __forceinline__ void attention_exact(float (&O)[36], const uint32_t (&Q)[16], const Scratch* sc, int bh, int lane) {
  const char* kb = (const char*)&sc->kv[bh][0][0][0];
  const char* vb = (const char*)&sc->kv[bh][1][0][0];
  const int g = lane >> 2, q = lane & 3;
  float m0 = -INFINITY, m1 = -INFINITY, l0 = 0.f, l1 = 0.f;
  float o[8][4] = {};
#pragma unroll 1
  for (int k0 = 0; k0 < T_SEQ; k0 += 8) {
    float s[4] = {0.f, 0.f, 0.f, 0.f};
#pragma unroll
    for (int c = 0; c < 8; c++) hmma8(s, &Q[2 * c], __ldcg((const uint32_t*)(kb + (k0 + g) * 128 + ((c ^ g) << 4) + q * 4)));
    float n0 = fmaxf(s[0], s[1]), n1 = fmaxf(s[2], s[3]);
    n0 = fmaxf(n0, __shfl_xor_sync(0xffffffffu, n0, 1)); n1 = fmaxf(n1, __shfl_xor_sync(0xffffffffu, n1, 1));
    n0 = fmaxf(m0, fmaxf(n0, __shfl_xor_sync(0xffffffffu, n0, 2))); n1 = fmaxf(m1, fmaxf(n1, __shfl_xor_sync(0xffffffffu, n1, 2)));
    const float a0 = ex2_hw(m0 - n0), a1 = ex2_hw(m1 - n1);
    m0 = n0; m1 = n1;
    const uint32_t pp[2] = {pack2(ex2_hw(s[0] - n0), ex2_hw(s[1] - n0)), pack2(ex2_hw(s[2] - n1), ex2_hw(s[3] - n1))};
    l0 = fmaf(l0, a0, bf_lo(pp[0]) + bf_hi(pp[0])); l1 = fmaf(l1, a1, bf_lo(pp[1]) + bf_hi(pp[1]));
#pragma unroll
    for (int j = 0; j < 8; j++) {
      const uint32_t v0 = __ldcg((const uint16_t*)(vb + (k0 + 2 * q) * 128 + ((j ^ (2 * q)) << 4) + g * 2));
      const uint32_t v1 = __ldcg((const uint16_t*)(vb + (k0 + 2 * q + 1) * 128 + ((j ^ (2 * q + 1)) << 4) + g * 2));
      o[j][0] *= a0; o[j][1] *= a0; o[j][2] *= a1; o[j][3] *= a1;
      hmma8(o[j], pp, v0 | (v1 << 16));
    }
  }
  l0 += __shfl_xor_sync(0xffffffffu, l0, 1); l1 += __shfl_xor_sync(0xffffffffu, l1, 1);
  O[32] = l0 + __shfl_xor_sync(0xffffffffu, l0, 2); O[34] = l1 + __shfl_xor_sync(0xffffffffu, l1, 2);
#pragma unroll
  for (int i = 0; i < 32; i++) O[i] = o[i >> 2][i & 3];
}

__device__ __forceinline__ uint32_t fill_entry(int f, int r, int bh) {
  int m, x = r, y, dx = 0;
  if (f < F_QKV || f >= 48) {
    const int i = f & 15;
    m = f < F_QKV ? M_FF1A : M_FF2A;
    if (i < 8) { x = 4 * r + ((0xE2u >> i) & 1) * 2; y = r ^ ((0xE790u >> (2 * i)) & 3); dx = 1; }
    else { m++; x = r ^ (((i >> 1) - 3) & 3); y = 4 * r + 2 * (i & 1); }
  } else if (f < F_KV) {
    const int i = f - F_QKV;
    m = M_QKV;
    if (i == 1 || i >= 5) { y = r ^ (i == 1 ? 0 : 2); }
    else { x = 4 + r; y = r ^ (i ? i - 1 : 0); dx = 4; }
  } else if (f < F_WO) {
    const int i = f - F_KV;
    m = M_KV; x = 0; y = bh * 32 + (i & 2) * 8 + (i >> 2) * 4 + (i & 1) * 2;
  } else if (f >= F_PW1 && f < F_PW2) {
    m = M_PW1; y = r ^ (f - F_PW1); dx = 4;
  } else {
    m = f < F_PW1 ? M_WO : M_PW2; y = r ^ ((f & 1) * 2);
  }
  return m | (x << 4) | (y << 8) | (dx << 16);
}
__device__ __forceinline__ void tma_fill(uint32_t st, const CUtensorMap* map, uint32_t x, uint32_t y, uint32_t x2, uint32_t y2) {
  asm volatile("{\n.reg .pred p;\nelect.sync _|p, 0xffffffff;\n"
               "@p mbarrier.arrive.expect_tx.shared::cta.b64 _, [%1], 16384;\n"
               "@p cp.async.bulk.tensor.2d.shared::cluster.global.mbarrier::complete_tx::bytes [%0], [%2, {%3, %4}], [%1];\n"
               "@p cp.async.bulk.tensor.2d.shared::cluster.global.mbarrier::complete_tx::bytes [%0 + 8192], [%2, {%5, %6}], [%1];\n}"
               :: "r"(SM_BASE + st * STAGE_BYTES), "r"(SM_BASE + SM_FULL + st * 8), "l"(map), "r"(x), "r"(y), "r"(x2), "r"(y2) : "memory");
}
__device__ __forceinline__ void l2_prefetch(const void* p, uint32_t total, int b) {
  const uint32_t part = total / NCTA;
  asm volatile("cp.async.bulk.prefetch.L2.global [%0], %1;" :: "l"((const char*)p + (size_t)b * part), "r"(part) : "memory");
}

__global__ void __launch_bounds__(384, 1) conformer_kernel(Scratch* __restrict__ sc, __nv_bfloat16* __restrict__ out,
                                                           const __nv_bfloat16* __restrict__ dw, const __nv_bfloat16* __restrict__ xin,
                                                           const __nv_bfloat16* __restrict__ w_ff1a, const __grid_constant__ Params p) {
  extern __shared__ __align__(1024) uint8_t smem[];
  const int tid = threadIdx.x, lane = tid & 31;
  const int cw = __shfl_sync(0xffffffffu, tid >> 5, 0), wg = cw >> 2, w = cw & 3;
  const int b = blockIdx.x, r = b & 3, batch = b >> 6, t = (b >> 2) & 15;
  if ((uint32_t)__cvta_generic_to_shared(smem) != SM_BASE) return;
  PROF_MARK(0);
  PROF_TIME(30);

  if (cw == 8) {
    if (lane == 0) {
      asm volatile("prefetch.tensormap [%0];" :: "l"(&p.map[M_X]) : "memory");
      asm volatile("prefetch.tensormap [%0];" :: "l"(&p.map[M_FF1A]) : "memory");
      mbar_init(SM_BASE + SM_XBAR, 1);
#pragma unroll
      for (int i = 0; i < NSTAGE; i++) mbar_init(SM_BASE + SM_FULL + i * 8, 1);
      fence_async_smem();
    }
    __syncwarp();
    asm volatile("{\n.reg .pred p;\nelect.sync _|p, 0xffffffff;\n"
                 "@p mbarrier.arrive.expect_tx.shared::cta.b64 _, [%1], 32768;\n"
                 "@p cp.async.bulk.tensor.4d.shared::cluster.global.mbarrier::complete_tx::bytes [%0], [%2, {0, %3, 0, %4}], [%1];\n}"
                 :: "r"(SM_BASE + SM_STG), "r"(SM_BASE + SM_XBAR), "l"(&p.map[M_X]), "r"(t * 64), "r"(batch) : "memory");
    bar_arrive(0, 320);
    PROF_MARK(9);
#pragma unroll 1
    for (int f = 0; f < 8; f++) {
      const uint32_t x = 256 * r + ((0xE2u >> f) & 1) * 128, y = (r ^ ((0xE790u >> (2 * f)) & 3)) * 64;
      tma_fill(f, &p.map[M_FF1A], x, y, x + 64, y);
    }
    PROF_MARK(1);
  } else if (cw == 9) {
    if (lane == 0) {
#pragma unroll
      for (int i = 0; i < NSTAGE; i++) mbar_init(SM_BASE + SM_EMPTY + i * 8, 4);
    }
    __syncwarp();
    bar_arrive(0, 320);
    bar_arrive(BAR_INIT, 64);
  } else if (cw == 11) {
    if (lane == 0) {
      l2_prefetch(xin, 2 * T_SEQ * DM * 2, b);
      l2_prefetch(w_ff1a, 256 * 1024 * 2, b);
    }
  } else if (wg < 2) {
    if (tid < 144) sts128(SM_BASE + SM_CS + tid * 16, 0, 0, 0, 0);
    if (wg == 1) {
      const int i = tid - 128;
      sts32(SM_BASE + SM_EYE + i * 4, i >= 96 ? 0x3F803F80u : ((i & 32) == 0 && (i & 3) == ((i >> 3) & 3)) ? (0x3F00u << ((i & 4) * 4)) : 0u);
    }
    fence_async_smem();
    bar_sync(0, 320);
  }

  if (wg == 2) {
    asm volatile("setmaxnreg.dec.sync.aligned.u32 40;");
    if (cw == 8) {
      const uint32_t* flag = sc->flag[batch * 4 + r][lane];
      const uint32_t prev = ((volatile uint32_t*)sc->epoch)[b];
      uint32_t entry[2], ready = 0, st = 8, parity = 1;
#pragma unroll 1
      for (int i = 0; i < 2; i++) { entry[1] = fill_entry(i * 32 + lane, r, batch * 4 + r); if (i == 0) entry[0] = entry[1]; }
      bar_sync(BAR_INIT, 64);
#pragma unroll 1
      for (int f = 8; f < F_TOTAL; f++) {
        const uint32_t e = __shfl_sync(0xffffffffu, f < 32 ? entry[0] : entry[1], f);
        if ((e & 15) == M_KV) {
          const uint32_t need = 3u << ((e >> 8) & 31);
          uint32_t spin = 0;
#pragma unroll 1
          while ((ready & need) != need && ++spin < SPIN_LIMIT) {
            uint32_t v;
            asm volatile("ld.relaxed.gpu.global.u32 %0, [%1];" : "=r"(v) : "l"(flag) : "memory");
            ready = __ballot_sync(0xffffffffu, v - 1 == prev);
          }
        }
        if (f == F_KV) PROF_MARK(8);
        mbar_wait(SM_BASE + SM_EMPTY + st * 8, parity);
        const uint32_t x = (e << 2) & 0x3C0, y = (e >> 2) & 0x3FC0, dx = (e >> 16) << 6;
        tma_fill(st, &p.map[e & 15], x, y, x + dx, dx ? y : y ^ 64);
        if (++st == NSTAGE) { st = 0; parity ^= 1; }
      }
    } else if (here(cw) != 11) {
      const int kind = w - 1;
      const uint32_t epoch = ((volatile uint32_t*)sc->epoch)[b] + 1;
      if (kind == 0) {
        bar_sync(BAR_K, 160);
      } else {
        uint32_t v, spin = 0;
#pragma unroll 1
        do {
          asm volatile("ld.relaxed.gpu.global.u32 %0, [%1];" : "=r"(v) : "l"(sc->ready[(b & ~3) + (lane & 3)]) : "memory");
        } while (__any_sync(0xffffffffu, v != epoch) && ++spin < SPIN_LIMIT);
        bar_arrive(BAR_RDY, 160);
        bar_arrive(BAR_RDY1, 160);
        bar_sync(BAR_V, 160);
      }
      if (lane == 0) {
        asm volatile("cp.async.bulk.global.shared::cta.bulk_group [%0], [%1], %2;"
                     :: "l"(&sc->kv[batch * 4 + r][kind][t][0]), "r"(SM_BASE + SM_STG + kind * TILE_BYTES), "r"(TILE_BYTES) : "memory");
        asm volatile("cp.async.bulk.commit_group;\ncp.async.bulk.wait_group 0;" ::: "memory");
        asm volatile("st.relaxed.gpu.global.u32 [%0], %1;" :: "l"(sc->flag[batch * 4 + r][kind * 16 + t]), "r"(epoch) : "memory");
      }
    } else {
      const uint32_t epoch = ((volatile uint32_t*)sc->epoch)[b] + 1;
      if (lane == 0) {
        asm volatile("prefetch.tensormap [%0];" :: "l"(&p.map[M_FF1B]) : "memory");
        l2_prefetch(p.w_ff1b, 1024 * 256 * 2, b);
        l2_prefetch(p.w_qkv, 256 * 768 * 2, b);
        l2_prefetch(p.w_pw1, 256 * 512 * 2, b);
        l2_prefetch(p.w_ff2a, 256 * 1024 * 2, b);
      }
#pragma unroll 1
      for (uint4* dst = &sc->x[b][X_CLEAR + lane]; dst < &sc->x[b][X_ST + 32]; dst += 32) {
        const uint32_t t0 = clock_now();
        st_vec(dst, 0u, 0u, 0u, 0u);
        while (clock_now() - t0 < 24) {}
      }
      asm volatile("fence.acq_rel.gpu;" ::: "memory");
      __syncwarp();
      if (lane == 0) {
        asm volatile("st.relaxed.gpu.global.u32 [%0], %1;" :: "l"(sc->ready[b]), "r"(epoch) : "memory");
        l2_prefetch(p.w_o, 256 * 256 * 2, b);
        l2_prefetch(p.w_pw2, 256 * 256 * 2, b);
        l2_prefetch(p.w_ff2b, 1024 * 256 * 2, b);
#pragma unroll
        for (int i = M_QKV; i < M_X; i++) asm volatile("prefetch.tensormap [%0];" :: "l"(&p.map[i]) : "memory");
      }
    }
  } else {
    asm volatile("setmaxnreg.inc.sync.aligned.u32 232;");
    const int q = lane & 3, th = tid & 127;
    constexpr uint32_t stg = SM_BASE + SM_STG;
    const uint32_t mrow = 16 * w + (lane & 15);
    const uint32_t maddr = stg + mrow * 128 + (((lane >> 4) ^ (lane & 7)) << 4);
    const uint32_t res = stg + 3 * TILE_BYTES + w * 2048 + lane * 16;
    uint4* const xp = &sc->x[b][th];
    const int nvalid = T_SEQ - t * 64, row0 = 16 * w + (lane >> 2);

    uint32_t A[4][16];
    uint32_t sent = 0;
    mbar_wait(SM_BASE + SM_XBAR, 0);
    PROF_MARK(1);
#pragma unroll
    for (int c = 0; c < 4; c++) tile_load(maddr + (r ^ c) * TILE_BYTES, A[c]);
    if (wg == 0) {
      float sa[4] = {0.f, 0.f, 0.f, 0.f}, sb[4] = {0.f, 0.f, 0.f, 0.f};
#pragma unroll
      for (int i = 0; i < 16; i++) hmma((i & 1) ? sb : sa, &A[i >> 2][4 * (i & 3)], 0x3F803F80u, 0x3F803F80u);
      bar_arrive(BAR_X, 256);
      const float s0 = (sa[0] + sb[0]) * (1.f / DM), s1 = (sa[2] + sb[2]) * (1.f / DM);
      const uint32_t m0 = pack2(s0, s0), m1 = pack2(s1, s1);
#pragma unroll
      for (int c = 0; c < 4; c++) {
#pragma unroll
        for (int i = 0; i < 16; i++) asm("sub.rn.bf16x2 %0, %0, %1;" : "+r"(A[c][i]) : "r"((i & 1) ? m1 : m0));
        pin(A[c]);
      }
    } else {
      const uint32_t epoch = ((volatile uint32_t*)sc->epoch)[b] + 1, tag = epoch & 1;
      {
        RowAcc ra[2] = {};
#pragma unroll
        for (int c = 0; c < 4; c++) row_acc(ra[c & 1], A[c]);
        const float2 qa = row_squares(ra[0], lane & 4), qb = row_squares(ra[1], lane & 4);
        const int src = (lane & 28) | (lane >> 3);
        const float q0 = __shfl_sync(0xffffffffu, qa.x + qb.x, src), q1 = __shfl_sync(0xffffffffu, qa.y + qb.y, src);
        bar_sync(BAR_X, 256);
        res_store(res, A[0]);
        norm_produce(row_norm(ra[0].s[0] + ra[1].s[0], q0, ra[0].s[2] + ra[1].s[2], q1, 0.5f), th, 4);
      }
      PROF_MARK(5);
      SCHED();
      uint4 cv[8];
      if (b < 72) {
        const __nv_bfloat16* wp; int ld, col;
        if (b < 24) { wp = p.w_qkv; ld = 768; col = b * 32; }
        else if (b < 40) { wp = p.w_pw1; ld = 512; col = (b - 24) * 32; }
        else { wp = p.w_ff2a; ld = 1024; col = (b - 40) * 32; }
        const uint4* src = (const uint4*)(wp + (size_t)(th >> 2) * ld + col + q * 8);
#pragma unroll
        for (int i = 0; i < 8; i++) cv[i] = __ldg(src + i * 4 * ld);
      }
      if (b < 72) {
        float c[8] = {0.f, 0.f, 0.f, 0.f, 0.f, 0.f, 0.f, 0.f};
#pragma unroll
        for (int i = 0; i < 8; i++) {
          const uint4 v = cv[i];
          c[0] += bf_lo(v.x); c[1] += bf_hi(v.x); c[2] += bf_lo(v.y); c[3] += bf_hi(v.y);
          c[4] += bf_lo(v.z); c[5] += bf_hi(v.z); c[6] += bf_lo(v.w); c[7] += bf_hi(v.w);
        }
#pragma unroll 1
        for (int m = 4; m <= 16; m <<= 1)
#pragma unroll
          for (int k = 0; k < 8; k++) c[k] += __shfl_xor_sync(0xffffffffu, c[k], m);
        if (lane < 4) {
          const uint32_t a = SM_BASE + SM_CS + 1792 + w * 128 + lane * 32;
          sts128(a, __float_as_uint(c[0]), __float_as_uint(c[1]), __float_as_uint(c[2]), __float_as_uint(c[3]));
          sts128(a + 16, __float_as_uint(c[4]), __float_as_uint(c[5]), __float_as_uint(c[6]), __float_as_uint(c[7]));
        }
        bar_sync(BAR_WG1, 128);
        if (th < 8) {
          float o[4] = {0.f, 0.f, 0.f, 0.f};
#pragma unroll 1
          for (int k = 0; k < 4; k++) {
            uint32_t e[4];
            lds128(SM_BASE + SM_CS + 1792 + k * 128 + th * 16, e[0], e[1], e[2], e[3]);
#pragma unroll
            for (int i = 0; i < 4; i++) o[i] += __uint_as_float(e[i]);
          }
          st_vec(&sc->cs[b * 8 + th], (__float_as_uint(o[0]) & ~1u) | tag, __float_as_uint(o[1]), __float_as_uint(o[2]), __float_as_uint(o[3]));
        }
      }
      bar_sync(BAR_WG1, 128);
      PROF_MARK(2);
#pragma unroll 1
      for (int i = th; i < 144; i += 128) {
        const int j = i >> 4;
        int src;
        if (j < CS_PW1) src = 320 + 64 * r + i;
        else if (j < CS_QKV) src = 192 + (j - CS_PW1) * 64 + 16 * r + (i & 15);
        else src = ((j - CS_QKV + 1) % 3) * 64 + 16 * r + (i & 15);
        uint32_t e[4], spin = 0;
#pragma unroll 1
        do {
          ld_vec(&sc->cs[src], e[0], e[1], e[2], e[3]);
        } while (((e[0] ^ tag) & 1u) && ++spin < SPIN_LIMIT);
        const float c0 = __uint_as_float(e[0] & ~1u), c1 = __uint_as_float(e[1]), c2 = __uint_as_float(e[2]), c3 = __uint_as_float(e[3]);
        const uint32_t h0 = pack2(c0, c1), h1 = pack2(c2, c3);
        const uint32_t a = SM_BASE + SM_CS + j * 256 + (i & 15) * 8;
        sts64(a ^ ((a >> 3) & 0x70), h0, h1);
        sts64((a + 128) ^ (((a + 128) >> 3) & 0x70), pack2(c0 - bf_lo(h0), c1 - bf_hi(h0)), pack2(c2 - bf_lo(h1), c3 - bf_hi(h1)));
      }
      fence_async_smem();
      PROF_MARK(4);
      bar_sync(BAR_RDY1, 160);
      norm_duty(sc, th, 1, 1.f, 3);
    }

#pragma unroll 1
    for (uint32_t pass = 0; pass < 2; pass++) {
      uint32_t Q[16];
      if (wg == 0) {
        float acc[4][32];
        uint32_t H[4][16];
        if (!pass) ACQUIRE(0);
        mma_tile<true>(acc[0], A[0], LO(0)); mma_tile<true>(acc[1], A[0], HI(0));
        if (!pass) ACQUIRE(1);
        mma_tile<true>(acc[2], A[0], LO(1)); mma_tile<true>(acc[3], A[0], HI(1));
        if (pass) gather_first<1, X_AG0>(A, xp, 1, sent); else acquire_n<2, 3>();
        mma_tile<false>(acc[0], A[1], LO(2)); mma_tile<false>(acc[1], A[1], HI(2));
        if (pass) { gather_rest<1, X_AG0>(A, xp, 1); RELEASE(F_PW2, F_PW2 + 1); }
        PROF_MARK(2 + pass * 16);
        mma_tile<false>(acc[0], A[2], LO(3));
        WG_WAIT(3);
        uint32_t mu[4];
        float rs0, rs1, tn[2][4];
        norm_consume(here(th), mu, rs0, rs1);
        mma_tile_fold<2 * CS_FF2>(acc[0], A[3], LO(4), mu);
        RELEASE(0, 1);
        acquire_n<5, 3>();
        mma_tile<false>(acc[1], A[2], HI(3));
#define SEGS(a, b) silu_segs<a, b>(acc, tn, H, rs0, rs1)
        WG_WAIT(1); pin(acc[0]);
        SEGS(0, 1);
        mma_tile_fold<2 * CS_FF2 + 2>(acc[1], A[3], HI(4), mu);
        SEGS(1, 4);
        mma_tile<false>(acc[2], A[1], LO(5));
        SEGS(4, 6);
        mma_tile<false>(acc[2], A[2], LO(6));
        SEGS(6, 8);
        WG_WAIT(2); pin(acc[1]);
        RELEASE(2, 4);
        SEGS(8, 9);
        mma_tile_fold<2 * CS_FF2 + 4>(acc[2], A[3], LO(7), mu);
        SEGS(9, 12);
        mma_tile<false>(acc[3], A[1], HI(5));
        acquire_n<8, 2>();
        SEGS(12, 14);
        mma_tile<false>(acc[3], A[2], HI(6));
        SEGS(14, 16);
        WG_WAIT(2); pin(acc[2]);
        SEGS(16, 17);
        mma_tile_fold<2 * CS_FF2 + 6>(acc[3], A[3], HI(7), mu);
        SEGS(17, 20);
        mma_tile_reuse(acc[1], H[0], LO(8));
        acquire_n<10, 2>();
        SEGS(20, 22);
        mma_tile<false>(acc[1], H[1], HI(8));
        SEGS(22, 24);
        WG_WAIT(2); pin(acc[3]);
        RELEASE(5, 7);
        SEGS(24, 26);
        mma_tile<false>(acc[1], H[2], LO(9));
        SEGS(26, 28);
        mma_tile_reuse(acc[2], H[0], LO(10));
        SEGS(28, 31);
        mma_tile<false>(acc[2], H[1], HI(10));
        SEGS(31, 34);
#undef SEGS
        PROF_MARK(3 + pass * 16);
        const uint32_t rtag = here(pass ^ 1);
        const uint4* rs_in = xp + X_RS;
        mma_tile<false>(acc[1], H[3], HI(9));
        mma_tile<false>(acc[2], H[2], LO(11));
        acquire_n<12, 2>();
        uint4* rs_out = peer<1>(xp) + X_RS;
        mma_tile<false>(acc[2], H[3], HI(11));
        WG_WAIT(2); pin(acc[1]);
        send_half<0>(rs_out, acc[1], rtag);
        mma_tile_reuse(acc[3], H[0], LO(12));
        SCHED();
        send_half<1>(rs_out, acc[1], rtag);
        mma_tile<false>(acc[3], H[1], HI(12));
        rs_out = peer<2>(xp) + X_RS + 512;
        WG_WAIT(2); pin(acc[2]);
        send_half<0>(rs_out, acc[2], rtag);
        mma_tile<false>(acc[3], H[2], LO(13));
        SCHED();
        send_half<1>(rs_out, acc[2], rtag);
        mma_tile<false>(acc[3], H[3], HI(13));
        RELEASE(8, 11);
        acquire_n<14, 2>();
        mma_tile_reuse(acc[1], H[0], LO(14));
        rs_out = peer<3>(xp) + X_RS + 1024;
        if (!pass) bar_sync(BAR_RDY, 160);
        fetch(rs_in, A[1]);
        SCHED();
        mma_tile<false>(acc[1], H[1], HI(14));
        WG_WAIT(2); pin(acc[3]);
        send_half<0>(rs_out, acc[3], rtag);
        send_half<1>(rs_out, acc[3], rtag);
        mma_tile<false>(acc[1], H[2], LO(15)); mma_tile<false>(acc[1], H[3], HI(15));
        SCHED();
        res_load(res, acc[2]);
        if (!pass) acquire_n<F_QKV, 6>();
        confirm(rs_in, A[1], rtag);
        mma_add_half(acc[2], A[1]);
        PROF_MARK(44);
        fetch(rs_in + 512, A[2]);
        fetch(rs_in + 1024, A[3]);
        confirm(rs_in + 512, A[2], rtag);
        mma_add_half(acc[2], A[2]);
        SCHED();
        confirm(rs_in + 1024, A[3], rtag);
        mma_add_half(acc[2], A[3]);
        PROF_MARK(4 + pass * 16);
        WG_WAIT(0); pin(acc[2]); pin(acc[1]);
#pragma unroll
        for (int i = 0; i < 16; i++) A[0][i] = pack2(fmaf(acc[1][2 * i], 0.5f, acc[2][2 * i]), fmaf(acc[1][2 * i + 1], 0.5f, acc[2][2 * i + 1]));
        if (pass) {
          PROF_MARK(21);
          stat_publish(A[0], sc, here(th), 0);
          const RowNorm fn = stat_gather(sc, here(th), 0, 1.f);
          const float nm0 = -fn.m0 * fn.rs0, nm1 = -fn.m1 * fn.rs1;
#pragma unroll
          for (int i = 0; i < 16; i++) {
            const float rs = (i & 1) ? fn.rs1 : fn.rs0, nm = (i & 1) ? nm1 : nm0;
            A[0][i] = pack2(fmaf(bf_lo(A[0][i]), rs, nm), fmaf(bf_hi(A[0][i]), rs, nm));
          }
          tile_store(here(maddr), A[0]);
          __syncwarp();
          const int row = 16 * w + (lane >> 3);
          uint4* dst = (uint4*)(out + ((size_t)batch * T_SEQ + t * 64 + row) * DM + 64 * r) + (lane & 7);
          const uint32_t src = stg + row * 128 + (((lane & 7) ^ (lane >> 3)) << 4);
#pragma unroll
          for (int i = 0; i < 4; i++) {
            uint4 v;
            lds128((src ^ ((i & 1) << 6)) + i * 512, v.x, v.y, v.z, v.w);
            if (row + 4 * i < nvalid) dst[i * 4 * (DM / 8)] = v;
          }
          PROF_MARK(22);
          PROF_TIME(31);
          break;
        }
        sent = send_residual(A[0], sc, xp, res, 1);
        PROF_MARK(5);
        mma_tile<true>(acc[0], A[0], LO(F_QKV)); mma_tile<true>(acc[1], A[0], HI(F_QKV));
        mma_tile<true>(acc[2], A[0], LO(F_QKV + 1));
        gather_first<1, X_AG0>(A, xp, 1, sent);
        mma_tile<false>(acc[0], A[1], LO(F_QKV + 2)); mma_tile<false>(acc[1], A[1], HI(F_QKV + 2));
        gather_rest<1, X_AG0>(A, xp, 1);
        PROF_MARK(6);
        mma_tile<false>(acc[0], A[2], LO(F_QKV + 3));
        norm_consume(here(th), mu, rs0, rs1);
        if (row0 >= nvalid) rs0 = 0.f;
        if (row0 + 8 >= nvalid) rs1 = 0.f;
        mma_tile_fold<2 * CS_QKV - 6>(acc[0], A[3], LO(F_QKV + 4), mu);
        RELEASE(12, 15);
        mma_tile<false>(acc[1], A[2], HI(F_QKV + 3));
        mma_tile_fold<2 * CS_QKV - 4>(acc[1], A[3], HI(F_QKV + 4), mu);
        WG_WAIT(2); pin(acc[0]);
        scale_pack(acc[0], Q, rs0, rs1);
        tile_store(here(maddr), Q);
        fence_async_smem();
        bar_arrive(BAR_K, 160);
        mma_tile<false>(acc[2], A[1], HI(F_QKV + 1)); mma_tile<false>(acc[2], A[2], LO(F_QKV + 5));
        WG_WAIT(2); pin(acc[1]);
        scale_pack(acc[1], Q, rs0, rs1);
        tile_store(here(maddr) + TILE_BYTES, Q);
        fence_async_smem();
        bar_arrive(BAR_V, 160);
        mma_tile_fold<2 * CS_QKV - 2>(acc[2], A[3], HI(F_QKV + 5), mu);
        WG_WAIT(0); pin(acc[2]);
        scale_pack(acc[2], Q, rs0 * SM_SCALE_LOG2, rs1 * SM_SCALE_LOG2);
        res_store(here(res) - TILE_BYTES, Q);
        bar_arrive(BAR_Q, 256);
        acquire_n<F_SPARE, 2>();
        RELEASE(F_QKV, F_SPARE + 1);
      } else {
        bar_sync(BAR_Q, 256);
#pragma unroll
        for (int s = 0; s < 4; s++) lds128(res - TILE_BYTES + s * 512, Q[4 * s], Q[4 * s + 1], Q[4 * s + 2], Q[4 * s + 3]);
        if (w < 2) {
          const uint32_t v = w ? 0u : 0x3F803F80u;
#pragma unroll
          for (int s = 0; s < 4; s++) sts128(res - TILE_BYTES + s * 512, v, v, v, v);
          fence_async_smem();
        }
      }
      bar_sync(BAR_ATT, 256);
      PROF_MARK(7);

      const int dir = cw == 0 ? -1 : 1;
      uint32_t tap[15];
      {
        const uint32_t* dwp = (const uint32_t*)(dw + 64 * r) + lane + 7 * (DM / 2);
#pragma unroll
        for (int k = 0; k < 15; k++) tap[k] = __ldg(dwp + dir * (k - 7) * (DM / 2));
      }

      float O[36];
      {
        float S[2][32];
        uint32_t P[2][16], nm[4];
        pin(Q);
        WG_FENCE();
        qk_tile(S[0], Q, RING + (SM_STG >> 4));
        WG_COMMIT();
#pragma unroll
        for (int i = 0; i < 36; i++) O[i] = 0.f;
#pragma unroll
        for (int i = 0; i < 16; i++) P[1][i] = 0u;
        WG_WAIT(0); pin(S[0]);
        const float m0 = tile_max<0>(S[0]), m1 = tile_max<2>(S[0]);
        nm[0] = pack2(q ? 0.f : -m0, 0.f); nm[1] = pack2(q ? 0.f : -m1, 0.f); nm[2] = 0u; nm[3] = 0u;
#pragma unroll
        for (int k = 0; k < 15; k++) asm("mul.rn.bf16x2 %0, %0, %1;" : "+r"(tap[k]) : "r"(0x3F003F00u));
        pin(nm); pin(O); pin(P[1]); pin(tap);
        uint32_t sk = wg, sv = wg;
        mbar_wait(SM_BASE + SM_FULL + sk * 8, 0);
        PROF_MARK(8);
        WG_FENCE();
        qk_tile(S[0], Q, RING + sk * 1024);
        qk_shift(S[0], nm);
        WG_COMMIT();
        WG_WAIT(0); pin(S[0]);
#pragma unroll 1
        for (int it = 0; it < 4; it++) {
          attn_step(S[0], S[1], P[0], P[1], O, Q, nm, RING + sk * 1024 + 512, RING_V + (sv * 1024 + 512) * V_STEP);
          const uint32_t sn = it == 2 ? wg : sk + (it == 3 ? 2 : 4);
          mbar_wait(SM_BASE + SM_FULL + sn * 8, it >= 2);
          mbar_wait(SM_BASE + SM_FULL + (sk + 2) * 8, it == 3);
          WG_WAIT(0); pin(O); pin(S[1]); pin(P[1]);
          if (lane == 0) {
            mbar_arrive(SM_BASE + SM_EMPTY + sk * 8);
            if (it) mbar_arrive(SM_BASE + SM_EMPTY + sv * 8);
          }
          sv = sk + 2; sk = sn;
          attn_step(S[1], S[0], P[1], P[0], O, Q, nm, RING + sk * 1024, RING_V + (sv * 1024) * V_STEP);
          WG_WAIT(0); pin(O); pin(S[0]); pin(P[0]);
        }
        WG_FENCE();
        pv_tile(O, P[1], RING_V + (sv * 1024 + 512) * V_STEP, (uint64_t)wg << 22);
        WG_COMMIT();
        WG_WAIT(0); pin(O);
      }
      PROF_MARK(9);

      if (wg == 1) {
        const uint32_t mo = stg + here(th) * 16;
#pragma unroll
        for (int i = 0; i < 9; i++)
          sts128(mo + i * 2048 + (i >> 3) * 4096, __float_as_uint(O[4 * i]), __float_as_uint(O[4 * i + 1]), __float_as_uint(O[4 * i + 2]), __float_as_uint(O[4 * i + 3]));
        bar_arrive(BAR_MERGE, 256);
        norm_duty(sc, here(th), 0, 0.5f, 0);
      } else {
        const uint32_t mo = stg + here(th) * 16;
        bar_sync(BAR_MERGE, 256);
#pragma unroll
        for (int i = 8; i >= 0; i--) {
          uint32_t e[4];
          lds128(mo + i * 2048 + (i >> 3) * 4096, e[0], e[1], e[2], e[3]);
#pragma unroll
          for (int k = 0; k < 4; k++) O[4 * i + k] += __uint_as_float(e[k]);
        }
        const bool safe = O[32] > 0x1p-60f && O[32] < 0x1p60f && O[34] > 0x1p-60f && O[34] < 0x1p60f;
        if (__builtin_expect(__any_sync(0xffffffffu, !safe), 0)) attention_exact(O, Q, sc, batch * 4 + r, lane);
        const float i0 = rcp_hw(O[32]), i1 = rcp_hw(O[34]);
#pragma unroll
        for (int i = 0; i < 16; i++) { const float v = (i & 1) ? i1 : i0; A[0][i] = pack2(O[2 * i] * v, O[2 * i + 1] * v); }
        PROF_MARK(10);
        sent = proj_residual<F_WO, 6>(A, sc, xp, res, 0);
        PROF_MARK(12);
        float acc[2][32];
        mma_tile<true>(acc[0], A[0], LO(F_PW1)); mma_tile<true>(acc[1], A[0], HI(F_PW1));
        gather_first<1, X_AG0>(A, xp, 0, sent);
        mma_tile<false>(acc[1], A[1], HI(F_PW1 + 1)); mma_tile<false>(acc[0], A[1], LO(F_PW1 + 1));
        gather_rest<1, X_AG0>(A, xp, 0);
        PROF_MARK(13);
        mma_tile<false>(acc[1], A[2], HI(F_PW1 + 2));
        uint32_t mu[4];
        float rs0, rs1;
        norm_consume(here(th), mu, rs0, rs1);
        if (row0 >= nvalid) rs0 = 0.f;
        if (row0 + 8 >= nvalid) rs1 = 0.f;
        mma_tile_fold<2 * CS_PW1 + 2>(acc[1], A[3], HI(F_PW1 + 3), mu);
        RELEASE(F_KV + 14, F_WO + 1);
        mma_tile<false>(acc[0], A[2], LO(F_PW1 + 2));
        mma_tile_fold<2 * CS_PW1>(acc[0], A[3], LO(F_PW1 + 3), mu);
        WG_WAIT(2); pin(acc[1]);
#pragma unroll
        for (int i = 0; i < 32; i++) acc[1][i] = tanh_hw(acc[1][i] * ((i & 2) ? rs1 : rs0));
#pragma unroll
        for (int i = 0; i < 32; i++) { const float rs = (i & 2) ? rs1 : rs0; acc[1][i] = fmaf(acc[1][i], rs, rs); }
        pin(acc[1]);
        SCHED();
        WG_WAIT(0); pin(acc[0]);
#pragma unroll
        for (int i = 0; i < 16; i++) A[0][i] = pack2(acc[0][2 * i] * acc[1][2 * i], acc[0][2 * i + 1] * acc[1][2 * i + 1]);
        const uint32_t ga = stg + TILE_BYTES + here(mrow) * G_PITCH + (lane >> 4) * 16;
#pragma unroll
        for (int s = 0; s < 4; s++) stsm4(ga + s * 32, &A[0][4 * s]);
        RELEASE(F_PW1, F_PW1 + 3);
      }
      bar_sync(BAR_G, 256);
      PROF_MARK(14);

      {
        const int first = cw == 0 ? 14 : 8 * cw - 7;
        const uint32_t gsrc = stg + TILE_BYTES + first * G_PITCH + lane * 4;
        uint32_t in[22];
#pragma unroll
        for (int i = 0; i < 15; i++) in[i] = lds32(gsrc + dir * i * (int)G_PITCH);
        const bool edge = cw == 0 || cw == 7;
        const bool nbr = cw == 0 ? t > 0 : t < 15;
        if (edge) {
          if (nbr) {
            uint4* dst = &sc->x[b + 4 * dir][X_HALO + (cw == 0 ? 96 : 0) + lane];
            st_vec(dst, HALO_TAG, in[14], in[13], in[12]);
            st_vec(dst + 32, HALO_TAG, in[11], in[10], in[9]);
            st_vec(dst + 64, HALO_TAG, in[8], 0u, 0u);
          }
        } else {
#pragma unroll
          for (int i = 15; i < 22; i++) in[i] = lds32(gsrc + i * G_PITCH);
        }
        uint32_t cv[8];
#pragma unroll
        for (int i = 0; i < 15; i++)
#pragma unroll
          for (int o = 0; o < 8; o++) {
            if (i == o) asm("mul.rn.bf16x2 %0, %1, %2;" : "=r"(cv[o]) : "r"(in[i]), "r"(tap[0]));
            if (i > o) asm("fma.rn.bf16x2 %0, %1, %2, %0;" : "+r"(cv[o]) : "r"(in[i]), "r"(tap[i - o]));
          }
        pin(cv);
        PROF_MARK(45);
        if (edge) {
#pragma unroll
          for (int i = 15; i < 22; i++) in[i] = 0u;
          if (nbr) {
            const uint4* src = &sc->x[b][X_HALO + (cw == 0 ? 0 : 96) + lane];
            uint32_t e0, e1, e2, u0, u1, spin = 0;
#pragma unroll 1
            do {
              ld_vec(src, e0, in[15], in[16], in[17]);
              ld_vec(src + 32, e1, in[18], in[19], in[20]);
              ld_vec(src + 64, e2, in[21], u0, u1);
            } while (__any_sync(0xffffffffu, ((e0 ^ HALO_TAG) | (e1 ^ HALO_TAG) | (e2 ^ HALO_TAG)) != 0) && ++spin < SPIN_LIMIT);
          }
        }
#pragma unroll
        for (int i = 15; i < 22; i++)
#pragma unroll
          for (int o = 0; o < 8; o++)
            if (i - o <= 14) asm("fma.rn.bf16x2 %0, %1, %2, %0;" : "+r"(cv[o]) : "r"(in[i]), "r"(tap[i - o]));
        PROF_MARK(46);
        const uint32_t fl = cw == 0 ? 7 : 0;
        const uint32_t cdst = (stg + cw * 1024 + lane * 4) ^ (fl * 144);
#pragma unroll
        for (int o = 0; o < 8; o++) {
          const float a = bf_lo(cv[o]), c = bf_hi(cv[o]);
          sts32(cdst ^ (o * 144), pack2(fmaf(a, tanh_hw(a), a), fmaf(c, tanh_hw(c), c)));
        }
      }
      if (wg == 1) {
        bar_arrive(BAR_C, 256);
        norm_duty(sc, here(th), 1, 0.5f, 0);
        if (th == 0) ((volatile uint32_t*)sc->epoch)[b] += 1;
        break;
      }
      bar_sync(BAR_C, 256);
      tile_load(here(maddr), A[0]);
      PROF_MARK(15);
      sent = proj_residual<F_PW2, 2>(A, sc, xp, res, 1);
      PROF_MARK(17);
    }
  }
}

typedef CUresult (*EncodeFn)(CUtensorMap*, CUtensorMapDataType, cuuint32_t, void*, const cuuint64_t*, const cuuint64_t*,
                             const cuuint32_t*, const cuuint32_t*, CUtensorMapInterleave, CUtensorMapSwizzle,
                             CUtensorMapL2promotion, CUtensorMapFloatOOBfill);

void make_map(EncodeFn fn, CUtensorMap* m, const void* w, int rows, int cols, CUtensorMapSwizzle swz) {
  const cuuint64_t dims[2] = {(cuuint64_t)cols, (cuuint64_t)rows}, strides[1] = {(cuuint64_t)cols * 2};
  const cuuint32_t box[2] = {64, 64}, es[2] = {1, 1};
  fn(m, CU_TENSOR_MAP_DATA_TYPE_BFLOAT16, 2, const_cast<void*>(w), dims, strides, box, es, CU_TENSOR_MAP_INTERLEAVE_NONE,
     swz, CU_TENSOR_MAP_L2_PROMOTION_L2_128B, CU_TENSOR_MAP_FLOAT_OOB_FILL_NONE);
}

}

extern "C" void kernel_launch(void* const* d_in, const int* in_sizes, int n_in, void* d_out, int out_size) {
  static EncodeFn fn = nullptr;
  static Scratch* sc = nullptr;
  if (!fn) {
    void* f = nullptr;
    cudaDriverEntryPointQueryResult st;
    cudaGetDriverEntryPoint("cuTensorMapEncodeTiled", &f, cudaEnableDefault, &st);
    fn = (EncodeFn)f;
    void* raw = nullptr;
    cudaGetSymbolAddress(&raw, g_scratch);
    sc = (Scratch*)(((uintptr_t)raw + X_ALIGN - 1) & ~(uintptr_t)(X_ALIGN - 1));
    cudaFuncSetAttribute(conformer_kernel, cudaFuncAttributeMaxDynamicSharedMemorySize, SM_TOTAL);
  }
  typedef const __nv_bfloat16* W;
  const CUtensorMapSwizzle S = CU_TENSOR_MAP_SWIZZLE_128B;
  Params p;
  {
    const cuuint64_t dims[4] = {64, T_SEQ, 4, 2}, strides[3] = {512, 128, T_SEQ * 512};
    const cuuint32_t box[4] = {64, 64, 4, 1}, es[4] = {1, 1, 1, 1};
    fn(&p.map[M_X], CU_TENSOR_MAP_DATA_TYPE_BFLOAT16, 4, d_in[0], dims, strides, box, es, CU_TENSOR_MAP_INTERLEAVE_NONE, S,
       CU_TENSOR_MAP_L2_PROMOTION_L2_128B, CU_TENSOR_MAP_FLOAT_OOB_FILL_NONE);
  }
  make_map(fn, &p.map[M_FF1A], d_in[1], 256, 1024, S);
  make_map(fn, &p.map[M_FF1B], d_in[2], 1024, 256, S);
  make_map(fn, &p.map[M_QKV], d_in[3], 256, 768, S);
  make_map(fn, &p.map[M_KV], sc->kv, 16384, 64, CU_TENSOR_MAP_SWIZZLE_NONE);
  make_map(fn, &p.map[M_WO], d_in[4], 256, 256, S);
  make_map(fn, &p.map[M_PW1], d_in[5], 256, 512, S);
  make_map(fn, &p.map[M_PW2], d_in[7], 256, 256, S);
  make_map(fn, &p.map[M_FF2A], d_in[8], 256, 1024, S);
  make_map(fn, &p.map[M_FF2B], d_in[9], 1024, 256, S);
  p.w_ff1b = (W)d_in[2]; p.w_qkv = (W)d_in[3]; p.w_o = (W)d_in[4]; p.w_pw1 = (W)d_in[5];
  p.w_pw2 = (W)d_in[7]; p.w_ff2a = (W)d_in[8]; p.w_ff2b = (W)d_in[9];

  cudaLaunchConfig_t cfg = {};
  cfg.gridDim = dim3(NCTA);
  cfg.blockDim = dim3(384);
  cfg.dynamicSmemBytes = SM_TOTAL;
  cfg.stream = cudaStreamPerThread;
  cudaLaunchAttribute at[1];
  at[0].id = cudaLaunchAttributeCooperative;
  at[0].val.cooperative = 1;
  cfg.attrs = at;
  cfg.numAttrs = 1;
  cudaLaunchKernelEx(&cfg, conformer_kernel, sc, (__nv_bfloat16*)d_out, (W)d_in[6], (W)d_in[0], (W)d_in[1], p);
}
```

```cpp
#include <cuda_runtime.h>
#include <cuda_bf16.h>
#include <cuda.h>
#include <stdint.h>

namespace {

constexpr int T_SEQ = 1000;
constexpr int DM = 256;
constexpr int NCTA = 128;
constexpr int NSTAGE = 12;
constexpr uint32_t STAGE_BYTES = 16384;
constexpr uint32_t TILE_BYTES = 8192;
constexpr uint32_t SM_BASE = 1024;
constexpr uint32_t SM_STG = NSTAGE * STAGE_BYTES;
constexpr uint32_t SM_FULL = SM_STG + 32768;
constexpr uint32_t SM_EMPTY = SM_FULL + 96;
constexpr uint32_t SM_XBAR = SM_FULL + 192;
constexpr uint32_t SM_EYE = SM_FULL + 256;
constexpr uint32_t SM_ONE = SM_FULL + 640;
constexpr uint32_t SM_CS = SM_FULL + 768;
constexpr uint32_t SM_TOTAL = SM_FULL + 3072;
constexpr int CS_FF2 = 0, CS_PW1 = 4, CS_QKV = 6;
constexpr uint32_t SPIN_LIMIT = 1u << 16;
constexpr float LN_EPS = 1e-5f;
constexpr float SM_SCALE_LOG2 = 0.125f * 1.4426950408889634f;
constexpr uint32_t G_PITCH = 144;

constexpr int F_QKV = 16, F_SPARE = 22, F_KV = 24, F_WO = 40, F_PW1 = 42, F_PW2 = 46, F_TOTAL = 64;
enum { M_FF1A, M_FF1B, M_QKV, M_KV, M_WO, M_PW1, M_PW2, M_FF2A, M_FF2B, M_X, M_COUNT };
enum { BAR_K = 1, BAR_V, BAR_Q, BAR_MERGE, BAR_G, BAR_C, BAR_WG1, BAR_RDY, BAR_ST, BAR_ATT, BAR_INIT, BAR_RDY1, BAR_X, BAR_RES };

struct Params {
  CUtensorMap map[M_COUNT];
  const __nv_bfloat16 *w_ff1b, *w_qkv, *w_o, *w_pw1, *w_pw2, *w_ff2a, *w_ff2b;
};

constexpr int X_RS = 0, X_AG1 = X_RS, X_HALO = X_RS + 512, X_CLEAR = 1024, X_AG0 = 1536, X_ST = 2048, X_SIZE = 4096;
constexpr uint32_t HALO_TAG = 0xFFFF0001u;
struct Scratch {
  uint4 x[NCTA][X_SIZE];
  uint4 kv[8][2][16][512];
  uint4 cs[576];
  uint32_t flag[8][32][32];
  uint32_t ready[NCTA][32];
  uint32_t epoch[NCTA];
};
constexpr size_t X_ALIGN = 4 * X_SIZE * sizeof(uint4);
__device__ uint8_t g_scratch[sizeof(Scratch) + X_ALIGN];
#define PROF_TIME(i)
#define PROF_MARK(i)

__device__ __forceinline__ void mbar_init(uint32_t bar, uint32_t cnt) {
  asm volatile("mbarrier.init.shared::cta.b64 [%0], %1;" :: "r"(bar), "r"(cnt) : "memory");
}
__device__ __forceinline__ void mbar_wait(uint32_t bar, uint32_t parity) {
  asm volatile("{\n.reg .pred p;\n.reg .u32 c;\nmov.u32 c, 0;\n"
               "WAIT_LOOP:\nmbarrier.try_wait.parity.shared::cta.b64 p, [%0], %1;\n@p bra WAIT_DONE;\n"
               "add.u32 c, c, 1;\nsetp.lt.u32 p, c, %2;\n@p bra WAIT_LOOP;\nWAIT_DONE:\n}"
               :: "r"(bar), "r"(parity), "n"(SPIN_LIMIT) : "memory");
}
__device__ __forceinline__ void mbar_arrive(uint32_t bar) {
  asm volatile("mbarrier.arrive.shared::cta.b64 _, [%0];" :: "r"(bar) : "memory");
}
#define bar_sync(id, n) asm volatile("bar.sync %0, %1;" :: "n"((int)(id)), "n"(n) : "memory")
#define bar_arrive(id, n) asm volatile("bar.arrive %0, %1;" :: "n"((int)(id)), "n"(n) : "memory")
__device__ __forceinline__ void fence_async_smem() { asm volatile("fence.proxy.async.shared::cta;" ::: "memory"); }

__device__ __forceinline__ void st_vec(uint4* p, uint32_t a, uint32_t b, uint32_t c, uint32_t d) {
  asm volatile("{\n.reg .b128 v;\n.reg .b64 lo, hi;\nmov.b64 lo, {%1, %2};\nmov.b64 hi, {%3, %4};\nmov.b128 v, {lo, hi};\n"
               "st.relaxed.gpu.global.b128 [%0], v;\n}" :: "l"(p), "r"(a), "r"(b), "r"(c), "r"(d) : "memory");
}
__device__ __forceinline__ void ld_vec(const uint4* p, uint32_t& a, uint32_t& b, uint32_t& c, uint32_t& d) {
  asm volatile("{\n.reg .b128 v;\n.reg .b64 lo, hi;\nld.relaxed.gpu.global.b128 v, [%4];\nmov.b128 {lo, hi}, v;\n"
               "mov.b64 {%0, %1}, lo;\nmov.b64 {%2, %3}, hi;\n}" : "=r"(a), "=r"(b), "=r"(c), "=r"(d) : "l"(p) : "memory");
}
__device__ __forceinline__ void sts128(uint32_t a, uint32_t x, uint32_t y, uint32_t z, uint32_t w) {
  asm volatile("st.shared.v4.u32 [%0], {%1, %2, %3, %4};" :: "r"(a), "r"(x), "r"(y), "r"(z), "r"(w) : "memory");
}
__device__ __forceinline__ void lds128(uint32_t a, uint32_t& x, uint32_t& y, uint32_t& z, uint32_t& w) {
  asm volatile("ld.shared.v4.u32 {%0, %1, %2, %3}, [%4];" : "=r"(x), "=r"(y), "=r"(z), "=r"(w) : "r"(a) : "memory");
}
__device__ __forceinline__ uint32_t lds32(uint32_t a) {
  uint32_t x; asm volatile("ld.shared.u32 %0, [%1];" : "=r"(x) : "r"(a) : "memory"); return x;
}
__device__ __forceinline__ void sts32(uint32_t a, uint32_t x) { asm volatile("st.shared.u32 [%0], %1;" :: "r"(a), "r"(x) : "memory"); }
__device__ __forceinline__ void sts64(uint32_t a, uint32_t x, uint32_t y) {
  asm volatile("st.shared.v2.u32 [%0], {%1, %2};" :: "r"(a), "r"(x), "r"(y) : "memory");
}
__device__ __forceinline__ void stsm4(uint32_t a, const uint32_t* r) {
  asm volatile("stmatrix.sync.aligned.m8n8.x4.shared.b16 [%0], {%1, %2, %3, %4};" :: "r"(a), "r"(r[0]), "r"(r[1]), "r"(r[2]), "r"(r[3]) : "memory");
}
__device__ __forceinline__ void ldsm4(uint32_t a, uint32_t* r) {
  asm volatile("ldmatrix.sync.aligned.m8n8.x4.shared.b16 {%0, %1, %2, %3}, [%4];" : "=r"(r[0]), "=r"(r[1]), "=r"(r[2]), "=r"(r[3]) : "r"(a) : "memory");
}
__device__ __forceinline__ uint32_t pack2(float lo, float hi) {
  uint32_t r; asm("cvt.rn.bf16x2.f32 %0, %1, %2;" : "=r"(r) : "f"(hi), "f"(lo)); return r;
}
__device__ __forceinline__ float bf_lo(uint32_t w) { return __uint_as_float(w << 16); }
__device__ __forceinline__ float bf_hi(uint32_t w) { return __uint_as_float(w & 0xffff0000u); }
__device__ __forceinline__ float tanh_hw(float x) { float y; asm volatile("tanh.approx.f32 %0, %1;" : "=f"(y) : "f"(x)); return y; }
__device__ __forceinline__ float rcp_hw(float x) { float y; asm("rcp.approx.ftz.f32 %0, %1;" : "=f"(y) : "f"(x)); return y; }
__device__ __forceinline__ float ex2_hw(float x) { float y; asm("ex2.approx.ftz.f32 %0, %1;" : "=f"(y) : "f"(x)); return y; }

__device__ __forceinline__ uint32_t here(uint32_t v) { asm volatile("" : "+r"(v)); return v; }

#define SCHED() asm volatile("pmevent 1;" ::: "memory")
#define WG_FENCE() asm volatile("wgmma.fence.sync.aligned;" ::: "memory")
#define WG_COMMIT() asm volatile("wgmma.commit_group.sync.aligned;" ::: "memory")
#define WG_WAIT(n) asm volatile("wgmma.wait_group.sync.aligned %0;" :: "n"(n) : "memory")

template <int N> __device__ __forceinline__ void pin(float (&d)[N]) {
#pragma unroll
  for (int i = 0; i < N; i++) asm volatile("" : "+f"(d[i]) :: "memory");
}
template <int N> __device__ __forceinline__ void pin(uint32_t (&d)[N]) {
#pragma unroll
  for (int i = 0; i < N; i++) asm volatile("" : "+r"(d[i]) :: "memory");
}

#define WG_D32 "{%0, %1, %2, %3, %4, %5, %6, %7, %8, %9, %10, %11, %12, %13, %14, %15, %16, %17, %18, %19, %20, %21, %22, %23, %24, %25, %26, %27, %28, %29, %30, %31}"
template <int TB> __device__ __forceinline__ void wgmma64_acc(float (&d)[32], const uint32_t* a, uint64_t db) {
  asm volatile("wgmma.mma_async.sync.aligned.m64n64k16.f32.bf16.bf16 " WG_D32 ", {%32, %33, %34, %35}, %36, 1, 1, 1, %37;"
    : "+f"(d[0]), "+f"(d[1]), "+f"(d[2]), "+f"(d[3]), "+f"(d[4]), "+f"(d[5]), "+f"(d[6]), "+f"(d[7]),
      "+f"(d[8]), "+f"(d[9]), "+f"(d[10]), "+f"(d[11]), "+f"(d[12]), "+f"(d[13]), "+f"(d[14]), "+f"(d[15]),
      "+f"(d[16]), "+f"(d[17]), "+f"(d[18]), "+f"(d[19]), "+f"(d[20]), "+f"(d[21]), "+f"(d[22]), "+f"(d[23]),
      "+f"(d[24]), "+f"(d[25]), "+f"(d[26]), "+f"(d[27]), "+f"(d[28]), "+f"(d[29]), "+f"(d[30]), "+f"(d[31])
    : "r"(a[0]), "r"(a[1]), "r"(a[2]), "r"(a[3]), "l"(db), "n"(TB));
}
__device__ __forceinline__ void wgmma64_reuse(float (&d)[32], const uint32_t* a, uint64_t db, uint32_t zero) {
  asm volatile("{\n.reg .pred p;\nsetp.ne.u32 p, %37, 0;\nwgmma.mma_async.sync.aligned.m64n64k16.f32.bf16.bf16 " WG_D32 ", {%32, %33, %34, %35}, %36, p, 1, 1, 1;\n}"
    : "+f"(d[0]), "+f"(d[1]), "+f"(d[2]), "+f"(d[3]), "+f"(d[4]), "+f"(d[5]), "+f"(d[6]), "+f"(d[7]),
      "+f"(d[8]), "+f"(d[9]), "+f"(d[10]), "+f"(d[11]), "+f"(d[12]), "+f"(d[13]), "+f"(d[14]), "+f"(d[15]),
      "+f"(d[16]), "+f"(d[17]), "+f"(d[18]), "+f"(d[19]), "+f"(d[20]), "+f"(d[21]), "+f"(d[22]), "+f"(d[23]),
      "+f"(d[24]), "+f"(d[25]), "+f"(d[26]), "+f"(d[27]), "+f"(d[28]), "+f"(d[29]), "+f"(d[30]), "+f"(d[31])
    : "r"(a[0]), "r"(a[1]), "r"(a[2]), "r"(a[3]), "l"(db), "r"(zero));
}
template <int TB> __device__ __forceinline__ void wgmma64_set(float (&d)[32], const uint32_t* a, uint64_t db) {
  asm volatile("wgmma.mma_async.sync.aligned.m64n64k16.f32.bf16.bf16 " WG_D32 ", {%32, %33, %34, %35}, %36, 0, 1, 1, %37;"
    : "=f"(d[0]), "=f"(d[1]), "=f"(d[2]), "=f"(d[3]), "=f"(d[4]), "=f"(d[5]), "=f"(d[6]), "=f"(d[7]),
      "=f"(d[8]), "=f"(d[9]), "=f"(d[10]), "=f"(d[11]), "=f"(d[12]), "=f"(d[13]), "=f"(d[14]), "=f"(d[15]),
      "=f"(d[16]), "=f"(d[17]), "=f"(d[18]), "=f"(d[19]), "=f"(d[20]), "=f"(d[21]), "=f"(d[22]), "=f"(d[23]),
      "=f"(d[24]), "=f"(d[25]), "=f"(d[26]), "=f"(d[27]), "=f"(d[28]), "=f"(d[29]), "=f"(d[30]), "=f"(d[31])
    : "r"(a[0]), "r"(a[1]), "r"(a[2]), "r"(a[3]), "l"(db), "n"(TB));
}

__device__ __forceinline__ void wgmma72_acc(float (&d)[36], const uint32_t* a, uint64_t db) {
  asm volatile("wgmma.mma_async.sync.aligned.m64n72k16.f32.bf16.bf16 {%0, %1, %2, %3, %4, %5, %6, %7, %8, %9, %10, %11, %12, %13, %14, %15, %16, %17, %18, %19, %20, %21, %22, %23, %24, %25, %26, %27, %28, %29, %30, %31, %32, %33, %34, %35}, {%36, %37, %38, %39}, %40, 1, 1, 1, 1;"
    : "+f"(d[0]), "+f"(d[1]), "+f"(d[2]), "+f"(d[3]), "+f"(d[4]), "+f"(d[5]), "+f"(d[6]), "+f"(d[7]), "+f"(d[8]),
      "+f"(d[9]), "+f"(d[10]), "+f"(d[11]), "+f"(d[12]), "+f"(d[13]), "+f"(d[14]), "+f"(d[15]), "+f"(d[16]), "+f"(d[17]),
      "+f"(d[18]), "+f"(d[19]), "+f"(d[20]), "+f"(d[21]), "+f"(d[22]), "+f"(d[23]), "+f"(d[24]), "+f"(d[25]), "+f"(d[26]),
      "+f"(d[27]), "+f"(d[28]), "+f"(d[29]), "+f"(d[30]), "+f"(d[31]), "+f"(d[32]), "+f"(d[33]), "+f"(d[34]), "+f"(d[35])
    : "r"(a[0]), "r"(a[1]), "r"(a[2]), "r"(a[3]), "l"(db));
}
__device__ __forceinline__ void wgmma16_acc(float* d, const uint32_t* a, uint64_t db) {
  asm volatile("wgmma.mma_async.sync.aligned.m64n16k16.f32.bf16.bf16 {%0, %1, %2, %3, %4, %5, %6, %7}, {%8, %9, %10, %11}, %12, 1, 1, 1, 0;"
    : "+f"(d[0]), "+f"(d[1]), "+f"(d[2]), "+f"(d[3]), "+f"(d[4]), "+f"(d[5]), "+f"(d[6]), "+f"(d[7])
    : "r"(a[0]), "r"(a[1]), "r"(a[2]), "r"(a[3]), "l"(db));
}
__device__ __forceinline__ void hmma(float (&d)[4], const uint32_t* a, uint32_t b0, uint32_t b1) {
  asm("mma.sync.aligned.m16n8k16.row.col.f32.bf16.bf16.f32 {%0, %1, %2, %3}, {%4, %5, %6, %7}, {%8, %9}, {%0, %1, %2, %3};"
    : "+f"(d[0]), "+f"(d[1]), "+f"(d[2]), "+f"(d[3]) : "r"(a[0]), "r"(a[1]), "r"(a[2]), "r"(a[3]), "r"(b0), "r"(b1));
}

__device__ __forceinline__ void hmma8(float (&d)[4], const uint32_t* a, uint32_t b0) {
  asm("mma.sync.aligned.m16n8k8.row.col.f32.bf16.bf16.f32 {%0, %1, %2, %3}, {%4, %5}, {%6}, {%0, %1, %2, %3};"
    : "+f"(d[0]), "+f"(d[1]), "+f"(d[2]), "+f"(d[3]) : "r"(a[0]), "r"(a[1]), "r"(b0));
}

template <bool FIRST> __device__ __forceinline__ void mma_tile(float (&d)[32], const uint32_t (&a)[16], uint64_t db) {
  WG_FENCE();
#pragma unroll
  for (int s = 0; s < 4; s++) {
    if (FIRST && s == 0) wgmma64_set<1>(d, &a[0], db); else wgmma64_acc<1>(d, &a[4 * s], db + s * 128);
  }
  WG_COMMIT();
}
__device__ __forceinline__ void mma_tile_reuse(float (&d)[32], const uint32_t (&a)[16], uint64_t db) {
  WG_FENCE();
  wgmma64_reuse(d, &a[0], db, blockIdx.y);
#pragma unroll
  for (int s = 1; s < 4; s++) wgmma64_acc<1>(d, &a[4 * s], db + s * 128);
  WG_COMMIT();
}
template <int ROW> __device__ __forceinline__ void mma_tile_fold(float (&d)[32], const uint32_t (&a)[16], uint64_t db, const uint32_t (&mu)[4]) {
  WG_FENCE();
#pragma unroll
  for (int s = 0; s < 4; s++) wgmma64_acc<1>(d, &a[4 * s], db + s * 128);
  wgmma64_acc<1>(d, mu, (uint64_t)((SM_BASE + SM_CS + ROW * 128) >> 4) | (uint64_t(1) << 16) | (uint64_t(1) << 62));
  WG_COMMIT();
}
__device__ __forceinline__ void mma_add_half(float (&d)[32], const uint32_t (&a)[16]) {
  const uint64_t db = (uint64_t)((SM_BASE + SM_EYE) >> 4) | (uint64_t(8) << 16) | (uint64_t(8) << 32);
  WG_FENCE();
#pragma unroll
  for (int s = 0; s < 4; s++) wgmma16_acc(&d[8 * s], &a[4 * s], db);
  WG_COMMIT();
}
#define ACQUIRE(f) mbar_wait(SM_BASE + SM_FULL + ((f) % NSTAGE) * 8, ((f) / NSTAGE) & 1)
template <int F, int N> __device__ __forceinline__ void acquire_n() {
  static_assert(F % NSTAGE + N <= NSTAGE, "stages must not wrap");
  uint32_t spin = 0, ok;
  do {
    ok = 1;
#pragma unroll
    for (int i = 0; i < N; i++)
      asm volatile("{\n.reg .pred p;\nmbarrier.try_wait.parity.shared::cta.b64 p, [%1], %2;\nselp.u32 %0, %0, 0, p;\n}"
                   : "+r"(ok) : "r"(SM_BASE + SM_FULL + (F % NSTAGE + i) * 8), "r"((F / NSTAGE) & 1) : "memory");
  } while (!ok && ++spin < SPIN_LIMIT);
}
#define RELEASE(f0, f1) do { if (lane == 0) { _Pragma("unroll") for (int f_ = (f0); f_ <= (f1); f_++) mbar_arrive(SM_BASE + SM_EMPTY + (f_ % NSTAGE) * 8); } } while (0)
constexpr uint64_t RING = (uint64_t)(SM_BASE >> 4) | (uint64_t(1) << 16) | (uint64_t(64) << 32) | (uint64_t(1) << 62);
#define LO(f) (RING + ((f) % NSTAGE) * 1024)
#define HI(f) (RING + ((f) % NSTAGE) * 1024 + 512)

template <int C> __device__ __forceinline__ uint4* peer(uint4* p) {
  asm volatile("" : "+l"(p));
  return (uint4*)((uintptr_t)p ^ (C * X_SIZE * sizeof(uint4)));
}
__device__ __forceinline__ uint32_t clock_now() { uint32_t c; asm volatile("mov.u32 %0, %%clock;" : "=r"(c) :: "memory"); return c; }
__device__ __forceinline__ void publish(uint4* dst, uint32_t (&a)[16], uint32_t tag) {
#pragma unroll
  for (int s = 0; s < 4; s++) a[4 * s] = (a[4 * s] & ~1u) | tag;
  pin(a);
  SCHED();
#pragma unroll
  for (int s = 0; s < 4; s++) st_vec(dst + s * 128, a[4 * s], a[4 * s + 1], a[4 * s + 2], a[4 * s + 3]);
  SCHED();
}
__device__ __forceinline__ void fetch(const uint4* src, uint32_t (&a)[16]) {
#pragma unroll
  for (int s = 0; s < 4; s++) ld_vec(src + s * 128, a[4 * s], a[4 * s + 1], a[4 * s + 2], a[4 * s + 3]);
}
__device__ __forceinline__ uint32_t miss(const uint32_t (&a)[16], uint32_t tag) {
  return (a[0] ^ tag) | (a[4] ^ tag) | (a[8] ^ tag) | (a[12] ^ tag);
}
__device__ __forceinline__ bool stale(uint32_t v) { return __any_sync(0xffffffffu, here(v) & 1u); }
__device__ __forceinline__ void confirm(const uint4* src, uint32_t (&a)[16], uint32_t tag) {
  uint32_t spin = 0;
  while (__builtin_expect(stale(miss(a, tag)), 0) && ++spin < SPIN_LIMIT) fetch(src, a);
}
constexpr uint32_t GATHER_DELAY = 400;
template <int C0, int C1, int SLOT> __device__ __forceinline__ void gather_wait(uint32_t (&A)[4][16], uint4* xp, uint32_t tag) {
  uint32_t spin = 0;
  while (__builtin_expect(stale(miss(A[C0], tag) | miss(A[C1], tag)), 0) && ++spin < SPIN_LIMIT) {
    fetch(peer<C0>(xp) + SLOT, A[C0]);
    if (C1 != C0) fetch(peer<C1>(xp) + SLOT, A[C1]);
  }
}
template <int C, int SLOT> __device__ __forceinline__ void gather_first(uint32_t (&A)[4][16], uint4* xp, uint32_t tag, uint32_t sent) {
  while (clock_now() - sent < GATHER_DELAY) {}
  fetch(peer<1>(xp) + SLOT, A[1]); fetch(peer<2>(xp) + SLOT, A[2]); fetch(peer<3>(xp) + SLOT, A[3]);
  gather_wait<1, C, SLOT>(A, xp, tag);
}
template <int C, int SLOT> __device__ __forceinline__ void gather_rest(uint32_t (&A)[4][16], uint4* xp, uint32_t tag) {
  SCHED();
  gather_wait<C + 1, 3, SLOT>(A, xp, tag);
}
__device__ __forceinline__ void pack_acc(const float (&d)[32], uint32_t (&a)[16]) {
#pragma unroll
  for (int i = 0; i < 16; i++) a[i] = pack2(d[2 * i], d[2 * i + 1]);
}
__device__ __forceinline__ void res_store(uint32_t slot, const uint32_t (&a)[16]) {
#pragma unroll
  for (int s = 0; s < 4; s++) sts128(slot + s * 512, a[4 * s], a[4 * s + 1], a[4 * s + 2], a[4 * s + 3]);
}
__device__ __forceinline__ void res_load(uint32_t slot, float (&d)[32]) {
  uint32_t a[16];
#pragma unroll
  for (int s = 0; s < 4; s++) lds128(slot + s * 512, a[4 * s], a[4 * s + 1], a[4 * s + 2], a[4 * s + 3]);
#pragma unroll
  for (int i = 0; i < 16; i++) { d[2 * i] = bf_lo(a[i]); d[2 * i + 1] = bf_hi(a[i]); }
  pin(d);
}
__device__ __forceinline__ void tile_store(uint32_t maddr, const uint32_t (&a)[16]) {
#pragma unroll
  for (int s = 0; s < 4; s++) stsm4(maddr ^ (s << 5), &a[4 * s]);
}
__device__ __forceinline__ void tile_load(uint32_t maddr, uint32_t (&a)[16]) {
#pragma unroll
  for (int s = 0; s < 4; s++) ldsm4(maddr ^ (s << 5), &a[4 * s]);
}

struct RowAcc { float s[4], u[2][4], v[2][4]; };
__device__ __forceinline__ void row_acc(RowAcc& t, const uint32_t (&a)[16]) {
#pragma unroll
  for (int s = 0; s < 8; s++) {
    if ((s & 1) == 0) hmma(t.s, &a[2 * s], 0x3F803F80u, 0x3F803F80u);
    hmma8(t.u[s & 1], &a[2 * s], a[2 * s]);
    hmma8(t.v[s & 1], &a[2 * s], a[2 * s + 1]);
  }
}
__device__ __forceinline__ float2 row_squares(const RowAcc& t, bool odd) {
  return make_float2(odd ? t.u[0][1] + t.u[1][1] : t.u[0][0] + t.u[1][0], odd ? t.v[0][3] + t.v[1][3] : t.v[0][2] + t.v[1][2]);
}
__device__ __forceinline__ void stat_publish(const uint32_t (&a)[16], Scratch* sc, uint32_t th, uint32_t tag) {
  RowAcc t = {};
  row_acc(t, a);
  const float2 q = row_squares(t, th & 4);
  if ((th & 3) == ((th >> 3) & 3))
    st_vec(&sc->x[blockIdx.x][X_ST + (th >> 2)], (__float_as_uint(t.s[0]) & ~1u) | tag, __float_as_uint(q.x), __float_as_uint(t.s[2]), __float_as_uint(q.y));
}
struct RowNorm { float m0, rs0, m1, rs1; };
__device__ __forceinline__ RowNorm row_norm(float s0, float q0, float s1, float q1, float scale) {
  RowNorm n;
  n.m0 = s0 * (1.f / DM); n.m1 = s1 * (1.f / DM);
  n.rs0 = scale * rsqrtf(fmaxf(fmaf(-n.m0, n.m0, q0 * (1.f / DM)), 0.f) + LN_EPS);
  n.rs1 = scale * rsqrtf(fmaxf(fmaf(-n.m1, n.m1, q1 * (1.f / DM)), 0.f) + LN_EPS);
  return n;
}
__device__ __forceinline__ RowNorm stat_gather(Scratch* sc, uint32_t th, uint32_t tag, float scale) {
  const uint4* src = &sc->x[blockIdx.x & ~3u][X_ST + (th >> 2)];
  uint32_t v[16], spin = 0;
  do {
#pragma unroll
    for (int j = 0; j < 4; j++) ld_vec(src + j * X_SIZE, v[4 * j], v[4 * j + 1], v[4 * j + 2], v[4 * j + 3]);
  } while (stale(miss(v, tag)) && ++spin < SPIN_LIMIT);
  float f[4];
#pragma unroll
  for (int i = 0; i < 4; i++)
    f[i] = (__uint_as_float(v[i]) + __uint_as_float(v[4 + i])) + (__uint_as_float(v[8 + i]) + __uint_as_float(v[12 + i]));
  return row_norm(f[0], f[1], f[2], f[3], scale);
}
constexpr uint32_t SM_NORM = SM_BASE + SM_STG + 2 * TILE_BYTES + 4096;
__device__ __forceinline__ void norm_produce(const RowNorm& n, uint32_t th, uint32_t qsel) {
  const bool sel = (th & 3) == qsel;
  const float a = sel ? -n.m0 : 0.f, c = sel ? -n.m1 : 0.f;
  const uint32_t ah = pack2(a, a), ch = pack2(c, c);
  const float al = a - bf_lo(ah), cl = c - bf_lo(ch);
  sts128(SM_NORM + th * 16, ah, ch, pack2(al, al), pack2(cl, cl));
  sts64(SM_NORM + 2048 + th * 8, __float_as_uint(n.rs0), __float_as_uint(n.rs1));
  bar_arrive(BAR_ST, 256);
}
__device__ __forceinline__ void norm_duty(Scratch* sc, uint32_t th, uint32_t tag, float scale, uint32_t qsel) {
  bar_sync(BAR_RES, 256);
  norm_produce(stat_gather(sc, th, tag, scale), th, qsel);
}
__device__ __forceinline__ void norm_consume(uint32_t th, uint32_t (&mu)[4], float& rs0, float& rs1) {
  bar_sync(BAR_ST, 256);
  lds128(SM_NORM + th * 16, mu[0], mu[1], mu[2], mu[3]);
  asm volatile("ld.shared.v2.f32 {%0, %1}, [%2];" : "=f"(rs0), "=f"(rs1) : "r"(SM_NORM + 2048 + th * 8) : "memory");
}
__device__ __forceinline__ void scale_pack(const float (&d)[32], uint32_t (&a)[16], float rs0, float rs1) {
#pragma unroll
  for (int i = 0; i < 16; i++) { const float rs = (i & 1) ? rs1 : rs0; a[i] = pack2(d[2 * i] * rs, d[2 * i + 1] * rs); }
}
template <int S> __device__ __forceinline__ void silu_seg(float (&acc)[4][32], float (&tn)[2][4], uint32_t (&H)[4][16], float rs0, float rs1) {
  if (S >= 2) {
    const float* h = &acc[(S - 2) >> 3][4 * ((S - 2) & 7)];
    const float* v = tn[S & 1];
    uint32_t* o = &H[(S - 2) >> 3][2 * ((S - 2) & 7)];
    o[0] = pack2(fmaf(h[0], v[0], h[0]), fmaf(h[1], v[1], h[1]));
    o[1] = pack2(fmaf(h[2], v[2], h[2]), fmaf(h[3], v[3], h[3]));
    asm volatile("" : "+r"(o[0]), "+r"(o[1]));
  }
  if (S >= 1 && S <= 32) {
#pragma unroll
    for (int k = 0; k < 4; k++) tn[(S - 1) & 1][k] = tanh_hw(acc[((S - 1) >> 3) & 3][4 * ((S - 1) & 7) + k]);
  }
  if (S < 32) {
    float* h = &acc[(S >> 3) & 3][4 * (S & 7)];
    h[0] *= rs0; h[1] *= rs0; h[2] *= rs1; h[3] *= rs1;
    asm volatile("" : "+f"(h[0]), "+f"(h[1]), "+f"(h[2]), "+f"(h[3]));
  }
  SCHED();
}
template <int S0, int S1> __device__ __forceinline__ void silu_segs(float (&acc)[4][32], float (&tn)[2][4], uint32_t (&H)[4][16], float rs0, float rs1) {
  silu_seg<S0>(acc, tn, H, rs0, rs1);
  if constexpr (S0 + 1 < S1) silu_segs<S0 + 1, S1>(acc, tn, H, rs0, rs1);
}
template <int HALF> __device__ __forceinline__ void send_half(uint4* dst, const float (&d)[32], uint32_t tag) {
  uint32_t o[8];
#pragma unroll
  for (int i = 0; i < 8; i++) o[i] = pack2(d[16 * HALF + 2 * i], d[16 * HALF + 2 * i + 1]);
  o[0] = (o[0] & ~1u) | tag; o[4] = (o[4] & ~1u) | tag;
  pin(o);
  SCHED();
  st_vec(dst + HALF * 256, o[0], o[1], o[2], o[3]);
  st_vec(dst + HALF * 256 + 128, o[4], o[5], o[6], o[7]);
  SCHED();
}
__device__ __forceinline__ uint32_t send_residual(uint32_t (&a)[16], Scratch* sc, uint4* xp, uint32_t res, uint32_t tag) {
  const uint32_t exact[4] = {a[0], a[4], a[8], a[12]};
  publish(xp + X_AG0, a, tag);
  const uint32_t sent = clock_now();
  stat_publish(a, sc, threadIdx.x, tag);
  res_store(res, a);
#pragma unroll
  for (int s = 0; s < 4; s++) sts32(res + s * 512, exact[s]);
  bar_arrive(BAR_RES, 256);
  return sent;
}
template <int F, int N> __device__ __forceinline__ uint32_t proj_residual(uint32_t (&A)[4][16], Scratch* sc, uint4* xp, uint32_t res, uint32_t tag) {
  float acc[32];
  publish(xp + X_AG1, A[0], tag);
  const uint32_t sent = clock_now();
  acquire_n<F, N>();
  if (F == F_PW2) acquire_n<0, 5>();
  res_load(res, acc);
  mma_tile<false>(acc, A[0], LO(F));
  gather_first<2, X_AG1>(A, xp, tag, sent);
  mma_tile<false>(acc, A[1], HI(F));
  mma_tile<false>(acc, A[2], LO(F + 1));
  gather_rest<2, X_AG1>(A, xp, tag);
  PROF_MARK(F == F_WO ? 11 : 16);
  mma_tile<false>(acc, A[3], HI(F + 1));
  WG_WAIT(0); pin(acc);
  pack_acc(acc, A[0]);
  return send_residual(A[0], sc, xp, res, tag);
}

__device__ __forceinline__ void qk_tile(float (&S)[32], const uint32_t (&Q)[16], uint64_t dk) {
#pragma unroll
  for (int s = 0; s < 4; s++) {
    if (s == 0) wgmma64_set<0>(S, &Q[0], dk); else wgmma64_acc<0>(S, &Q[4 * s], dk + s * 2);
  }
}
__device__ __forceinline__ void qk_shift(float (&S)[32], const uint32_t (&nm)[4]) { wgmma64_acc<0>(S, nm, (uint64_t)((SM_BASE + SM_ONE) >> 4)); }
constexpr uint64_t V_STEP = uint64_t(1) - (uint64_t(1) << 16);
constexpr uint64_t RING_V = RING - (uint64_t(1) << 16) + ((uint64_t)((SM_STG + 2 * TILE_BYTES) >> 4) << 16);
__device__ __forceinline__ void pv_tile(float (&O)[36], const uint32_t (&P)[16], uint64_t dv, uint64_t pad) {
#pragma unroll
  for (int s = 0; s < 4; s++) wgmma72_acc(O, &P[4 * s], dv + s * 128 * V_STEP + (s < 2 ? 0 : (s - 1) * pad));
}
__device__ __forceinline__ void attn_step(const float (&Sc)[32], float (&Sn)[32], uint32_t (&Pc)[16], uint32_t (&Pp)[16], float (&O)[36],
                                          const uint32_t (&Q)[16], const uint32_t (&nm)[4], uint64_t dk, uint64_t dv) {
  WG_FENCE();
  qk_tile(Sn, Q, dk);
  qk_shift(Sn, nm);
  pv_tile(O, Pp, dv, 0);
  WG_COMMIT();
  SCHED();
#pragma unroll
  for (int i = 0; i < 16; i++) Pc[i] = pack2(ex2_hw(Sc[2 * i]), ex2_hw(Sc[2 * i + 1]));
  pin(Pc);
  SCHED();
}
template <int R> __device__ __forceinline__ float tile_max(const float (&S)[32]) {
  float t[4];
#pragma unroll
  for (int j = 0; j < 4; j++) t[j] = fmaxf(fmaxf(S[8 * j + R], S[8 * j + R + 1]), fmaxf(S[8 * j + R + 4], S[8 * j + R + 5]));
  float n = fmaxf(fmaxf(t[0], t[1]), fmaxf(t[2], t[3]));
  n = fmaxf(n, __shfl_xor_sync(0xffffffffu, n, 1));
  return fmaxf(n, __shfl_xor_sync(0xffffffffu, n, 2));
}
__device__ __forceinline__ void attention_exact(float (&O)[36], const uint32_t (&Q)[16], const Scratch* sc, int bh, int lane) {
  const char* kb = (const char*)&sc->kv[bh][0][0][0];
  const char* vb = (const char*)&sc->kv[bh][1][0][0];
  const int g = lane >> 2, q = lane & 3;
  float m0 = -INFINITY, m1 = -INFINITY, l0 = 0.f, l1 = 0.f;
  float o[8][4] = {};
#pragma unroll 1
  for (int k0 = 0; k0 < T_SEQ; k0 += 8) {
    float s[4] = {0.f, 0.f, 0.f, 0.f};
#pragma unroll
    for (int c = 0; c < 8; c++) hmma8(s, &Q[2 * c], __ldcg((const uint32_t*)(kb + (k0 + g) * 128 + ((c ^ g) << 4) + q * 4)));
    float n0 = fmaxf(s[0], s[1]), n1 = fmaxf(s[2], s[3]);
    n0 = fmaxf(n0, __shfl_xor_sync(0xffffffffu, n0, 1)); n1 = fmaxf(n1, __shfl_xor_sync(0xffffffffu, n1, 1));
    n0 = fmaxf(m0, fmaxf(n0, __shfl_xor_sync(0xffffffffu, n0, 2))); n1 = fmaxf(m1, fmaxf(n1, __shfl_xor_sync(0xffffffffu, n1, 2)));
    const float a0 = ex2_hw(m0 - n0), a1 = ex2_hw(m1 - n1);
    m0 = n0; m1 = n1;
    const uint32_t pp[2] = {pack2(ex2_hw(s[0] - n0), ex2_hw(s[1] - n0)), pack2(ex2_hw(s[2] - n1), ex2_hw(s[3] - n1))};
    l0 = fmaf(l0, a0, bf_lo(pp[0]) + bf_hi(pp[0])); l1 = fmaf(l1, a1, bf_lo(pp[1]) + bf_hi(pp[1]));
#pragma unroll
    for (int j = 0; j < 8; j++) {
      const uint32_t v0 = __ldcg((const uint16_t*)(vb + (k0 + 2 * q) * 128 + ((j ^ (2 * q)) << 4) + g * 2));
      const uint32_t v1 = __ldcg((const uint16_t*)(vb + (k0 + 2 * q + 1) * 128 + ((j ^ (2 * q + 1)) << 4) + g * 2));
      o[j][0] *= a0; o[j][1] *= a0; o[j][2] *= a1; o[j][3] *= a1;
      hmma8(o[j], pp, v0 | (v1 << 16));
    }
  }
  l0 += __shfl_xor_sync(0xffffffffu, l0, 1); l1 += __shfl_xor_sync(0xffffffffu, l1, 1);
  O[32] = l0 + __shfl_xor_sync(0xffffffffu, l0, 2); O[34] = l1 + __shfl_xor_sync(0xffffffffu, l1, 2);
#pragma unroll
  for (int i = 0; i < 32; i++) O[i] = o[i >> 2][i & 3];
}

__device__ __forceinline__ uint32_t fill_entry(int f, int r, int bh) {
  int m, x = r, y, dx = 0;
  if (f < F_QKV || f >= 48) {
    const int i = f & 15;
    m = f < F_QKV ? M_FF1A : M_FF2A;
    if (i < 8) { x = 4 * r + ((0xE2u >> i) & 1) * 2; y = r ^ ((0xE790u >> (2 * i)) & 3); dx = 1; }
    else { m++; x = r ^ (((i >> 1) - 3) & 3); y = 4 * r + 2 * (i & 1); }
  } else if (f < F_KV) {
    const int i = f - F_QKV;
    m = M_QKV;
    if (i == 1 || i >= 5) { y = r ^ (i == 1 ? 0 : 2); }
    else { x = 4 + r; y = r ^ (i ? i - 1 : 0); dx = 4; }
  } else if (f < F_WO) {
    const int i = f - F_KV;
    m = M_KV; x = 0; y = bh * 32 + (i & 2) * 8 + (i >> 2) * 4 + (i & 1) * 2;
  } else if (f >= F_PW1 && f < F_PW2) {
    m = M_PW1; y = r ^ (f - F_PW1); dx = 4;
  } else {
    m = f < F_PW1 ? M_WO : M_PW2; y = r ^ ((f & 1) * 2);
  }
  return m | (x << 4) | (y << 8) | (dx << 16);
}
__device__ __forceinline__ void tma_fill(uint32_t st, const CUtensorMap* map, uint32_t x, uint32_t y, uint32_t x2, uint32_t y2) {
  asm volatile("{\n.reg .pred p;\nelect.sync _|p, 0xffffffff;\n"
               "@p mbarrier.arrive.expect_tx.shared::cta.b64 _, [%1], 16384;\n"
               "@p cp.async.bulk.tensor.2d.shared::cluster.global.mbarrier::complete_tx::bytes [%0], [%2, {%3, %4}], [%1];\n"
               "@p cp.async.bulk.tensor.2d.shared::cluster.global.mbarrier::complete_tx::bytes [%0 + 8192], [%2, {%5, %6}], [%1];\n}"
               :: "r"(SM_BASE + st * STAGE_BYTES), "r"(SM_BASE + SM_FULL + st * 8), "l"(map), "r"(x), "r"(y), "r"(x2), "r"(y2) : "memory");
}
__device__ __forceinline__ void l2_prefetch(const void* p, uint32_t total, int b) {
  const uint32_t part = total / NCTA;
  asm volatile("cp.async.bulk.prefetch.L2.global [%0], %1;" :: "l"((const char*)p + (size_t)b * part), "r"(part) : "memory");
}

__global__ void __launch_bounds__(384, 1) conformer_kernel(Scratch* __restrict__ sc, __nv_bfloat16* __restrict__ out,
                                                           const __nv_bfloat16* __restrict__ dw, const __nv_bfloat16* __restrict__ xin,
                                                           const __nv_bfloat16* __restrict__ w_ff1a, const __grid_constant__ Params p) {
  extern __shared__ __align__(1024) uint8_t smem[];
  const int tid = threadIdx.x, lane = tid & 31;
  const int cw = __shfl_sync(0xffffffffu, tid >> 5, 0), wg = cw >> 2, w = cw & 3;
  const int b = blockIdx.x, r = b & 3, batch = b >> 6, t = (b >> 2) & 15;
  if ((uint32_t)__cvta_generic_to_shared(smem) != SM_BASE) return;
  PROF_MARK(0);
  PROF_TIME(30);

  if (wg == 2) {
    asm volatile("setmaxnreg.dec.sync.aligned.u32 40;");
    if (cw == 8) {
      if (lane == 0) {
        asm volatile("prefetch.tensormap [%0];" :: "l"(&p.map[M_X]) : "memory");
        asm volatile("prefetch.tensormap [%0];" :: "l"(&p.map[M_FF1A]) : "memory");
        mbar_init(SM_BASE + SM_XBAR, 1);
#pragma unroll
        for (int i = 0; i < NSTAGE; i++) mbar_init(SM_BASE + SM_FULL + i * 8, 1);
        fence_async_smem();
      }
      __syncwarp();
      asm volatile("{\n.reg .pred p;\nelect.sync _|p, 0xffffffff;\n"
                   "@p mbarrier.arrive.expect_tx.shared::cta.b64 _, [%1], 32768;\n"
                   "@p cp.async.bulk.tensor.4d.shared::cluster.global.mbarrier::complete_tx::bytes [%0], [%2, {0, %3, 0, %4}], [%1];\n}"
                   :: "r"(SM_BASE + SM_STG), "r"(SM_BASE + SM_XBAR), "l"(&p.map[M_X]), "r"(t * 64), "r"(batch) : "memory");
      bar_arrive(0, 320);
      PROF_MARK(9);
#pragma unroll
      for (int f = 0; f < 8; f++) {
        const uint32_t x = 256 * r + ((0xE2u >> f) & 1) * 128, y = (r ^ ((0xE790u >> (2 * f)) & 3)) * 64;
        tma_fill(f, &p.map[M_FF1A], x, y, x + 64, y);
      }
      PROF_MARK(1);
      const uint32_t* flag = sc->flag[batch * 4 + r][lane];
      const uint32_t prev = ((volatile uint32_t*)sc->epoch)[b];
      uint32_t entry[2], ready = 0, st = 8, parity = 1;
#pragma unroll 1
      for (int i = 0; i < 2; i++) { entry[1] = fill_entry(i * 32 + lane, r, batch * 4 + r); if (i == 0) entry[0] = entry[1]; }
      bar_sync(BAR_INIT, 64);
#pragma unroll 1
      for (int f = 8; f < F_TOTAL; f++) {
        const uint32_t e = __shfl_sync(0xffffffffu, f < 32 ? entry[0] : entry[1], f);
        if ((e & 15) == M_KV) {
          const uint32_t need = 3u << ((e >> 8) & 31);
          uint32_t spin = 0;
#pragma unroll 1
          while ((ready & need) != need && ++spin < SPIN_LIMIT) {
            uint32_t v;
            asm volatile("ld.relaxed.gpu.global.u32 %0, [%1];" : "=r"(v) : "l"(flag) : "memory");
            ready = __ballot_sync(0xffffffffu, v - 1 == prev);
          }
        }
        if (f == F_KV) PROF_MARK(8);
        mbar_wait(SM_BASE + SM_EMPTY + st * 8, parity);
        const uint32_t x = (e << 2) & 0x3C0, y = (e >> 2) & 0x3FC0, dx = (e >> 16) << 6;
        tma_fill(st, &p.map[e & 15], x, y, x + dx, dx ? y : y ^ 64);
        if (++st == NSTAGE) { st = 0; parity ^= 1; }
      }
    } else if (here(cw) != 11) {
      const int kind = w - 1;
      const uint32_t prev = ((volatile uint32_t*)sc->epoch)[b];
      if (kind == 0) {
        if (lane == 0) {
#pragma unroll
          for (int i = 0; i < NSTAGE; i++) mbar_init(SM_BASE + SM_EMPTY + i * 8, 4);
        }
        __syncwarp();
        bar_arrive(0, 320);
        bar_arrive(BAR_INIT, 64);
        bar_sync(BAR_K, 160);
      } else {
        uint32_t v, spin = 0;
#pragma unroll 1
        do {
          asm volatile("ld.relaxed.gpu.global.u32 %0, [%1];" : "=r"(v) : "l"(sc->ready[(b & ~3) + (lane & 3)]) : "memory");
        } while (__any_sync(0xffffffffu, v - 1 != prev) && ++spin < SPIN_LIMIT);
        bar_arrive(BAR_RDY, 160);
        bar_arrive(BAR_RDY1, 160);
        bar_sync(BAR_V, 160);
      }
      if (lane == 0) {
        asm volatile("cp.async.bulk.global.shared::cta.bulk_group [%0], [%1], %2;"
                     :: "l"(&sc->kv[batch * 4 + r][kind][t][0]), "r"(SM_BASE + SM_STG + kind * TILE_BYTES), "r"(TILE_BYTES) : "memory");
        asm volatile("cp.async.bulk.commit_group;\ncp.async.bulk.wait_group 0;" ::: "memory");
        asm volatile("st.relaxed.gpu.global.u32 [%0], %1;" :: "l"(sc->flag[batch * 4 + r][kind * 16 + t]), "r"(prev + 1) : "memory");
      }
    } else {
      if (lane == 0) {
        l2_prefetch(xin, 2 * T_SEQ * DM * 2, b);
        l2_prefetch(w_ff1a, 256 * 1024 * 2, b);
      }
      const uint32_t epoch = ((volatile uint32_t*)sc->epoch)[b] + 1;
      if (lane == 0 && epoch) {
        asm volatile("prefetch.tensormap [%0];" :: "l"(&p.map[M_FF1B]) : "memory");
        l2_prefetch(p.w_ff1b, 1024 * 256 * 2, b);
        l2_prefetch(p.w_qkv, 256 * 768 * 2, b);
        l2_prefetch(p.w_pw1, 256 * 512 * 2, b);
        l2_prefetch(p.w_ff2a, 256 * 1024 * 2, b);
      }
#pragma unroll 1
      for (uint4* dst = &sc->x[b][X_CLEAR + lane]; dst < &sc->x[b][X_ST + 32]; dst += 32) {
        const uint32_t t0 = clock_now();
        st_vec(dst, 0u, 0u, 0u, 0u);
        while (clock_now() - t0 < 24) {}
      }
      asm volatile("fence.acq_rel.gpu;" ::: "memory");
      __syncwarp();
      if (lane == 0) {
        asm volatile("st.relaxed.gpu.global.u32 [%0], %1;" :: "l"(sc->ready[b]), "r"(epoch) : "memory");
        l2_prefetch(p.w_o, 256 * 256 * 2, b);
        l2_prefetch(p.w_pw2, 256 * 256 * 2, b);
        l2_prefetch(p.w_ff2b, 1024 * 256 * 2, b);
#pragma unroll
        for (int i = M_QKV; i < M_X; i++) asm volatile("prefetch.tensormap [%0];" :: "l"(&p.map[i]) : "memory");
      }
    }
  } else {
    asm volatile("setmaxnreg.inc.sync.aligned.u32 232;");
    if (tid < 144) sts128(SM_BASE + SM_CS + tid * 16, 0, 0, 0, 0);
    if (wg == 1) {
      const int i = tid - 128;
      sts32(SM_BASE + SM_EYE + i * 4, i >= 96 ? 0x3F803F80u : ((i & 32) == 0 && (i & 3) == ((i >> 3) & 3)) ? (0x3F00u << ((i & 4) * 4)) : 0u);
    }
    fence_async_smem();
    bar_sync(0, 320);
    const int q = lane & 3, th = tid & 127;
    constexpr uint32_t stg = SM_BASE + SM_STG;
    const uint32_t mrow = 16 * w + (lane & 15);
    const uint32_t maddr = stg + mrow * 128 + (((lane >> 4) ^ (lane & 7)) << 4);
    const uint32_t res = stg + 3 * TILE_BYTES + w * 2048 + lane * 16;
    uint4* const xp = &sc->x[b][th];
    const int nvalid = T_SEQ - t * 64, row0 = 16 * w + (lane >> 2);

    uint32_t A[4][16];
    uint32_t sent = 0;
    mbar_wait(SM_BASE + SM_XBAR, 0);
    PROF_MARK(1);
#pragma unroll
    for (int c = 0; c < 4; c++) tile_load(maddr + (r ^ c) * TILE_BYTES, A[c]);
    if (wg == 0) {
      float sa[4] = {0.f, 0.f, 0.f, 0.f}, sb[4] = {0.f, 0.f, 0.f, 0.f};
#pragma unroll
      for (int i = 0; i < 16; i++) hmma((i & 1) ? sb : sa, &A[i >> 2][4 * (i & 3)], 0x3F803F80u, 0x3F803F80u);
      bar_arrive(BAR_X, 256);
      const float s0 = (sa[0] + sb[0]) * (1.f / DM), s1 = (sa[2] + sb[2]) * (1.f / DM);
      const uint32_t m0 = pack2(s0, s0), m1 = pack2(s1, s1);
#pragma unroll
      for (int c = 0; c < 4; c++) {
#pragma unroll
        for (int i = 0; i < 16; i++) asm("sub.rn.bf16x2 %0, %0, %1;" : "+r"(A[c][i]) : "r"((i & 1) ? m1 : m0));
        pin(A[c]);
      }
    } else {
      const uint32_t epoch = ((volatile uint32_t*)sc->epoch)[b] + 1, tag = epoch & 1;
      {
        RowAcc ra[2] = {};
#pragma unroll
        for (int c = 0; c < 4; c++) row_acc(ra[c & 1], A[c]);
        const float2 qa = row_squares(ra[0], lane & 4), qb = row_squares(ra[1], lane & 4);
        const int src = (lane & 28) | (lane >> 3);
        const float q0 = __shfl_sync(0xffffffffu, qa.x + qb.x, src), q1 = __shfl_sync(0xffffffffu, qa.y + qb.y, src);
        bar_sync(BAR_X, 256);
        res_store(res, A[0]);
        norm_produce(row_norm(ra[0].s[0] + ra[1].s[0], q0, ra[0].s[2] + ra[1].s[2], q1, 0.5f), th, 4);
      }
      PROF_MARK(5);
      SCHED();
      uint4 cv[8];
      if (b < 72) {
        const __nv_bfloat16* wp; int ld, col;
        if (b < 24) { wp = p.w_qkv; ld = 768; col = b * 32; }
        else if (b < 40) { wp = p.w_pw1; ld = 512; col = (b - 24) * 32; }
        else { wp = p.w_ff2a; ld = 1024; col = (b - 40) * 32; }
        const uint4* src = (const uint4*)(wp + (size_t)(th >> 2) * ld + col + q * 8);
#pragma unroll
        for (int i = 0; i < 8; i++) cv[i] = __ldg(src + i * 4 * ld);
      }
      if (b < 72) {
        float c[8] = {0.f, 0.f, 0.f, 0.f, 0.f, 0.f, 0.f, 0.f};
#pragma unroll
        for (int i = 0; i < 8; i++) {
          const uint4 v = cv[i];
          c[0] += bf_lo(v.x); c[1] += bf_hi(v.x); c[2] += bf_lo(v.y); c[3] += bf_hi(v.y);
          c[4] += bf_lo(v.z); c[5] += bf_hi(v.z); c[6] += bf_lo(v.w); c[7] += bf_hi(v.w);
        }
#pragma unroll 1
        for (int m = 4; m <= 16; m <<= 1)
#pragma unroll
          for (int k = 0; k < 8; k++) c[k] += __shfl_xor_sync(0xffffffffu, c[k], m);
        if (lane < 4) {
          const uint32_t a = SM_BASE + SM_CS + 1792 + w * 128 + lane * 32;
          sts128(a, __float_as_uint(c[0]), __float_as_uint(c[1]), __float_as_uint(c[2]), __float_as_uint(c[3]));
          sts128(a + 16, __float_as_uint(c[4]), __float_as_uint(c[5]), __float_as_uint(c[6]), __float_as_uint(c[7]));
        }
        bar_sync(BAR_WG1, 128);
        if (th < 8) {
          float o[4] = {0.f, 0.f, 0.f, 0.f};
#pragma unroll 1
          for (int k = 0; k < 4; k++) {
            uint32_t e[4];
            lds128(SM_BASE + SM_CS + 1792 + k * 128 + th * 16, e[0], e[1], e[2], e[3]);
#pragma unroll
            for (int i = 0; i < 4; i++) o[i] += __uint_as_float(e[i]);
          }
          st_vec(&sc->cs[b * 8 + th], (__float_as_uint(o[0]) & ~1u) | tag, __float_as_uint(o[1]), __float_as_uint(o[2]), __float_as_uint(o[3]));
        }
      }
      bar_sync(BAR_WG1, 128);
      PROF_MARK(2);
#pragma unroll 1
      for (int i = th; i < 144; i += 128) {
        const int j = i >> 4;
        int src;
        if (j < CS_PW1) src = 320 + 64 * r + i;
        else if (j < CS_QKV) src = 192 + (j - CS_PW1) * 64 + 16 * r + (i & 15);
        else src = ((j - CS_QKV + 1) % 3) * 64 + 16 * r + (i & 15);
        uint32_t e[4], spin = 0;
#pragma unroll 1
        do {
          ld_vec(&sc->cs[src], e[0], e[1], e[2], e[3]);
        } while (((e[0] ^ tag) & 1u) && ++spin < SPIN_LIMIT);
        const float c0 = __uint_as_float(e[0] & ~1u), c1 = __uint_as_float(e[1]), c2 = __uint_as_float(e[2]), c3 = __uint_as_float(e[3]);
        const uint32_t h0 = pack2(c0, c1), h1 = pack2(c2, c3);
        const uint32_t a = SM_BASE + SM_CS + j * 256 + (i & 15) * 8;
        sts64(a ^ ((a >> 3) & 0x70), h0, h1);
        sts64((a + 128) ^ (((a + 128) >> 3) & 0x70), pack2(c0 - bf_lo(h0), c1 - bf_hi(h0)), pack2(c2 - bf_lo(h1), c3 - bf_hi(h1)));
      }
      fence_async_smem();
      PROF_MARK(4);
      bar_sync(BAR_RDY1, 160);
      norm_duty(sc, th, 1, 1.f, 3);
    }

#pragma unroll 1
    for (uint32_t pass = 0; pass < 2; pass++) {
      uint32_t Q[16];
      if (wg == 0) {
        float acc[4][32];
        uint32_t H[4][16];
        if (!pass) { PROF_MARK(47); ACQUIRE(0); PROF_MARK(48); }
        mma_tile<true>(acc[0], A[0], LO(0)); mma_tile<true>(acc[1], A[0], HI(0));
        if (!pass) ACQUIRE(1);
        mma_tile<true>(acc[2], A[0], LO(1)); mma_tile<true>(acc[3], A[0], HI(1));
        if (pass) gather_first<1, X_AG0>(A, xp, 1, sent); else acquire_n<2, 3>();
        mma_tile<false>(acc[0], A[1], LO(2)); mma_tile<false>(acc[1], A[1], HI(2));
        if (pass) { gather_rest<1, X_AG0>(A, xp, 1); RELEASE(F_PW2, F_PW2 + 1); }
        PROF_MARK(2 + pass * 16);
        mma_tile<false>(acc[0], A[2], LO(3));
        WG_WAIT(3);
        uint32_t mu[4];
        float rs0, rs1, tn[2][4];
        norm_consume(here(th), mu, rs0, rs1);
        mma_tile_fold<2 * CS_FF2>(acc[0], A[3], LO(4), mu);
        RELEASE(0, 1);
        acquire_n<5, 3>();
        mma_tile<false>(acc[1], A[2], HI(3));
#define SEGS(a, b) silu_segs<a, b>(acc, tn, H, rs0, rs1)
        WG_WAIT(1); pin(acc[0]);
        SEGS(0, 1);
        mma_tile_fold<2 * CS_FF2 + 2>(acc[1], A[3], HI(4), mu);
        SEGS(1, 4);
        mma_tile<false>(acc[2], A[1], LO(5));
        SEGS(4, 6);
        mma_tile<false>(acc[2], A[2], LO(6));
        SEGS(6, 8);
        WG_WAIT(2); pin(acc[1]);
        RELEASE(2, 4);
        SEGS(8, 9);
        mma_tile_fold<2 * CS_FF2 + 4>(acc[2], A[3], LO(7), mu);
        SEGS(9, 12);
        mma_tile<false>(acc[3], A[1], HI(5));
        acquire_n<8, 2>();
        SEGS(12, 14);
        mma_tile<false>(acc[3], A[2], HI(6));
        SEGS(14, 16);
        WG_WAIT(2); pin(acc[2]);
        SEGS(16, 17);
        mma_tile_fold<2 * CS_FF2 + 6>(acc[3], A[3], HI(7), mu);
        SEGS(17, 20);
        mma_tile_reuse(acc[1], H[0], LO(8));
        acquire_n<10, 2>();
        SEGS(20, 22);
        mma_tile<false>(acc[1], H[1], HI(8));
        SEGS(22, 24);
        WG_WAIT(2); pin(acc[3]);
        RELEASE(5, 7);
        SEGS(24, 26);
        mma_tile<false>(acc[1], H[2], LO(9));
        SEGS(26, 28);
        mma_tile_reuse(acc[2], H[0], LO(10));
        SEGS(28, 31);
        mma_tile<false>(acc[2], H[1], HI(10));
        SEGS(31, 34);
#undef SEGS
        PROF_MARK(3 + pass * 16);
        const uint32_t rtag = here(pass ^ 1);
        const uint4* rs_in = xp + X_RS;
        mma_tile<false>(acc[1], H[3], HI(9));
        mma_tile<false>(acc[2], H[2], LO(11));
        acquire_n<12, 2>();
        uint4* rs_out = peer<1>(xp) + X_RS;
        mma_tile<false>(acc[2], H[3], HI(11));
        WG_WAIT(2); pin(acc[1]);
        RELEASE(8, 9);
        send_half<0>(rs_out, acc[1], rtag);
        mma_tile_reuse(acc[3], H[0], LO(12));
        SCHED();
        send_half<1>(rs_out, acc[1], rtag);
        mma_tile<false>(acc[3], H[1], HI(12));
        rs_out = peer<2>(xp) + X_RS + 512;
        WG_WAIT(2); pin(acc[2]);
        send_half<0>(rs_out, acc[2], rtag);
        mma_tile<false>(acc[3], H[2], LO(13));
        SCHED();
        send_half<1>(rs_out, acc[2], rtag);
        mma_tile<false>(acc[3], H[3], HI(13));
        acquire_n<14, 2>();
        mma_tile_reuse(acc[1], H[0], LO(14));
        rs_out = peer<3>(xp) + X_RS + 1024;
        if (!pass) bar_sync(BAR_RDY, 160);
        fetch(rs_in, A[1]);
        SCHED();
        mma_tile<false>(acc[1], H[1], HI(14));
        WG_WAIT(2); pin(acc[3]);
        send_half<0>(rs_out, acc[3], rtag);
        send_half<1>(rs_out, acc[3], rtag);
        mma_tile<false>(acc[1], H[2], LO(15)); mma_tile<false>(acc[1], H[3], HI(15));
        SCHED();
        res_load(res, acc[2]);
        if (!pass) acquire_n<F_QKV, 3>();
        confirm(rs_in, A[1], rtag);
        mma_add_half(acc[2], A[1]);
        PROF_MARK(44);
        fetch(rs_in + 512, A[2]);
        fetch(rs_in + 1024, A[3]);
        confirm(rs_in + 512, A[2], rtag);
        mma_add_half(acc[2], A[2]);
        SCHED();
        confirm(rs_in + 1024, A[3], rtag);
        mma_add_half(acc[2], A[3]);
        PROF_MARK(4 + pass * 16);
        WG_WAIT(0); pin(acc[2]); pin(acc[1]);
#pragma unroll
        for (int i = 0; i < 16; i++) A[0][i] = pack2(fmaf(acc[1][2 * i], 0.5f, acc[2][2 * i]), fmaf(acc[1][2 * i + 1], 0.5f, acc[2][2 * i + 1]));
        if (pass) {
          PROF_MARK(21);
          stat_publish(A[0], sc, here(th), 0);
          const RowNorm fn = stat_gather(sc, here(th), 0, 1.f);
          const float nm0 = -fn.m0 * fn.rs0, nm1 = -fn.m1 * fn.rs1;
#pragma unroll
          for (int i = 0; i < 16; i++) {
            const float rs = (i & 1) ? fn.rs1 : fn.rs0, nm = (i & 1) ? nm1 : nm0;
            A[0][i] = pack2(fmaf(bf_lo(A[0][i]), rs, nm), fmaf(bf_hi(A[0][i]), rs, nm));
          }
          tile_store(here(maddr), A[0]);
          __syncwarp();
          const int row = 16 * w + (lane >> 3);
          uint4* dst = (uint4*)(out + ((size_t)batch * T_SEQ + t * 64 + row) * DM + 64 * r) + (lane & 7);
          const uint32_t src = stg + row * 128 + (((lane & 7) ^ (lane >> 3)) << 4);
#pragma unroll
          for (int i = 0; i < 4; i++) {
            uint4 v;
            lds128((src ^ ((i & 1) << 6)) + i * 512, v.x, v.y, v.z, v.w);
            if (row + 4 * i < nvalid) dst[i * 4 * (DM / 8)] = v;
          }
          PROF_MARK(22);
          PROF_TIME(31);
          break;
        }
        sent = send_residual(A[0], sc, xp, res, 1);
        PROF_MARK(5);
        mma_tile<true>(acc[0], A[0], LO(F_QKV)); mma_tile<true>(acc[1], A[0], HI(F_QKV));
        mma_tile<true>(acc[2], A[0], LO(F_QKV + 1));
        gather_first<1, X_AG0>(A, xp, 1, sent);
        mma_tile<false>(acc[0], A[1], LO(F_QKV + 2)); mma_tile<false>(acc[1], A[1], HI(F_QKV + 2));
        acquire_n<F_QKV + 3, 3>();
        gather_rest<1, X_AG0>(A, xp, 1);
        PROF_MARK(6);
        mma_tile<false>(acc[0], A[2], LO(F_QKV + 3));
        norm_consume(here(th), mu, rs0, rs1);
        if (row0 >= nvalid) rs0 = 0.f;
        if (row0 + 8 >= nvalid) rs1 = 0.f;
        mma_tile_fold<2 * CS_QKV - 6>(acc[0], A[3], LO(F_QKV + 4), mu);
        RELEASE(10, 15);
        mma_tile<false>(acc[1], A[2], HI(F_QKV + 3));
        mma_tile_fold<2 * CS_QKV - 4>(acc[1], A[3], HI(F_QKV + 4), mu);
        WG_WAIT(2); pin(acc[0]);
        scale_pack(acc[0], Q, rs0, rs1);
        tile_store(here(maddr), Q);
        fence_async_smem();
        bar_arrive(BAR_K, 160);
        mma_tile<false>(acc[2], A[1], HI(F_QKV + 1)); mma_tile<false>(acc[2], A[2], LO(F_QKV + 5));
        WG_WAIT(2); pin(acc[1]);
        scale_pack(acc[1], Q, rs0, rs1);
        tile_store(here(maddr) + TILE_BYTES, Q);
        fence_async_smem();
        bar_arrive(BAR_V, 160);
        mma_tile_fold<2 * CS_QKV - 2>(acc[2], A[3], HI(F_QKV + 5), mu);
        WG_WAIT(0); pin(acc[2]);
        scale_pack(acc[2], Q, rs0 * SM_SCALE_LOG2, rs1 * SM_SCALE_LOG2);
        res_store(here(res) - TILE_BYTES, Q);
        bar_arrive(BAR_Q, 256);
        RELEASE(F_QKV, F_QKV + 5);
      } else {
        bar_sync(BAR_Q, 256);
#pragma unroll
        for (int s = 0; s < 4; s++) lds128(res - TILE_BYTES + s * 512, Q[4 * s], Q[4 * s + 1], Q[4 * s + 2], Q[4 * s + 3]);
        if (w < 2) {
          const uint32_t v = w ? 0u : 0x3F803F80u;
#pragma unroll
          for (int s = 0; s < 4; s++) sts128(res - TILE_BYTES + s * 512, v, v, v, v);
          fence_async_smem();
        }
      }
      bar_sync(BAR_ATT, 256);
      PROF_MARK(7);

      const int dir = cw == 0 ? -1 : 1;
      uint32_t tap[15];
      {
        const uint32_t* dwp = (const uint32_t*)(dw + 64 * r) + lane + 7 * (DM / 2);
#pragma unroll
        for (int k = 0; k < 15; k++) tap[k] = __ldg(dwp + dir * (k - 7) * (DM / 2));
      }

      float O[36];
      {
        float S[2][32];
        uint32_t P[2][16], nm[4];
        pin(Q);
        WG_FENCE();
        qk_tile(S[0], Q, RING + (SM_STG >> 4));
        WG_COMMIT();
#pragma unroll
        for (int i = 0; i < 36; i++) O[i] = 0.f;
#pragma unroll
        for (int i = 0; i < 16; i++) P[1][i] = 0u;
        WG_WAIT(0); pin(S[0]);
        const float m0 = tile_max<0>(S[0]), m1 = tile_max<2>(S[0]);
        nm[0] = pack2(q ? 0.f : -m0, 0.f); nm[1] = pack2(q ? 0.f : -m1, 0.f); nm[2] = 0u; nm[3] = 0u;
#pragma unroll
        for (int k = 0; k < 15; k++) asm("mul.rn.bf16x2 %0, %0, %1;" : "+r"(tap[k]) : "r"(0x3F003F00u));
        pin(nm); pin(O); pin(P[1]); pin(tap);
        uint32_t sk = wg, sv = wg;
        mbar_wait(SM_BASE + SM_FULL + (F_SPARE % NSTAGE + wg) * 8, 1);
        if (lane == 0) mbar_arrive(SM_BASE + SM_EMPTY + (F_SPARE % NSTAGE + wg) * 8);
        mbar_wait(SM_BASE + SM_FULL + sk * 8, 0);
        PROF_MARK(8);
        WG_FENCE();
        qk_tile(S[0], Q, RING + sk * 1024);
        qk_shift(S[0], nm);
        WG_COMMIT();
        WG_WAIT(0); pin(S[0]);
#pragma unroll 1
        for (int it = 0; it < 4; it++) {
          attn_step(S[0], S[1], P[0], P[1], O, Q, nm, RING + sk * 1024 + 512, RING_V + (sv * 1024 + 512) * V_STEP);
          const uint32_t sn = it == 2 ? wg : sk + (it == 3 ? 2 : 4);
          mbar_wait(SM_BASE + SM_FULL + sn * 8, it >= 2);
          mbar_wait(SM_BASE + SM_FULL + (sk + 2) * 8, it == 3);
          WG_WAIT(0); pin(O); pin(S[1]); pin(P[1]);
          if (lane == 0) {
            mbar_arrive(SM_BASE + SM_EMPTY + sk * 8);
            if (it) mbar_arrive(SM_BASE + SM_EMPTY + sv * 8);
          }
          sv = sk + 2; sk = sn;
          attn_step(S[1], S[0], P[1], P[0], O, Q, nm, RING + sk * 1024, RING_V + (sv * 1024) * V_STEP);
          WG_WAIT(0); pin(O); pin(S[0]); pin(P[0]);
        }
        WG_FENCE();
        pv_tile(O, P[1], RING_V + (sv * 1024 + 512) * V_STEP, (uint64_t)wg << 22);
        WG_COMMIT();
        WG_WAIT(0); pin(O);
      }
      PROF_MARK(9);

      if (wg == 1) {
        const uint32_t mo = stg + here(th) * 16;
#pragma unroll
        for (int i = 0; i < 9; i++)
          sts128(mo + i * 2048 + (i >> 3) * 4096, __float_as_uint(O[4 * i]), __float_as_uint(O[4 * i + 1]), __float_as_uint(O[4 * i + 2]), __float_as_uint(O[4 * i + 3]));
        bar_arrive(BAR_MERGE, 256);
        norm_duty(sc, here(th), 0, 0.5f, 0);
      } else {
        const uint32_t mo = stg + here(th) * 16;
        bar_sync(BAR_MERGE, 256);
#pragma unroll
        for (int i = 8; i >= 0; i--) {
          uint32_t e[4];
          lds128(mo + i * 2048 + (i >> 3) * 4096, e[0], e[1], e[2], e[3]);
#pragma unroll
          for (int k = 0; k < 4; k++) O[4 * i + k] += __uint_as_float(e[k]);
        }
        const bool safe = O[32] > 0x1p-60f && O[32] < 0x1p60f && O[34] > 0x1p-60f && O[34] < 0x1p60f;
        if (__builtin_expect(__any_sync(0xffffffffu, !safe), 0)) attention_exact(O, Q, sc, batch * 4 + r, lane);
        const float i0 = rcp_hw(O[32]), i1 = rcp_hw(O[34]);
#pragma unroll
        for (int i = 0; i < 16; i++) { const float v = (i & 1) ? i1 : i0; A[0][i] = pack2(O[2 * i] * v, O[2 * i + 1] * v); }
        PROF_MARK(10);
        sent = proj_residual<F_WO, 6>(A, sc, xp, res, 0);
        PROF_MARK(12);
        float acc[2][32];
        mma_tile<true>(acc[0], A[0], LO(F_PW1)); mma_tile<true>(acc[1], A[0], HI(F_PW1));
        gather_first<1, X_AG0>(A, xp, 0, sent);
        mma_tile<false>(acc[1], A[1], HI(F_PW1 + 1)); mma_tile<false>(acc[0], A[1], LO(F_PW1 + 1));
        gather_rest<1, X_AG0>(A, xp, 0);
        PROF_MARK(13);
        mma_tile<false>(acc[1], A[2], HI(F_PW1 + 2));
        uint32_t mu[4];
        float rs0, rs1;
        norm_consume(here(th), mu, rs0, rs1);
        if (row0 >= nvalid) rs0 = 0.f;
        if (row0 + 8 >= nvalid) rs1 = 0.f;
        mma_tile_fold<2 * CS_PW1 + 2>(acc[1], A[3], HI(F_PW1 + 3), mu);
        RELEASE(F_KV + 14, F_WO + 1);
        mma_tile<false>(acc[0], A[2], LO(F_PW1 + 2));
        mma_tile_fold<2 * CS_PW1>(acc[0], A[3], LO(F_PW1 + 3), mu);
        WG_WAIT(2); pin(acc[1]);
#pragma unroll
        for (int i = 0; i < 32; i++) acc[1][i] = tanh_hw(acc[1][i] * ((i & 2) ? rs1 : rs0));
#pragma unroll
        for (int i = 0; i < 32; i++) { const float rs = (i & 2) ? rs1 : rs0; acc[1][i] = fmaf(acc[1][i], rs, rs); }
        pin(acc[1]);
        SCHED();
        WG_WAIT(0); pin(acc[0]);
#pragma unroll
        for (int i = 0; i < 16; i++) A[0][i] = pack2(acc[0][2 * i] * acc[1][2 * i], acc[0][2 * i + 1] * acc[1][2 * i + 1]);
        const uint32_t ga = stg + TILE_BYTES + here(mrow) * G_PITCH + (lane >> 4) * 16;
#pragma unroll
        for (int s = 0; s < 4; s++) stsm4(ga + s * 32, &A[0][4 * s]);
        RELEASE(F_PW1, F_PW1 + 3);
      }
      bar_sync(BAR_G, 256);
      PROF_MARK(14);

      {
        const int first = cw == 0 ? 14 : 8 * cw - 7;
        const uint32_t gsrc = stg + TILE_BYTES + first * G_PITCH + lane * 4;
        uint32_t in[22];
#pragma unroll
        for (int i = 0; i < 15; i++) in[i] = lds32(gsrc + dir * i * (int)G_PITCH);
        const bool edge = cw == 0 || cw == 7;
        const bool nbr = cw == 0 ? t > 0 : t < 15;
        if (edge) {
          if (nbr) {
            uint4* dst = &sc->x[b + 4 * dir][X_HALO + (cw == 0 ? 96 : 0) + lane];
            st_vec(dst, HALO_TAG, in[14], in[13], in[12]);
            st_vec(dst + 32, HALO_TAG, in[11], in[10], in[9]);
            st_vec(dst + 64, HALO_TAG, in[8], 0u, 0u);
          }
        } else {
#pragma unroll
          for (int i = 15; i < 22; i++) in[i] = lds32(gsrc + i * G_PITCH);
        }
        uint32_t cv[8];
#pragma unroll
        for (int i = 0; i < 15; i++)
#pragma unroll
          for (int o = 0; o < 8; o++) {
            if (i == o) asm("mul.rn.bf16x2 %0, %1, %2;" : "=r"(cv[o]) : "r"(in[i]), "r"(tap[0]));
            if (i > o) asm("fma.rn.bf16x2 %0, %1, %2, %0;" : "+r"(cv[o]) : "r"(in[i]), "r"(tap[i - o]));
          }
        pin(cv);
        PROF_MARK(45);
        if (edge) {
#pragma unroll
          for (int i = 15; i < 22; i++) in[i] = 0u;
          if (nbr) {
            const uint4* src = &sc->x[b][X_HALO + (cw == 0 ? 0 : 96) + lane];
            uint32_t e0, e1, e2, u0, u1, spin = 0;
#pragma unroll 1
            do {
              ld_vec(src, e0, in[15], in[16], in[17]);
              ld_vec(src + 32, e1, in[18], in[19], in[20]);
              ld_vec(src + 64, e2, in[21], u0, u1);
            } while (__any_sync(0xffffffffu, ((e0 ^ HALO_TAG) | (e1 ^ HALO_TAG) | (e2 ^ HALO_TAG)) != 0) && ++spin < SPIN_LIMIT);
          }
        }
#pragma unroll
        for (int i = 15; i < 22; i++)
#pragma unroll
          for (int o = 0; o < 8; o++)
            if (i - o <= 14) asm("fma.rn.bf16x2 %0, %1, %2, %0;" : "+r"(cv[o]) : "r"(in[i]), "r"(tap[i - o]));
        PROF_MARK(46);
        const uint32_t fl = cw == 0 ? 7 : 0;
        const uint32_t cdst = (stg + cw * 1024 + lane * 4) ^ (fl * 144);
#pragma unroll
        for (int o = 0; o < 8; o++) {
          const float a = bf_lo(cv[o]), c = bf_hi(cv[o]);
          sts32(cdst ^ (o * 144), pack2(fmaf(a, tanh_hw(a), a), fmaf(c, tanh_hw(c), c)));
        }
      }
      if (wg == 1) {
        bar_arrive(BAR_C, 256);
        norm_duty(sc, here(th), 1, 0.5f, 0);
        if (th == 0) ((volatile uint32_t*)sc->epoch)[b] += 1;
        break;
      }
      bar_sync(BAR_C, 256);
      tile_load(here(maddr), A[0]);
      PROF_MARK(15);
      sent = proj_residual<F_PW2, 2>(A, sc, xp, res, 1);
      PROF_MARK(17);
    }
  }
}

typedef CUresult (*EncodeFn)(CUtensorMap*, CUtensorMapDataType, cuuint32_t, void*, const cuuint64_t*, const cuuint64_t*,
                             const cuuint32_t*, const cuuint32_t*, CUtensorMapInterleave, CUtensorMapSwizzle,
                             CUtensorMapL2promotion, CUtensorMapFloatOOBfill);

void make_map(EncodeFn fn, CUtensorMap* m, const void* w, int rows, int cols, CUtensorMapSwizzle swz) {
  const cuuint64_t dims[2] = {(cuuint64_t)cols, (cuuint64_t)rows}, strides[1] = {(cuuint64_t)cols * 2};
  const cuuint32_t box[2] = {64, 64}, es[2] = {1, 1};
  fn(m, CU_TENSOR_MAP_DATA_TYPE_BFLOAT16, 2, const_cast<void*>(w), dims, strides, box, es, CU_TENSOR_MAP_INTERLEAVE_NONE,
     swz, CU_TENSOR_MAP_L2_PROMOTION_L2_128B, CU_TENSOR_MAP_FLOAT_OOB_FILL_NONE);
}

}

extern "C" void kernel_launch(void* const* d_in, const int* in_sizes, int n_in, void* d_out, int out_size) {
  static EncodeFn fn = nullptr;
  static Scratch* sc = nullptr;
  if (!fn) {
    void* f = nullptr;
    cudaDriverEntryPointQueryResult st;
    cudaGetDriverEntryPoint("cuTensorMapEncodeTiled", &f, cudaEnableDefault, &st);
    fn = (EncodeFn)f;
    void* raw = nullptr;
    cudaGetSymbolAddress(&raw, g_scratch);
    sc = (Scratch*)(((uintptr_t)raw + X_ALIGN - 1) & ~(uintptr_t)(X_ALIGN - 1));
    cudaFuncSetAttribute(conformer_kernel, cudaFuncAttributeMaxDynamicSharedMemorySize, SM_TOTAL);
  }
  typedef const __nv_bfloat16* W;
  const CUtensorMapSwizzle S = CU_TENSOR_MAP_SWIZZLE_128B;
  Params p;
  {
    const cuuint64_t dims[4] = {64, T_SEQ, 4, 2}, strides[3] = {512, 128, T_SEQ * 512};
    const cuuint32_t box[4] = {64, 64, 4, 1}, es[4] = {1, 1, 1, 1};
    fn(&p.map[M_X], CU_TENSOR_MAP_DATA_TYPE_BFLOAT16, 4, d_in[0], dims, strides, box, es, CU_TENSOR_MAP_INTERLEAVE_NONE, S,
       CU_TENSOR_MAP_L2_PROMOTION_L2_128B, CU_TENSOR_MAP_FLOAT_OOB_FILL_NONE);
  }
  make_map(fn, &p.map[M_FF1A], d_in[1], 256, 1024, S);
  make_map(fn, &p.map[M_FF1B], d_in[2], 1024, 256, S);
  make_map(fn, &p.map[M_QKV], d_in[3], 256, 768, S);
  make_map(fn, &p.map[M_KV], sc->kv, 16384, 64, CU_TENSOR_MAP_SWIZZLE_NONE);
  make_map(fn, &p.map[M_WO], d_in[4], 256, 256, S);
  make_map(fn, &p.map[M_PW1], d_in[5], 256, 512, S);
  make_map(fn, &p.map[M_PW2], d_in[7], 256, 256, S);
  make_map(fn, &p.map[M_FF2A], d_in[8], 256, 1024, S);
  make_map(fn, &p.map[M_FF2B], d_in[9], 1024, 256, S);
  p.w_ff1b = (W)d_in[2]; p.w_qkv = (W)d_in[3]; p.w_o = (W)d_in[4]; p.w_pw1 = (W)d_in[5];
  p.w_pw2 = (W)d_in[7]; p.w_ff2a = (W)d_in[8]; p.w_ff2b = (W)d_in[9];

  cudaLaunchConfig_t cfg = {};
  cfg.gridDim = dim3(NCTA);
  cfg.blockDim = dim3(384);
  cfg.dynamicSmemBytes = SM_TOTAL;
  cfg.stream = cudaStreamPerThread;
  cudaLaunchAttribute at[1];
  at[0].id = cudaLaunchAttributeCooperative;
  at[0].val.cooperative = 1;
  cfg.attrs = at;
  cfg.numAttrs = 1;
  cudaLaunchKernelEx(&cfg, conformer_kernel, sc, (__nv_bfloat16*)d_out, (W)d_in[6], (W)d_in[0], (W)d_in[1], p);
}
```

```cpp
#include <cuda_runtime.h>
#include <cuda_bf16.h>
#include <cuda.h>
#include <stdint.h>

namespace {

constexpr int T_SEQ = 1000;
constexpr int DM = 256;
constexpr int NCTA = 128;
constexpr int NSTAGE = 12;
constexpr uint32_t STAGE_BYTES = 16384;
constexpr uint32_t TILE_BYTES = 8192;
constexpr uint32_t SM_BASE = 1024;
constexpr uint32_t SM_STG = NSTAGE * STAGE_BYTES;
constexpr uint32_t SM_FULL = SM_STG + 32768;
constexpr uint32_t SM_EMPTY = SM_FULL + 96;
constexpr uint32_t SM_XBAR = SM_FULL + 192;
constexpr uint32_t SM_EYE = SM_FULL + 256;
constexpr uint32_t SM_ONE = SM_FULL + 640;
constexpr uint32_t SM_CS = SM_FULL + 768;
constexpr uint32_t SM_TOTAL = SM_FULL + 3072;
constexpr int CS_FF2 = 0, CS_PW1 = 4, CS_QKV = 6;
constexpr uint32_t SPIN_LIMIT = 1u << 16;
constexpr float LN_EPS = 1e-5f;
constexpr float SM_SCALE_LOG2 = 0.125f * 1.4426950408889634f;
constexpr uint32_t G_PITCH = 144;

constexpr int F_QKV = 16, F_SPARE = 22, F_KV = 24, F_WO = 40, F_PW1 = 42, F_PW2 = 46, F_TOTAL = 64;
enum { M_FF1A, M_FF1B, M_QKV, M_KV, M_WO, M_PW1, M_PW2, M_FF2A, M_FF2B, M_X, M_COUNT };
enum { BAR_K = 1, BAR_V, BAR_Q, BAR_MERGE, BAR_G, BAR_C, BAR_WG1, BAR_RDY, BAR_ST, BAR_ATT, BAR_INIT, BAR_RDY1, BAR_X, BAR_RES };

struct Params {
  CUtensorMap map[M_COUNT];
  const __nv_bfloat16 *w_ff1b, *w_qkv, *w_o, *w_pw1, *w_pw2, *w_ff2a, *w_ff2b;
};

constexpr int X_RS = 0, X_AG1 = X_RS, X_HALO = X_RS + 512, X_CLEAR = 1024, X_AG0 = 1536, X_ST = 2048, X_SIZE = 4096;
constexpr uint32_t HALO_TAG = 0xFFFF0001u;
struct Scratch {
  uint4 x[NCTA][X_SIZE];
  uint4 kv[8][2][16][512];
  uint4 cs[576];
  uint32_t flag[8][32][32];
  uint32_t ready[NCTA][32];
  uint32_t epoch[NCTA];
};
constexpr size_t X_ALIGN = 4 * X_SIZE * sizeof(uint4);
__device__ uint8_t g_scratch[sizeof(Scratch) + X_ALIGN];
#define PROF_TIME(i)
#define PROF_MARK(i)

__device__ __forceinline__ void mbar_init(uint32_t bar, uint32_t cnt) {
  asm volatile("mbarrier.init.shared::cta.b64 [%0], %1;" :: "r"(bar), "r"(cnt) : "memory");
}
__device__ __forceinline__ void mbar_wait(uint32_t bar, uint32_t parity) {
  asm volatile("{\n.reg .pred p;\n.reg .u32 c;\nmov.u32 c, 0;\n"
               "WAIT_LOOP:\nmbarrier.try_wait.parity.shared::cta.b64 p, [%0], %1;\n@p bra WAIT_DONE;\n"
               "add.u32 c, c, 1;\nsetp.lt.u32 p, c, %2;\n@p bra WAIT_LOOP;\nWAIT_DONE:\n}"
               :: "r"(bar), "r"(parity), "n"(SPIN_LIMIT) : "memory");
}
__device__ __forceinline__ void mbar_arrive(uint32_t bar) {
  asm volatile("mbarrier.arrive.shared::cta.b64 _, [%0];" :: "r"(bar) : "memory");
}
#define bar_sync(id, n) asm volatile("bar.sync %0, %1;" :: "n"((int)(id)), "n"(n) : "memory")
#define bar_arrive(id, n) asm volatile("bar.arrive %0, %1;" :: "n"((int)(id)), "n"(n) : "memory")
__device__ __forceinline__ void fence_async_smem() { asm volatile("fence.proxy.async.shared::cta;" ::: "memory"); }

__device__ __forceinline__ void st_vec(uint4* p, uint32_t a, uint32_t b, uint32_t c, uint32_t d) {
  asm volatile("{\n.reg .b128 v;\n.reg .b64 lo, hi;\nmov.b64 lo, {%1, %2};\nmov.b64 hi, {%3, %4};\nmov.b128 v, {lo, hi};\n"
               "st.relaxed.gpu.global.b128 [%0], v;\n}" :: "l"(p), "r"(a), "r"(b), "r"(c), "r"(d) : "memory");
}
__device__ __forceinline__ void ld_vec(const uint4* p, uint32_t& a, uint32_t& b, uint32_t& c, uint32_t& d) {
  asm volatile("{\n.reg .b128 v;\n.reg .b64 lo, hi;\nld.relaxed.gpu.global.b128 v, [%4];\nmov.b128 {lo, hi}, v;\n"
               "mov.b64 {%0, %1}, lo;\nmov.b64 {%2, %3}, hi;\n}" : "=r"(a), "=r"(b), "=r"(c), "=r"(d) : "l"(p) : "memory");
}
__device__ __forceinline__ void sts128(uint32_t a, uint32_t x, uint32_t y, uint32_t z, uint32_t w) {
  asm volatile("st.shared.v4.u32 [%0], {%1, %2, %3, %4};" :: "r"(a), "r"(x), "r"(y), "r"(z), "r"(w) : "memory");
}
__device__ __forceinline__ void lds128(uint32_t a, uint32_t& x, uint32_t& y, uint32_t& z, uint32_t& w) {
  asm volatile("ld.shared.v4.u32 {%0, %1, %2, %3}, [%4];" : "=r"(x), "=r"(y), "=r"(z), "=r"(w) : "r"(a) : "memory");
}
__device__ __forceinline__ uint32_t lds32(uint32_t a) {
  uint32_t x; asm volatile("ld.shared.u32 %0, [%1];" : "=r"(x) : "r"(a) : "memory"); return x;
}
__device__ __forceinline__ void sts32(uint32_t a, uint32_t x) { asm volatile("st.shared.u32 [%0], %1;" :: "r"(a), "r"(x) : "memory"); }
__device__ __forceinline__ void sts64(uint32_t a, uint32_t x, uint32_t y) {
  asm volatile("st.shared.v2.u32 [%0], {%1, %2};" :: "r"(a), "r"(x), "r"(y) : "memory");
}
__device__ __forceinline__ void stsm4(uint32_t a, const uint32_t* r) {
  asm volatile("stmatrix.sync.aligned.m8n8.x4.shared.b16 [%0], {%1, %2, %3, %4};" :: "r"(a), "r"(r[0]), "r"(r[1]), "r"(r[2]), "r"(r[3]) : "memory");
}
__device__ __forceinline__ void ldsm4(uint32_t a, uint32_t* r) {
  asm volatile("ldmatrix.sync.aligned.m8n8.x4.shared.b16 {%0, %1, %2, %3}, [%4];" : "=r"(r[0]), "=r"(r[1]), "=r"(r[2]), "=r"(r[3]) : "r"(a) : "memory");
}
__device__ __forceinline__ uint32_t pack2(float lo, float hi) {
  uint32_t r; asm("cvt.rn.bf16x2.f32 %0, %1, %2;" : "=r"(r) : "f"(hi), "f"(lo)); return r;
}
__device__ __forceinline__ float bf_lo(uint32_t w) { return __uint_as_float(w << 16); }
__device__ __forceinline__ float bf_hi(uint32_t w) { return __uint_as_float(w & 0xffff0000u); }
__device__ __forceinline__ float tanh_hw(float x) { float y; asm volatile("tanh.approx.f32 %0, %1;" : "=f"(y) : "f"(x)); return y; }
__device__ __forceinline__ float rcp_hw(float x) { float y; asm("rcp.approx.ftz.f32 %0, %1;" : "=f"(y) : "f"(x)); return y; }
__device__ __forceinline__ float ex2_hw(float x) { float y; asm("ex2.approx.ftz.f32 %0, %1;" : "=f"(y) : "f"(x)); return y; }

__device__ __forceinline__ uint32_t here(uint32_t v) { asm volatile("" : "+r"(v)); return v; }

#define SCHED() asm volatile("pmevent 1;" ::: "memory")
#define WG_FENCE() asm volatile("wgmma.fence.sync.aligned;" ::: "memory")
#define WG_COMMIT() asm volatile("wgmma.commit_group.sync.aligned;" ::: "memory")
#define WG_WAIT(n) asm volatile("wgmma.wait_group.sync.aligned %0;" :: "n"(n) : "memory")

template <int N> __device__ __forceinline__ void pin(float (&d)[N]) {
#pragma unroll
  for (int i = 0; i < N; i++) asm volatile("" : "+f"(d[i]) :: "memory");
}
template <int N> __device__ __forceinline__ void pin(uint32_t (&d)[N]) {
#pragma unroll
  for (int i = 0; i < N; i++) asm volatile("" : "+r"(d[i]) :: "memory");
}

#define WG_D32 "{%0, %1, %2, %3, %4, %5, %6, %7, %8, %9, %10, %11, %12, %13, %14, %15, %16, %17, %18, %19, %20, %21, %22, %23, %24, %25, %26, %27, %28, %29, %30, %31}"
template <int TB> __device__ __forceinline__ void wgmma64_acc(float (&d)[32], const uint32_t* a, uint64_t db) {
  asm volatile("wgmma.mma_async.sync.aligned.m64n64k16.f32.bf16.bf16 " WG_D32 ", {%32, %33, %34, %35}, %36, 1, 1, 1, %37;"
    : "+f"(d[0]), "+f"(d[1]), "+f"(d[2]), "+f"(d[3]), "+f"(d[4]), "+f"(d[5]), "+f"(d[6]), "+f"(d[7]),
      "+f"(d[8]), "+f"(d[9]), "+f"(d[10]), "+f"(d[11]), "+f"(d[12]), "+f"(d[13]), "+f"(d[14]), "+f"(d[15]),
      "+f"(d[16]), "+f"(d[17]), "+f"(d[18]), "+f"(d[19]), "+f"(d[20]), "+f"(d[21]), "+f"(d[22]), "+f"(d[23]),
      "+f"(d[24]), "+f"(d[25]), "+f"(d[26]), "+f"(d[27]), "+f"(d[28]), "+f"(d[29]), "+f"(d[30]), "+f"(d[31])
    : "r"(a[0]), "r"(a[1]), "r"(a[2]), "r"(a[3]), "l"(db), "n"(TB));
}
__device__ __forceinline__ void wgmma64_reuse(float (&d)[32], const uint32_t* a, uint64_t db, uint32_t zero) {
  asm volatile("{\n.reg .pred p;\nsetp.ne.u32 p, %37, 0;\nwgmma.mma_async.sync.aligned.m64n64k16.f32.bf16.bf16 " WG_D32 ", {%32, %33, %34, %35}, %36, p, 1, 1, 1;\n}"
    : "+f"(d[0]), "+f"(d[1]), "+f"(d[2]), "+f"(d[3]), "+f"(d[4]), "+f"(d[5]), "+f"(d[6]), "+f"(d[7]),
      "+f"(d[8]), "+f"(d[9]), "+f"(d[10]), "+f"(d[11]), "+f"(d[12]), "+f"(d[13]), "+f"(d[14]), "+f"(d[15]),
      "+f"(d[16]), "+f"(d[17]), "+f"(d[18]), "+f"(d[19]), "+f"(d[20]), "+f"(d[21]), "+f"(d[22]), "+f"(d[23]),
      "+f"(d[24]), "+f"(d[25]), "+f"(d[26]), "+f"(d[27]), "+f"(d[28]), "+f"(d[29]), "+f"(d[30]), "+f"(d[31])
    : "r"(a[0]), "r"(a[1]), "r"(a[2]), "r"(a[3]), "l"(db), "r"(zero));
}
template <int TB> __device__ __forceinline__ void wgmma64_set(float (&d)[32], const uint32_t* a, uint64_t db) {
  asm volatile("wgmma.mma_async.sync.aligned.m64n64k16.f32.bf16.bf16 " WG_D32 ", {%32, %33, %34, %35}, %36, 0, 1, 1, %37;"
    : "=f"(d[0]), "=f"(d[1]), "=f"(d[2]), "=f"(d[3]), "=f"(d[4]), "=f"(d[5]), "=f"(d[6]), "=f"(d[7]),
      "=f"(d[8]), "=f"(d[9]), "=f"(d[10]), "=f"(d[11]), "=f"(d[12]), "=f"(d[13]), "=f"(d[14]), "=f"(d[15]),
      "=f"(d[16]), "=f"(d[17]), "=f"(d[18]), "=f"(d[19]), "=f"(d[20]), "=f"(d[21]), "=f"(d[22]), "=f"(d[23]),
      "=f"(d[24]), "=f"(d[25]), "=f"(d[26]), "=f"(d[27]), "=f"(d[28]), "=f"(d[29]), "=f"(d[30]), "=f"(d[31])
    : "r"(a[0]), "r"(a[1]), "r"(a[2]), "r"(a[3]), "l"(db), "n"(TB));
}

__device__ __forceinline__ void wgmma72_acc(float (&d)[36], const uint32_t* a, uint64_t db) {
  asm volatile("wgmma.mma_async.sync.aligned.m64n72k16.f32.bf16.bf16 {%0, %1, %2, %3, %4, %5, %6, %7, %8, %9, %10, %11, %12, %13, %14, %15, %16, %17, %18, %19, %20, %21, %22, %23, %24, %25, %26, %27, %28, %29, %30, %31, %32, %33, %34, %35}, {%36, %37, %38, %39}, %40, 1, 1, 1, 1;"
    : "+f"(d[0]), "+f"(d[1]), "+f"(d[2]), "+f"(d[3]), "+f"(d[4]), "+f"(d[5]), "+f"(d[6]), "+f"(d[7]), "+f"(d[8]),
      "+f"(d[9]), "+f"(d[10]), "+f"(d[11]), "+f"(d[12]), "+f"(d[13]), "+f"(d[14]), "+f"(d[15]), "+f"(d[16]), "+f"(d[17]),
      "+f"(d[18]), "+f"(d[19]), "+f"(d[20]), "+f"(d[21]), "+f"(d[22]), "+f"(d[23]), "+f"(d[24]), "+f"(d[25]), "+f"(d[26]),
      "+f"(d[27]), "+f"(d[28]), "+f"(d[29]), "+f"(d[30]), "+f"(d[31]), "+f"(d[32]), "+f"(d[33]), "+f"(d[34]), "+f"(d[35])
    : "r"(a[0]), "r"(a[1]), "r"(a[2]), "r"(a[3]), "l"(db));
}
__device__ __forceinline__ void wgmma16_acc(float* d, const uint32_t* a, uint64_t db) {
  asm volatile("wgmma.mma_async.sync.aligned.m64n16k16.f32.bf16.bf16 {%0, %1, %2, %3, %4, %5, %6, %7}, {%8, %9, %10, %11}, %12, 1, 1, 1, 0;"
    : "+f"(d[0]), "+f"(d[1]), "+f"(d[2]), "+f"(d[3]), "+f"(d[4]), "+f"(d[5]), "+f"(d[6]), "+f"(d[7])
    : "r"(a[0]), "r"(a[1]), "r"(a[2]), "r"(a[3]), "l"(db));
}
__device__ __forceinline__ void hmma(float (&d)[4], const uint32_t* a, uint32_t b0, uint32_t b1) {
  asm("mma.sync.aligned.m16n8k16.row.col.f32.bf16.bf16.f32 {%0, %1, %2, %3}, {%4, %5, %6, %7}, {%8, %9}, {%0, %1, %2, %3};"
    : "+f"(d[0]), "+f"(d[1]), "+f"(d[2]), "+f"(d[3]) : "r"(a[0]), "r"(a[1]), "r"(a[2]), "r"(a[3]), "r"(b0), "r"(b1));
}

__device__ __forceinline__ void hmma8(float (&d)[4], const uint32_t* a, uint32_t b0) {
  asm("mma.sync.aligned.m16n8k8.row.col.f32.bf16.bf16.f32 {%0, %1, %2, %3}, {%4, %5}, {%6}, {%0, %1, %2, %3};"
    : "+f"(d[0]), "+f"(d[1]), "+f"(d[2]), "+f"(d[3]) : "r"(a[0]), "r"(a[1]), "r"(b0));
}

template <bool FIRST> __device__ __forceinline__ void mma_tile(float (&d)[32], const uint32_t (&a)[16], uint64_t db) {
  WG_FENCE();
#pragma unroll
  for (int s = 0; s < 4; s++) {
    if (FIRST && s == 0) wgmma64_set<1>(d, &a[0], db); else wgmma64_acc<1>(d, &a[4 * s], db + s * 128);
  }
  WG_COMMIT();
}
__device__ __forceinline__ void mma_tile_reuse(float (&d)[32], const uint32_t (&a)[16], uint64_t db) {
  WG_FENCE();
  wgmma64_reuse(d, &a[0], db, blockIdx.y);
#pragma unroll
  for (int s = 1; s < 4; s++) wgmma64_acc<1>(d, &a[4 * s], db + s * 128);
  WG_COMMIT();
}
template <int ROW> __device__ __forceinline__ void mma_tile_fold(float (&d)[32], const uint32_t (&a)[16], uint64_t db, const uint32_t (&mu)[4]) {
  WG_FENCE();
#pragma unroll
  for (int s = 0; s < 4; s++) wgmma64_acc<1>(d, &a[4 * s], db + s * 128);
  wgmma64_acc<1>(d, mu, (uint64_t)((SM_BASE + SM_CS + ROW * 128) >> 4) | (uint64_t(1) << 16) | (uint64_t(1) << 62));
  WG_COMMIT();
}
__device__ __forceinline__ void mma_add_half(float (&d)[32], const uint32_t (&a)[16]) {
  const uint64_t db = (uint64_t)((SM_BASE + SM_EYE) >> 4) | (uint64_t(8) << 16) | (uint64_t(8) << 32);
  WG_FENCE();
#pragma unroll
  for (int s = 0; s < 4; s++) wgmma16_acc(&d[8 * s], &a[4 * s], db);
  WG_COMMIT();
}
#define ACQUIRE(f) mbar_wait(SM_BASE + SM_FULL + ((f) % NSTAGE) * 8, ((f) / NSTAGE) & 1)
template <int F, int N> __device__ __forceinline__ void acquire_n() {
  static_assert(F % NSTAGE + N <= NSTAGE, "stages must not wrap");
  uint32_t spin = 0, ok;
  do {
    ok = 1;
#pragma unroll
    for (int i = 0; i < N; i++)
      asm volatile("{\n.reg .pred p;\nmbarrier.try_wait.parity.shared::cta.b64 p, [%1], %2;\nselp.u32 %0, %0, 0, p;\n}"
                   : "+r"(ok) : "r"(SM_BASE + SM_FULL + (F % NSTAGE + i) * 8), "r"((F / NSTAGE) & 1) : "memory");
  } while (!ok && ++spin < SPIN_LIMIT);
}
#define RELEASE(f0, f1) do { if (lane == 0) { _Pragma("unroll") for (int f_ = (f0); f_ <= (f1); f_++) mbar_arrive(SM_BASE + SM_EMPTY + (f_ % NSTAGE) * 8); } } while (0)
constexpr uint64_t RING = (uint64_t)(SM_BASE >> 4) | (uint64_t(1) << 16) | (uint64_t(64) << 32) | (uint64_t(1) << 62);
#define LO(f) (RING + ((f) % NSTAGE) * 1024)
#define HI(f) (RING + ((f) % NSTAGE) * 1024 + 512)

template <int C> __device__ __forceinline__ uint4* peer(uint4* p) {
  asm volatile("" : "+l"(p));
  return (uint4*)((uintptr_t)p ^ (C * X_SIZE * sizeof(uint4)));
}
__device__ __forceinline__ uint32_t clock_now() { uint32_t c; asm volatile("mov.u32 %0, %%clock;" : "=r"(c) :: "memory"); return c; }
__device__ __forceinline__ void publish(uint4* dst, uint32_t (&a)[16], uint32_t tag) {
#pragma unroll
  for (int s = 0; s < 4; s++) a[4 * s] = (a[4 * s] & ~1u) | tag;
  pin(a);
  SCHED();
#pragma unroll
  for (int s = 0; s < 4; s++) st_vec(dst + s * 128, a[4 * s], a[4 * s + 1], a[4 * s + 2], a[4 * s + 3]);
  SCHED();
}
__device__ __forceinline__ void fetch(const uint4* src, uint32_t (&a)[16]) {
#pragma unroll
  for (int s = 0; s < 4; s++) ld_vec(src + s * 128, a[4 * s], a[4 * s + 1], a[4 * s + 2], a[4 * s + 3]);
}
__device__ __forceinline__ uint32_t miss(const uint32_t (&a)[16], uint32_t tag) {
  return (a[0] ^ tag) | (a[4] ^ tag) | (a[8] ^ tag) | (a[12] ^ tag);
}
__device__ __forceinline__ bool stale(uint32_t v) { return __any_sync(0xffffffffu, here(v) & 1u); }
__device__ __forceinline__ void confirm(const uint4* src, uint32_t (&a)[16], uint32_t tag) {
  uint32_t spin = 0;
  while (__builtin_expect(stale(miss(a, tag)), 0) && ++spin < SPIN_LIMIT) fetch(src, a);
}
constexpr uint32_t GATHER_DELAY = 400;
template <int C0, int C1, int SLOT> __device__ __forceinline__ void gather_wait(uint32_t (&A)[4][16], uint4* xp, uint32_t tag) {
  uint32_t spin = 0;
  while (__builtin_expect(stale(miss(A[C0], tag) | miss(A[C1], tag)), 0) && ++spin < SPIN_LIMIT) {
    fetch(peer<C0>(xp) + SLOT, A[C0]);
    if (C1 != C0) fetch(peer<C1>(xp) + SLOT, A[C1]);
  }
}
template <int C, int SLOT> __device__ __forceinline__ void gather_first(uint32_t (&A)[4][16], uint4* xp, uint32_t tag, uint32_t sent) {
  while (clock_now() - sent < GATHER_DELAY) {}
  fetch(peer<1>(xp) + SLOT, A[1]); fetch(peer<2>(xp) + SLOT, A[2]); fetch(peer<3>(xp) + SLOT, A[3]);
  gather_wait<1, C, SLOT>(A, xp, tag);
}
template <int C, int SLOT> __device__ __forceinline__ void gather_rest(uint32_t (&A)[4][16], uint4* xp, uint32_t tag) {
  SCHED();
  gather_wait<C + 1, 3, SLOT>(A, xp, tag);
}
__device__ __forceinline__ void pack_acc(const float (&d)[32], uint32_t (&a)[16]) {
#pragma unroll
  for (int i = 0; i < 16; i++) a[i] = pack2(d[2 * i], d[2 * i + 1]);
}
__device__ __forceinline__ void res_store(uint32_t slot, const uint32_t (&a)[16]) {
#pragma unroll
  for (int s = 0; s < 4; s++) sts128(slot + s * 512, a[4 * s], a[4 * s + 1], a[4 * s + 2], a[4 * s + 3]);
}
__device__ __forceinline__ void res_load(uint32_t slot, float (&d)[32]) {
  uint32_t a[16];
#pragma unroll
  for (int s = 0; s < 4; s++) lds128(slot + s * 512, a[4 * s], a[4 * s + 1], a[4 * s + 2], a[4 * s + 3]);
#pragma unroll
  for (int i = 0; i < 16; i++) { d[2 * i] = bf_lo(a[i]); d[2 * i + 1] = bf_hi(a[i]); }
  pin(d);
}
__device__ __forceinline__ void tile_store(uint32_t maddr, const uint32_t (&a)[16]) {
#pragma unroll
  for (int s = 0; s < 4; s++) stsm4(maddr ^ (s << 5), &a[4 * s]);
}
__device__ __forceinline__ void tile_load(uint32_t maddr, uint32_t (&a)[16]) {
#pragma unroll
  for (int s = 0; s < 4; s++) ldsm4(maddr ^ (s << 5), &a[4 * s]);
}

struct RowAcc { float s[4], u[2][4], v[2][4]; };
__device__ __forceinline__ void row_acc(RowAcc& t, const uint32_t (&a)[16]) {
#pragma unroll
  for (int s = 0; s < 8; s++) {
    if ((s & 1) == 0) hmma(t.s, &a[2 * s], 0x3F803F80u, 0x3F803F80u);
    hmma8(t.u[s & 1], &a[2 * s], a[2 * s]);
    hmma8(t.v[s & 1], &a[2 * s], a[2 * s + 1]);
  }
}
__device__ __forceinline__ float2 row_squares(const RowAcc& t, bool odd) {
  return make_float2(odd ? t.u[0][1] + t.u[1][1] : t.u[0][0] + t.u[1][0], odd ? t.v[0][3] + t.v[1][3] : t.v[0][2] + t.v[1][2]);
}
__device__ __forceinline__ void stat_publish(const uint32_t (&a)[16], Scratch* sc, uint32_t th, uint32_t tag) {
  RowAcc t = {};
  row_acc(t, a);
  const float2 q = row_squares(t, th & 4);
  if ((th & 3) == ((th >> 3) & 3))
    st_vec(&sc->x[blockIdx.x][X_ST + (th >> 2)], (__float_as_uint(t.s[0]) & ~1u) | tag, __float_as_uint(q.x), __float_as_uint(t.s[2]), __float_as_uint(q.y));
}
struct RowNorm { float m0, rs0, m1, rs1; };
__device__ __forceinline__ RowNorm row_norm(float s0, float q0, float s1, float q1, float scale) {
  RowNorm n;
  n.m0 = s0 * (1.f / DM); n.m1 = s1 * (1.f / DM);
  n.rs0 = scale * rsqrtf(fmaxf(fmaf(-n.m0, n.m0, q0 * (1.f / DM)), 0.f) + LN_EPS);
  n.rs1 = scale * rsqrtf(fmaxf(fmaf(-n.m1, n.m1, q1 * (1.f / DM)), 0.f) + LN_EPS);
  return n;
}
__device__ __forceinline__ RowNorm stat_gather(Scratch* sc, uint32_t th, uint32_t tag, float scale) {
  const uint4* src = &sc->x[blockIdx.x & ~3u][X_ST + (th >> 2)];
  uint32_t v[16], spin = 0;
  do {
#pragma unroll
    for (int j = 0; j < 4; j++) ld_vec(src + j * X_SIZE, v[4 * j], v[4 * j + 1], v[4 * j + 2], v[4 * j + 3]);
  } while (stale(miss(v, tag)) && ++spin < SPIN_LIMIT);
  float f[4];
#pragma unroll
  for (int i = 0; i < 4; i++)
    f[i] = (__uint_as_float(v[i]) + __uint_as_float(v[4 + i])) + (__uint_as_float(v[8 + i]) + __uint_as_float(v[12 + i]));
  return row_norm(f[0], f[1], f[2], f[3], scale);
}
constexpr uint32_t SM_NORM = SM_BASE + SM_STG + 2 * TILE_BYTES + 4096;
__device__ __forceinline__ void norm_produce(const RowNorm& n, uint32_t th, uint32_t qsel) {
  const bool sel = (th & 3) == qsel;
  const float a = sel ? -n.m0 : 0.f, c = sel ? -n.m1 : 0.f;
  const uint32_t ah = pack2(a, a), ch = pack2(c, c);
  const float al = a - bf_lo(ah), cl = c - bf_lo(ch);
  sts128(SM_NORM + th * 16, ah, ch, pack2(al, al), pack2(cl, cl));
  sts64(SM_NORM + 2048 + th * 8, __float_as_uint(n.rs0), __float_as_uint(n.rs1));
  bar_arrive(BAR_ST, 256);
}
__device__ __forceinline__ void norm_duty(Scratch* sc, uint32_t th, uint32_t tag, float scale, uint32_t qsel) {
  bar_sync(BAR_RES, 256);
  norm_produce(stat_gather(sc, th, tag, scale), th, qsel);
}
__device__ __forceinline__ void norm_consume(uint32_t th, uint32_t (&mu)[4], float& rs0, float& rs1) {
  bar_sync(BAR_ST, 256);
  lds128(SM_NORM + th * 16, mu[0], mu[1], mu[2], mu[3]);
  asm volatile("ld.shared.v2.f32 {%0, %1}, [%2];" : "=f"(rs0), "=f"(rs1) : "r"(SM_NORM + 2048 + th * 8) : "memory");
}
__device__ __forceinline__ void scale_pack(const float (&d)[32], uint32_t (&a)[16], float rs0, float rs1) {
#pragma unroll
  for (int i = 0; i < 16; i++) { const float rs = (i & 1) ? rs1 : rs0; a[i] = pack2(d[2 * i] * rs, d[2 * i + 1] * rs); }
}
template <int S> __device__ __forceinline__ void silu_seg(float (&acc)[4][32], float (&tn)[2][4], uint32_t (&H)[4][16], float rs0, float rs1) {
  if (S >= 2) {
    const float* h = &acc[(S - 2) >> 3][4 * ((S - 2) & 7)];
    const float* v = tn[S & 1];
    uint32_t* o = &H[(S - 2) >> 3][2 * ((S - 2) & 7)];
    o[0] = pack2(fmaf(h[0], v[0], h[0]), fmaf(h[1], v[1], h[1]));
    o[1] = pack2(fmaf(h[2], v[2], h[2]), fmaf(h[3], v[3], h[3]));
    asm volatile("" : "+r"(o[0]), "+r"(o[1]));
  }
  if (S >= 1 && S <= 32) {
#pragma unroll
    for (int k = 0; k < 4; k++) tn[(S - 1) & 1][k] = tanh_hw(acc[((S - 1) >> 3) & 3][4 * ((S - 1) & 7) + k]);
  }
  if (S < 32) {
    float* h = &acc[(S >> 3) & 3][4 * (S & 7)];
    h[0] *= rs0; h[1] *= rs0; h[2] *= rs1; h[3] *= rs1;
    asm volatile("" : "+f"(h[0]), "+f"(h[1]), "+f"(h[2]), "+f"(h[3]));
  }
  SCHED();
}
template <int S0, int S1> __device__ __forceinline__ void silu_segs(float (&acc)[4][32], float (&tn)[2][4], uint32_t (&H)[4][16], float rs0, float rs1) {
  silu_seg<S0>(acc, tn, H, rs0, rs1);
  if constexpr (S0 + 1 < S1) silu_segs<S0 + 1, S1>(acc, tn, H, rs0, rs1);
}
template <int HALF> __device__ __forceinline__ void send_half(uint4* dst, const float (&d)[32], uint32_t tag) {
  uint32_t o[8];
#pragma unroll
  for (int i = 0; i < 8; i++) o[i] = pack2(d[16 * HALF + 2 * i], d[16 * HALF + 2 * i + 1]);
  o[0] = (o[0] & ~1u) | tag; o[4] = (o[4] & ~1u) | tag;
  pin(o);
  SCHED();
  st_vec(dst + HALF * 256, o[0], o[1], o[2], o[3]);
  st_vec(dst + HALF * 256 + 128, o[4], o[5], o[6], o[7]);
  SCHED();
}
__device__ __forceinline__ uint32_t send_residual(uint32_t (&a)[16], Scratch* sc, uint4* xp, uint32_t res, uint32_t tag) {
  const uint32_t exact[4] = {a[0], a[4], a[8], a[12]};
  publish(xp + X_AG0, a, tag);
  const uint32_t sent = clock_now();
  stat_publish(a, sc, threadIdx.x, tag);
  res_store(res, a);
#pragma unroll
  for (int s = 0; s < 4; s++) sts32(res + s * 512, exact[s]);
  bar_arrive(BAR_RES, 256);
  return sent;
}
template <int F, int N> __device__ __forceinline__ uint32_t proj_residual(uint32_t (&A)[4][16], Scratch* sc, uint4* xp, uint32_t res, uint32_t tag) {
  float acc[32];
  publish(xp + X_AG1, A[0], tag);
  const uint32_t sent = clock_now();
  acquire_n<F, N>();
  if (F == F_PW2) acquire_n<0, 5>();
  res_load(res, acc);
  mma_tile<false>(acc, A[0], LO(F));
  gather_first<2, X_AG1>(A, xp, tag, sent);
  mma_tile<false>(acc, A[1], HI(F));
  mma_tile<false>(acc, A[2], LO(F + 1));
  gather_rest<2, X_AG1>(A, xp, tag);
  PROF_MARK(F == F_WO ? 11 : 16);
  mma_tile<false>(acc, A[3], HI(F + 1));
  WG_WAIT(0); pin(acc);
  pack_acc(acc, A[0]);
  return send_residual(A[0], sc, xp, res, tag);
}

__device__ __forceinline__ void qk_tile(float (&S)[32], const uint32_t (&Q)[16], uint64_t dk) {
#pragma unroll
  for (int s = 0; s < 4; s++) {
    if (s == 0) wgmma64_set<0>(S, &Q[0], dk); else wgmma64_acc<0>(S, &Q[4 * s], dk + s * 2);
  }
}
__device__ __forceinline__ void qk_shift(float (&S)[32], const uint32_t (&nm)[4]) { wgmma64_acc<0>(S, nm, (uint64_t)((SM_BASE + SM_ONE) >> 4)); }
constexpr uint64_t V_STEP = uint64_t(1) - (uint64_t(1) << 16);
constexpr uint64_t RING_V = RING - (uint64_t(1) << 16) + ((uint64_t)((SM_STG + 2 * TILE_BYTES) >> 4) << 16);
__device__ __forceinline__ void pv_tile(float (&O)[36], const uint32_t (&P)[16], uint64_t dv, uint64_t pad) {
#pragma unroll
  for (int s = 0; s < 4; s++) wgmma72_acc(O, &P[4 * s], dv + s * 128 * V_STEP + (s < 2 ? 0 : (s - 1) * pad));
}
__device__ __forceinline__ void attn_step(const float (&Sc)[32], float (&Sn)[32], uint32_t (&Pc)[16], uint32_t (&Pp)[16], float (&O)[36],
                                          const uint32_t (&Q)[16], const uint32_t (&nm)[4], uint64_t dk, uint64_t dv) {
  WG_FENCE();
  qk_tile(Sn, Q, dk);
  qk_shift(Sn, nm);
  pv_tile(O, Pp, dv, 0);
  WG_COMMIT();
  SCHED();
#pragma unroll
  for (int i = 0; i < 16; i++) Pc[i] = pack2(ex2_hw(Sc[2 * i]), ex2_hw(Sc[2 * i + 1]));
  pin(Pc);
  SCHED();
}
template <int R> __device__ __forceinline__ float tile_max(const float (&S)[32]) {
  float t[4];
#pragma unroll
  for (int j = 0; j < 4; j++) t[j] = fmaxf(fmaxf(S[8 * j + R], S[8 * j + R + 1]), fmaxf(S[8 * j + R + 4], S[8 * j + R + 5]));
  float n = fmaxf(fmaxf(t[0], t[1]), fmaxf(t[2], t[3]));
  n = fmaxf(n, __shfl_xor_sync(0xffffffffu, n, 1));
  return fmaxf(n, __shfl_xor_sync(0xffffffffu, n, 2));
}
__device__ __forceinline__ void attention_exact(float (&O)[36], const uint32_t (&Q)[16], const Scratch* sc, int bh, int lane) {
  const char* kb = (const char*)&sc->kv[bh][0][0][0];
  const char* vb = (const char*)&sc->kv[bh][1][0][0];
  const int g = lane >> 2, q = lane & 3;
  float m0 = -INFINITY, m1 = -INFINITY, l0 = 0.f, l1 = 0.f;
  float o[8][4] = {};
#pragma unroll 1
  for (int k0 = 0; k0 < T_SEQ; k0 += 8) {
    float s[4] = {0.f, 0.f, 0.f, 0.f};
#pragma unroll
    for (int c = 0; c < 8; c++) hmma8(s, &Q[2 * c], __ldcg((const uint32_t*)(kb + (k0 + g) * 128 + ((c ^ g) << 4) + q * 4)));
    float n0 = fmaxf(s[0], s[1]), n1 = fmaxf(s[2], s[3]);
    n0 = fmaxf(n0, __shfl_xor_sync(0xffffffffu, n0, 1)); n1 = fmaxf(n1, __shfl_xor_sync(0xffffffffu, n1, 1));
    n0 = fmaxf(m0, fmaxf(n0, __shfl_xor_sync(0xffffffffu, n0, 2))); n1 = fmaxf(m1, fmaxf(n1, __shfl_xor_sync(0xffffffffu, n1, 2)));
    const float a0 = ex2_hw(m0 - n0), a1 = ex2_hw(m1 - n1);
    m0 = n0; m1 = n1;
    const uint32_t pp[2] = {pack2(ex2_hw(s[0] - n0), ex2_hw(s[1] - n0)), pack2(ex2_hw(s[2] - n1), ex2_hw(s[3] - n1))};
    l0 = fmaf(l0, a0, bf_lo(pp[0]) + bf_hi(pp[0])); l1 = fmaf(l1, a1, bf_lo(pp[1]) + bf_hi(pp[1]));
#pragma unroll
    for (int j = 0; j < 8; j++) {
      const uint32_t v0 = __ldcg((const uint16_t*)(vb + (k0 + 2 * q) * 128 + ((j ^ (2 * q)) << 4) + g * 2));
      const uint32_t v1 = __ldcg((const uint16_t*)(vb + (k0 + 2 * q + 1) * 128 + ((j ^ (2 * q + 1)) << 4) + g * 2));
      o[j][0] *= a0; o[j][1] *= a0; o[j][2] *= a1; o[j][3] *= a1;
      hmma8(o[j], pp, v0 | (v1 << 16));
    }
  }
  l0 += __shfl_xor_sync(0xffffffffu, l0, 1); l1 += __shfl_xor_sync(0xffffffffu, l1, 1);
  O[32] = l0 + __shfl_xor_sync(0xffffffffu, l0, 2); O[34] = l1 + __shfl_xor_sync(0xffffffffu, l1, 2);
#pragma unroll
  for (int i = 0; i < 32; i++) O[i] = o[i >> 2][i & 3];
}

__device__ __forceinline__ uint32_t fill_entry(int f, int r, int bh) {
  int m, x = r, y, dx = 0;
  if (f < F_QKV || f >= 48) {
    const int i = f & 15;
    m = f < F_QKV ? M_FF1A : M_FF2A;
    if (i < 8) { x = 4 * r + ((0xE2u >> i) & 1) * 2; y = r ^ ((0xE790u >> (2 * i)) & 3); dx = 1; }
    else { m++; x = r ^ (((i >> 1) - 3) & 3); y = 4 * r + 2 * (i & 1); }
  } else if (f < F_KV) {
    const int i = f - F_QKV;
    m = M_QKV;
    if (i == 1 || i >= 5) { y = r ^ (i == 1 ? 0 : 2); }
    else { x = 4 + r; y = r ^ (i ? i - 1 : 0); dx = 4; }
  } else if (f < F_WO) {
    const int i = f - F_KV;
    m = M_KV; x = 0; y = bh * 32 + (i & 2) * 8 + (i >> 2) * 4 + (i & 1) * 2;
  } else if (f >= F_PW1 && f < F_PW2) {
    m = M_PW1; y = r ^ (f - F_PW1); dx = 4;
  } else {
    m = f < F_PW1 ? M_WO : M_PW2; y = r ^ ((f & 1) * 2);
  }
  return m | (x << 4) | (y << 8) | (dx << 16);
}
__device__ __forceinline__ void tma_fill(uint32_t st, const CUtensorMap* map, uint32_t x, uint32_t y, uint32_t x2, uint32_t y2) {
  asm volatile("{\n.reg .pred p;\nelect.sync _|p, 0xffffffff;\n"
               "@p mbarrier.arrive.expect_tx.shared::cta.b64 _, [%1], 16384;\n"
               "@p cp.async.bulk.tensor.2d.shared::cluster.global.mbarrier::complete_tx::bytes [%0], [%2, {%3, %4}], [%1];\n"
               "@p cp.async.bulk.tensor.2d.shared::cluster.global.mbarrier::complete_tx::bytes [%0 + 8192], [%2, {%5, %6}], [%1];\n}"
               :: "r"(SM_BASE + st * STAGE_BYTES), "r"(SM_BASE + SM_FULL + st * 8), "l"(map), "r"(x), "r"(y), "r"(x2), "r"(y2) : "memory");
}
__device__ __forceinline__ void l2_prefetch(const void* p, uint32_t total, int b) {
  const uint32_t part = total / NCTA;
  asm volatile("cp.async.bulk.prefetch.L2.global [%0], %1;" :: "l"((const char*)p + (size_t)b * part), "r"(part) : "memory");
}

__global__ void __launch_bounds__(384, 1) conformer_kernel(Scratch* __restrict__ sc, __nv_bfloat16* __restrict__ out,
                                                           const __nv_bfloat16* __restrict__ dw, const __nv_bfloat16* __restrict__ xin,
                                                           const __nv_bfloat16* __restrict__ w_ff1a, const __grid_constant__ Params p) {
  extern __shared__ __align__(1024) uint8_t smem[];
  const int tid = threadIdx.x, lane = tid & 31;
  if (tid == 0) {
    l2_prefetch(xin, 2 * T_SEQ * DM * 2, blockIdx.x);
    l2_prefetch(w_ff1a, 256 * 1024 * 2, blockIdx.x);
  }
  const int cw = __shfl_sync(0xffffffffu, tid >> 5, 0), wg = cw >> 2, w = cw & 3;
  const int b = blockIdx.x, r = b & 3, batch = b >> 6, t = (b >> 2) & 15;
  if ((uint32_t)__cvta_generic_to_shared(smem) != SM_BASE) return;
  PROF_MARK(0);
  PROF_TIME(30);

  if (wg == 2) {
    asm volatile("setmaxnreg.dec.sync.aligned.u32 40;");
    if (cw == 8) {
      if (lane == 0) {
        asm volatile("prefetch.tensormap [%0];" :: "l"(&p.map[M_X]) : "memory");
        asm volatile("prefetch.tensormap [%0];" :: "l"(&p.map[M_FF1A]) : "memory");
        mbar_init(SM_BASE + SM_XBAR, 1);
#pragma unroll
        for (int i = 0; i < NSTAGE; i++) mbar_init(SM_BASE + SM_FULL + i * 8, 1);
        fence_async_smem();
      }
      __syncwarp();
      asm volatile("{\n.reg .pred p;\nelect.sync _|p, 0xffffffff;\n"
                   "@p mbarrier.arrive.expect_tx.shared::cta.b64 _, [%1], 32768;\n"
                   "@p cp.async.bulk.tensor.4d.shared::cluster.global.mbarrier::complete_tx::bytes [%0], [%2, {0, %3, 0, %4}], [%1];\n}"
                   :: "r"(SM_BASE + SM_STG), "r"(SM_BASE + SM_XBAR), "l"(&p.map[M_X]), "r"(t * 64), "r"(batch) : "memory");
      bar_arrive(0, 320);
      PROF_MARK(9);
#pragma unroll
      for (int f = 0; f < 8; f++) {
        const uint32_t x = 256 * r + ((0xE2u >> f) & 1) * 128, y = (r ^ ((0xE790u >> (2 * f)) & 3)) * 64;
        tma_fill(f, &p.map[M_FF1A], x, y, x + 64, y);
      }
      PROF_MARK(1);
      const uint32_t* flag = sc->flag[batch * 4 + r][lane];
      const uint32_t prev = ((volatile uint32_t*)sc->epoch)[b];
      uint32_t entry[2], ready = 0, st = 8, parity = 1;
#pragma unroll 1
      for (int i = 0; i < 2; i++) { entry[1] = fill_entry(i * 32 + lane, r, batch * 4 + r); if (i == 0) entry[0] = entry[1]; }
      bar_sync(BAR_INIT, 64);
#pragma unroll 1
      for (int f = 8; f < F_TOTAL; f++) {
        const uint32_t e = __shfl_sync(0xffffffffu, f < 32 ? entry[0] : entry[1], f);
        if ((e & 15) == M_KV) {
          const uint32_t need = 3u << ((e >> 8) & 31);
          uint32_t spin = 0;
#pragma unroll 1
          while ((ready & need) != need && ++spin < SPIN_LIMIT) {
            uint32_t v;
            asm volatile("ld.relaxed.gpu.global.u32 %0, [%1];" : "=r"(v) : "l"(flag) : "memory");
            ready = __ballot_sync(0xffffffffu, v - 1 == prev);
          }
        }
        if (f == F_KV) PROF_MARK(8);
        mbar_wait(SM_BASE + SM_EMPTY + st * 8, parity);
        const uint32_t x = (e << 2) & 0x3C0, y = (e >> 2) & 0x3FC0, dx = (e >> 16) << 6;
        tma_fill(st, &p.map[e & 15], x, y, x + dx, dx ? y : y ^ 64);
        if (++st == NSTAGE) { st = 0; parity ^= 1; }
      }
    } else if (here(cw) != 11) {
      const int kind = w - 1;
      const uint32_t prev = ((volatile uint32_t*)sc->epoch)[b];
      if (kind == 0) {
        if (lane == 0) {
#pragma unroll
          for (int i = 0; i < NSTAGE; i++) mbar_init(SM_BASE + SM_EMPTY + i * 8, 4);
        }
        __syncwarp();
        bar_arrive(0, 320);
        bar_arrive(BAR_INIT, 64);
        bar_sync(BAR_K, 160);
      } else {
        uint32_t v, spin = 0;
#pragma unroll 1
        do {
          asm volatile("ld.relaxed.gpu.global.u32 %0, [%1];" : "=r"(v) : "l"(sc->ready[(b & ~3) + (lane & 3)]) : "memory");
        } while (__any_sync(0xffffffffu, v - 1 != prev) && ++spin < SPIN_LIMIT);
        bar_arrive(BAR_RDY, 160);
        bar_arrive(BAR_RDY1, 160);
        bar_sync(BAR_V, 160);
      }
      if (lane == 0) {
        asm volatile("cp.async.bulk.global.shared::cta.bulk_group [%0], [%1], %2;"
                     :: "l"(&sc->kv[batch * 4 + r][kind][t][0]), "r"(SM_BASE + SM_STG + kind * TILE_BYTES), "r"(TILE_BYTES) : "memory");
        asm volatile("cp.async.bulk.commit_group;\ncp.async.bulk.wait_group 0;" ::: "memory");
        asm volatile("st.relaxed.gpu.global.u32 [%0], %1;" :: "l"(sc->flag[batch * 4 + r][kind * 16 + t]), "r"(prev + 1) : "memory");
      }
    } else {
      const uint32_t epoch = ((volatile uint32_t*)sc->epoch)[b] + 1;
      if (lane == 0 && epoch) {
        asm volatile("prefetch.tensormap [%0];" :: "l"(&p.map[M_FF1B]) : "memory");
        l2_prefetch(p.w_ff1b, 1024 * 256 * 2, b);
        l2_prefetch(p.w_qkv, 256 * 768 * 2, b);
        l2_prefetch(p.w_pw1, 256 * 512 * 2, b);
        l2_prefetch(p.w_ff2a, 256 * 1024 * 2, b);
      }
#pragma unroll 1
      for (int i = 0; i < 11; i++) {
        const uint32_t t0 = clock_now();
        uint4* dst = &sc->x[b][X_CLEAR + i * 96 + lane];
        st_vec(dst, 0u, 0u, 0u, 0u); st_vec(dst + 32, 0u, 0u, 0u, 0u); st_vec(dst + 64, 0u, 0u, 0u, 0u);
        while (clock_now() - t0 < 100) {}
      }
      asm volatile("fence.acq_rel.gpu;" ::: "memory");
      __syncwarp();
      if (lane == 0) {
        asm volatile("st.relaxed.gpu.global.u32 [%0], %1;" :: "l"(sc->ready[b]), "r"(epoch) : "memory");
        l2_prefetch(p.w_o, 256 * 256 * 2, b);
        l2_prefetch(p.w_pw2, 256 * 256 * 2, b);
        l2_prefetch(p.w_ff2b, 1024 * 256 * 2, b);
#pragma unroll
        for (int i = M_QKV; i < M_X; i++) asm volatile("prefetch.tensormap [%0];" :: "l"(&p.map[i]) : "memory");
      }
    }
  } else {
    asm volatile("setmaxnreg.inc.sync.aligned.u32 232;");
    if (tid < 144) sts128(SM_BASE + SM_CS + tid * 16, 0, 0, 0, 0);
    if (wg == 1) {
      const int i = tid - 128;
      sts32(SM_BASE + SM_EYE + i * 4, i >= 96 ? 0x3F803F80u : ((i & 32) == 0 && (i & 3) == ((i >> 3) & 3)) ? (0x3F00u << ((i & 4) * 4)) : 0u);
    }
    fence_async_smem();
    bar_sync(0, 320);
    const int q = lane & 3, th = tid & 127;
    constexpr uint32_t stg = SM_BASE + SM_STG;
    const uint32_t mrow = 16 * w + (lane & 15);
    const uint32_t maddr = stg + mrow * 128 + (((lane >> 4) ^ (lane & 7)) << 4);
    const uint32_t res = stg + 3 * TILE_BYTES + w * 2048 + lane * 16;
    uint4* const xp = &sc->x[b][th];
    const int nvalid = T_SEQ - t * 64, row0 = 16 * w + (lane >> 2);

    uint32_t A[4][16];
    uint32_t sent = 0;
    RowNorm n0;
#pragma unroll 1
    for (int real = 0; real < 2; real++) {
      if (real) mbar_wait(SM_BASE + SM_XBAR, 0);
      PROF_MARK(1);
#pragma unroll
      for (int c = 0; c < 4; c++) tile_load(maddr + (r ^ c) * TILE_BYTES, A[c]);
      if (wg == 0) {
        float sa[4] = {0.f, 0.f, 0.f, 0.f}, sb[4] = {0.f, 0.f, 0.f, 0.f};
#pragma unroll
        for (int i = 0; i < 16; i++) hmma((i & 1) ? sb : sa, &A[i >> 2][4 * (i & 3)], 0x3F803F80u, 0x3F803F80u);
        const float s0 = (sa[0] + sb[0]) * (1.f / DM), s1 = (sa[2] + sb[2]) * (1.f / DM);
        const uint32_t m0 = pack2(s0, s0), m1 = pack2(s1, s1);
#pragma unroll
        for (int c = 0; c < 4; c++) {
#pragma unroll
          for (int i = 0; i < 16; i++) asm("sub.rn.bf16x2 %0, %0, %1;" : "+r"(A[c][i]) : "r"((i & 1) ? m1 : m0));
          pin(A[c]);
        }
      } else {
        RowAcc ra[2] = {};
#pragma unroll
        for (int c = 0; c < 4; c++) row_acc(ra[c & 1], A[c]);
        const float2 qa = row_squares(ra[0], lane & 4), qb = row_squares(ra[1], lane & 4);
        const int src = (lane & 28) | (lane >> 3);
        const float q0 = __shfl_sync(0xffffffffu, qa.x + qb.x, src), q1 = __shfl_sync(0xffffffffu, qa.y + qb.y, src);
        n0 = row_norm(ra[0].s[0] + ra[1].s[0], q0, ra[0].s[2] + ra[1].s[2], q1, 0.5f);
        asm volatile("" : "+f"(n0.rs0), "+f"(n0.rs1));
      }
    }
    if (wg == 0) {
      bar_arrive(BAR_X, 256);
    } else {
      const uint32_t epoch = ((volatile uint32_t*)sc->epoch)[b] + 1, tag = epoch & 1;
      bar_sync(BAR_X, 256);
      res_store(res, A[0]);
      norm_produce(n0, th, 4);
      PROF_MARK(5);
      SCHED();
      uint4 cv[8];
      if (b < 72) {
        const __nv_bfloat16* wp; int ld, col;
        if (b < 24) { wp = p.w_qkv; ld = 768; col = b * 32; }
        else if (b < 40) { wp = p.w_pw1; ld = 512; col = (b - 24) * 32; }
        else { wp = p.w_ff2a; ld = 1024; col = (b - 40) * 32; }
        const uint4* src = (const uint4*)(wp + (size_t)(th >> 2) * ld + col + q * 8);
#pragma unroll
        for (int i = 0; i < 8; i++) cv[i] = __ldg(src + i * 4 * ld);
      }
      if (b < 72) {
        float c[8] = {0.f, 0.f, 0.f, 0.f, 0.f, 0.f, 0.f, 0.f};
#pragma unroll
        for (int i = 0; i < 8; i++) {
          const uint4 v = cv[i];
          c[0] += bf_lo(v.x); c[1] += bf_hi(v.x); c[2] += bf_lo(v.y); c[3] += bf_hi(v.y);
          c[4] += bf_lo(v.z); c[5] += bf_hi(v.z); c[6] += bf_lo(v.w); c[7] += bf_hi(v.w);
        }
#pragma unroll 1
        for (int m = 4; m <= 16; m <<= 1)
#pragma unroll
          for (int k = 0; k < 8; k++) c[k] += __shfl_xor_sync(0xffffffffu, c[k], m);
        if (lane < 4) {
          const uint32_t a = SM_BASE + SM_CS + 1792 + w * 128 + lane * 32;
          sts128(a, __float_as_uint(c[0]), __float_as_uint(c[1]), __float_as_uint(c[2]), __float_as_uint(c[3]));
          sts128(a + 16, __float_as_uint(c[4]), __float_as_uint(c[5]), __float_as_uint(c[6]), __float_as_uint(c[7]));
        }
        bar_sync(BAR_WG1, 128);
        if (th < 8) {
          float o[4] = {0.f, 0.f, 0.f, 0.f};
#pragma unroll 1
          for (int k = 0; k < 4; k++) {
            uint32_t e[4];
            lds128(SM_BASE + SM_CS + 1792 + k * 128 + th * 16, e[0], e[1], e[2], e[3]);
#pragma unroll
            for (int i = 0; i < 4; i++) o[i] += __uint_as_float(e[i]);
          }
          st_vec(&sc->cs[b * 8 + th], (__float_as_uint(o[0]) & ~1u) | tag, __float_as_uint(o[1]), __float_as_uint(o[2]), __float_as_uint(o[3]));
        }
      }
      bar_sync(BAR_WG1, 128);
      PROF_MARK(2);
#pragma unroll 1
      for (int i = th; i < 144; i += 128) {
        const int j = i >> 4;
        int src;
        if (j < CS_PW1) src = 320 + 64 * r + i;
        else if (j < CS_QKV) src = 192 + (j - CS_PW1) * 64 + 16 * r + (i & 15);
        else src = ((j - CS_QKV + 1) % 3) * 64 + 16 * r + (i & 15);
        uint32_t e[4], spin = 0;
#pragma unroll 1
        do {
          ld_vec(&sc->cs[src], e[0], e[1], e[2], e[3]);
        } while (((e[0] ^ tag) & 1u) && ++spin < SPIN_LIMIT);
        const float c0 = __uint_as_float(e[0] & ~1u), c1 = __uint_as_float(e[1]), c2 = __uint_as_float(e[2]), c3 = __uint_as_float(e[3]);
        const uint32_t h0 = pack2(c0, c1), h1 = pack2(c2, c3);
        const uint32_t a = SM_BASE + SM_CS + j * 256 + (i & 15) * 8;
        sts64(a ^ ((a >> 3) & 0x70), h0, h1);
        sts64((a + 128) ^ (((a + 128) >> 3) & 0x70), pack2(c0 - bf_lo(h0), c1 - bf_hi(h0)), pack2(c2 - bf_lo(h1), c3 - bf_hi(h1)));
      }
      fence_async_smem();
      PROF_MARK(4);
      bar_sync(BAR_RDY1, 160);
      norm_duty(sc, th, 1, 1.f, 3);
    }

#pragma unroll 1
    for (uint32_t pass = 0; pass < 2; pass++) {
      uint32_t Q[16];
      if (wg == 0) {
        float acc[4][32];
        uint32_t H[4][16];
        if (!pass) { PROF_MARK(47); ACQUIRE(0); PROF_MARK(48); }
        mma_tile<true>(acc[0], A[0], LO(0)); mma_tile<true>(acc[1], A[0], HI(0));
        if (!pass) ACQUIRE(1);
        mma_tile<true>(acc[2], A[0], LO(1)); mma_tile<true>(acc[3], A[0], HI(1));
        if (pass) gather_first<1, X_AG0>(A, xp, 1, sent); else acquire_n<2, 3>();
        mma_tile<false>(acc[0], A[1], LO(2)); mma_tile<false>(acc[1], A[1], HI(2));
        if (pass) { gather_rest<1, X_AG0>(A, xp, 1); RELEASE(F_PW2, F_PW2 + 1); }
        PROF_MARK(2 + pass * 16);
        mma_tile<false>(acc[0], A[2], LO(3));
        WG_WAIT(3);
        uint32_t mu[4];
        float rs0, rs1, tn[2][4];
        norm_consume(here(th), mu, rs0, rs1);
        mma_tile_fold<2 * CS_FF2>(acc[0], A[3], LO(4), mu);
        RELEASE(0, 1);
        acquire_n<5, 3>();
        mma_tile<false>(acc[1], A[2], HI(3));
#define SEGS(a, b) silu_segs<a, b>(acc, tn, H, rs0, rs1)
        WG_WAIT(1); pin(acc[0]);
        SEGS(0, 1);
        mma_tile_fold<2 * CS_FF2 + 2>(acc[1], A[3], HI(4), mu);
        SEGS(1, 4);
        mma_tile<false>(acc[2], A[1], LO(5));
        SEGS(4, 6);
        mma_tile<false>(acc[2], A[2], LO(6));
        SEGS(6, 8);
        WG_WAIT(2); pin(acc[1]);
        RELEASE(2, 4);
        SEGS(8, 9);
        mma_tile_fold<2 * CS_FF2 + 4>(acc[2], A[3], LO(7), mu);
        SEGS(9, 12);
        mma_tile<false>(acc[3], A[1], HI(5));
        acquire_n<8, 2>();
        SEGS(12, 14);
        mma_tile<false>(acc[3], A[2], HI(6));
        SEGS(14, 16);
        WG_WAIT(2); pin(acc[2]);
        SEGS(16, 17);
        mma_tile_fold<2 * CS_FF2 + 6>(acc[3], A[3], HI(7), mu);
        SEGS(17, 20);
        mma_tile_reuse(acc[1], H[0], LO(8));
        acquire_n<10, 2>();
        SEGS(20, 22);
        mma_tile<false>(acc[1], H[1], HI(8));
        SEGS(22, 24);
        WG_WAIT(2); pin(acc[3]);
        RELEASE(5, 7);
        SEGS(24, 26);
        mma_tile<false>(acc[1], H[2], LO(9));
        SEGS(26, 28);
        mma_tile_reuse(acc[2], H[0], LO(10));
        SEGS(28, 31);
        mma_tile<false>(acc[2], H[1], HI(10));
        SEGS(31, 34);
#undef SEGS
        PROF_MARK(3 + pass * 16);
        const uint32_t rtag = here(pass ^ 1);
        const uint4* rs_in = xp + X_RS;
        mma_tile<false>(acc[1], H[3], HI(9));
        mma_tile<false>(acc[2], H[2], LO(11));
        acquire_n<12, 2>();
        uint4* rs_out = peer<1>(xp) + X_RS;
        mma_tile<false>(acc[2], H[3], HI(11));
        WG_WAIT(2); pin(acc[1]);
        RELEASE(8, 9);
        send_half<0>(rs_out, acc[1], rtag);
        mma_tile_reuse(acc[3], H[0], LO(12));
        SCHED();
        send_half<1>(rs_out, acc[1], rtag);
        mma_tile<false>(acc[3], H[1], HI(12));
        rs_out = peer<2>(xp) + X_RS + 512;
        WG_WAIT(2); pin(acc[2]);
        send_half<0>(rs_out, acc[2], rtag);
        mma_tile<false>(acc[3], H[2], LO(13));
        SCHED();
        send_half<1>(rs_out, acc[2], rtag);
        mma_tile<false>(acc[3], H[3], HI(13));
        acquire_n<14, 2>();
        mma_tile_reuse(acc[1], H[0], LO(14));
        rs_out = peer<3>(xp) + X_RS + 1024;
        if (!pass) bar_sync(BAR_RDY, 160);
        fetch(rs_in, A[1]);
        SCHED();
        mma_tile<false>(acc[1], H[1], HI(14));
        WG_WAIT(2); pin(acc[3]);
        send_half<0>(rs_out, acc[3], rtag);
        send_half<1>(rs_out, acc[3], rtag);
        mma_tile<false>(acc[1], H[2], LO(15)); mma_tile<false>(acc[1], H[3], HI(15));
        SCHED();
        res_load(res, acc[2]);
        if (!pass) acquire_n<F_QKV, 3>();
        confirm(rs_in, A[1], rtag);
        mma_add_half(acc[2], A[1]);
        PROF_MARK(44);
        fetch(rs_in + 512, A[2]);
        fetch(rs_in + 1024, A[3]);
        confirm(rs_in + 512, A[2], rtag);
        mma_add_half(acc[2], A[2]);
        SCHED();
        confirm(rs_in + 1024, A[3], rtag);
        mma_add_half(acc[2], A[3]);
        PROF_MARK(4 + pass * 16);
        WG_WAIT(0); pin(acc[2]); pin(acc[1]);
#pragma unroll
        for (int i = 0; i < 16; i++) A[0][i] = pack2(fmaf(acc[1][2 * i], 0.5f, acc[2][2 * i]), fmaf(acc[1][2 * i + 1], 0.5f, acc[2][2 * i + 1]));
        if (pass) {
          PROF_MARK(21);
          stat_publish(A[0], sc, here(th), 0);
          const RowNorm fn = stat_gather(sc, here(th), 0, 1.f);
          const float nm0 = -fn.m0 * fn.rs0, nm1 = -fn.m1 * fn.rs1;
#pragma unroll
          for (int i = 0; i < 16; i++) {
            const float rs = (i & 1) ? fn.rs1 : fn.rs0, nm = (i & 1) ? nm1 : nm0;
            A[0][i] = pack2(fmaf(bf_lo(A[0][i]), rs, nm), fmaf(bf_hi(A[0][i]), rs, nm));
          }
          tile_store(here(maddr), A[0]);
          __syncwarp();
          const int row = 16 * w + (lane >> 3);
          uint4* dst = (uint4*)(out + ((size_t)batch * T_SEQ + t * 64 + row) * DM + 64 * r) + (lane & 7);
          const uint32_t src = stg + row * 128 + (((lane & 7) ^ (lane >> 3)) << 4);
#pragma unroll
          for (int i = 0; i < 4; i++) {
            uint4 v;
            lds128((src ^ ((i & 1) << 6)) + i * 512, v.x, v.y, v.z, v.w);
            if (row + 4 * i < nvalid) dst[i * 4 * (DM / 8)] = v;
          }
          PROF_MARK(22);
          PROF_TIME(31);
          break;
        }
        sent = send_residual(A[0], sc, xp, res, 1);
        PROF_MARK(5);
        mma_tile<true>(acc[0], A[0], LO(F_QKV)); mma_tile<true>(acc[1], A[0], HI(F_QKV));
        mma_tile<true>(acc[2], A[0], LO(F_QKV + 1));
        gather_first<1, X_AG0>(A, xp, 1, sent);
        mma_tile<false>(acc[0], A[1], LO(F_QKV + 2)); mma_tile<false>(acc[1], A[1], HI(F_QKV + 2));
        acquire_n<F_QKV + 3, 3>();
        gather_rest<1, X_AG0>(A, xp, 1);
        PROF_MARK(6);
        mma_tile<false>(acc[0], A[2], LO(F_QKV + 3));
        norm_consume(here(th), mu, rs0, rs1);
        if (row0 >= nvalid) rs0 = 0.f;
        if (row0 + 8 >= nvalid) rs1 = 0.f;
        mma_tile_fold<2 * CS_QKV - 6>(acc[0], A[3], LO(F_QKV + 4), mu);
        RELEASE(10, 15);
        mma_tile<false>(acc[1], A[2], HI(F_QKV + 3));
        mma_tile_fold<2 * CS_QKV - 4>(acc[1], A[3], HI(F_QKV + 4), mu);
        WG_WAIT(2); pin(acc[0]);
        scale_pack(acc[0], Q, rs0, rs1);
        tile_store(here(maddr), Q);
        fence_async_smem();
        bar_arrive(BAR_K, 160);
        mma_tile<false>(acc[2], A[1], HI(F_QKV + 1)); mma_tile<false>(acc[2], A[2], LO(F_QKV + 5));
        WG_WAIT(2); pin(acc[1]);
        scale_pack(acc[1], Q, rs0, rs1);
        tile_store(here(maddr) + TILE_BYTES, Q);
        fence_async_smem();
        bar_arrive(BAR_V, 160);
        mma_tile_fold<2 * CS_QKV - 2>(acc[2], A[3], HI(F_QKV + 5), mu);
        WG_WAIT(0); pin(acc[2]);
        scale_pack(acc[2], Q, rs0 * SM_SCALE_LOG2, rs1 * SM_SCALE_LOG2);
        res_store(here(res) - TILE_BYTES, Q);
        bar_arrive(BAR_Q, 256);
        RELEASE(F_QKV, F_QKV + 5);
      } else {
        bar_sync(BAR_Q, 256);
#pragma unroll
        for (int s = 0; s < 4; s++) lds128(res - TILE_BYTES + s * 512, Q[4 * s], Q[4 * s + 1], Q[4 * s + 2], Q[4 * s + 3]);
        if (w < 2) {
          const uint32_t v = w ? 0u : 0x3F803F80u;
#pragma unroll
          for (int s = 0; s < 4; s++) sts128(res - TILE_BYTES + s * 512, v, v, v, v);
          fence_async_smem();
        }
      }
      bar_sync(BAR_ATT, 256);
      PROF_MARK(7);

      const int dir = cw == 0 ? -1 : 1;
      uint32_t tap[15];
      {
        const uint32_t* dwp = (const uint32_t*)(dw + 64 * r) + lane + 7 * (DM / 2);
#pragma unroll
        for (int k = 0; k < 15; k++) tap[k] = __ldg(dwp + dir * (k - 7) * (DM / 2));
      }

      float O[36];
      {
        float S[2][32];
        uint32_t P[2][16], nm[4];
        pin(Q);
        WG_FENCE();
        qk_tile(S[0], Q, RING + (SM_STG >> 4));
        WG_COMMIT();
#pragma unroll
        for (int i = 0; i < 36; i++) O[i] = 0.f;
#pragma unroll
        for (int i = 0; i < 16; i++) P[1][i] = 0u;
        WG_WAIT(0); pin(S[0]);
        const float m0 = tile_max<0>(S[0]), m1 = tile_max<2>(S[0]);
        nm[0] = pack2(q ? 0.f : -m0, 0.f); nm[1] = pack2(q ? 0.f : -m1, 0.f); nm[2] = 0u; nm[3] = 0u;
#pragma unroll
        for (int k = 0; k < 15; k++) asm("mul.rn.bf16x2 %0, %0, %1;" : "+r"(tap[k]) : "r"(0x3F003F00u));
        pin(nm); pin(O); pin(P[1]); pin(tap);
        uint32_t sk = wg, sv = wg;
        mbar_wait(SM_BASE + SM_FULL + (F_SPARE % NSTAGE + wg) * 8, 1);
        if (lane == 0) mbar_arrive(SM_BASE + SM_EMPTY + (F_SPARE % NSTAGE + wg) * 8);
        mbar_wait(SM_BASE + SM_FULL + sk * 8, 0);
        PROF_MARK(8);
        WG_FENCE();
        qk_tile(S[0], Q, RING + sk * 1024);
        qk_shift(S[0], nm);
        WG_COMMIT();
        WG_WAIT(0); pin(S[0]);
#pragma unroll 1
        for (int it = 0; it < 4; it++) {
          attn_step(S[0], S[1], P[0], P[1], O, Q, nm, RING + sk * 1024 + 512, RING_V + (sv * 1024 + 512) * V_STEP);
          const uint32_t sn = it == 2 ? wg : sk + (it == 3 ? 2 : 4);
          mbar_wait(SM_BASE + SM_FULL + sn * 8, it >= 2);
          mbar_wait(SM_BASE + SM_FULL + (sk + 2) * 8, it == 3);
          WG_WAIT(0); pin(O); pin(S[1]); pin(P[1]);
          if (lane == 0) {
            mbar_arrive(SM_BASE + SM_EMPTY + sk * 8);
            if (it) mbar_arrive(SM_BASE + SM_EMPTY + sv * 8);
          }
          sv = sk + 2; sk = sn;
          attn_step(S[1], S[0], P[1], P[0], O, Q, nm, RING + sk * 1024, RING_V + (sv * 1024) * V_STEP);
          WG_WAIT(0); pin(O); pin(S[0]); pin(P[0]);
        }
        WG_FENCE();
        pv_tile(O, P[1], RING_V + (sv * 1024 + 512) * V_STEP, (uint64_t)wg << 22);
        WG_COMMIT();
        WG_WAIT(0); pin(O);
      }
      PROF_MARK(9);

      if (wg == 1) {
        const uint32_t mo = stg + here(th) * 16;
#pragma unroll
        for (int i = 0; i < 9; i++)
          sts128(mo + i * 2048 + (i >> 3) * 4096, __float_as_uint(O[4 * i]), __float_as_uint(O[4 * i + 1]), __float_as_uint(O[4 * i + 2]), __float_as_uint(O[4 * i + 3]));
        bar_arrive(BAR_MERGE, 256);
        norm_duty(sc, here(th), 0, 0.5f, 0);
      } else {
        const uint32_t mo = stg + here(th) * 16;
        bar_sync(BAR_MERGE, 256);
#pragma unroll
        for (int i = 8; i >= 0; i--) {
          uint32_t e[4];
          lds128(mo + i * 2048 + (i >> 3) * 4096, e[0], e[1], e[2], e[3]);
#pragma unroll
          for (int k = 0; k < 4; k++) O[4 * i + k] += __uint_as_float(e[k]);
        }
        const bool safe = O[32] > 0x1p-60f && O[32] < 0x1p60f && O[34] > 0x1p-60f && O[34] < 0x1p60f;
        if (__builtin_expect(__any_sync(0xffffffffu, !safe), 0)) attention_exact(O, Q, sc, batch * 4 + r, lane);
        const float i0 = rcp_hw(O[32]), i1 = rcp_hw(O[34]);
#pragma unroll
        for (int i = 0; i < 16; i++) { const float v = (i & 1) ? i1 : i0; A[0][i] = pack2(O[2 * i] * v, O[2 * i + 1] * v); }
        PROF_MARK(10);
        sent = proj_residual<F_WO, 6>(A, sc, xp, res, 0);
        PROF_MARK(12);
        float acc[2][32];
        mma_tile<true>(acc[0], A[0], LO(F_PW1)); mma_tile<true>(acc[1], A[0], HI(F_PW1));
        gather_first<1, X_AG0>(A, xp, 0, sent);
        mma_tile<false>(acc[1], A[1], HI(F_PW1 + 1)); mma_tile<false>(acc[0], A[1], LO(F_PW1 + 1));
        gather_rest<1, X_AG0>(A, xp, 0);
        PROF_MARK(13);
        mma_tile<false>(acc[1], A[2], HI(F_PW1 + 2));
        uint32_t mu[4];
        float rs0, rs1;
        norm_consume(here(th), mu, rs0, rs1);
        if (row0 >= nvalid) rs0 = 0.f;
        if (row0 + 8 >= nvalid) rs1 = 0.f;
        mma_tile_fold<2 * CS_PW1 + 2>(acc[1], A[3], HI(F_PW1 + 3), mu);
        RELEASE(F_KV + 14, F_WO + 1);
        mma_tile<false>(acc[0], A[2], LO(F_PW1 + 2));
        mma_tile_fold<2 * CS_PW1>(acc[0], A[3], LO(F_PW1 + 3), mu);
        WG_WAIT(2); pin(acc[1]);
#pragma unroll
        for (int i = 0; i < 32; i++) acc[1][i] = tanh_hw(acc[1][i] * ((i & 2) ? rs1 : rs0));
#pragma unroll
        for (int i = 0; i < 32; i++) { const float rs = (i & 2) ? rs1 : rs0; acc[1][i] = fmaf(acc[1][i], rs, rs); }
        pin(acc[1]);
        SCHED();
        WG_WAIT(0); pin(acc[0]);
#pragma unroll
        for (int i = 0; i < 16; i++) A[0][i] = pack2(acc[0][2 * i] * acc[1][2 * i], acc[0][2 * i + 1] * acc[1][2 * i + 1]);
        const uint32_t ga = stg + TILE_BYTES + here(mrow) * G_PITCH + (lane >> 4) * 16;
#pragma unroll
        for (int s = 0; s < 4; s++) stsm4(ga + s * 32, &A[0][4 * s]);
        RELEASE(F_PW1, F_PW1 + 3);
      }
#pragma unroll 1
      for (int real = wg ^ 1; real < 2; real++) {
        if (real) bar_sync(BAR_G, 256);
        PROF_MARK(14);
        const int first = cw == 0 ? 14 : 8 * cw - 7;
        const uint32_t gsrc = stg + TILE_BYTES + first * G_PITCH + lane * 4;
        uint32_t in[22];
#pragma unroll
        for (int i = 0; i < 15; i++) in[i] = lds32(gsrc + dir * i * (int)G_PITCH);
        const bool edge = cw == 0 || cw == 7;
        const bool nbr = real && (cw == 0 ? t > 0 : t < 15);
        if (edge) {
          if (nbr) {
            uint4* dst = &sc->x[b + 4 * dir][X_HALO + (cw == 0 ? 96 : 0) + lane];
            st_vec(dst, HALO_TAG, in[14], in[13], in[12]);
            st_vec(dst + 32, HALO_TAG, in[11], in[10], in[9]);
            st_vec(dst + 64, HALO_TAG, in[8], 0u, 0u);
          }
        } else {
#pragma unroll
          for (int i = 15; i < 22; i++) in[i] = lds32(gsrc + i * G_PITCH);
        }
        uint32_t cv[8];
#pragma unroll
        for (int i = 0; i < 15; i++)
#pragma unroll
          for (int o = 0; o < 8; o++) {
            if (i == o) asm("mul.rn.bf16x2 %0, %1, %2;" : "=r"(cv[o]) : "r"(in[i]), "r"(tap[0]));
            if (i > o) asm("fma.rn.bf16x2 %0, %1, %2, %0;" : "+r"(cv[o]) : "r"(in[i]), "r"(tap[i - o]));
          }
        pin(cv);
        PROF_MARK(45);
        if (edge) {
#pragma unroll
          for (int i = 15; i < 22; i++) in[i] = 0u;
          if (nbr) {
            const uint4* src = &sc->x[b][X_HALO + (cw == 0 ? 0 : 96) + lane];
            uint32_t e0, e1, e2, u0, u1, spin = 0;
#pragma unroll 1
            do {
              ld_vec(src, e0, in[15], in[16], in[17]);
              ld_vec(src + 32, e1, in[18], in[19], in[20]);
              ld_vec(src + 64, e2, in[21], u0, u1);
            } while (__any_sync(0xffffffffu, ((e0 ^ HALO_TAG) | (e1 ^ HALO_TAG) | (e2 ^ HALO_TAG)) != 0) && ++spin < SPIN_LIMIT);
          }
        }
#pragma unroll
        for (int i = 15; i < 22; i++)
#pragma unroll
          for (int o = 0; o < 8; o++)
            if (i - o <= 14) asm("fma.rn.bf16x2 %0, %1, %2, %0;" : "+r"(cv[o]) : "r"(in[i]), "r"(tap[i - o]));
        PROF_MARK(46);
        const uint32_t fl = cw == 0 ? 7 : 0;
        const uint32_t cdst = (stg + cw * 1024 + lane * 4) ^ (fl * 144);
#pragma unroll
        for (int o = 0; o < 8; o++) {
          const float a = bf_lo(cv[o]), c = bf_hi(cv[o]);
          sts32(cdst ^ (o * 144), pack2(fmaf(a, tanh_hw(a), a), fmaf(c, tanh_hw(c), c)));
        }
      }
      if (wg == 1) {
        bar_arrive(BAR_C, 256);
        norm_duty(sc, here(th), 1, 0.5f, 0);
        if (th == 0) ((volatile uint32_t*)sc->epoch)[b] += 1;
        break;
      }
      bar_sync(BAR_C, 256);
      tile_load(here(maddr), A[0]);
      PROF_MARK(15);
      sent = proj_residual<F_PW2, 2>(A, sc, xp, res, 1);
      PROF_MARK(17);
    }
  }
}

typedef CUresult (*EncodeFn)(CUtensorMap*, CUtensorMapDataType, cuuint32_t, void*, const cuuint64_t*, const cuuint64_t*,
                             const cuuint32_t*, const cuuint32_t*, CUtensorMapInterleave, CUtensorMapSwizzle,
                             CUtensorMapL2promotion, CUtensorMapFloatOOBfill);

void make_map(EncodeFn fn, CUtensorMap* m, const void* w, int rows, int cols, CUtensorMapSwizzle swz) {
  const cuuint64_t dims[2] = {(cuuint64_t)cols, (cuuint64_t)rows}, strides[1] = {(cuuint64_t)cols * 2};
  const cuuint32_t box[2] = {64, 64}, es[2] = {1, 1};
  fn(m, CU_TENSOR_MAP_DATA_TYPE_BFLOAT16, 2, const_cast<void*>(w), dims, strides, box, es, CU_TENSOR_MAP_INTERLEAVE_NONE,
     swz, CU_TENSOR_MAP_L2_PROMOTION_L2_128B, CU_TENSOR_MAP_FLOAT_OOB_FILL_NONE);
}

}

extern "C" void kernel_launch(void* const* d_in, const int* in_sizes, int n_in, void* d_out, int out_size) {
  static EncodeFn fn = nullptr;
  static Scratch* sc = nullptr;
  if (!fn) {
    void* f = nullptr;
    cudaDriverEntryPointQueryResult st;
    cudaGetDriverEntryPoint("cuTensorMapEncodeTiled", &f, cudaEnableDefault, &st);
    fn = (EncodeFn)f;
    void* raw = nullptr;
    cudaGetSymbolAddress(&raw, g_scratch);
    sc = (Scratch*)(((uintptr_t)raw + X_ALIGN - 1) & ~(uintptr_t)(X_ALIGN - 1));
    cudaFuncSetAttribute(conformer_kernel, cudaFuncAttributeMaxDynamicSharedMemorySize, SM_TOTAL);
  }
  typedef const __nv_bfloat16* W;
  const CUtensorMapSwizzle S = CU_TENSOR_MAP_SWIZZLE_128B;
  Params p;
  {
    const cuuint64_t dims[4] = {64, T_SEQ, 4, 2}, strides[3] = {512, 128, T_SEQ * 512};
    const cuuint32_t box[4] = {64, 64, 4, 1}, es[4] = {1, 1, 1, 1};
    fn(&p.map[M_X], CU_TENSOR_MAP_DATA_TYPE_BFLOAT16, 4, d_in[0], dims, strides, box, es, CU_TENSOR_MAP_INTERLEAVE_NONE, S,
       CU_TENSOR_MAP_L2_PROMOTION_L2_128B, CU_TENSOR_MAP_FLOAT_OOB_FILL_NONE);
  }
  make_map(fn, &p.map[M_FF1A], d_in[1], 256, 1024, S);
  make_map(fn, &p.map[M_FF1B], d_in[2], 1024, 256, S);
  make_map(fn, &p.map[M_QKV], d_in[3], 256, 768, S);
  make_map(fn, &p.map[M_KV], sc->kv, 16384, 64, CU_TENSOR_MAP_SWIZZLE_NONE);
  make_map(fn, &p.map[M_WO], d_in[4], 256, 256, S);
  make_map(fn, &p.map[M_PW1], d_in[5], 256, 512, S);
  make_map(fn, &p.map[M_PW2], d_in[7], 256, 256, S);
  make_map(fn, &p.map[M_FF2A], d_in[8], 256, 1024, S);
  make_map(fn, &p.map[M_FF2B], d_in[9], 1024, 256, S);
  p.w_ff1b = (W)d_in[2]; p.w_qkv = (W)d_in[3]; p.w_o = (W)d_in[4]; p.w_pw1 = (W)d_in[5];
  p.w_pw2 = (W)d_in[7]; p.w_ff2a = (W)d_in[8]; p.w_ff2b = (W)d_in[9];

  cudaLaunchConfig_t cfg = {};
  cfg.gridDim = dim3(NCTA);
  cfg.blockDim = dim3(384);
  cfg.dynamicSmemBytes = SM_TOTAL;
  cfg.stream = cudaStreamPerThread;
  cudaLaunchAttribute at[1];
  at[0].id = cudaLaunchAttributeCooperative;
  at[0].val.cooperative = 1;
  cfg.attrs = at;
  cfg.numAttrs = 1;
  cudaLaunchKernelEx(&cfg, conformer_kernel, sc, (__nv_bfloat16*)d_out, (W)d_in[6], (W)d_in[0], (W)d_in[1], p);
}
```

```cpp
#include <cuda_runtime.h>
#include <cuda_bf16.h>
#include <cuda.h>
#include <stdint.h>

namespace {

constexpr int T_SEQ = 1000;
constexpr int DM = 256;
constexpr int NCTA = 128;
constexpr int NSTAGE = 12;
constexpr uint32_t STAGE_BYTES = 16384;
constexpr uint32_t TILE_BYTES = 8192;
constexpr uint32_t SM_BASE = 1024;
constexpr uint32_t SM_STG = NSTAGE * STAGE_BYTES;
constexpr uint32_t SM_FULL = SM_STG + 32768;
constexpr uint32_t SM_EMPTY = SM_FULL + 96;
constexpr uint32_t SM_XBAR = SM_FULL + 192;
constexpr uint32_t SM_EYE = SM_FULL + 256;
constexpr uint32_t SM_ONE = SM_FULL + 640;
constexpr uint32_t SM_CS = SM_FULL + 768;
constexpr uint32_t SM_TOTAL = SM_FULL + 3072;
constexpr int CS_FF2 = 0, CS_PW1 = 4, CS_QKV = 6;
constexpr uint32_t SPIN_LIMIT = 1u << 16;
constexpr float LN_EPS = 1e-5f;
constexpr float SM_SCALE_LOG2 = 0.125f * 1.4426950408889634f;
constexpr uint32_t G_PITCH = 144;

constexpr int F_QKV = 16, F_SPARE = 22, F_KV = 24, F_WO = 40, F_PW1 = 42, F_PW2 = 46, F_TOTAL = 64;
enum { M_FF1A, M_FF1B, M_QKV, M_KV, M_WO, M_PW1, M_PW2, M_FF2A, M_FF2B, M_X, M_COUNT };
enum { BAR_K = 1, BAR_V, BAR_Q, BAR_MERGE, BAR_G, BAR_C, BAR_WG1, BAR_RDY, BAR_ST, BAR_ATT, BAR_INIT, BAR_RDY1, BAR_X, BAR_RES };

struct Params {
  CUtensorMap map[M_COUNT];
  const __nv_bfloat16 *w_ff1b, *w_qkv, *w_o, *w_pw1, *w_pw2, *w_ff2a, *w_ff2b;
};

constexpr int X_RS = 0, X_AG1 = X_RS, X_HALO = X_RS + 512, X_CLEAR = 1024, X_AG0 = 1536, X_ST = 2048, X_SIZE = 4096;
constexpr uint32_t HALO_TAG = 0xFFFF0001u;
struct Scratch {
  uint4 x[NCTA][X_SIZE];
  uint4 kv[8][2][16][512];
  uint4 cs[576];
  uint32_t flag[8][32][32];
  uint32_t ready[NCTA][32];
  uint32_t epoch[NCTA];
};
constexpr size_t X_ALIGN = 4 * X_SIZE * sizeof(uint4);
__device__ uint8_t g_scratch[sizeof(Scratch) + X_ALIGN];
#define PROF_TIME(i)
#define PROF_MARK(i)

__device__ __forceinline__ void mbar_init(uint32_t bar, uint32_t cnt) {
  asm volatile("mbarrier.init.shared::cta.b64 [%0], %1;" :: "r"(bar), "r"(cnt) : "memory");
}
__device__ __forceinline__ void mbar_wait(uint32_t bar, uint32_t parity) {
  asm volatile("{\n.reg .pred p;\n.reg .u32 c;\nmov.u32 c, 0;\n"
               "WAIT_LOOP:\nmbarrier.try_wait.parity.shared::cta.b64 p, [%0], %1;\n@p bra WAIT_DONE;\n"
               "add.u32 c, c, 1;\nsetp.lt.u32 p, c, %2;\n@p bra WAIT_LOOP;\nWAIT_DONE:\n}"
               :: "r"(bar), "r"(parity), "n"(SPIN_LIMIT) : "memory");
}
__device__ __forceinline__ void mbar_arrive(uint32_t bar) {
  asm volatile("mbarrier.arrive.shared::cta.b64 _, [%0];" :: "r"(bar) : "memory");
}
#define bar_sync(id, n) asm volatile("bar.sync %0, %1;" :: "n"((int)(id)), "n"(n) : "memory")
#define bar_arrive(id, n) asm volatile("bar.arrive %0, %1;" :: "n"((int)(id)), "n"(n) : "memory")
__device__ __forceinline__ void fence_async_smem() { asm volatile("fence.proxy.async.shared::cta;" ::: "memory"); }

__device__ __forceinline__ void st_vec(uint4* p, uint32_t a, uint32_t b, uint32_t c, uint32_t d) {
  asm volatile("{\n.reg .b128 v;\n.reg .b64 lo, hi;\nmov.b64 lo, {%1, %2};\nmov.b64 hi, {%3, %4};\nmov.b128 v, {lo, hi};\n"
               "st.relaxed.gpu.global.b128 [%0], v;\n}" :: "l"(p), "r"(a), "r"(b), "r"(c), "r"(d) : "memory");
}
__device__ __forceinline__ void ld_vec(const uint4* p, uint32_t& a, uint32_t& b, uint32_t& c, uint32_t& d) {
  asm volatile("{\n.reg .b128 v;\n.reg .b64 lo, hi;\nld.relaxed.gpu.global.b128 v, [%4];\nmov.b128 {lo, hi}, v;\n"
               "mov.b64 {%0, %1}, lo;\nmov.b64 {%2, %3}, hi;\n}" : "=r"(a), "=r"(b), "=r"(c), "=r"(d) : "l"(p) : "memory");
}
__device__ __forceinline__ void sts128(uint32_t a, uint32_t x, uint32_t y, uint32_t z, uint32_t w) {
  asm volatile("st.shared.v4.u32 [%0], {%1, %2, %3, %4};" :: "r"(a), "r"(x), "r"(y), "r"(z), "r"(w) : "memory");
}
__device__ __forceinline__ void lds128(uint32_t a, uint32_t& x, uint32_t& y, uint32_t& z, uint32_t& w) {
  asm volatile("ld.shared.v4.u32 {%0, %1, %2, %3}, [%4];" : "=r"(x), "=r"(y), "=r"(z), "=r"(w) : "r"(a) : "memory");
}
__device__ __forceinline__ uint32_t lds32(uint32_t a) {
  uint32_t x; asm volatile("ld.shared.u32 %0, [%1];" : "=r"(x) : "r"(a) : "memory"); return x;
}
__device__ __forceinline__ void sts32(uint32_t a, uint32_t x) { asm volatile("st.shared.u32 [%0], %1;" :: "r"(a), "r"(x) : "memory"); }
__device__ __forceinline__ void sts64(uint32_t a, uint32_t x, uint32_t y) {
  asm volatile("st.shared.v2.u32 [%0], {%1, %2};" :: "r"(a), "r"(x), "r"(y) : "memory");
}
__device__ __forceinline__ void stsm4(uint32_t a, const uint32_t* r) {
  asm volatile("stmatrix.sync.aligned.m8n8.x4.shared.b16 [%0], {%1, %2, %3, %4};" :: "r"(a), "r"(r[0]), "r"(r[1]), "r"(r[2]), "r"(r[3]) : "memory");
}
__device__ __forceinline__ void ldsm4(uint32_t a, uint32_t* r) {
  asm volatile("ldmatrix.sync.aligned.m8n8.x4.shared.b16 {%0, %1, %2, %3}, [%4];" : "=r"(r[0]), "=r"(r[1]), "=r"(r[2]), "=r"(r[3]) : "r"(a) : "memory");
}
__device__ __forceinline__ uint32_t pack2(float lo, float hi) {
  uint32_t r; asm("cvt.rn.bf16x2.f32 %0, %1, %2;" : "=r"(r) : "f"(hi), "f"(lo)); return r;
}
__device__ __forceinline__ float bf_lo(uint32_t w) { return __uint_as_float(w << 16); }
__device__ __forceinline__ float bf_hi(uint32_t w) { return __uint_as_float(w & 0xffff0000u); }
__device__ __forceinline__ float tanh_hw(float x) { float y; asm volatile("tanh.approx.f32 %0, %1;" : "=f"(y) : "f"(x)); return y; }
__device__ __forceinline__ float rcp_hw(float x) { float y; asm("rcp.approx.ftz.f32 %0, %1;" : "=f"(y) : "f"(x)); return y; }
__device__ __forceinline__ float ex2_hw(float x) { float y; asm("ex2.approx.ftz.f32 %0, %1;" : "=f"(y) : "f"(x)); return y; }

__device__ __forceinline__ uint32_t here(uint32_t v) { asm volatile("" : "+r"(v)); return v; }

#define SCHED() asm volatile("pmevent 1;" ::: "memory")
#define WG_FENCE() asm volatile("wgmma.fence.sync.aligned;" ::: "memory")
#define WG_COMMIT() asm volatile("wgmma.commit_group.sync.aligned;" ::: "memory")
#define WG_WAIT(n) asm volatile("wgmma.wait_group.sync.aligned %0;" :: "n"(n) : "memory")

template <int N> __device__ __forceinline__ void pin(float (&d)[N]) {
#pragma unroll
  for (int i = 0; i < N; i++) asm volatile("" : "+f"(d[i]) :: "memory");
}
template <int N> __device__ __forceinline__ void pin(uint32_t (&d)[N]) {
#pragma unroll
  for (int i = 0; i < N; i++) asm volatile("" : "+r"(d[i]) :: "memory");
}

#define WG_D32 "{%0, %1, %2, %3, %4, %5, %6, %7, %8, %9, %10, %11, %12, %13, %14, %15, %16, %17, %18, %19, %20, %21, %22, %23, %24, %25, %26, %27, %28, %29, %30, %31}"
template <int TB> __device__ __forceinline__ void wgmma64_acc(float (&d)[32], const uint32_t* a, uint64_t db) {
  asm volatile("wgmma.mma_async.sync.aligned.m64n64k16.f32.bf16.bf16 " WG_D32 ", {%32, %33, %34, %35}, %36, 1, 1, 1, %37;"
    : "+f"(d[0]), "+f"(d[1]), "+f"(d[2]), "+f"(d[3]), "+f"(d[4]), "+f"(d[5]), "+f"(d[6]), "+f"(d[7]),
      "+f"(d[8]), "+f"(d[9]), "+f"(d[10]), "+f"(d[11]), "+f"(d[12]), "+f"(d[13]), "+f"(d[14]), "+f"(d[15]),
      "+f"(d[16]), "+f"(d[17]), "+f"(d[18]), "+f"(d[19]), "+f"(d[20]), "+f"(d[21]), "+f"(d[22]), "+f"(d[23]),
      "+f"(d[24]), "+f"(d[25]), "+f"(d[26]), "+f"(d[27]), "+f"(d[28]), "+f"(d[29]), "+f"(d[30]), "+f"(d[31])
    : "r"(a[0]), "r"(a[1]), "r"(a[2]), "r"(a[3]), "l"(db), "n"(TB));
}
__device__ __forceinline__ void wgmma64_reuse(float (&d)[32], const uint32_t* a, uint64_t db, uint32_t zero) {
  asm volatile("{\n.reg .pred p;\nsetp.ne.u32 p, %37, 0;\nwgmma.mma_async.sync.aligned.m64n64k16.f32.bf16.bf16 " WG_D32 ", {%32, %33, %34, %35}, %36, p, 1, 1, 1;\n}"
    : "+f"(d[0]), "+f"(d[1]), "+f"(d[2]), "+f"(d[3]), "+f"(d[4]), "+f"(d[5]), "+f"(d[6]), "+f"(d[7]),
      "+f"(d[8]), "+f"(d[9]), "+f"(d[10]), "+f"(d[11]), "+f"(d[12]), "+f"(d[13]), "+f"(d[14]), "+f"(d[15]),
      "+f"(d[16]), "+f"(d[17]), "+f"(d[18]), "+f"(d[19]), "+f"(d[20]), "+f"(d[21]), "+f"(d[22]), "+f"(d[23]),
      "+f"(d[24]), "+f"(d[25]), "+f"(d[26]), "+f"(d[27]), "+f"(d[28]), "+f"(d[29]), "+f"(d[30]), "+f"(d[31])
    : "r"(a[0]), "r"(a[1]), "r"(a[2]), "r"(a[3]), "l"(db), "r"(zero));
}
template <int TB> __device__ __forceinline__ void wgmma64_set(float (&d)[32], const uint32_t* a, uint64_t db) {
  asm volatile("wgmma.mma_async.sync.aligned.m64n64k16.f32.bf16.bf16 " WG_D32 ", {%32, %33, %34, %35}, %36, 0, 1, 1, %37;"
    : "=f"(d[0]), "=f"(d[1]), "=f"(d[2]), "=f"(d[3]), "=f"(d[4]), "=f"(d[5]), "=f"(d[6]), "=f"(d[7]),
      "=f"(d[8]), "=f"(d[9]), "=f"(d[10]), "=f"(d[11]), "=f"(d[12]), "=f"(d[13]), "=f"(d[14]), "=f"(d[15]),
      "=f"(d[16]), "=f"(d[17]), "=f"(d[18]), "=f"(d[19]), "=f"(d[20]), "=f"(d[21]), "=f"(d[22]), "=f"(d[23]),
      "=f"(d[24]), "=f"(d[25]), "=f"(d[26]), "=f"(d[27]), "=f"(d[28]), "=f"(d[29]), "=f"(d[30]), "=f"(d[31])
    : "r"(a[0]), "r"(a[1]), "r"(a[2]), "r"(a[3]), "l"(db), "n"(TB));
}

__device__ __forceinline__ void wgmma72_acc(float (&d)[36], const uint32_t* a, uint64_t db) {
  asm volatile("wgmma.mma_async.sync.aligned.m64n72k16.f32.bf16.bf16 {%0, %1, %2, %3, %4, %5, %6, %7, %8, %9, %10, %11, %12, %13, %14, %15, %16, %17, %18, %19, %20, %21, %22, %23, %24, %25, %26, %27, %28, %29, %30, %31, %32, %33, %34, %35}, {%36, %37, %38, %39}, %40, 1, 1, 1, 1;"
    : "+f"(d[0]), "+f"(d[1]), "+f"(d[2]), "+f"(d[3]), "+f"(d[4]), "+f"(d[5]), "+f"(d[6]), "+f"(d[7]), "+f"(d[8]),
      "+f"(d[9]), "+f"(d[10]), "+f"(d[11]), "+f"(d[12]), "+f"(d[13]), "+f"(d[14]), "+f"(d[15]), "+f"(d[16]), "+f"(d[17]),
      "+f"(d[18]), "+f"(d[19]), "+f"(d[20]), "+f"(d[21]), "+f"(d[22]), "+f"(d[23]), "+f"(d[24]), "+f"(d[25]), "+f"(d[26]),
      "+f"(d[27]), "+f"(d[28]), "+f"(d[29]), "+f"(d[30]), "+f"(d[31]), "+f"(d[32]), "+f"(d[33]), "+f"(d[34]), "+f"(d[35])
    : "r"(a[0]), "r"(a[1]), "r"(a[2]), "r"(a[3]), "l"(db));
}
__device__ __forceinline__ void wgmma16_acc(float* d, const uint32_t* a, uint64_t db) {
  asm volatile("wgmma.mma_async.sync.aligned.m64n16k16.f32.bf16.bf16 {%0, %1, %2, %3, %4, %5, %6, %7}, {%8, %9, %10, %11}, %12, 1, 1, 1, 0;"
    : "+f"(d[0]), "+f"(d[1]), "+f"(d[2]), "+f"(d[3]), "+f"(d[4]), "+f"(d[5]), "+f"(d[6]), "+f"(d[7])
    : "r"(a[0]), "r"(a[1]), "r"(a[2]), "r"(a[3]), "l"(db));
}
__device__ __forceinline__ void hmma(float (&d)[4], const uint32_t* a, uint32_t b0, uint32_t b1) {
  asm("mma.sync.aligned.m16n8k16.row.col.f32.bf16.bf16.f32 {%0, %1, %2, %3}, {%4, %5, %6, %7}, {%8, %9}, {%0, %1, %2, %3};"
    : "+f"(d[0]), "+f"(d[1]), "+f"(d[2]), "+f"(d[3]) : "r"(a[0]), "r"(a[1]), "r"(a[2]), "r"(a[3]), "r"(b0), "r"(b1));
}

__device__ __forceinline__ void hmma8(float (&d)[4], const uint32_t* a, uint32_t b0) {
  asm("mma.sync.aligned.m16n8k8.row.col.f32.bf16.bf16.f32 {%0, %1, %2, %3}, {%4, %5}, {%6}, {%0, %1, %2, %3};"
    : "+f"(d[0]), "+f"(d[1]), "+f"(d[2]), "+f"(d[3]) : "r"(a[0]), "r"(a[1]), "r"(b0));
}

template <bool FIRST> __device__ __forceinline__ void mma_tile(float (&d)[32], const uint32_t (&a)[16], uint64_t db) {
  WG_FENCE();
#pragma unroll
  for (int s = 0; s < 4; s++) {
    if (FIRST && s == 0) wgmma64_set<1>(d, &a[0], db); else wgmma64_acc<1>(d, &a[4 * s], db + s * 128);
  }
  WG_COMMIT();
}
__device__ __forceinline__ void mma_tile_reuse(float (&d)[32], const uint32_t (&a)[16], uint64_t db) {
  WG_FENCE();
  wgmma64_reuse(d, &a[0], db, blockIdx.y);
#pragma unroll
  for (int s = 1; s < 4; s++) wgmma64_acc<1>(d, &a[4 * s], db + s * 128);
  WG_COMMIT();
}
template <int ROW> __device__ __forceinline__ void mma_tile_fold(float (&d)[32], const uint32_t (&a)[16], uint64_t db, const uint32_t (&mu)[4]) {
  WG_FENCE();
#pragma unroll
  for (int s = 0; s < 4; s++) wgmma64_acc<1>(d, &a[4 * s], db + s * 128);
  wgmma64_acc<1>(d, mu, (uint64_t)((SM_BASE + SM_CS + ROW * 128) >> 4) | (uint64_t(1) << 16) | (uint64_t(1) << 62));
  WG_COMMIT();
}
__device__ __forceinline__ void mma_add_half(float (&d)[32], const uint32_t (&a)[16]) {
  const uint64_t db = (uint64_t)((SM_BASE + SM_EYE) >> 4) | (uint64_t(8) << 16) | (uint64_t(8) << 32);
  WG_FENCE();
#pragma unroll
  for (int s = 0; s < 4; s++) wgmma16_acc(&d[8 * s], &a[4 * s], db);
  WG_COMMIT();
}
#define ACQUIRE(f) mbar_wait(SM_BASE + SM_FULL + ((f) % NSTAGE) * 8, ((f) / NSTAGE) & 1)
template <int F, int N> __device__ __forceinline__ uint32_t probe_n() {
  static_assert(F % NSTAGE + N <= NSTAGE, "stages must not wrap");
  uint32_t ok = 1;
#pragma unroll
  for (int i = 0; i < N; i++)
    asm volatile("{\n.reg .pred p;\nmbarrier.test_wait.parity.shared::cta.b64 p, [%1], %2;\nselp.u32 %0, %0, 0, p;\n}"
                 : "+r"(ok) : "r"(SM_BASE + SM_FULL + (F % NSTAGE + i) * 8), "r"((F / NSTAGE) & 1) : "memory");
  return ok;
}
template <int F, int N> __device__ __forceinline__ void settle_n(uint32_t ok) {
  if (__builtin_expect(!ok, 0)) {
#pragma unroll 1
    for (int i = 0; i < N; i++) mbar_wait(SM_BASE + SM_FULL + (F % NSTAGE + i) * 8, (F / NSTAGE) & 1);
  }
}
template <int F, int N> __device__ __forceinline__ void acquire_n() { settle_n<F, N>(probe_n<F, N>()); }
#define RELEASE(f0, f1) do { if (lane == 0) { _Pragma("unroll") for (int f_ = (f0); f_ <= (f1); f_++) mbar_arrive(SM_BASE + SM_EMPTY + (f_ % NSTAGE) * 8); } } while (0)
constexpr uint64_t RING = (uint64_t)(SM_BASE >> 4) | (uint64_t(1) << 16) | (uint64_t(64) << 32) | (uint64_t(1) << 62);
#define LO(f) (RING + ((f) % NSTAGE) * 1024)
#define HI(f) (RING + ((f) % NSTAGE) * 1024 + 512)

template <int C> __device__ __forceinline__ uint4* peer(uint4* p) {
  asm volatile("" : "+l"(p));
  return (uint4*)((uintptr_t)p ^ (C * X_SIZE * sizeof(uint4)));
}
__device__ __forceinline__ uint32_t clock_now() { uint32_t c; asm volatile("mov.u32 %0, %%clock;" : "=r"(c) :: "memory"); return c; }
__device__ __forceinline__ void publish(uint4* dst, uint32_t (&a)[16], uint32_t tag) {
#pragma unroll
  for (int s = 0; s < 4; s++) a[4 * s] = (a[4 * s] & ~1u) | tag;
  pin(a);
  SCHED();
#pragma unroll
  for (int s = 0; s < 4; s++) st_vec(dst + s * 128, a[4 * s], a[4 * s + 1], a[4 * s + 2], a[4 * s + 3]);
  SCHED();
}
__device__ __forceinline__ void fetch(const uint4* src, uint32_t (&a)[16]) {
#pragma unroll
  for (int s = 0; s < 4; s++) ld_vec(src + s * 128, a[4 * s], a[4 * s + 1], a[4 * s + 2], a[4 * s + 3]);
}
__device__ __forceinline__ uint32_t miss(const uint32_t (&a)[16], uint32_t tag) {
  return (a[0] ^ tag) | (a[4] ^ tag) | (a[8] ^ tag) | (a[12] ^ tag);
}
__device__ __forceinline__ bool stale(uint32_t v) { return __any_sync(0xffffffffu, here(v) & 1u); }
__device__ __forceinline__ void confirm(const uint4* src, uint32_t (&a)[16], uint32_t tag) {
  uint32_t spin = 0;
  while (__builtin_expect(stale(miss(a, tag)), 0) && ++spin < SPIN_LIMIT) fetch(src, a);
}
constexpr uint32_t GATHER_DELAY = 400;
template <int C0, int C1, int SLOT> __device__ __forceinline__ void gather_wait(uint32_t (&A)[4][16], uint4* xp, uint32_t tag) {
  uint32_t spin = 0;
  while (__builtin_expect(stale(miss(A[C0], tag) | miss(A[C1], tag)), 0) && ++spin < SPIN_LIMIT) {
    fetch(peer<C0>(xp) + SLOT, A[C0]);
    if (C1 != C0) fetch(peer<C1>(xp) + SLOT, A[C1]);
  }
}
template <int C, int SLOT> __device__ __forceinline__ void gather_first(uint32_t (&A)[4][16], uint4* xp, uint32_t tag, uint32_t sent) {
  while (clock_now() - sent < GATHER_DELAY) {}
  fetch(peer<1>(xp) + SLOT, A[1]); fetch(peer<2>(xp) + SLOT, A[2]); fetch(peer<3>(xp) + SLOT, A[3]);
  gather_wait<1, C, SLOT>(A, xp, tag);
}
template <int C, int SLOT> __device__ __forceinline__ void gather_rest(uint32_t (&A)[4][16], uint4* xp, uint32_t tag) {
  SCHED();
  gather_wait<C + 1, 3, SLOT>(A, xp, tag);
}
__device__ __forceinline__ void pack_acc(const float (&d)[32], uint32_t (&a)[16]) {
#pragma unroll
  for (int i = 0; i < 16; i++) a[i] = pack2(d[2 * i], d[2 * i + 1]);
}
__device__ __forceinline__ void res_store(uint32_t slot, const uint32_t (&a)[16]) {
#pragma unroll
  for (int s = 0; s < 4; s++) sts128(slot + s * 512, a[4 * s], a[4 * s + 1], a[4 * s + 2], a[4 * s + 3]);
}
__device__ __forceinline__ void res_load(uint32_t slot, float (&d)[32]) {
  uint32_t a[16];
#pragma unroll
  for (int s = 0; s < 4; s++) lds128(slot + s * 512, a[4 * s], a[4 * s + 1], a[4 * s + 2], a[4 * s + 3]);
#pragma unroll
  for (int i = 0; i < 16; i++) { d[2 * i] = bf_lo(a[i]); d[2 * i + 1] = bf_hi(a[i]); }
  pin(d);
}
__device__ __forceinline__ void tile_store(uint32_t maddr, const uint32_t (&a)[16]) {
#pragma unroll
  for (int s = 0; s < 4; s++) stsm4(maddr ^ (s << 5), &a[4 * s]);
}
__device__ __forceinline__ void tile_load(uint32_t maddr, uint32_t (&a)[16]) {
#pragma unroll
  for (int s = 0; s < 4; s++) ldsm4(maddr ^ (s << 5), &a[4 * s]);
}

struct RowAcc { float s[4], u[2][4], v[2][4]; };
__device__ __forceinline__ void row_acc(RowAcc& t, const uint32_t (&a)[16]) {
#pragma unroll
  for (int s = 0; s < 8; s++) {
    if ((s & 1) == 0) hmma(t.s, &a[2 * s], 0x3F803F80u, 0x3F803F80u);
    hmma8(t.u[s & 1], &a[2 * s], a[2 * s]);
    hmma8(t.v[s & 1], &a[2 * s], a[2 * s + 1]);
  }
}
__device__ __forceinline__ float2 row_squares(const RowAcc& t, bool odd) {
  return make_float2(odd ? t.u[0][1] + t.u[1][1] : t.u[0][0] + t.u[1][0], odd ? t.v[0][3] + t.v[1][3] : t.v[0][2] + t.v[1][2]);
}
__device__ __forceinline__ void stat_publish(const uint32_t (&a)[16], Scratch* sc, uint32_t th, uint32_t tag) {
  RowAcc t = {};
  row_acc(t, a);
  const float2 q = row_squares(t, th & 4);
  if ((th & 3) == ((th >> 3) & 3))
    st_vec(&sc->x[blockIdx.x][X_ST + (th >> 2)], (__float_as_uint(t.s[0]) & ~1u) | tag, __float_as_uint(q.x), __float_as_uint(t.s[2]), __float_as_uint(q.y));
}
struct RowNorm { float m0, rs0, m1, rs1; };
__device__ __forceinline__ RowNorm row_norm(float s0, float q0, float s1, float q1, float scale) {
  RowNorm n;
  n.m0 = s0 * (1.f / DM); n.m1 = s1 * (1.f / DM);
  n.rs0 = scale * rsqrtf(fmaxf(fmaf(-n.m0, n.m0, q0 * (1.f / DM)), 0.f) + LN_EPS);
  n.rs1 = scale * rsqrtf(fmaxf(fmaf(-n.m1, n.m1, q1 * (1.f / DM)), 0.f) + LN_EPS);
  return n;
}
__device__ __forceinline__ RowNorm stat_gather(Scratch* sc, uint32_t th, uint32_t tag, float scale) {
  const uint4* src = &sc->x[blockIdx.x & ~3u][X_ST + (th >> 2)];
  uint32_t v[16], spin = 0;
  do {
#pragma unroll
    for (int j = 0; j < 4; j++) ld_vec(src + j * X_SIZE, v[4 * j], v[4 * j + 1], v[4 * j + 2], v[4 * j + 3]);
  } while (stale(miss(v, tag)) && ++spin < SPIN_LIMIT);
  float f[4];
#pragma unroll
  for (int i = 0; i < 4; i++)
    f[i] = (__uint_as_float(v[i]) + __uint_as_float(v[4 + i])) + (__uint_as_float(v[8 + i]) + __uint_as_float(v[12 + i]));
  return row_norm(f[0], f[1], f[2], f[3], scale);
}
constexpr uint32_t SM_NORM = SM_BASE + SM_STG + 2 * TILE_BYTES + 4096;
__device__ __forceinline__ void norm_produce(const RowNorm& n, uint32_t th, uint32_t qsel) {
  const bool sel = (th & 3) == qsel;
  const float a = sel ? -n.m0 : 0.f, c = sel ? -n.m1 : 0.f;
  const uint32_t ah = pack2(a, a), ch = pack2(c, c);
  const float al = a - bf_lo(ah), cl = c - bf_lo(ch);
  sts128(SM_NORM + th * 16, ah, ch, pack2(al, al), pack2(cl, cl));
  sts64(SM_NORM + 2048 + th * 8, __float_as_uint(n.rs0), __float_as_uint(n.rs1));
  bar_arrive(BAR_ST, 256);
}
__device__ __forceinline__ void norm_duty(Scratch* sc, uint32_t th, uint32_t tag, float scale, uint32_t qsel) {
  bar_sync(BAR_RES, 256);
  norm_produce(stat_gather(sc, th, tag, scale), th, qsel);
}
__device__ __forceinline__ void norm_consume(uint32_t th, uint32_t (&mu)[4], float& rs0, float& rs1) {
  bar_sync(BAR_ST, 256);
  lds128(SM_NORM + th * 16, mu[0], mu[1], mu[2], mu[3]);
  asm volatile("ld.shared.v2.f32 {%0, %1}, [%2];" : "=f"(rs0), "=f"(rs1) : "r"(SM_NORM + 2048 + th * 8) : "memory");
}
__device__ __forceinline__ void scale_pack(const float (&d)[32], uint32_t (&a)[16], float rs0, float rs1) {
#pragma unroll
  for (int i = 0; i < 16; i++) { const float rs = (i & 1) ? rs1 : rs0; a[i] = pack2(d[2 * i] * rs, d[2 * i + 1] * rs); }
}
template <int S> __device__ __forceinline__ void silu_seg(float (&acc)[4][32], float (&tn)[2][4], uint32_t (&H)[4][16], float rs0, float rs1) {
  if (S >= 2) {
    const float* h = &acc[(S - 2) >> 3][4 * ((S - 2) & 7)];
    const float* v = tn[S & 1];
    uint32_t* o = &H[(S - 2) >> 3][2 * ((S - 2) & 7)];
    o[0] = pack2(fmaf(h[0], v[0], h[0]), fmaf(h[1], v[1], h[1]));
    o[1] = pack2(fmaf(h[2], v[2], h[2]), fmaf(h[3], v[3], h[3]));
    asm volatile("" : "+r"(o[0]), "+r"(o[1]));
  }
  if (S >= 1 && S <= 32) {
#pragma unroll
    for (int k = 0; k < 4; k++) tn[(S - 1) & 1][k] = tanh_hw(acc[((S - 1) >> 3) & 3][4 * ((S - 1) & 7) + k]);
  }
  if (S < 32) {
    float* h = &acc[(S >> 3) & 3][4 * (S & 7)];
    h[0] *= rs0; h[1] *= rs0; h[2] *= rs1; h[3] *= rs1;
    asm volatile("" : "+f"(h[0]), "+f"(h[1]), "+f"(h[2]), "+f"(h[3]));
  }
  SCHED();
}
template <int S0, int S1> __device__ __forceinline__ void silu_segs(float (&acc)[4][32], float (&tn)[2][4], uint32_t (&H)[4][16], float rs0, float rs1) {
  silu_seg<S0>(acc, tn, H, rs0, rs1);
  if constexpr (S0 + 1 < S1) silu_segs<S0 + 1, S1>(acc, tn, H, rs0, rs1);
}
template <int HALF> __device__ __forceinline__ void send_half(uint4* dst, const float (&d)[32], uint32_t tag) {
  uint32_t o[8];
#pragma unroll
  for (int i = 0; i < 8; i++) o[i] = pack2(d[16 * HALF + 2 * i], d[16 * HALF + 2 * i + 1]);
  o[0] = (o[0] & ~1u) | tag; o[4] = (o[4] & ~1u) | tag;
  pin(o);
  SCHED();
  st_vec(dst + HALF * 256, o[0], o[1], o[2], o[3]);
  st_vec(dst + HALF * 256 + 128, o[4], o[5], o[6], o[7]);
  SCHED();
}
__device__ __forceinline__ uint32_t send_residual(uint32_t (&a)[16], Scratch* sc, uint4* xp, uint32_t res, uint32_t tag) {
  const uint32_t exact[4] = {a[0], a[4], a[8], a[12]};
  publish(xp + X_AG0, a, tag);
  const uint32_t sent = clock_now();
  stat_publish(a, sc, threadIdx.x, tag);
  res_store(res, a);
#pragma unroll
  for (int s = 0; s < 4; s++) sts32(res + s * 512, exact[s]);
  bar_arrive(BAR_RES, 256);
  return sent;
}
template <int F, int N> __device__ __forceinline__ uint32_t proj_residual(uint32_t (&A)[4][16], Scratch* sc, uint4* xp, uint32_t res, uint32_t tag) {
  float acc[32];
  publish(xp + X_AG1, A[0], tag);
  const uint32_t sent = clock_now();
  acquire_n<F, N>();
  if (F == F_PW2) acquire_n<0, 5>();
  res_load(res, acc);
  mma_tile<false>(acc, A[0], LO(F));
  gather_first<2, X_AG1>(A, xp, tag, sent);
  mma_tile<false>(acc, A[1], HI(F));
  mma_tile<false>(acc, A[2], LO(F + 1));
  gather_rest<2, X_AG1>(A, xp, tag);
  PROF_MARK(F == F_WO ? 11 : 16);
  mma_tile<false>(acc, A[3], HI(F + 1));
  WG_WAIT(0); pin(acc);
  pack_acc(acc, A[0]);
  return send_residual(A[0], sc, xp, res, tag);
}

__device__ __forceinline__ void qk_tile(float (&S)[32], const uint32_t (&Q)[16], uint64_t dk) {
#pragma unroll
  for (int s = 0; s < 4; s++) {
    if (s == 0) wgmma64_set<0>(S, &Q[0], dk); else wgmma64_acc<0>(S, &Q[4 * s], dk + s * 2);
  }
}
__device__ __forceinline__ void qk_shift(float (&S)[32], const uint32_t (&nm)[4]) { wgmma64_acc<0>(S, nm, (uint64_t)((SM_BASE + SM_ONE) >> 4)); }
constexpr uint64_t V_STEP = uint64_t(1) - (uint64_t(1) << 16);
constexpr uint64_t RING_V = RING - (uint64_t(1) << 16) + ((uint64_t)((SM_STG + 2 * TILE_BYTES) >> 4) << 16);
__device__ __forceinline__ void pv_tile(float (&O)[36], const uint32_t (&P)[16], uint64_t dv, uint64_t pad) {
#pragma unroll
  for (int s = 0; s < 4; s++) wgmma72_acc(O, &P[4 * s], dv + s * 128 * V_STEP + (s < 2 ? 0 : (s - 1) * pad));
}
__device__ __forceinline__ void attn_step(const float (&Sc)[32], float (&Sn)[32], uint32_t (&Pc)[16], uint32_t (&Pp)[16], float (&O)[36],
                                          const uint32_t (&Q)[16], const uint32_t (&nm)[4], uint64_t dk, uint64_t dv) {
  WG_FENCE();
  qk_tile(Sn, Q, dk);
  qk_shift(Sn, nm);
  pv_tile(O, Pp, dv, 0);
  WG_COMMIT();
  SCHED();
#pragma unroll
  for (int i = 0; i < 16; i++) Pc[i] = pack2(ex2_hw(Sc[2 * i]), ex2_hw(Sc[2 * i + 1]));
  pin(Pc);
  SCHED();
}
template <int R> __device__ __forceinline__ float tile_max(const float (&S)[32]) {
  float t[4];
#pragma unroll
  for (int j = 0; j < 4; j++) t[j] = fmaxf(fmaxf(S[8 * j + R], S[8 * j + R + 1]), fmaxf(S[8 * j + R + 4], S[8 * j + R + 5]));
  float n = fmaxf(fmaxf(t[0], t[1]), fmaxf(t[2], t[3]));
  n = fmaxf(n, __shfl_xor_sync(0xffffffffu, n, 1));
  return fmaxf(n, __shfl_xor_sync(0xffffffffu, n, 2));
}
__device__ __forceinline__ void attention_exact(float (&O)[36], const uint32_t (&Q)[16], const Scratch* sc, int bh, int lane) {
  const char* kb = (const char*)&sc->kv[bh][0][0][0];
  const char* vb = (const char*)&sc->kv[bh][1][0][0];
  const int g = lane >> 2, q = lane & 3;
  float m0 = -INFINITY, m1 = -INFINITY, l0 = 0.f, l1 = 0.f;
  float o[8][4] = {};
#pragma unroll 1
  for (int k0 = 0; k0 < T_SEQ; k0 += 8) {
    float s[4] = {0.f, 0.f, 0.f, 0.f};
#pragma unroll
    for (int c = 0; c < 8; c++) hmma8(s, &Q[2 * c], __ldcg((const uint32_t*)(kb + (k0 + g) * 128 + ((c ^ g) << 4) + q * 4)));
    float n0 = fmaxf(s[0], s[1]), n1 = fmaxf(s[2], s[3]);
    n0 = fmaxf(n0, __shfl_xor_sync(0xffffffffu, n0, 1)); n1 = fmaxf(n1, __shfl_xor_sync(0xffffffffu, n1, 1));
    n0 = fmaxf(m0, fmaxf(n0, __shfl_xor_sync(0xffffffffu, n0, 2))); n1 = fmaxf(m1, fmaxf(n1, __shfl_xor_sync(0xffffffffu, n1, 2)));
    const float a0 = ex2_hw(m0 - n0), a1 = ex2_hw(m1 - n1);
    m0 = n0; m1 = n1;
    const uint32_t pp[2] = {pack2(ex2_hw(s[0] - n0), ex2_hw(s[1] - n0)), pack2(ex2_hw(s[2] - n1), ex2_hw(s[3] - n1))};
    l0 = fmaf(l0, a0, bf_lo(pp[0]) + bf_hi(pp[0])); l1 = fmaf(l1, a1, bf_lo(pp[1]) + bf_hi(pp[1]));
#pragma unroll
    for (int j = 0; j < 8; j++) {
      const uint32_t v0 = __ldcg((const uint16_t*)(vb + (k0 + 2 * q) * 128 + ((j ^ (2 * q)) << 4) + g * 2));
      const uint32_t v1 = __ldcg((const uint16_t*)(vb + (k0 + 2 * q + 1) * 128 + ((j ^ (2 * q + 1)) << 4) + g * 2));
      o[j][0] *= a0; o[j][1] *= a0; o[j][2] *= a1; o[j][3] *= a1;
      hmma8(o[j], pp, v0 | (v1 << 16));
    }
  }
  l0 += __shfl_xor_sync(0xffffffffu, l0, 1); l1 += __shfl_xor_sync(0xffffffffu, l1, 1);
  O[32] = l0 + __shfl_xor_sync(0xffffffffu, l0, 2); O[34] = l1 + __shfl_xor_sync(0xffffffffu, l1, 2);
#pragma unroll
  for (int i = 0; i < 32; i++) O[i] = o[i >> 2][i & 3];
}

__device__ __forceinline__ uint32_t fill_entry(int f, int r, int bh) {
  int m, x = r, y, dx = 0;
  if (f < F_QKV || f >= 48) {
    const int i = f & 15;
    m = f < F_QKV ? M_FF1A : M_FF2A;
    if (i < 8) { x = 4 * r + ((0xE2u >> i) & 1) * 2; y = r ^ ((0xE790u >> (2 * i)) & 3); dx = 1; }
    else { m++; x = r ^ (((i >> 1) - 3) & 3); y = 4 * r + 2 * (i & 1); }
  } else if (f < F_KV) {
    const int i = f - F_QKV;
    m = M_QKV;
    if (i == 1 || i >= 5) { y = r ^ (i == 1 ? 0 : 2); }
    else { x = 4 + r; y = r ^ (i ? i - 1 : 0); dx = 4; }
  } else if (f < F_WO) {
    const int i = f - F_KV;
    m = M_KV; x = 0; y = bh * 32 + (i & 2) * 8 + (i >> 2) * 4 + (i & 1) * 2;
  } else if (f >= F_PW1 && f < F_PW2) {
    m = M_PW1; y = r ^ (f - F_PW1); dx = 4;
  } else {
    m = f < F_PW1 ? M_WO : M_PW2; y = r ^ ((f & 1) * 2);
  }
  return m | (x << 4) | (y << 8) | (dx << 16);
}
__device__ __forceinline__ void tma_fill(uint32_t st, const CUtensorMap* map, uint32_t x, uint32_t y, uint32_t x2, uint32_t y2) {
  asm volatile("{\n.reg .pred p;\nelect.sync _|p, 0xffffffff;\n"
               "@p mbarrier.arrive.expect_tx.shared::cta.b64 _, [%1], 16384;\n"
               "@p cp.async.bulk.tensor.2d.shared::cluster.global.mbarrier::complete_tx::bytes [%0], [%2, {%3, %4}], [%1];\n"
               "@p cp.async.bulk.tensor.2d.shared::cluster.global.mbarrier::complete_tx::bytes [%0 + 8192], [%2, {%5, %6}], [%1];\n}"
               :: "r"(SM_BASE + st * STAGE_BYTES), "r"(SM_BASE + SM_FULL + st * 8), "l"(map), "r"(x), "r"(y), "r"(x2), "r"(y2) : "memory");
}
__device__ __forceinline__ void l2_prefetch(const void* p, uint32_t total, int b) {
  const uint32_t part = total / NCTA;
  asm volatile("cp.async.bulk.prefetch.L2.global [%0], %1;" :: "l"((const char*)p + (size_t)b * part), "r"(part) : "memory");
}

__global__ void __launch_bounds__(384, 1) conformer_kernel(Scratch* __restrict__ sc, __nv_bfloat16* __restrict__ out,
                                                           const __nv_bfloat16* __restrict__ dw, const __nv_bfloat16* __restrict__ xin,
                                                           const __nv_bfloat16* __restrict__ w_ff1a, const __grid_constant__ Params p) {
  extern __shared__ __align__(1024) uint8_t smem[];
  const int tid = threadIdx.x, lane = tid & 31;
  if (tid == 0) {
    l2_prefetch(xin, 2 * T_SEQ * DM * 2, blockIdx.x);
    l2_prefetch(w_ff1a, 256 * 1024 * 2, blockIdx.x);
  }
  const int cw = __shfl_sync(0xffffffffu, tid >> 5, 0), wg = cw >> 2, w = cw & 3;
  const int b = blockIdx.x, r = b & 3, batch = b >> 6, t = (b >> 2) & 15;
  if ((uint32_t)__cvta_generic_to_shared(smem) != SM_BASE) return;
  PROF_MARK(0);
  PROF_TIME(30);

  if (wg == 2) {
    asm volatile("setmaxnreg.dec.sync.aligned.u32 40;");
    if (cw == 8) {
      if (lane == 0) {
        asm volatile("prefetch.tensormap [%0];" :: "l"(&p.map[M_X]) : "memory");
        asm volatile("prefetch.tensormap [%0];" :: "l"(&p.map[M_FF1A]) : "memory");
        mbar_init(SM_BASE + SM_XBAR, 1);
#pragma unroll
        for (int i = 0; i < NSTAGE; i++) mbar_init(SM_BASE + SM_FULL + i * 8, 1);
        fence_async_smem();
      }
      __syncwarp();
      asm volatile("{\n.reg .pred p;\nelect.sync _|p, 0xffffffff;\n"
                   "@p mbarrier.arrive.expect_tx.shared::cta.b64 _, [%1], 32768;\n"
                   "@p cp.async.bulk.tensor.4d.shared::cluster.global.mbarrier::complete_tx::bytes [%0], [%2, {0, %3, 0, %4}], [%1];\n}"
                   :: "r"(SM_BASE + SM_STG), "r"(SM_BASE + SM_XBAR), "l"(&p.map[M_X]), "r"(t * 64), "r"(batch) : "memory");
      bar_arrive(0, 320);
      PROF_MARK(9);
#pragma unroll
      for (int f = 0; f < 8; f++) {
        const uint32_t x = 256 * r + ((0xE2u >> f) & 1) * 128, y = (r ^ ((0xE790u >> (2 * f)) & 3)) * 64;
        tma_fill(f, &p.map[M_FF1A], x, y, x + 64, y);
      }
      PROF_MARK(1);
      const uint32_t* flag = sc->flag[batch * 4 + r][lane];
      const uint32_t prev = ((volatile uint32_t*)sc->epoch)[b];
      uint32_t entry[2], ready = 0, st = 8, parity = 1;
#pragma unroll 1
      for (int i = 0; i < 2; i++) { entry[1] = fill_entry(i * 32 + lane, r, batch * 4 + r); if (i == 0) entry[0] = entry[1]; }
      bar_sync(BAR_INIT, 64);
#pragma unroll 1
      for (int f = 8; f < F_TOTAL; f++) {
        const uint32_t e = __shfl_sync(0xffffffffu, f < 32 ? entry[0] : entry[1], f);
        if ((e & 15) == M_KV) {
          const uint32_t need = 3u << ((e >> 8) & 31);
          uint32_t spin = 0;
#pragma unroll 1
          while ((ready & need) != need && ++spin < SPIN_LIMIT) {
            uint32_t v;
            asm volatile("ld.relaxed.gpu.global.u32 %0, [%1];" : "=r"(v) : "l"(flag) : "memory");
            ready = __ballot_sync(0xffffffffu, v - 1 == prev);
          }
        }
        if (f == F_KV) PROF_MARK(8);
        mbar_wait(SM_BASE + SM_EMPTY + st * 8, parity);
        const uint32_t x = (e << 2) & 0x3C0, y = (e >> 2) & 0x3FC0, dx = (e >> 16) << 6;
        tma_fill(st, &p.map[e & 15], x, y, x + dx, dx ? y : y ^ 64);
        if (++st == NSTAGE) { st = 0; parity ^= 1; }
      }
    } else if (here(cw) != 11) {
      const int kind = w - 1;
      const uint32_t prev = ((volatile uint32_t*)sc->epoch)[b];
      if (kind == 0) {
        if (lane == 0) {
#pragma unroll
          for (int i = 0; i < NSTAGE; i++) mbar_init(SM_BASE + SM_EMPTY + i * 8, 4);
        }
        __syncwarp();
        bar_arrive(0, 320);
        bar_arrive(BAR_INIT, 64);
        bar_sync(BAR_K, 160);
      } else {
        uint32_t v, spin = 0;
#pragma unroll 1
        do {
          asm volatile("ld.relaxed.gpu.global.u32 %0, [%1];" : "=r"(v) : "l"(sc->ready[(b & ~3) + (lane & 3)]) : "memory");
        } while (__any_sync(0xffffffffu, v - 1 != prev) && ++spin < SPIN_LIMIT);
        bar_arrive(BAR_RDY, 160);
        bar_arrive(BAR_RDY1, 160);
        bar_sync(BAR_V, 160);
      }
      if (lane == 0) {
        asm volatile("cp.async.bulk.global.shared::cta.bulk_group [%0], [%1], %2;"
                     :: "l"(&sc->kv[batch * 4 + r][kind][t][0]), "r"(SM_BASE + SM_STG + kind * TILE_BYTES), "r"(TILE_BYTES) : "memory");
        asm volatile("cp.async.bulk.commit_group;\ncp.async.bulk.wait_group 0;" ::: "memory");
        asm volatile("st.relaxed.gpu.global.u32 [%0], %1;" :: "l"(sc->flag[batch * 4 + r][kind * 16 + t]), "r"(prev + 1) : "memory");
      }
    } else {
      const uint32_t epoch = ((volatile uint32_t*)sc->epoch)[b] + 1;
      if (lane == 0 && epoch) {
        asm volatile("prefetch.tensormap [%0];" :: "l"(&p.map[M_FF1B]) : "memory");
        l2_prefetch(p.w_ff1b, 1024 * 256 * 2, b);
        l2_prefetch(p.w_qkv, 256 * 768 * 2, b);
        l2_prefetch(p.w_pw1, 256 * 512 * 2, b);
        l2_prefetch(p.w_ff2a, 256 * 1024 * 2, b);
      }
#pragma unroll 1
      for (int i = 0; i < 11; i++) {
        const uint32_t t0 = clock_now();
        uint4* dst = &sc->x[b][X_CLEAR + i * 96 + lane];
        st_vec(dst, 0u, 0u, 0u, 0u); st_vec(dst + 32, 0u, 0u, 0u, 0u); st_vec(dst + 64, 0u, 0u, 0u, 0u);
        while (clock_now() - t0 < 100) {}
      }
      asm volatile("fence.acq_rel.gpu;" ::: "memory");
      __syncwarp();
      if (lane == 0) {
        asm volatile("st.relaxed.gpu.global.u32 [%0], %1;" :: "l"(sc->ready[b]), "r"(epoch) : "memory");
        l2_prefetch(p.w_o, 256 * 256 * 2, b);
        l2_prefetch(p.w_pw2, 256 * 256 * 2, b);
        l2_prefetch(p.w_ff2b, 1024 * 256 * 2, b);
#pragma unroll
        for (int i = M_QKV; i < M_X; i++) asm volatile("prefetch.tensormap [%0];" :: "l"(&p.map[i]) : "memory");
      }
    }
  } else {
    asm volatile("setmaxnreg.inc.sync.aligned.u32 232;");
    if (tid < 144) sts128(SM_BASE + SM_CS + tid * 16, 0, 0, 0, 0);
    if (wg == 1) {
      const int i = tid - 128;
      sts32(SM_BASE + SM_EYE + i * 4, i >= 96 ? 0x3F803F80u : ((i & 32) == 0 && (i & 3) == ((i >> 3) & 3)) ? (0x3F00u << ((i & 4) * 4)) : 0u);
    }
    fence_async_smem();
    bar_sync(0, 320);
    const int q = lane & 3, th = tid & 127;
    constexpr uint32_t stg = SM_BASE + SM_STG;
    const uint32_t mrow = 16 * w + (lane & 15);
    const uint32_t maddr = stg + mrow * 128 + (((lane >> 4) ^ (lane & 7)) << 4);
    const uint32_t res = stg + 3 * TILE_BYTES + w * 2048 + lane * 16;
    uint4* const xp = &sc->x[b][th];
    const int nvalid = T_SEQ - t * 64, row0 = 16 * w + (lane >> 2);

    uint32_t A[4][16];
    uint32_t sent = 0;
    mbar_wait(SM_BASE + SM_XBAR, 0);
    if (wg == 1) bar_sync(BAR_X, 256);
    PROF_MARK(1);
#pragma unroll
    for (int c = 0; c < 4; c++) tile_load(maddr + (r ^ c) * TILE_BYTES, A[c]);
    if (wg == 0) {
      float sa[4][4] = {};
#pragma unroll
      for (int i = 0; i < 16; i++) hmma(sa[i & 3], &A[i >> 2][4 * (i & 3)], 0x3F803F80u, 0x3F803F80u);
      bar_arrive(BAR_X, 256);
      const float s0 = ((sa[0][0] + sa[1][0]) + (sa[2][0] + sa[3][0])) * (1.f / DM), s1 = ((sa[0][2] + sa[1][2]) + (sa[2][2] + sa[3][2])) * (1.f / DM);
      const uint32_t m0 = pack2(s0, s0), m1 = pack2(s1, s1);
#pragma unroll
      for (int c = 0; c < 4; c++) {
#pragma unroll
        for (int i = 0; i < 16; i++) asm("sub.rn.bf16x2 %0, %0, %1;" : "+r"(A[c][i]) : "r"((i & 1) ? m1 : m0));
        pin(A[c]);
      }
    } else {
      const uint32_t epoch = ((volatile uint32_t*)sc->epoch)[b] + 1, tag = epoch & 1;
      {
        RowAcc ra[2] = {};
#pragma unroll
        for (int c = 0; c < 4; c++) row_acc(ra[c & 1], A[c]);
        const float2 qa = row_squares(ra[0], lane & 4), qb = row_squares(ra[1], lane & 4);
        const int src = (lane & 28) | (lane >> 3);
        const float q0 = __shfl_sync(0xffffffffu, qa.x + qb.x, src), q1 = __shfl_sync(0xffffffffu, qa.y + qb.y, src);
        bar_sync(BAR_WG1, 128);
        res_store(res, A[0]);
        norm_produce(row_norm(ra[0].s[0] + ra[1].s[0], q0, ra[0].s[2] + ra[1].s[2], q1, 0.5f), th, 4);
      }
      PROF_MARK(5);
      SCHED();
      uint4 cv[8];
      if (b < 72) {
        const __nv_bfloat16* wp; int ld, col;
        if (b < 24) { wp = p.w_qkv; ld = 768; col = b * 32; }
        else if (b < 40) { wp = p.w_pw1; ld = 512; col = (b - 24) * 32; }
        else { wp = p.w_ff2a; ld = 1024; col = (b - 40) * 32; }
        const uint4* src = (const uint4*)(wp + (size_t)(th >> 2) * ld + col + q * 8);
#pragma unroll
        for (int i = 0; i < 8; i++) cv[i] = __ldg(src + i * 4 * ld);
      }
      if (b < 72) {
        float c[8] = {0.f, 0.f, 0.f, 0.f, 0.f, 0.f, 0.f, 0.f};
#pragma unroll
        for (int i = 0; i < 8; i++) {
          const uint4 v = cv[i];
          c[0] += bf_lo(v.x); c[1] += bf_hi(v.x); c[2] += bf_lo(v.y); c[3] += bf_hi(v.y);
          c[4] += bf_lo(v.z); c[5] += bf_hi(v.z); c[6] += bf_lo(v.w); c[7] += bf_hi(v.w);
        }
#pragma unroll 1
        for (int m = 4; m <= 16; m <<= 1)
#pragma unroll
          for (int k = 0; k < 8; k++) c[k] += __shfl_xor_sync(0xffffffffu, c[k], m);
        if (lane < 4) {
          const uint32_t a = SM_BASE + SM_CS + 1792 + w * 128 + lane * 32;
          sts128(a, __float_as_uint(c[0]), __float_as_uint(c[1]), __float_as_uint(c[2]), __float_as_uint(c[3]));
          sts128(a + 16, __float_as_uint(c[4]), __float_as_uint(c[5]), __float_as_uint(c[6]), __float_as_uint(c[7]));
        }
        bar_sync(BAR_WG1, 128);
        if (th < 8) {
          float o[4] = {0.f, 0.f, 0.f, 0.f};
#pragma unroll 1
          for (int k = 0; k < 4; k++) {
            uint32_t e[4];
            lds128(SM_BASE + SM_CS + 1792 + k * 128 + th * 16, e[0], e[1], e[2], e[3]);
#pragma unroll
            for (int i = 0; i < 4; i++) o[i] += __uint_as_float(e[i]);
          }
          st_vec(&sc->cs[b * 8 + th], (__float_as_uint(o[0]) & ~1u) | tag, __float_as_uint(o[1]), __float_as_uint(o[2]), __float_as_uint(o[3]));
        }
      }
      bar_sync(BAR_WG1, 128);
      PROF_MARK(2);
#pragma unroll 1
      for (int i = th; i < 144; i += 128) {
        const int j = i >> 4;
        int src;
        if (j < CS_PW1) src = 320 + 64 * r + i;
        else if (j < CS_QKV) src = 192 + (j - CS_PW1) * 64 + 16 * r + (i & 15);
        else src = ((j - CS_QKV + 1) % 3) * 64 + 16 * r + (i & 15);
        uint32_t e[4], spin = 0;
#pragma unroll 1
        do {
          ld_vec(&sc->cs[src], e[0], e[1], e[2], e[3]);
        } while (((e[0] ^ tag) & 1u) && ++spin < SPIN_LIMIT);
        const float c0 = __uint_as_float(e[0] & ~1u), c1 = __uint_as_float(e[1]), c2 = __uint_as_float(e[2]), c3 = __uint_as_float(e[3]);
        const uint32_t h0 = pack2(c0, c1), h1 = pack2(c2, c3);
        const uint32_t a = SM_BASE + SM_CS + j * 256 + (i & 15) * 8;
        sts64(a ^ ((a >> 3) & 0x70), h0, h1);
        sts64((a + 128) ^ (((a + 128) >> 3) & 0x70), pack2(c0 - bf_lo(h0), c1 - bf_hi(h0)), pack2(c2 - bf_lo(h1), c3 - bf_hi(h1)));
      }
      fence_async_smem();
      PROF_MARK(4);
      bar_sync(BAR_RDY1, 160);
      norm_duty(sc, th, 1, 1.f, 3);
    }

#pragma unroll 1
    for (uint32_t pass = 0; pass < 2; pass++) {
      uint32_t Q[16];
      if (wg == 0) {
        float acc[4][32];
        uint32_t H[4][16];
        if (!pass) { PROF_MARK(47); ACQUIRE(0); }
        mma_tile<true>(acc[0], A[0], LO(0)); mma_tile<true>(acc[1], A[0], HI(0));
        if (!pass) ACQUIRE(1);
        mma_tile<true>(acc[2], A[0], LO(1)); mma_tile<true>(acc[3], A[0], HI(1));
        if (pass) gather_first<1, X_AG0>(A, xp, 1, sent); else acquire_n<2, 3>();
        mma_tile<false>(acc[0], A[1], LO(2)); mma_tile<false>(acc[1], A[1], HI(2));
        if (pass) { gather_rest<1, X_AG0>(A, xp, 1); RELEASE(F_PW2, F_PW2 + 1); }
        PROF_MARK(2 + pass * 16);
        mma_tile<false>(acc[0], A[2], LO(3));
        WG_WAIT(3);
        uint32_t mu[4];
        float rs0, rs1, tn[2][4];
        norm_consume(here(th), mu, rs0, rs1);
        mma_tile_fold<2 * CS_FF2>(acc[0], A[3], LO(4), mu);
        RELEASE(0, 1);
        mma_tile<false>(acc[1], A[2], HI(3));
#define SEGS(a, b) silu_segs<a, b>(acc, tn, H, rs0, rs1)
        WG_WAIT(1); pin(acc[0]);
        SEGS(0, 1);
        mma_tile_fold<2 * CS_FF2 + 2>(acc[1], A[3], HI(4), mu);
        SEGS(1, 3);
        uint32_t ok = probe_n<5, 3>();
        SEGS(3, 4);
        settle_n<5, 3>(ok);
        mma_tile<false>(acc[2], A[1], LO(5));
        SEGS(4, 6);
        mma_tile<false>(acc[2], A[2], LO(6));
        SEGS(6, 8);
        WG_WAIT(2); pin(acc[1]);
        RELEASE(2, 4);
        SEGS(8, 9);
        mma_tile_fold<2 * CS_FF2 + 4>(acc[2], A[3], LO(7), mu);
        SEGS(9, 12);
        mma_tile<false>(acc[3], A[1], HI(5));
        SEGS(12, 14);
        mma_tile<false>(acc[3], A[2], HI(6));
        SEGS(14, 16);
        WG_WAIT(2); pin(acc[2]);
        SEGS(16, 17);
        mma_tile_fold<2 * CS_FF2 + 6>(acc[3], A[3], HI(7), mu);
        SEGS(17, 19);
        ok = probe_n<8, 2>();
        SEGS(19, 20);
        settle_n<8, 2>(ok);
        mma_tile_reuse(acc[1], H[0], LO(8));
        SEGS(20, 22);
        mma_tile<false>(acc[1], H[1], HI(8));
        SEGS(22, 24);
        WG_WAIT(2); pin(acc[3]);
        RELEASE(5, 7);
        SEGS(24, 26);
        mma_tile<false>(acc[1], H[2], LO(9));
        SEGS(26, 27);
        ok = probe_n<10, 2>();
        SEGS(27, 28);
        settle_n<10, 2>(ok);
        mma_tile_reuse(acc[2], H[0], LO(10));
        SEGS(28, 31);
        mma_tile<false>(acc[2], H[1], HI(10));
        SEGS(31, 34);
#undef SEGS
        PROF_MARK(3 + pass * 16);
        const uint32_t rtag = here(pass ^ 1);
        const uint4* rs_in = xp + X_RS;
        mma_tile<false>(acc[1], H[3], HI(9));
        mma_tile<false>(acc[2], H[2], LO(11));
        ok = probe_n<12, 2>();
        uint4* rs_out = peer<1>(xp) + X_RS;
        mma_tile<false>(acc[2], H[3], HI(11));
        settle_n<12, 2>(ok);
        WG_WAIT(2); pin(acc[1]);
        RELEASE(8, 9);
        send_half<0>(rs_out, acc[1], rtag);
        mma_tile_reuse(acc[3], H[0], LO(12));
        SCHED();
        send_half<1>(rs_out, acc[1], rtag);
        mma_tile<false>(acc[3], H[1], HI(12));
        rs_out = peer<2>(xp) + X_RS + 512;
        WG_WAIT(2); pin(acc[2]);
        send_half<0>(rs_out, acc[2], rtag);
        mma_tile<false>(acc[3], H[2], LO(13));
        SCHED();
        ok = probe_n<14, 2>();
        send_half<1>(rs_out, acc[2], rtag);
        mma_tile<false>(acc[3], H[3], HI(13));
        settle_n<14, 2>(ok);
        mma_tile_reuse(acc[1], H[0], LO(14));
        rs_out = peer<3>(xp) + X_RS + 1024;
        if (!pass) bar_sync(BAR_RDY, 160);
        fetch(rs_in, A[1]);
        SCHED();
        mma_tile<false>(acc[1], H[1], HI(14));
        WG_WAIT(2); pin(acc[3]);
        send_half<0>(rs_out, acc[3], rtag);
        send_half<1>(rs_out, acc[3], rtag);
        mma_tile<false>(acc[1], H[2], LO(15)); mma_tile<false>(acc[1], H[3], HI(15));
        SCHED();
        res_load(res, acc[2]);
        if (!pass) acquire_n<F_QKV, 3>();
        confirm(rs_in, A[1], rtag);
        mma_add_half(acc[2], A[1]);
        fetch(rs_in + 512, A[2]);
        fetch(rs_in + 1024, A[3]);
        confirm(rs_in + 512, A[2], rtag);
        mma_add_half(acc[2], A[2]);
        SCHED();
        confirm(rs_in + 1024, A[3], rtag);
        mma_add_half(acc[2], A[3]);
        PROF_MARK(4 + pass * 16);
        WG_WAIT(0); pin(acc[2]); pin(acc[1]);
#pragma unroll
        for (int i = 0; i < 16; i++) A[0][i] = pack2(fmaf(acc[1][2 * i], 0.5f, acc[2][2 * i]), fmaf(acc[1][2 * i + 1], 0.5f, acc[2][2 * i + 1]));
        if (pass) {
          PROF_MARK(21);
          stat_publish(A[0], sc, here(th), 0);
          const RowNorm fn = stat_gather(sc, here(th), 0, 1.f);
          const float nm0 = -fn.m0 * fn.rs0, nm1 = -fn.m1 * fn.rs1;
#pragma unroll
          for (int i = 0; i < 16; i++) {
            const float rs = (i & 1) ? fn.rs1 : fn.rs0, nm = (i & 1) ? nm1 : nm0;
            A[0][i] = pack2(fmaf(bf_lo(A[0][i]), rs, nm), fmaf(bf_hi(A[0][i]), rs, nm));
          }
          tile_store(here(maddr), A[0]);
          __syncwarp();
          const int row = 16 * w + (lane >> 3);
          uint4* dst = (uint4*)(out + ((size_t)batch * T_SEQ + t * 64 + row) * DM + 64 * r) + (lane & 7);
          const uint32_t src = stg + row * 128 + (((lane & 7) ^ (lane >> 3)) << 4);
#pragma unroll
          for (int i = 0; i < 4; i++) {
            uint4 v;
            lds128((src ^ ((i & 1) << 6)) + i * 512, v.x, v.y, v.z, v.w);
            if (row + 4 * i < nvalid) dst[i * 4 * (DM / 8)] = v;
          }
          PROF_MARK(22);
          PROF_TIME(31);
          break;
        }
        sent = send_residual(A[0], sc, xp, res, 1);
        PROF_MARK(5);
        mma_tile<true>(acc[0], A[0], LO(F_QKV)); mma_tile<true>(acc[1], A[0], HI(F_QKV));
        mma_tile<true>(acc[2], A[0], LO(F_QKV + 1));
        gather_first<1, X_AG0>(A, xp, 1, sent);
        mma_tile<false>(acc[0], A[1], LO(F_QKV + 2)); mma_tile<false>(acc[1], A[1], HI(F_QKV + 2));
        acquire_n<F_QKV + 3, 3>();
        gather_rest<1, X_AG0>(A, xp, 1);
        PROF_MARK(6);
        mma_tile<false>(acc[0], A[2], LO(F_QKV + 3));
        norm_consume(here(th), mu, rs0, rs1);
        if (row0 >= nvalid) rs0 = 0.f;
        if (row0 + 8 >= nvalid) rs1 = 0.f;
        mma_tile_fold<2 * CS_QKV - 6>(acc[0], A[3], LO(F_QKV + 4), mu);
        RELEASE(10, 15);
        mma_tile<false>(acc[1], A[2], HI(F_QKV + 3));
        mma_tile_fold<2 * CS_QKV - 4>(acc[1], A[3], HI(F_QKV + 4), mu);
        WG_WAIT(2); pin(acc[0]);
        scale_pack(acc[0], Q, rs0, rs1);
        tile_store(here(maddr), Q);
        fence_async_smem();
        bar_arrive(BAR_K, 160);
        mma_tile<false>(acc[2], A[1], HI(F_QKV + 1)); mma_tile<false>(acc[2], A[2], LO(F_QKV + 5));
        WG_WAIT(2); pin(acc[1]);
        scale_pack(acc[1], Q, rs0, rs1);
        tile_store(here(maddr) + TILE_BYTES, Q);
        fence_async_smem();
        bar_arrive(BAR_V, 160);
        mma_tile_fold<2 * CS_QKV - 2>(acc[2], A[3], HI(F_QKV + 5), mu);
        WG_WAIT(0); pin(acc[2]);
        scale_pack(acc[2], Q, rs0 * SM_SCALE_LOG2, rs1 * SM_SCALE_LOG2);
        res_store(here(res) - TILE_BYTES, Q);
        bar_arrive(BAR_Q, 256);
        RELEASE(F_QKV, F_QKV + 5);
      } else {
        bar_sync(BAR_Q, 256);
#pragma unroll
        for (int s = 0; s < 4; s++) lds128(res - TILE_BYTES + s * 512, Q[4 * s], Q[4 * s + 1], Q[4 * s + 2], Q[4 * s + 3]);
        if (w < 2) {
          const uint32_t v = w ? 0u : 0x3F803F80u;
#pragma unroll
          for (int s = 0; s < 4; s++) sts128(res - TILE_BYTES + s * 512, v, v, v, v);
          fence_async_smem();
        }
      }
      bar_sync(BAR_ATT, 256);
      PROF_MARK(7);

      const int dir = cw == 0 ? -1 : 1;
      uint32_t tap[15];
      {
        const uint32_t* dwp = (const uint32_t*)(dw + 64 * r) + lane + 7 * (DM / 2);
#pragma unroll
        for (int k = 0; k < 15; k++) tap[k] = __ldg(dwp + dir * (k - 7) * (DM / 2));
      }

      float O[36];
      {
        float S[2][32];
        uint32_t P[2][16], nm[4];
        pin(Q);
        WG_FENCE();
        qk_tile(S[0], Q, RING + (SM_STG >> 4));
        WG_COMMIT();
#pragma unroll
        for (int i = 0; i < 36; i++) O[i] = 0.f;
#pragma unroll
        for (int i = 0; i < 16; i++) P[1][i] = 0u;
        WG_WAIT(0); pin(S[0]);
        const float m0 = tile_max<0>(S[0]), m1 = tile_max<2>(S[0]);
        nm[0] = pack2(q ? 0.f : -m0, 0.f); nm[1] = pack2(q ? 0.f : -m1, 0.f); nm[2] = 0u; nm[3] = 0u;
#pragma unroll
        for (int k = 0; k < 15; k++) asm("mul.rn.bf16x2 %0, %0, %1;" : "+r"(tap[k]) : "r"(0x3F003F00u));
        pin(nm); pin(O); pin(P[1]); pin(tap);
        uint32_t sk = wg, sv = wg;
        mbar_wait(SM_BASE + SM_FULL + (F_SPARE % NSTAGE + wg) * 8, 1);
        if (lane == 0) mbar_arrive(SM_BASE + SM_EMPTY + (F_SPARE % NSTAGE + wg) * 8);
        mbar_wait(SM_BASE + SM_FULL + sk * 8, 0);
        PROF_MARK(8);
        WG_FENCE();
        qk_tile(S[0], Q, RING + sk * 1024);
        qk_shift(S[0], nm);
        WG_COMMIT();
        WG_WAIT(0); pin(S[0]);
#pragma unroll 1
        for (int it = 0; it < 4; it++) {
          attn_step(S[0], S[1], P[0], P[1], O, Q, nm, RING + sk * 1024 + 512, RING_V + (sv * 1024 + 512) * V_STEP);
          const uint32_t sn = it == 2 ? wg : sk + (it == 3 ? 2 : 4);
          mbar_wait(SM_BASE + SM_FULL + sn * 8, it >= 2);
          mbar_wait(SM_BASE + SM_FULL + (sk + 2) * 8, it == 3);
          WG_WAIT(0); pin(O); pin(S[1]); pin(P[1]);
          if (lane == 0) {
            mbar_arrive(SM_BASE + SM_EMPTY + sk * 8);
            if (it) mbar_arrive(SM_BASE + SM_EMPTY + sv * 8);
          }
          sv = sk + 2; sk = sn;
          attn_step(S[1], S[0], P[1], P[0], O, Q, nm, RING + sk * 1024, RING_V + (sv * 1024) * V_STEP);
          WG_WAIT(0); pin(O); pin(S[0]); pin(P[0]);
        }
        WG_FENCE();
        pv_tile(O, P[1], RING_V + (sv * 1024 + 512) * V_STEP, (uint64_t)wg << 22);
        WG_COMMIT();
        WG_WAIT(0); pin(O);
      }
      PROF_MARK(9);

      if (wg == 1) {
        const uint32_t mo = stg + here(th) * 16;
#pragma unroll
        for (int i = 0; i < 9; i++)
          sts128(mo + i * 2048 + (i >> 3) * 4096, __float_as_uint(O[4 * i]), __float_as_uint(O[4 * i + 1]), __float_as_uint(O[4 * i + 2]), __float_as_uint(O[4 * i + 3]));
        bar_arrive(BAR_MERGE, 256);
        norm_duty(sc, here(th), 0, 0.5f, 0);
      } else {
        const uint32_t mo = stg + here(th) * 16;
        bar_sync(BAR_MERGE, 256);
#pragma unroll
        for (int i = 8; i >= 0; i--) {
          uint32_t e[4];
          lds128(mo + i * 2048 + (i >> 3) * 4096, e[0], e[1], e[2], e[3]);
#pragma unroll
          for (int k = 0; k < 4; k++) O[4 * i + k] += __uint_as_float(e[k]);
        }
        const bool safe = O[32] > 0x1p-60f && O[32] < 0x1p60f && O[34] > 0x1p-60f && O[34] < 0x1p60f;
        if (__builtin_expect(__any_sync(0xffffffffu, !safe), 0)) attention_exact(O, Q, sc, batch * 4 + r, lane);
        const float i0 = rcp_hw(O[32]), i1 = rcp_hw(O[34]);
#pragma unroll
        for (int i = 0; i < 16; i++) { const float v = (i & 1) ? i1 : i0; A[0][i] = pack2(O[2 * i] * v, O[2 * i + 1] * v); }
        PROF_MARK(10);
        sent = proj_residual<F_WO, 6>(A, sc, xp, res, 0);
        PROF_MARK(12);
        float acc[2][32];
        mma_tile<true>(acc[0], A[0], LO(F_PW1)); mma_tile<true>(acc[1], A[0], HI(F_PW1));
        gather_first<1, X_AG0>(A, xp, 0, sent);
        mma_tile<false>(acc[1], A[1], HI(F_PW1 + 1)); mma_tile<false>(acc[0], A[1], LO(F_PW1 + 1));
        gather_rest<1, X_AG0>(A, xp, 0);
        PROF_MARK(13);
        mma_tile<false>(acc[1], A[2], HI(F_PW1 + 2));
        uint32_t mu[4];
        float rs0, rs1;
        norm_consume(here(th), mu, rs0, rs1);
        if (row0 >= nvalid) rs0 = 0.f;
        if (row0 + 8 >= nvalid) rs1 = 0.f;
        mma_tile_fold<2 * CS_PW1 + 2>(acc[1], A[3], HI(F_PW1 + 3), mu);
        RELEASE(F_KV + 14, F_WO + 1);
        mma_tile<false>(acc[0], A[2], LO(F_PW1 + 2));
        mma_tile_fold<2 * CS_PW1>(acc[0], A[3], LO(F_PW1 + 3), mu);
        WG_WAIT(2); pin(acc[1]);
#pragma unroll
        for (int i = 0; i < 32; i++) acc[1][i] = tanh_hw(acc[1][i] * ((i & 2) ? rs1 : rs0));
#pragma unroll
        for (int i = 0; i < 32; i++) { const float rs = (i & 2) ? rs1 : rs0; acc[1][i] = fmaf(acc[1][i], rs, rs); }
        pin(acc[1]);
        SCHED();
        WG_WAIT(0); pin(acc[0]);
#pragma unroll
        for (int i = 0; i < 16; i++) A[0][i] = pack2(acc[0][2 * i] * acc[1][2 * i], acc[0][2 * i + 1] * acc[1][2 * i + 1]);
        const uint32_t ga = stg + TILE_BYTES + here(mrow) * G_PITCH + (lane >> 4) * 16;
#pragma unroll
        for (int s = 0; s < 4; s++) stsm4(ga + s * 32, &A[0][4 * s]);
        RELEASE(F_PW1, F_PW1 + 3);
      }
      {
        const uint32_t gsrc = stg + TILE_BYTES + (8 * cw - 7) * G_PITCH + lane * 4;
        const bool edge = cw == 0 || cw == 7;
        const bool nbr = cw == 0 ? t > 0 : t < 15;
        uint4* const hdst = &sc->x[b + 4 * dir][X_HALO + (cw == 0 ? 96 : 0) + lane];
        uint32_t in[22];
        bar_sync(BAR_G, 256);
        PROF_MARK(14);
        if (cw == 0) {
#pragma unroll
          for (int i = 14; i >= 0; i--) in[i] = lds32(gsrc + (21 - i) * G_PITCH);
        } else {
#pragma unroll
          for (int i = 14; i >= 0; i--) in[i] = lds32(gsrc + i * G_PITCH);
        }
        if (edge) {
          if (nbr) {
            st_vec(hdst, HALO_TAG, in[14], in[13], in[12]);
            st_vec(hdst + 32, HALO_TAG, in[11], in[10], in[9]);
            st_vec(hdst + 64, HALO_TAG, in[8], 0u, 0u);
          }
        } else {
#pragma unroll
          for (int i = 15; i < 22; i++) in[i] = lds32(gsrc + i * G_PITCH);
        }
        uint32_t cv[8];
#pragma unroll
        for (int i = 0; i < 15; i++)
#pragma unroll
          for (int o = 0; o < 8; o++) {
            if (i == o) asm("mul.rn.bf16x2 %0, %1, %2;" : "=r"(cv[o]) : "r"(in[i]), "r"(tap[0]));
            if (i > o) asm("fma.rn.bf16x2 %0, %1, %2, %0;" : "+r"(cv[o]) : "r"(in[i]), "r"(tap[i - o]));
          }
        pin(cv);
        if (edge) {
#pragma unroll
          for (int i = 15; i < 22; i++) in[i] = 0u;
          if (nbr) {
            const uint4* src = &sc->x[b][X_HALO + (cw == 0 ? 0 : 96) + lane];
            uint32_t e0, e1, e2, u0, u1, spin = 0;
#pragma unroll 1
            do {
              ld_vec(src, e0, in[15], in[16], in[17]);
              ld_vec(src + 32, e1, in[18], in[19], in[20]);
              ld_vec(src + 64, e2, in[21], u0, u1);
            } while (__any_sync(0xffffffffu, ((e0 ^ HALO_TAG) | (e1 ^ HALO_TAG) | (e2 ^ HALO_TAG)) != 0) && ++spin < SPIN_LIMIT);
          }
        }
#pragma unroll
        for (int i = 15; i < 22; i++)
#pragma unroll
          for (int o = 0; o < 8; o++)
            if (i - o <= 14) asm("fma.rn.bf16x2 %0, %1, %2, %0;" : "+r"(cv[o]) : "r"(in[i]), "r"(tap[i - o]));
        const uint32_t fl = cw == 0 ? 7 : 0;
        const uint32_t cdst = (stg + cw * 1024 + lane * 4) ^ (fl * 144);
#pragma unroll
        for (int o = 0; o < 8; o++) {
          const float a = bf_lo(cv[o]), c = bf_hi(cv[o]);
          sts32(cdst ^ (o * 144), pack2(fmaf(a, tanh_hw(a), a), fmaf(c, tanh_hw(c), c)));
        }
      }
      if (wg == 1) {
        bar_arrive(BAR_C, 256);
        norm_duty(sc, here(th), 1, 0.5f, 0);
        if (th == 0) ((volatile uint32_t*)sc->epoch)[b] += 1;
        break;
      }
      bar_sync(BAR_C, 256);
      tile_load(here(maddr), A[0]);
      PROF_MARK(15);
      sent = proj_residual<F_PW2, 2>(A, sc, xp, res, 1);
      PROF_MARK(17);
    }
  }
}

typedef CUresult (*EncodeFn)(CUtensorMap*, CUtensorMapDataType, cuuint32_t, void*, const cuuint64_t*, const cuuint64_t*,
                             const cuuint32_t*, const cuuint32_t*, CUtensorMapInterleave, CUtensorMapSwizzle,
                             CUtensorMapL2promotion, CUtensorMapFloatOOBfill);

void make_map(EncodeFn fn, CUtensorMap* m, const void* w, int rows, int cols, CUtensorMapSwizzle swz) {
  const cuuint64_t dims[2] = {(cuuint64_t)cols, (cuuint64_t)rows}, strides[1] = {(cuuint64_t)cols * 2};
  const cuuint32_t box[2] = {64, 64}, es[2] = {1, 1};
  fn(m, CU_TENSOR_MAP_DATA_TYPE_BFLOAT16, 2, const_cast<void*>(w), dims, strides, box, es, CU_TENSOR_MAP_INTERLEAVE_NONE,
     swz, CU_TENSOR_MAP_L2_PROMOTION_L2_128B, CU_TENSOR_MAP_FLOAT_OOB_FILL_NONE);
}

}

extern "C" void kernel_launch(void* const* d_in, const int* in_sizes, int n_in, void* d_out, int out_size) {
  static EncodeFn fn = nullptr;
  static Scratch* sc = nullptr;
  if (!fn) {
    void* f = nullptr;
    cudaDriverEntryPointQueryResult st;
    cudaGetDriverEntryPoint("cuTensorMapEncodeTiled", &f, cudaEnableDefault, &st);
    fn = (EncodeFn)f;
    void* raw = nullptr;
    cudaGetSymbolAddress(&raw, g_scratch);
    sc = (Scratch*)(((uintptr_t)raw + X_ALIGN - 1) & ~(uintptr_t)(X_ALIGN - 1));
    cudaFuncSetAttribute(conformer_kernel, cudaFuncAttributeMaxDynamicSharedMemorySize, SM_TOTAL);
  }
  typedef const __nv_bfloat16* W;
  const CUtensorMapSwizzle S = CU_TENSOR_MAP_SWIZZLE_128B;
  Params p;
  {
    const cuuint64_t dims[4] = {64, T_SEQ, 4, 2}, strides[3] = {512, 128, T_SEQ * 512};
    const cuuint32_t box[4] = {64, 64, 4, 1}, es[4] = {1, 1, 1, 1};
    fn(&p.map[M_X], CU_TENSOR_MAP_DATA_TYPE_BFLOAT16, 4, d_in[0], dims, strides, box, es, CU_TENSOR_MAP_INTERLEAVE_NONE, S,
       CU_TENSOR_MAP_L2_PROMOTION_L2_128B, CU_TENSOR_MAP_FLOAT_OOB_FILL_NONE);
  }
  make_map(fn, &p.map[M_FF1A], d_in[1], 256, 1024, S);
  make_map(fn, &p.map[M_FF1B], d_in[2], 1024, 256, S);
  make_map(fn, &p.map[M_QKV], d_in[3], 256, 768, S);
  make_map(fn, &p.map[M_KV], sc->kv, 16384, 64, CU_TENSOR_MAP_SWIZZLE_NONE);
  make_map(fn, &p.map[M_WO], d_in[4], 256, 256, S);
  make_map(fn, &p.map[M_PW1], d_in[5], 256, 512, S);
  make_map(fn, &p.map[M_PW2], d_in[7], 256, 256, S);
  make_map(fn, &p.map[M_FF2A], d_in[8], 256, 1024, S);
  make_map(fn, &p.map[M_FF2B], d_in[9], 1024, 256, S);
  p.w_ff1b = (W)d_in[2]; p.w_qkv = (W)d_in[3]; p.w_o = (W)d_in[4]; p.w_pw1 = (W)d_in[5];
  p.w_pw2 = (W)d_in[7]; p.w_ff2a = (W)d_in[8]; p.w_ff2b = (W)d_in[9];

  cudaLaunchConfig_t cfg = {};
  cfg.gridDim = dim3(NCTA);
  cfg.blockDim = dim3(384);
  cfg.dynamicSmemBytes = SM_TOTAL;
  cfg.stream = cudaStreamPerThread;
  cudaLaunchAttribute at[1];
  at[0].id = cudaLaunchAttributeCooperative;
  at[0].val.cooperative = 1;
  cfg.attrs = at;
  cfg.numAttrs = 1;
  cudaLaunchKernelEx(&cfg, conformer_kernel, sc, (__nv_bfloat16*)d_out, (W)d_in[6], (W)d_in[0], (W)d_in[1], p);
}
```

```cpp
#include <cuda_runtime.h>
#include <cuda_bf16.h>
#include <cuda.h>
#include <stdint.h>

namespace {

constexpr int T_SEQ = 1000;
constexpr int DM = 256;
constexpr int NCTA = 128;
constexpr int NSTAGE = 12;
constexpr uint32_t STAGE_BYTES = 16384;
constexpr uint32_t TILE_BYTES = 8192;
constexpr uint32_t SM_BASE = 1024;
constexpr uint32_t SM_STG = NSTAGE * STAGE_BYTES;
constexpr uint32_t SM_FULL = SM_STG + 32768;
constexpr uint32_t SM_EMPTY = SM_FULL + 96;
constexpr uint32_t SM_XBAR = SM_FULL + 192;
constexpr uint32_t SM_EYE = SM_FULL + 256;
constexpr uint32_t SM_ONE = SM_FULL + 640;
constexpr uint32_t SM_CS = SM_FULL + 768;
constexpr uint32_t SM_TOTAL = SM_FULL + 3072;
constexpr int CS_FF2 = 0, CS_PW1 = 4, CS_QKV = 6;
constexpr uint32_t SPIN_LIMIT = 1u << 16;
constexpr float LN_EPS = 1e-5f;
constexpr float SM_SCALE_LOG2 = 0.125f * 1.4426950408889634f;
constexpr uint32_t G_PITCH = 144;

constexpr int F_QKV = 16, F_SPARE = 22, F_KV = 24, F_WO = 40, F_PW1 = 42, F_PW2 = 46, F_TOTAL = 64;
enum { M_FF1A, M_FF1B, M_QKV, M_KV, M_WO, M_PW1, M_PW2, M_FF2A, M_FF2B, M_X, M_COUNT };
enum { BAR_K = 1, BAR_V, BAR_Q, BAR_MERGE, BAR_G, BAR_C, BAR_WG1, BAR_RDY, BAR_CS, BAR_ATT, BAR_INIT, BAR_HALF };

struct Params {
  CUtensorMap map[M_COUNT];
  const __nv_bfloat16 *w_ff1b, *w_qkv, *w_o, *w_pw1, *w_pw2, *w_ff2a, *w_ff2b;
};

constexpr int X_RS = 0, X_AG1 = X_RS, X_HALO = X_RS + 512, X_CLEAR = 1024, X_AG0 = 1536, X_ST = 2048, X_SIZE = 4096;
constexpr uint32_t HALO_TAG = 0xFFFF0001u;
struct Scratch {
  uint4 x[NCTA][X_SIZE];
  uint4 kv[8][2][16][512];
  uint4 cs[576];
  uint32_t flag[8][32][32];
  uint32_t ready[NCTA][32];
  uint32_t epoch[NCTA];
};
constexpr size_t X_ALIGN = 4 * X_SIZE * sizeof(uint4);
__device__ uint8_t g_scratch[sizeof(Scratch) + X_ALIGN];
#define PROF_TIME(i)
#define PROF_MARK(i)

__device__ __forceinline__ void mbar_init(uint32_t bar, uint32_t cnt) {
  asm volatile("mbarrier.init.shared::cta.b64 [%0], %1;" :: "r"(bar), "r"(cnt) : "memory");
}
__device__ __forceinline__ void mbar_wait(uint32_t bar, uint32_t parity) {
  asm volatile("{\n.reg .pred p;\n.reg .u32 c;\nmov.u32 c, 0;\n"
               "WAIT_LOOP:\nmbarrier.try_wait.parity.shared::cta.b64 p, [%0], %1;\n@p bra WAIT_DONE;\n"
               "add.u32 c, c, 1;\nsetp.lt.u32 p, c, %2;\n@p bra WAIT_LOOP;\nWAIT_DONE:\n}"
               :: "r"(bar), "r"(parity), "n"(SPIN_LIMIT) : "memory");
}
__device__ __forceinline__ void mbar_arrive(uint32_t bar) {
  asm volatile("mbarrier.arrive.shared::cta.b64 _, [%0];" :: "r"(bar) : "memory");
}
#define bar_sync(id, n) asm volatile("bar.sync %0, %1;" :: "n"((int)(id)), "n"(n) : "memory")
#define bar_arrive(id, n) asm volatile("bar.arrive %0, %1;" :: "n"((int)(id)), "n"(n) : "memory")
__device__ __forceinline__ void fence_async_smem() { asm volatile("fence.proxy.async.shared::cta;" ::: "memory"); }

__device__ __forceinline__ void st_vec(uint4* p, uint32_t a, uint32_t b, uint32_t c, uint32_t d) {
  asm volatile("{\n.reg .b128 v;\n.reg .b64 lo, hi;\nmov.b64 lo, {%1, %2};\nmov.b64 hi, {%3, %4};\nmov.b128 v, {lo, hi};\n"
               "st.relaxed.gpu.global.b128 [%0], v;\n}" :: "l"(p), "r"(a), "r"(b), "r"(c), "r"(d) : "memory");
}
__device__ __forceinline__ void ld_vec(const uint4* p, uint32_t& a, uint32_t& b, uint32_t& c, uint32_t& d) {
  asm volatile("{\n.reg .b128 v;\n.reg .b64 lo, hi;\nld.relaxed.gpu.global.b128 v, [%4];\nmov.b128 {lo, hi}, v;\n"
               "mov.b64 {%0, %1}, lo;\nmov.b64 {%2, %3}, hi;\n}" : "=r"(a), "=r"(b), "=r"(c), "=r"(d) : "l"(p) : "memory");
}
__device__ __forceinline__ void sts128(uint32_t a, uint32_t x, uint32_t y, uint32_t z, uint32_t w) {
  asm volatile("st.shared.v4.u32 [%0], {%1, %2, %3, %4};" :: "r"(a), "r"(x), "r"(y), "r"(z), "r"(w) : "memory");
}
__device__ __forceinline__ void lds128(uint32_t a, uint32_t& x, uint32_t& y, uint32_t& z, uint32_t& w) {
  asm volatile("ld.shared.v4.u32 {%0, %1, %2, %3}, [%4];" : "=r"(x), "=r"(y), "=r"(z), "=r"(w) : "r"(a) : "memory");
}
__device__ __forceinline__ uint32_t lds32(uint32_t a) {
  uint32_t x; asm volatile("ld.shared.u32 %0, [%1];" : "=r"(x) : "r"(a) : "memory"); return x;
}
__device__ __forceinline__ void sts32(uint32_t a, uint32_t x) { asm volatile("st.shared.u32 [%0], %1;" :: "r"(a), "r"(x) : "memory"); }
__device__ __forceinline__ void sts64(uint32_t a, uint32_t x, uint32_t y) {
  asm volatile("st.shared.v2.u32 [%0], {%1, %2};" :: "r"(a), "r"(x), "r"(y) : "memory");
}
__device__ __forceinline__ void stsm4(uint32_t a, const uint32_t* r) {
  asm volatile("stmatrix.sync.aligned.m8n8.x4.shared.b16 [%0], {%1, %2, %3, %4};" :: "r"(a), "r"(r[0]), "r"(r[1]), "r"(r[2]), "r"(r[3]) : "memory");
}
__device__ __forceinline__ void ldsm4(uint32_t a, uint32_t* r) {
  asm volatile("ldmatrix.sync.aligned.m8n8.x4.shared.b16 {%0, %1, %2, %3}, [%4];" : "=r"(r[0]), "=r"(r[1]), "=r"(r[2]), "=r"(r[3]) : "r"(a) : "memory");
}
__device__ __forceinline__ uint32_t pack2(float lo, float hi) {
  uint32_t r; asm("cvt.rn.bf16x2.f32 %0, %1, %2;" : "=r"(r) : "f"(hi), "f"(lo)); return r;
}
__device__ __forceinline__ float bf_lo(uint32_t w) { return __uint_as_float(w << 16); }
__device__ __forceinline__ float bf_hi(uint32_t w) { return __uint_as_float(w & 0xffff0000u); }
__device__ __forceinline__ float tanh_hw(float x) { float y; asm volatile("tanh.approx.f32 %0, %1;" : "=f"(y) : "f"(x)); return y; }
__device__ __forceinline__ float rcp_hw(float x) { float y; asm("rcp.approx.ftz.f32 %0, %1;" : "=f"(y) : "f"(x)); return y; }
__device__ __forceinline__ float ex2_hw(float x) { float y; asm("ex2.approx.ftz.f32 %0, %1;" : "=f"(y) : "f"(x)); return y; }

__device__ __forceinline__ uint32_t here(uint32_t v) { asm volatile("" : "+r"(v)); return v; }

#define SCHED() asm volatile("pmevent 1;" ::: "memory")
#define WG_FENCE() asm volatile("wgmma.fence.sync.aligned;" ::: "memory")
#define WG_COMMIT() asm volatile("wgmma.commit_group.sync.aligned;" ::: "memory")
#define WG_WAIT(n) asm volatile("wgmma.wait_group.sync.aligned %0;" :: "n"(n) : "memory")

template <int N> __device__ __forceinline__ void pin(float (&d)[N]) {
#pragma unroll
  for (int i = 0; i < N; i++) asm volatile("" : "+f"(d[i]) :: "memory");
}
template <int N> __device__ __forceinline__ void pin(uint32_t (&d)[N]) {
#pragma unroll
  for (int i = 0; i < N; i++) asm volatile("" : "+r"(d[i]) :: "memory");
}

#define WG_D32 "{%0, %1, %2, %3, %4, %5, %6, %7, %8, %9, %10, %11, %12, %13, %14, %15, %16, %17, %18, %19, %20, %21, %22, %23, %24, %25, %26, %27, %28, %29, %30, %31}"
template <int TB> __device__ __forceinline__ void wgmma64_acc(float (&d)[32], const uint32_t* a, uint64_t db) {
  asm volatile("wgmma.mma_async.sync.aligned.m64n64k16.f32.bf16.bf16 " WG_D32 ", {%32, %33, %34, %35}, %36, 1, 1, 1, %37;"
    : "+f"(d[0]), "+f"(d[1]), "+f"(d[2]), "+f"(d[3]), "+f"(d[4]), "+f"(d[5]), "+f"(d[6]), "+f"(d[7]),
      "+f"(d[8]), "+f"(d[9]), "+f"(d[10]), "+f"(d[11]), "+f"(d[12]), "+f"(d[13]), "+f"(d[14]), "+f"(d[15]),
      "+f"(d[16]), "+f"(d[17]), "+f"(d[18]), "+f"(d[19]), "+f"(d[20]), "+f"(d[21]), "+f"(d[22]), "+f"(d[23]),
      "+f"(d[24]), "+f"(d[25]), "+f"(d[26]), "+f"(d[27]), "+f"(d[28]), "+f"(d[29]), "+f"(d[30]), "+f"(d[31])
    : "r"(a[0]), "r"(a[1]), "r"(a[2]), "r"(a[3]), "l"(db), "n"(TB));
}
__device__ __forceinline__ void wgmma64_reuse(float (&d)[32], const uint32_t* a, uint64_t db, uint32_t zero) {
  asm volatile("{\n.reg .pred p;\nsetp.ne.u32 p, %37, 0;\nwgmma.mma_async.sync.aligned.m64n64k16.f32.bf16.bf16 " WG_D32 ", {%32, %33, %34, %35}, %36, p, 1, 1, 1;\n}"
    : "+f"(d[0]), "+f"(d[1]), "+f"(d[2]), "+f"(d[3]), "+f"(d[4]), "+f"(d[5]), "+f"(d[6]), "+f"(d[7]),
      "+f"(d[8]), "+f"(d[9]), "+f"(d[10]), "+f"(d[11]), "+f"(d[12]), "+f"(d[13]), "+f"(d[14]), "+f"(d[15]),
      "+f"(d[16]), "+f"(d[17]), "+f"(d[18]), "+f"(d[19]), "+f"(d[20]), "+f"(d[21]), "+f"(d[22]), "+f"(d[23]),
      "+f"(d[24]), "+f"(d[25]), "+f"(d[26]), "+f"(d[27]), "+f"(d[28]), "+f"(d[29]), "+f"(d[30]), "+f"(d[31])
    : "r"(a[0]), "r"(a[1]), "r"(a[2]), "r"(a[3]), "l"(db), "r"(zero));
}
template <int TB> __device__ __forceinline__ void wgmma64_set(float (&d)[32], const uint32_t* a, uint64_t db) {
  asm volatile("wgmma.mma_async.sync.aligned.m64n64k16.f32.bf16.bf16 " WG_D32 ", {%32, %33, %34, %35}, %36, 0, 1, 1, %37;"
    : "=f"(d[0]), "=f"(d[1]), "=f"(d[2]), "=f"(d[3]), "=f"(d[4]), "=f"(d[5]), "=f"(d[6]), "=f"(d[7]),
      "=f"(d[8]), "=f"(d[9]), "=f"(d[10]), "=f"(d[11]), "=f"(d[12]), "=f"(d[13]), "=f"(d[14]), "=f"(d[15]),
      "=f"(d[16]), "=f"(d[17]), "=f"(d[18]), "=f"(d[19]), "=f"(d[20]), "=f"(d[21]), "=f"(d[22]), "=f"(d[23]),
      "=f"(d[24]), "=f"(d[25]), "=f"(d[26]), "=f"(d[27]), "=f"(d[28]), "=f"(d[29]), "=f"(d[30]), "=f"(d[31])
    : "r"(a[0]), "r"(a[1]), "r"(a[2]), "r"(a[3]), "l"(db), "n"(TB));
}

__device__ __forceinline__ void wgmma72_acc(float (&d)[36], const uint32_t* a, uint64_t db) {
  asm volatile("wgmma.mma_async.sync.aligned.m64n72k16.f32.bf16.bf16 {%0, %1, %2, %3, %4, %5, %6, %7, %8, %9, %10, %11, %12, %13, %14, %15, %16, %17, %18, %19, %20, %21, %22, %23, %24, %25, %26, %27, %28, %29, %30, %31, %32, %33, %34, %35}, {%36, %37, %38, %39}, %40, 1, 1, 1, 1;"
    : "+f"(d[0]), "+f"(d[1]), "+f"(d[2]), "+f"(d[3]), "+f"(d[4]), "+f"(d[5]), "+f"(d[6]), "+f"(d[7]), "+f"(d[8]),
      "+f"(d[9]), "+f"(d[10]), "+f"(d[11]), "+f"(d[12]), "+f"(d[13]), "+f"(d[14]), "+f"(d[15]), "+f"(d[16]), "+f"(d[17]),
      "+f"(d[18]), "+f"(d[19]), "+f"(d[20]), "+f"(d[21]), "+f"(d[22]), "+f"(d[23]), "+f"(d[24]), "+f"(d[25]), "+f"(d[26]),
      "+f"(d[27]), "+f"(d[28]), "+f"(d[29]), "+f"(d[30]), "+f"(d[31]), "+f"(d[32]), "+f"(d[33]), "+f"(d[34]), "+f"(d[35])
    : "r"(a[0]), "r"(a[1]), "r"(a[2]), "r"(a[3]), "l"(db));
}
__device__ __forceinline__ void wgmma16_acc(float* d, const uint32_t* a, uint64_t db) {
  asm volatile("wgmma.mma_async.sync.aligned.m64n16k16.f32.bf16.bf16 {%0, %1, %2, %3, %4, %5, %6, %7}, {%8, %9, %10, %11}, %12, 1, 1, 1, 0;"
    : "+f"(d[0]), "+f"(d[1]), "+f"(d[2]), "+f"(d[3]), "+f"(d[4]), "+f"(d[5]), "+f"(d[6]), "+f"(d[7])
    : "r"(a[0]), "r"(a[1]), "r"(a[2]), "r"(a[3]), "l"(db));
}
__device__ __forceinline__ void hmma(float (&d)[4], const uint32_t* a, uint32_t b0, uint32_t b1) {
  asm("mma.sync.aligned.m16n8k16.row.col.f32.bf16.bf16.f32 {%0, %1, %2, %3}, {%4, %5, %6, %7}, {%8, %9}, {%0, %1, %2, %3};"
    : "+f"(d[0]), "+f"(d[1]), "+f"(d[2]), "+f"(d[3]) : "r"(a[0]), "r"(a[1]), "r"(a[2]), "r"(a[3]), "r"(b0), "r"(b1));
}

__device__ __forceinline__ void hmma8(float (&d)[4], const uint32_t* a, uint32_t b0) {
  asm("mma.sync.aligned.m16n8k8.row.col.f32.bf16.bf16.f32 {%0, %1, %2, %3}, {%4, %5}, {%6}, {%0, %1, %2, %3};"
    : "+f"(d[0]), "+f"(d[1]), "+f"(d[2]), "+f"(d[3]) : "r"(a[0]), "r"(a[1]), "r"(b0));
}

template <bool FIRST> __device__ __forceinline__ void mma_tile(float (&d)[32], const uint32_t (&a)[16], uint64_t db) {
  WG_FENCE();
#pragma unroll
  for (int s = 0; s < 4; s++) {
    if (FIRST && s == 0) wgmma64_set<1>(d, &a[0], db); else wgmma64_acc<1>(d, &a[4 * s], db + s * 128);
  }
  WG_COMMIT();
}
__device__ __forceinline__ void mma_tile_reuse(float (&d)[32], const uint32_t (&a)[16], uint64_t db) {
  WG_FENCE();
  wgmma64_reuse(d, &a[0], db, blockIdx.y);
#pragma unroll
  for (int s = 1; s < 4; s++) wgmma64_acc<1>(d, &a[4 * s], db + s * 128);
  WG_COMMIT();
}
template <int ROW> __device__ __forceinline__ void fold_step(float (&d)[32], const uint32_t (&mu)[4]) {
  wgmma64_acc<1>(d, mu, (uint64_t)((SM_BASE + SM_CS + ROW * 128) >> 4) | (uint64_t(1) << 16) | (uint64_t(1) << 62));
}
template <int ROW> __device__ __forceinline__ void mma_fold(float (&d)[32], const uint32_t (&mu)[4]) {
  WG_FENCE();
  fold_step<ROW>(d, mu);
  WG_COMMIT();
}
template <int ROW> __device__ __forceinline__ void mma_tile_fold(float (&d)[32], const uint32_t (&a)[16], uint64_t db, const uint32_t (&mu)[4]) {
  WG_FENCE();
#pragma unroll
  for (int s = 0; s < 4; s++) wgmma64_acc<1>(d, &a[4 * s], db + s * 128);
  fold_step<ROW>(d, mu);
  WG_COMMIT();
}
__device__ __forceinline__ void mma_add_half(float (&d)[32], const uint32_t (&a)[16]) {
  const uint64_t db = (uint64_t)((SM_BASE + SM_EYE) >> 4) | (uint64_t(8) << 16) | (uint64_t(8) << 32);
  WG_FENCE();
#pragma unroll
  for (int s = 0; s < 4; s++) wgmma16_acc(&d[8 * s], &a[4 * s], db);
  WG_COMMIT();
}
#define ACQUIRE(f) mbar_wait(SM_BASE + SM_FULL + ((f) % NSTAGE) * 8, ((f) / NSTAGE) & 1)
template <int F, int N> __device__ __forceinline__ uint32_t probe_n() {
  static_assert(F % NSTAGE + N <= NSTAGE, "stages must not wrap");
  uint32_t ok = 1;
#pragma unroll
  for (int i = 0; i < N; i++)
    asm volatile("{\n.reg .pred p;\nmbarrier.test_wait.parity.shared::cta.b64 p, [%1], %2;\nselp.u32 %0, %0, 0, p;\n}"
                 : "+r"(ok) : "r"(SM_BASE + SM_FULL + (F % NSTAGE + i) * 8), "r"((F / NSTAGE) & 1) : "memory");
  return ok;
}
template <int F, int N> __device__ __forceinline__ void settle_n(uint32_t ok) {
  if (__builtin_expect(!ok, 0)) {
#pragma unroll 1
    for (int i = 0; i < N; i++) mbar_wait(SM_BASE + SM_FULL + (F % NSTAGE + i) * 8, (F / NSTAGE) & 1);
  }
}
template <int F, int N> __device__ __forceinline__ void acquire_n() { settle_n<F, N>(probe_n<F, N>()); }
#define RELEASE(f0, f1) do { if (lane == 0) { _Pragma("unroll") for (int f_ = (f0); f_ <= (f1); f_++) mbar_arrive(SM_BASE + SM_EMPTY + (f_ % NSTAGE) * 8); } } while (0)
constexpr uint64_t RING = (uint64_t)(SM_BASE >> 4) | (uint64_t(1) << 16) | (uint64_t(64) << 32) | (uint64_t(1) << 62);
#define LO(f) (RING + ((f) % NSTAGE) * 1024)
#define HI(f) (RING + ((f) % NSTAGE) * 1024 + 512)

template <int C> __device__ __forceinline__ uint4* peer(uint4* p) {
  asm volatile("" : "+l"(p));
  return (uint4*)((uintptr_t)p ^ (C * X_SIZE * sizeof(uint4)));
}
__device__ __forceinline__ uint32_t clock_now() { uint32_t c; asm volatile("mov.u32 %0, %%clock;" : "=r"(c) :: "memory"); return c; }
__device__ __forceinline__ void publish(uint4* dst, uint32_t (&a)[16], uint32_t tag) {
#pragma unroll
  for (int s = 0; s < 4; s++) a[4 * s] = (a[4 * s] & ~1u) | tag;
  pin(a);
  SCHED();
#pragma unroll
  for (int s = 0; s < 4; s++) st_vec(dst + s * 128, a[4 * s], a[4 * s + 1], a[4 * s + 2], a[4 * s + 3]);
  SCHED();
}
__device__ __forceinline__ void fetch(const uint4* src, uint32_t (&a)[16]) {
#pragma unroll
  for (int s = 0; s < 4; s++) ld_vec(src + s * 128, a[4 * s], a[4 * s + 1], a[4 * s + 2], a[4 * s + 3]);
}
__device__ __forceinline__ uint32_t miss(const uint32_t (&a)[16], uint32_t tag) {
  return (a[0] ^ tag) | (a[4] ^ tag) | (a[8] ^ tag) | (a[12] ^ tag);
}
__device__ __forceinline__ bool stale(uint32_t v) { return __any_sync(0xffffffffu, here(v) & 1u); }
__device__ __forceinline__ void confirm(const uint4* src, uint32_t (&a)[16], uint32_t tag) {
  uint32_t spin = 0;
  while (__builtin_expect(stale(miss(a, tag)), 0) && ++spin < SPIN_LIMIT) fetch(src, a);
}
constexpr uint32_t GATHER_DELAY = 400;
__device__ __forceinline__ void stat_fetch(const Scratch* sc, uint32_t (&st)[4]) {
  const uint32_t th = here(threadIdx.x);
  ld_vec(&sc->x[(blockIdx.x & ~3u) + (th & 3)][X_ST + (th >> 2)], st[0], st[1], st[2], st[3]);
}
template <int C, int SLOT> __device__ __forceinline__ void gather_first(uint32_t (&A)[4][16], uint32_t (&st)[4], const Scratch* sc, uint4* xp,
                                                                        uint32_t tag, uint32_t sent) {
  while (clock_now() - sent < GATHER_DELAY) {}
  fetch(peer<1>(xp) + SLOT, A[1]); fetch(peer<2>(xp) + SLOT, A[2]); fetch(peer<3>(xp) + SLOT, A[3]);
  if (SLOT == X_AG0) stat_fetch(sc, st);
  uint32_t spin = 0;
  while (__builtin_expect(stale(miss(A[1], tag) | miss(A[C], tag)), 0) && ++spin < SPIN_LIMIT) {
    fetch(peer<1>(xp) + SLOT, A[1]);
    if (C == 2) fetch(peer<2>(xp) + SLOT, A[2]);
  }
}
template <int C, int SLOT> __device__ __forceinline__ void gather_rest(uint32_t (&A)[4][16], uint4* xp, uint32_t tag) {
  SCHED();
  uint32_t spin = 0;
  while (__builtin_expect(stale(miss(A[C + 1], tag) | miss(A[3], tag)), 0) && ++spin < SPIN_LIMIT) {
    if (C == 1) fetch(peer<2>(xp) + SLOT, A[2]);
    fetch(peer<3>(xp) + SLOT, A[3]);
  }
}
__device__ __forceinline__ void pack_acc(const float (&d)[32], uint32_t (&a)[16]) {
#pragma unroll
  for (int i = 0; i < 16; i++) a[i] = pack2(d[2 * i], d[2 * i + 1]);
}
__device__ __forceinline__ void frag_store(uint32_t slot, const uint32_t (&a)[16]) {
#pragma unroll
  for (int s = 0; s < 4; s++) sts128(slot + s * 512, a[4 * s], a[4 * s + 1], a[4 * s + 2], a[4 * s + 3]);
}
__device__ __forceinline__ void tile_store(uint32_t maddr, const uint32_t (&a)[16]) {
#pragma unroll
  for (int s = 0; s < 4; s++) stsm4(maddr ^ (s << 5), &a[4 * s]);
}
__device__ __forceinline__ void tile_load(uint32_t maddr, uint32_t (&a)[16]) {
#pragma unroll
  for (int s = 0; s < 4; s++) ldsm4(maddr ^ (s << 5), &a[4 * s]);
}

__device__ __forceinline__ void res_load(uint32_t maddr, float (&d)[32]) {
  uint32_t a[16];
  tile_load(here(maddr) + 3 * TILE_BYTES, a);
#pragma unroll
  for (int i = 0; i < 16; i++) { d[2 * i] = bf_lo(a[i]); d[2 * i + 1] = bf_hi(a[i]); }
  pin(d);
}

struct RowAcc { float s[4], u[2][4], v[2][4]; };
__device__ __forceinline__ void row_acc(RowAcc& t, const uint32_t (&a)[16]) {
#pragma unroll
  for (int s = 0; s < 8; s++) {
    if ((s & 1) == 0) hmma(t.s, &a[2 * s], 0x3F803F80u, 0x3F803F80u);
    hmma8(t.u[s & 1], &a[2 * s], a[2 * s]);
    hmma8(t.v[s & 1], &a[2 * s], a[2 * s + 1]);
  }
}
__device__ __forceinline__ float2 row_squares(const RowAcc& t, bool odd) {
  return make_float2(odd ? t.u[0][1] + t.u[1][1] : t.u[0][0] + t.u[1][0], odd ? t.v[0][3] + t.v[1][3] : t.v[0][2] + t.v[1][2]);
}
__device__ __forceinline__ void stat_publish(const uint32_t (&a)[16], Scratch* sc, uint32_t th, uint32_t tag) {
  RowAcc t = {};
  row_acc(t, a);
  const float2 q = row_squares(t, th & 4);
  if ((th & 3) == ((th >> 3) & 3))
    st_vec(&sc->x[blockIdx.x][X_ST + (th >> 2)], (__float_as_uint(t.s[0]) & ~1u) | tag, __float_as_uint(q.x), __float_as_uint(t.s[2]), __float_as_uint(q.y));
}
struct RowNorm { float m0, rs0, m1, rs1; };
__device__ __forceinline__ RowNorm row_norm(float s0, float q0, float s1, float q1, float scale) {
  RowNorm n;
  n.m0 = s0 * (1.f / DM); n.m1 = s1 * (1.f / DM);
  n.rs0 = scale * rsqrtf(fmaxf(fmaf(-n.m0, n.m0, q0 * (1.f / DM)), 0.f) + LN_EPS);
  n.rs1 = scale * rsqrtf(fmaxf(fmaf(-n.m1, n.m1, q1 * (1.f / DM)), 0.f) + LN_EPS);
  return n;
}
__device__ __forceinline__ RowNorm stat_finish(const Scratch* sc, uint32_t (&st)[4], uint32_t tag, float scale) {
  uint32_t spin = 0;
  while (__builtin_expect(stale(st[0] ^ tag), 0) && ++spin < SPIN_LIMIT) stat_fetch(sc, st);
  float f[4];
#pragma unroll
  for (int i = 0; i < 4; i++) {
    f[i] = __uint_as_float(st[i]);
    f[i] += __shfl_xor_sync(0xffffffffu, f[i], 1);
    f[i] += __shfl_xor_sync(0xffffffffu, f[i], 2);
  }
  return row_norm(f[0], f[1], f[2], f[3], scale);
}
__device__ __forceinline__ void mean_frag(uint32_t (&mu)[4], const RowNorm& n, bool sel) {
  const float a = sel ? -n.m0 : 0.f, c = sel ? -n.m1 : 0.f;
  mu[0] = pack2(a, a); mu[1] = pack2(c, c);
  const float al = a - bf_lo(mu[0]), cl = c - bf_lo(mu[1]);
  mu[2] = pack2(al, al); mu[3] = pack2(cl, cl);
  pin(mu);
}
__device__ __forceinline__ void centre(uint32_t (&a)[16], uint32_t m0, uint32_t m1) {
#pragma unroll
  for (int i = 0; i < 16; i++) asm("sub.rn.bf16x2 %0, %0, %1;" : "+r"(a[i]) : "r"((i & 1) ? m1 : m0));
  pin(a);
}
__device__ __forceinline__ void scale_pack(const float (&d)[32], uint32_t (&a)[16], float rs0, float rs1) {
#pragma unroll
  for (int i = 0; i < 16; i++) { const float rs = (i & 1) ? rs1 : rs0; a[i] = pack2(d[2 * i] * rs, d[2 * i + 1] * rs); }
}
template <int S> __device__ __forceinline__ void silu_seg(float (&acc)[4][32], float (&tn)[2][4], uint32_t (&H)[4][16], float rs0, float rs1) {
  if (S >= 2) {
    const float* h = &acc[(S - 2) >> 3][4 * ((S - 2) & 7)];
    const float* v = tn[S & 1];
    uint32_t* o = &H[(S - 2) >> 3][2 * ((S - 2) & 7)];
    o[0] = pack2(fmaf(h[0], v[0], h[0]), fmaf(h[1], v[1], h[1]));
    o[1] = pack2(fmaf(h[2], v[2], h[2]), fmaf(h[3], v[3], h[3]));
    asm volatile("" : "+r"(o[0]), "+r"(o[1]));
  }
  if (S >= 1 && S <= 32) {
#pragma unroll
    for (int k = 0; k < 4; k++) tn[(S - 1) & 1][k] = tanh_hw(acc[((S - 1) >> 3) & 3][4 * ((S - 1) & 7) + k]);
  }
  if (S < 32) {
    float* h = &acc[(S >> 3) & 3][4 * (S & 7)];
    h[0] *= rs0; h[1] *= rs0; h[2] *= rs1; h[3] *= rs1;
    asm volatile("" : "+f"(h[0]), "+f"(h[1]), "+f"(h[2]), "+f"(h[3]));
  }
  SCHED();
}
template <int S0, int S1> __device__ __forceinline__ void silu_segs(float (&acc)[4][32], float (&tn)[2][4], uint32_t (&H)[4][16], float rs0, float rs1) {
  silu_seg<S0>(acc, tn, H, rs0, rs1);
  if constexpr (S0 + 1 < S1) silu_segs<S0 + 1, S1>(acc, tn, H, rs0, rs1);
}
template <int HALF> __device__ __forceinline__ void send_half(uint4* dst, const float (&d)[32], uint32_t tag) {
  uint32_t o[8];
#pragma unroll
  for (int i = 0; i < 8; i++) o[i] = pack2(d[16 * HALF + 2 * i], d[16 * HALF + 2 * i + 1]);
  o[0] = (o[0] & ~1u) | tag; o[4] = (o[4] & ~1u) | tag;
  pin(o);
  SCHED();
  st_vec(dst + HALF * 256, o[0], o[1], o[2], o[3]);
  st_vec(dst + HALF * 256 + 128, o[4], o[5], o[6], o[7]);
  SCHED();
}
__device__ __forceinline__ uint32_t send_residual(uint32_t (&a)[16], Scratch* sc, uint4* xp, uint32_t maddr, uint32_t tag) {
  const uint32_t exact[4] = {a[0], a[4], a[8], a[12]};
  publish(xp + X_AG0, a, tag);
  const uint32_t sent = clock_now();
  const uint32_t th = here(threadIdx.x);
  stat_publish(a, sc, th, tag);
  tile_store(here(maddr) + 3 * TILE_BYTES, a);
  stsm4(SM_BASE + SM_STG + 3 * TILE_BYTES + (th >> 5) * 2048 + (th & 7) * 128 + ((((th >> 2) & 6) ^ (th & 7)) << 4), exact);
  return sent;
}
template <int F, int N> __device__ __forceinline__ uint32_t proj_residual(uint32_t (&A)[4][16], Scratch* sc, uint4* xp, uint32_t maddr,
                                                                          uint32_t tag, uint32_t sent) {
  float acc[32];
  uint32_t st[4];
  acquire_n<F, N>();
  if (F == F_PW2) acquire_n<0, 5>();
  res_load(maddr, acc);
  mma_tile<false>(acc, A[0], LO(F));
  gather_first<2, X_AG1>(A, st, sc, xp, tag, sent);
  mma_tile<false>(acc, A[1], HI(F));
  mma_tile<false>(acc, A[2], LO(F + 1));
  gather_rest<2, X_AG1>(A, xp, tag);
  PROF_MARK(F == F_WO ? 11 : 16);
  mma_tile<false>(acc, A[3], HI(F + 1));
  WG_WAIT(0); pin(acc);
  pack_acc(acc, A[0]);
  return send_residual(A[0], sc, xp, maddr, tag);
}

__device__ __forceinline__ void qk_tile(float (&S)[32], const uint32_t (&Q)[16], uint64_t dk) {
#pragma unroll
  for (int s = 0; s < 4; s++) {
    if (s == 0) wgmma64_set<0>(S, &Q[0], dk); else wgmma64_acc<0>(S, &Q[4 * s], dk + s * 2);
  }
}
__device__ __forceinline__ void qk_shift(float (&S)[32], const uint32_t (&nm)[4]) { wgmma64_acc<0>(S, nm, (uint64_t)((SM_BASE + SM_ONE) >> 4)); }
constexpr uint64_t V_STEP = uint64_t(1) - (uint64_t(1) << 16);
constexpr uint64_t RING_V = RING - (uint64_t(1) << 16) + ((uint64_t)((SM_STG + 2 * TILE_BYTES) >> 4) << 16);
__device__ __forceinline__ void pv_tile(float (&O)[36], const uint32_t (&P)[16], uint64_t dv, uint64_t pad) {
#pragma unroll
  for (int s = 0; s < 4; s++) wgmma72_acc(O, &P[4 * s], dv + s * 128 * V_STEP + (s < 2 ? 0 : (s - 1) * pad));
}
__device__ __forceinline__ void attn_step(const float (&Sc)[32], float (&Sn)[32], uint32_t (&Pc)[16], uint32_t (&Pp)[16], float (&O)[36],
                                          const uint32_t (&Q)[16], const uint32_t (&nm)[4], uint64_t dk, uint64_t dv) {
  WG_FENCE();
  qk_tile(Sn, Q, dk);
  qk_shift(Sn, nm);
  pv_tile(O, Pp, dv, 0);
  WG_COMMIT();
  SCHED();
#pragma unroll
  for (int i = 0; i < 16; i++) Pc[i] = pack2(ex2_hw(Sc[2 * i]), ex2_hw(Sc[2 * i + 1]));
  pin(Pc);
  SCHED();
}
template <int R> __device__ __forceinline__ float tile_max(const float (&S)[32]) {
  float t[4];
#pragma unroll
  for (int j = 0; j < 4; j++) t[j] = fmaxf(fmaxf(S[8 * j + R], S[8 * j + R + 1]), fmaxf(S[8 * j + R + 4], S[8 * j + R + 5]));
  float n = fmaxf(fmaxf(t[0], t[1]), fmaxf(t[2], t[3]));
  n = fmaxf(n, __shfl_xor_sync(0xffffffffu, n, 1));
  return fmaxf(n, __shfl_xor_sync(0xffffffffu, n, 2));
}
__device__ __forceinline__ void attention_exact(float (&O)[36], const uint32_t (&Q)[16], const Scratch* sc, int bh, int lane, int half) {
  const char* kb = (const char*)&sc->kv[bh][0][0][0];
  const char* vb = (const char*)&sc->kv[bh][1][0][0];
  const int g = lane >> 2, q = lane & 3;
  float m0 = -INFINITY, m1 = -INFINITY, l0 = 0.f, l1 = 0.f;
  float o[4][4] = {};
#pragma unroll 1
  for (int k0 = 0; k0 < T_SEQ; k0 += 8) {
    float s[4] = {0.f, 0.f, 0.f, 0.f};
#pragma unroll
    for (int c = 0; c < 8; c++) hmma8(s, &Q[2 * c], __ldcg((const uint32_t*)(kb + (k0 + g) * 128 + ((c ^ g) << 4) + q * 4)));
    float n0 = fmaxf(s[0], s[1]), n1 = fmaxf(s[2], s[3]);
    n0 = fmaxf(n0, __shfl_xor_sync(0xffffffffu, n0, 1)); n1 = fmaxf(n1, __shfl_xor_sync(0xffffffffu, n1, 1));
    n0 = fmaxf(m0, fmaxf(n0, __shfl_xor_sync(0xffffffffu, n0, 2))); n1 = fmaxf(m1, fmaxf(n1, __shfl_xor_sync(0xffffffffu, n1, 2)));
    const float a0 = ex2_hw(m0 - n0), a1 = ex2_hw(m1 - n1);
    m0 = n0; m1 = n1;
    const uint32_t pp[2] = {pack2(ex2_hw(s[0] - n0), ex2_hw(s[1] - n0)), pack2(ex2_hw(s[2] - n1), ex2_hw(s[3] - n1))};
    l0 = fmaf(l0, a0, bf_lo(pp[0]) + bf_hi(pp[0])); l1 = fmaf(l1, a1, bf_lo(pp[1]) + bf_hi(pp[1]));
#pragma unroll
    for (int j = 0; j < 4; j++) {
      const int c = 4 * half + j;
      const uint32_t v0 = __ldcg((const uint16_t*)(vb + (k0 + 2 * q) * 128 + ((c ^ (2 * q)) << 4) + g * 2));
      const uint32_t v1 = __ldcg((const uint16_t*)(vb + (k0 + 2 * q + 1) * 128 + ((c ^ (2 * q + 1)) << 4) + g * 2));
      o[j][0] *= a0; o[j][1] *= a0; o[j][2] *= a1; o[j][3] *= a1;
      hmma8(o[j], pp, v0 | (v1 << 16));
    }
  }
  l0 += __shfl_xor_sync(0xffffffffu, l0, 1); l1 += __shfl_xor_sync(0xffffffffu, l1, 1);
  O[32] = l0 + __shfl_xor_sync(0xffffffffu, l0, 2); O[34] = l1 + __shfl_xor_sync(0xffffffffu, l1, 2);
#pragma unroll
  for (int i = 0; i < 16; i++) O[i] = o[i >> 2][i & 3];
}

__device__ __forceinline__ uint32_t fill_entry(int f, int r, int bh) {
  int m, x = r, y, dx = 0;
  if (f < F_QKV || f >= 48) {
    const int i = f & 15;
    m = f < F_QKV ? M_FF1A : M_FF2A;
    if (i < 8) { x = 4 * r + ((0xE2u >> i) & 1) * 2; y = r ^ ((0xE790u >> (2 * i)) & 3); dx = 1; }
    else { m++; x = r ^ (((i >> 1) - 3) & 3); y = 4 * r + 2 * (i & 1); }
  } else if (f < F_KV) {
    const int i = f - F_QKV;
    m = M_QKV;
    if (i == 1 || i >= 5) { y = r ^ (i == 1 ? 0 : 2); }
    else { x = 4 + r; y = r ^ (i ? i - 1 : 0); dx = 4; }
  } else if (f < F_WO) {
    const int i = f - F_KV;
    m = M_KV; x = 0; y = bh * 32 + (i & 2) * 8 + (i >> 2) * 4 + (i & 1) * 2;
  } else if (f >= F_PW1 && f < F_PW2) {
    m = M_PW1; y = r ^ (f - F_PW1); dx = 4;
  } else {
    m = f < F_PW1 ? M_WO : M_PW2; y = r ^ ((f & 1) * 2);
  }
  return m | (x << 4) | (y << 8) | (dx << 16);
}
__device__ __forceinline__ void tma_fill(uint32_t st, const CUtensorMap* map, uint32_t x, uint32_t y, uint32_t x2, uint32_t y2) {
  asm volatile("{\n.reg .pred p;\nelect.sync _|p, 0xffffffff;\n"
               "@p mbarrier.arrive.expect_tx.shared::cta.b64 _, [%1], 16384;\n"
               "@p cp.async.bulk.tensor.2d.shared::cluster.global.mbarrier::complete_tx::bytes [%0], [%2, {%3, %4}], [%1];\n"
               "@p cp.async.bulk.tensor.2d.shared::cluster.global.mbarrier::complete_tx::bytes [%0 + 8192], [%2, {%5, %6}], [%1];\n}"
               :: "r"(SM_BASE + st * STAGE_BYTES), "r"(SM_BASE + SM_FULL + st * 8), "l"(map), "r"(x), "r"(y), "r"(x2), "r"(y2) : "memory");
}
__device__ __forceinline__ void l2_prefetch(const void* p, uint32_t total, int b) {
  const uint32_t part = total / NCTA;
  asm volatile("cp.async.bulk.prefetch.L2.global [%0], %1;" :: "l"((const char*)p + (size_t)b * part), "r"(part) : "memory");
}

__global__ void __launch_bounds__(384, 1) conformer_kernel(Scratch* __restrict__ sc, __nv_bfloat16* __restrict__ out,
                                                           const __nv_bfloat16* __restrict__ dw, const __nv_bfloat16* __restrict__ xin,
                                                           const __nv_bfloat16* __restrict__ w_ff1a, const __grid_constant__ Params p) {
  extern __shared__ __align__(1024) uint8_t smem[];
  const int tid = threadIdx.x, lane = tid & 31;
  if (tid == 0) {
    l2_prefetch(xin, 2 * T_SEQ * DM * 2, blockIdx.x);
    l2_prefetch(w_ff1a, 256 * 1024 * 2, blockIdx.x);
  }
  const int cw = __shfl_sync(0xffffffffu, tid >> 5, 0), wg = cw >> 2, w = cw & 3;
  const int b = blockIdx.x, r = b & 3, batch = b >> 6, t = (b >> 2) & 15;
  if ((uint32_t)__cvta_generic_to_shared(smem) != SM_BASE) return;
  PROF_MARK(0);
  PROF_TIME(30);

  if (wg == 2) {
    asm volatile("setmaxnreg.dec.sync.aligned.u32 40;");
    if (cw == 8) {
      if (lane == 0) {
        asm volatile("prefetch.tensormap [%0];" :: "l"(&p.map[M_X]) : "memory");
        asm volatile("prefetch.tensormap [%0];" :: "l"(&p.map[M_FF1A]) : "memory");
        mbar_init(SM_BASE + SM_XBAR, 1);
        mbar_init(SM_BASE + SM_XBAR + 8, 3);
#pragma unroll
        for (int i = 0; i < NSTAGE; i++) mbar_init(SM_BASE + SM_FULL + i * 8, 1);
        fence_async_smem();
      }
      __syncwarp();
      bar_arrive(0, 320);
      PROF_MARK(9);
#pragma unroll
      for (int f = 0; f < 8; f++) {
        const uint32_t x = 256 * r + ((0xE2u >> f) & 1) * 128, y = (r ^ ((0xE790u >> (2 * f)) & 3)) * 64;
#pragma unroll
        for (int c = (f == 0 ? 0 : 1); c < (f == 0 ? 1 : f == 2 ? 4 : 0); c++)
          asm volatile("{\n.reg .pred p;\nelect.sync _|p, 0xffffffff;\n"
                       "@p mbarrier.arrive.expect_tx.shared::cta.b64 _, [%1], 8192;\n"
                       "@p cp.async.bulk.tensor.3d.shared::cluster.global.mbarrier::complete_tx::bytes [%0], [%2, {%3, %4, %5}], [%1];\n}"
                       :: "r"(SM_BASE + SM_STG + (3 - c) * TILE_BYTES), "r"(SM_BASE + SM_XBAR + (c ? 8 : 0)), "l"(&p.map[M_X]),
                          "r"((r ^ c) * 64), "r"(t * 64), "r"(batch) : "memory");
        tma_fill(f, &p.map[M_FF1A], x, y, x + 64, y);
      }
      PROF_MARK(1);
      const uint32_t* flag = sc->flag[batch * 4 + r][lane];
      const uint32_t prev = ((volatile uint32_t*)sc->epoch)[b];
      uint32_t entry[2], ready = 0, st = 8, parity = 1;
#pragma unroll 1
      for (int i = 0; i < 2; i++) { entry[1] = fill_entry(i * 32 + lane, r, batch * 4 + r); if (i == 0) entry[0] = entry[1]; }
      bar_sync(BAR_INIT, 64);
#pragma unroll 1
      for (int f = 8; f < F_TOTAL; f++) {
        const uint32_t e = __shfl_sync(0xffffffffu, f < 32 ? entry[0] : entry[1], f);
        if ((e & 15) == M_KV) {
          const uint32_t need = 3u << ((e >> 8) & 31);
          uint32_t spin = 0;
#pragma unroll 1
          while ((ready & need) != need && ++spin < SPIN_LIMIT) {
            uint32_t v;
            asm volatile("ld.relaxed.gpu.global.u32 %0, [%1];" : "=r"(v) : "l"(flag) : "memory");
            ready = __ballot_sync(0xffffffffu, v - 1 == prev);
          }
        }
        if (f == F_KV) PROF_MARK(8);
        mbar_wait(SM_BASE + SM_EMPTY + st * 8, parity);
        const uint32_t x = (e << 2) & 0x3C0, y = (e >> 2) & 0x3FC0, dx = (e >> 16) << 6;
        tma_fill(st, &p.map[e & 15], x, y, x + dx, dx ? y : y ^ 64);
        if (++st == NSTAGE) { st = 0; parity ^= 1; }
      }
    } else if (here(cw) != 11) {
      const int kind = w - 1;
      const uint32_t prev = ((volatile uint32_t*)sc->epoch)[b];
      if (kind == 0) {
        if (lane == 0) {
#pragma unroll
          for (int i = 0; i < NSTAGE; i++) mbar_init(SM_BASE + SM_EMPTY + i * 8, 4);
        }
        __syncwarp();
        bar_arrive(0, 320);
        bar_arrive(BAR_INIT, 64);
        bar_sync(BAR_K, 160);
      } else {
        uint32_t v, spin = 0;
#pragma unroll 1
        do {
          asm volatile("ld.relaxed.gpu.global.u32 %0, [%1];" : "=r"(v) : "l"(sc->ready[(b & ~3) + (lane & 3)]) : "memory");
        } while (__any_sync(0xffffffffu, v - 1 != prev) && ++spin < SPIN_LIMIT);
        bar_arrive(BAR_RDY, 160);
        bar_sync(BAR_V, 160);
      }
      if (lane == 0) {
        asm volatile("cp.async.bulk.global.shared::cta.bulk_group [%0], [%1], %2;"
                     :: "l"(&sc->kv[batch * 4 + r][kind][t][0]), "r"(SM_BASE + SM_STG + kind * TILE_BYTES), "r"(TILE_BYTES) : "memory");
        asm volatile("cp.async.bulk.commit_group;\ncp.async.bulk.wait_group 0;" ::: "memory");
        asm volatile("st.relaxed.gpu.global.u32 [%0], %1;" :: "l"(sc->flag[batch * 4 + r][kind * 16 + t]), "r"(prev + 1) : "memory");
      }
    } else {
      const uint32_t epoch = ((volatile uint32_t*)sc->epoch)[b] + 1;
      if (lane == 0 && epoch) {
        asm volatile("prefetch.tensormap [%0];" :: "l"(&p.map[M_FF1B]) : "memory");
        l2_prefetch(p.w_ff1b, 1024 * 256 * 2, b);
        l2_prefetch(p.w_qkv, 256 * 768 * 2, b);
        l2_prefetch(p.w_pw1, 256 * 512 * 2, b);
        l2_prefetch(p.w_ff2a, 256 * 1024 * 2, b);
      }
#pragma unroll 1
      for (int i = 0; i < 11; i++) {
        const uint32_t t0 = clock_now();
        uint4* dst = &sc->x[b][X_CLEAR + i * 96 + lane];
        st_vec(dst, 0u, 0u, 0u, 0u); st_vec(dst + 32, 0u, 0u, 0u, 0u); st_vec(dst + 64, 0u, 0u, 0u, 0u);
        while (clock_now() - t0 < 100) {}
      }
      asm volatile("fence.acq_rel.gpu;" ::: "memory");
      __syncwarp();
      if (lane == 0) {
        asm volatile("st.relaxed.gpu.global.u32 [%0], %1;" :: "l"(sc->ready[b]), "r"(epoch) : "memory");
        l2_prefetch(p.w_o, 256 * 256 * 2, b);
        l2_prefetch(p.w_pw2, 256 * 256 * 2, b);
        l2_prefetch(p.w_ff2b, 1024 * 256 * 2, b);
#pragma unroll
        for (int i = M_QKV; i < M_X; i++) asm volatile("prefetch.tensormap [%0];" :: "l"(&p.map[i]) : "memory");
      }
    }
  } else {
    asm volatile("setmaxnreg.inc.sync.aligned.u32 232;");
    const int q = lane & 3, th = tid & 127;
    constexpr uint32_t stg = SM_BASE + SM_STG;
    const uint32_t mrow = 16 * w + (lane & 15);
    const uint32_t maddr = stg + mrow * 128 + (((lane >> 4) ^ (lane & 7)) << 4);
    const uint32_t qslot = stg + 2 * TILE_BYTES + w * 2048 + lane * 16;
    uint4* const xp = &sc->x[b][th];
    const int nvalid = T_SEQ - t * 64, row0 = 16 * w + (lane >> 2);

    uint32_t A[4][16];
    uint32_t sent = 0;
    constexpr uint32_t SM_LN0 = SM_BASE + SM_CS + 1792;
    uint32_t st[4];
    if (wg == 0) {
      if (tid < 112) sts128(SM_BASE + SM_CS + tid * 16, 0, 0, 0, 0);
      sts32(SM_BASE + SM_EYE + tid * 4, tid >= 96 ? 0x3F803F80u : ((tid & 32) == 0 && (tid & 3) == ((tid >> 3) & 3)) ? (0x3F00u << ((tid & 4) * 4)) : 0u);
      fence_async_smem();
      bar_sync(0, 320);
      lds128(SM_LN0 + (th >> 2) * 16, st[0], st[1], st[2], st[3]);
      mbar_wait(SM_BASE + SM_XBAR, 0);
      PROF_MARK(1);
      tile_load(maddr + 3 * TILE_BYTES, A[0]);
      centre(A[0], st[0], st[1]);
    } else {
      {
        const uint4* src = (const uint4*)(xin + ((size_t)batch * T_SEQ + t * 64 + row0) * DM) + q;
#pragma unroll
        for (int i = 0; i < 16; i++) {
          const uint4 v = row0 + (i & 8) < nvalid ? __ldg(src + (i & 8) * (DM / 8) + (i & 7) * 4) : make_uint4(0, 0, 0, 0);
          uint32_t* a = &A[i >> 2][4 * (i & 3)];
          a[0] = v.x; a[1] = v.y; a[2] = v.z; a[3] = v.w;
        }
        RowAcc ra[2] = {};
#pragma unroll
        for (int c = 0; c < 4; c++) row_acc(ra[c >> 1], A[c]);
        const float2 qa = row_squares(ra[0], lane & 4), qb = row_squares(ra[1], lane & 4);
        const RowNorm n = row_norm(ra[0].s[0] + ra[0].s[2], qa.x + qa.y, ra[1].s[0] + ra[1].s[2], qb.x + qb.y, 0.5f);
        if (q == ((lane >> 3) & 3)) sts128(SM_LN0 + (th >> 2) * 16, pack2(n.m0, n.m0), pack2(n.m1, n.m1), __float_as_uint(n.rs0), __float_as_uint(n.rs1));
      }
      bar_sync(0, 320);
      const uint32_t epoch = ((volatile uint32_t*)sc->epoch)[b] + 1, tag = epoch & 1;
      PROF_MARK(5);
      SCHED();
      uint4 cv[8];
      if (b < 72) {
        const __nv_bfloat16* wp; int ld, col;
        if (b < 24) { wp = p.w_qkv; ld = 768; col = b * 32; }
        else if (b < 40) { wp = p.w_pw1; ld = 512; col = (b - 24) * 32; }
        else { wp = p.w_ff2a; ld = 1024; col = (b - 40) * 32; }
        const uint4* src = (const uint4*)(wp + (size_t)(th >> 2) * ld + col + q * 8);
#pragma unroll
        for (int i = 0; i < 8; i++) cv[i] = __ldg(src + i * 4 * ld);
      }
      if (b < 72) {
        float c[8] = {0.f, 0.f, 0.f, 0.f, 0.f, 0.f, 0.f, 0.f};
#pragma unroll
        for (int i = 0; i < 8; i++) {
          const uint4 v = cv[i];
          c[0] += bf_lo(v.x); c[1] += bf_hi(v.x); c[2] += bf_lo(v.y); c[3] += bf_hi(v.y);
          c[4] += bf_lo(v.z); c[5] += bf_hi(v.z); c[6] += bf_lo(v.w); c[7] += bf_hi(v.w);
        }
#pragma unroll 1
        for (int m = 4; m <= 16; m <<= 1)
#pragma unroll
          for (int k = 0; k < 8; k++) c[k] += __shfl_xor_sync(0xffffffffu, c[k], m);
        mbar_wait(SM_BASE + SM_EMPTY, 0);
        if (lane < 4) {
          const uint32_t a = SM_BASE + SM_CS + 1792 + w * 128 + lane * 32;
          sts128(a, __float_as_uint(c[0]), __float_as_uint(c[1]), __float_as_uint(c[2]), __float_as_uint(c[3]));
          sts128(a + 16, __float_as_uint(c[4]), __float_as_uint(c[5]), __float_as_uint(c[6]), __float_as_uint(c[7]));
        }
        bar_sync(BAR_WG1, 128);
        if (th < 8) {
          float o[4] = {0.f, 0.f, 0.f, 0.f};
#pragma unroll 1
          for (int k = 0; k < 4; k++) {
            uint32_t e[4];
            lds128(SM_BASE + SM_CS + 1792 + k * 128 + th * 16, e[0], e[1], e[2], e[3]);
#pragma unroll
            for (int i = 0; i < 4; i++) o[i] += __uint_as_float(e[i]);
          }
          st_vec(&sc->cs[b * 8 + th], (__float_as_uint(o[0]) & ~1u) | tag, __float_as_uint(o[1]), __float_as_uint(o[2]), __float_as_uint(o[3]));
        }
      }
      mbar_wait(SM_BASE + SM_EMPTY, 0);
      bar_sync(BAR_WG1, 128);
      PROF_MARK(2);
#pragma unroll 1
      for (int i = th; i < 144; i += 128) {
        const int j = i >> 4;
        int src;
        if (j < CS_PW1) src = 320 + 64 * r + i;
        else if (j < CS_QKV) src = 192 + (j - CS_PW1) * 64 + 16 * r + (i & 15);
        else src = ((j - CS_QKV + 1) % 3) * 64 + 16 * r + (i & 15);
        uint32_t e[4], spin = 0;
#pragma unroll 1
        do {
          ld_vec(&sc->cs[src], e[0], e[1], e[2], e[3]);
        } while (((e[0] ^ tag) & 1u) && ++spin < SPIN_LIMIT);
        const float c0 = __uint_as_float(e[0] & ~1u), c1 = __uint_as_float(e[1]), c2 = __uint_as_float(e[2]), c3 = __uint_as_float(e[3]);
        const uint32_t h0 = pack2(c0, c1), h1 = pack2(c2, c3);
        const uint32_t a = SM_BASE + SM_CS + j * 256 + (i & 15) * 8;
        sts64(a ^ ((a >> 3) & 0x70), h0, h1);
        sts64((a + 128) ^ (((a + 128) >> 3) & 0x70), pack2(c0 - bf_lo(h0), c1 - bf_hi(h0)), pack2(c2 - bf_lo(h1), c3 - bf_hi(h1)));
      }
      fence_async_smem();
      PROF_MARK(4);
      bar_arrive(BAR_CS, 256);
    }

#pragma unroll 1
    for (uint32_t pass = 0; pass < 2; pass++) {
      uint32_t Q[16];
      if (wg == 0) {
        float acc[4][32];
        uint32_t H[4][16];
        if (!pass) { PROF_MARK(47); ACQUIRE(0); }
        mma_tile<true>(acc[0], A[0], LO(0)); mma_tile<true>(acc[1], A[0], HI(0));
        if (!pass) ACQUIRE(1);
        mma_tile<true>(acc[2], A[0], LO(1)); mma_tile<true>(acc[3], A[0], HI(1));
        if (pass) {
          gather_first<1, X_AG0>(A, st, sc, xp, 1, sent);
        } else {
          mbar_wait(SM_BASE + SM_XBAR + 8, 0);
#pragma unroll
          for (int c = 1; c < 4; c++) tile_load(here(maddr) + (3 - c) * TILE_BYTES, A[c]);
          centre(A[1], st[0], st[1]);
          acquire_n<2, 3>();
        }
        mma_tile<false>(acc[0], A[1], LO(2)); mma_tile<false>(acc[1], A[1], HI(2));
        if (pass) {
          gather_rest<1, X_AG0>(A, xp, 1);
          RELEASE(F_PW2, F_PW2 + 1);
        } else {
          centre(A[2], st[0], st[1]); centre(A[3], st[0], st[1]);
        }
        PROF_MARK(2 + pass * 16);
        mma_tile<false>(acc[0], A[2], LO(3)); mma_tile<false>(acc[0], A[3], LO(4));
        WG_WAIT(4);
        RELEASE(0, 1);
        uint32_t mu[4] = {0u, 0u, 0u, 0u};
        float rs0 = __uint_as_float(st[2]), rs1 = __uint_as_float(st[3]), tn[2][4];
        if (pass) {
          const RowNorm n = stat_finish(sc, st, 1, 0.5f);
          rs0 = n.rs0; rs1 = n.rs1;
          mean_frag(mu, n, q == 0);
        }
        pin(mu);
        mma_fold<2 * CS_FF2>(acc[0], mu);
        mma_tile<false>(acc[1], A[2], HI(3));
#define SEGS(a, b) silu_segs<a, b>(acc, tn, H, rs0, rs1)
        WG_WAIT(1); pin(acc[0]);
        SEGS(0, 1);
        mma_tile_fold<2 * CS_FF2 + 2>(acc[1], A[3], HI(4), mu);
        SEGS(1, 3);
        uint32_t ok = probe_n<5, 3>();
        SEGS(3, 4);
        settle_n<5, 3>(ok);
        mma_tile<false>(acc[2], A[1], LO(5));
        SEGS(4, 6);
        mma_tile<false>(acc[2], A[2], LO(6));
        SEGS(6, 8);
        WG_WAIT(2); pin(acc[1]);
        RELEASE(2, 4);
        SEGS(8, 9);
        mma_tile_fold<2 * CS_FF2 + 4>(acc[2], A[3], LO(7), mu);
        SEGS(9, 12);
        mma_tile<false>(acc[3], A[1], HI(5));
        SEGS(12, 14);
        mma_tile<false>(acc[3], A[2], HI(6));
        SEGS(14, 16);
        WG_WAIT(2); pin(acc[2]);
        SEGS(16, 17);
        mma_tile_fold<2 * CS_FF2 + 6>(acc[3], A[3], HI(7), mu);
        SEGS(17, 19);
        ok = probe_n<8, 2>();
        SEGS(19, 20);
        settle_n<8, 2>(ok);
        mma_tile_reuse(acc[1], H[0], LO(8));
        SEGS(20, 22);
        mma_tile<false>(acc[1], H[1], HI(8));
        SEGS(22, 24);
        WG_WAIT(2); pin(acc[3]);
        RELEASE(5, 7);
        SEGS(24, 26);
        mma_tile<false>(acc[1], H[2], LO(9));
        SEGS(26, 27);
        ok = probe_n<10, 2>();
        SEGS(27, 28);
        settle_n<10, 2>(ok);
        mma_tile_reuse(acc[2], H[0], LO(10));
        SEGS(28, 31);
        mma_tile<false>(acc[2], H[1], HI(10));
        SEGS(31, 34);
#undef SEGS
        PROF_MARK(3 + pass * 16);
        const uint32_t rtag = here(pass ^ 1);
        const uint4* rs_in = xp + X_RS;
        mma_tile<false>(acc[1], H[3], HI(9));
        mma_tile<false>(acc[2], H[2], LO(11));
        ok = probe_n<12, 2>();
        uint4* rs_out = peer<1>(xp) + X_RS;
        mma_tile<false>(acc[2], H[3], HI(11));
        settle_n<12, 2>(ok);
        WG_WAIT(2); pin(acc[1]);
        RELEASE(8, 9);
        send_half<0>(rs_out, acc[1], rtag);
        mma_tile_reuse(acc[3], H[0], LO(12));
        SCHED();
        send_half<1>(rs_out, acc[1], rtag);
        mma_tile<false>(acc[3], H[1], HI(12));
        rs_out = peer<2>(xp) + X_RS + 512;
        WG_WAIT(2); pin(acc[2]);
        send_half<0>(rs_out, acc[2], rtag);
        mma_tile<false>(acc[3], H[2], LO(13));
        SCHED();
        ok = probe_n<14, 2>();
        send_half<1>(rs_out, acc[2], rtag);
        mma_tile<false>(acc[3], H[3], HI(13));
        settle_n<14, 2>(ok);
        mma_tile_reuse(acc[1], H[0], LO(14));
        rs_out = peer<3>(xp) + X_RS + 1024;
        if (!pass) bar_sync(BAR_RDY, 160);
        fetch(rs_in, A[1]);
        SCHED();
        mma_tile<false>(acc[1], H[1], HI(14));
        WG_WAIT(2); pin(acc[3]);
        send_half<0>(rs_out, acc[3], rtag);
        send_half<1>(rs_out, acc[3], rtag);
        sent = clock_now();
        mma_tile<false>(acc[1], H[2], LO(15)); mma_tile<false>(acc[1], H[3], HI(15));
        SCHED();
        confirm(rs_in, A[1], rtag);
        fetch(rs_in + 512, A[2]);
        SCHED();
        res_load(maddr, acc[2]);
        mma_add_half(acc[2], A[1]);
        while (clock_now() - sent < GATHER_DELAY) {}
        fetch(rs_in + 1024, A[3]);
        if (!pass) { acquire_n<F_QKV, 3>(); bar_sync(BAR_CS, 256); }
        {
          uint32_t spin = 0;
          while (__builtin_expect(stale(miss(A[2], rtag) | miss(A[3], rtag)), 0) && ++spin < SPIN_LIMIT) { fetch(rs_in + 512, A[2]); fetch(rs_in + 1024, A[3]); }
        }
        mma_add_half(acc[2], A[2]);
        mma_add_half(acc[2], A[3]);
        PROF_MARK(4 + pass * 16);
        WG_WAIT(0); pin(acc[2]); pin(acc[1]);
#pragma unroll
        for (int i = 0; i < 16; i++) A[0][i] = pack2(fmaf(acc[1][2 * i], 0.5f, acc[2][2 * i]), fmaf(acc[1][2 * i + 1], 0.5f, acc[2][2 * i + 1]));
        if (pass) {
          PROF_MARK(21);
          stat_publish(A[0], sc, here(th), 0);
          stat_fetch(sc, st);
          const RowNorm fn = stat_finish(sc, st, 0, 1.f);
          const float nm0 = -fn.m0 * fn.rs0, nm1 = -fn.m1 * fn.rs1;
#pragma unroll
          for (int i = 0; i < 16; i++) {
            const float rs = (i & 1) ? fn.rs1 : fn.rs0, nm = (i & 1) ? nm1 : nm0;
            A[0][i] = pack2(fmaf(bf_lo(A[0][i]), rs, nm), fmaf(bf_hi(A[0][i]), rs, nm));
          }
          tile_store(here(maddr), A[0]);
          __syncwarp();
          const int row = 16 * w + (lane >> 3);
          uint4* dst = (uint4*)(out + ((size_t)batch * T_SEQ + t * 64 + row) * DM + 64 * r) + (lane & 7);
          const uint32_t src = stg + row * 128 + (((lane & 7) ^ (lane >> 3)) << 4);
#pragma unroll
          for (int i = 0; i < 4; i++) {
            uint4 v;
            lds128((src ^ ((i & 1) << 6)) + i * 512, v.x, v.y, v.z, v.w);
            if (row + 4 * i < nvalid) dst[i * 4 * (DM / 8)] = v;
          }
          PROF_MARK(22);
          PROF_TIME(31);
          break;
        }
        sent = send_residual(A[0], sc, xp, maddr, 1);
        PROF_MARK(5);
        mma_tile<true>(acc[0], A[0], LO(F_QKV)); mma_tile<true>(acc[1], A[0], HI(F_QKV));
        mma_tile<true>(acc[2], A[0], LO(F_QKV + 1));
        gather_first<1, X_AG0>(A, st, sc, xp, 1, sent);
        mma_tile<false>(acc[0], A[1], LO(F_QKV + 2)); mma_tile<false>(acc[1], A[1], HI(F_QKV + 2));
        acquire_n<F_QKV + 3, 3>();
        gather_rest<1, X_AG0>(A, xp, 1);
        PROF_MARK(6);
        mma_tile<false>(acc[0], A[2], LO(F_QKV + 3)); mma_tile<false>(acc[0], A[3], LO(F_QKV + 4));
        SCHED();
        {
          const RowNorm n = stat_finish(sc, st, 1, 1.f);
          rs0 = row0 < nvalid ? n.rs0 : 0.f; rs1 = row0 + 8 < nvalid ? n.rs1 : 0.f;
          mean_frag(mu, n, q == 3);
        }
        mma_fold<2 * CS_QKV - 6>(acc[0], mu);
        RELEASE(10, 15);
        WG_WAIT(0); pin(acc[0]);
        scale_pack(acc[0], Q, rs0, rs1);
        tile_store(here(maddr), Q);
        SCHED();
        mma_tile<false>(acc[1], A[2], HI(F_QKV + 3));
        fence_async_smem();
        bar_arrive(BAR_K, 160);
        mma_tile_fold<2 * CS_QKV - 4>(acc[1], A[3], HI(F_QKV + 4), mu);
        mma_tile<false>(acc[2], A[1], HI(F_QKV + 1)); mma_tile<false>(acc[2], A[2], LO(F_QKV + 5));
        WG_WAIT(2); pin(acc[1]);
        scale_pack(acc[1], Q, rs0, rs1);
        tile_store(here(maddr) + TILE_BYTES, Q);
        fence_async_smem();
        bar_arrive(BAR_V, 160);
        mma_tile_fold<2 * CS_QKV - 2>(acc[2], A[3], HI(F_QKV + 5), mu);
        WG_WAIT(0); pin(acc[2]);
        scale_pack(acc[2], Q, rs0 * SM_SCALE_LOG2, rs1 * SM_SCALE_LOG2);
        frag_store(here(qslot), Q);
        bar_arrive(BAR_Q, 256);
        RELEASE(F_QKV, F_QKV + 5);
      } else {
        bar_sync(BAR_Q, 256);
#pragma unroll
        for (int s = 0; s < 4; s++) lds128(qslot + s * 512, Q[4 * s], Q[4 * s + 1], Q[4 * s + 2], Q[4 * s + 3]);
        if (w < 2) {
          const uint32_t v = w ? 0u : 0x3F803F80u;
#pragma unroll
          for (int s = 0; s < 4; s++) sts128(qslot + s * 512, v, v, v, v);
          fence_async_smem();
        }
      }
      bar_sync(BAR_ATT, 256);
      PROF_MARK(7);

      const int dir = cw == 0 ? -1 : 1;
      uint32_t tap[15];
      {
        const uint32_t* dwp = (const uint32_t*)(dw + 64 * r) + lane + 7 * (DM / 2);
#pragma unroll
        for (int k = 0; k < 15; k++) tap[k] = __ldg(dwp + dir * (k - 7) * (DM / 2));
      }

      float O[36];
      {
        float S[2][32];
        uint32_t P[2][16], nm[4];
        pin(Q);
        WG_FENCE();
        qk_tile(S[0], Q, RING + (SM_STG >> 4));
        WG_COMMIT();
#pragma unroll
        for (int i = 0; i < 36; i++) O[i] = 0.f;
#pragma unroll
        for (int i = 0; i < 16; i++) P[1][i] = 0u;
        WG_WAIT(0); pin(S[0]);
        const float m0 = tile_max<0>(S[0]), m1 = tile_max<2>(S[0]);
        nm[0] = pack2(q ? 0.f : -m0, 0.f); nm[1] = pack2(q ? 0.f : -m1, 0.f); nm[2] = 0u; nm[3] = 0u;
#pragma unroll
        for (int k = 0; k < 15; k++) asm("mul.rn.bf16x2 %0, %0, %1;" : "+r"(tap[k]) : "r"(0x3F003F00u));
        pin(nm); pin(O); pin(P[1]); pin(tap);
        uint32_t sk = wg, sv = wg;
        mbar_wait(SM_BASE + SM_FULL + (F_SPARE % NSTAGE + wg) * 8, 1);
        if (lane == 0) mbar_arrive(SM_BASE + SM_EMPTY + (F_SPARE % NSTAGE + wg) * 8);
        mbar_wait(SM_BASE + SM_FULL + sk * 8, 0);
        PROF_MARK(8);
        WG_FENCE();
        qk_tile(S[0], Q, RING + sk * 1024);
        qk_shift(S[0], nm);
        WG_COMMIT();
        WG_WAIT(0); pin(S[0]);
#pragma unroll 1
        for (int it = 0; it < 4; it++) {
          attn_step(S[0], S[1], P[0], P[1], O, Q, nm, RING + sk * 1024 + 512, RING_V + (sv * 1024 + 512) * V_STEP);
          const uint32_t sn = it == 2 ? wg : sk + (it == 3 ? 2 : 4);
          mbar_wait(SM_BASE + SM_FULL + sn * 8, it >= 2);
          mbar_wait(SM_BASE + SM_FULL + (sk + 2) * 8, it == 3);
          WG_WAIT(0); pin(O); pin(S[1]); pin(P[1]);
          if (lane == 0) {
            mbar_arrive(SM_BASE + SM_EMPTY + sk * 8);
            if (it) mbar_arrive(SM_BASE + SM_EMPTY + sv * 8);
          }
          sv = sk + 2; sk = sn;
          attn_step(S[1], S[0], P[1], P[0], O, Q, nm, RING + sk * 1024, RING_V + (sv * 1024) * V_STEP);
          WG_WAIT(0); pin(O); pin(S[0]); pin(P[0]);
        }
        WG_FENCE();
        pv_tile(O, P[1], RING_V + (sv * 1024 + 512) * V_STEP, (uint64_t)wg << 22);
        WG_COMMIT();
        WG_WAIT(0); pin(O);
      }
      PROF_MARK(9);

      {
        const uint32_t mo = stg + here(th) * 16;
        sts64(mo + 5 * 4096 + wg * 8, __float_as_uint(O[32]), __float_as_uint(O[34]));
        if (wg == 0) {
#pragma unroll
          for (int i = 4; i < 8; i++)
            sts128(mo + i * 2048, __float_as_uint(O[4 * i]), __float_as_uint(O[4 * i + 1]), __float_as_uint(O[4 * i + 2]), __float_as_uint(O[4 * i + 3]));
        } else {
#pragma unroll
          for (int i = 0; i < 4; i++)
            sts128(mo + i * 2048, __float_as_uint(O[4 * i]), __float_as_uint(O[4 * i + 1]), __float_as_uint(O[4 * i + 2]), __float_as_uint(O[4 * i + 3]));
#pragma unroll
          for (int i = 0; i < 16; i++) O[i] = O[16 + i];
        }
        bar_sync(BAR_MERGE, 256);
        uint32_t e[4];
        lds128(mo + 5 * 4096, e[0], e[1], e[2], e[3]);
        O[32] = __uint_as_float(e[0]) + __uint_as_float(e[2]); O[34] = __uint_as_float(e[1]) + __uint_as_float(e[3]);
#pragma unroll
        for (int i = 0; i < 4; i++) {
          lds128(mo + wg * TILE_BYTES + i * 2048, e[0], e[1], e[2], e[3]);
#pragma unroll
          for (int k = 0; k < 4; k++) O[4 * i + k] += __uint_as_float(e[k]);
        }
        const bool safe = O[32] > 0x1p-60f && O[32] < 0x1p60f && O[34] > 0x1p-60f && O[34] < 0x1p60f;
        if (__builtin_expect(__any_sync(0xffffffffu, !safe), 0)) attention_exact(O, Q, sc, batch * 4 + r, lane, wg);
        const float i0 = rcp_hw(O[32]), i1 = rcp_hw(O[34]);
#pragma unroll
        for (int i = 0; i < 8; i++) { const float v = (i & 1) ? i1 : i0; A[0][i] = pack2(O[2 * i] * v, O[2 * i + 1] * v); }
        A[0][0] &= ~1u; A[0][4] &= ~1u;
        uint4* dst = xp + X_AG1 + wg * 256;
        SCHED();
        st_vec(dst, A[0][0], A[0][1], A[0][2], A[0][3]);
        st_vec(dst + 128, A[0][4], A[0][5], A[0][6], A[0][7]);
        SCHED();
        sent = clock_now();
      }
      if (wg == 1) {
        const uint32_t mo = stg + TILE_BYTES + here(th) * 16;
        sts128(mo, A[0][0], A[0][1], A[0][2], A[0][3]);
        sts128(mo + 2048, A[0][4], A[0][5], A[0][6], A[0][7]);
        bar_arrive(BAR_HALF, 256);
      } else {
        PROF_MARK(10);
        const uint32_t mo = stg + TILE_BYTES + here(th) * 16;
        bar_sync(BAR_HALF, 256);
        lds128(mo, A[0][8], A[0][9], A[0][10], A[0][11]);
        lds128(mo + 2048, A[0][12], A[0][13], A[0][14], A[0][15]);
        sent = proj_residual<F_WO, 6>(A, sc, xp, maddr, 0, sent);
        PROF_MARK(12);
        float acc[2][32];
        mma_tile<true>(acc[0], A[0], LO(F_PW1)); mma_tile<true>(acc[1], A[0], HI(F_PW1));
        gather_first<1, X_AG0>(A, st, sc, xp, 0, sent);
        mma_tile<false>(acc[1], A[1], HI(F_PW1 + 1)); mma_tile<false>(acc[0], A[1], LO(F_PW1 + 1));
        gather_rest<1, X_AG0>(A, xp, 0);
        PROF_MARK(13);
        mma_tile<false>(acc[1], A[2], HI(F_PW1 + 2)); mma_tile<false>(acc[1], A[3], HI(F_PW1 + 3));
        SCHED();
        uint32_t mu[4];
        const RowNorm n = stat_finish(sc, st, 0, 0.5f);
        const float rs0 = row0 < nvalid ? n.rs0 : 0.f, rs1 = row0 + 8 < nvalid ? n.rs1 : 0.f;
        mean_frag(mu, n, q == 0);
        mma_fold<2 * CS_PW1 + 2>(acc[1], mu);
        RELEASE(F_KV + 14, F_WO + 1);
        mma_tile<false>(acc[0], A[2], LO(F_PW1 + 2));
        mma_tile_fold<2 * CS_PW1>(acc[0], A[3], LO(F_PW1 + 3), mu);
        WG_WAIT(2); pin(acc[1]);
#pragma unroll
        for (int i = 0; i < 32; i++) acc[1][i] = tanh_hw(acc[1][i] * ((i & 2) ? rs1 : rs0));
#pragma unroll
        for (int i = 0; i < 32; i++) { const float rs = (i & 2) ? rs1 : rs0; acc[1][i] = fmaf(acc[1][i], rs, rs); }
        pin(acc[1]);
        SCHED();
        WG_WAIT(0); pin(acc[0]);
#pragma unroll
        for (int i = 0; i < 16; i++) A[0][i] = pack2(acc[0][2 * i] * acc[1][2 * i], acc[0][2 * i + 1] * acc[1][2 * i + 1]);
        const uint32_t ga = stg + TILE_BYTES + here(mrow) * G_PITCH + (lane >> 4) * 16;
#pragma unroll
        for (int s = 0; s < 4; s++) stsm4(ga + s * 32, &A[0][4 * s]);
        RELEASE(F_PW1, F_PW1 + 3);
      }
      {
        const uint32_t gsrc = stg + TILE_BYTES + (8 * cw - 7) * G_PITCH + lane * 4;
        const bool edge = cw == 0 || cw == 7;
        const bool nbr = cw == 0 ? t > 0 : t < 15;
        uint4* const hdst = &sc->x[b + 4 * dir][X_HALO + (cw == 0 ? 96 : 0) + lane];
        uint32_t in[22];
        bar_sync(BAR_G, 256);
        PROF_MARK(14);
        if (cw == 0) {
#pragma unroll
          for (int i = 14; i >= 0; i--) in[i] = lds32(gsrc + (21 - i) * G_PITCH);
        } else {
#pragma unroll
          for (int i = 14; i >= 0; i--) in[i] = lds32(gsrc + i * G_PITCH);
        }
        if (edge) {
          if (nbr) {
            st_vec(hdst, HALO_TAG, in[14], in[13], in[12]);
            st_vec(hdst + 32, HALO_TAG, in[11], in[10], in[9]);
            st_vec(hdst + 64, HALO_TAG, in[8], 0u, 0u);
          }
        } else {
#pragma unroll
          for (int i = 15; i < 22; i++) in[i] = lds32(gsrc + i * G_PITCH);
        }
        uint32_t cv[8];
#pragma unroll
        for (int i = 0; i < 15; i++)
#pragma unroll
          for (int o = 0; o < 8; o++) {
            if (i == o) asm("mul.rn.bf16x2 %0, %1, %2;" : "=r"(cv[o]) : "r"(in[i]), "r"(tap[0]));
            if (i > o) asm("fma.rn.bf16x2 %0, %1, %2, %0;" : "+r"(cv[o]) : "r"(in[i]), "r"(tap[i - o]));
          }
        pin(cv);
        if (edge) {
#pragma unroll
          for (int i = 15; i < 22; i++) in[i] = 0u;
          if (nbr) {
            const uint4* src = &sc->x[b][X_HALO + (cw == 0 ? 0 : 96) + lane];
            uint32_t e0, e1, e2, u0, u1, spin = 0;
#pragma unroll 1
            do {
              ld_vec(src, e0, in[15], in[16], in[17]);
              ld_vec(src + 32, e1, in[18], in[19], in[20]);
              ld_vec(src + 64, e2, in[21], u0, u1);
            } while (__any_sync(0xffffffffu, ((e0 ^ HALO_TAG) | (e1 ^ HALO_TAG) | (e2 ^ HALO_TAG)) != 0) && ++spin < SPIN_LIMIT);
          }
        }
#pragma unroll
        for (int i = 15; i < 22; i++)
#pragma unroll
          for (int o = 0; o < 8; o++)
            if (i - o <= 14) asm("fma.rn.bf16x2 %0, %1, %2, %0;" : "+r"(cv[o]) : "r"(in[i]), "r"(tap[i - o]));
        const uint32_t fl = cw == 0 ? 7 : 0;
        const uint32_t cdst = (stg + cw * 1024 + lane * 4) ^ (fl * 144);
#pragma unroll
        for (int o = 0; o < 8; o++) {
          const float a = bf_lo(cv[o]), c = bf_hi(cv[o]);
          sts32(cdst ^ (o * 144), pack2(fmaf(a, tanh_hw(a), a), fmaf(c, tanh_hw(c), c)));
        }
      }
      if (wg == 1) {
        bar_arrive(BAR_C, 256);
        if (th == 0) ((volatile uint32_t*)sc->epoch)[b] += 1;
        break;
      }
      bar_sync(BAR_C, 256);
      tile_load(here(maddr), A[0]);
      PROF_MARK(15);
      publish(xp + X_AG1, A[0], 1);
      sent = proj_residual<F_PW2, 2>(A, sc, xp, maddr, 1, clock_now());
      PROF_MARK(17);
    }
  }
}

typedef CUresult (*EncodeFn)(CUtensorMap*, CUtensorMapDataType, cuuint32_t, void*, const cuuint64_t*, const cuuint64_t*,
                             const cuuint32_t*, const cuuint32_t*, CUtensorMapInterleave, CUtensorMapSwizzle,
                             CUtensorMapL2promotion, CUtensorMapFloatOOBfill);

void make_map(EncodeFn fn, CUtensorMap* m, const void* w, int rows, int cols, CUtensorMapSwizzle swz) {
  const cuuint64_t dims[2] = {(cuuint64_t)cols, (cuuint64_t)rows}, strides[1] = {(cuuint64_t)cols * 2};
  const cuuint32_t box[2] = {64, 64}, es[2] = {1, 1};
  fn(m, CU_TENSOR_MAP_DATA_TYPE_BFLOAT16, 2, const_cast<void*>(w), dims, strides, box, es, CU_TENSOR_MAP_INTERLEAVE_NONE,
     swz, CU_TENSOR_MAP_L2_PROMOTION_L2_128B, CU_TENSOR_MAP_FLOAT_OOB_FILL_NONE);
}

}

extern "C" void kernel_launch(void* const* d_in, const int* in_sizes, int n_in, void* d_out, int out_size) {
  static EncodeFn fn = nullptr;
  static Scratch* sc = nullptr;
  if (!fn) {
    void* f = nullptr;
    cudaDriverEntryPointQueryResult st;
    cudaGetDriverEntryPoint("cuTensorMapEncodeTiled", &f, cudaEnableDefault, &st);
    fn = (EncodeFn)f;
    void* raw = nullptr;
    cudaGetSymbolAddress(&raw, g_scratch);
    sc = (Scratch*)(((uintptr_t)raw + X_ALIGN - 1) & ~(uintptr_t)(X_ALIGN - 1));
    cudaFuncSetAttribute(conformer_kernel, cudaFuncAttributeMaxDynamicSharedMemorySize, SM_TOTAL);
  }
  typedef const __nv_bfloat16* W;
  const CUtensorMapSwizzle S = CU_TENSOR_MAP_SWIZZLE_128B;
  Params p;
  {
    const cuuint64_t dims[3] = {DM, T_SEQ, 2}, strides[2] = {DM * 2, T_SEQ * DM * 2};
    const cuuint32_t box[3] = {64, 64, 1}, es[3] = {1, 1, 1};
    fn(&p.map[M_X], CU_TENSOR_MAP_DATA_TYPE_BFLOAT16, 3, d_in[0], dims, strides, box, es, CU_TENSOR_MAP_INTERLEAVE_NONE, S,
       CU_TENSOR_MAP_L2_PROMOTION_L2_128B, CU_TENSOR_MAP_FLOAT_OOB_FILL_NONE);
  }
  make_map(fn, &p.map[M_FF1A], d_in[1], 256, 1024, S);
  make_map(fn, &p.map[M_FF1B], d_in[2], 1024, 256, S);
  make_map(fn, &p.map[M_QKV], d_in[3], 256, 768, S);
  make_map(fn, &p.map[M_KV], sc->kv, 16384, 64, CU_TENSOR_MAP_SWIZZLE_NONE);
  make_map(fn, &p.map[M_WO], d_in[4], 256, 256, S);
  make_map(fn, &p.map[M_PW1], d_in[5], 256, 512, S);
  make_map(fn, &p.map[M_PW2], d_in[7], 256, 256, S);
  make_map(fn, &p.map[M_FF2A], d_in[8], 256, 1024, S);
  make_map(fn, &p.map[M_FF2B], d_in[9], 1024, 256, S);
  p.w_ff1b = (W)d_in[2]; p.w_qkv = (W)d_in[3]; p.w_o = (W)d_in[4]; p.w_pw1 = (W)d_in[5];
  p.w_pw2 = (W)d_in[7]; p.w_ff2a = (W)d_in[8]; p.w_ff2b = (W)d_in[9];

  cudaLaunchConfig_t cfg = {};
  cfg.gridDim = dim3(NCTA);
  cfg.blockDim = dim3(384);
  cfg.dynamicSmemBytes = SM_TOTAL;
  cfg.stream = cudaStreamPerThread;
  cudaLaunchAttribute at[1];
  at[0].id = cudaLaunchAttributeCooperative;
  at[0].val.cooperative = 1;
  cfg.attrs = at;
  cfg.numAttrs = 1;
  cudaLaunchKernelEx(&cfg, conformer_kernel, sc, (__nv_bfloat16*)d_out, (W)d_in[6], (W)d_in[0], (W)d_in[1], p);
}
```

```cpp
#include <cuda_runtime.h>
#include <cuda_bf16.h>
#include <cuda.h>
#include <stdint.h>

namespace {

constexpr int T_SEQ = 1000;
constexpr int DM = 256;
constexpr int NCTA = 128;
constexpr int NSTAGE = 12;
constexpr uint32_t STAGE_BYTES = 16384;
constexpr uint32_t TILE_BYTES = 8192;
constexpr uint32_t SM_BASE = 1024;
constexpr uint32_t SM_STG = NSTAGE * STAGE_BYTES;
constexpr uint32_t SM_FULL = SM_STG + 32768;
constexpr uint32_t SM_EMPTY = SM_FULL + 96;
constexpr uint32_t SM_XBAR = SM_FULL + 192;
constexpr uint32_t SM_EYE = SM_FULL + 256;
constexpr uint32_t SM_ONE = SM_FULL + 640;
constexpr uint32_t SM_CS = SM_FULL + 768;
constexpr uint32_t SM_TOTAL = SM_FULL + 3072;
constexpr int CS_FF2 = 0, CS_PW1 = 4, CS_QKV = 6;
constexpr uint32_t SPIN_LIMIT = 1u << 16;
constexpr float LN_EPS = 1e-5f;
constexpr float SM_SCALE_LOG2 = 0.125f * 1.4426950408889634f;
constexpr uint32_t G_PITCH = 144;

constexpr int F_QKV = 16, F_SPARE = 22, F_KV = 24, F_WO = 40, F_PW1 = 42, F_PW2 = 46, F_TOTAL = 64;
enum { M_FF1A, M_FF1B, M_QKV, M_KV, M_WO, M_PW1, M_PW2, M_FF2A, M_FF2B, M_X, M_COUNT };
enum { BAR_K = 1, BAR_V, BAR_Q, BAR_MERGE, BAR_G, BAR_C, BAR_WG1, BAR_RDY, BAR_CS, BAR_ATT, BAR_INIT, BAR_HALF };

struct Params {
  CUtensorMap map[M_COUNT];
  const __nv_bfloat16 *w_ff1b, *w_qkv, *w_o, *w_pw1, *w_pw2, *w_ff2a, *w_ff2b;
};

constexpr int X_RS = 0, X_AG1 = X_RS, X_HALO = X_RS + 512, X_CLEAR = 1024, X_AG0 = 1536, X_ST = 2048, X_SIZE = 4096;
constexpr uint32_t HALO_TAG = 0xFFFF0001u;
struct Scratch {
  uint4 x[NCTA][X_SIZE];
  uint4 kv[8][2][16][512];
  uint4 cs[576];
  uint32_t flag[8][32][32];
  uint32_t ready[NCTA][32];
  uint32_t epoch[NCTA];
};
constexpr size_t X_ALIGN = 4 * X_SIZE * sizeof(uint4);
__device__ uint8_t g_scratch[sizeof(Scratch) + X_ALIGN];
#define PROF_TIME(i)
#define PROF_MARK(i)

__device__ __forceinline__ void mbar_init(uint32_t bar, uint32_t cnt) {
  asm volatile("mbarrier.init.shared::cta.b64 [%0], %1;" :: "r"(bar), "r"(cnt) : "memory");
}
__device__ __forceinline__ void mbar_wait(uint32_t bar, uint32_t parity) {
  asm volatile("{\n.reg .pred p;\n.reg .u32 c;\nmov.u32 c, 0;\n"
               "WAIT_LOOP:\nmbarrier.try_wait.parity.shared::cta.b64 p, [%0], %1;\n@p bra WAIT_DONE;\n"
               "add.u32 c, c, 1;\nsetp.lt.u32 p, c, %2;\n@p bra WAIT_LOOP;\nWAIT_DONE:\n}"
               :: "r"(bar), "r"(parity), "n"(SPIN_LIMIT) : "memory");
}
__device__ __forceinline__ void mbar_arrive(uint32_t bar) {
  asm volatile("mbarrier.arrive.shared::cta.b64 _, [%0];" :: "r"(bar) : "memory");
}
#define bar_sync(id, n) asm volatile("bar.sync %0, %1;" :: "n"((int)(id)), "n"(n) : "memory")
#define bar_arrive(id, n) asm volatile("bar.arrive %0, %1;" :: "n"((int)(id)), "n"(n) : "memory")
__device__ __forceinline__ void fence_async_smem() { asm volatile("fence.proxy.async.shared::cta;" ::: "memory"); }

__device__ __forceinline__ void st_vec(uint4* p, uint32_t a, uint32_t b, uint32_t c, uint32_t d) {
  asm volatile("{\n.reg .b128 v;\n.reg .b64 lo, hi;\nmov.b64 lo, {%1, %2};\nmov.b64 hi, {%3, %4};\nmov.b128 v, {lo, hi};\n"
               "st.relaxed.gpu.global.b128 [%0], v;\n}" :: "l"(p), "r"(a), "r"(b), "r"(c), "r"(d) : "memory");
}
__device__ __forceinline__ void ld_vec(const uint4* p, uint32_t& a, uint32_t& b, uint32_t& c, uint32_t& d) {
  asm volatile("{\n.reg .b128 v;\n.reg .b64 lo, hi;\nld.relaxed.gpu.global.b128 v, [%4];\nmov.b128 {lo, hi}, v;\n"
               "mov.b64 {%0, %1}, lo;\nmov.b64 {%2, %3}, hi;\n}" : "=r"(a), "=r"(b), "=r"(c), "=r"(d) : "l"(p) : "memory");
}
__device__ __forceinline__ void sts128(uint32_t a, uint32_t x, uint32_t y, uint32_t z, uint32_t w) {
  asm volatile("st.shared.v4.u32 [%0], {%1, %2, %3, %4};" :: "r"(a), "r"(x), "r"(y), "r"(z), "r"(w) : "memory");
}
__device__ __forceinline__ void lds128(uint32_t a, uint32_t& x, uint32_t& y, uint32_t& z, uint32_t& w) {
  asm volatile("ld.shared.v4.u32 {%0, %1, %2, %3}, [%4];" : "=r"(x), "=r"(y), "=r"(z), "=r"(w) : "r"(a) : "memory");
}
__device__ __forceinline__ uint32_t lds32(uint32_t a) {
  uint32_t x; asm volatile("ld.shared.u32 %0, [%1];" : "=r"(x) : "r"(a) : "memory"); return x;
}
__device__ __forceinline__ void sts32(uint32_t a, uint32_t x) { asm volatile("st.shared.u32 [%0], %1;" :: "r"(a), "r"(x) : "memory"); }
__device__ __forceinline__ void sts64(uint32_t a, uint32_t x, uint32_t y) {
  asm volatile("st.shared.v2.u32 [%0], {%1, %2};" :: "r"(a), "r"(x), "r"(y) : "memory");
}
__device__ __forceinline__ void stsm4(uint32_t a, const uint32_t* r) {
  asm volatile("stmatrix.sync.aligned.m8n8.x4.shared.b16 [%0], {%1, %2, %3, %4};" :: "r"(a), "r"(r[0]), "r"(r[1]), "r"(r[2]), "r"(r[3]) : "memory");
}
__device__ __forceinline__ void ldsm4(uint32_t a, uint32_t* r) {
  asm volatile("ldmatrix.sync.aligned.m8n8.x4.shared.b16 {%0, %1, %2, %3}, [%4];" : "=r"(r[0]), "=r"(r[1]), "=r"(r[2]), "=r"(r[3]) : "r"(a) : "memory");
}
__device__ __forceinline__ uint32_t pack2(float lo, float hi) {
  uint32_t r; asm("cvt.rn.bf16x2.f32 %0, %1, %2;" : "=r"(r) : "f"(hi), "f"(lo)); return r;
}
__device__ __forceinline__ float bf_lo(uint32_t w) { return __uint_as_float(w << 16); }
__device__ __forceinline__ float bf_hi(uint32_t w) { return __uint_as_float(w & 0xffff0000u); }
__device__ __forceinline__ float tanh_hw(float x) { float y; asm volatile("tanh.approx.f32 %0, %1;" : "=f"(y) : "f"(x)); return y; }
__device__ __forceinline__ float rcp_hw(float x) { float y; asm("rcp.approx.ftz.f32 %0, %1;" : "=f"(y) : "f"(x)); return y; }
__device__ __forceinline__ float ex2_hw(float x) { float y; asm("ex2.approx.ftz.f32 %0, %1;" : "=f"(y) : "f"(x)); return y; }

__device__ __forceinline__ uint32_t here(uint32_t v) { asm volatile("" : "+r"(v)); return v; }

#define SCHED() asm volatile("pmevent 1;" ::: "memory")
#define WG_FENCE() asm volatile("wgmma.fence.sync.aligned;" ::: "memory")
#define WG_COMMIT() asm volatile("wgmma.commit_group.sync.aligned;" ::: "memory")
#define WG_WAIT(n) asm volatile("wgmma.wait_group.sync.aligned %0;" :: "n"(n) : "memory")

template <int N> __device__ __forceinline__ void pin(float (&d)[N]) {
#pragma unroll
  for (int i = 0; i < N; i++) asm volatile("" : "+f"(d[i]) :: "memory");
}
template <int N> __device__ __forceinline__ void pin(uint32_t (&d)[N]) {
#pragma unroll
  for (int i = 0; i < N; i++) asm volatile("" : "+r"(d[i]) :: "memory");
}

#define WG_D32 "{%0, %1, %2, %3, %4, %5, %6, %7, %8, %9, %10, %11, %12, %13, %14, %15, %16, %17, %18, %19, %20, %21, %22, %23, %24, %25, %26, %27, %28, %29, %30, %31}"
template <int TB> __device__ __forceinline__ void wgmma64_acc(float (&d)[32], const uint32_t* a, uint64_t db) {
  asm volatile("wgmma.mma_async.sync.aligned.m64n64k16.f32.bf16.bf16 " WG_D32 ", {%32, %33, %34, %35}, %36, 1, 1, 1, %37;"
    : "+f"(d[0]), "+f"(d[1]), "+f"(d[2]), "+f"(d[3]), "+f"(d[4]), "+f"(d[5]), "+f"(d[6]), "+f"(d[7]),
      "+f"(d[8]), "+f"(d[9]), "+f"(d[10]), "+f"(d[11]), "+f"(d[12]), "+f"(d[13]), "+f"(d[14]), "+f"(d[15]),
      "+f"(d[16]), "+f"(d[17]), "+f"(d[18]), "+f"(d[19]), "+f"(d[20]), "+f"(d[21]), "+f"(d[22]), "+f"(d[23]),
      "+f"(d[24]), "+f"(d[25]), "+f"(d[26]), "+f"(d[27]), "+f"(d[28]), "+f"(d[29]), "+f"(d[30]), "+f"(d[31])
    : "r"(a[0]), "r"(a[1]), "r"(a[2]), "r"(a[3]), "l"(db), "n"(TB));
}
__device__ __forceinline__ void wgmma64_reuse(float (&d)[32], const uint32_t* a, uint64_t db, uint32_t zero) {
  asm volatile("{\n.reg .pred p;\nsetp.ne.u32 p, %37, 0;\nwgmma.mma_async.sync.aligned.m64n64k16.f32.bf16.bf16 " WG_D32 ", {%32, %33, %34, %35}, %36, p, 1, 1, 1;\n}"
    : "+f"(d[0]), "+f"(d[1]), "+f"(d[2]), "+f"(d[3]), "+f"(d[4]), "+f"(d[5]), "+f"(d[6]), "+f"(d[7]),
      "+f"(d[8]), "+f"(d[9]), "+f"(d[10]), "+f"(d[11]), "+f"(d[12]), "+f"(d[13]), "+f"(d[14]), "+f"(d[15]),
      "+f"(d[16]), "+f"(d[17]), "+f"(d[18]), "+f"(d[19]), "+f"(d[20]), "+f"(d[21]), "+f"(d[22]), "+f"(d[23]),
      "+f"(d[24]), "+f"(d[25]), "+f"(d[26]), "+f"(d[27]), "+f"(d[28]), "+f"(d[29]), "+f"(d[30]), "+f"(d[31])
    : "r"(a[0]), "r"(a[1]), "r"(a[2]), "r"(a[3]), "l"(db), "r"(zero));
}
template <int TB> __device__ __forceinline__ void wgmma64_set(float (&d)[32], const uint32_t* a, uint64_t db) {
  asm volatile("wgmma.mma_async.sync.aligned.m64n64k16.f32.bf16.bf16 " WG_D32 ", {%32, %33, %34, %35}, %36, 0, 1, 1, %37;"
    : "=f"(d[0]), "=f"(d[1]), "=f"(d[2]), "=f"(d[3]), "=f"(d[4]), "=f"(d[5]), "=f"(d[6]), "=f"(d[7]),
      "=f"(d[8]), "=f"(d[9]), "=f"(d[10]), "=f"(d[11]), "=f"(d[12]), "=f"(d[13]), "=f"(d[14]), "=f"(d[15]),
      "=f"(d[16]), "=f"(d[17]), "=f"(d[18]), "=f"(d[19]), "=f"(d[20]), "=f"(d[21]), "=f"(d[22]), "=f"(d[23]),
      "=f"(d[24]), "=f"(d[25]), "=f"(d[26]), "=f"(d[27]), "=f"(d[28]), "=f"(d[29]), "=f"(d[30]), "=f"(d[31])
    : "r"(a[0]), "r"(a[1]), "r"(a[2]), "r"(a[3]), "l"(db), "n"(TB));
}

__device__ __forceinline__ void wgmma72_acc(float (&d)[36], const uint32_t* a, uint64_t db) {
  asm volatile("wgmma.mma_async.sync.aligned.m64n72k16.f32.bf16.bf16 {%0, %1, %2, %3, %4, %5, %6, %7, %8, %9, %10, %11, %12, %13, %14, %15, %16, %17, %18, %19, %20, %21, %22, %23, %24, %25, %26, %27, %28, %29, %30, %31, %32, %33, %34, %35}, {%36, %37, %38, %39}, %40, 1, 1, 1, 1;"
    : "+f"(d[0]), "+f"(d[1]), "+f"(d[2]), "+f"(d[3]), "+f"(d[4]), "+f"(d[5]), "+f"(d[6]), "+f"(d[7]), "+f"(d[8]),
      "+f"(d[9]), "+f"(d[10]), "+f"(d[11]), "+f"(d[12]), "+f"(d[13]), "+f"(d[14]), "+f"(d[15]), "+f"(d[16]), "+f"(d[17]),
      "+f"(d[18]), "+f"(d[19]), "+f"(d[20]), "+f"(d[21]), "+f"(d[22]), "+f"(d[23]), "+f"(d[24]), "+f"(d[25]), "+f"(d[26]),
      "+f"(d[27]), "+f"(d[28]), "+f"(d[29]), "+f"(d[30]), "+f"(d[31]), "+f"(d[32]), "+f"(d[33]), "+f"(d[34]), "+f"(d[35])
    : "r"(a[0]), "r"(a[1]), "r"(a[2]), "r"(a[3]), "l"(db));
}
__device__ __forceinline__ void wgmma16_acc(float* d, const uint32_t* a, uint64_t db) {
  asm volatile("wgmma.mma_async.sync.aligned.m64n16k16.f32.bf16.bf16 {%0, %1, %2, %3, %4, %5, %6, %7}, {%8, %9, %10, %11}, %12, 1, 1, 1, 0;"
    : "+f"(d[0]), "+f"(d[1]), "+f"(d[2]), "+f"(d[3]), "+f"(d[4]), "+f"(d[5]), "+f"(d[6]), "+f"(d[7])
    : "r"(a[0]), "r"(a[1]), "r"(a[2]), "r"(a[3]), "l"(db));
}
__device__ __forceinline__ void hmma(float (&d)[4], const uint32_t* a, uint32_t b0, uint32_t b1) {
  asm("mma.sync.aligned.m16n8k16.row.col.f32.bf16.bf16.f32 {%0, %1, %2, %3}, {%4, %5, %6, %7}, {%8, %9}, {%0, %1, %2, %3};"
    : "+f"(d[0]), "+f"(d[1]), "+f"(d[2]), "+f"(d[3]) : "r"(a[0]), "r"(a[1]), "r"(a[2]), "r"(a[3]), "r"(b0), "r"(b1));
}

__device__ __forceinline__ void hmma8(float (&d)[4], const uint32_t* a, uint32_t b0) {
  asm("mma.sync.aligned.m16n8k8.row.col.f32.bf16.bf16.f32 {%0, %1, %2, %3}, {%4, %5}, {%6}, {%0, %1, %2, %3};"
    : "+f"(d[0]), "+f"(d[1]), "+f"(d[2]), "+f"(d[3]) : "r"(a[0]), "r"(a[1]), "r"(b0));
}

template <bool FIRST> __device__ __forceinline__ void mma_tile(float (&d)[32], const uint32_t (&a)[16], uint64_t db) {
  WG_FENCE();
#pragma unroll
  for (int s = 0; s < 4; s++) {
    if (FIRST && s == 0) wgmma64_set<1>(d, &a[0], db); else wgmma64_acc<1>(d, &a[4 * s], db + s * 128);
  }
  WG_COMMIT();
}
__device__ __forceinline__ void mma_tile_reuse(float (&d)[32], const uint32_t (&a)[16], uint64_t db) {
  WG_FENCE();
  wgmma64_reuse(d, &a[0], db, blockIdx.y);
#pragma unroll
  for (int s = 1; s < 4; s++) wgmma64_acc<1>(d, &a[4 * s], db + s * 128);
  WG_COMMIT();
}
template <int ROW> __device__ __forceinline__ void fold_step(float (&d)[32], const uint32_t (&mu)[4]) {
  wgmma64_acc<1>(d, mu, (uint64_t)((SM_BASE + SM_CS + ROW * 128) >> 4) | (uint64_t(1) << 16) | (uint64_t(1) << 62));
}
template <int ROW> __device__ __forceinline__ void mma_fold(float (&d)[32], const uint32_t (&mu)[4]) {
  WG_FENCE();
  fold_step<ROW>(d, mu);
  WG_COMMIT();
}
template <int ROW> __device__ __forceinline__ void mma_tile_fold(float (&d)[32], const uint32_t (&a)[16], uint64_t db, const uint32_t (&mu)[4]) {
  WG_FENCE();
#pragma unroll
  for (int s = 0; s < 4; s++) wgmma64_acc<1>(d, &a[4 * s], db + s * 128);
  fold_step<ROW>(d, mu);
  WG_COMMIT();
}
__device__ __forceinline__ void mma_add_half(float (&d)[32], const uint32_t (&a)[16]) {
  const uint64_t db = (uint64_t)((SM_BASE + SM_EYE) >> 4) | (uint64_t(8) << 16) | (uint64_t(8) << 32);
  WG_FENCE();
#pragma unroll
  for (int s = 0; s < 4; s++) wgmma16_acc(&d[8 * s], &a[4 * s], db);
  WG_COMMIT();
}
#define ACQUIRE(f) mbar_wait(SM_BASE + SM_FULL + ((f) % NSTAGE) * 8, ((f) / NSTAGE) & 1)
template <int F, int N> __device__ __forceinline__ uint32_t probe_n() {
  static_assert(F % NSTAGE + N <= NSTAGE, "stages must not wrap");
  uint32_t ok = 1;
#pragma unroll
  for (int i = 0; i < N; i++)
    asm volatile("{\n.reg .pred p;\nmbarrier.test_wait.parity.shared::cta.b64 p, [%1], %2;\nselp.u32 %0, %0, 0, p;\n}"
                 : "+r"(ok) : "r"(SM_BASE + SM_FULL + (F % NSTAGE + i) * 8), "r"((F / NSTAGE) & 1) : "memory");
  return ok;
}
template <int F, int N> __device__ __forceinline__ void settle_n(uint32_t ok) {
  if (__builtin_expect(!ok, 0)) {
#pragma unroll 1
    for (int i = 0; i < N; i++) mbar_wait(SM_BASE + SM_FULL + (F % NSTAGE + i) * 8, (F / NSTAGE) & 1);
  }
}
template <int F, int N> __device__ __forceinline__ void acquire_n() { settle_n<F, N>(probe_n<F, N>()); }
#define RELEASE(f0, f1) do { if (lane == 0) { _Pragma("unroll") for (int f_ = (f0); f_ <= (f1); f_++) mbar_arrive(SM_BASE + SM_EMPTY + (f_ % NSTAGE) * 8); } } while (0)
constexpr uint64_t RING = (uint64_t)(SM_BASE >> 4) | (uint64_t(1) << 16) | (uint64_t(64) << 32) | (uint64_t(1) << 62);
#define LO(f) (RING + ((f) % NSTAGE) * 1024)
#define HI(f) (RING + ((f) % NSTAGE) * 1024 + 512)

template <int C> __device__ __forceinline__ uint4* peer(uint4* p) {
  asm volatile("" : "+l"(p));
  return (uint4*)((uintptr_t)p ^ (C * X_SIZE * sizeof(uint4)));
}
__device__ __forceinline__ uint32_t clock_now() { uint32_t c; asm volatile("mov.u32 %0, %%clock;" : "=r"(c) :: "memory"); return c; }
__device__ __forceinline__ void publish(uint4* dst, uint32_t (&a)[16], uint32_t tag) {
#pragma unroll
  for (int s = 0; s < 4; s++) a[4 * s] = (a[4 * s] & ~1u) | tag;
  pin(a);
  SCHED();
#pragma unroll
  for (int s = 0; s < 4; s++) st_vec(dst + s * 128, a[4 * s], a[4 * s + 1], a[4 * s + 2], a[4 * s + 3]);
  SCHED();
}
__device__ __forceinline__ void fetch(const uint4* src, uint32_t (&a)[16]) {
#pragma unroll
  for (int s = 0; s < 4; s++) ld_vec(src + s * 128, a[4 * s], a[4 * s + 1], a[4 * s + 2], a[4 * s + 3]);
}
__device__ __forceinline__ uint32_t miss(const uint32_t (&a)[16], uint32_t tag) {
  return (a[0] ^ tag) | (a[4] ^ tag) | (a[8] ^ tag) | (a[12] ^ tag);
}
__device__ __forceinline__ bool stale(uint32_t v) { return __any_sync(0xffffffffu, here(v) & 1u); }
__device__ __forceinline__ void confirm(const uint4* src, uint32_t (&a)[16], uint32_t tag) {
  uint32_t spin = 0;
  while (__builtin_expect(stale(miss(a, tag)), 0) && ++spin < SPIN_LIMIT) fetch(src, a);
}
constexpr uint32_t GATHER_DELAY = 400;
__device__ __forceinline__ void stat_fetch(const Scratch* sc, uint32_t (&st)[4]) {
  const uint32_t th = here(threadIdx.x);
  ld_vec(&sc->x[(blockIdx.x & ~3u) + (th & 3)][X_ST + (th >> 2)], st[0], st[1], st[2], st[3]);
}
template <int C, int SLOT> __device__ __forceinline__ void gather_first(uint32_t (&A)[4][16], uint32_t (&st)[4], const Scratch* sc, uint4* xp,
                                                                        uint32_t tag, uint32_t sent) {
  while (clock_now() - sent < GATHER_DELAY) {}
  fetch(peer<1>(xp) + SLOT, A[1]); fetch(peer<2>(xp) + SLOT, A[2]); fetch(peer<3>(xp) + SLOT, A[3]);
  if (SLOT == X_AG0) stat_fetch(sc, st);
  uint32_t spin = 0;
  while (__builtin_expect(stale(miss(A[1], tag) | miss(A[C], tag)), 0) && ++spin < SPIN_LIMIT) {
    fetch(peer<1>(xp) + SLOT, A[1]);
    if (C == 2) fetch(peer<2>(xp) + SLOT, A[2]);
  }
}
template <int C, int SLOT> __device__ __forceinline__ void gather_rest(uint32_t (&A)[4][16], uint4* xp, uint32_t tag) {
  SCHED();
  uint32_t spin = 0;
  while (__builtin_expect(stale(miss(A[C + 1], tag) | miss(A[3], tag)), 0) && ++spin < SPIN_LIMIT) {
    if (C == 1) fetch(peer<2>(xp) + SLOT, A[2]);
    fetch(peer<3>(xp) + SLOT, A[3]);
  }
}
__device__ __forceinline__ void pack_acc(const float (&d)[32], uint32_t (&a)[16]) {
#pragma unroll
  for (int i = 0; i < 16; i++) a[i] = pack2(d[2 * i], d[2 * i + 1]);
}
__device__ __forceinline__ void frag_store(uint32_t slot, const uint32_t (&a)[16]) {
#pragma unroll
  for (int s = 0; s < 4; s++) sts128(slot + s * 512, a[4 * s], a[4 * s + 1], a[4 * s + 2], a[4 * s + 3]);
}
__device__ __forceinline__ void tile_store(uint32_t maddr, const uint32_t (&a)[16]) {
#pragma unroll
  for (int s = 0; s < 4; s++) stsm4(maddr ^ (s << 5), &a[4 * s]);
}
__device__ __forceinline__ void tile_load(uint32_t maddr, uint32_t (&a)[16]) {
#pragma unroll
  for (int s = 0; s < 4; s++) ldsm4(maddr ^ (s << 5), &a[4 * s]);
}

__device__ __forceinline__ void res_load(uint32_t maddr, float (&d)[32]) {
  uint32_t a[16];
  tile_load(here(maddr) + 3 * TILE_BYTES, a);
#pragma unroll
  for (int i = 0; i < 16; i++) { d[2 * i] = bf_lo(a[i]); d[2 * i + 1] = bf_hi(a[i]); }
  pin(d);
}

struct RowAcc { float s[4], u[2][4], v[2][4]; };
__device__ __forceinline__ void row_acc(RowAcc& t, const uint32_t (&a)[16]) {
#pragma unroll
  for (int s = 0; s < 8; s++) {
    if ((s & 1) == 0) hmma(t.s, &a[2 * s], 0x3F803F80u, 0x3F803F80u);
    hmma8(t.u[s & 1], &a[2 * s], a[2 * s]);
    hmma8(t.v[s & 1], &a[2 * s], a[2 * s + 1]);
  }
}
__device__ __forceinline__ float2 row_squares(const RowAcc& t, bool odd) {
  return make_float2(odd ? t.u[0][1] + t.u[1][1] : t.u[0][0] + t.u[1][0], odd ? t.v[0][3] + t.v[1][3] : t.v[0][2] + t.v[1][2]);
}
__device__ __forceinline__ void stat_publish(const uint32_t (&a)[16], Scratch* sc, uint32_t th, uint32_t tag) {
  RowAcc t = {};
  row_acc(t, a);
  const float2 q = row_squares(t, th & 4);
  if ((th & 3) == ((th >> 3) & 3))
    st_vec(&sc->x[blockIdx.x][X_ST + (th >> 2)], (__float_as_uint(t.s[0]) & ~1u) | tag, __float_as_uint(q.x), __float_as_uint(t.s[2]), __float_as_uint(q.y));
}
struct RowNorm { float m0, rs0, m1, rs1; };
__device__ __forceinline__ RowNorm row_norm(float s0, float q0, float s1, float q1, float scale) {
  RowNorm n;
  n.m0 = s0 * (1.f / DM); n.m1 = s1 * (1.f / DM);
  n.rs0 = scale * rsqrtf(fmaxf(fmaf(-n.m0, n.m0, q0 * (1.f / DM)), 0.f) + LN_EPS);
  n.rs1 = scale * rsqrtf(fmaxf(fmaf(-n.m1, n.m1, q1 * (1.f / DM)), 0.f) + LN_EPS);
  return n;
}
__device__ __forceinline__ RowNorm stat_finish(const Scratch* sc, uint32_t (&st)[4], uint32_t tag, float scale) {
  uint32_t spin = 0;
  while (__builtin_expect(stale(st[0] ^ tag), 0) && ++spin < SPIN_LIMIT) stat_fetch(sc, st);
  float f[4];
#pragma unroll
  for (int i = 0; i < 4; i++) {
    f[i] = __uint_as_float(st[i]);
    f[i] += __shfl_xor_sync(0xffffffffu, f[i], 1);
    f[i] += __shfl_xor_sync(0xffffffffu, f[i], 2);
  }
  return row_norm(f[0], f[1], f[2], f[3], scale);
}
__device__ __forceinline__ void mean_frag(uint32_t (&mu)[4], const RowNorm& n, bool sel) {
  const float a = sel ? -n.m0 : 0.f, c = sel ? -n.m1 : 0.f;
  mu[0] = pack2(a, a); mu[1] = pack2(c, c);
  const float al = a - bf_lo(mu[0]), cl = c - bf_lo(mu[1]);
  mu[2] = pack2(al, al); mu[3] = pack2(cl, cl);
  pin(mu);
}
__device__ __forceinline__ void centre(uint32_t (&a)[16], uint32_t m0, uint32_t m1) {
#pragma unroll
  for (int i = 0; i < 16; i++) asm("sub.rn.bf16x2 %0, %0, %1;" : "+r"(a[i]) : "r"((i & 1) ? m1 : m0));
  pin(a);
}
__device__ __forceinline__ void scale_pack(const float (&d)[32], uint32_t (&a)[16], float rs0, float rs1) {
#pragma unroll
  for (int i = 0; i < 16; i++) { const float rs = (i & 1) ? rs1 : rs0; a[i] = pack2(d[2 * i] * rs, d[2 * i + 1] * rs); }
}
template <int S> __device__ __forceinline__ void silu_seg(float (&acc)[4][32], float (&tn)[2][4], uint32_t (&H)[4][16], float rs0, float rs1) {
  if (S >= 2) {
    const float* h = &acc[(S - 2) >> 3][4 * ((S - 2) & 7)];
    const float* v = tn[S & 1];
    uint32_t* o = &H[(S - 2) >> 3][2 * ((S - 2) & 7)];
    o[0] = pack2(fmaf(h[0], v[0], h[0]), fmaf(h[1], v[1], h[1]));
    o[1] = pack2(fmaf(h[2], v[2], h[2]), fmaf(h[3], v[3], h[3]));
    asm volatile("" : "+r"(o[0]), "+r"(o[1]));
  }
  if (S >= 1 && S <= 32) {
#pragma unroll
    for (int k = 0; k < 4; k++) tn[(S - 1) & 1][k] = tanh_hw(acc[((S - 1) >> 3) & 3][4 * ((S - 1) & 7) + k]);
  }
  if (S < 32) {
    float* h = &acc[(S >> 3) & 3][4 * (S & 7)];
    h[0] *= rs0; h[1] *= rs0; h[2] *= rs1; h[3] *= rs1;
    asm volatile("" : "+f"(h[0]), "+f"(h[1]), "+f"(h[2]), "+f"(h[3]));
  }
  SCHED();
}
template <int S0, int S1> __device__ __forceinline__ void silu_segs(float (&acc)[4][32], float (&tn)[2][4], uint32_t (&H)[4][16], float rs0, float rs1) {
  silu_seg<S0>(acc, tn, H, rs0, rs1);
  if constexpr (S0 + 1 < S1) silu_segs<S0 + 1, S1>(acc, tn, H, rs0, rs1);
}
template <int HALF> __device__ __forceinline__ void send_half(uint4* dst, const float (&d)[32], uint32_t tag) {
  uint32_t o[8];
#pragma unroll
  for (int i = 0; i < 8; i++) o[i] = pack2(d[16 * HALF + 2 * i], d[16 * HALF + 2 * i + 1]);
  o[0] = (o[0] & ~1u) | tag; o[4] = (o[4] & ~1u) | tag;
  pin(o);
  SCHED();
  st_vec(dst + HALF * 256, o[0], o[1], o[2], o[3]);
  st_vec(dst + HALF * 256 + 128, o[4], o[5], o[6], o[7]);
  SCHED();
}
__device__ __forceinline__ uint32_t send_residual(uint32_t (&a)[16], Scratch* sc, uint4* xp, uint32_t maddr, uint32_t tag) {
  const uint32_t exact[4] = {a[0], a[4], a[8], a[12]};
  publish(xp + X_AG0, a, tag);
  const uint32_t sent = clock_now();
  const uint32_t th = here(threadIdx.x);
  stat_publish(a, sc, th, tag);
  tile_store(here(maddr) + 3 * TILE_BYTES, a);
  stsm4(SM_BASE + SM_STG + 3 * TILE_BYTES + (th >> 5) * 2048 + (th & 7) * 128 + ((((th >> 2) & 6) ^ (th & 7)) << 4), exact);
  return sent;
}
template <int F, int N> __device__ __forceinline__ uint32_t proj_residual(uint32_t (&A)[4][16], Scratch* sc, uint4* xp, uint32_t maddr,
                                                                          uint32_t tag, uint32_t sent) {
  float acc[32];
  uint32_t st[4];
  acquire_n<F, N>();
  if (F == F_PW2) acquire_n<0, 5>();
  res_load(maddr, acc);
  mma_tile<false>(acc, A[0], LO(F));
  gather_first<2, X_AG1>(A, st, sc, xp, tag, sent);
  mma_tile<false>(acc, A[1], HI(F));
  mma_tile<false>(acc, A[2], LO(F + 1));
  gather_rest<2, X_AG1>(A, xp, tag);
  PROF_MARK(F == F_WO ? 11 : 16);
  mma_tile<false>(acc, A[3], HI(F + 1));
  WG_WAIT(0); pin(acc);
  pack_acc(acc, A[0]);
  return send_residual(A[0], sc, xp, maddr, tag);
}

__device__ __forceinline__ void qk_tile(float (&S)[32], const uint32_t (&Q)[16], uint64_t dk) {
#pragma unroll
  for (int s = 0; s < 4; s++) {
    if (s == 0) wgmma64_set<0>(S, &Q[0], dk); else wgmma64_acc<0>(S, &Q[4 * s], dk + s * 2);
  }
}
__device__ __forceinline__ void qk_shift(float (&S)[32], const uint32_t (&nm)[4]) { wgmma64_acc<0>(S, nm, (uint64_t)((SM_BASE + SM_ONE) >> 4)); }
constexpr uint64_t V_STEP = uint64_t(1) - (uint64_t(1) << 16);
constexpr uint64_t RING_V = RING - (uint64_t(1) << 16) + ((uint64_t)((SM_STG + 2 * TILE_BYTES) >> 4) << 16);
__device__ __forceinline__ void pv_tile(float (&O)[36], const uint32_t (&P)[16], uint64_t dv, uint64_t pad) {
#pragma unroll
  for (int s = 0; s < 4; s++) wgmma72_acc(O, &P[4 * s], dv + s * 128 * V_STEP + (s < 2 ? 0 : (s - 1) * pad));
}
__device__ __forceinline__ void attn_step(const float (&Sc)[32], float (&Sn)[32], uint32_t (&Pc)[16], uint32_t (&Pp)[16], float (&O)[36],
                                          const uint32_t (&Q)[16], const uint32_t (&nm)[4], uint64_t dk, uint64_t dv) {
  WG_FENCE();
  qk_tile(Sn, Q, dk);
  qk_shift(Sn, nm);
  pv_tile(O, Pp, dv, 0);
  WG_COMMIT();
  SCHED();
#pragma unroll
  for (int i = 0; i < 16; i++) Pc[i] = pack2(ex2_hw(Sc[2 * i]), ex2_hw(Sc[2 * i + 1]));
  pin(Pc);
  SCHED();
}
template <int R> __device__ __forceinline__ float tile_max(const float (&S)[32]) {
  float t[4];
#pragma unroll
  for (int j = 0; j < 4; j++) t[j] = fmaxf(fmaxf(S[8 * j + R], S[8 * j + R + 1]), fmaxf(S[8 * j + R + 4], S[8 * j + R + 5]));
  float n = fmaxf(fmaxf(t[0], t[1]), fmaxf(t[2], t[3]));
  n = fmaxf(n, __shfl_xor_sync(0xffffffffu, n, 1));
  return fmaxf(n, __shfl_xor_sync(0xffffffffu, n, 2));
}
__device__ __forceinline__ void attention_exact(float (&O)[36], const uint32_t (&Q)[16], const Scratch* sc, int bh, int lane, int half) {
  const char* kb = (const char*)&sc->kv[bh][0][0][0];
  const char* vb = (const char*)&sc->kv[bh][1][0][0];
  const int g = lane >> 2, q = lane & 3;
  float m0 = -INFINITY, m1 = -INFINITY, l0 = 0.f, l1 = 0.f;
  float o[4][4] = {};
#pragma unroll 1
  for (int k0 = 0; k0 < T_SEQ; k0 += 8) {
    float s[4] = {0.f, 0.f, 0.f, 0.f};
#pragma unroll
    for (int c = 0; c < 8; c++) hmma8(s, &Q[2 * c], __ldcg((const uint32_t*)(kb + (k0 + g) * 128 + ((c ^ g) << 4) + q * 4)));
    float n0 = fmaxf(s[0], s[1]), n1 = fmaxf(s[2], s[3]);
    n0 = fmaxf(n0, __shfl_xor_sync(0xffffffffu, n0, 1)); n1 = fmaxf(n1, __shfl_xor_sync(0xffffffffu, n1, 1));
    n0 = fmaxf(m0, fmaxf(n0, __shfl_xor_sync(0xffffffffu, n0, 2))); n1 = fmaxf(m1, fmaxf(n1, __shfl_xor_sync(0xffffffffu, n1, 2)));
    const float a0 = ex2_hw(m0 - n0), a1 = ex2_hw(m1 - n1);
    m0 = n0; m1 = n1;
    const uint32_t pp[2] = {pack2(ex2_hw(s[0] - n0), ex2_hw(s[1] - n0)), pack2(ex2_hw(s[2] - n1), ex2_hw(s[3] - n1))};
    l0 = fmaf(l0, a0, bf_lo(pp[0]) + bf_hi(pp[0])); l1 = fmaf(l1, a1, bf_lo(pp[1]) + bf_hi(pp[1]));
#pragma unroll
    for (int j = 0; j < 4; j++) {
      const int c = 4 * half + j;
      const uint32_t v0 = __ldcg((const uint16_t*)(vb + (k0 + 2 * q) * 128 + ((c ^ (2 * q)) << 4) + g * 2));
      const uint32_t v1 = __ldcg((const uint16_t*)(vb + (k0 + 2 * q + 1) * 128 + ((c ^ (2 * q + 1)) << 4) + g * 2));
      o[j][0] *= a0; o[j][1] *= a0; o[j][2] *= a1; o[j][3] *= a1;
      hmma8(o[j], pp, v0 | (v1 << 16));
    }
  }
  l0 += __shfl_xor_sync(0xffffffffu, l0, 1); l1 += __shfl_xor_sync(0xffffffffu, l1, 1);
  O[32] = l0 + __shfl_xor_sync(0xffffffffu, l0, 2); O[34] = l1 + __shfl_xor_sync(0xffffffffu, l1, 2);
#pragma unroll
  for (int i = 0; i < 16; i++) O[i] = o[i >> 2][i & 3];
}

__device__ __forceinline__ uint32_t fill_entry(int f, int r, int bh) {
  int m, x = r, y, dx = 0;
  if (f < F_QKV || f >= 48) {
    const int i = f & 15;
    m = f < F_QKV ? M_FF1A : M_FF2A;
    if (i < 8) { x = 4 * r + ((0xE2u >> i) & 1) * 2; y = r ^ ((0xE790u >> (2 * i)) & 3); dx = 1; }
    else { m++; x = r ^ (((i >> 1) - 3) & 3); y = 4 * r + 2 * (i & 1); }
  } else if (f < F_KV) {
    const int i = f - F_QKV;
    m = M_QKV;
    if (i == 1 || i >= 5) { y = r ^ (i == 1 ? 0 : 2); }
    else { x = 4 + r; y = r ^ (i ? i - 1 : 0); dx = 4; }
  } else if (f < F_WO) {
    const int i = f - F_KV;
    m = M_KV; x = 0; y = bh * 32 + (i & 2) * 8 + (i >> 2) * 4 + (i & 1) * 2;
  } else if (f >= F_PW1 && f < F_PW2) {
    m = M_PW1; y = r ^ (f - F_PW1); dx = 4;
  } else {
    m = f < F_PW1 ? M_WO : M_PW2; y = r ^ ((f & 1) * 2);
  }
  return m | (x << 4) | (y << 8) | (dx << 16);
}
__device__ __forceinline__ void tma_fill(uint32_t st, const CUtensorMap* map, uint32_t x, uint32_t y, uint32_t x2, uint32_t y2) {
  asm volatile("{\n.reg .pred p;\nelect.sync _|p, 0xffffffff;\n"
               "@p mbarrier.arrive.expect_tx.shared::cta.b64 _, [%1], 16384;\n"
               "@p cp.async.bulk.tensor.2d.shared::cluster.global.mbarrier::complete_tx::bytes [%0], [%2, {%3, %4}], [%1];\n"
               "@p cp.async.bulk.tensor.2d.shared::cluster.global.mbarrier::complete_tx::bytes [%0 + 8192], [%2, {%5, %6}], [%1];\n}"
               :: "r"(SM_BASE + st * STAGE_BYTES), "r"(SM_BASE + SM_FULL + st * 8), "l"(map), "r"(x), "r"(y), "r"(x2), "r"(y2) : "memory");
}
__device__ __forceinline__ void l2_prefetch(const void* p, uint32_t total, int b) {
  const uint32_t part = total / NCTA;
  asm volatile("cp.async.bulk.prefetch.L2.global [%0], %1;" :: "l"((const char*)p + (size_t)b * part), "r"(part) : "memory");
}

__global__ void __launch_bounds__(384, 1) conformer_kernel(Scratch* __restrict__ sc, __nv_bfloat16* __restrict__ out,
                                                           const __nv_bfloat16* __restrict__ dw, const __nv_bfloat16* __restrict__ xin,
                                                           const __nv_bfloat16* __restrict__ w_ff1a, const __grid_constant__ Params p) {
  extern __shared__ __align__(1024) uint8_t smem[];
  const int tid = threadIdx.x, lane = tid & 31;
  if (tid == 0) {
    l2_prefetch(xin, 2 * T_SEQ * DM * 2, blockIdx.x);
    l2_prefetch(w_ff1a, 256 * 1024 * 2, blockIdx.x);
  }
  const int cw = __shfl_sync(0xffffffffu, tid >> 5, 0), wg = cw >> 2, w = cw & 3;
  const int b = blockIdx.x, r = b & 3, batch = b >> 6, t = (b >> 2) & 15;
  if ((uint32_t)__cvta_generic_to_shared(smem) != SM_BASE) return;
  PROF_MARK(0);
  PROF_TIME(30);

  if (wg == 2) {
    asm volatile("setmaxnreg.dec.sync.aligned.u32 40;");
    if (cw == 8) {
      if (lane == 0) {
        asm volatile("prefetch.tensormap [%0];" :: "l"(&p.map[M_X]) : "memory");
        asm volatile("prefetch.tensormap [%0];" :: "l"(&p.map[M_FF1A]) : "memory");
        mbar_init(SM_BASE + SM_XBAR, 4);
#pragma unroll
        for (int i = 0; i < NSTAGE; i++) mbar_init(SM_BASE + SM_FULL + i * 8, 1);
        fence_async_smem();
      }
      __syncwarp();
      bar_arrive(0, 320);
      PROF_MARK(9);
#pragma unroll
      for (int f = 0; f < 8; f++) {
        const uint32_t x = 256 * r + ((0xE2u >> f) & 1) * 128, y = (r ^ ((0xE790u >> (2 * f)) & 3)) * 64;
#pragma unroll
        for (int c = 0; c < (f == 0 ? 4 : 0); c++)
          asm volatile("{\n.reg .pred p;\nelect.sync _|p, 0xffffffff;\n"
                       "@p mbarrier.arrive.expect_tx.shared::cta.b64 _, [%1], 8192;\n"
                       "@p cp.async.bulk.tensor.3d.shared::cluster.global.mbarrier::complete_tx::bytes [%0], [%2, {%3, %4, %5}], [%1];\n}"
                       :: "r"(SM_BASE + SM_STG + (3 - c) * TILE_BYTES), "r"(SM_BASE + SM_XBAR), "l"(&p.map[M_X]),
                          "r"((r ^ c) * 64), "r"(t * 64), "r"(batch) : "memory");
        tma_fill(f, &p.map[M_FF1A], x, y, x + 64, y);
      }
      PROF_MARK(1);
      const uint32_t* flag = sc->flag[batch * 4 + r][lane];
      const uint32_t prev = ((volatile uint32_t*)sc->epoch)[b];
      uint32_t entry[2], ready = 0, st = 8, parity = 1;
#pragma unroll 1
      for (int i = 0; i < 2; i++) { entry[1] = fill_entry(i * 32 + lane, r, batch * 4 + r); if (i == 0) entry[0] = entry[1]; }
      bar_sync(BAR_INIT, 64);
#pragma unroll 1
      for (int f = 8; f < F_TOTAL; f++) {
        const uint32_t e = __shfl_sync(0xffffffffu, f < 32 ? entry[0] : entry[1], f);
        if ((e & 15) == M_KV) {
          const uint32_t need = 3u << ((e >> 8) & 31);
          uint32_t spin = 0;
#pragma unroll 1
          while ((ready & need) != need && ++spin < SPIN_LIMIT) {
            uint32_t v;
            asm volatile("ld.relaxed.gpu.global.u32 %0, [%1];" : "=r"(v) : "l"(flag) : "memory");
            ready = __ballot_sync(0xffffffffu, v - 1 == prev);
          }
        }
        if (f == F_KV) PROF_MARK(8);
        mbar_wait(SM_BASE + SM_EMPTY + st * 8, parity);
        const uint32_t x = (e << 2) & 0x3C0, y = (e >> 2) & 0x3FC0, dx = (e >> 16) << 6;
        tma_fill(st, &p.map[e & 15], x, y, x + dx, dx ? y : y ^ 64);
        if (++st == NSTAGE) { st = 0; parity ^= 1; }
      }
    } else if (here(cw) != 11) {
      const int kind = w - 1;
      const uint32_t prev = ((volatile uint32_t*)sc->epoch)[b];
      if (kind == 0) {
        if (lane == 0) {
#pragma unroll
          for (int i = 0; i < NSTAGE; i++) mbar_init(SM_BASE + SM_EMPTY + i * 8, 4);
        }
        __syncwarp();
        bar_arrive(0, 320);
        bar_arrive(BAR_INIT, 64);
        bar_sync(BAR_K, 160);
      } else {
        uint32_t v, spin = 0;
#pragma unroll 1
        do {
          asm volatile("ld.relaxed.gpu.global.u32 %0, [%1];" : "=r"(v) : "l"(sc->ready[(b & ~3) + (lane & 3)]) : "memory");
        } while (__any_sync(0xffffffffu, v - 1 != prev) && ++spin < SPIN_LIMIT);
        bar_arrive(BAR_RDY, 160);
        bar_sync(BAR_V, 160);
      }
      if (lane == 0) {
        asm volatile("cp.async.bulk.global.shared::cta.bulk_group [%0], [%1], %2;"
                     :: "l"(&sc->kv[batch * 4 + r][kind][t][0]), "r"(SM_BASE + SM_STG + kind * TILE_BYTES), "r"(TILE_BYTES) : "memory");
        asm volatile("cp.async.bulk.commit_group;\ncp.async.bulk.wait_group 0;" ::: "memory");
        asm volatile("st.relaxed.gpu.global.u32 [%0], %1;" :: "l"(sc->flag[batch * 4 + r][kind * 16 + t]), "r"(prev + 1) : "memory");
      }
    } else {
      const uint32_t epoch = ((volatile uint32_t*)sc->epoch)[b] + 1;
      if (lane == 0 && epoch) {
        asm volatile("prefetch.tensormap [%0];" :: "l"(&p.map[M_FF1B]) : "memory");
        l2_prefetch(p.w_ff1b, 1024 * 256 * 2, b);
        l2_prefetch(p.w_qkv, 256 * 768 * 2, b);
        l2_prefetch(p.w_pw1, 256 * 512 * 2, b);
        l2_prefetch(p.w_ff2a, 256 * 1024 * 2, b);
      }
#pragma unroll 1
      for (int i = 0; i < 11; i++) {
        const uint32_t t0 = clock_now();
        uint4* dst = &sc->x[b][X_CLEAR + i * 96 + lane];
        st_vec(dst, 0u, 0u, 0u, 0u); st_vec(dst + 32, 0u, 0u, 0u, 0u); st_vec(dst + 64, 0u, 0u, 0u, 0u);
        while (clock_now() - t0 < 100) {}
      }
      asm volatile("fence.acq_rel.gpu;" ::: "memory");
      __syncwarp();
      if (lane == 0) {
        asm volatile("st.relaxed.gpu.global.u32 [%0], %1;" :: "l"(sc->ready[b]), "r"(epoch) : "memory");
        l2_prefetch(p.w_o, 256 * 256 * 2, b);
        l2_prefetch(p.w_pw2, 256 * 256 * 2, b);
        l2_prefetch(p.w_ff2b, 1024 * 256 * 2, b);
#pragma unroll
        for (int i = M_QKV; i < M_X; i++) asm volatile("prefetch.tensormap [%0];" :: "l"(&p.map[i]) : "memory");
      }
    }
  } else {
    asm volatile("setmaxnreg.inc.sync.aligned.u32 232;");
    const int q = lane & 3, th = tid & 127;
    constexpr uint32_t stg = SM_BASE + SM_STG;
    const uint32_t mrow = 16 * w + (lane & 15);
    const uint32_t maddr = stg + mrow * 128 + (((lane >> 4) ^ (lane & 7)) << 4);
    const uint32_t qslot = stg + 2 * TILE_BYTES + w * 2048 + lane * 16;
    uint4* const xp = &sc->x[b][th];
    const int nvalid = T_SEQ - t * 64, row0 = 16 * w + (lane >> 2);

    uint32_t A[4][16];
    uint32_t sent = 0;
    uint32_t st[4];
    if (tid < 144) sts128(SM_BASE + SM_CS + tid * 16, 0, 0, 0, 0);
    if (wg == 1) sts32(SM_BASE + SM_EYE + th * 4, th >= 96 ? 0x3F803F80u : ((th & 32) == 0 && (th & 3) == ((th >> 3) & 3)) ? (0x3F00u << ((th & 4) * 4)) : 0u);
    fence_async_smem();
    bar_sync(0, 320);
    if (wg == 0) {
      mbar_wait(SM_BASE + SM_XBAR, 0);
      PROF_MARK(1);
      RowAcc ra[2] = {};
#pragma unroll
      for (int c = 0; c < 4; c++) {
        tile_load(maddr + (3 - c) * TILE_BYTES, A[c]);
        row_acc(ra[c & 1], A[c]);
      }
      const float s0 = ra[0].s[0] + ra[1].s[0], s1 = ra[0].s[2] + ra[1].s[2];
      st[0] = pack2(s0 * (1.f / DM), s0 * (1.f / DM)); st[1] = pack2(s1 * (1.f / DM), s1 * (1.f / DM));
      centre(A[0], st[0], st[1]);
      const float2 qa = row_squares(ra[0], lane & 4), qb = row_squares(ra[1], lane & 4);
      const int src = (lane & 28) | (lane >> 3);
      const RowNorm n = row_norm(s0, __shfl_sync(0xffffffffu, qa.x + qb.x, src), s1, __shfl_sync(0xffffffffu, qa.y + qb.y, src), 0.5f);
      st[2] = __float_as_uint(n.rs0); st[3] = __float_as_uint(n.rs1);
    } else {
      const uint32_t epoch = ((volatile uint32_t*)sc->epoch)[b] + 1, tag = epoch & 1;
      mbar_wait(SM_BASE + SM_FULL + 4 * 8, 0);
      PROF_MARK(5);
      if (b < 72) {
        const __nv_bfloat16* wp; int ld, col;
        if (b < 24) { wp = p.w_qkv; ld = 768; col = b * 32; }
        else if (b < 40) { wp = p.w_pw1; ld = 512; col = (b - 24) * 32; }
        else { wp = p.w_ff2a; ld = 1024; col = (b - 40) * 32; }
        const uint4* src = (const uint4*)(wp + (size_t)(th >> 2) * ld + col + q * 8);
        float c[8] = {0.f, 0.f, 0.f, 0.f, 0.f, 0.f, 0.f, 0.f};
#pragma unroll 1
        for (int h = 0; h < 4; h++, src += 8 * ld) {
#pragma unroll
          for (int i = 0; i < 2; i++) {
            const uint4 v = __ldg(src + i * 4 * ld);
            c[0] += bf_lo(v.x); c[1] += bf_hi(v.x); c[2] += bf_lo(v.y); c[3] += bf_hi(v.y);
            c[4] += bf_lo(v.z); c[5] += bf_hi(v.z); c[6] += bf_lo(v.w); c[7] += bf_hi(v.w);
          }
        }
#pragma unroll 1
        for (int m = 4; m <= 16; m <<= 1)
#pragma unroll
          for (int k = 0; k < 8; k++) c[k] += __shfl_xor_sync(0xffffffffu, c[k], m);
        if (lane < 4) {
          const uint32_t a = SM_BASE + SM_CS + 1792 + w * 128 + lane * 32;
          sts128(a, __float_as_uint(c[0]), __float_as_uint(c[1]), __float_as_uint(c[2]), __float_as_uint(c[3]));
          sts128(a + 16, __float_as_uint(c[4]), __float_as_uint(c[5]), __float_as_uint(c[6]), __float_as_uint(c[7]));
        }
        bar_sync(BAR_WG1, 128);
        if (th < 8) {
          float o[4] = {0.f, 0.f, 0.f, 0.f};
#pragma unroll 1
          for (int k = 0; k < 4; k++) {
            uint32_t e[4];
            lds128(SM_BASE + SM_CS + 1792 + k * 128 + th * 16, e[0], e[1], e[2], e[3]);
#pragma unroll
            for (int i = 0; i < 4; i++) o[i] += __uint_as_float(e[i]);
          }
          st_vec(&sc->cs[b * 8 + th], (__float_as_uint(o[0]) & ~1u) | tag, __float_as_uint(o[1]), __float_as_uint(o[2]), __float_as_uint(o[3]));
        }
      }
      bar_sync(BAR_WG1, 128);
      PROF_MARK(2);
#pragma unroll 1
      for (int i = th; i < 144; i += 128) {
        const int j = i >> 4;
        int src;
        if (j < CS_PW1) src = 320 + 64 * r + i;
        else if (j < CS_QKV) src = 192 + (j - CS_PW1) * 64 + 16 * r + (i & 15);
        else src = ((j - CS_QKV + 1) % 3) * 64 + 16 * r + (i & 15);
        uint32_t e[4], spin = 0;
#pragma unroll 1
        do {
          ld_vec(&sc->cs[src], e[0], e[1], e[2], e[3]);
        } while (((e[0] ^ tag) & 1u) && ++spin < SPIN_LIMIT);
        const float c0 = __uint_as_float(e[0] & ~1u), c1 = __uint_as_float(e[1]), c2 = __uint_as_float(e[2]), c3 = __uint_as_float(e[3]);
        const uint32_t h0 = pack2(c0, c1), h1 = pack2(c2, c3);
        const uint32_t a = SM_BASE + SM_CS + j * 256 + (i & 15) * 8;
        sts64(a ^ ((a >> 3) & 0x70), h0, h1);
        sts64((a + 128) ^ (((a + 128) >> 3) & 0x70), pack2(c0 - bf_lo(h0), c1 - bf_hi(h0)), pack2(c2 - bf_lo(h1), c3 - bf_hi(h1)));
      }
      fence_async_smem();
      PROF_MARK(4);
      bar_arrive(BAR_CS, 256);
    }

#pragma unroll 1
    for (uint32_t pass = 0; pass < 2; pass++) {
      uint32_t Q[16];
      if (wg == 0) {
        float acc[4][32];
        uint32_t H[4][16];
        if (!pass) { PROF_MARK(47); ACQUIRE(0); }
        mma_tile<true>(acc[0], A[0], LO(0)); mma_tile<true>(acc[1], A[0], HI(0));
        if (!pass) ACQUIRE(1);
        mma_tile<true>(acc[2], A[0], LO(1)); mma_tile<true>(acc[3], A[0], HI(1));
        if (pass) {
          gather_first<1, X_AG0>(A, st, sc, xp, 1, sent);
        } else {
          centre(A[1], st[0], st[1]);
          acquire_n<2, 3>();
        }
        mma_tile<false>(acc[0], A[1], LO(2)); mma_tile<false>(acc[1], A[1], HI(2));
        if (pass) {
          gather_rest<1, X_AG0>(A, xp, 1);
          RELEASE(F_PW2, F_PW2 + 1);
        } else {
          centre(A[2], st[0], st[1]); centre(A[3], st[0], st[1]);
        }
        PROF_MARK(2 + pass * 16);
        mma_tile<false>(acc[0], A[2], LO(3)); mma_tile<false>(acc[0], A[3], LO(4));
        WG_WAIT(4);
        RELEASE(0, 1);
        uint32_t mu[4] = {0u, 0u, 0u, 0u};
        float rs0 = __uint_as_float(st[2]), rs1 = __uint_as_float(st[3]), tn[2][4];
        if (pass) {
          const RowNorm n = stat_finish(sc, st, 1, 0.5f);
          rs0 = n.rs0; rs1 = n.rs1;
          mean_frag(mu, n, q == 0);
        }
        pin(mu);
        mma_fold<2 * CS_FF2>(acc[0], mu);
        mma_tile<false>(acc[1], A[2], HI(3));
#define SEGS(a, b) silu_segs<a, b>(acc, tn, H, rs0, rs1)
        WG_WAIT(1); pin(acc[0]);
        SEGS(0, 1);
        mma_tile_fold<2 * CS_FF2 + 2>(acc[1], A[3], HI(4), mu);
        SEGS(1, 3);
        uint32_t ok = probe_n<5, 3>();
        SEGS(3, 4);
        settle_n<5, 3>(ok);
        mma_tile<false>(acc[2], A[1], LO(5));
        SEGS(4, 6);
        mma_tile<false>(acc[2], A[2], LO(6));
        SEGS(6, 8);
        WG_WAIT(2); pin(acc[1]);
        RELEASE(2, 4);
        SEGS(8, 9);
        mma_tile_fold<2 * CS_FF2 + 4>(acc[2], A[3], LO(7), mu);
        SEGS(9, 12);
        mma_tile<false>(acc[3], A[1], HI(5));
        SEGS(12, 14);
        mma_tile<false>(acc[3], A[2], HI(6));
        SEGS(14, 16);
        WG_WAIT(2); pin(acc[2]);
        SEGS(16, 17);
        mma_tile_fold<2 * CS_FF2 + 6>(acc[3], A[3], HI(7), mu);
        SEGS(17, 19);
        ok = probe_n<8, 2>();
        SEGS(19, 20);
        settle_n<8, 2>(ok);
        mma_tile_reuse(acc[1], H[0], LO(8));
        SEGS(20, 22);
        mma_tile<false>(acc[1], H[1], HI(8));
        SEGS(22, 24);
        WG_WAIT(2); pin(acc[3]);
        RELEASE(5, 7);
        SEGS(24, 26);
        mma_tile<false>(acc[1], H[2], LO(9));
        SEGS(26, 27);
        ok = probe_n<10, 2>();
        SEGS(27, 28);
        settle_n<10, 2>(ok);
        mma_tile_reuse(acc[2], H[0], LO(10));
        SEGS(28, 31);
        mma_tile<false>(acc[2], H[1], HI(10));
        SEGS(31, 34);
#undef SEGS
        PROF_MARK(3 + pass * 16);
        const uint32_t rtag = here(pass ^ 1);
        const uint4* rs_in = xp + X_RS;
        mma_tile<false>(acc[1], H[3], HI(9));
        mma_tile<false>(acc[2], H[2], LO(11));
        ok = probe_n<12, 2>();
        uint4* rs_out = peer<1>(xp) + X_RS;
        mma_tile<false>(acc[2], H[3], HI(11));
        settle_n<12, 2>(ok);
        WG_WAIT(2); pin(acc[1]);
        RELEASE(8, 9);
        send_half<0>(rs_out, acc[1], rtag);
        mma_tile_reuse(acc[3], H[0], LO(12));
        SCHED();
        send_half<1>(rs_out, acc[1], rtag);
        mma_tile<false>(acc[3], H[1], HI(12));
        rs_out = peer<2>(xp) + X_RS + 512;
        WG_WAIT(2); pin(acc[2]);
        send_half<0>(rs_out, acc[2], rtag);
        mma_tile<false>(acc[3], H[2], LO(13));
        SCHED();
        ok = probe_n<14, 2>();
        send_half<1>(rs_out, acc[2], rtag);
        mma_tile<false>(acc[3], H[3], HI(13));
        settle_n<14, 2>(ok);
        mma_tile_reuse(acc[1], H[0], LO(14));
        rs_out = peer<3>(xp) + X_RS + 1024;
        if (!pass) bar_sync(BAR_RDY, 160);
        fetch(rs_in, A[1]);
        SCHED();
        mma_tile<false>(acc[1], H[1], HI(14));
        WG_WAIT(2); pin(acc[3]);
        send_half<0>(rs_out, acc[3], rtag);
        send_half<1>(rs_out, acc[3], rtag);
        sent = clock_now();
        mma_tile<false>(acc[1], H[2], LO(15)); mma_tile<false>(acc[1], H[3], HI(15));
        SCHED();
        confirm(rs_in, A[1], rtag);
        fetch(rs_in + 512, A[2]);
        SCHED();
        res_load(maddr, acc[2]);
        mma_add_half(acc[2], A[1]);
        while (clock_now() - sent < GATHER_DELAY) {}
        fetch(rs_in + 1024, A[3]);
        if (!pass) { acquire_n<F_QKV, 3>(); bar_sync(BAR_CS, 256); }
        {
          uint32_t spin = 0;
          while (__builtin_expect(stale(miss(A[2], rtag) | miss(A[3], rtag)), 0) && ++spin < SPIN_LIMIT) { fetch(rs_in + 512, A[2]); fetch(rs_in + 1024, A[3]); }
        }
        mma_add_half(acc[2], A[2]);
        mma_add_half(acc[2], A[3]);
        PROF_MARK(4 + pass * 16);
        WG_WAIT(0); pin(acc[2]); pin(acc[1]);
#pragma unroll
        for (int i = 0; i < 16; i++) A[0][i] = pack2(fmaf(acc[1][2 * i], 0.5f, acc[2][2 * i]), fmaf(acc[1][2 * i + 1], 0.5f, acc[2][2 * i + 1]));
        if (pass) {
          PROF_MARK(21);
          stat_publish(A[0], sc, here(th), 0);
          stat_fetch(sc, st);
          const RowNorm fn = stat_finish(sc, st, 0, 1.f);
          const float nm0 = -fn.m0 * fn.rs0, nm1 = -fn.m1 * fn.rs1;
#pragma unroll
          for (int i = 0; i < 16; i++) {
            const float rs = (i & 1) ? fn.rs1 : fn.rs0, nm = (i & 1) ? nm1 : nm0;
            A[0][i] = pack2(fmaf(bf_lo(A[0][i]), rs, nm), fmaf(bf_hi(A[0][i]), rs, nm));
          }
          tile_store(here(maddr), A[0]);
          __syncwarp();
          const int row = 16 * w + (lane >> 3);
          uint4* dst = (uint4*)(out + ((size_t)batch * T_SEQ + t * 64 + row) * DM + 64 * r) + (lane & 7);
          const uint32_t src = stg + row * 128 + (((lane & 7) ^ (lane >> 3)) << 4);
#pragma unroll
          for (int i = 0; i < 4; i++) {
            uint4 v;
            lds128((src ^ ((i & 1) << 6)) + i * 512, v.x, v.y, v.z, v.w);
            if (row + 4 * i < nvalid) dst[i * 4 * (DM / 8)] = v;
          }
          PROF_MARK(22);
          PROF_TIME(31);
          break;
        }
        sent = send_residual(A[0], sc, xp, maddr, 1);
        PROF_MARK(5);
        mma_tile<true>(acc[0], A[0], LO(F_QKV)); mma_tile<true>(acc[1], A[0], HI(F_QKV));
        mma_tile<true>(acc[2], A[0], LO(F_QKV + 1));
        gather_first<1, X_AG0>(A, st, sc, xp, 1, sent);
        mma_tile<false>(acc[0], A[1], LO(F_QKV + 2)); mma_tile<false>(acc[1], A[1], HI(F_QKV + 2));
        acquire_n<F_QKV + 3, 3>();
        gather_rest<1, X_AG0>(A, xp, 1);
        PROF_MARK(6);
        mma_tile<false>(acc[0], A[2], LO(F_QKV + 3)); mma_tile<false>(acc[0], A[3], LO(F_QKV + 4));
        SCHED();
        {
          const RowNorm n = stat_finish(sc, st, 1, 1.f);
          rs0 = row0 < nvalid ? n.rs0 : 0.f; rs1 = row0 + 8 < nvalid ? n.rs1 : 0.f;
          mean_frag(mu, n, q == 3);
        }
        mma_fold<2 * CS_QKV - 6>(acc[0], mu);
        RELEASE(10, 15);
        WG_WAIT(0); pin(acc[0]);
        scale_pack(acc[0], Q, rs0, rs1);
        tile_store(here(maddr), Q);
        SCHED();
        mma_tile<false>(acc[1], A[2], HI(F_QKV + 3));
        fence_async_smem();
        bar_arrive(BAR_K, 160);
        mma_tile_fold<2 * CS_QKV - 4>(acc[1], A[3], HI(F_QKV + 4), mu);
        mma_tile<false>(acc[2], A[1], HI(F_QKV + 1)); mma_tile<false>(acc[2], A[2], LO(F_QKV + 5));
        WG_WAIT(2); pin(acc[1]);
        scale_pack(acc[1], Q, rs0, rs1);
        tile_store(here(maddr) + TILE_BYTES, Q);
        fence_async_smem();
        bar_arrive(BAR_V, 160);
        mma_tile_fold<2 * CS_QKV - 2>(acc[2], A[3], HI(F_QKV + 5), mu);
        WG_WAIT(0); pin(acc[2]);
        scale_pack(acc[2], Q, rs0 * SM_SCALE_LOG2, rs1 * SM_SCALE_LOG2);
        frag_store(here(qslot), Q);
        bar_arrive(BAR_Q, 256);
        RELEASE(F_QKV, F_QKV + 5);
      } else {
        bar_sync(BAR_Q, 256);
#pragma unroll
        for (int s = 0; s < 4; s++) lds128(qslot + s * 512, Q[4 * s], Q[4 * s + 1], Q[4 * s + 2], Q[4 * s + 3]);
        if (w < 2) {
          const uint32_t v = w ? 0u : 0x3F803F80u;
#pragma unroll
          for (int s = 0; s < 4; s++) sts128(qslot + s * 512, v, v, v, v);
          fence_async_smem();
        }
      }
      bar_sync(BAR_ATT, 256);
      PROF_MARK(7);

      const int dir = cw == 0 ? -1 : 1;
      uint32_t tap[15];
      {
        const uint32_t* dwp = (const uint32_t*)(dw + 64 * r) + lane + 7 * (DM / 2);
#pragma unroll
        for (int k = 0; k < 15; k++) tap[k] = __ldg(dwp + dir * (k - 7) * (DM / 2));
      }

      float O[36];
      {
        float S[2][32];
        uint32_t P[2][16], nm[4];
        pin(Q);
        WG_FENCE();
        qk_tile(S[0], Q, RING + (SM_STG >> 4));
        WG_COMMIT();
#pragma unroll
        for (int i = 0; i < 36; i++) O[i] = 0.f;
#pragma unroll
        for (int i = 0; i < 16; i++) P[1][i] = 0u;
        WG_WAIT(0); pin(S[0]);
        const float m0 = tile_max<0>(S[0]), m1 = tile_max<2>(S[0]);
        nm[0] = pack2(q ? 0.f : -m0, 0.f); nm[1] = pack2(q ? 0.f : -m1, 0.f); nm[2] = 0u; nm[3] = 0u;
#pragma unroll
        for (int k = 0; k < 15; k++) asm("mul.rn.bf16x2 %0, %0, %1;" : "+r"(tap[k]) : "r"(0x3F003F00u));
        pin(nm); pin(O); pin(P[1]); pin(tap);
        uint32_t sk = wg, sv = wg;
        mbar_wait(SM_BASE + SM_FULL + (F_SPARE % NSTAGE + wg) * 8, 1);
        if (lane == 0) mbar_arrive(SM_BASE + SM_EMPTY + (F_SPARE % NSTAGE + wg) * 8);
        mbar_wait(SM_BASE + SM_FULL + sk * 8, 0);
        PROF_MARK(8);
        WG_FENCE();
        qk_tile(S[0], Q, RING + sk * 1024);
        qk_shift(S[0], nm);
        WG_COMMIT();
        WG_WAIT(0); pin(S[0]);
#pragma unroll 1
        for (int it = 0; it < 4; it++) {
          attn_step(S[0], S[1], P[0], P[1], O, Q, nm, RING + sk * 1024 + 512, RING_V + (sv * 1024 + 512) * V_STEP);
          const uint32_t sn = it == 2 ? wg : sk + (it == 3 ? 2 : 4);
          mbar_wait(SM_BASE + SM_FULL + sn * 8, it >= 2);
          mbar_wait(SM_BASE + SM_FULL + (sk + 2) * 8, it == 3);
          WG_WAIT(0); pin(O); pin(S[1]); pin(P[1]);
          if (lane == 0) {
            mbar_arrive(SM_BASE + SM_EMPTY + sk * 8);
            if (it) mbar_arrive(SM_BASE + SM_EMPTY + sv * 8);
          }
          sv = sk + 2; sk = sn;
          attn_step(S[1], S[0], P[1], P[0], O, Q, nm, RING + sk * 1024, RING_V + (sv * 1024) * V_STEP);
          WG_WAIT(0); pin(O); pin(S[0]); pin(P[0]);
        }
        WG_FENCE();
        pv_tile(O, P[1], RING_V + (sv * 1024 + 512) * V_STEP, (uint64_t)wg << 22);
        WG_COMMIT();
        WG_WAIT(0); pin(O);
      }
      PROF_MARK(9);

      {
        const uint32_t mo = stg + here(th) * 16;
        sts64(mo + 5 * 4096 + wg * 8, __float_as_uint(O[32]), __float_as_uint(O[34]));
        if (wg == 0) {
#pragma unroll
          for (int i = 4; i < 8; i++)
            sts128(mo + i * 2048, __float_as_uint(O[4 * i]), __float_as_uint(O[4 * i + 1]), __float_as_uint(O[4 * i + 2]), __float_as_uint(O[4 * i + 3]));
        } else {
#pragma unroll
          for (int i = 0; i < 4; i++)
            sts128(mo + i * 2048, __float_as_uint(O[4 * i]), __float_as_uint(O[4 * i + 1]), __float_as_uint(O[4 * i + 2]), __float_as_uint(O[4 * i + 3]));
#pragma unroll
          for (int i = 0; i < 16; i++) O[i] = O[16 + i];
        }
        bar_sync(BAR_MERGE, 256);
        uint32_t e[4];
        lds128(mo + 5 * 4096, e[0], e[1], e[2], e[3]);
        O[32] = __uint_as_float(e[0]) + __uint_as_float(e[2]); O[34] = __uint_as_float(e[1]) + __uint_as_float(e[3]);
#pragma unroll
        for (int i = 0; i < 4; i++) {
          lds128(mo + wg * TILE_BYTES + i * 2048, e[0], e[1], e[2], e[3]);
#pragma unroll
          for (int k = 0; k < 4; k++) O[4 * i + k] += __uint_as_float(e[k]);
        }
        const bool safe = O[32] > 0x1p-60f && O[32] < 0x1p60f && O[34] > 0x1p-60f && O[34] < 0x1p60f;
        if (__builtin_expect(__any_sync(0xffffffffu, !safe), 0)) attention_exact(O, Q, sc, batch * 4 + r, lane, wg);
        const float i0 = rcp_hw(O[32]), i1 = rcp_hw(O[34]);
#pragma unroll
        for (int i = 0; i < 8; i++) { const float v = (i & 1) ? i1 : i0; A[0][i] = pack2(O[2 * i] * v, O[2 * i + 1] * v); }
        A[0][0] &= ~1u; A[0][4] &= ~1u;
        uint4* dst = xp + X_AG1 + wg * 256;
        SCHED();
        st_vec(dst, A[0][0], A[0][1], A[0][2], A[0][3]);
        st_vec(dst + 128, A[0][4], A[0][5], A[0][6], A[0][7]);
        SCHED();
        sent = clock_now();
      }
      if (wg == 1) {
        const uint32_t mo = stg + TILE_BYTES + here(th) * 16;
        sts128(mo, A[0][0], A[0][1], A[0][2], A[0][3]);
        sts128(mo + 2048, A[0][4], A[0][5], A[0][6], A[0][7]);
        bar_arrive(BAR_HALF, 256);
      } else {
        PROF_MARK(10);
        const uint32_t mo = stg + TILE_BYTES + here(th) * 16;
        bar_sync(BAR_HALF, 256);
        lds128(mo, A[0][8], A[0][9], A[0][10], A[0][11]);
        lds128(mo + 2048, A[0][12], A[0][13], A[0][14], A[0][15]);
        sent = proj_residual<F_WO, 6>(A, sc, xp, maddr, 0, sent);
        PROF_MARK(12);
        float acc[2][32];
        mma_tile<true>(acc[0], A[0], LO(F_PW1)); mma_tile<true>(acc[1], A[0], HI(F_PW1));
        gather_first<1, X_AG0>(A, st, sc, xp, 0, sent);
        mma_tile<false>(acc[1], A[1], HI(F_PW1 + 1)); mma_tile<false>(acc[0], A[1], LO(F_PW1 + 1));
        gather_rest<1, X_AG0>(A, xp, 0);
        PROF_MARK(13);
        mma_tile<false>(acc[1], A[2], HI(F_PW1 + 2)); mma_tile<false>(acc[1], A[3], HI(F_PW1 + 3));
        SCHED();
        uint32_t mu[4];
        const RowNorm n = stat_finish(sc, st, 0, 0.5f);
        const float rs0 = row0 < nvalid ? n.rs0 : 0.f, rs1 = row0 + 8 < nvalid ? n.rs1 : 0.f;
        mean_frag(mu, n, q == 0);
        mma_fold<2 * CS_PW1 + 2>(acc[1], mu);
        RELEASE(F_KV + 14, F_WO + 1);
        mma_tile<false>(acc[0], A[2], LO(F_PW1 + 2));
        mma_tile_fold<2 * CS_PW1>(acc[0], A[3], LO(F_PW1 + 3), mu);
        WG_WAIT(2); pin(acc[1]);
#pragma unroll
        for (int i = 0; i < 32; i++) acc[1][i] = tanh_hw(acc[1][i] * ((i & 2) ? rs1 : rs0));
#pragma unroll
        for (int i = 0; i < 32; i++) { const float rs = (i & 2) ? rs1 : rs0; acc[1][i] = fmaf(acc[1][i], rs, rs); }
        pin(acc[1]);
        SCHED();
        WG_WAIT(0); pin(acc[0]);
#pragma unroll
        for (int i = 0; i < 16; i++) A[0][i] = pack2(acc[0][2 * i] * acc[1][2 * i], acc[0][2 * i + 1] * acc[1][2 * i + 1]);
        const uint32_t ga = stg + TILE_BYTES + here(mrow) * G_PITCH + (lane >> 4) * 16;
#pragma unroll
        for (int s = 0; s < 4; s++) stsm4(ga + s * 32, &A[0][4 * s]);
        RELEASE(F_PW1, F_PW1 + 3);
      }
      {
        const uint32_t gsrc = stg + TILE_BYTES + (8 * cw - 7) * G_PITCH + lane * 4;
        const bool edge = cw == 0 || cw == 7;
        const bool nbr = cw == 0 ? t > 0 : t < 15;
        uint4* const hdst = &sc->x[b + 4 * dir][X_HALO + (cw == 0 ? 96 : 0) + lane];
        uint32_t in[22];
        bar_sync(BAR_G, 256);
        PROF_MARK(14);
        if (cw == 0) {
#pragma unroll
          for (int i = 14; i >= 0; i--) in[i] = lds32(gsrc + (21 - i) * G_PITCH);
        } else {
#pragma unroll
          for (int i = 14; i >= 0; i--) in[i] = lds32(gsrc + i * G_PITCH);
        }
        if (edge) {
          if (nbr) {
            st_vec(hdst, HALO_TAG, in[14], in[13], in[12]);
            st_vec(hdst + 32, HALO_TAG, in[11], in[10], in[9]);
            st_vec(hdst + 64, HALO_TAG, in[8], 0u, 0u);
          }
        } else {
#pragma unroll
          for (int i = 15; i < 22; i++) in[i] = lds32(gsrc + i * G_PITCH);
        }
        uint32_t cv[8];
#pragma unroll
        for (int i = 0; i < 15; i++)
#pragma unroll
          for (int o = 0; o < 8; o++) {
            if (i == o) asm("mul.rn.bf16x2 %0, %1, %2;" : "=r"(cv[o]) : "r"(in[i]), "r"(tap[0]));
            if (i > o) asm("fma.rn.bf16x2 %0, %1, %2, %0;" : "+r"(cv[o]) : "r"(in[i]), "r"(tap[i - o]));
          }
        pin(cv);
        if (edge) {
#pragma unroll
          for (int i = 15; i < 22; i++) in[i] = 0u;
          if (nbr) {
            const uint4* src = &sc->x[b][X_HALO + (cw == 0 ? 0 : 96) + lane];
            uint32_t e0, e1, e2, u0, u1, spin = 0;
#pragma unroll 1
            do {
              ld_vec(src, e0, in[15], in[16], in[17]);
              ld_vec(src + 32, e1, in[18], in[19], in[20]);
              ld_vec(src + 64, e2, in[21], u0, u1);
            } while (__any_sync(0xffffffffu, ((e0 ^ HALO_TAG) | (e1 ^ HALO_TAG) | (e2 ^ HALO_TAG)) != 0) && ++spin < SPIN_LIMIT);
          }
        }
#pragma unroll
        for (int i = 15; i < 22; i++)
#pragma unroll
          for (int o = 0; o < 8; o++)
            if (i - o <= 14) asm("fma.rn.bf16x2 %0, %1, %2, %0;" : "+r"(cv[o]) : "r"(in[i]), "r"(tap[i - o]));
        const uint32_t fl = cw == 0 ? 7 : 0;
        const uint32_t cdst = (stg + cw * 1024 + lane * 4) ^ (fl * 144);
#pragma unroll
        for (int o = 0; o < 8; o++) {
          const float a = bf_lo(cv[o]), c = bf_hi(cv[o]);
          sts32(cdst ^ (o * 144), pack2(fmaf(a, tanh_hw(a), a), fmaf(c, tanh_hw(c), c)));
        }
      }
      if (wg == 1) {
        bar_arrive(BAR_C, 256);
        if (th == 0) ((volatile uint32_t*)sc->epoch)[b] += 1;
        break;
      }
      bar_sync(BAR_C, 256);
      tile_load(here(maddr), A[0]);
      PROF_MARK(15);
      publish(xp + X_AG1, A[0], 1);
      sent = proj_residual<F_PW2, 2>(A, sc, xp, maddr, 1, clock_now());
      PROF_MARK(17);
    }
  }
}

typedef CUresult (*EncodeFn)(CUtensorMap*, CUtensorMapDataType, cuuint32_t, void*, const cuuint64_t*, const cuuint64_t*,
                             const cuuint32_t*, const cuuint32_t*, CUtensorMapInterleave, CUtensorMapSwizzle,
                             CUtensorMapL2promotion, CUtensorMapFloatOOBfill);

void make_map(EncodeFn fn, CUtensorMap* m, const void* w, int rows, int cols, CUtensorMapSwizzle swz) {
  const cuuint64_t dims[2] = {(cuuint64_t)cols, (cuuint64_t)rows}, strides[1] = {(cuuint64_t)cols * 2};
  const cuuint32_t box[2] = {64, 64}, es[2] = {1, 1};
  fn(m, CU_TENSOR_MAP_DATA_TYPE_BFLOAT16, 2, const_cast<void*>(w), dims, strides, box, es, CU_TENSOR_MAP_INTERLEAVE_NONE,
     swz, CU_TENSOR_MAP_L2_PROMOTION_L2_128B, CU_TENSOR_MAP_FLOAT_OOB_FILL_NONE);
}

}

extern "C" void kernel_launch(void* const* d_in, const int* in_sizes, int n_in, void* d_out, int out_size) {
  static EncodeFn fn = nullptr;
  static Scratch* sc = nullptr;
  if (!fn) {
    void* f = nullptr;
    cudaDriverEntryPointQueryResult st;
    cudaGetDriverEntryPoint("cuTensorMapEncodeTiled", &f, cudaEnableDefault, &st);
    fn = (EncodeFn)f;
    void* raw = nullptr;
    cudaGetSymbolAddress(&raw, g_scratch);
    sc = (Scratch*)(((uintptr_t)raw + X_ALIGN - 1) & ~(uintptr_t)(X_ALIGN - 1));
    cudaFuncSetAttribute(conformer_kernel, cudaFuncAttributeMaxDynamicSharedMemorySize, SM_TOTAL);
  }
  typedef const __nv_bfloat16* W;
  const CUtensorMapSwizzle S = CU_TENSOR_MAP_SWIZZLE_128B;
  Params p;
  {
    const cuuint64_t dims[3] = {DM, T_SEQ, 2}, strides[2] = {DM * 2, T_SEQ * DM * 2};
    const cuuint32_t box[3] = {64, 64, 1}, es[3] = {1, 1, 1};
    fn(&p.map[M_X], CU_TENSOR_MAP_DATA_TYPE_BFLOAT16, 3, d_in[0], dims, strides, box, es, CU_TENSOR_MAP_INTERLEAVE_NONE, S,
       CU_TENSOR_MAP_L2_PROMOTION_L2_128B, CU_TENSOR_MAP_FLOAT_OOB_FILL_NONE);
  }
  make_map(fn, &p.map[M_FF1A], d_in[1], 256, 1024, S);
  make_map(fn, &p.map[M_FF1B], d_in[2], 1024, 256, S);
  make_map(fn, &p.map[M_QKV], d_in[3], 256, 768, S);
  make_map(fn, &p.map[M_KV], sc->kv, 16384, 64, CU_TENSOR_MAP_SWIZZLE_NONE);
  make_map(fn, &p.map[M_WO], d_in[4], 256, 256, S);
  make_map(fn, &p.map[M_PW1], d_in[5], 256, 512, S);
  make_map(fn, &p.map[M_PW2], d_in[7], 256, 256, S);
  make_map(fn, &p.map[M_FF2A], d_in[8], 256, 1024, S);
  make_map(fn, &p.map[M_FF2B], d_in[9], 1024, 256, S);
  p.w_ff1b = (W)d_in[2]; p.w_qkv = (W)d_in[3]; p.w_o = (W)d_in[4]; p.w_pw1 = (W)d_in[5];
  p.w_pw2 = (W)d_in[7]; p.w_ff2a = (W)d_in[8]; p.w_ff2b = (W)d_in[9];

  cudaLaunchConfig_t cfg = {};
  cfg.gridDim = dim3(NCTA);
  cfg.blockDim = dim3(384);
  cfg.dynamicSmemBytes = SM_TOTAL;
  cfg.stream = cudaStreamPerThread;
  cudaLaunchAttribute at[1];
  at[0].id = cudaLaunchAttributeCooperative;
  at[0].val.cooperative = 1;
  cfg.attrs = at;
  cfg.numAttrs = 1;
  cudaLaunchKernelEx(&cfg, conformer_kernel, sc, (__nv_bfloat16*)d_out, (W)d_in[6], (W)d_in[0], (W)d_in[1], p);
}
```

```cpp
#include <cuda_runtime.h>
#include <cuda_bf16.h>
#include <cuda.h>
#include <stdint.h>

namespace {

constexpr int T_SEQ = 1000;
constexpr int DM = 256;
constexpr int NCTA = 128;
constexpr int NSTAGE = 12;
constexpr uint32_t STAGE_BYTES = 16384;
constexpr uint32_t TILE_BYTES = 8192;
constexpr uint32_t SM_BASE = 1024;
constexpr uint32_t SM_STG = NSTAGE * STAGE_BYTES;
constexpr uint32_t SM_FULL = SM_STG + 32768;
constexpr uint32_t SM_EMPTY = SM_FULL + 96;
constexpr uint32_t SM_XBAR = SM_FULL + 192;
constexpr uint32_t SM_EYE = SM_FULL + 256;
constexpr uint32_t SM_ONE = SM_FULL + 640;
constexpr uint32_t SM_CS = SM_FULL + 768;
constexpr uint32_t SM_TOTAL = SM_FULL + 3072;
constexpr int CS_FF2 = 0, CS_PW1 = 4, CS_QKV = 6;
constexpr uint32_t SPIN_LIMIT = 1u << 16;
constexpr float LN_EPS = 1e-5f;
constexpr float SM_SCALE_LOG2 = 0.125f * 1.4426950408889634f;
constexpr uint32_t G_PITCH = 144;

constexpr int F_QKV = 16, F_SPARE = 22, F_KV = 24, F_WO = 40, F_PW1 = 42, F_PW2 = 46, F_TOTAL = 64;
enum { M_FF1A, M_FF1B, M_QKV, M_KV, M_WO, M_PW1, M_PW2, M_FF2A, M_FF2B, M_X, M_COUNT };
enum { BAR_K = 1, BAR_V, BAR_Q, BAR_MERGE, BAR_G, BAR_C, BAR_WG1, BAR_RDY, BAR_CS, BAR_ATT, BAR_INIT, BAR_HALF };

struct Params {
  CUtensorMap map[M_COUNT];
  const __nv_bfloat16 *w_ff1b, *w_qkv, *w_o, *w_pw1, *w_pw2, *w_ff2a, *w_ff2b;
};

constexpr int X_RS = 0, X_AG1 = X_RS, X_HALO = X_RS + 512, X_CLEAR = 1024, X_AG0 = 1536, X_ST = 2048, X_SIZE = 4096;
constexpr uint32_t HALO_TAG = 0xFFFF0001u;
struct Scratch {
  uint4 x[NCTA][X_SIZE];
  uint4 kv[8][2][16][512];
  uint4 cs[576];
  uint32_t flag[8][32][32];
  uint32_t ready[NCTA][32];
  uint32_t epoch[NCTA];
};
constexpr size_t X_ALIGN = 4 * X_SIZE * sizeof(uint4);
__device__ uint8_t g_scratch[sizeof(Scratch) + X_ALIGN];
#define PROF_TIME(i)
#define PROF_MARK(i)
#define PROF_MARK2(i, j)
#define PROF_MARK0(i)

__device__ __forceinline__ void mbar_init(uint32_t bar, uint32_t cnt) {
  asm volatile("mbarrier.init.shared::cta.b64 [%0], %1;" :: "r"(bar), "r"(cnt) : "memory");
}
__device__ __forceinline__ void mbar_wait(uint32_t bar, uint32_t parity) {
  asm volatile("{\n.reg .pred p;\n.reg .u32 c;\nmov.u32 c, 0;\n"
               "WAIT_LOOP:\nmbarrier.try_wait.parity.shared::cta.b64 p, [%0], %1;\n@p bra WAIT_DONE;\n"
               "add.u32 c, c, 1;\nsetp.lt.u32 p, c, %2;\n@p bra WAIT_LOOP;\nWAIT_DONE:\n}"
               :: "r"(bar), "r"(parity), "n"(SPIN_LIMIT) : "memory");
}
__device__ __forceinline__ void mbar_arrive(uint32_t bar) {
  asm volatile("mbarrier.arrive.shared::cta.b64 _, [%0];" :: "r"(bar) : "memory");
}
#define bar_sync(id, n) asm volatile("bar.sync %0, %1;" :: "n"((int)(id)), "n"(n) : "memory")
#define bar_arrive(id, n) asm volatile("bar.arrive %0, %1;" :: "n"((int)(id)), "n"(n) : "memory")
__device__ __forceinline__ void fence_async_smem() { asm volatile("fence.proxy.async.shared::cta;" ::: "memory"); }

__device__ __forceinline__ void st_vec(uint4* p, uint32_t a, uint32_t b, uint32_t c, uint32_t d) {
  asm volatile("{\n.reg .b128 v;\n.reg .b64 lo, hi;\nmov.b64 lo, {%1, %2};\nmov.b64 hi, {%3, %4};\nmov.b128 v, {lo, hi};\n"
               "st.relaxed.gpu.global.b128 [%0], v;\n}" :: "l"(p), "r"(a), "r"(b), "r"(c), "r"(d) : "memory");
}
__device__ __forceinline__ void ld_vec(const uint4* p, uint32_t& a, uint32_t& b, uint32_t& c, uint32_t& d) {
  asm volatile("{\n.reg .b128 v;\n.reg .b64 lo, hi;\nld.relaxed.gpu.global.b128 v, [%4];\nmov.b128 {lo, hi}, v;\n"
               "mov.b64 {%0, %1}, lo;\nmov.b64 {%2, %3}, hi;\n}" : "=r"(a), "=r"(b), "=r"(c), "=r"(d) : "l"(p) : "memory");
}
__device__ __forceinline__ void sts128(uint32_t a, uint32_t x, uint32_t y, uint32_t z, uint32_t w) {
  asm volatile("st.shared.v4.u32 [%0], {%1, %2, %3, %4};" :: "r"(a), "r"(x), "r"(y), "r"(z), "r"(w) : "memory");
}
__device__ __forceinline__ void lds128(uint32_t a, uint32_t& x, uint32_t& y, uint32_t& z, uint32_t& w) {
  asm volatile("ld.shared.v4.u32 {%0, %1, %2, %3}, [%4];" : "=r"(x), "=r"(y), "=r"(z), "=r"(w) : "r"(a) : "memory");
}
__device__ __forceinline__ uint32_t lds32(uint32_t a) {
  uint32_t x; asm volatile("ld.shared.u32 %0, [%1];" : "=r"(x) : "r"(a) : "memory"); return x;
}
__device__ __forceinline__ void sts32(uint32_t a, uint32_t x) { asm volatile("st.shared.u32 [%0], %1;" :: "r"(a), "r"(x) : "memory"); }
__device__ __forceinline__ void sts64(uint32_t a, uint32_t x, uint32_t y) {
  asm volatile("st.shared.v2.u32 [%0], {%1, %2};" :: "r"(a), "r"(x), "r"(y) : "memory");
}
__device__ __forceinline__ void stsm4(uint32_t a, const uint32_t* r) {
  asm volatile("stmatrix.sync.aligned.m8n8.x4.shared.b16 [%0], {%1, %2, %3, %4};" :: "r"(a), "r"(r[0]), "r"(r[1]), "r"(r[2]), "r"(r[3]) : "memory");
}
__device__ __forceinline__ void ldsm4(uint32_t a, uint32_t* r) {
  asm volatile("ldmatrix.sync.aligned.m8n8.x4.shared.b16 {%0, %1, %2, %3}, [%4];" : "=r"(r[0]), "=r"(r[1]), "=r"(r[2]), "=r"(r[3]) : "r"(a) : "memory");
}
__device__ __forceinline__ uint32_t pack2(float lo, float hi) {
  uint32_t r; asm("cvt.rn.bf16x2.f32 %0, %1, %2;" : "=r"(r) : "f"(hi), "f"(lo)); return r;
}
__device__ __forceinline__ float bf_lo(uint32_t w) { return __uint_as_float(w << 16); }
__device__ __forceinline__ float bf_hi(uint32_t w) { return __uint_as_float(w & 0xffff0000u); }
__device__ __forceinline__ float tanh_hw(float x) { float y; asm volatile("tanh.approx.f32 %0, %1;" : "=f"(y) : "f"(x)); return y; }
__device__ __forceinline__ float rcp_hw(float x) { float y; asm("rcp.approx.ftz.f32 %0, %1;" : "=f"(y) : "f"(x)); return y; }
__device__ __forceinline__ float ex2_hw(float x) { float y; asm("ex2.approx.ftz.f32 %0, %1;" : "=f"(y) : "f"(x)); return y; }

__device__ __forceinline__ uint32_t here(uint32_t v) { asm volatile("" : "+r"(v)); return v; }

#define SCHED() asm volatile("pmevent 1;" ::: "memory")
#define WG_FENCE() asm volatile("wgmma.fence.sync.aligned;" ::: "memory")
#define WG_COMMIT() asm volatile("wgmma.commit_group.sync.aligned;" ::: "memory")
#define WG_WAIT(n) asm volatile("wgmma.wait_group.sync.aligned %0;" :: "n"(n) : "memory")

template <int N> __device__ __forceinline__ void pin(float (&d)[N]) {
#pragma unroll
  for (int i = 0; i < N; i++) asm volatile("" : "+f"(d[i]) :: "memory");
}
template <int N> __device__ __forceinline__ void pin(uint32_t (&d)[N]) {
#pragma unroll
  for (int i = 0; i < N; i++) asm volatile("" : "+r"(d[i]) :: "memory");
}

#define WG_D32 "{%0, %1, %2, %3, %4, %5, %6, %7, %8, %9, %10, %11, %12, %13, %14, %15, %16, %17, %18, %19, %20, %21, %22, %23, %24, %25, %26, %27, %28, %29, %30, %31}"
template <int TB> __device__ __forceinline__ void wgmma64_acc(float (&d)[32], const uint32_t* a, uint64_t db) {
  asm volatile("wgmma.mma_async.sync.aligned.m64n64k16.f32.bf16.bf16 " WG_D32 ", {%32, %33, %34, %35}, %36, 1, 1, 1, %37;"
    : "+f"(d[0]), "+f"(d[1]), "+f"(d[2]), "+f"(d[3]), "+f"(d[4]), "+f"(d[5]), "+f"(d[6]), "+f"(d[7]),
      "+f"(d[8]), "+f"(d[9]), "+f"(d[10]), "+f"(d[11]), "+f"(d[12]), "+f"(d[13]), "+f"(d[14]), "+f"(d[15]),
      "+f"(d[16]), "+f"(d[17]), "+f"(d[18]), "+f"(d[19]), "+f"(d[20]), "+f"(d[21]), "+f"(d[22]), "+f"(d[23]),
      "+f"(d[24]), "+f"(d[25]), "+f"(d[26]), "+f"(d[27]), "+f"(d[28]), "+f"(d[29]), "+f"(d[30]), "+f"(d[31])
    : "r"(a[0]), "r"(a[1]), "r"(a[2]), "r"(a[3]), "l"(db), "n"(TB));
}
template <int TB> __device__ __forceinline__ void wgmma64_reuse(float (&d)[32], const uint32_t* a, uint64_t db, uint32_t zero) {
  asm volatile("{\n.reg .pred p;\nsetp.ne.u32 p, %37, 0;\nwgmma.mma_async.sync.aligned.m64n64k16.f32.bf16.bf16 " WG_D32 ", {%32, %33, %34, %35}, %36, p, 1, 1, %38;\n}"
    : "+f"(d[0]), "+f"(d[1]), "+f"(d[2]), "+f"(d[3]), "+f"(d[4]), "+f"(d[5]), "+f"(d[6]), "+f"(d[7]),
      "+f"(d[8]), "+f"(d[9]), "+f"(d[10]), "+f"(d[11]), "+f"(d[12]), "+f"(d[13]), "+f"(d[14]), "+f"(d[15]),
      "+f"(d[16]), "+f"(d[17]), "+f"(d[18]), "+f"(d[19]), "+f"(d[20]), "+f"(d[21]), "+f"(d[22]), "+f"(d[23]),
      "+f"(d[24]), "+f"(d[25]), "+f"(d[26]), "+f"(d[27]), "+f"(d[28]), "+f"(d[29]), "+f"(d[30]), "+f"(d[31])
    : "r"(a[0]), "r"(a[1]), "r"(a[2]), "r"(a[3]), "l"(db), "r"(zero), "n"(TB));
}
template <int TB> __device__ __forceinline__ void wgmma64_set(float (&d)[32], const uint32_t* a, uint64_t db) {
  asm volatile("wgmma.mma_async.sync.aligned.m64n64k16.f32.bf16.bf16 " WG_D32 ", {%32, %33, %34, %35}, %36, 0, 1, 1, %37;"
    : "=f"(d[0]), "=f"(d[1]), "=f"(d[2]), "=f"(d[3]), "=f"(d[4]), "=f"(d[5]), "=f"(d[6]), "=f"(d[7]),
      "=f"(d[8]), "=f"(d[9]), "=f"(d[10]), "=f"(d[11]), "=f"(d[12]), "=f"(d[13]), "=f"(d[14]), "=f"(d[15]),
      "=f"(d[16]), "=f"(d[17]), "=f"(d[18]), "=f"(d[19]), "=f"(d[20]), "=f"(d[21]), "=f"(d[22]), "=f"(d[23]),
      "=f"(d[24]), "=f"(d[25]), "=f"(d[26]), "=f"(d[27]), "=f"(d[28]), "=f"(d[29]), "=f"(d[30]), "=f"(d[31])
    : "r"(a[0]), "r"(a[1]), "r"(a[2]), "r"(a[3]), "l"(db), "n"(TB));
}

__device__ __forceinline__ void wgmma72_acc(float (&d)[36], const uint32_t* a, uint64_t db) {
  asm volatile("wgmma.mma_async.sync.aligned.m64n72k16.f32.bf16.bf16 {%0, %1, %2, %3, %4, %5, %6, %7, %8, %9, %10, %11, %12, %13, %14, %15, %16, %17, %18, %19, %20, %21, %22, %23, %24, %25, %26, %27, %28, %29, %30, %31, %32, %33, %34, %35}, {%36, %37, %38, %39}, %40, 1, 1, 1, 1;"
    : "+f"(d[0]), "+f"(d[1]), "+f"(d[2]), "+f"(d[3]), "+f"(d[4]), "+f"(d[5]), "+f"(d[6]), "+f"(d[7]), "+f"(d[8]),
      "+f"(d[9]), "+f"(d[10]), "+f"(d[11]), "+f"(d[12]), "+f"(d[13]), "+f"(d[14]), "+f"(d[15]), "+f"(d[16]), "+f"(d[17]),
      "+f"(d[18]), "+f"(d[19]), "+f"(d[20]), "+f"(d[21]), "+f"(d[22]), "+f"(d[23]), "+f"(d[24]), "+f"(d[25]), "+f"(d[26]),
      "+f"(d[27]), "+f"(d[28]), "+f"(d[29]), "+f"(d[30]), "+f"(d[31]), "+f"(d[32]), "+f"(d[33]), "+f"(d[34]), "+f"(d[35])
    : "r"(a[0]), "r"(a[1]), "r"(a[2]), "r"(a[3]), "l"(db));
}
__device__ __forceinline__ void wgmma16_acc(float* d, const uint32_t* a, uint64_t db) {
  asm volatile("wgmma.mma_async.sync.aligned.m64n16k16.f32.bf16.bf16 {%0, %1, %2, %3, %4, %5, %6, %7}, {%8, %9, %10, %11}, %12, 1, 1, 1, 0;"
    : "+f"(d[0]), "+f"(d[1]), "+f"(d[2]), "+f"(d[3]), "+f"(d[4]), "+f"(d[5]), "+f"(d[6]), "+f"(d[7])
    : "r"(a[0]), "r"(a[1]), "r"(a[2]), "r"(a[3]), "l"(db));
}
__device__ __forceinline__ void hmma(float (&d)[4], const uint32_t* a, uint32_t b0, uint32_t b1) {
  asm("mma.sync.aligned.m16n8k16.row.col.f32.bf16.bf16.f32 {%0, %1, %2, %3}, {%4, %5, %6, %7}, {%8, %9}, {%0, %1, %2, %3};"
    : "+f"(d[0]), "+f"(d[1]), "+f"(d[2]), "+f"(d[3]) : "r"(a[0]), "r"(a[1]), "r"(a[2]), "r"(a[3]), "r"(b0), "r"(b1));
}

__device__ __forceinline__ void hmma8(float (&d)[4], const uint32_t* a, uint32_t b0) {
  asm("mma.sync.aligned.m16n8k8.row.col.f32.bf16.bf16.f32 {%0, %1, %2, %3}, {%4, %5}, {%6}, {%0, %1, %2, %3};"
    : "+f"(d[0]), "+f"(d[1]), "+f"(d[2]), "+f"(d[3]) : "r"(a[0]), "r"(a[1]), "r"(b0));
}

template <bool FIRST> __device__ __forceinline__ void mma_tile(float (&d)[32], const uint32_t (&a)[16], uint64_t db) {
  WG_FENCE();
#pragma unroll
  for (int s = 0; s < 4; s++) {
    if (FIRST && s == 0) wgmma64_set<1>(d, &a[0], db); else wgmma64_acc<1>(d, &a[4 * s], db + s * 128);
  }
  WG_COMMIT();
}
__device__ __forceinline__ void mma_tile_reuse(float (&d)[32], const uint32_t (&a)[16], uint64_t db) {
  WG_FENCE();
  wgmma64_reuse<1>(d, &a[0], db, blockIdx.y);
#pragma unroll
  for (int s = 1; s < 4; s++) wgmma64_acc<1>(d, &a[4 * s], db + s * 128);
  WG_COMMIT();
}
template <int ROW> __device__ __forceinline__ void fold_step(float (&d)[32], const uint32_t (&mu)[4]) {
  wgmma64_acc<1>(d, mu, (uint64_t)((SM_BASE + SM_CS + ROW * 128) >> 4) | (uint64_t(1) << 16) | (uint64_t(1) << 62));
}
template <int ROW> __device__ __forceinline__ void mma_fold(float (&d)[32], const uint32_t (&mu)[4]) {
  WG_FENCE();
  fold_step<ROW>(d, mu);
  WG_COMMIT();
}
template <int ROW> __device__ __forceinline__ void mma_tile_fold(float (&d)[32], const uint32_t (&a)[16], uint64_t db, const uint32_t (&mu)[4]) {
  WG_FENCE();
#pragma unroll
  for (int s = 0; s < 4; s++) wgmma64_acc<1>(d, &a[4 * s], db + s * 128);
  fold_step<ROW>(d, mu);
  WG_COMMIT();
}
__device__ __forceinline__ void mma_add_half(float (&d)[32], const uint32_t (&a)[16]) {
  const uint64_t db = (uint64_t)((SM_BASE + SM_EYE) >> 4) | (uint64_t(8) << 16) | (uint64_t(8) << 32);
  WG_FENCE();
#pragma unroll
  for (int s = 0; s < 4; s++) wgmma16_acc(&d[8 * s], &a[4 * s], db);
  WG_COMMIT();
}
#define ACQUIRE(f) mbar_wait(SM_BASE + SM_FULL + ((f) % NSTAGE) * 8, ((f) / NSTAGE) & 1)
__device__ __forceinline__ void mbar_probe(uint32_t& ok, uint32_t bar, uint32_t parity) {
  asm volatile("{\n.reg .pred p;\nmbarrier.test_wait.parity.shared::cta.b64 p, [%1], %2;\nselp.u32 %0, %0, 0, p;\n}"
               : "+r"(ok) : "r"(bar), "r"(parity) : "memory");
}
template <int F, int N> __device__ __forceinline__ uint32_t probe_n() {
  static_assert(F % NSTAGE + N <= NSTAGE, "stages must not wrap");
  uint32_t ok = 1;
#pragma unroll
  for (int i = 0; i < N; i++) mbar_probe(ok, SM_BASE + SM_FULL + (F % NSTAGE + i) * 8, (F / NSTAGE) & 1);
  return ok;
}
template <int F, int N> __device__ __forceinline__ void settle_n(uint32_t ok) {
  if (__builtin_expect(!ok, 0)) {
#pragma unroll 1
    for (int i = 0; i < N; i++) mbar_wait(SM_BASE + SM_FULL + (F % NSTAGE + i) * 8, (F / NSTAGE) & 1);
  }
}
template <int F, int N> __device__ __forceinline__ void acquire_n() { settle_n<F, N>(probe_n<F, N>()); }
#define RELEASE(f0, f1) do { if (lane == 0) { _Pragma("unroll") for (int f_ = (f0); f_ <= (f1); f_++) mbar_arrive(SM_BASE + SM_EMPTY + (f_ % NSTAGE) * 8); } } while (0)
constexpr uint64_t RING = (uint64_t)(SM_BASE >> 4) | (uint64_t(1) << 16) | (uint64_t(64) << 32) | (uint64_t(1) << 62);
#define LO(f) (RING + ((f) % NSTAGE) * 1024)
#define HI(f) (RING + ((f) % NSTAGE) * 1024 + 512)

template <int C> __device__ __forceinline__ uint4* peer(uint4* p) {
  asm volatile("" : "+l"(p));
  return (uint4*)((uintptr_t)p ^ (C * X_SIZE * sizeof(uint4)));
}
__device__ __forceinline__ uint32_t clock_now() { uint32_t c; asm volatile("mov.u32 %0, %%clock;" : "=r"(c) :: "memory"); return c; }
__device__ __forceinline__ void publish(uint4* dst, uint32_t (&a)[16], uint32_t tag) {
#pragma unroll
  for (int s = 0; s < 4; s++) a[4 * s] = (a[4 * s] & ~1u) | tag;
  pin(a);
  SCHED();
#pragma unroll
  for (int s = 0; s < 4; s++) st_vec(dst + s * 128, a[4 * s], a[4 * s + 1], a[4 * s + 2], a[4 * s + 3]);
  SCHED();
}
__device__ __forceinline__ void fetch(const uint4* src, uint32_t (&a)[16]) {
#pragma unroll
  for (int s = 0; s < 4; s++) ld_vec(src + s * 128, a[4 * s], a[4 * s + 1], a[4 * s + 2], a[4 * s + 3]);
}
__device__ __forceinline__ uint32_t miss(const uint32_t (&a)[16], uint32_t tag) {
  return (a[0] ^ tag) | (a[4] ^ tag) | (a[8] ^ tag) | (a[12] ^ tag);
}
__device__ __forceinline__ bool stale(uint32_t v) { return __any_sync(0xffffffffu, here(v) & 1u); }
constexpr uint32_t GATHER_DELAY = 400;
__device__ __forceinline__ void stat_fetch(const Scratch* sc, uint32_t (&st)[4]) {
  const uint32_t th = here(threadIdx.x);
  ld_vec(&sc->x[(blockIdx.x & ~3u) + (th & 3)][X_ST + (th >> 2)], st[0], st[1], st[2], st[3]);
}
template <int C, int SLOT> __device__ __forceinline__ void gather_first(uint32_t (&A)[4][16], uint32_t (&st)[4], const Scratch* sc, uint4* xp,
                                                                        uint32_t tag, uint32_t sent) {
  while (clock_now() - sent < GATHER_DELAY) {}
  fetch(peer<1>(xp) + SLOT, A[1]); fetch(peer<2>(xp) + SLOT, A[2]); fetch(peer<3>(xp) + SLOT, A[3]);
  if (SLOT == X_AG0) stat_fetch(sc, st);
  uint32_t spin = 0;
  while (__builtin_expect(stale(miss(A[1], tag) | miss(A[C], tag)), 0) && ++spin < SPIN_LIMIT) {
    fetch(peer<1>(xp) + SLOT, A[1]);
    if (C == 2) fetch(peer<2>(xp) + SLOT, A[2]);
  }
}
template <int C, int SLOT> __device__ __forceinline__ void gather_rest(uint32_t (&A)[4][16], uint4* xp, uint32_t tag) {
  SCHED();
  uint32_t spin = 0;
  while (__builtin_expect(stale(miss(A[C + 1], tag) | miss(A[3], tag)), 0) && ++spin < SPIN_LIMIT) {
    if (C == 1) fetch(peer<2>(xp) + SLOT, A[2]);
    fetch(peer<3>(xp) + SLOT, A[3]);
  }
}
__device__ __forceinline__ void pack_acc(const float (&d)[32], uint32_t (&a)[16]) {
#pragma unroll
  for (int i = 0; i < 16; i++) a[i] = pack2(d[2 * i], d[2 * i + 1]);
}
__device__ __forceinline__ void frag_store(uint32_t slot, const uint32_t (&a)[16]) {
#pragma unroll
  for (int s = 0; s < 4; s++) sts128(slot + s * 512, a[4 * s], a[4 * s + 1], a[4 * s + 2], a[4 * s + 3]);
}
__device__ __forceinline__ void tile_store(uint32_t maddr, const uint32_t (&a)[16]) {
#pragma unroll
  for (int s = 0; s < 4; s++) stsm4(maddr ^ (s << 5), &a[4 * s]);
}
__device__ __forceinline__ void tile_load(uint32_t maddr, uint32_t (&a)[16]) {
#pragma unroll
  for (int s = 0; s < 4; s++) ldsm4(maddr ^ (s << 5), &a[4 * s]);
}

__device__ __forceinline__ void res_load(uint32_t maddr, float (&d)[32]) {
  uint32_t a[16];
  tile_load(here(maddr) + 3 * TILE_BYTES, a);
#pragma unroll
  for (int i = 0; i < 16; i++) { d[2 * i] = bf_lo(a[i]); d[2 * i + 1] = bf_hi(a[i]); }
  pin(d);
}

struct RowAcc { float s[4], u[2][4], v[2][4]; };
__device__ __forceinline__ void row_acc(RowAcc& t, const uint32_t (&a)[16]) {
#pragma unroll
  for (int s = 0; s < 8; s++) {
    if ((s & 1) == 0) hmma(t.s, &a[2 * s], 0x3F803F80u, 0x3F803F80u);
    hmma8(t.u[s & 1], &a[2 * s], a[2 * s]);
    hmma8(t.v[s & 1], &a[2 * s], a[2 * s + 1]);
  }
}
__device__ __forceinline__ float2 row_squares(const RowAcc& t, bool odd) {
  return make_float2(odd ? t.u[0][1] + t.u[1][1] : t.u[0][0] + t.u[1][0], odd ? t.v[0][3] + t.v[1][3] : t.v[0][2] + t.v[1][2]);
}
__device__ __forceinline__ void stat_publish(const uint32_t (&a)[16], Scratch* sc, uint32_t th, uint32_t tag) {
  RowAcc t = {};
  row_acc(t, a);
  const float2 q = row_squares(t, th & 4);
  if ((th & 3) == ((th >> 3) & 3))
    st_vec(&sc->x[blockIdx.x][X_ST + (th >> 2)], (__float_as_uint(t.s[0]) & ~1u) | tag, __float_as_uint(q.x), __float_as_uint(t.s[2]), __float_as_uint(q.y));
}
struct RowNorm { float m0, rs0, m1, rs1; };
__device__ __forceinline__ RowNorm row_norm(float s0, float q0, float s1, float q1, float scale) {
  RowNorm n;
  n.m0 = s0 * (1.f / DM); n.m1 = s1 * (1.f / DM);
  n.rs0 = scale * rsqrtf(fmaxf(fmaf(-n.m0, n.m0, q0 * (1.f / DM)), 0.f) + LN_EPS);
  n.rs1 = scale * rsqrtf(fmaxf(fmaf(-n.m1, n.m1, q1 * (1.f / DM)), 0.f) + LN_EPS);
  return n;
}
__device__ __forceinline__ RowNorm stat_finish(const Scratch* sc, uint32_t (&st)[4], uint32_t tag, float scale) {
  uint32_t spin = 0;
  while (__builtin_expect(stale(st[0] ^ tag), 0) && ++spin < SPIN_LIMIT) stat_fetch(sc, st);
  float f[4];
#pragma unroll
  for (int i = 0; i < 4; i++) {
    f[i] = __uint_as_float(st[i]);
    f[i] += __shfl_xor_sync(0xffffffffu, f[i], 1);
    f[i] += __shfl_xor_sync(0xffffffffu, f[i], 2);
  }
  return row_norm(f[0], f[1], f[2], f[3], scale);
}
__device__ __forceinline__ void mean_frag(uint32_t (&mu)[4], const RowNorm& n, bool sel) {
  const float a = sel ? -n.m0 : 0.f, c = sel ? -n.m1 : 0.f;
  mu[0] = pack2(a, a); mu[1] = pack2(c, c);
  const float al = a - bf_lo(mu[0]), cl = c - bf_lo(mu[1]);
  mu[2] = pack2(al, al); mu[3] = pack2(cl, cl);
  pin(mu);
}
__device__ __forceinline__ void centre(uint32_t (&a)[16], uint32_t m0, uint32_t m1) {
#pragma unroll
  for (int i = 0; i < 16; i++) asm("sub.rn.bf16x2 %0, %0, %1;" : "+r"(a[i]) : "r"((i & 1) ? m1 : m0));
  pin(a);
}
__device__ __forceinline__ void scale_pack(const float (&d)[32], uint32_t (&a)[16], float rs0, float rs1) {
#pragma unroll
  for (int i = 0; i < 16; i++) { const float rs = (i & 1) ? rs1 : rs0; a[i] = pack2(d[2 * i] * rs, d[2 * i + 1] * rs); }
}
template <int S> __device__ __forceinline__ void silu_seg(float (&acc)[4][32], float (&tn)[2][4], uint32_t (&H)[4][16], float rs0, float rs1) {
  if (S >= 2) {
    const float* h = &acc[(S - 2) >> 3][4 * ((S - 2) & 7)];
    const float* v = tn[S & 1];
    uint32_t* o = &H[(S - 2) >> 3][2 * ((S - 2) & 7)];
    o[0] = pack2(fmaf(h[0], v[0], h[0]), fmaf(h[1], v[1], h[1]));
    o[1] = pack2(fmaf(h[2], v[2], h[2]), fmaf(h[3], v[3], h[3]));
    asm volatile("" : "+r"(o[0]), "+r"(o[1]));
  }
  if (S >= 1 && S <= 32) {
#pragma unroll
    for (int k = 0; k < 4; k++) tn[(S - 1) & 1][k] = tanh_hw(acc[((S - 1) >> 3) & 3][4 * ((S - 1) & 7) + k]);
  }
  if (S < 32) {
    float* h = &acc[(S >> 3) & 3][4 * (S & 7)];
    h[0] *= rs0; h[1] *= rs0; h[2] *= rs1; h[3] *= rs1;
    asm volatile("" : "+f"(h[0]), "+f"(h[1]), "+f"(h[2]), "+f"(h[3]));
  }
  SCHED();
}
template <int S0, int S1> __device__ __forceinline__ void silu_segs(float (&acc)[4][32], float (&tn)[2][4], uint32_t (&H)[4][16], float rs0, float rs1) {
  silu_seg<S0>(acc, tn, H, rs0, rs1);
  if constexpr (S0 + 1 < S1) silu_segs<S0 + 1, S1>(acc, tn, H, rs0, rs1);
}
template <int HALF> __device__ __forceinline__ void send_half(uint4* dst, const float (&d)[32], uint32_t tag) {
  uint32_t o[8];
#pragma unroll
  for (int i = 0; i < 8; i++) o[i] = pack2(d[16 * HALF + 2 * i], d[16 * HALF + 2 * i + 1]);
  o[0] = (o[0] & ~1u) | tag; o[4] = (o[4] & ~1u) | tag;
  pin(o);
  SCHED();
  st_vec(dst + HALF * 256, o[0], o[1], o[2], o[3]);
  st_vec(dst + HALF * 256 + 128, o[4], o[5], o[6], o[7]);
  SCHED();
}
__device__ __forceinline__ uint32_t send_residual(uint32_t (&a)[16], Scratch* sc, uint4* xp, uint32_t maddr, uint32_t tag) {
  const uint32_t exact[4] = {a[0], a[4], a[8], a[12]};
  publish(xp + X_AG0, a, tag);
  const uint32_t sent = clock_now();
  const uint32_t th = here(threadIdx.x);
  stat_publish(a, sc, th, tag);
  tile_store(here(maddr) + 3 * TILE_BYTES, a);
  stsm4(SM_BASE + SM_STG + 3 * TILE_BYTES + (th >> 5) * 2048 + (th & 7) * 128 + ((((th >> 2) & 6) ^ (th & 7)) << 4), exact);
  return sent;
}
template <int F, int N> __device__ __forceinline__ uint32_t proj_residual(uint32_t (&A)[4][16], Scratch* sc, uint4* xp, uint32_t maddr,
                                                                          uint32_t tag, uint32_t sent) {
  float acc[32];
  uint32_t st[4];
  acquire_n<F, N>();
  if (F == F_PW2) acquire_n<0, 5>();
  res_load(maddr, acc);
  mma_tile<false>(acc, A[0], LO(F));
  gather_first<2, X_AG1>(A, st, sc, xp, tag, sent);
  mma_tile<false>(acc, A[1], HI(F));
  mma_tile<false>(acc, A[2], LO(F + 1));
  gather_rest<2, X_AG1>(A, xp, tag);
  PROF_MARK0(F == F_WO ? 11 : 16);
  mma_tile<false>(acc, A[3], HI(F + 1));
  WG_WAIT(0); pin(acc);
  pack_acc(acc, A[0]);
  return send_residual(A[0], sc, xp, maddr, tag);
}

__device__ __forceinline__ uint64_t ring_desc(uint32_t lo) { return (RING & ~uint64_t(0xFFFFFFFFu)) | lo; }
__device__ __forceinline__ void qk_tile(float (&S)[32], const uint32_t (&Q)[16], uint32_t dk) {
  wgmma64_reuse<0>(S, &Q[0], ring_desc(dk), blockIdx.y);
#pragma unroll
  for (int s = 1; s < 4; s++) wgmma64_acc<0>(S, &Q[4 * s], ring_desc(dk + s * 2));
}
__device__ __forceinline__ void qk_shift(float (&S)[32], const uint32_t (&nm)[4]) { wgmma64_acc<0>(S, nm, (uint64_t)((SM_BASE + SM_ONE) >> 4)); }
constexpr uint32_t RING_K = (uint32_t)RING, V_STEP = 1u - (1u << 16);
constexpr uint32_t RING_V = (SM_BASE >> 4) | (((SM_STG + 2 * TILE_BYTES) >> 4) << 16);
__device__ __forceinline__ void pv_tile(float (&O)[36], const uint32_t (&P)[16], uint32_t dv, uint32_t pad) {
#pragma unroll
  for (int s = 0; s < 4; s++) wgmma72_acc(O, &P[4 * s], ring_desc(dv + s * 128 * V_STEP + (s < 2 ? 0 : (s - 1) * pad)));
}
__device__ __forceinline__ void attn_step(const float (&Sc)[32], float (&Sn)[32], uint32_t (&Pc)[16], uint32_t (&Pp)[16], float (&O)[36],
                                          const uint32_t (&Q)[16], const uint32_t (&nm)[4], uint32_t dk, uint32_t dv, bool next, bool prev) {
  if (next) {
    WG_FENCE();
    qk_tile(Sn, Q, dk);
    qk_shift(Sn, nm);
  }
  if (prev) {
    WG_FENCE();
    pv_tile(O, Pp, dv, 0);
  }
  WG_COMMIT();
  SCHED();
#pragma unroll
  for (int i = 0; i < 16; i++) Pc[i] = pack2(ex2_hw(Sc[2 * i]), ex2_hw(Sc[2 * i + 1]));
  pin(Pc);
  SCHED();
}
template <int R> __device__ __forceinline__ float tile_max(const float (&S)[32]) {
  float t[4];
#pragma unroll
  for (int j = 0; j < 4; j++) t[j] = fmaxf(fmaxf(S[8 * j + R], S[8 * j + R + 1]), fmaxf(S[8 * j + R + 4], S[8 * j + R + 5]));
  float n = fmaxf(fmaxf(t[0], t[1]), fmaxf(t[2], t[3]));
  n = fmaxf(n, __shfl_xor_sync(0xffffffffu, n, 1));
  return fmaxf(n, __shfl_xor_sync(0xffffffffu, n, 2));
}
__device__ __forceinline__ void attention_exact(float (&O)[36], const uint32_t (&Q)[16], const Scratch* sc, int bh, int lane, int half) {
  const char* kb = (const char*)&sc->kv[bh][0][0][0];
  const char* vb = (const char*)&sc->kv[bh][1][0][0];
  const int g = lane >> 2, q = lane & 3;
  float m0 = -INFINITY, m1 = -INFINITY, l0 = 0.f, l1 = 0.f;
  float o[4][4] = {};
#pragma unroll 1
  for (int k0 = 0; k0 < T_SEQ; k0 += 8) {
    float s[4] = {0.f, 0.f, 0.f, 0.f};
#pragma unroll
    for (int c = 0; c < 8; c++) hmma8(s, &Q[2 * c], __ldcg((const uint32_t*)(kb + (k0 + g) * 128 + ((c ^ g) << 4) + q * 4)));
    float n0 = fmaxf(s[0], s[1]), n1 = fmaxf(s[2], s[3]);
    n0 = fmaxf(n0, __shfl_xor_sync(0xffffffffu, n0, 1)); n1 = fmaxf(n1, __shfl_xor_sync(0xffffffffu, n1, 1));
    n0 = fmaxf(m0, fmaxf(n0, __shfl_xor_sync(0xffffffffu, n0, 2))); n1 = fmaxf(m1, fmaxf(n1, __shfl_xor_sync(0xffffffffu, n1, 2)));
    const float a0 = ex2_hw(m0 - n0), a1 = ex2_hw(m1 - n1);
    m0 = n0; m1 = n1;
    const uint32_t pp[2] = {pack2(ex2_hw(s[0] - n0), ex2_hw(s[1] - n0)), pack2(ex2_hw(s[2] - n1), ex2_hw(s[3] - n1))};
    l0 = fmaf(l0, a0, bf_lo(pp[0]) + bf_hi(pp[0])); l1 = fmaf(l1, a1, bf_lo(pp[1]) + bf_hi(pp[1]));
#pragma unroll
    for (int j = 0; j < 4; j++) {
      const int c = 4 * half + j;
      const uint32_t v0 = __ldcg((const uint16_t*)(vb + (k0 + 2 * q) * 128 + ((c ^ (2 * q)) << 4) + g * 2));
      const uint32_t v1 = __ldcg((const uint16_t*)(vb + (k0 + 2 * q + 1) * 128 + ((c ^ (2 * q + 1)) << 4) + g * 2));
      o[j][0] *= a0; o[j][1] *= a0; o[j][2] *= a1; o[j][3] *= a1;
      hmma8(o[j], pp, v0 | (v1 << 16));
    }
  }
  l0 += __shfl_xor_sync(0xffffffffu, l0, 1); l1 += __shfl_xor_sync(0xffffffffu, l1, 1);
  O[32] = l0 + __shfl_xor_sync(0xffffffffu, l0, 2); O[34] = l1 + __shfl_xor_sync(0xffffffffu, l1, 2);
#pragma unroll
  for (int i = 0; i < 16; i++) O[i] = o[i >> 2][i & 3];
}

__device__ __forceinline__ uint32_t fill_entry(int f, int r, int bh) {
  int m, x = r, y, dx = 0;
  if (f < F_QKV || f >= 48) {
    const int i = f & 15;
    m = f < F_QKV ? M_FF1A : M_FF2A;
    if (i < 8) { x = 4 * r + ((0xE2u >> i) & 1) * 2; y = r ^ ((0xE790u >> (2 * i)) & 3); dx = 1; }
    else { m++; x = r ^ (((i >> 1) - 3) & 3); y = 4 * r + 2 * (i & 1); }
  } else if (f < F_KV) {
    const int i = f - F_QKV;
    m = M_QKV;
    if (i == 1 || i >= 5) { y = r ^ (i == 1 ? 0 : 2); }
    else { x = 4 + r; y = r ^ (i ? i - 1 : 0); dx = 4; }
  } else if (f < F_WO) {
    const int i = f - F_KV;
    m = M_KV; x = 0; y = bh * 32 + (i & 2) * 8 + (i >> 2) * 4 + (i & 1) * 2;
  } else if (f >= F_PW1 && f < F_PW2) {
    m = M_PW1; y = r ^ (f - F_PW1); dx = 4;
  } else {
    m = f < F_PW1 ? M_WO : M_PW2; y = r ^ ((f & 1) * 2);
  }
  return m | (x << 4) | (y << 8) | (dx << 16);
}
__device__ __forceinline__ void tma_fill(uint32_t st, const CUtensorMap* map, uint32_t x, uint32_t y, uint32_t x2, uint32_t y2) {
  asm volatile("{\n.reg .pred p;\nelect.sync _|p, 0xffffffff;\n"
               "@p mbarrier.arrive.expect_tx.shared::cta.b64 _, [%1], 16384;\n"
               "@p cp.async.bulk.tensor.2d.shared::cluster.global.mbarrier::complete_tx::bytes [%0], [%2, {%3, %4}], [%1];\n"
               "@p cp.async.bulk.tensor.2d.shared::cluster.global.mbarrier::complete_tx::bytes [%0 + 8192], [%2, {%5, %6}], [%1];\n}"
               :: "r"(SM_BASE + st * STAGE_BYTES), "r"(SM_BASE + SM_FULL + st * 8), "l"(map), "r"(x), "r"(y), "r"(x2), "r"(y2) : "memory");
}
__device__ __forceinline__ void l2_prefetch(const void* p, uint32_t total, int b) {
  const uint32_t part = total / NCTA;
  asm volatile("cp.async.bulk.prefetch.L2.global [%0], %1;" :: "l"((const char*)p + (size_t)b * part), "r"(part) : "memory");
}

__global__ void __launch_bounds__(384, 1) conformer_kernel(Scratch* __restrict__ sc, __nv_bfloat16* __restrict__ out,
                                                           const __nv_bfloat16* __restrict__ dw, const __nv_bfloat16* __restrict__ xin,
                                                           const __nv_bfloat16* __restrict__ w_ff1a, const __grid_constant__ Params p) {
  extern __shared__ __align__(1024) uint8_t smem[];
  const int tid = threadIdx.x, lane = tid & 31;
  if (tid == 0) {
    l2_prefetch(xin, 2 * T_SEQ * DM * 2, blockIdx.x);
    l2_prefetch(w_ff1a, 256 * 1024 * 2, blockIdx.x);
  }
  const int cw = __shfl_sync(0xffffffffu, tid >> 5, 0), wg = cw >> 2, w = cw & 3;
  const int b = blockIdx.x, r = b & 3, batch = b >> 6, t = (b >> 2) & 15;
  if ((uint32_t)__cvta_generic_to_shared(smem) != SM_BASE) return;
  PROF_MARK(0);
  PROF_TIME(30);

  if (wg == 2) {
    asm volatile("setmaxnreg.dec.sync.aligned.u32 40;");
    if (cw == 8) {
      if (lane == 0) {
        asm volatile("prefetch.tensormap [%0];" :: "l"(&p.map[M_X]) : "memory");
        asm volatile("prefetch.tensormap [%0];" :: "l"(&p.map[M_FF1A]) : "memory");
        mbar_init(SM_BASE + SM_XBAR, 4);
#pragma unroll
        for (int i = 0; i < NSTAGE; i++) mbar_init(SM_BASE + SM_FULL + i * 8, 1);
        fence_async_smem();
      }
      __syncwarp();
      bar_arrive(0, 320);
      PROF_MARK(9);
#pragma unroll
      for (int f = 0; f < 8; f++) {
        const uint32_t x = 256 * r + ((0xE2u >> f) & 1) * 128, y = (r ^ ((0xE790u >> (2 * f)) & 3)) * 64;
#pragma unroll
        for (int c = 0; c < (f == 0 ? 4 : 0); c++)
          asm volatile("{\n.reg .pred p;\nelect.sync _|p, 0xffffffff;\n"
                       "@p mbarrier.arrive.expect_tx.shared::cta.b64 _, [%1], 8192;\n"
                       "@p cp.async.bulk.tensor.3d.shared::cluster.global.mbarrier::complete_tx::bytes [%0], [%2, {%3, %4, %5}], [%1];\n}"
                       :: "r"(SM_BASE + SM_STG + (3 - c) * TILE_BYTES), "r"(SM_BASE + SM_XBAR), "l"(&p.map[M_X]),
                          "r"((r ^ c) * 64), "r"(t * 64), "r"(batch) : "memory");
        tma_fill(f, &p.map[M_FF1A], x, y, x + 64, y);
      }
      PROF_MARK(1);
      const uint32_t* flag = sc->flag[batch * 4 + r][lane];
      const uint32_t prev = ((volatile uint32_t*)sc->epoch)[b];
      uint32_t entry[2], ready = 0, st = 8, parity = 1;
#pragma unroll 1
      for (int i = 0; i < 2; i++) { entry[1] = fill_entry(i * 32 + lane, r, batch * 4 + r); if (i == 0) entry[0] = entry[1]; }
      bar_sync(BAR_INIT, 64);
#pragma unroll 1
      for (int f = 8; f < F_TOTAL; f++) {
        const uint32_t e = __shfl_sync(0xffffffffu, f < 32 ? entry[0] : entry[1], f);
        if ((e & 15) == M_KV) {
          const uint32_t need = 3u << ((e >> 8) & 31);
          uint32_t spin = 0;
#pragma unroll 1
          while ((ready & need) != need && ++spin < SPIN_LIMIT) {
            uint32_t v;
            asm volatile("ld.relaxed.gpu.global.u32 %0, [%1];" : "=r"(v) : "l"(flag) : "memory");
            ready = __ballot_sync(0xffffffffu, v - 1 == prev);
          }
        }
        if (f == F_KV) PROF_MARK(8);
        mbar_wait(SM_BASE + SM_EMPTY + st * 8, parity);
        const uint32_t x = (e << 2) & 0x3C0, y = (e >> 2) & 0x3FC0, dx = (e >> 16) << 6;
        tma_fill(st, &p.map[e & 15], x, y, x + dx, dx ? y : y ^ 64);
        if (++st == NSTAGE) { st = 0; parity ^= 1; }
      }
    } else if (here(cw) != 11) {
      const int kind = w - 1;
      const uint32_t prev = ((volatile uint32_t*)sc->epoch)[b];
      if (kind == 0) {
        if (lane == 0) {
#pragma unroll
          for (int i = 0; i < NSTAGE; i++) mbar_init(SM_BASE + SM_EMPTY + i * 8, 4);
        }
        __syncwarp();
        bar_arrive(0, 320);
        bar_arrive(BAR_INIT, 64);
        bar_sync(BAR_K, 160);
      } else {
        uint32_t v, spin = 0;
#pragma unroll 1
        do {
          asm volatile("ld.relaxed.gpu.global.u32 %0, [%1];" : "=r"(v) : "l"(sc->ready[(b & ~3) + (lane & 3)]) : "memory");
        } while (__any_sync(0xffffffffu, v - 1 != prev) && ++spin < SPIN_LIMIT);
        bar_arrive(BAR_RDY, 160);
PROF_MARK(3);
        bar_sync(BAR_V, 160);
      }
      if (lane == 0) {
        asm volatile("cp.async.bulk.global.shared::cta.bulk_group [%0], [%1], %2;"
                     :: "l"(&sc->kv[batch * 4 + r][kind][t][0]), "r"(SM_BASE + SM_STG + kind * TILE_BYTES), "r"(TILE_BYTES) : "memory");
PROF_MARK(4 + kind * 2);
        asm volatile("cp.async.bulk.commit_group;\ncp.async.bulk.wait_group 0;" ::: "memory");
PROF_MARK(5 + kind * 2);
        asm volatile("st.relaxed.gpu.global.u32 [%0], %1;" :: "l"(sc->flag[batch * 4 + r][kind * 16 + t]), "r"(prev + 1) : "memory");
      }
    } else {
      const uint32_t epoch = ((volatile uint32_t*)sc->epoch)[b] + 1;
      if (lane == 0 && epoch) {
        asm volatile("prefetch.tensormap [%0];" :: "l"(&p.map[M_FF1B]) : "memory");
        l2_prefetch(p.w_ff1b, 1024 * 256 * 2, b);
        l2_prefetch(p.w_qkv, 256 * 768 * 2, b);
        l2_prefetch(p.w_pw1, 256 * 512 * 2, b);
        l2_prefetch(p.w_ff2a, 256 * 1024 * 2, b);
      }
#pragma unroll 1
      for (int i = 0; i < 11; i++) {
        const uint32_t t0 = clock_now();
        uint4* dst = &sc->x[b][X_CLEAR + i * 96 + lane];
        st_vec(dst, 0u, 0u, 0u, 0u); st_vec(dst + 32, 0u, 0u, 0u, 0u); st_vec(dst + 64, 0u, 0u, 0u, 0u);
        while (clock_now() - t0 < 100) {}
      }
PROF_MARK(28);
      asm volatile("fence.acq_rel.gpu;" ::: "memory");
      __syncwarp();
      if (lane == 0) {
        asm volatile("st.relaxed.gpu.global.u32 [%0], %1;" :: "l"(sc->ready[b]), "r"(epoch) : "memory");
        l2_prefetch(p.w_o, 256 * 256 * 2, b);
        l2_prefetch(p.w_pw2, 256 * 256 * 2, b);
        l2_prefetch(p.w_ff2b, 1024 * 256 * 2, b);
#pragma unroll
        for (int i = M_QKV; i < M_X; i++) asm volatile("prefetch.tensormap [%0];" :: "l"(&p.map[i]) : "memory");
      }
      PROF_MARK(2);
    }
  } else {
    asm volatile("setmaxnreg.inc.sync.aligned.u32 232;");
    const int q = lane & 3, th = tid & 127;
    constexpr uint32_t stg = SM_BASE + SM_STG;
    const uint32_t mrow = 16 * w + (lane & 15);
    const uint32_t maddr = stg + mrow * 128 + (((lane >> 4) ^ (lane & 7)) << 4);
    const uint32_t qslot = stg + 2 * TILE_BYTES + w * 2048 + lane * 16;
    uint4* const xp = &sc->x[b][th];
    const int nvalid = T_SEQ - t * 64, row0 = 16 * w + (lane >> 2);

    uint32_t A[4][16];
    uint32_t sent = 0;
    uint32_t st[4];
    if (tid < 144) sts128(SM_BASE + SM_CS + tid * 16, 0, 0, 0, 0);
    if (wg == 1) sts32(SM_BASE + SM_EYE + th * 4, th >= 96 ? 0x3F803F80u : ((th & 32) == 0 && (th & 3) == ((th >> 3) & 3)) ? (0x3F00u << ((th & 4) * 4)) : 0u);
    fence_async_smem();
    bar_sync(0, 320);
    if (wg == 0) {
      mbar_wait(SM_BASE + SM_XBAR, 0);
      PROF_MARK(1);
      RowAcc ra[2] = {};
#pragma unroll
      for (int c = 0; c < 4; c++) {
        tile_load(maddr + (3 - c) * TILE_BYTES, A[c]);
        row_acc(ra[c & 1], A[c]);
      }
      const float s0 = ra[0].s[0] + ra[1].s[0], s1 = ra[0].s[2] + ra[1].s[2];
      st[0] = pack2(s0 * (1.f / DM), s0 * (1.f / DM)); st[1] = pack2(s1 * (1.f / DM), s1 * (1.f / DM));
      centre(A[0], st[0], st[1]);
      const float2 qa = row_squares(ra[0], lane & 4), qb = row_squares(ra[1], lane & 4);
      const int src = (lane & 28) | (lane >> 3);
      const RowNorm n = row_norm(s0, __shfl_sync(0xffffffffu, qa.x + qb.x, src), s1, __shfl_sync(0xffffffffu, qa.y + qb.y, src), 0.5f);
      st[2] = __float_as_uint(n.rs0); st[3] = __float_as_uint(n.rs1);
    } else {
      const uint32_t epoch = ((volatile uint32_t*)sc->epoch)[b] + 1, tag = epoch & 1;
      mbar_wait(SM_BASE + SM_FULL + 4 * 8, 0);
      PROF_MARK(5);
      if (b < 72) {
        const __nv_bfloat16* wp; int ld, col;
        if (b < 24) { wp = p.w_qkv; ld = 768; col = b * 32; }
        else if (b < 40) { wp = p.w_pw1; ld = 512; col = (b - 24) * 32; }
        else { wp = p.w_ff2a; ld = 1024; col = (b - 40) * 32; }
        const uint4* src = (const uint4*)(wp + (size_t)(th >> 2) * ld + col + q * 8);
        float c[8] = {0.f, 0.f, 0.f, 0.f, 0.f, 0.f, 0.f, 0.f};
#pragma unroll 1
        for (int h = 0; h < 2; h++, src += 16 * ld) {
#pragma unroll
          for (int i = 0; i < 4; i++) {
            const uint4 v = __ldg(src + i * 4 * ld);
            c[0] += bf_lo(v.x); c[1] += bf_hi(v.x); c[2] += bf_lo(v.y); c[3] += bf_hi(v.y);
            c[4] += bf_lo(v.z); c[5] += bf_hi(v.z); c[6] += bf_lo(v.w); c[7] += bf_hi(v.w);
          }
        }
#pragma unroll 1
        for (int m = 4; m <= 16; m <<= 1)
#pragma unroll
          for (int k = 0; k < 8; k++) c[k] += __shfl_xor_sync(0xffffffffu, c[k], m);
        if (lane < 4) {
          const uint32_t a = SM_BASE + SM_CS + 1792 + w * 128 + lane * 32;
          sts128(a, __float_as_uint(c[0]), __float_as_uint(c[1]), __float_as_uint(c[2]), __float_as_uint(c[3]));
          sts128(a + 16, __float_as_uint(c[4]), __float_as_uint(c[5]), __float_as_uint(c[6]), __float_as_uint(c[7]));
        }
        bar_sync(BAR_WG1, 128);
        if (th < 8) {
          float o[4] = {0.f, 0.f, 0.f, 0.f};
#pragma unroll 1
          for (int k = 0; k < 4; k++) {
            uint32_t e[4];
            lds128(SM_BASE + SM_CS + 1792 + k * 128 + th * 16, e[0], e[1], e[2], e[3]);
#pragma unroll
            for (int i = 0; i < 4; i++) o[i] += __uint_as_float(e[i]);
          }
          st_vec(&sc->cs[b * 8 + th], (__float_as_uint(o[0]) & ~1u) | tag, __float_as_uint(o[1]), __float_as_uint(o[2]), __float_as_uint(o[3]));
        }
      }
      bar_sync(BAR_WG1, 128);
      PROF_MARK(2);
      if (th < 72) {
        const int j = th >> 3, i = (th & 7) * 2;
        int src;
        if (j < CS_PW1) src = 320 + 64 * r + 16 * j;
        else if (j < CS_QKV) src = 192 + (j - CS_PW1) * 64 + 16 * r;
        else src = ((j - CS_QKV + 1) % 3) * 64 + 16 * r;
        uint32_t e[8], hi[4], lo[4], spin = 0;
#pragma unroll 1
        do {
          ld_vec(&sc->cs[src + i], e[0], e[1], e[2], e[3]);
          ld_vec(&sc->cs[src + i + 1], e[4], e[5], e[6], e[7]);
        } while ((((e[0] ^ tag) | (e[4] ^ tag)) & 1u) && ++spin < SPIN_LIMIT);
        e[0] &= ~1u; e[4] &= ~1u;
#pragma unroll
        for (int k = 0; k < 4; k++) {
          const float c0 = __uint_as_float(e[2 * k]), c1 = __uint_as_float(e[2 * k + 1]);
          hi[k] = pack2(c0, c1);
          lo[k] = pack2(c0 - bf_lo(hi[k]), c1 - bf_hi(hi[k]));
        }
        const uint32_t a = SM_BASE + SM_CS + j * 256 + i * 8;
        sts128(a ^ ((a >> 3) & 0x70), hi[0], hi[1], hi[2], hi[3]);
        sts128((a + 128) ^ (((a + 128) >> 3) & 0x70), lo[0], lo[1], lo[2], lo[3]);
      }
      fence_async_smem();
      PROF_MARK(4);
      bar_arrive(BAR_CS, 256);
    }

#pragma unroll 1
    for (uint32_t pass = 0; pass < 2; pass++) {
      uint32_t Q[16];
      if (wg == 0) {
        float acc[4][32];
        uint32_t H[4][16];
        if (!pass) { PROF_MARK(47); ACQUIRE(0); }
        mma_tile<true>(acc[0], A[0], LO(0)); mma_tile<true>(acc[1], A[0], HI(0));
        if (!pass) ACQUIRE(1);
        mma_tile<true>(acc[2], A[0], LO(1)); mma_tile<true>(acc[3], A[0], HI(1));
        if (pass) {
          gather_first<1, X_AG0>(A, st, sc, xp, 1, sent);
        } else {
          centre(A[1], st[0], st[1]);
          acquire_n<2, 3>();
        }
        mma_tile<false>(acc[0], A[1], LO(2)); mma_tile<false>(acc[1], A[1], HI(2));
        if (pass) {
          gather_rest<1, X_AG0>(A, xp, 1);
          RELEASE(F_PW2, F_PW2 + 1);
        } else {
          centre(A[2], st[0], st[1]); centre(A[3], st[0], st[1]);
        }
        PROF_MARK2(2, 18);
        mma_tile<false>(acc[0], A[2], LO(3)); mma_tile<false>(acc[0], A[3], LO(4));
        WG_WAIT(4);
        RELEASE(0, 1);
        uint32_t mu[4] = {0u, 0u, 0u, 0u};
        float rs0 = __uint_as_float(st[2]), rs1 = __uint_as_float(st[3]), tn[2][4];
        if (pass) {
          const RowNorm n = stat_finish(sc, st, 1, 0.5f);
          rs0 = n.rs0; rs1 = n.rs1;
          mean_frag(mu, n, q == 0);
        }
        pin(mu);
        mma_fold<2 * CS_FF2>(acc[0], mu);
        mma_tile<false>(acc[1], A[2], HI(3));
#define SEGS(a, b) silu_segs<a, b>(acc, tn, H, rs0, rs1)
        WG_WAIT(1); pin(acc[0]);
        SEGS(0, 1);
        mma_tile_fold<2 * CS_FF2 + 2>(acc[1], A[3], HI(4), mu);
        SEGS(1, 3);
        uint32_t ok = probe_n<5, 3>();
        SEGS(3, 4);
        settle_n<5, 3>(ok);
        mma_tile<false>(acc[2], A[1], LO(5));
        SEGS(4, 6);
        mma_tile<false>(acc[2], A[2], LO(6));
        SEGS(6, 8);
        WG_WAIT(2); pin(acc[1]);
        RELEASE(2, 4);
        SEGS(8, 9);
        mma_tile_fold<2 * CS_FF2 + 4>(acc[2], A[3], LO(7), mu);
        SEGS(9, 12);
        mma_tile<false>(acc[3], A[1], HI(5));
        SEGS(12, 14);
        mma_tile<false>(acc[3], A[2], HI(6));
        SEGS(14, 16);
        WG_WAIT(2); pin(acc[2]);
        SEGS(16, 17);
        mma_tile_fold<2 * CS_FF2 + 6>(acc[3], A[3], HI(7), mu);
        SEGS(17, 19);
        ok = probe_n<8, 2>();
        SEGS(19, 20);
        settle_n<8, 2>(ok);
        mma_tile_reuse(acc[1], H[0], LO(8));
        SEGS(20, 22);
        mma_tile<false>(acc[1], H[1], HI(8));
        SEGS(22, 24);
        WG_WAIT(2); pin(acc[3]);
        RELEASE(5, 7);
        SEGS(24, 26);
        mma_tile<false>(acc[1], H[2], LO(9));
        SEGS(26, 27);
        ok = probe_n<10, 2>();
        SEGS(27, 28);
        settle_n<10, 2>(ok);
        mma_tile_reuse(acc[2], H[0], LO(10));
        SEGS(28, 31);
        mma_tile<false>(acc[2], H[1], HI(10));
        SEGS(31, 34);
#undef SEGS
        PROF_MARK2(3, 19);
        const uint32_t rtag = here(pass ^ 1);
        const uint4* rs_in = xp + X_RS;
        mma_tile<false>(acc[1], H[3], HI(9));
        mma_tile<false>(acc[2], H[2], LO(11));
        ok = probe_n<12, 2>();
        uint4* rs_out = peer<1>(xp) + X_RS;
        mma_tile<false>(acc[2], H[3], HI(11));
        settle_n<12, 2>(ok);
        WG_WAIT(2); pin(acc[1]);
        RELEASE(8, 9);
        send_half<0>(rs_out, acc[1], rtag);
        mma_tile_reuse(acc[3], H[0], LO(12));
        SCHED();
        send_half<1>(rs_out, acc[1], rtag);
        mma_tile<false>(acc[3], H[1], HI(12));
        rs_out = peer<2>(xp) + X_RS + 512;
        WG_WAIT(2); pin(acc[2]);
        send_half<0>(rs_out, acc[2], rtag);
        mma_tile<false>(acc[3], H[2], LO(13));
        SCHED();
        ok = probe_n<14, 2>();
        send_half<1>(rs_out, acc[2], rtag);
        mma_tile<false>(acc[3], H[3], HI(13));
        settle_n<14, 2>(ok);
        mma_tile_reuse(acc[1], H[0], LO(14));
        rs_out = peer<3>(xp) + X_RS + 1024;
        if (!pass) bar_sync(BAR_RDY, 160);
        fetch(rs_in, A[1]);
        SCHED();
        mma_tile<false>(acc[1], H[1], HI(14));
        WG_WAIT(2); pin(acc[3]);
        send_half<0>(rs_out, acc[3], rtag);
        send_half<1>(rs_out, acc[3], rtag);
        sent = clock_now();
        mma_tile<false>(acc[1], H[2], LO(15)); mma_tile<false>(acc[1], H[3], HI(15));
        SCHED();
        fetch(rs_in + 512, A[2]);
        SCHED();
        res_load(maddr, acc[2]);
        while (clock_now() - sent < GATHER_DELAY) {}
        fetch(rs_in + 1024, A[3]);
        if (!pass) acquire_n<F_QKV, 3>();
        {
          uint32_t spin = 0;
          while (__builtin_expect(stale(miss(A[1], rtag) | miss(A[2], rtag) | miss(A[3], rtag)), 0) && ++spin < SPIN_LIMIT) {
            if (stale(miss(A[1], rtag) | miss(A[2], rtag))) { fetch(rs_in, A[1]); fetch(rs_in + 512, A[2]); }
            fetch(rs_in + 1024, A[3]);
          }
        }
        mma_add_half(acc[2], A[1]);
        mma_add_half(acc[2], A[2]);
        mma_add_half(acc[2], A[3]);
        PROF_MARK2(4, 20);
        WG_WAIT(0); pin(acc[2]); pin(acc[1]);
#pragma unroll
        for (int i = 0; i < 16; i++) A[0][i] = pack2(fmaf(acc[1][2 * i], 0.5f, acc[2][2 * i]), fmaf(acc[1][2 * i + 1], 0.5f, acc[2][2 * i + 1]));
        if (pass) {
          PROF_MARK(21);
          stat_publish(A[0], sc, here(th), 0);
          stat_fetch(sc, st);
          const RowNorm fn = stat_finish(sc, st, 0, 1.f);
          const float nm0 = -fn.m0 * fn.rs0, nm1 = -fn.m1 * fn.rs1;
#pragma unroll
          for (int i = 0; i < 16; i++) {
            const float rs = (i & 1) ? fn.rs1 : fn.rs0, nm = (i & 1) ? nm1 : nm0;
            A[0][i] = pack2(fmaf(bf_lo(A[0][i]), rs, nm), fmaf(bf_hi(A[0][i]), rs, nm));
          }
          tile_store(here(maddr), A[0]);
          __syncwarp();
          const int row = 16 * w + (lane >> 3);
          uint4* dst = (uint4*)(out + ((size_t)batch * T_SEQ + t * 64 + row) * DM + 64 * r) + (lane & 7);
          const uint32_t src = stg + row * 128 + (((lane & 7) ^ (lane >> 3)) << 4);
#pragma unroll
          for (int i = 0; i < 4; i++) {
            uint4 v;
            lds128((src ^ ((i & 1) << 6)) + i * 512, v.x, v.y, v.z, v.w);
            if (row + 4 * i < nvalid) dst[i * 4 * (DM / 8)] = v;
          }
          PROF_MARK(22);
          PROF_TIME(31);
          break;
        }
        sent = send_residual(A[0], sc, xp, maddr, 1);
        PROF_MARK(5);
        mma_tile<true>(acc[0], A[0], LO(F_QKV)); mma_tile<true>(acc[1], A[0], HI(F_QKV));
        mma_tile<true>(acc[2], A[0], LO(F_QKV + 1));
        gather_first<1, X_AG0>(A, st, sc, xp, 1, sent);
        mma_tile<false>(acc[0], A[1], LO(F_QKV + 2)); mma_tile<false>(acc[1], A[1], HI(F_QKV + 2));
        acquire_n<F_QKV + 3, 3>();
        bar_sync(BAR_CS, 256);
        gather_rest<1, X_AG0>(A, xp, 1);
        PROF_MARK(6);
        mma_tile<false>(acc[0], A[2], LO(F_QKV + 3)); mma_tile<false>(acc[0], A[3], LO(F_QKV + 4));
        SCHED();
        {
          const RowNorm n = stat_finish(sc, st, 1, 1.f);
          rs0 = row0 < nvalid ? n.rs0 : 0.f; rs1 = row0 + 8 < nvalid ? n.rs1 : 0.f;
          mean_frag(mu, n, q == 3);
        }
        mma_fold<2 * CS_QKV - 6>(acc[0], mu);
        RELEASE(10, 15);
        WG_WAIT(0); pin(acc[0]);
        scale_pack(acc[0], Q, rs0, rs1);
        tile_store(here(maddr), Q);
        SCHED();
        mma_tile<false>(acc[1], A[2], HI(F_QKV + 3));
        fence_async_smem();
        bar_arrive(BAR_K, 160);
        mma_tile_fold<2 * CS_QKV - 4>(acc[1], A[3], HI(F_QKV + 4), mu);
        mma_tile<false>(acc[2], A[1], HI(F_QKV + 1)); mma_tile<false>(acc[2], A[2], LO(F_QKV + 5));
        WG_WAIT(2); pin(acc[1]);
        scale_pack(acc[1], Q, rs0, rs1);
        tile_store(here(maddr) + TILE_BYTES, Q);
        fence_async_smem();
        bar_arrive(BAR_V, 160);
        mma_tile_fold<2 * CS_QKV - 2>(acc[2], A[3], HI(F_QKV + 5), mu);
        WG_WAIT(0); pin(acc[2]);
        scale_pack(acc[2], Q, rs0 * SM_SCALE_LOG2, rs1 * SM_SCALE_LOG2);
        frag_store(here(qslot), Q);
        bar_arrive(BAR_Q, 256);
        RELEASE(F_QKV, F_QKV + 5);
      } else {
        bar_sync(BAR_Q, 256);
#pragma unroll
        for (int s = 0; s < 4; s++) lds128(qslot + s * 512, Q[4 * s], Q[4 * s + 1], Q[4 * s + 2], Q[4 * s + 3]);
        if (w < 2) {
          const uint32_t v = w ? 0u : 0x3F803F80u;
#pragma unroll
          for (int s = 0; s < 4; s++) sts128(qslot + s * 512, v, v, v, v);
          fence_async_smem();
        }
      }
      bar_sync(BAR_ATT, 256);
      PROF_MARK(7);

      const int dir = cw == 0 ? -1 : 1;
      uint32_t tap[15];
      {
        const uint32_t* dwp = (const uint32_t*)(dw + 64 * r) + lane + 7 * (DM / 2);
#pragma unroll
        for (int k = 0; k < 15; k++) tap[k] = __ldg(dwp + dir * (k - 7) * (DM / 2));
      }

      float O[36];
      {
        float S[2][32];
        uint32_t P[2][16], nm[4];
#pragma unroll
        for (int i = 0; i < 32; i++) { S[0][i] = 0.f; S[1][i] = 0.f; }
        pin(Q); pin(S[0]);
        WG_FENCE();
        qk_tile(S[0], Q, RING_K + (SM_STG >> 4));
        WG_COMMIT();
#pragma unroll
        for (int i = 0; i < 36; i++) O[i] = 0.f;
#pragma unroll
        for (int i = 0; i < 16; i++) P[1][i] = 0u;
        WG_WAIT(0); pin(S[0]);
        const float m0 = tile_max<0>(S[0]), m1 = tile_max<2>(S[0]);
        nm[0] = pack2(q ? 0.f : -m0, 0.f); nm[1] = pack2(q ? 0.f : -m1, 0.f); nm[2] = 0u; nm[3] = 0u;
#pragma unroll
        for (int k = 0; k < 15; k++) asm("mul.rn.bf16x2 %0, %0, %1;" : "+r"(tap[k]) : "r"(0x3F003F00u));
        pin(nm); pin(O); pin(P[1]); pin(tap);
        uint32_t sk = wg, sv = F_SPARE % NSTAGE + wg;
        mbar_wait(SM_BASE + SM_FULL + sv * 8, 1);
        mbar_wait(SM_BASE + SM_FULL + sk * 8, 0);
        PROF_MARK(8);
        WG_FENCE();
        qk_tile(S[0], Q, RING_K + sk * 1024);
        qk_shift(S[0], nm);
        WG_COMMIT();
        WG_WAIT(0); pin(S[0]); pin(S[1]);
#pragma unroll 1
        for (int it = 0; it < 4; it++) {
          const uint32_t sn = it >= 2 ? wg : sk + 4;
          uint32_t ok = 1;
          mbar_probe(ok, SM_BASE + SM_FULL + sn * 8, it >= 2);
          mbar_probe(ok, SM_BASE + SM_FULL + (sk + 2) * 8, it == 3);
          attn_step(S[0], S[1], P[0], P[1], O, Q, nm, RING_K + sk * 1024 + 512, RING_V + (sv * 1024 + 512) * V_STEP, true, it > 0);
          if (__builtin_expect(!ok, 0)) {
            mbar_wait(SM_BASE + SM_FULL + sn * 8, it >= 2);
            mbar_wait(SM_BASE + SM_FULL + (sk + 2) * 8, it == 3);
          }
          WG_WAIT(0); pin(O); pin(S[1]); pin(P[1]);
          asm volatile("{\n.reg .pred p;\nsetp.eq.u32 p, %2, 0;\n@p mbarrier.arrive.shared::cta.b64 _, [%0];\n@p mbarrier.arrive.shared::cta.b64 _, [%1];\n}"
                       :: "r"(SM_BASE + SM_EMPTY + sk * 8), "r"(SM_BASE + SM_EMPTY + sv * 8), "r"(lane) : "memory");
          sv = sk + 2; sk = sn;
          attn_step(S[1], S[0], P[1], P[0], O, Q, nm, RING_K + sk * 1024, RING_V + (sv * 1024) * V_STEP, it < 3, true);
          WG_WAIT(0); pin(O); pin(S[0]); pin(P[0]);
        }
        WG_FENCE();
        pv_tile(O, P[1], RING_V + (sv * 1024 + 512) * V_STEP, wg << 22);
        WG_COMMIT();
        WG_WAIT(0); pin(O);
      }
      PROF_MARK(9);

      {
        const uint32_t mo = stg + here(th) * 16;
        sts64(mo + 5 * 4096 + wg * 8, __float_as_uint(O[32]), __float_as_uint(O[34]));
        if (wg == 0) {
#pragma unroll
          for (int i = 4; i < 8; i++)
            sts128(mo + i * 2048, __float_as_uint(O[4 * i]), __float_as_uint(O[4 * i + 1]), __float_as_uint(O[4 * i + 2]), __float_as_uint(O[4 * i + 3]));
        } else {
#pragma unroll
          for (int i = 0; i < 4; i++)
            sts128(mo + i * 2048, __float_as_uint(O[4 * i]), __float_as_uint(O[4 * i + 1]), __float_as_uint(O[4 * i + 2]), __float_as_uint(O[4 * i + 3]));
#pragma unroll
          for (int i = 0; i < 16; i++) O[i] = O[16 + i];
        }
        bar_sync(BAR_MERGE, 256);
        uint32_t e[4];
        lds128(mo + 5 * 4096, e[0], e[1], e[2], e[3]);
        O[32] = __uint_as_float(e[0]) + __uint_as_float(e[2]); O[34] = __uint_as_float(e[1]) + __uint_as_float(e[3]);
#pragma unroll
        for (int i = 0; i < 4; i++) {
          lds128(mo + wg * TILE_BYTES + i * 2048, e[0], e[1], e[2], e[3]);
#pragma unroll
          for (int k = 0; k < 4; k++) O[4 * i + k] += __uint_as_float(e[k]);
        }
        const bool safe = O[32] > 0x1p-60f && O[32] < 0x1p60f && O[34] > 0x1p-60f && O[34] < 0x1p60f;
        if (__builtin_expect(__any_sync(0xffffffffu, !safe), 0)) attention_exact(O, Q, sc, batch * 4 + r, lane, wg);
        const float i0 = rcp_hw(O[32]), i1 = rcp_hw(O[34]);
#pragma unroll
        for (int i = 0; i < 8; i++) { const float v = (i & 1) ? i1 : i0; A[0][i] = pack2(O[2 * i] * v, O[2 * i + 1] * v); }
        A[0][0] &= ~1u; A[0][4] &= ~1u;
        uint4* dst = xp + X_AG1 + wg * 256;
        SCHED();
        st_vec(dst, A[0][0], A[0][1], A[0][2], A[0][3]);
        st_vec(dst + 128, A[0][4], A[0][5], A[0][6], A[0][7]);
        SCHED();
        sent = clock_now();
      }
      if (wg == 1) {
        const uint32_t mo = stg + TILE_BYTES + here(th) * 16;
        sts128(mo, A[0][0], A[0][1], A[0][2], A[0][3]);
        sts128(mo + 2048, A[0][4], A[0][5], A[0][6], A[0][7]);
        bar_arrive(BAR_HALF, 256);
      } else {
        PROF_MARK(10);
        const uint32_t mo = stg + TILE_BYTES + here(th) * 16;
        bar_sync(BAR_HALF, 256);
        lds128(mo, A[0][8], A[0][9], A[0][10], A[0][11]);
        lds128(mo + 2048, A[0][12], A[0][13], A[0][14], A[0][15]);
        sent = proj_residual<F_WO, 6>(A, sc, xp, maddr, 0, sent);
        PROF_MARK(12);
        float acc[2][32];
        mma_tile<true>(acc[0], A[0], LO(F_PW1)); mma_tile<true>(acc[1], A[0], HI(F_PW1));
        gather_first<1, X_AG0>(A, st, sc, xp, 0, sent);
        mma_tile<false>(acc[1], A[1], HI(F_PW1 + 1)); mma_tile<false>(acc[0], A[1], LO(F_PW1 + 1));
        gather_rest<1, X_AG0>(A, xp, 0);
        PROF_MARK(13);
        mma_tile<false>(acc[1], A[2], HI(F_PW1 + 2)); mma_tile<false>(acc[1], A[3], HI(F_PW1 + 3));
        SCHED();
        uint32_t mu[4];
        const RowNorm n = stat_finish(sc, st, 0, 0.5f);
        const float rs0 = row0 < nvalid ? n.rs0 : 0.f, rs1 = row0 + 8 < nvalid ? n.rs1 : 0.f;
        mean_frag(mu, n, q == 0);
        mma_fold<2 * CS_PW1 + 2>(acc[1], mu);
        RELEASE(F_KV + 14, F_WO + 1);
        mma_tile<false>(acc[0], A[2], LO(F_PW1 + 2));
        mma_tile_fold<2 * CS_PW1>(acc[0], A[3], LO(F_PW1 + 3), mu);
        WG_WAIT(2); pin(acc[1]);
#pragma unroll
        for (int i = 0; i < 32; i++) acc[1][i] = tanh_hw(acc[1][i] * ((i & 2) ? rs1 : rs0));
#pragma unroll
        for (int i = 0; i < 32; i++) { const float rs = (i & 2) ? rs1 : rs0; acc[1][i] = fmaf(acc[1][i], rs, rs); }
        pin(acc[1]);
        SCHED();
        WG_WAIT(0); pin(acc[0]);
#pragma unroll
        for (int i = 0; i < 16; i++) A[0][i] = pack2(acc[0][2 * i] * acc[1][2 * i], acc[0][2 * i + 1] * acc[1][2 * i + 1]);
        const uint32_t ga = stg + TILE_BYTES + here(mrow) * G_PITCH + (lane >> 4) * 16;
#pragma unroll
        for (int s = 0; s < 4; s++) stsm4(ga + s * 32, &A[0][4 * s]);
        RELEASE(F_PW1, F_PW1 + 3);
      }
      {
        const uint32_t gsrc = stg + TILE_BYTES + (8 * cw - 7) * G_PITCH + lane * 4;
        const bool edge = cw == 0 || cw == 7;
        const bool nbr = cw == 0 ? t > 0 : t < 15;
        uint4* const hdst = &sc->x[b + 4 * dir][X_HALO + (cw == 0 ? 96 : 0) + lane];
        uint32_t in[22];
        bar_sync(BAR_G, 256);
        PROF_MARK(14);
        if (cw == 0) {
#pragma unroll
          for (int i = 14; i >= 0; i--) in[i] = lds32(gsrc + (21 - i) * G_PITCH);
        } else {
#pragma unroll
          for (int i = 14; i >= 0; i--) in[i] = lds32(gsrc + i * G_PITCH);
        }
        if (edge) {
          if (nbr) {
            st_vec(hdst, HALO_TAG, in[14], in[13], in[12]);
            st_vec(hdst + 32, HALO_TAG, in[11], in[10], in[9]);
            st_vec(hdst + 64, HALO_TAG, in[8], 0u, 0u);
          }
        } else {
#pragma unroll
          for (int i = 15; i < 22; i++) in[i] = lds32(gsrc + i * G_PITCH);
        }
        uint32_t cv[8];
#pragma unroll
        for (int i = 0; i < 15; i++)
#pragma unroll
          for (int o = 0; o < 8; o++) {
            if (i == o) asm("mul.rn.bf16x2 %0, %1, %2;" : "=r"(cv[o]) : "r"(in[i]), "r"(tap[0]));
            if (i > o) asm("fma.rn.bf16x2 %0, %1, %2, %0;" : "+r"(cv[o]) : "r"(in[i]), "r"(tap[i - o]));
          }
        pin(cv);
        if (edge) {
#pragma unroll
          for (int i = 15; i < 22; i++) in[i] = 0u;
          if (nbr) {
            const uint4* src = &sc->x[b][X_HALO + (cw == 0 ? 0 : 96) + lane];
            uint32_t e0, e1, e2, u0, u1, spin = 0;
#pragma unroll 1
            do {
              ld_vec(src, e0, in[15], in[16], in[17]);
              ld_vec(src + 32, e1, in[18], in[19], in[20]);
              ld_vec(src + 64, e2, in[21], u0, u1);
            } while (__any_sync(0xffffffffu, ((e0 ^ HALO_TAG) | (e1 ^ HALO_TAG) | (e2 ^ HALO_TAG)) != 0) && ++spin < SPIN_LIMIT);
          }
        }
#pragma unroll
        for (int i = 15; i < 22; i++)
#pragma unroll
          for (int o = 0; o < 8; o++)
            if (i - o <= 14) asm("fma.rn.bf16x2 %0, %1, %2, %0;" : "+r"(cv[o]) : "r"(in[i]), "r"(tap[i - o]));
        const uint32_t fl = cw == 0 ? 7 : 0;
        const uint32_t cdst = (stg + cw * 1024 + lane * 4) ^ (fl * 144);
#pragma unroll
        for (int o = 0; o < 8; o++) {
          const float a = bf_lo(cv[o]), c = bf_hi(cv[o]);
          sts32(cdst ^ (o * 144), pack2(fmaf(a, tanh_hw(a), a), fmaf(c, tanh_hw(c), c)));
        }
      }
      if (wg == 1) {
        bar_arrive(BAR_C, 256);
        if (th == 0) ((volatile uint32_t*)sc->epoch)[b] += 1;
        break;
      }
      bar_sync(BAR_C, 256);
      tile_load(here(maddr), A[0]);
      PROF_MARK(15);
      publish(xp + X_AG1, A[0], 1);
      sent = proj_residual<F_PW2, 2>(A, sc, xp, maddr, 1, clock_now());
      PROF_MARK(17);
    }
  }
}

typedef CUresult (*EncodeFn)(CUtensorMap*, CUtensorMapDataType, cuuint32_t, void*, const cuuint64_t*, const cuuint64_t*,
                             const cuuint32_t*, const cuuint32_t*, CUtensorMapInterleave, CUtensorMapSwizzle,
                             CUtensorMapL2promotion, CUtensorMapFloatOOBfill);

void make_map(EncodeFn fn, CUtensorMap* m, const void* w, int rows, int cols, CUtensorMapSwizzle swz) {
  const cuuint64_t dims[2] = {(cuuint64_t)cols, (cuuint64_t)rows}, strides[1] = {(cuuint64_t)cols * 2};
  const cuuint32_t box[2] = {64, 64}, es[2] = {1, 1};
  fn(m, CU_TENSOR_MAP_DATA_TYPE_BFLOAT16, 2, const_cast<void*>(w), dims, strides, box, es, CU_TENSOR_MAP_INTERLEAVE_NONE,
     swz, CU_TENSOR_MAP_L2_PROMOTION_L2_128B, CU_TENSOR_MAP_FLOAT_OOB_FILL_NONE);
}

}

extern "C" void kernel_launch(void* const* d_in, const int* in_sizes, int n_in, void* d_out, int out_size) {
  static EncodeFn fn = nullptr;
  static Scratch* sc = nullptr;
  if (!fn) {
    void* f = nullptr;
    cudaDriverEntryPointQueryResult st;
    cudaGetDriverEntryPoint("cuTensorMapEncodeTiled", &f, cudaEnableDefault, &st);
    fn = (EncodeFn)f;
    void* raw = nullptr;
    cudaGetSymbolAddress(&raw, g_scratch);
    sc = (Scratch*)(((uintptr_t)raw + X_ALIGN - 1) & ~(uintptr_t)(X_ALIGN - 1));
    cudaFuncSetAttribute(conformer_kernel, cudaFuncAttributeMaxDynamicSharedMemorySize, SM_TOTAL);
  }
  typedef const __nv_bfloat16* W;
  const CUtensorMapSwizzle S = CU_TENSOR_MAP_SWIZZLE_128B;
  Params p;
  {
    const cuuint64_t dims[3] = {DM, T_SEQ, 2}, strides[2] = {DM * 2, T_SEQ * DM * 2};
    const cuuint32_t box[3] = {64, 64, 1}, es[3] = {1, 1, 1};
    fn(&p.map[M_X], CU_TENSOR_MAP_DATA_TYPE_BFLOAT16, 3, d_in[0], dims, strides, box, es, CU_TENSOR_MAP_INTERLEAVE_NONE, S,
       CU_TENSOR_MAP_L2_PROMOTION_L2_128B, CU_TENSOR_MAP_FLOAT_OOB_FILL_NONE);
  }
  make_map(fn, &p.map[M_FF1A], d_in[1], 256, 1024, S);
  make_map(fn, &p.map[M_FF1B], d_in[2], 1024, 256, S);
  make_map(fn, &p.map[M_QKV], d_in[3], 256, 768, S);
  make_map(fn, &p.map[M_KV], sc->kv, 16384, 64, CU_TENSOR_MAP_SWIZZLE_NONE);
  make_map(fn, &p.map[M_WO], d_in[4], 256, 256, S);
  make_map(fn, &p.map[M_PW1], d_in[5], 256, 512, S);
  make_map(fn, &p.map[M_PW2], d_in[7], 256, 256, S);
  make_map(fn, &p.map[M_FF2A], d_in[8], 256, 1024, S);
  make_map(fn, &p.map[M_FF2B], d_in[9], 1024, 256, S);
  p.w_ff1b = (W)d_in[2]; p.w_qkv = (W)d_in[3]; p.w_o = (W)d_in[4]; p.w_pw1 = (W)d_in[5];
  p.w_pw2 = (W)d_in[7]; p.w_ff2a = (W)d_in[8]; p.w_ff2b = (W)d_in[9];

  cudaLaunchConfig_t cfg = {};
  cfg.gridDim = dim3(NCTA);
  cfg.blockDim = dim3(384);
  cfg.dynamicSmemBytes = SM_TOTAL;
  cfg.stream = cudaStreamPerThread;
  cudaLaunchAttribute at[1];
  at[0].id = cudaLaunchAttributeCooperative;
  at[0].val.cooperative = 1;
  cfg.attrs = at;
  cfg.numAttrs = 1;
  cudaLaunchKernelEx(&cfg, conformer_kernel, sc, (__nv_bfloat16*)d_out, (W)d_in[6], (W)d_in[0], (W)d_in[1], p);
}
```

```cpp
#include <cuda_runtime.h>
#include <cuda_bf16.h>
#include <cuda.h>
#include <stdint.h>

namespace {

constexpr int T_SEQ = 1000;
constexpr int DM = 256;
constexpr int NCTA = 128;
constexpr int NSTAGE = 12;
constexpr uint32_t STAGE_BYTES = 16384;
constexpr uint32_t TILE_BYTES = 8192;
constexpr uint32_t SM_BASE = 1024;
constexpr uint32_t SM_STG = NSTAGE * STAGE_BYTES;
constexpr uint32_t SM_FULL = SM_STG + 32768;
constexpr uint32_t SM_EMPTY = SM_FULL + 96;
constexpr uint32_t SM_XBAR = SM_FULL + 192;
constexpr uint32_t SM_EYE = SM_FULL + 256;
constexpr uint32_t SM_ONE = SM_FULL + 640;
constexpr uint32_t SM_CS = SM_FULL + 768;
constexpr uint32_t SM_TOTAL = SM_FULL + 3072;
constexpr int CS_FF2 = 0, CS_PW1 = 4, CS_QKV = 6;
constexpr uint32_t SPIN_LIMIT = 1u << 16;
constexpr float LN_EPS = 1e-5f;
constexpr float SM_SCALE_LOG2 = 0.125f * 1.4426950408889634f;
constexpr uint32_t G_PITCH = 144;

constexpr int F_QKV = 16, F_SPARE = 22, F_KV = 24, F_WO = 40, F_PW1 = 42, F_PW2 = 46, F_TOTAL = 64;
enum { M_FF1A, M_FF1B, M_QKV, M_WO, M_PW1, M_PW2, M_FF2A, M_FF2B, M_X, M_COUNT };
enum { BAR_K = 1, BAR_V, BAR_Q, BAR_MERGE, BAR_G, BAR_C, BAR_WG1, BAR_RDY, BAR_CS, BAR_ATT, BAR_INIT, BAR_HALF };

struct Params {
  CUtensorMap map[M_COUNT];
  const __nv_bfloat16 *w_ff1b, *w_qkv, *w_o, *w_pw1, *w_pw2, *w_ff2a, *w_ff2b;
};

constexpr int X_RS = 0, X_AG1 = X_RS, X_HALO = X_RS + 512, X_CLEAR = 1024, X_AG0 = 1536, X_ST = 2048, X_SIZE = 4096;
constexpr uint32_t HALO_TAG = 0xFFFF0001u;
struct Scratch {
  uint4 x[NCTA][X_SIZE];
  uint4 kv[8][2][16][512];
  uint4 cs[576];
  uint32_t flag[8][32][32];
  uint32_t ready[NCTA][32];
  uint32_t epoch[NCTA];
};
constexpr size_t X_ALIGN = 4 * X_SIZE * sizeof(uint4);
__device__ uint8_t g_scratch[sizeof(Scratch) + X_ALIGN];
#define PROF_TIME(i)
#define PROF_MARK(i)
#define PROF_MARK2(i, j)
#define PROF_MARK0(i)
#define PROF_AT(a)

__device__ __forceinline__ void mbar_init(uint32_t bar, uint32_t cnt) {
  asm volatile("mbarrier.init.shared::cta.b64 [%0], %1;" :: "r"(bar), "r"(cnt) : "memory");
}
__device__ __forceinline__ void mbar_wait(uint32_t bar, uint32_t parity) {
  asm volatile("{\n.reg .pred p;\n.reg .u32 c;\nmov.u32 c, 0;\n"
               "WAIT_LOOP:\nmbarrier.try_wait.parity.shared::cta.b64 p, [%0], %1;\n@p bra WAIT_DONE;\n"
               "add.u32 c, c, 1;\nsetp.lt.u32 p, c, %2;\n@p bra WAIT_LOOP;\nWAIT_DONE:\n}"
               :: "r"(bar), "r"(parity), "n"(SPIN_LIMIT) : "memory");
}
__device__ __forceinline__ void mbar_arrive(uint32_t bar) {
  asm volatile("mbarrier.arrive.shared::cta.b64 _, [%0];" :: "r"(bar) : "memory");
}
#define bar_sync(id, n) asm volatile("bar.sync %0, %1;" :: "n"((int)(id)), "n"(n) : "memory")
#define bar_arrive(id, n) asm volatile("bar.arrive %0, %1;" :: "n"((int)(id)), "n"(n) : "memory")
__device__ __forceinline__ void fence_async_smem() { asm volatile("fence.proxy.async.shared::cta;" ::: "memory"); }

__device__ __forceinline__ void st_vec(uint4* p, uint32_t a, uint32_t b, uint32_t c, uint32_t d) {
  asm volatile("{\n.reg .b128 v;\n.reg .b64 lo, hi;\nmov.b64 lo, {%1, %2};\nmov.b64 hi, {%3, %4};\nmov.b128 v, {lo, hi};\n"
               "st.relaxed.gpu.global.b128 [%0], v;\n}" :: "l"(p), "r"(a), "r"(b), "r"(c), "r"(d) : "memory");
}
__device__ __forceinline__ void ld_vec(const uint4* p, uint32_t& a, uint32_t& b, uint32_t& c, uint32_t& d) {
  asm volatile("{\n.reg .b128 v;\n.reg .b64 lo, hi;\nld.relaxed.gpu.global.b128 v, [%4];\nmov.b128 {lo, hi}, v;\n"
               "mov.b64 {%0, %1}, lo;\nmov.b64 {%2, %3}, hi;\n}" : "=r"(a), "=r"(b), "=r"(c), "=r"(d) : "l"(p) : "memory");
}
__device__ __forceinline__ void sts128(uint32_t a, uint32_t x, uint32_t y, uint32_t z, uint32_t w) {
  asm volatile("st.shared.v4.u32 [%0], {%1, %2, %3, %4};" :: "r"(a), "r"(x), "r"(y), "r"(z), "r"(w) : "memory");
}
__device__ __forceinline__ void lds128(uint32_t a, uint32_t& x, uint32_t& y, uint32_t& z, uint32_t& w) {
  asm volatile("ld.shared.v4.u32 {%0, %1, %2, %3}, [%4];" : "=r"(x), "=r"(y), "=r"(z), "=r"(w) : "r"(a) : "memory");
}
__device__ __forceinline__ uint32_t lds32(uint32_t a) {
  uint32_t x; asm volatile("ld.shared.u32 %0, [%1];" : "=r"(x) : "r"(a) : "memory"); return x;
}
__device__ __forceinline__ void sts32(uint32_t a, uint32_t x) { asm volatile("st.shared.u32 [%0], %1;" :: "r"(a), "r"(x) : "memory"); }
__device__ __forceinline__ void sts64(uint32_t a, uint32_t x, uint32_t y) {
  asm volatile("st.shared.v2.u32 [%0], {%1, %2};" :: "r"(a), "r"(x), "r"(y) : "memory");
}
__device__ __forceinline__ void stsm4(uint32_t a, const uint32_t* r) {
  asm volatile("stmatrix.sync.aligned.m8n8.x4.shared.b16 [%0], {%1, %2, %3, %4};" :: "r"(a), "r"(r[0]), "r"(r[1]), "r"(r[2]), "r"(r[3]) : "memory");
}
__device__ __forceinline__ void ldsm4(uint32_t a, uint32_t* r) {
  asm volatile("ldmatrix.sync.aligned.m8n8.x4.shared.b16 {%0, %1, %2, %3}, [%4];" : "=r"(r[0]), "=r"(r[1]), "=r"(r[2]), "=r"(r[3]) : "r"(a) : "memory");
}
__device__ __forceinline__ uint32_t pack2(float lo, float hi) {
  uint32_t r; asm("cvt.rn.bf16x2.f32 %0, %1, %2;" : "=r"(r) : "f"(hi), "f"(lo)); return r;
}
__device__ __forceinline__ float bf_lo(uint32_t w) { return __uint_as_float(w << 16); }
__device__ __forceinline__ float bf_hi(uint32_t w) { return __uint_as_float(w & 0xffff0000u); }
__device__ __forceinline__ float tanh_hw(float x) { float y; asm volatile("tanh.approx.f32 %0, %1;" : "=f"(y) : "f"(x)); return y; }
__device__ __forceinline__ float rcp_hw(float x) { float y; asm("rcp.approx.ftz.f32 %0, %1;" : "=f"(y) : "f"(x)); return y; }
__device__ __forceinline__ float rsqrt_hw(float x) { float y; asm("rsqrt.approx.ftz.f32 %0, %1;" : "=f"(y) : "f"(x)); return y; }
__device__ __forceinline__ float ex2_hw(float x) { float y; asm("ex2.approx.ftz.f32 %0, %1;" : "=f"(y) : "f"(x)); return y; }

__device__ __forceinline__ uint32_t here(uint32_t v) { asm volatile("" : "+r"(v)); return v; }

#define SCHED() asm volatile("pmevent 1;" ::: "memory")
#define WG_FENCE() asm volatile("wgmma.fence.sync.aligned;" ::: "memory")
#define WG_COMMIT() asm volatile("wgmma.commit_group.sync.aligned;" ::: "memory")
#define WG_WAIT(n) asm volatile("wgmma.wait_group.sync.aligned %0;" :: "n"(n) : "memory")

template <int N> __device__ __forceinline__ void pin(float (&d)[N]) {
#pragma unroll
  for (int i = 0; i < N; i++) asm volatile("" : "+f"(d[i]) :: "memory");
}
template <int N> __device__ __forceinline__ void pin(uint32_t (&d)[N]) {
#pragma unroll
  for (int i = 0; i < N; i++) asm volatile("" : "+r"(d[i]) :: "memory");
}

#define WG_D32 "{%0, %1, %2, %3, %4, %5, %6, %7, %8, %9, %10, %11, %12, %13, %14, %15, %16, %17, %18, %19, %20, %21, %22, %23, %24, %25, %26, %27, %28, %29, %30, %31}"
template <int TB> __device__ __forceinline__ void wgmma64_acc(float (&d)[32], const uint32_t* a, uint64_t db) {
  asm volatile("wgmma.mma_async.sync.aligned.m64n64k16.f32.bf16.bf16 " WG_D32 ", {%32, %33, %34, %35}, %36, 1, 1, 1, %37;"
    : "+f"(d[0]), "+f"(d[1]), "+f"(d[2]), "+f"(d[3]), "+f"(d[4]), "+f"(d[5]), "+f"(d[6]), "+f"(d[7]),
      "+f"(d[8]), "+f"(d[9]), "+f"(d[10]), "+f"(d[11]), "+f"(d[12]), "+f"(d[13]), "+f"(d[14]), "+f"(d[15]),
      "+f"(d[16]), "+f"(d[17]), "+f"(d[18]), "+f"(d[19]), "+f"(d[20]), "+f"(d[21]), "+f"(d[22]), "+f"(d[23]),
      "+f"(d[24]), "+f"(d[25]), "+f"(d[26]), "+f"(d[27]), "+f"(d[28]), "+f"(d[29]), "+f"(d[30]), "+f"(d[31])
    : "r"(a[0]), "r"(a[1]), "r"(a[2]), "r"(a[3]), "l"(db), "n"(TB));
}
template <int TB> __device__ __forceinline__ void wgmma64_reuse(float (&d)[32], const uint32_t* a, uint64_t db, uint32_t zero) {
  asm volatile("{\n.reg .pred p;\nsetp.ne.u32 p, %37, 0;\nwgmma.mma_async.sync.aligned.m64n64k16.f32.bf16.bf16 " WG_D32 ", {%32, %33, %34, %35}, %36, p, 1, 1, %38;\n}"
    : "+f"(d[0]), "+f"(d[1]), "+f"(d[2]), "+f"(d[3]), "+f"(d[4]), "+f"(d[5]), "+f"(d[6]), "+f"(d[7]),
      "+f"(d[8]), "+f"(d[9]), "+f"(d[10]), "+f"(d[11]), "+f"(d[12]), "+f"(d[13]), "+f"(d[14]), "+f"(d[15]),
      "+f"(d[16]), "+f"(d[17]), "+f"(d[18]), "+f"(d[19]), "+f"(d[20]), "+f"(d[21]), "+f"(d[22]), "+f"(d[23]),
      "+f"(d[24]), "+f"(d[25]), "+f"(d[26]), "+f"(d[27]), "+f"(d[28]), "+f"(d[29]), "+f"(d[30]), "+f"(d[31])
    : "r"(a[0]), "r"(a[1]), "r"(a[2]), "r"(a[3]), "l"(db), "r"(zero), "n"(TB));
}
template <int TB> __device__ __forceinline__ void wgmma64_set(float (&d)[32], const uint32_t* a, uint64_t db) {
  asm volatile("wgmma.mma_async.sync.aligned.m64n64k16.f32.bf16.bf16 " WG_D32 ", {%32, %33, %34, %35}, %36, 0, 1, 1, %37;"
    : "=f"(d[0]), "=f"(d[1]), "=f"(d[2]), "=f"(d[3]), "=f"(d[4]), "=f"(d[5]), "=f"(d[6]), "=f"(d[7]),
      "=f"(d[8]), "=f"(d[9]), "=f"(d[10]), "=f"(d[11]), "=f"(d[12]), "=f"(d[13]), "=f"(d[14]), "=f"(d[15]),
      "=f"(d[16]), "=f"(d[17]), "=f"(d[18]), "=f"(d[19]), "=f"(d[20]), "=f"(d[21]), "=f"(d[22]), "=f"(d[23]),
      "=f"(d[24]), "=f"(d[25]), "=f"(d[26]), "=f"(d[27]), "=f"(d[28]), "=f"(d[29]), "=f"(d[30]), "=f"(d[31])
    : "r"(a[0]), "r"(a[1]), "r"(a[2]), "r"(a[3]), "l"(db), "n"(TB));
}

__device__ __forceinline__ void wgmma72_acc(float (&d)[36], const uint32_t* a, uint64_t db) {
  asm volatile("wgmma.mma_async.sync.aligned.m64n72k16.f32.bf16.bf16 {%0, %1, %2, %3, %4, %5, %6, %7, %8, %9, %10, %11, %12, %13, %14, %15, %16, %17, %18, %19, %20, %21, %22, %23, %24, %25, %26, %27, %28, %29, %30, %31, %32, %33, %34, %35}, {%36, %37, %38, %39}, %40, 1, 1, 1, 1;"
    : "+f"(d[0]), "+f"(d[1]), "+f"(d[2]), "+f"(d[3]), "+f"(d[4]), "+f"(d[5]), "+f"(d[6]), "+f"(d[7]), "+f"(d[8]),
      "+f"(d[9]), "+f"(d[10]), "+f"(d[11]), "+f"(d[12]), "+f"(d[13]), "+f"(d[14]), "+f"(d[15]), "+f"(d[16]), "+f"(d[17]),
      "+f"(d[18]), "+f"(d[19]), "+f"(d[20]), "+f"(d[21]), "+f"(d[22]), "+f"(d[23]), "+f"(d[24]), "+f"(d[25]), "+f"(d[26]),
      "+f"(d[27]), "+f"(d[28]), "+f"(d[29]), "+f"(d[30]), "+f"(d[31]), "+f"(d[32]), "+f"(d[33]), "+f"(d[34]), "+f"(d[35])
    : "r"(a[0]), "r"(a[1]), "r"(a[2]), "r"(a[3]), "l"(db));
}
__device__ __forceinline__ void wgmma16_acc(float* d, const uint32_t* a, uint64_t db) {
  asm volatile("wgmma.mma_async.sync.aligned.m64n16k16.f32.bf16.bf16 {%0, %1, %2, %3, %4, %5, %6, %7}, {%8, %9, %10, %11}, %12, 1, 1, 1, 0;"
    : "+f"(d[0]), "+f"(d[1]), "+f"(d[2]), "+f"(d[3]), "+f"(d[4]), "+f"(d[5]), "+f"(d[6]), "+f"(d[7])
    : "r"(a[0]), "r"(a[1]), "r"(a[2]), "r"(a[3]), "l"(db));
}
__device__ __forceinline__ void hmma(float (&d)[4], const uint32_t* a, uint32_t b0, uint32_t b1) {
  asm("mma.sync.aligned.m16n8k16.row.col.f32.bf16.bf16.f32 {%0, %1, %2, %3}, {%4, %5, %6, %7}, {%8, %9}, {%0, %1, %2, %3};"
    : "+f"(d[0]), "+f"(d[1]), "+f"(d[2]), "+f"(d[3]) : "r"(a[0]), "r"(a[1]), "r"(a[2]), "r"(a[3]), "r"(b0), "r"(b1));
}

__device__ __forceinline__ void hmma8(float (&d)[4], const uint32_t* a, uint32_t b0) {
  asm("mma.sync.aligned.m16n8k8.row.col.f32.bf16.bf16.f32 {%0, %1, %2, %3}, {%4, %5}, {%6}, {%0, %1, %2, %3};"
    : "+f"(d[0]), "+f"(d[1]), "+f"(d[2]), "+f"(d[3]) : "r"(a[0]), "r"(a[1]), "r"(b0));
}

template <bool FIRST> __device__ __forceinline__ void mma_tile(float (&d)[32], const uint32_t (&a)[16], uint64_t db) {
  WG_FENCE();
#pragma unroll
  for (int s = 0; s < 4; s++) {
    if (FIRST && s == 0) wgmma64_set<1>(d, &a[0], db); else wgmma64_acc<1>(d, &a[4 * s], db + s * 128);
  }
  WG_COMMIT();
}
__device__ __forceinline__ void mma_tile_reuse(float (&d)[32], const uint32_t (&a)[16], uint64_t db) {
  WG_FENCE();
  wgmma64_reuse<1>(d, &a[0], db, blockIdx.y);
#pragma unroll
  for (int s = 1; s < 4; s++) wgmma64_acc<1>(d, &a[4 * s], db + s * 128);
  WG_COMMIT();
}
template <int ROW> __device__ __forceinline__ void fold_step(float (&d)[32], const uint32_t (&mu)[4]) {
  wgmma64_acc<1>(d, mu, (uint64_t)((SM_BASE + SM_CS + ROW * 128) >> 4) | (uint64_t(1) << 16) | (uint64_t(1) << 62));
}
template <int ROW> __device__ __forceinline__ void mma_fold(float (&d)[32], const uint32_t (&mu)[4]) {
  WG_FENCE();
  fold_step<ROW>(d, mu);
  WG_COMMIT();
}
template <int ROW> __device__ __forceinline__ void mma_tile_fold(float (&d)[32], const uint32_t (&a)[16], uint64_t db, const uint32_t (&mu)[4]) {
  WG_FENCE();
#pragma unroll
  for (int s = 0; s < 4; s++) wgmma64_acc<1>(d, &a[4 * s], db + s * 128);
  fold_step<ROW>(d, mu);
  WG_COMMIT();
}
__device__ __forceinline__ void mma_add_half(float (&d)[32], const uint32_t (&a)[16]) {
  const uint64_t db = (uint64_t)((SM_BASE + SM_EYE) >> 4) | (uint64_t(8) << 16) | (uint64_t(8) << 32);
  WG_FENCE();
#pragma unroll
  for (int s = 0; s < 4; s++) wgmma16_acc(&d[8 * s], &a[4 * s], db);
  WG_COMMIT();
}
#define ACQUIRE(f) mbar_wait(SM_BASE + SM_FULL + ((f) % NSTAGE) * 8, ((f) / NSTAGE) & 1)
__device__ __forceinline__ void mbar_probe(uint32_t& ok, uint32_t bar, uint32_t parity) {
  asm volatile("{\n.reg .pred p;\nmbarrier.test_wait.parity.shared::cta.b64 p, [%1], %2;\nselp.u32 %0, %0, 0, p;\n}"
               : "+r"(ok) : "r"(bar), "r"(parity) : "memory");
}
template <int F, int N> __device__ __forceinline__ uint32_t probe_n() {
  static_assert(F % NSTAGE + N <= NSTAGE, "stages must not wrap");
  uint32_t ok = 1;
#pragma unroll
  for (int i = 0; i < N; i++) mbar_probe(ok, SM_BASE + SM_FULL + (F % NSTAGE + i) * 8, (F / NSTAGE) & 1);
  return ok;
}
template <int F, int N> __device__ __forceinline__ void settle_n(uint32_t ok) {
  if (__builtin_expect(!ok, 0)) {
#pragma unroll 1
    for (int i = 0; i < N; i++) mbar_wait(SM_BASE + SM_FULL + (F % NSTAGE + i) * 8, (F / NSTAGE) & 1);
  }
}
template <int F, int N> __device__ __forceinline__ void acquire_n() { settle_n<F, N>(probe_n<F, N>()); }
#define RELEASE(f0, f1) do { if (lane == 0) { _Pragma("unroll") for (int f_ = (f0); f_ <= (f1); f_++) mbar_arrive(SM_BASE + SM_EMPTY + (f_ % NSTAGE) * 8); } } while (0)
constexpr uint64_t RING = (uint64_t)(SM_BASE >> 4) | (uint64_t(1) << 16) | (uint64_t(64) << 32) | (uint64_t(1) << 62);
#define LO(f) (RING + ((f) % NSTAGE) * 1024)
#define HI(f) (RING + ((f) % NSTAGE) * 1024 + 512)

template <int C> __device__ __forceinline__ uint4* peer(uint4* p) {
  asm volatile("" : "+l"(p));
  return (uint4*)((uintptr_t)p ^ (C * X_SIZE * sizeof(uint4)));
}
__device__ __forceinline__ uint32_t clock_now() { uint32_t c; asm volatile("mov.u32 %0, %%clock;" : "=r"(c) :: "memory"); return c; }
__device__ __forceinline__ void publish(uint4* dst, uint32_t (&a)[16], uint32_t tag) {
#pragma unroll
  for (int s = 0; s < 4; s++) a[4 * s] = (a[4 * s] & ~1u) | tag;
  pin(a);
  SCHED();
#pragma unroll
  for (int s = 0; s < 4; s++) st_vec(dst + s * 128, a[4 * s], a[4 * s + 1], a[4 * s + 2], a[4 * s + 3]);
  SCHED();
}
__device__ __forceinline__ void fetch(const uint4* src, uint32_t (&a)[16]) {
#pragma unroll
  for (int s = 0; s < 4; s++) ld_vec(src + s * 128, a[4 * s], a[4 * s + 1], a[4 * s + 2], a[4 * s + 3]);
}
__device__ __forceinline__ uint32_t miss(const uint32_t (&a)[16], uint32_t tag) {
  return (a[0] ^ tag) | (a[4] ^ tag) | (a[8] ^ tag) | (a[12] ^ tag);
}
__device__ __forceinline__ bool stale(uint32_t v) { return __any_sync(0xffffffffu, here(v) & 1u); }
#define GD0 400
#define GD1 400
#define RD 550
constexpr uint32_t SCATTER_DELAY = RD;
__device__ __forceinline__ void stat_fetch(const Scratch* sc, uint32_t (&st)[4]) {
  const uint32_t th = here(threadIdx.x);
  ld_vec(&sc->x[(blockIdx.x & ~3u) + (th & 3)][X_ST + (th >> 2)], st[0], st[1], st[2], st[3]);
}
template <int C, int SLOT> __device__ __forceinline__ void gather_first(uint32_t (&A)[4][16], uint32_t (&st)[4], const Scratch* sc, uint4* xp,
                                                                        uint32_t tag, uint32_t sent) {
  while (clock_now() - sent < (SLOT == X_AG0 ? GD0 : GD1)) {}
  fetch(peer<1>(xp) + SLOT, A[1]); fetch(peer<2>(xp) + SLOT, A[2]); fetch(peer<3>(xp) + SLOT, A[3]);
  if (SLOT == X_AG0) stat_fetch(sc, st);
  uint32_t spin = 0;
  while (__builtin_expect(stale(miss(A[1], tag) | miss(A[C], tag)), 0) && ++spin < SPIN_LIMIT) {
    fetch(peer<1>(xp) + SLOT, A[1]);
    if (C == 2) fetch(peer<2>(xp) + SLOT, A[2]);
  }
}
template <int C, int SLOT> __device__ __forceinline__ void gather_rest(uint32_t (&A)[4][16], uint4* xp, uint32_t tag) {
  SCHED();
  uint32_t spin = 0;
  while (__builtin_expect(stale(miss(A[C + 1], tag) | miss(A[3], tag)), 0) && ++spin < SPIN_LIMIT) {
    if (C == 1) fetch(peer<2>(xp) + SLOT, A[2]);
    fetch(peer<3>(xp) + SLOT, A[3]);
  }
}
__device__ __forceinline__ void pack_acc(const float (&d)[32], uint32_t (&a)[16]) {
#pragma unroll
  for (int i = 0; i < 16; i++) a[i] = pack2(d[2 * i], d[2 * i + 1]);
}
__device__ __forceinline__ void frag_store(uint32_t slot, const uint32_t (&a)[16]) {
#pragma unroll
  for (int s = 0; s < 4; s++) sts128(slot + s * 512, a[4 * s], a[4 * s + 1], a[4 * s + 2], a[4 * s + 3]);
}
__device__ __forceinline__ void tile_store(uint32_t maddr, const uint32_t (&a)[16]) {
#pragma unroll
  for (int s = 0; s < 4; s++) stsm4(maddr ^ (s << 5), &a[4 * s]);
}
__device__ __forceinline__ void tile_load(uint32_t maddr, uint32_t (&a)[16]) {
#pragma unroll
  for (int s = 0; s < 4; s++) ldsm4(maddr ^ (s << 5), &a[4 * s]);
}

__device__ __forceinline__ void res_load(uint32_t maddr, float (&d)[32]) {
  uint32_t a[16];
  tile_load(here(maddr) + 3 * TILE_BYTES, a);
#pragma unroll
  for (int i = 0; i < 16; i++) { d[2 * i] = bf_lo(a[i]); d[2 * i + 1] = bf_hi(a[i]); }
  pin(d);
}

struct RowAcc { float s[4], u[2][4], v[2][4]; };
__device__ __forceinline__ void row_acc(RowAcc& t, const uint32_t (&a)[16]) {
#pragma unroll
  for (int s = 0; s < 8; s++) {
    if ((s & 1) == 0) hmma(t.s, &a[2 * s], 0x3F803F80u, 0x3F803F80u);
    hmma8(t.u[s & 1], &a[2 * s], a[2 * s]);
    hmma8(t.v[s & 1], &a[2 * s], a[2 * s + 1]);
  }
}
__device__ __forceinline__ float2 row_squares(const RowAcc& t, bool odd) {
  return make_float2(odd ? t.u[0][1] + t.u[1][1] : t.u[0][0] + t.u[1][0], odd ? t.v[0][3] + t.v[1][3] : t.v[0][2] + t.v[1][2]);
}
__device__ __forceinline__ void stat_publish(const uint32_t (&a)[16], Scratch* sc, uint32_t th, uint32_t tag) {
  RowAcc t = {};
  row_acc(t, a);
  const float2 q = row_squares(t, th & 4);
  if ((th & 3) == ((th >> 3) & 3))
    st_vec(&sc->x[blockIdx.x][X_ST + (th >> 2)], (__float_as_uint(t.s[0]) & ~1u) | tag, __float_as_uint(q.x), __float_as_uint(t.s[2]), __float_as_uint(q.y));
}
struct RowNorm { float m0, rs0, m1, rs1; };
__device__ __forceinline__ RowNorm row_norm(float s0, float q0, float s1, float q1, float scale) {
  RowNorm n;
  n.m0 = s0 * (1.f / DM); n.m1 = s1 * (1.f / DM);
  n.rs0 = scale * rsqrt_hw(fmaxf(fmaf(-n.m0, n.m0, q0 * (1.f / DM)), 0.f) + LN_EPS);
  n.rs1 = scale * rsqrt_hw(fmaxf(fmaf(-n.m1, n.m1, q1 * (1.f / DM)), 0.f) + LN_EPS);
  return n;
}
__device__ __forceinline__ RowNorm stat_finish(const Scratch* sc, uint32_t (&st)[4], uint32_t tag, float scale) {
  uint32_t spin = 0;
  while (__builtin_expect(stale(st[0] ^ tag), 0) && ++spin < SPIN_LIMIT) stat_fetch(sc, st);
  float f[4];
#pragma unroll
  for (int i = 0; i < 4; i++) {
    f[i] = __uint_as_float(st[i]);
    f[i] += __shfl_xor_sync(0xffffffffu, f[i], 1);
    f[i] += __shfl_xor_sync(0xffffffffu, f[i], 2);
  }
  return row_norm(f[0], f[1], f[2], f[3], scale);
}
__device__ __forceinline__ void mean_frag(uint32_t (&mu)[4], const RowNorm& n, bool sel) {
  const float a = sel ? -n.m0 : 0.f, c = sel ? -n.m1 : 0.f;
  mu[0] = pack2(a, a); mu[1] = pack2(c, c);
  const float al = a - bf_lo(mu[0]), cl = c - bf_lo(mu[1]);
  mu[2] = pack2(al, al); mu[3] = pack2(cl, cl);
  pin(mu);
}
__device__ __forceinline__ void centre(uint32_t (&a)[16], uint32_t m0, uint32_t m1) {
#pragma unroll
  for (int i = 0; i < 16; i++) asm("sub.rn.bf16x2 %0, %0, %1;" : "+r"(a[i]) : "r"((i & 1) ? m1 : m0));
  pin(a);
}
__device__ __forceinline__ void scale_pack(const float (&d)[32], uint32_t (&a)[16], float rs0, float rs1) {
#pragma unroll
  for (int i = 0; i < 16; i++) { const float rs = (i & 1) ? rs1 : rs0; a[i] = pack2(d[2 * i] * rs, d[2 * i + 1] * rs); }
}
template <int S> __device__ __forceinline__ void silu_seg(float (&acc)[4][32], float (&tn)[2][4], uint32_t (&H)[4][16], float rs0, float rs1) {
  if (S >= 2) {
    const float* h = &acc[(S - 2) >> 3][4 * ((S - 2) & 7)];
    const float* v = tn[S & 1];
    uint32_t* o = &H[(S - 2) >> 3][2 * ((S - 2) & 7)];
    o[0] = pack2(fmaf(h[0], v[0], h[0]), fmaf(h[1], v[1], h[1]));
    o[1] = pack2(fmaf(h[2], v[2], h[2]), fmaf(h[3], v[3], h[3]));
    asm volatile("" : "+r"(o[0]), "+r"(o[1]));
  }
  if (S >= 1 && S <= 32) {
#pragma unroll
    for (int k = 0; k < 4; k++) tn[(S - 1) & 1][k] = tanh_hw(acc[((S - 1) >> 3) & 3][4 * ((S - 1) & 7) + k]);
  }
  if (S < 32) {
    float* h = &acc[(S >> 3) & 3][4 * (S & 7)];
    h[0] *= rs0; h[1] *= rs0; h[2] *= rs1; h[3] *= rs1;
    asm volatile("" : "+f"(h[0]), "+f"(h[1]), "+f"(h[2]), "+f"(h[3]));
  }
  SCHED();
}
template <int S0, int S1> __device__ __forceinline__ void silu_segs(float (&acc)[4][32], float (&tn)[2][4], uint32_t (&H)[4][16], float rs0, float rs1) {
  silu_seg<S0>(acc, tn, H, rs0, rs1);
  if constexpr (S0 + 1 < S1) silu_segs<S0 + 1, S1>(acc, tn, H, rs0, rs1);
}
template <int HALF> __device__ __forceinline__ void send_half(uint4* dst, const float (&d)[32], uint32_t tag) {
  uint32_t o[8];
#pragma unroll
  for (int i = 0; i < 8; i++) o[i] = pack2(d[16 * HALF + 2 * i], d[16 * HALF + 2 * i + 1]);
  o[0] = (o[0] & ~1u) | tag; o[4] = (o[4] & ~1u) | tag;
  pin(o);
  SCHED();
  st_vec(dst + HALF * 256, o[0], o[1], o[2], o[3]);
  st_vec(dst + HALF * 256 + 128, o[4], o[5], o[6], o[7]);
  SCHED();
}
__device__ __forceinline__ uint32_t send_residual(uint32_t (&a)[16], Scratch* sc, uint4* xp, uint32_t maddr, uint32_t tag) {
  const uint32_t exact[4] = {a[0], a[4], a[8], a[12]};
  publish(xp + X_AG0, a, tag);
  const uint32_t sent = clock_now();
  const uint32_t th = here(threadIdx.x);
  stat_publish(a, sc, th, tag);
  tile_store(here(maddr) + 3 * TILE_BYTES, a);
  stsm4(SM_BASE + SM_STG + 3 * TILE_BYTES + (th >> 5) * 2048 + (th & 7) * 128 + ((((th >> 2) & 6) ^ (th & 7)) << 4), exact);
  return sent;
}
template <int F, int N> __device__ __forceinline__ uint32_t proj_residual(uint32_t (&A)[4][16], Scratch* sc, uint4* xp, uint32_t maddr,
                                                                          uint32_t tag, uint32_t sent, int lane) {
  float acc[32];
  uint32_t st[4];
  acquire_n<F, N>();
  if (F == F_PW2) acquire_n<0, 5>();
  res_load(maddr, acc);
  mma_tile<false>(acc, A[0], LO(F));
  gather_first<2, X_AG1>(A, st, sc, xp, tag, sent);
  mma_tile<false>(acc, A[1], HI(F));
  mma_tile<false>(acc, A[2], LO(F + 1));
  gather_rest<2, X_AG1>(A, xp, tag);
  PROF_MARK0(F == F_WO ? 11 : 16);
  mma_tile<false>(acc, A[3], HI(F + 1));
  RELEASE(F - 2, F - 1);
  WG_WAIT(0); pin(acc);
  pack_acc(acc, A[0]);
  return send_residual(A[0], sc, xp, maddr, tag);
}

__device__ __forceinline__ uint64_t ring_desc(uint32_t lo) { return (RING & ~uint64_t(0xFFFFFFFFu)) | lo; }
__device__ __forceinline__ void qk_tile(float (&S)[32], const uint32_t (&Q)[16], uint32_t dk) {
  wgmma64_reuse<0>(S, &Q[0], ring_desc(dk), blockIdx.y);
#pragma unroll
  for (int s = 1; s < 4; s++) wgmma64_acc<0>(S, &Q[4 * s], ring_desc(dk + s * 2));
}
__device__ __forceinline__ void qk_shift(float (&S)[32], const uint32_t (&nm)[4]) { wgmma64_acc<0>(S, nm, (uint64_t)((SM_BASE + SM_ONE) >> 4)); }
constexpr uint32_t RING_K = (uint32_t)RING, V_STEP = 1u - (1u << 16);
constexpr uint32_t RING_V = (SM_BASE >> 4) | (((SM_STG + 2 * TILE_BYTES) >> 4) << 16);
__device__ __forceinline__ void pv_tile(float (&O)[36], const uint32_t (&P)[16], uint32_t dv, uint32_t pad) {
#pragma unroll
  for (int s = 0; s < 4; s++) wgmma72_acc(O, &P[4 * s], ring_desc(dv + s * 128 * V_STEP + (s < 2 ? 0 : (s - 1) * pad)));
}
__device__ __forceinline__ void attn_step(const float (&Sc)[32], float (&Sn)[32], uint32_t (&Pc)[16], uint32_t (&Pp)[16], float (&O)[36],
                                          const uint32_t (&Q)[16], const uint32_t (&nm)[4], uint32_t dk, uint32_t dv, bool next, bool prev) {
  if (next) {
    WG_FENCE();
    qk_tile(Sn, Q, dk);
    qk_shift(Sn, nm);
  }
  if (prev) {
    WG_FENCE();
    pv_tile(O, Pp, dv, 0);
  }
  WG_COMMIT();
  SCHED();
#pragma unroll
  for (int i = 0; i < 16; i++) Pc[i] = pack2(ex2_hw(Sc[2 * i]), ex2_hw(Sc[2 * i + 1]));
  pin(Pc);
  SCHED();
}
template <int R> __device__ __forceinline__ float tile_max(const float (&S)[32]) {
  float t[4];
#pragma unroll
  for (int j = 0; j < 4; j++) t[j] = fmaxf(fmaxf(S[8 * j + R], S[8 * j + R + 1]), fmaxf(S[8 * j + R + 4], S[8 * j + R + 5]));
  float n = fmaxf(fmaxf(t[0], t[1]), fmaxf(t[2], t[3]));
  n = fmaxf(n, __shfl_xor_sync(0xffffffffu, n, 1));
  return fmaxf(n, __shfl_xor_sync(0xffffffffu, n, 2));
}
__device__ __forceinline__ void attention_exact(float (&O)[36], const uint32_t (&Q)[16], const Scratch* sc, int bh, int lane, int half) {
  const char* kb = (const char*)&sc->kv[bh][0][0][0];
  const char* vb = (const char*)&sc->kv[bh][1][0][0];
  const int g = lane >> 2, q = lane & 3;
  float m0 = -INFINITY, m1 = -INFINITY, l0 = 0.f, l1 = 0.f;
  float o[4][4] = {};
#pragma unroll 1
  for (int k0 = 0; k0 < T_SEQ; k0 += 8) {
    float s[4] = {0.f, 0.f, 0.f, 0.f};
#pragma unroll
    for (int c = 0; c < 8; c++) hmma8(s, &Q[2 * c], __ldcg((const uint32_t*)(kb + (k0 + g) * 128 + ((c ^ g) << 4) + q * 4)));
    float n0 = fmaxf(s[0], s[1]), n1 = fmaxf(s[2], s[3]);
    n0 = fmaxf(n0, __shfl_xor_sync(0xffffffffu, n0, 1)); n1 = fmaxf(n1, __shfl_xor_sync(0xffffffffu, n1, 1));
    n0 = fmaxf(m0, fmaxf(n0, __shfl_xor_sync(0xffffffffu, n0, 2))); n1 = fmaxf(m1, fmaxf(n1, __shfl_xor_sync(0xffffffffu, n1, 2)));
    const float a0 = ex2_hw(m0 - n0), a1 = ex2_hw(m1 - n1);
    m0 = n0; m1 = n1;
    const uint32_t pp[2] = {pack2(ex2_hw(s[0] - n0), ex2_hw(s[1] - n0)), pack2(ex2_hw(s[2] - n1), ex2_hw(s[3] - n1))};
    l0 = fmaf(l0, a0, bf_lo(pp[0]) + bf_hi(pp[0])); l1 = fmaf(l1, a1, bf_lo(pp[1]) + bf_hi(pp[1]));
#pragma unroll
    for (int j = 0; j < 4; j++) {
      const int c = 4 * half + j;
      const uint32_t v0 = __ldcg((const uint16_t*)(vb + (k0 + 2 * q) * 128 + ((c ^ (2 * q)) << 4) + g * 2));
      const uint32_t v1 = __ldcg((const uint16_t*)(vb + (k0 + 2 * q + 1) * 128 + ((c ^ (2 * q + 1)) << 4) + g * 2));
      o[j][0] *= a0; o[j][1] *= a0; o[j][2] *= a1; o[j][3] *= a1;
      hmma8(o[j], pp, v0 | (v1 << 16));
    }
  }
  l0 += __shfl_xor_sync(0xffffffffu, l0, 1); l1 += __shfl_xor_sync(0xffffffffu, l1, 1);
  O[32] = l0 + __shfl_xor_sync(0xffffffffu, l0, 2); O[34] = l1 + __shfl_xor_sync(0xffffffffu, l1, 2);
#pragma unroll
  for (int i = 0; i < 16; i++) O[i] = o[i >> 2][i & 3];
}

__device__ __forceinline__ uint32_t fill_entry(int f, int r) {
  int m, x = r, y, dx = 0;
  if (f < F_QKV || f >= 48) {
    const int i = f & 15;
    m = f < F_QKV ? M_FF1A : M_FF2A;
    if (i < 8) { x = 4 * r + ((0xE2u >> i) & 1) * 2; y = r ^ ((0xE790u >> (2 * i)) & 3); dx = 1; }
    else { m++; x = r ^ (((i >> 1) - 3) & 3); y = 4 * r + 2 * (i & 1); }
  } else if (f < F_KV) {
    const int i = f - F_QKV;
    m = M_QKV;
    if (i == 1 || i >= 5) { y = r ^ (i == 1 ? 0 : 2); }
    else { x = 4 + r; y = r ^ (i ? i - 1 : 0); dx = 4; }
  } else if (f >= F_PW1 && f < F_PW2) {
    m = M_PW1; y = r ^ (f - F_PW1); dx = 4;
  } else {
    m = f < F_PW1 ? M_WO : M_PW2; y = r ^ ((f & 1) * 2);
  }
  return m | (x << 4) | (y << 8) | (dx << 16);
}
__device__ __forceinline__ void tma_fill(uint32_t st, const CUtensorMap* map, uint32_t x, uint32_t y, uint32_t x2, uint32_t y2) {
  asm volatile("{\n.reg .pred p;\nelect.sync _|p, 0xffffffff;\n"
               "@p mbarrier.arrive.expect_tx.shared::cta.b64 _, [%1], 16384;\n"
               "@p cp.async.bulk.tensor.2d.shared::cluster.global.mbarrier::complete_tx::bytes [%0], [%2, {%3, %4}], [%1];\n"
               "@p cp.async.bulk.tensor.2d.shared::cluster.global.mbarrier::complete_tx::bytes [%0 + 8192], [%2, {%5, %6}], [%1];\n}"
               :: "r"(SM_BASE + st * STAGE_BYTES), "r"(SM_BASE + SM_FULL + st * 8), "l"(map), "r"(x), "r"(y), "r"(x2), "r"(y2) : "memory");
}
template <int F0, int N> __device__ __forceinline__ void weight_fills(const Params& p, uint32_t entry) {
  uint32_t st = F0 % NSTAGE, parity = ((F0 / NSTAGE) & 1) ^ 1, e = __shfl_sync(0xffffffffu, entry, 0);
#pragma unroll 1
  for (int i = 1; i <= N; i++) {
    const uint32_t x = (e << 2) & 0x3C0, y = (e >> 2) & 0x3FC0, dx = (e >> 16) << 6;
    const CUtensorMap* map = &p.map[e & 15];
    e = __shfl_sync(0xffffffffu, entry, i);
    mbar_wait(SM_BASE + SM_EMPTY + st * 8, parity);
    tma_fill(st, map, x, y, x + dx, dx ? y : y ^ 64);
    if (++st == NSTAGE) { st = 0; parity ^= 1; }
  }
}
__device__ __forceinline__ void kv_fills(const Scratch* sc, int bh, int kind, uint32_t prev, int lane) {
  const uint32_t* flag = sc->flag[bh][kind * 16 + (lane & 15)];
  uint32_t ready = 0;
#pragma unroll 1
  for (int j = 0; j < 8; j++) {
    uint32_t spin = 0;
#pragma unroll 1
    while (((ready >> (2 * j)) & 3) != 3 && ++spin < SPIN_LIMIT) {
      uint32_t v;
      asm volatile("ld.relaxed.gpu.global.u32 %0, [%1];" : "=r"(v) : "l"(flag) : "memory");
      ready = __ballot_sync(0xffffffffu, v - 1 == prev);
    }
    const uint32_t st = (j < 6 ? 4 * (j >> 1) : 0) + (j & 1) + 2 * kind;
    mbar_wait(SM_BASE + SM_EMPTY + st * 8, j < 6);
    asm volatile("{\n.reg .pred p;\nelect.sync _|p, 0xffffffff;\n"
                 "@p mbarrier.arrive.expect_tx.shared::cta.b64 _, [%1], 16384;\n"
                 "@p cp.async.bulk.shared::cluster.global.mbarrier::complete_tx::bytes [%0], [%2], 16384, [%1];\n}"
                 :: "r"(SM_BASE + st * STAGE_BYTES), "r"(SM_BASE + SM_FULL + st * 8), "l"(sc->kv[bh][kind][2 * j]) : "memory");
    PROF_AT(256 + 512 + (10 + kind * 8 + j) * 4);
  }
}
__device__ __forceinline__ void l2_prefetch(const void* p, uint32_t total, int b) {
  const uint32_t part = total / NCTA;
  asm volatile("cp.async.bulk.prefetch.L2.global [%0], %1;" :: "l"((const char*)p + (size_t)b * part), "r"(part) : "memory");
}

__global__ void __launch_bounds__(384, 1) conformer_kernel(Scratch* __restrict__ sc, __nv_bfloat16* __restrict__ out,
                                                           const __nv_bfloat16* __restrict__ dw, const __nv_bfloat16* __restrict__ xin,
                                                           const __nv_bfloat16* __restrict__ w_ff1a, const __grid_constant__ Params p) {
  extern __shared__ __align__(1024) uint8_t smem[];
  const int tid = threadIdx.x, lane = tid & 31;
  if (tid == 0) {
    l2_prefetch(xin, 2 * T_SEQ * DM * 2, blockIdx.x);
    l2_prefetch(w_ff1a, 256 * 1024 * 2, blockIdx.x);
  }
  const int cw = __shfl_sync(0xffffffffu, tid >> 5, 0), wg = cw >> 2, w = cw & 3;
  const int b = blockIdx.x, r = b & 3, batch = b >> 6, t = (b >> 2) & 15;
  if ((uint32_t)__cvta_generic_to_shared(smem) != SM_BASE) return;
  PROF_MARK(0);
  PROF_TIME(30);

  if (wg == 2) {
    asm volatile("setmaxnreg.dec.sync.aligned.u32 40;");
    if (cw == 8) {
      if (lane == 0) {
        asm volatile("prefetch.tensormap [%0];" :: "l"(&p.map[M_X]) : "memory");
        asm volatile("prefetch.tensormap [%0];" :: "l"(&p.map[M_FF1A]) : "memory");
#pragma unroll
        for (int i = 0; i < 4; i++) mbar_init(SM_BASE + SM_XBAR + i * 8, 1);
#pragma unroll
        for (int i = 0; i < NSTAGE; i++) mbar_init(SM_BASE + SM_FULL + i * 8, 1);
        fence_async_smem();
      }
      __syncwarp();
      bar_arrive(0, 352);
      PROF_MARK(9);
#pragma unroll
      for (int f = 0; f < 8; f++) {
        const uint32_t x = 256 * r + ((0xE2u >> f) & 1) * 128, y = (r ^ ((0xE790u >> (2 * f)) & 3)) * 64;
#pragma unroll
        for (int c = 0; c < (f == 0 ? 4 : 0); c++)
          asm volatile("{\n.reg .pred p;\nelect.sync _|p, 0xffffffff;\n"
                       "@p mbarrier.arrive.expect_tx.shared::cta.b64 _, [%1], 8192;\n"
                       "@p cp.async.bulk.tensor.3d.shared::cluster.global.mbarrier::complete_tx::bytes [%0], [%2, {%3, %4, %5}], [%1];\n}"
                       :: "r"(SM_BASE + SM_STG + (3 - c) * TILE_BYTES), "r"(SM_BASE + SM_XBAR + c * 8), "l"(&p.map[M_X]),
                          "r"((r ^ c) * 64), "r"(t * 64), "r"(batch) : "memory");
        tma_fill(f, &p.map[M_FF1A], x, y, x + 64, y);
      }
      PROF_MARK(1);
      const uint32_t prev = ((volatile uint32_t*)sc->epoch)[b];
      uint32_t entry[2];
#pragma unroll 1
      for (int i = 0; i < 2; i++) { entry[1] = fill_entry(8 + i * 32 + lane, r); if (i == 0) entry[0] = entry[1]; }
      bar_sync(BAR_INIT, 64);
      weight_fills<8, F_KV - 8>(p, entry[0]);
      kv_fills(sc, batch * 4 + r, 0, prev, lane);
      weight_fills<F_WO, F_TOTAL - F_WO>(p, entry[1]);
    } else if (here(cw) != 11) {
      const int kind = w - 1;
      const uint32_t prev = ((volatile uint32_t*)sc->epoch)[b];
      if (kind == 0) {
        if (lane == 0) {
#pragma unroll
          for (int i = 0; i < NSTAGE; i++) mbar_init(SM_BASE + SM_EMPTY + i * 8, 4);
        }
        __syncwarp();
        bar_arrive(0, 352);
        bar_arrive(BAR_INIT, 64);
        bar_sync(BAR_K, 160);
      } else {
        uint32_t v, spin = 0;
#pragma unroll 1
        do {
          asm volatile("ld.relaxed.gpu.global.u32 %0, [%1];" : "=r"(v) : "l"(sc->ready[(b & ~3) + (lane & 3)]) : "memory");
        } while (__any_sync(0xffffffffu, v - 1 != prev) && ++spin < SPIN_LIMIT);
        bar_arrive(BAR_RDY, 160);
PROF_MARK(3);
        bar_sync(BAR_V, 160);
      }
      if (lane == 0) {
        asm volatile("cp.async.bulk.global.shared::cta.bulk_group [%0], [%1], %2;"
                     :: "l"(&sc->kv[batch * 4 + r][kind][t][0]), "r"(SM_BASE + SM_STG + kind * TILE_BYTES), "r"(TILE_BYTES) : "memory");
PROF_MARK(4 + kind * 2);
        asm volatile("cp.async.bulk.commit_group;\ncp.async.bulk.wait_group 0;" ::: "memory");
PROF_MARK(5 + kind * 2);
        asm volatile("st.relaxed.gpu.global.u32 [%0], %1;" :: "l"(sc->flag[batch * 4 + r][kind * 16 + t]), "r"(prev + 1) : "memory");
      }
    } else {
      const uint32_t epoch = ((volatile uint32_t*)sc->epoch)[b] + 1;
      bar_sync(0, 352);
      if (lane == 0 && epoch) {
        asm volatile("prefetch.tensormap [%0];" :: "l"(&p.map[M_FF1B]) : "memory");
        l2_prefetch(p.w_ff1b, 1024 * 256 * 2, b);
        l2_prefetch(p.w_qkv, 256 * 768 * 2, b);
        l2_prefetch(p.w_pw1, 256 * 512 * 2, b);
        l2_prefetch(p.w_ff2a, 256 * 1024 * 2, b);
      }
#pragma unroll 1
      for (int i = 0; i < 11; i++) {
        const uint32_t t0 = clock_now();
        uint4* dst = &sc->x[b][X_CLEAR + i * 96 + lane];
        st_vec(dst, 0u, 0u, 0u, 0u); st_vec(dst + 32, 0u, 0u, 0u, 0u); st_vec(dst + 64, 0u, 0u, 0u, 0u);
        while (clock_now() - t0 < 100) {}
      }
PROF_MARK(28);
      asm volatile("fence.acq_rel.gpu;" ::: "memory");
      mbar_wait(SM_BASE + SM_FULL + (NSTAGE - 1) * 8, 0);
      __syncwarp();
      if (lane == 0) {
        asm volatile("st.relaxed.gpu.global.u32 [%0], %1;" :: "l"(sc->ready[b]), "r"(epoch) : "memory");
        l2_prefetch(p.w_o, 256 * 256 * 2, b);
        l2_prefetch(p.w_pw2, 256 * 256 * 2, b);
        l2_prefetch(p.w_ff2b, 1024 * 256 * 2, b);
#pragma unroll
        for (int i = M_QKV; i < M_X; i++) asm volatile("prefetch.tensormap [%0];" :: "l"(&p.map[i]) : "memory");
      }
      PROF_MARK(2);
      __syncwarp();
      mbar_wait(SM_BASE + SM_FULL + (NSTAGE - 1) * 8, 1);
      kv_fills(sc, batch * 4 + r, 1, epoch - 1, lane);
    }
  } else {
    asm volatile("setmaxnreg.inc.sync.aligned.u32 232;");
    const int q = lane & 3, th = tid & 127;
    constexpr uint32_t stg = SM_BASE + SM_STG;
    const uint32_t mrow = 16 * w + (lane & 15);
    const uint32_t maddr = stg + mrow * 128 + (((lane >> 4) ^ (lane & 7)) << 4);
    const uint32_t qslot = stg + 2 * TILE_BYTES + w * 2048 + lane * 16;
    uint4* const xp = &sc->x[b][th];
    const int nvalid = T_SEQ - t * 64, row0 = 16 * w + (lane >> 2);

    uint32_t A[4][16];
    uint32_t sent = 0;
    uint32_t st[4];
    if (tid < 144) sts128(SM_BASE + SM_CS + tid * 16, 0, 0, 0, 0);
    if (wg == 1) sts32(SM_BASE + SM_EYE + th * 4, th >= 96 ? 0x3F803F80u : ((th & 32) == 0 && (th & 3) == ((th >> 3) & 3)) ? (0x3F00u << ((th & 4) * 4)) : 0u);
    fence_async_smem();
    bar_sync(0, 352);
    if (wg == 0) {
      RowAcc ra = {};
      mbar_wait(SM_BASE + SM_XBAR, 0);
      PROF_MARK0(45);
      tile_load(maddr + 3 * TILE_BYTES, A[0]);
#pragma unroll
      for (int c = 1; c < 4; c++) {
        mbar_wait(SM_BASE + SM_XBAR + c * 8, 0);
        tile_load(maddr + (3 - c) * TILE_BYTES, A[c]);
        row_acc(ra, A[c - 1]);
      }
      PROF_MARK(1);
      row_acc(ra, A[3]);
      PROF_MARK0(46);
      const float m0 = ra.s[0] * (1.f / DM), m1 = ra.s[2] * (1.f / DM);
      st[0] = pack2(m0, m0); st[1] = pack2(m1, m1);
      centre(A[0], st[0], st[1]);
      const float2 sq = row_squares(ra, lane & 4);
      st[2] = __float_as_uint(fmaf(-m0, m0, sq.x * (1.f / DM))); st[3] = __float_as_uint(fmaf(-m1, m1, sq.y * (1.f / DM)));
    } else {
      const uint32_t epoch = ((volatile uint32_t*)sc->epoch)[b] + 1, tag = epoch & 1;
      mbar_wait(SM_BASE + SM_FULL + 4 * 8, 0);
      PROF_MARK(5);
      if (b < 72) {
        const __nv_bfloat16* wp; int ld, col;
        if (b < 24) { wp = p.w_qkv; ld = 768; col = b * 32; }
        else if (b < 40) { wp = p.w_pw1; ld = 512; col = (b - 24) * 32; }
        else { wp = p.w_ff2a; ld = 1024; col = (b - 40) * 32; }
        const uint4* src = (const uint4*)(wp + (size_t)(th >> 2) * ld + col + q * 8);
        float c[8] = {0.f, 0.f, 0.f, 0.f, 0.f, 0.f, 0.f, 0.f};
#pragma unroll 1
        for (int h = 0; h < 2; h++, src += 16 * ld) {
#pragma unroll
          for (int i = 0; i < 4; i++) {
            const uint4 v = __ldg(src + i * 4 * ld);
            c[0] += bf_lo(v.x); c[1] += bf_hi(v.x); c[2] += bf_lo(v.y); c[3] += bf_hi(v.y);
            c[4] += bf_lo(v.z); c[5] += bf_hi(v.z); c[6] += bf_lo(v.w); c[7] += bf_hi(v.w);
          }
        }
#pragma unroll 1
        for (int m = 4; m <= 16; m <<= 1)
#pragma unroll
          for (int k = 0; k < 8; k++) c[k] += __shfl_xor_sync(0xffffffffu, c[k], m);
        if (lane < 4) {
          const uint32_t a = SM_BASE + SM_CS + 1792 + w * 128 + lane * 32;
          sts128(a, __float_as_uint(c[0]), __float_as_uint(c[1]), __float_as_uint(c[2]), __float_as_uint(c[3]));
          sts128(a + 16, __float_as_uint(c[4]), __float_as_uint(c[5]), __float_as_uint(c[6]), __float_as_uint(c[7]));
        }
        bar_sync(BAR_WG1, 128);
        if (th < 8) {
          float o[4] = {0.f, 0.f, 0.f, 0.f};
#pragma unroll 1
          for (int k = 0; k < 4; k++) {
            uint32_t e[4];
            lds128(SM_BASE + SM_CS + 1792 + k * 128 + th * 16, e[0], e[1], e[2], e[3]);
#pragma unroll
            for (int i = 0; i < 4; i++) o[i] += __uint_as_float(e[i]);
          }
          st_vec(&sc->cs[b * 8 + th], (__float_as_uint(o[0]) & ~1u) | tag, __float_as_uint(o[1]), __float_as_uint(o[2]), __float_as_uint(o[3]));
        }
      }
      bar_sync(BAR_WG1, 128);
      PROF_MARK(2);
      if (th < 72) {
        const int j = th >> 3, i = (th & 7) * 2;
        int src;
        if (j < CS_PW1) src = 320 + 64 * r + 16 * j;
        else if (j < CS_QKV) src = 192 + (j - CS_PW1) * 64 + 16 * r;
        else src = ((j - CS_QKV + 1) % 3) * 64 + 16 * r;
        uint32_t e[8], hi[4], lo[4], spin = 0;
#pragma unroll 1
        do {
          ld_vec(&sc->cs[src + i], e[0], e[1], e[2], e[3]);
          ld_vec(&sc->cs[src + i + 1], e[4], e[5], e[6], e[7]);
        } while ((((e[0] ^ tag) | (e[4] ^ tag)) & 1u) && ++spin < SPIN_LIMIT);
        e[0] &= ~1u; e[4] &= ~1u;
#pragma unroll
        for (int k = 0; k < 4; k++) {
          const float c0 = __uint_as_float(e[2 * k]), c1 = __uint_as_float(e[2 * k + 1]);
          hi[k] = pack2(c0, c1);
          lo[k] = pack2(c0 - bf_lo(hi[k]), c1 - bf_hi(hi[k]));
        }
        const uint32_t a = SM_BASE + SM_CS + j * 256 + i * 8;
        sts128(a ^ ((a >> 3) & 0x70), hi[0], hi[1], hi[2], hi[3]);
        sts128((a + 128) ^ (((a + 128) >> 3) & 0x70), lo[0], lo[1], lo[2], lo[3]);
      }
      fence_async_smem();
      PROF_MARK(4);
      bar_arrive(BAR_CS, 256);
    }

#pragma unroll 1
    for (uint32_t pass = 0; pass < 2; pass++) {
      uint32_t Q[16];
      if (wg == 0) {
        float acc[4][32];
        uint32_t H[4][16];
        if (!pass) { PROF_MARK(47); ACQUIRE(0); }
        mma_tile<true>(acc[0], A[0], LO(0)); mma_tile<true>(acc[1], A[0], HI(0));
        if (!pass) ACQUIRE(1);
        mma_tile<true>(acc[2], A[0], LO(1)); mma_tile<true>(acc[3], A[0], HI(1));
        if (pass) {
          gather_first<1, X_AG0>(A, st, sc, xp, 1, sent);
        } else {
          centre(A[1], st[0], st[1]);
          acquire_n<2, 3>();
        }
        mma_tile<false>(acc[0], A[1], LO(2)); mma_tile<false>(acc[1], A[1], HI(2));
        if (pass) {
          gather_rest<1, X_AG0>(A, xp, 1);
          RELEASE(F_PW2, F_PW2 + 1);
        } else {
          centre(A[2], st[0], st[1]); centre(A[3], st[0], st[1]);
        }
        PROF_MARK2(2, 18);
        mma_tile<false>(acc[0], A[2], LO(3)); mma_tile<false>(acc[0], A[3], LO(4));
        WG_WAIT(4);
        RELEASE(0, 1);
        uint32_t mu[4] = {0u, 0u, 0u, 0u};
        float rs0, rs1, tn[2][4];
        if (pass) {
          const RowNorm n = stat_finish(sc, st, 1, 0.5f);
          rs0 = n.rs0; rs1 = n.rs1;
          mean_frag(mu, n, q == 0);
        } else {
          const int src = (lane & 28) | (lane >> 3);
          rs0 = 0.5f * rsqrt_hw(fmaxf(__uint_as_float(__shfl_sync(0xffffffffu, st[2], src)), 0.f) + LN_EPS);
          rs1 = 0.5f * rsqrt_hw(fmaxf(__uint_as_float(__shfl_sync(0xffffffffu, st[3], src)), 0.f) + LN_EPS);
        }
        pin(mu);
        mma_fold<2 * CS_FF2>(acc[0], mu);
        mma_tile<false>(acc[1], A[2], HI(3));
#define SEGS(a, b) silu_segs<a, b>(acc, tn, H, rs0, rs1)
        WG_WAIT(1); pin(acc[0]);
        SEGS(0, 1);
        mma_tile_fold<2 * CS_FF2 + 2>(acc[1], A[3], HI(4), mu);
        SEGS(1, 3);
        uint32_t ok = probe_n<5, 3>();
        SEGS(3, 4);
        settle_n<5, 3>(ok);
        mma_tile<false>(acc[2], A[1], LO(5));
        SEGS(4, 6);
        mma_tile<false>(acc[2], A[2], LO(6));
        SEGS(6, 8);
        WG_WAIT(2); pin(acc[1]);
        RELEASE(2, 4);
        SEGS(8, 9);
        mma_tile_fold<2 * CS_FF2 + 4>(acc[2], A[3], LO(7), mu);
        SEGS(9, 12);
        mma_tile<false>(acc[3], A[1], HI(5));
        SEGS(12, 14);
        mma_tile<false>(acc[3], A[2], HI(6));
        SEGS(14, 16);
        WG_WAIT(2); pin(acc[2]);
        SEGS(16, 17);
        mma_tile_fold<2 * CS_FF2 + 6>(acc[3], A[3], HI(7), mu);
        SEGS(17, 19);
        ok = probe_n<8, 2>();
        SEGS(19, 20);
        settle_n<8, 2>(ok);
        mma_tile_reuse(acc[1], H[0], LO(8));
        SEGS(20, 22);
        mma_tile<false>(acc[1], H[1], HI(8));
        SEGS(22, 24);
        WG_WAIT(2); pin(acc[3]);
        RELEASE(5, 7);
        SEGS(24, 26);
        mma_tile<false>(acc[1], H[2], LO(9));
        SEGS(26, 27);
        ok = probe_n<10, 2>();
        SEGS(27, 28);
        settle_n<10, 2>(ok);
        mma_tile_reuse(acc[2], H[0], LO(10));
        SEGS(28, 31);
        mma_tile<false>(acc[2], H[1], HI(10));
        SEGS(31, 34);
#undef SEGS
        PROF_MARK2(3, 19);
        const uint32_t rtag = here(pass ^ 1);
        const uint4* rs_in = xp + X_RS;
        mma_tile<false>(acc[1], H[3], HI(9));
        mma_tile<false>(acc[2], H[2], LO(11));
        ok = probe_n<12, 2>();
        uint4* rs_out = peer<1>(xp) + X_RS;
        mma_tile<false>(acc[2], H[3], HI(11));
        settle_n<12, 2>(ok);
        WG_WAIT(2); pin(acc[1]);
        RELEASE(8, 9);
        send_half<0>(rs_out, acc[1], rtag);
        mma_tile_reuse(acc[3], H[0], LO(12));
        SCHED();
        send_half<1>(rs_out, acc[1], rtag);
        mma_tile<false>(acc[3], H[1], HI(12));
        rs_out = peer<2>(xp) + X_RS + 512;
        WG_WAIT(2); pin(acc[2]);
        send_half<0>(rs_out, acc[2], rtag);
        mma_tile<false>(acc[3], H[2], LO(13));
        SCHED();
        ok = probe_n<14, 2>();
        send_half<1>(rs_out, acc[2], rtag);
        mma_tile<false>(acc[3], H[3], HI(13));
        settle_n<14, 2>(ok);
        mma_tile_reuse(acc[1], H[0], LO(14));
        rs_out = peer<3>(xp) + X_RS + 1024;
        if (!pass) bar_sync(BAR_RDY, 160);
        fetch(rs_in, A[1]);
        SCHED();
        mma_tile<false>(acc[1], H[1], HI(14));
        WG_WAIT(2); pin(acc[3]);
        send_half<0>(rs_out, acc[3], rtag);
        send_half<1>(rs_out, acc[3], rtag);
        sent = clock_now();
        mma_tile<false>(acc[1], H[2], LO(15)); mma_tile<false>(acc[1], H[3], HI(15));
        SCHED();
        fetch(rs_in + 512, A[2]);
        SCHED();
        res_load(maddr, acc[2]);
        while (clock_now() - sent < SCATTER_DELAY) {}
        fetch(rs_in + 1024, A[3]);
        if (!pass) acquire_n<F_QKV, 3>();
        {
          uint32_t spin = 0;
          while (__builtin_expect(stale(miss(A[1], rtag) | miss(A[2], rtag) | miss(A[3], rtag)), 0) && ++spin < SPIN_LIMIT) {
            if (stale(miss(A[1], rtag) | miss(A[2], rtag))) { fetch(rs_in, A[1]); fetch(rs_in + 512, A[2]); }
            fetch(rs_in + 1024, A[3]);
          }
        }
        mma_add_half(acc[2], A[1]);
        mma_add_half(acc[2], A[2]);
        mma_add_half(acc[2], A[3]);
        PROF_MARK2(4, 20);
        WG_WAIT(0); pin(acc[2]); pin(acc[1]);
#pragma unroll
        for (int i = 0; i < 16; i++) A[0][i] = pack2(fmaf(acc[1][2 * i], 0.5f, acc[2][2 * i]), fmaf(acc[1][2 * i + 1], 0.5f, acc[2][2 * i + 1]));
        if (pass) {
          PROF_MARK(21);
          stat_publish(A[0], sc, here(th), 0);
          stat_fetch(sc, st);
          const RowNorm fn = stat_finish(sc, st, 0, 1.f);
          const float nm0 = -fn.m0 * fn.rs0, nm1 = -fn.m1 * fn.rs1;
#pragma unroll
          for (int i = 0; i < 16; i++) {
            const float rs = (i & 1) ? fn.rs1 : fn.rs0, nm = (i & 1) ? nm1 : nm0;
            A[0][i] = pack2(fmaf(bf_lo(A[0][i]), rs, nm), fmaf(bf_hi(A[0][i]), rs, nm));
          }
          tile_store(here(maddr), A[0]);
          __syncwarp();
          const int row = 16 * w + (lane >> 3);
          uint4* dst = (uint4*)(out + ((size_t)batch * T_SEQ + t * 64 + row) * DM + 64 * r) + (lane & 7);
          const uint32_t src = stg + row * 128 + (((lane & 7) ^ (lane >> 3)) << 4);
#pragma unroll
          for (int i = 0; i < 4; i++) {
            uint4 v;
            lds128((src ^ ((i & 1) << 6)) + i * 512, v.x, v.y, v.z, v.w);
            if (row + 4 * i < nvalid) dst[i * 4 * (DM / 8)] = v;
          }
          PROF_MARK(22);
          PROF_TIME(31);
          break;
        }
        sent = send_residual(A[0], sc, xp, maddr, 1);
        PROF_MARK(5);
        mma_tile<true>(acc[0], A[0], LO(F_QKV)); mma_tile<true>(acc[1], A[0], HI(F_QKV));
        mma_tile<true>(acc[2], A[0], LO(F_QKV + 1));
        gather_first<1, X_AG0>(A, st, sc, xp, 1, sent);
        mma_tile<false>(acc[0], A[1], LO(F_QKV + 2)); mma_tile<false>(acc[1], A[1], HI(F_QKV + 2));
        acquire_n<F_QKV + 3, 3>();
        bar_sync(BAR_CS, 256);
        gather_rest<1, X_AG0>(A, xp, 1);
        PROF_MARK(6);
        mma_tile<false>(acc[0], A[2], LO(F_QKV + 3)); mma_tile<false>(acc[0], A[3], LO(F_QKV + 4));
        SCHED();
        {
          const RowNorm n = stat_finish(sc, st, 1, 1.f);
          rs0 = row0 < nvalid ? n.rs0 : 0.f; rs1 = row0 + 8 < nvalid ? n.rs1 : 0.f;
          mean_frag(mu, n, q == 3);
        }
        mma_fold<2 * CS_QKV - 6>(acc[0], mu);
        RELEASE(10, 15);
        WG_WAIT(0); pin(acc[0]);
        scale_pack(acc[0], Q, rs0, rs1);
        tile_store(here(maddr), Q);
        SCHED();
        mma_tile<false>(acc[1], A[2], HI(F_QKV + 3));
        fence_async_smem();
        bar_arrive(BAR_K, 160);
        mma_tile_fold<2 * CS_QKV - 4>(acc[1], A[3], HI(F_QKV + 4), mu);
        mma_tile<false>(acc[2], A[1], HI(F_QKV + 1)); mma_tile<false>(acc[2], A[2], LO(F_QKV + 5));
        WG_WAIT(2); pin(acc[1]);
        scale_pack(acc[1], Q, rs0, rs1);
        tile_store(here(maddr) + TILE_BYTES, Q);
        fence_async_smem();
        bar_arrive(BAR_V, 160);
        mma_tile_fold<2 * CS_QKV - 2>(acc[2], A[3], HI(F_QKV + 5), mu);
        WG_WAIT(0); pin(acc[2]);
        scale_pack(acc[2], Q, rs0 * SM_SCALE_LOG2, rs1 * SM_SCALE_LOG2);
        frag_store(here(qslot), Q);
        bar_arrive(BAR_Q, 256);
        RELEASE(F_QKV, F_QKV + 5);
      } else {
        bar_sync(BAR_Q, 256);
#pragma unroll
        for (int s = 0; s < 4; s++) lds128(qslot + s * 512, Q[4 * s], Q[4 * s + 1], Q[4 * s + 2], Q[4 * s + 3]);
        if (w < 2) {
          const uint32_t v = w ? 0u : 0x3F803F80u;
#pragma unroll
          for (int s = 0; s < 4; s++) sts128(qslot + s * 512, v, v, v, v);
          fence_async_smem();
        }
      }
      bar_sync(BAR_ATT, 256);
      PROF_MARK(7);

      const int dir = cw == 0 ? -1 : 1;
      uint32_t tap[15];
      {
        const uint32_t* dwp = (const uint32_t*)(dw + 64 * r) + lane + 7 * (DM / 2);
#pragma unroll
        for (int k = 0; k < 15; k++) tap[k] = __ldg(dwp + dir * (k - 7) * (DM / 2));
      }

      float O[36];
      {
        float S[2][32];
        uint32_t P[2][16], nm[4];
#pragma unroll
        for (int i = 0; i < 32; i++) { S[0][i] = 0.f; S[1][i] = 0.f; }
        pin(Q); pin(S[0]);
        WG_FENCE();
        qk_tile(S[0], Q, RING_K + (SM_STG >> 4));
        WG_COMMIT();
#pragma unroll
        for (int i = 0; i < 36; i++) O[i] = 0.f;
#pragma unroll
        for (int i = 0; i < 16; i++) P[1][i] = 0u;
        WG_WAIT(0); pin(S[0]);
        const float m0 = tile_max<0>(S[0]), m1 = tile_max<2>(S[0]);
        nm[0] = pack2(q ? 0.f : -m0, 0.f); nm[1] = pack2(q ? 0.f : -m1, 0.f); nm[2] = 0u; nm[3] = 0u;
#pragma unroll
        for (int k = 0; k < 15; k++) asm("mul.rn.bf16x2 %0, %0, %1;" : "+r"(tap[k]) : "r"(0x3F003F00u));
        pin(nm); pin(O); pin(P[1]); pin(tap);
        uint32_t sk = wg, sv = F_SPARE % NSTAGE + wg;
        mbar_wait(SM_BASE + SM_FULL + sv * 8, 1);
        mbar_wait(SM_BASE + SM_FULL + sk * 8, 0);
        PROF_MARK(8);
        WG_FENCE();
        qk_tile(S[0], Q, RING_K + sk * 1024);
        qk_shift(S[0], nm);
        WG_COMMIT();
        WG_WAIT(0); pin(S[0]); pin(S[1]);
#pragma unroll 1
        for (int it = 0; it < 4; it++) {
          const uint32_t sn = it >= 2 ? wg : sk + 4;
          uint32_t ok = 1;
          mbar_probe(ok, SM_BASE + SM_FULL + sn * 8, it >= 2);
          mbar_probe(ok, SM_BASE + SM_FULL + (sk + 2) * 8, it == 3);
          attn_step(S[0], S[1], P[0], P[1], O, Q, nm, RING_K + sk * 1024 + 512, RING_V + (sv * 1024 + 512) * V_STEP, true, it > 0);
          PROF_MARK(24 + it * 3);
          if (__builtin_expect(!ok, 0)) {
            mbar_wait(SM_BASE + SM_FULL + sn * 8, it >= 2);
            mbar_wait(SM_BASE + SM_FULL + (sk + 2) * 8, it == 3);
          }
          WG_WAIT(0); pin(O); pin(S[1]); pin(P[1]);
          asm volatile("{\n.reg .pred p;\nsetp.eq.u32 p, %2, 0;\n@p mbarrier.arrive.shared::cta.b64 _, [%0];\n@p mbarrier.arrive.shared::cta.b64 _, [%1];\n}"
                       :: "r"(SM_BASE + SM_EMPTY + sk * 8), "r"(SM_BASE + SM_EMPTY + sv * 8), "r"(lane) : "memory");
          PROF_MARK(25 + it * 3);
          sv = sk + 2; sk = sn;
          attn_step(S[1], S[0], P[1], P[0], O, Q, nm, RING_K + sk * 1024, RING_V + (sv * 1024) * V_STEP, it < 3, true);
          WG_WAIT(0); pin(O); pin(S[0]); pin(P[0]);
          PROF_MARK(26 + it * 3);
        }
        WG_FENCE();
        pv_tile(O, P[1], RING_V + (sv * 1024 + 512) * V_STEP, wg << 22);
        WG_COMMIT();
        WG_WAIT(0); pin(O);
      }
      PROF_MARK(9);

      {
        const uint32_t mo = stg + here(th) * 16;
        sts64(mo + 5 * 4096 + wg * 8, __float_as_uint(O[32]), __float_as_uint(O[34]));
        if (wg == 0) {
#pragma unroll
          for (int i = 4; i < 8; i++)
            sts128(mo + i * 2048, __float_as_uint(O[4 * i]), __float_as_uint(O[4 * i + 1]), __float_as_uint(O[4 * i + 2]), __float_as_uint(O[4 * i + 3]));
        } else {
#pragma unroll
          for (int i = 0; i < 4; i++)
            sts128(mo + i * 2048, __float_as_uint(O[4 * i]), __float_as_uint(O[4 * i + 1]), __float_as_uint(O[4 * i + 2]), __float_as_uint(O[4 * i + 3]));
#pragma unroll
          for (int i = 0; i < 16; i++) O[i] = O[16 + i];
        }
        bar_sync(BAR_MERGE, 256);
        uint32_t e[4];
        lds128(mo + 5 * 4096, e[0], e[1], e[2], e[3]);
        O[32] = __uint_as_float(e[0]) + __uint_as_float(e[2]); O[34] = __uint_as_float(e[1]) + __uint_as_float(e[3]);
#pragma unroll
        for (int i = 0; i < 4; i++) {
          lds128(mo + wg * TILE_BYTES + i * 2048, e[0], e[1], e[2], e[3]);
#pragma unroll
          for (int k = 0; k < 4; k++) O[4 * i + k] += __uint_as_float(e[k]);
        }
        const bool safe = O[32] > 0x1p-60f && O[32] < 0x1p60f && O[34] > 0x1p-60f && O[34] < 0x1p60f;
        if (__builtin_expect(__any_sync(0xffffffffu, !safe), 0)) attention_exact(O, Q, sc, batch * 4 + r, lane, wg);
        const float i0 = rcp_hw(O[32]), i1 = rcp_hw(O[34]);
#pragma unroll
        for (int i = 0; i < 8; i++) { const float v = (i & 1) ? i1 : i0; A[0][i] = pack2(O[2 * i] * v, O[2 * i + 1] * v); }
        A[0][0] &= ~1u; A[0][4] &= ~1u;
        uint4* dst = xp + X_AG1 + wg * 256;
        SCHED();
        st_vec(dst, A[0][0], A[0][1], A[0][2], A[0][3]);
        st_vec(dst + 128, A[0][4], A[0][5], A[0][6], A[0][7]);
        SCHED();
        sent = clock_now();
      }
      if (wg == 1) {
        const uint32_t mo = stg + TILE_BYTES + here(th) * 16;
        sts128(mo, A[0][0], A[0][1], A[0][2], A[0][3]);
        sts128(mo + 2048, A[0][4], A[0][5], A[0][6], A[0][7]);
        bar_arrive(BAR_HALF, 256);
      } else {
        PROF_MARK(10);
        const uint32_t mo = stg + TILE_BYTES + here(th) * 16;
        bar_sync(BAR_HALF, 256);
        lds128(mo, A[0][8], A[0][9], A[0][10], A[0][11]);
        lds128(mo + 2048, A[0][12], A[0][13], A[0][14], A[0][15]);
        sent = proj_residual<F_WO, 6>(A, sc, xp, maddr, 0, sent, lane);
        PROF_MARK(12);
        float acc[2][32];
        mma_tile<true>(acc[0], A[0], LO(F_PW1)); mma_tile<true>(acc[1], A[0], HI(F_PW1));
        gather_first<1, X_AG0>(A, st, sc, xp, 0, sent);
        mma_tile<false>(acc[1], A[1], HI(F_PW1 + 1)); mma_tile<false>(acc[0], A[1], LO(F_PW1 + 1));
        gather_rest<1, X_AG0>(A, xp, 0);
        PROF_MARK(13);
        mma_tile<false>(acc[1], A[2], HI(F_PW1 + 2)); mma_tile<false>(acc[1], A[3], HI(F_PW1 + 3));
        WG_WAIT(2);
        RELEASE(F_WO, F_PW1 + 1);
        SCHED();
        uint32_t mu[4];
        const RowNorm n = stat_finish(sc, st, 0, 0.5f);
        const float rs0 = row0 < nvalid ? n.rs0 : 0.f, rs1 = row0 + 8 < nvalid ? n.rs1 : 0.f;
        mean_frag(mu, n, q == 0);
        mma_fold<2 * CS_PW1 + 2>(acc[1], mu);
        mma_tile<false>(acc[0], A[2], LO(F_PW1 + 2));
        mma_tile_fold<2 * CS_PW1>(acc[0], A[3], LO(F_PW1 + 3), mu);
        WG_WAIT(2); pin(acc[1]);
#pragma unroll
        for (int i = 0; i < 32; i++) acc[1][i] = tanh_hw(acc[1][i] * ((i & 2) ? rs1 : rs0));
#pragma unroll
        for (int i = 0; i < 32; i++) { const float rs = (i & 2) ? rs1 : rs0; acc[1][i] = fmaf(acc[1][i], rs, rs); }
        pin(acc[1]);
        SCHED();
        WG_WAIT(0); pin(acc[0]);
#pragma unroll
        for (int i = 0; i < 16; i++) A[0][i] = pack2(acc[0][2 * i] * acc[1][2 * i], acc[0][2 * i + 1] * acc[1][2 * i + 1]);
        const uint32_t ga = stg + TILE_BYTES + here(mrow) * G_PITCH + (lane >> 4) * 16;
#pragma unroll
        for (int s = 0; s < 4; s++) stsm4(ga + s * 32, &A[0][4 * s]);
      }
      {
        const uint32_t gsrc = stg + TILE_BYTES + (8 * cw - 7) * G_PITCH + lane * 4;
        const bool edge = cw == 0 || cw == 7;
        const bool nbr = cw == 0 ? t > 0 : t < 15;
        uint4* const hdst = &sc->x[b + 4 * dir][X_HALO + (cw == 0 ? 96 : 0) + lane];
        uint32_t in[22];
        bar_sync(BAR_G, 256);
        PROF_MARK(14);
        if (cw == 0) {
#pragma unroll
          for (int i = 14; i >= 0; i--) in[i] = lds32(gsrc + (21 - i) * G_PITCH);
        } else {
#pragma unroll
          for (int i = 14; i >= 0; i--) in[i] = lds32(gsrc + i * G_PITCH);
        }
        if (edge) {
          if (nbr) {
            st_vec(hdst, HALO_TAG, in[14], in[13], in[12]);
            st_vec(hdst + 32, HALO_TAG, in[11], in[10], in[9]);
            st_vec(hdst + 64, HALO_TAG, in[8], 0u, 0u);
          }
        } else {
#pragma unroll
          for (int i = 15; i < 22; i++) in[i] = lds32(gsrc + i * G_PITCH);
        }
        if (cw == 0) PROF_MARK0(40);
        uint32_t cv[8];
#pragma unroll
        for (int i = 0; i < 15; i++)
#pragma unroll
          for (int o = 0; o < 8; o++) {
            if (i == o) asm("mul.rn.bf16x2 %0, %1, %2;" : "=r"(cv[o]) : "r"(in[i]), "r"(tap[0]));
            if (i > o) asm("fma.rn.bf16x2 %0, %1, %2, %0;" : "+r"(cv[o]) : "r"(in[i]), "r"(tap[i - o]));
          }
        pin(cv);
        if (cw == 0) PROF_MARK0(41);
        if (edge) {
#pragma unroll
          for (int i = 15; i < 22; i++) in[i] = 0u;
          if (nbr) {
            const uint4* src = &sc->x[b][X_HALO + (cw == 0 ? 0 : 96) + lane];
            uint32_t e0, e1, e2, u0, u1, spin = 0;
#pragma unroll 1
            do {
              ld_vec(src, e0, in[15], in[16], in[17]);
              ld_vec(src + 32, e1, in[18], in[19], in[20]);
              ld_vec(src + 64, e2, in[21], u0, u1);
            } while (__any_sync(0xffffffffu, ((e0 ^ HALO_TAG) | (e1 ^ HALO_TAG) | (e2 ^ HALO_TAG)) != 0) && ++spin < SPIN_LIMIT);
          }
        }
#pragma unroll
        for (int i = 15; i < 22; i++)
#pragma unroll
          for (int o = 0; o < 8; o++)
            if (i - o <= 14) asm("fma.rn.bf16x2 %0, %1, %2, %0;" : "+r"(cv[o]) : "r"(in[i]), "r"(tap[i - o]));
        if (cw == 0) PROF_MARK0(42);
        if (cw == 7) PROF_MARK0(43);
        const uint32_t fl = cw == 0 ? 7 : 0;
        const uint32_t cdst = (stg + cw * 1024 + lane * 4) ^ (fl * 144);
#pragma unroll
        for (int o = 0; o < 8; o++) {
          const float a = bf_lo(cv[o]), c = bf_hi(cv[o]);
          sts32(cdst ^ (o * 144), pack2(fmaf(a, tanh_hw(a), a), fmaf(c, tanh_hw(c), c)));
        }
      }
      if (wg == 1) {
        bar_arrive(BAR_C, 256);
        if (th == 0) ((volatile uint32_t*)sc->epoch)[b] += 1;
        break;
      }
      bar_sync(BAR_C, 256);
      tile_load(here(maddr), A[0]);
      PROF_MARK(15);
      publish(xp + X_AG1, A[0], 1);
      sent = proj_residual<F_PW2, 2>(A, sc, xp, maddr, 1, clock_now(), lane);
      PROF_MARK(17);
    }
  }
}

typedef CUresult (*EncodeFn)(CUtensorMap*, CUtensorMapDataType, cuuint32_t, void*, const cuuint64_t*, const cuuint64_t*,
                             const cuuint32_t*, const cuuint32_t*, CUtensorMapInterleave, CUtensorMapSwizzle,
                             CUtensorMapL2promotion, CUtensorMapFloatOOBfill);

void make_map(EncodeFn fn, CUtensorMap* m, const void* w, int rows, int cols, CUtensorMapSwizzle swz) {
  const cuuint64_t dims[2] = {(cuuint64_t)cols, (cuuint64_t)rows}, strides[1] = {(cuuint64_t)cols * 2};
  const cuuint32_t box[2] = {64, 64}, es[2] = {1, 1};
  fn(m, CU_TENSOR_MAP_DATA_TYPE_BFLOAT16, 2, const_cast<void*>(w), dims, strides, box, es, CU_TENSOR_MAP_INTERLEAVE_NONE,
     swz, CU_TENSOR_MAP_L2_PROMOTION_L2_128B, CU_TENSOR_MAP_FLOAT_OOB_FILL_NONE);
}

}

extern "C" void kernel_launch(void* const* d_in, const int* in_sizes, int n_in, void* d_out, int out_size) {
  static EncodeFn fn = nullptr;
  static Scratch* sc = nullptr;
  if (!fn) {
    void* f = nullptr;
    cudaDriverEntryPointQueryResult st;
    cudaGetDriverEntryPoint("cuTensorMapEncodeTiled", &f, cudaEnableDefault, &st);
    fn = (EncodeFn)f;
    void* raw = nullptr;
    cudaGetSymbolAddress(&raw, g_scratch);
    sc = (Scratch*)(((uintptr_t)raw + X_ALIGN - 1) & ~(uintptr_t)(X_ALIGN - 1));
    cudaFuncSetAttribute(conformer_kernel, cudaFuncAttributeMaxDynamicSharedMemorySize, SM_TOTAL);
  }
  typedef const __nv_bfloat16* W;
  const CUtensorMapSwizzle S = CU_TENSOR_MAP_SWIZZLE_128B;
  Params p;
  {
    const cuuint64_t dims[3] = {DM, T_SEQ, 2}, strides[2] = {DM * 2, T_SEQ * DM * 2};
    const cuuint32_t box[3] = {64, 64, 1}, es[3] = {1, 1, 1};
    fn(&p.map[M_X], CU_TENSOR_MAP_DATA_TYPE_BFLOAT16, 3, d_in[0], dims, strides, box, es, CU_TENSOR_MAP_INTERLEAVE_NONE, S,
       CU_TENSOR_MAP_L2_PROMOTION_L2_128B, CU_TENSOR_MAP_FLOAT_OOB_FILL_NONE);
  }
  make_map(fn, &p.map[M_FF1A], d_in[1], 256, 1024, S);
  make_map(fn, &p.map[M_FF1B], d_in[2], 1024, 256, S);
  make_map(fn, &p.map[M_QKV], d_in[3], 256, 768, S);
  make_map(fn, &p.map[M_WO], d_in[4], 256, 256, S);
  make_map(fn, &p.map[M_PW1], d_in[5], 256, 512, S);
  make_map(fn, &p.map[M_PW2], d_in[7], 256, 256, S);
  make_map(fn, &p.map[M_FF2A], d_in[8], 256, 1024, S);
  make_map(fn, &p.map[M_FF2B], d_in[9], 1024, 256, S);
  p.w_ff1b = (W)d_in[2]; p.w_qkv = (W)d_in[3]; p.w_o = (W)d_in[4]; p.w_pw1 = (W)d_in[5];
  p.w_pw2 = (W)d_in[7]; p.w_ff2a = (W)d_in[8]; p.w_ff2b = (W)d_in[9];

  cudaLaunchConfig_t cfg = {};
  cfg.gridDim = dim3(NCTA);
  cfg.blockDim = dim3(384);
  cfg.dynamicSmemBytes = SM_TOTAL;
  cfg.stream = cudaStreamPerThread;
  cudaLaunchAttribute at[1];
  at[0].id = cudaLaunchAttributeCooperative;
  at[0].val.cooperative = 1;
  cfg.attrs = at;
  cfg.numAttrs = 1;
  cudaLaunchKernelEx(&cfg, conformer_kernel, sc, (__nv_bfloat16*)d_out, (W)d_in[6], (W)d_in[0], (W)d_in[1], p);
}
```

```cpp
#include <cuda_runtime.h>
#include <cuda_bf16.h>
#include <cuda.h>
#include <stdint.h>

namespace {

constexpr int T_SEQ = 1000;
constexpr int DM = 256;
constexpr int NCTA = 128;
constexpr int NSTAGE = 12;
constexpr uint32_t STAGE_BYTES = 16384;
constexpr uint32_t TILE_BYTES = 8192;
constexpr uint32_t SM_BASE = 1024;
constexpr uint32_t SM_STG = NSTAGE * STAGE_BYTES;
constexpr uint32_t SM_FULL = SM_STG + 32768;
constexpr uint32_t SM_EMPTY = SM_FULL + 96;
constexpr uint32_t SM_XBAR = SM_FULL + 192;
constexpr uint32_t SM_EYE = SM_FULL + 256;
constexpr uint32_t SM_ONE = SM_FULL + 640;
constexpr uint32_t SM_CS = SM_FULL + 768;
constexpr uint32_t SM_TOTAL = SM_FULL + 3072;
constexpr int CS_FF2 = 0, CS_PW1 = 4, CS_QKV = 6;
constexpr uint32_t SPIN_LIMIT = 1u << 16;
constexpr float LN_EPS = 1e-5f;
constexpr float SM_SCALE_LOG2 = 0.125f * 1.4426950408889634f;
constexpr uint32_t G_PITCH = 144;

constexpr int F_QKV = 16, F_SPARE = 22, F_KV = 24, F_WO = 40, F_PW1 = 42, F_PW2 = 46, F_TOTAL = 64;
enum { M_FF1A, M_FF1B, M_QKV, M_WO, M_PW1, M_PW2, M_FF2A, M_FF2B, M_X, M_COUNT };
enum { BAR_K = 1, BAR_V, BAR_Q, BAR_MERGE, BAR_G, BAR_C, BAR_WG1, BAR_RDY, BAR_CS, BAR_ATT, BAR_INIT, BAR_HALF };

struct Params {
  CUtensorMap map[M_COUNT];
  const __nv_bfloat16 *w_ff1b, *w_qkv, *w_o, *w_pw1, *w_pw2, *w_ff2a, *w_ff2b;
};

constexpr int X_RS = 0, X_AG1 = X_RS, X_HALO = X_RS + 512, X_AG0 = 1536, X_ST = 2048, X_SIZE = 4096;
constexpr uint32_t HALO_TAG = 0xFFFF0001u;
struct Scratch {
  uint4 x[NCTA][X_SIZE];
  uint4 kv[8][2][16][512];
  uint4 cs[576];
  uint32_t flag[8][32][32];
  uint32_t ready[NCTA][32];
  uint32_t epoch[NCTA];
};
constexpr size_t X_ALIGN = 4 * X_SIZE * sizeof(uint4);
__device__ uint8_t g_scratch[sizeof(Scratch) + X_ALIGN];
#define PROF_TIME(i)
#define PROF_MARK(i)
#define PROF_MARK2(i, j)
#define PROF_MARK0(i)
#define PROF_AT(a)

__device__ __forceinline__ void mbar_init(uint32_t bar, uint32_t cnt) {
  asm volatile("mbarrier.init.shared::cta.b64 [%0], %1;" :: "r"(bar), "r"(cnt) : "memory");
}
__device__ __forceinline__ void mbar_wait(uint32_t bar, uint32_t parity) {
  asm volatile("{\n.reg .pred p;\n.reg .u32 c;\nmov.u32 c, 0;\n"
               "WAIT_LOOP:\nmbarrier.try_wait.parity.shared::cta.b64 p, [%0], %1;\n@p bra WAIT_DONE;\n"
               "add.u32 c, c, 1;\nsetp.lt.u32 p, c, %2;\n@p bra WAIT_LOOP;\nWAIT_DONE:\n}"
               :: "r"(bar), "r"(parity), "n"(SPIN_LIMIT) : "memory");
}
__device__ __forceinline__ void mbar_arrive(uint32_t bar) {
  asm volatile("mbarrier.arrive.shared::cta.b64 _, [%0];" :: "r"(bar) : "memory");
}
#define bar_sync(id, n) asm volatile("bar.sync %0, %1;" :: "n"((int)(id)), "n"(n) : "memory")
#define bar_arrive(id, n) asm volatile("bar.arrive %0, %1;" :: "n"((int)(id)), "n"(n) : "memory")
__device__ __forceinline__ void fence_async_smem() { asm volatile("fence.proxy.async.shared::cta;" ::: "memory"); }

__device__ __forceinline__ void st_vec(uint4* p, uint32_t a, uint32_t b, uint32_t c, uint32_t d) {
  asm volatile("{\n.reg .b128 v;\n.reg .b64 lo, hi;\nmov.b64 lo, {%1, %2};\nmov.b64 hi, {%3, %4};\nmov.b128 v, {lo, hi};\n"
               "st.relaxed.gpu.global.b128 [%0], v;\n}" :: "l"(p), "r"(a), "r"(b), "r"(c), "r"(d) : "memory");
}
__device__ __forceinline__ void ld_vec(const uint4* p, uint32_t& a, uint32_t& b, uint32_t& c, uint32_t& d) {
  asm volatile("{\n.reg .b128 v;\n.reg .b64 lo, hi;\nld.relaxed.gpu.global.b128 v, [%4];\nmov.b128 {lo, hi}, v;\n"
               "mov.b64 {%0, %1}, lo;\nmov.b64 {%2, %3}, hi;\n}" : "=r"(a), "=r"(b), "=r"(c), "=r"(d) : "l"(p) : "memory");
}
__device__ __forceinline__ void sts128(uint32_t a, uint32_t x, uint32_t y, uint32_t z, uint32_t w) {
  asm volatile("st.shared.v4.u32 [%0], {%1, %2, %3, %4};" :: "r"(a), "r"(x), "r"(y), "r"(z), "r"(w) : "memory");
}
__device__ __forceinline__ void lds128(uint32_t a, uint32_t& x, uint32_t& y, uint32_t& z, uint32_t& w) {
  asm volatile("ld.shared.v4.u32 {%0, %1, %2, %3}, [%4];" : "=r"(x), "=r"(y), "=r"(z), "=r"(w) : "r"(a) : "memory");
}
__device__ __forceinline__ uint32_t lds32(uint32_t a) {
  uint32_t x; asm volatile("ld.shared.u32 %0, [%1];" : "=r"(x) : "r"(a) : "memory"); return x;
}
__device__ __forceinline__ void sts32(uint32_t a, uint32_t x) { asm volatile("st.shared.u32 [%0], %1;" :: "r"(a), "r"(x) : "memory"); }
__device__ __forceinline__ void sts64(uint32_t a, uint32_t x, uint32_t y) {
  asm volatile("st.shared.v2.u32 [%0], {%1, %2};" :: "r"(a), "r"(x), "r"(y) : "memory");
}
__device__ __forceinline__ void stsm4(uint32_t a, const uint32_t* r) {
  asm volatile("stmatrix.sync.aligned.m8n8.x4.shared.b16 [%0], {%1, %2, %3, %4};" :: "r"(a), "r"(r[0]), "r"(r[1]), "r"(r[2]), "r"(r[3]) : "memory");
}
__device__ __forceinline__ void ldsm4(uint32_t a, uint32_t* r) {
  asm volatile("ldmatrix.sync.aligned.m8n8.x4.shared.b16 {%0, %1, %2, %3}, [%4];" : "=r"(r[0]), "=r"(r[1]), "=r"(r[2]), "=r"(r[3]) : "r"(a) : "memory");
}
__device__ __forceinline__ uint32_t pack2(float lo, float hi) {
  uint32_t r; asm("cvt.rn.bf16x2.f32 %0, %1, %2;" : "=r"(r) : "f"(hi), "f"(lo)); return r;
}
__device__ __forceinline__ float bf_lo(uint32_t w) { return __uint_as_float(w << 16); }
__device__ __forceinline__ float bf_hi(uint32_t w) { return __uint_as_float(w & 0xffff0000u); }
__device__ __forceinline__ float tanh_hw(float x) { float y; asm volatile("tanh.approx.f32 %0, %1;" : "=f"(y) : "f"(x)); return y; }
__device__ __forceinline__ float rcp_hw(float x) { float y; asm("rcp.approx.ftz.f32 %0, %1;" : "=f"(y) : "f"(x)); return y; }
__device__ __forceinline__ float rsqrt_hw(float x) { float y; asm("rsqrt.approx.ftz.f32 %0, %1;" : "=f"(y) : "f"(x)); return y; }
__device__ __forceinline__ float ex2_hw(float x) { float y; asm("ex2.approx.ftz.f32 %0, %1;" : "=f"(y) : "f"(x)); return y; }

__device__ __forceinline__ uint32_t here(uint32_t v) { asm volatile("" : "+r"(v)); return v; }

#define SCHED() asm volatile("pmevent 1;" ::: "memory")
#define WG_FENCE() asm volatile("wgmma.fence.sync.aligned;" ::: "memory")
#define WG_COMMIT() asm volatile("wgmma.commit_group.sync.aligned;" ::: "memory")
#define WG_WAIT(n) asm volatile("wgmma.wait_group.sync.aligned %0;" :: "n"(n) : "memory")

template <int N> __device__ __forceinline__ void pin(float (&d)[N]) {
#pragma unroll
  for (int i = 0; i < N; i++) asm volatile("" : "+f"(d[i]) :: "memory");
}
template <int N> __device__ __forceinline__ void pin(uint32_t (&d)[N]) {
#pragma unroll
  for (int i = 0; i < N; i++) asm volatile("" : "+r"(d[i]) :: "memory");
}

#define WG_D32 "{%0, %1, %2, %3, %4, %5, %6, %7, %8, %9, %10, %11, %12, %13, %14, %15, %16, %17, %18, %19, %20, %21, %22, %23, %24, %25, %26, %27, %28, %29, %30, %31}"
template <int TB> __device__ __forceinline__ void wgmma64_acc(float (&d)[32], const uint32_t* a, uint64_t db) {
  asm volatile("wgmma.mma_async.sync.aligned.m64n64k16.f32.bf16.bf16 " WG_D32 ", {%32, %33, %34, %35}, %36, 1, 1, 1, %37;"
    : "+f"(d[0]), "+f"(d[1]), "+f"(d[2]), "+f"(d[3]), "+f"(d[4]), "+f"(d[5]), "+f"(d[6]), "+f"(d[7]),
      "+f"(d[8]), "+f"(d[9]), "+f"(d[10]), "+f"(d[11]), "+f"(d[12]), "+f"(d[13]), "+f"(d[14]), "+f"(d[15]),
      "+f"(d[16]), "+f"(d[17]), "+f"(d[18]), "+f"(d[19]), "+f"(d[20]), "+f"(d[21]), "+f"(d[22]), "+f"(d[23]),
      "+f"(d[24]), "+f"(d[25]), "+f"(d[26]), "+f"(d[27]), "+f"(d[28]), "+f"(d[29]), "+f"(d[30]), "+f"(d[31])
    : "r"(a[0]), "r"(a[1]), "r"(a[2]), "r"(a[3]), "l"(db), "n"(TB));
}
template <int TB> __device__ __forceinline__ void wgmma64_reuse(float (&d)[32], const uint32_t* a, uint64_t db, uint32_t zero) {
  asm volatile("{\n.reg .pred p;\nsetp.ne.u32 p, %37, 0;\nwgmma.mma_async.sync.aligned.m64n64k16.f32.bf16.bf16 " WG_D32 ", {%32, %33, %34, %35}, %36, p, 1, 1, %38;\n}"
    : "+f"(d[0]), "+f"(d[1]), "+f"(d[2]), "+f"(d[3]), "+f"(d[4]), "+f"(d[5]), "+f"(d[6]), "+f"(d[7]),
      "+f"(d[8]), "+f"(d[9]), "+f"(d[10]), "+f"(d[11]), "+f"(d[12]), "+f"(d[13]), "+f"(d[14]), "+f"(d[15]),
      "+f"(d[16]), "+f"(d[17]), "+f"(d[18]), "+f"(d[19]), "+f"(d[20]), "+f"(d[21]), "+f"(d[22]), "+f"(d[23]),
      "+f"(d[24]), "+f"(d[25]), "+f"(d[26]), "+f"(d[27]), "+f"(d[28]), "+f"(d[29]), "+f"(d[30]), "+f"(d[31])
    : "r"(a[0]), "r"(a[1]), "r"(a[2]), "r"(a[3]), "l"(db), "r"(zero), "n"(TB));
}
template <int TB> __device__ __forceinline__ void wgmma64_set(float (&d)[32], const uint32_t* a, uint64_t db) {
  asm volatile("wgmma.mma_async.sync.aligned.m64n64k16.f32.bf16.bf16 " WG_D32 ", {%32, %33, %34, %35}, %36, 0, 1, 1, %37;"
    : "=f"(d[0]), "=f"(d[1]), "=f"(d[2]), "=f"(d[3]), "=f"(d[4]), "=f"(d[5]), "=f"(d[6]), "=f"(d[7]),
      "=f"(d[8]), "=f"(d[9]), "=f"(d[10]), "=f"(d[11]), "=f"(d[12]), "=f"(d[13]), "=f"(d[14]), "=f"(d[15]),
      "=f"(d[16]), "=f"(d[17]), "=f"(d[18]), "=f"(d[19]), "=f"(d[20]), "=f"(d[21]), "=f"(d[22]), "=f"(d[23]),
      "=f"(d[24]), "=f"(d[25]), "=f"(d[26]), "=f"(d[27]), "=f"(d[28]), "=f"(d[29]), "=f"(d[30]), "=f"(d[31])
    : "r"(a[0]), "r"(a[1]), "r"(a[2]), "r"(a[3]), "l"(db), "n"(TB));
}

__device__ __forceinline__ void wgmma72_acc(float (&d)[36], const uint32_t* a, uint64_t db) {
  asm volatile("wgmma.mma_async.sync.aligned.m64n72k16.f32.bf16.bf16 {%0, %1, %2, %3, %4, %5, %6, %7, %8, %9, %10, %11, %12, %13, %14, %15, %16, %17, %18, %19, %20, %21, %22, %23, %24, %25, %26, %27, %28, %29, %30, %31, %32, %33, %34, %35}, {%36, %37, %38, %39}, %40, 1, 1, 1, 1;"
    : "+f"(d[0]), "+f"(d[1]), "+f"(d[2]), "+f"(d[3]), "+f"(d[4]), "+f"(d[5]), "+f"(d[6]), "+f"(d[7]), "+f"(d[8]),
      "+f"(d[9]), "+f"(d[10]), "+f"(d[11]), "+f"(d[12]), "+f"(d[13]), "+f"(d[14]), "+f"(d[15]), "+f"(d[16]), "+f"(d[17]),
      "+f"(d[18]), "+f"(d[19]), "+f"(d[20]), "+f"(d[21]), "+f"(d[22]), "+f"(d[23]), "+f"(d[24]), "+f"(d[25]), "+f"(d[26]),
      "+f"(d[27]), "+f"(d[28]), "+f"(d[29]), "+f"(d[30]), "+f"(d[31]), "+f"(d[32]), "+f"(d[33]), "+f"(d[34]), "+f"(d[35])
    : "r"(a[0]), "r"(a[1]), "r"(a[2]), "r"(a[3]), "l"(db));
}
__device__ __forceinline__ void wgmma16_acc(float* d, const uint32_t* a, uint64_t db) {
  asm volatile("wgmma.mma_async.sync.aligned.m64n16k16.f32.bf16.bf16 {%0, %1, %2, %3, %4, %5, %6, %7}, {%8, %9, %10, %11}, %12, 1, 1, 1, 0;"
    : "+f"(d[0]), "+f"(d[1]), "+f"(d[2]), "+f"(d[3]), "+f"(d[4]), "+f"(d[5]), "+f"(d[6]), "+f"(d[7])
    : "r"(a[0]), "r"(a[1]), "r"(a[2]), "r"(a[3]), "l"(db));
}
__device__ __forceinline__ void hmma(float (&d)[4], const uint32_t* a, uint32_t b0, uint32_t b1) {
  asm("mma.sync.aligned.m16n8k16.row.col.f32.bf16.bf16.f32 {%0, %1, %2, %3}, {%4, %5, %6, %7}, {%8, %9}, {%0, %1, %2, %3};"
    : "+f"(d[0]), "+f"(d[1]), "+f"(d[2]), "+f"(d[3]) : "r"(a[0]), "r"(a[1]), "r"(a[2]), "r"(a[3]), "r"(b0), "r"(b1));
}

__device__ __forceinline__ void hmma8(float (&d)[4], const uint32_t* a, uint32_t b0) {
  asm("mma.sync.aligned.m16n8k8.row.col.f32.bf16.bf16.f32 {%0, %1, %2, %3}, {%4, %5}, {%6}, {%0, %1, %2, %3};"
    : "+f"(d[0]), "+f"(d[1]), "+f"(d[2]), "+f"(d[3]) : "r"(a[0]), "r"(a[1]), "r"(b0));
}

template <bool FIRST> __device__ __forceinline__ void mma_tile(float (&d)[32], const uint32_t (&a)[16], uint64_t db) {
  WG_FENCE();
#pragma unroll
  for (int s = 0; s < 4; s++) {
    if (FIRST && s == 0) wgmma64_set<1>(d, &a[0], db); else wgmma64_acc<1>(d, &a[4 * s], db + s * 128);
  }
  WG_COMMIT();
}
__device__ __forceinline__ void mma_tile_reuse(float (&d)[32], const uint32_t (&a)[16], uint64_t db) {
  WG_FENCE();
  wgmma64_reuse<1>(d, &a[0], db, blockIdx.y);
#pragma unroll
  for (int s = 1; s < 4; s++) wgmma64_acc<1>(d, &a[4 * s], db + s * 128);
  WG_COMMIT();
}
template <int ROW> __device__ __forceinline__ void fold_step(float (&d)[32], const uint32_t (&mu)[4]) {
  wgmma64_acc<1>(d, mu, (uint64_t)((SM_BASE + SM_CS + ROW * 128) >> 4) | (uint64_t(1) << 16) | (uint64_t(1) << 62));
}
template <int ROW> __device__ __forceinline__ void mma_fold(float (&d)[32], const uint32_t (&mu)[4]) {
  WG_FENCE();
  fold_step<ROW>(d, mu);
  WG_COMMIT();
}
template <int ROW> __device__ __forceinline__ void mma_tile_fold(float (&d)[32], const uint32_t (&a)[16], uint64_t db, const uint32_t (&mu)[4]) {
  WG_FENCE();
#pragma unroll
  for (int s = 0; s < 4; s++) wgmma64_acc<1>(d, &a[4 * s], db + s * 128);
  fold_step<ROW>(d, mu);
  WG_COMMIT();
}
__device__ __forceinline__ void mma_add_half(float (&d)[32], const uint32_t (&a)[16]) {
  const uint64_t db = (uint64_t)((SM_BASE + SM_EYE) >> 4) | (uint64_t(8) << 16) | (uint64_t(8) << 32);
  WG_FENCE();
#pragma unroll
  for (int s = 0; s < 4; s++) wgmma16_acc(&d[8 * s], &a[4 * s], db);
  WG_COMMIT();
}
#define ACQUIRE(f) mbar_wait(SM_BASE + SM_FULL + ((f) % NSTAGE) * 8, ((f) / NSTAGE) & 1)
__device__ __forceinline__ void mbar_probe(uint32_t& ok, uint32_t bar, uint32_t parity) {
  asm volatile("{\n.reg .pred p;\nmbarrier.test_wait.parity.shared::cta.b64 p, [%1], %2;\nselp.u32 %0, %0, 0, p;\n}"
               : "+r"(ok) : "r"(bar), "r"(parity) : "memory");
}
template <int F, int N> __device__ __forceinline__ uint32_t probe_n() {
  static_assert(F % NSTAGE + N <= NSTAGE, "stages must not wrap");
  uint32_t ok = 1;
#pragma unroll
  for (int i = 0; i < N; i++) mbar_probe(ok, SM_BASE + SM_FULL + (F % NSTAGE + i) * 8, (F / NSTAGE) & 1);
  return ok;
}
template <int F, int N> __device__ __forceinline__ void settle_n(uint32_t ok) {
  if (__builtin_expect(!ok, 0)) {
#pragma unroll 1
    for (int i = 0; i < N; i++) mbar_wait(SM_BASE + SM_FULL + (F % NSTAGE + i) * 8, (F / NSTAGE) & 1);
  }
}
template <int F, int N> __device__ __forceinline__ void acquire_n() { settle_n<F, N>(probe_n<F, N>()); }
#define RELEASE(f0, f1) do { if (lane == 0) { _Pragma("unroll") for (int f_ = (f0); f_ <= (f1); f_++) mbar_arrive(SM_BASE + SM_EMPTY + (f_ % NSTAGE) * 8); } } while (0)
constexpr uint64_t RING = (uint64_t)(SM_BASE >> 4) | (uint64_t(1) << 16) | (uint64_t(64) << 32) | (uint64_t(1) << 62);
#define LO(f) (RING + ((f) % NSTAGE) * 1024)
#define HI(f) (RING + ((f) % NSTAGE) * 1024 + 512)

template <int C> __device__ __forceinline__ uint4* peer(uint4* p) {
  asm volatile("" : "+l"(p));
  return (uint4*)((uintptr_t)p ^ (C * X_SIZE * sizeof(uint4)));
}
__device__ __forceinline__ uint32_t clock_now() { uint32_t c; asm volatile("mov.u32 %0, %%clock;" : "=r"(c) :: "memory"); return c; }
__device__ __forceinline__ void publish(uint4* dst, uint32_t (&a)[16], uint32_t tag) {
#pragma unroll
  for (int s = 0; s < 4; s++) a[4 * s] = (a[4 * s] & ~1u) | tag;
  pin(a);
  SCHED();
#pragma unroll
  for (int s = 0; s < 4; s++) st_vec(dst + s * 128, a[4 * s], a[4 * s + 1], a[4 * s + 2], a[4 * s + 3]);
  SCHED();
}
__device__ __forceinline__ void fetch(const uint4* src, uint32_t (&a)[16]) {
#pragma unroll
  for (int s = 0; s < 4; s++) ld_vec(src + s * 128, a[4 * s], a[4 * s + 1], a[4 * s + 2], a[4 * s + 3]);
}
__device__ __forceinline__ uint32_t miss(const uint32_t (&a)[16], uint32_t tag) {
  return (a[0] ^ tag) | (a[4] ^ tag) | (a[8] ^ tag) | (a[12] ^ tag);
}
__device__ __forceinline__ bool stale(uint32_t v) { return __any_sync(0xffffffffu, here(v) & 1u); }
#define GD0 400
#define GD1 400
#define RD 550
constexpr uint32_t SCATTER_DELAY = RD;
__device__ __forceinline__ void stat_fetch(const Scratch* sc, uint32_t (&st)[4]) {
  const uint32_t th = here(threadIdx.x);
  ld_vec(&sc->x[(blockIdx.x & ~3u) + (th & 3)][X_ST + (th >> 2)], st[0], st[1], st[2], st[3]);
}
template <int C, int SLOT> __device__ __forceinline__ void gather_first(uint32_t (&A)[4][16], uint32_t (&st)[4], const Scratch* sc, uint4* xp,
                                                                        uint32_t tag, uint32_t sent) {
  while (clock_now() - sent < (SLOT == X_AG0 ? GD0 : GD1)) {}
  fetch(peer<1>(xp) + SLOT, A[1]); fetch(peer<2>(xp) + SLOT, A[2]); fetch(peer<3>(xp) + SLOT, A[3]);
  if (SLOT == X_AG0) stat_fetch(sc, st);
  uint32_t spin = 0;
  while (__builtin_expect(stale(miss(A[1], tag) | miss(A[C], tag)), 0) && ++spin < SPIN_LIMIT) {
    fetch(peer<1>(xp) + SLOT, A[1]);
    if (C == 2) fetch(peer<2>(xp) + SLOT, A[2]);
  }
}
template <int C, int SLOT> __device__ __forceinline__ void gather_rest(uint32_t (&A)[4][16], uint4* xp, uint32_t tag) {
  SCHED();
  uint32_t spin = 0;
  while (__builtin_expect(stale(miss(A[C + 1], tag) | miss(A[3], tag)), 0) && ++spin < SPIN_LIMIT) {
    if (C == 1) fetch(peer<2>(xp) + SLOT, A[2]);
    fetch(peer<3>(xp) + SLOT, A[3]);
  }
}
__device__ __forceinline__ void pack_acc(const float (&d)[32], uint32_t (&a)[16]) {
#pragma unroll
  for (int i = 0; i < 16; i++) a[i] = pack2(d[2 * i], d[2 * i + 1]);
}
__device__ __forceinline__ void frag_store(uint32_t slot, const uint32_t (&a)[16]) {
#pragma unroll
  for (int s = 0; s < 4; s++) sts128(slot + s * 512, a[4 * s], a[4 * s + 1], a[4 * s + 2], a[4 * s + 3]);
}
__device__ __forceinline__ void tile_store(uint32_t maddr, const uint32_t (&a)[16]) {
#pragma unroll
  for (int s = 0; s < 4; s++) stsm4(maddr ^ (s << 5), &a[4 * s]);
}
__device__ __forceinline__ void tile_load(uint32_t maddr, uint32_t (&a)[16]) {
#pragma unroll
  for (int s = 0; s < 4; s++) ldsm4(maddr ^ (s << 5), &a[4 * s]);
}

__device__ __forceinline__ void res_load(uint32_t maddr, float (&d)[32]) {
  uint32_t a[16];
  tile_load(here(maddr) + 3 * TILE_BYTES, a);
#pragma unroll
  for (int i = 0; i < 16; i++) { d[2 * i] = bf_lo(a[i]); d[2 * i + 1] = bf_hi(a[i]); }
  pin(d);
}

struct RowAcc { float s[4], u[2][4], v[2][4]; };
__device__ __forceinline__ void row_acc(RowAcc& t, const uint32_t (&a)[16]) {
#pragma unroll
  for (int s = 0; s < 8; s++) {
    if ((s & 1) == 0) hmma(t.s, &a[2 * s], 0x3F803F80u, 0x3F803F80u);
    hmma8(t.u[s & 1], &a[2 * s], a[2 * s]);
    hmma8(t.v[s & 1], &a[2 * s], a[2 * s + 1]);
  }
}
__device__ __forceinline__ float2 row_squares(const RowAcc& t, bool odd) {
  return make_float2(odd ? t.u[0][1] + t.u[1][1] : t.u[0][0] + t.u[1][0], odd ? t.v[0][3] + t.v[1][3] : t.v[0][2] + t.v[1][2]);
}
__device__ __forceinline__ void stat_publish(const uint32_t (&a)[16], Scratch* sc, uint32_t th, uint32_t tag) {
  RowAcc t = {};
  row_acc(t, a);
  const float2 q = row_squares(t, th & 4);
  if ((th & 3) == ((th >> 3) & 3))
    st_vec(&sc->x[blockIdx.x][X_ST + (th >> 2)], (__float_as_uint(t.s[0]) & ~1u) | tag, __float_as_uint(q.x), __float_as_uint(t.s[2]), __float_as_uint(q.y));
}
struct RowNorm { float m0, rs0, m1, rs1; };
__device__ __forceinline__ RowNorm row_norm(float s0, float q0, float s1, float q1, float scale) {
  RowNorm n;
  n.m0 = s0 * (1.f / DM); n.m1 = s1 * (1.f / DM);
  n.rs0 = scale * rsqrt_hw(fmaxf(fmaf(-n.m0, n.m0, q0 * (1.f / DM)), 0.f) + LN_EPS);
  n.rs1 = scale * rsqrt_hw(fmaxf(fmaf(-n.m1, n.m1, q1 * (1.f / DM)), 0.f) + LN_EPS);
  return n;
}
__device__ __forceinline__ RowNorm stat_finish(const Scratch* sc, uint32_t (&st)[4], uint32_t tag, float scale) {
  uint32_t spin = 0;
  while (__builtin_expect(stale(st[0] ^ tag), 0) && ++spin < SPIN_LIMIT) stat_fetch(sc, st);
  float f[4];
#pragma unroll
  for (int i = 0; i < 4; i++) {
    f[i] = __uint_as_float(st[i]);
    f[i] += __shfl_xor_sync(0xffffffffu, f[i], 1);
    f[i] += __shfl_xor_sync(0xffffffffu, f[i], 2);
  }
  return row_norm(f[0], f[1], f[2], f[3], scale);
}
__device__ __forceinline__ void mean_frag(uint32_t (&mu)[4], const RowNorm& n, bool sel) {
  const float a = sel ? -n.m0 : 0.f, c = sel ? -n.m1 : 0.f;
  mu[0] = pack2(a, a); mu[1] = pack2(c, c);
  const float al = a - bf_lo(mu[0]), cl = c - bf_lo(mu[1]);
  mu[2] = pack2(al, al); mu[3] = pack2(cl, cl);
  pin(mu);
}
__device__ __forceinline__ void centre(uint32_t (&a)[16], uint32_t m0, uint32_t m1) {
#pragma unroll
  for (int i = 0; i < 16; i++) asm("sub.rn.bf16x2 %0, %0, %1;" : "+r"(a[i]) : "r"((i & 1) ? m1 : m0));
  pin(a);
}
__device__ __forceinline__ void scale_pack(const float (&d)[32], uint32_t (&a)[16], float rs0, float rs1) {
#pragma unroll
  for (int i = 0; i < 16; i++) { const float rs = (i & 1) ? rs1 : rs0; a[i] = pack2(d[2 * i] * rs, d[2 * i + 1] * rs); }
}
template <int S> __device__ __forceinline__ void silu_seg(float (&acc)[4][32], float (&tn)[2][4], uint32_t (&H)[4][16], float rs0, float rs1) {
  if (S >= 2) {
    const float* h = &acc[(S - 2) >> 3][4 * ((S - 2) & 7)];
    const float* v = tn[S & 1];
    uint32_t* o = &H[(S - 2) >> 3][2 * ((S - 2) & 7)];
    o[0] = pack2(fmaf(h[0], v[0], h[0]), fmaf(h[1], v[1], h[1]));
    o[1] = pack2(fmaf(h[2], v[2], h[2]), fmaf(h[3], v[3], h[3]));
    asm volatile("" : "+r"(o[0]), "+r"(o[1]));
  }
  if (S >= 1 && S <= 32) {
#pragma unroll
    for (int k = 0; k < 4; k++) tn[(S - 1) & 1][k] = tanh_hw(acc[((S - 1) >> 3) & 3][4 * ((S - 1) & 7) + k]);
  }
  if (S < 32) {
    float* h = &acc[(S >> 3) & 3][4 * (S & 7)];
    h[0] *= rs0; h[1] *= rs0; h[2] *= rs1; h[3] *= rs1;
    asm volatile("" : "+f"(h[0]), "+f"(h[1]), "+f"(h[2]), "+f"(h[3]));
  }
  SCHED();
}
template <int S0, int S1> __device__ __forceinline__ void silu_segs(float (&acc)[4][32], float (&tn)[2][4], uint32_t (&H)[4][16], float rs0, float rs1) {
  silu_seg<S0>(acc, tn, H, rs0, rs1);
  if constexpr (S0 + 1 < S1) silu_segs<S0 + 1, S1>(acc, tn, H, rs0, rs1);
}
template <int HALF> __device__ __forceinline__ void send_half(uint4* dst, const float (&d)[32], uint32_t tag) {
  uint32_t o[8];
#pragma unroll
  for (int i = 0; i < 8; i++) o[i] = pack2(d[16 * HALF + 2 * i], d[16 * HALF + 2 * i + 1]);
  o[0] = (o[0] & ~1u) | tag; o[4] = (o[4] & ~1u) | tag;
  pin(o);
  SCHED();
  st_vec(dst + HALF * 256, o[0], o[1], o[2], o[3]);
  st_vec(dst + HALF * 256 + 128, o[4], o[5], o[6], o[7]);
  SCHED();
}
__device__ __forceinline__ uint32_t send_residual(uint32_t (&a)[16], Scratch* sc, uint4* xp, uint32_t maddr, uint32_t tag) {
  const uint32_t exact[4] = {a[0], a[4], a[8], a[12]};
  publish(xp + X_AG0, a, tag);
  const uint32_t sent = clock_now();
  const uint32_t th = here(threadIdx.x);
  stat_publish(a, sc, th, tag);
  tile_store(here(maddr) + 3 * TILE_BYTES, a);
  stsm4(SM_BASE + SM_STG + 3 * TILE_BYTES + (th >> 5) * 2048 + (th & 7) * 128 + ((((th >> 2) & 6) ^ (th & 7)) << 4), exact);
  return sent;
}
template <int F, int N> __device__ __forceinline__ uint32_t proj_residual(uint32_t (&A)[4][16], Scratch* sc, uint4* xp, uint32_t maddr,
                                                                          uint32_t tag, uint32_t sent, int lane) {
  float acc[32];
  uint32_t st[4];
  acquire_n<F, N>();
  if (F == F_PW2) acquire_n<0, 5>();
  res_load(maddr, acc);
  mma_tile<false>(acc, A[0], LO(F));
  gather_first<2, X_AG1>(A, st, sc, xp, tag, sent);
  mma_tile<false>(acc, A[1], HI(F));
  mma_tile<false>(acc, A[2], LO(F + 1));
  gather_rest<2, X_AG1>(A, xp, tag);
  PROF_MARK0(F == F_WO ? 11 : 16);
  mma_tile<false>(acc, A[3], HI(F + 1));
  RELEASE(F - 2, F - 1);
  WG_WAIT(0); pin(acc);
  pack_acc(acc, A[0]);
  return send_residual(A[0], sc, xp, maddr, tag);
}

__device__ __forceinline__ uint64_t ring_desc(uint32_t lo) { return (RING & ~uint64_t(0xFFFFFFFFu)) | lo; }
__device__ __forceinline__ void qk_tile(float (&S)[32], const uint32_t (&Q)[16], uint32_t dk) {
  wgmma64_reuse<0>(S, &Q[0], ring_desc(dk), blockIdx.y);
#pragma unroll
  for (int s = 1; s < 4; s++) wgmma64_acc<0>(S, &Q[4 * s], ring_desc(dk + s * 2));
}
__device__ __forceinline__ void qk_shift(float (&S)[32], const uint32_t (&nm)[4]) { wgmma64_acc<0>(S, nm, (uint64_t)((SM_BASE + SM_ONE) >> 4)); }
constexpr uint32_t RING_K = (uint32_t)RING, V_STEP = 1u - (1u << 16);
constexpr uint32_t RING_V = (SM_BASE >> 4) | (((SM_STG + 2 * TILE_BYTES) >> 4) << 16);
__device__ __forceinline__ void pv_tile(float (&O)[36], const uint32_t (&P)[16], uint32_t dv, uint32_t pad) {
#pragma unroll
  for (int s = 0; s < 4; s++) wgmma72_acc(O, &P[4 * s], ring_desc(dv + s * 128 * V_STEP + (s < 2 ? 0 : (s - 1) * pad)));
}
__device__ __forceinline__ void attn_step(const float (&Sc)[32], float (&Sn)[32], uint32_t (&Pc)[16], uint32_t (&Pp)[16], float (&O)[36],
                                          const uint32_t (&Q)[16], const uint32_t (&nm)[4], uint32_t dk, uint32_t dv, bool next, bool prev) {
  if (next) {
    WG_FENCE();
    qk_tile(Sn, Q, dk);
    qk_shift(Sn, nm);
  }
  if (prev) {
    WG_FENCE();
    pv_tile(O, Pp, dv, 0);
  }
  WG_COMMIT();
  SCHED();
#pragma unroll
  for (int i = 0; i < 16; i++) Pc[i] = pack2(ex2_hw(Sc[2 * i]), ex2_hw(Sc[2 * i + 1]));
  pin(Pc);
  SCHED();
}
template <int R> __device__ __forceinline__ float tile_max(const float (&S)[32]) {
  float t[4];
#pragma unroll
  for (int j = 0; j < 4; j++) t[j] = fmaxf(fmaxf(S[8 * j + R], S[8 * j + R + 1]), fmaxf(S[8 * j + R + 4], S[8 * j + R + 5]));
  float n = fmaxf(fmaxf(t[0], t[1]), fmaxf(t[2], t[3]));
  n = fmaxf(n, __shfl_xor_sync(0xffffffffu, n, 1));
  return fmaxf(n, __shfl_xor_sync(0xffffffffu, n, 2));
}
__device__ __forceinline__ void attention_exact(float (&O)[36], const uint32_t (&Q)[16], const Scratch* sc, int bh, int lane, int half) {
  const char* kb = (const char*)&sc->kv[bh][0][0][0];
  const char* vb = (const char*)&sc->kv[bh][1][0][0];
  const int g = lane >> 2, q = lane & 3;
  float m0 = -INFINITY, m1 = -INFINITY, l0 = 0.f, l1 = 0.f;
  float o[4][4] = {};
#pragma unroll 1
  for (int k0 = 0; k0 < T_SEQ; k0 += 8) {
    float s[4] = {0.f, 0.f, 0.f, 0.f};
#pragma unroll
    for (int c = 0; c < 8; c++) hmma8(s, &Q[2 * c], __ldcg((const uint32_t*)(kb + (k0 + g) * 128 + ((c ^ g) << 4) + q * 4)));
    float n0 = fmaxf(s[0], s[1]), n1 = fmaxf(s[2], s[3]);
    n0 = fmaxf(n0, __shfl_xor_sync(0xffffffffu, n0, 1)); n1 = fmaxf(n1, __shfl_xor_sync(0xffffffffu, n1, 1));
    n0 = fmaxf(m0, fmaxf(n0, __shfl_xor_sync(0xffffffffu, n0, 2))); n1 = fmaxf(m1, fmaxf(n1, __shfl_xor_sync(0xffffffffu, n1, 2)));
    const float a0 = ex2_hw(m0 - n0), a1 = ex2_hw(m1 - n1);
    m0 = n0; m1 = n1;
    const uint32_t pp[2] = {pack2(ex2_hw(s[0] - n0), ex2_hw(s[1] - n0)), pack2(ex2_hw(s[2] - n1), ex2_hw(s[3] - n1))};
    l0 = fmaf(l0, a0, bf_lo(pp[0]) + bf_hi(pp[0])); l1 = fmaf(l1, a1, bf_lo(pp[1]) + bf_hi(pp[1]));
#pragma unroll
    for (int j = 0; j < 4; j++) {
      const int c = 4 * half + j;
      const uint32_t v0 = __ldcg((const uint16_t*)(vb + (k0 + 2 * q) * 128 + ((c ^ (2 * q)) << 4) + g * 2));
      const uint32_t v1 = __ldcg((const uint16_t*)(vb + (k0 + 2 * q + 1) * 128 + ((c ^ (2 * q + 1)) << 4) + g * 2));
      o[j][0] *= a0; o[j][1] *= a0; o[j][2] *= a1; o[j][3] *= a1;
      hmma8(o[j], pp, v0 | (v1 << 16));
    }
  }
  l0 += __shfl_xor_sync(0xffffffffu, l0, 1); l1 += __shfl_xor_sync(0xffffffffu, l1, 1);
  O[32] = l0 + __shfl_xor_sync(0xffffffffu, l0, 2); O[34] = l1 + __shfl_xor_sync(0xffffffffu, l1, 2);
#pragma unroll
  for (int i = 0; i < 16; i++) O[i] = o[i >> 2][i & 3];
}

__device__ __forceinline__ uint32_t fill_entry(int f, int r) {
  int m, x = r, y, dx = 0;
  if (f < F_QKV || f >= 48) {
    const int i = f & 15;
    m = f < F_QKV ? M_FF1A : M_FF2A;
    if (i < 8) { x = 4 * r + ((0xE2u >> i) & 1) * 2; y = r ^ ((0xE790u >> (2 * i)) & 3); dx = 1; }
    else { m++; x = r ^ (((i >> 1) - 3) & 3); y = 4 * r + 2 * (i & 1); }
  } else if (f < F_KV) {
    const int i = f - F_QKV;
    m = M_QKV;
    if (i == 1 || i >= 5) { y = r ^ (i == 1 ? 0 : 2); }
    else { x = 4 + r; y = r ^ (i ? i - 1 : 0); dx = 4; }
  } else if (f >= F_PW1 && f < F_PW2) {
    m = M_PW1; y = r ^ (f - F_PW1); dx = 4;
  } else {
    m = f < F_PW1 ? M_WO : M_PW2; y = r ^ ((f & 1) * 2);
  }
  return m | (x << 4) | (y << 8) | (dx << 16);
}
__device__ __forceinline__ void tma_fill(uint32_t st, const CUtensorMap* map, uint32_t x, uint32_t y, uint32_t x2, uint32_t y2) {
  asm volatile("{\n.reg .pred p;\nelect.sync _|p, 0xffffffff;\n"
               "@p mbarrier.arrive.expect_tx.shared::cta.b64 _, [%1], 16384;\n"
               "@p cp.async.bulk.tensor.2d.shared::cluster.global.mbarrier::complete_tx::bytes [%0], [%2, {%3, %4}], [%1];\n"
               "@p cp.async.bulk.tensor.2d.shared::cluster.global.mbarrier::complete_tx::bytes [%0 + 8192], [%2, {%5, %6}], [%1];\n}"
               :: "r"(SM_BASE + st * STAGE_BYTES), "r"(SM_BASE + SM_FULL + st * 8), "l"(map), "r"(x), "r"(y), "r"(x2), "r"(y2) : "memory");
}
template <int F0, int N> __device__ __forceinline__ void weight_fills(const Params& p, uint32_t entry) {
  uint32_t st = F0 % NSTAGE, parity = ((F0 / NSTAGE) & 1) ^ 1, e = __shfl_sync(0xffffffffu, entry, 0);
#pragma unroll 1
  for (int i = 1; i <= N; i++) {
    const uint32_t x = (e << 2) & 0x3C0, y = (e >> 2) & 0x3FC0, dx = (e >> 16) << 6;
    const CUtensorMap* map = &p.map[e & 15];
    e = __shfl_sync(0xffffffffu, entry, i);
    mbar_wait(SM_BASE + SM_EMPTY + st * 8, parity);
    tma_fill(st, map, x, y, x + dx, dx ? y : y ^ 64);
    if (++st == NSTAGE) { st = 0; parity ^= 1; }
  }
}
__device__ __forceinline__ uint32_t kv_poll(const uint32_t* flag, uint32_t prev) {
  uint32_t v;
  asm volatile("ld.relaxed.gpu.global.u32 %0, [%1];" : "=r"(v) : "l"(flag) : "memory");
  return __ballot_sync(0xffffffffu, v - 1 == prev);
}
__device__ __forceinline__ void kv_fills(const Scratch* sc, int bh, int kind, uint32_t prev, const uint32_t* flag, uint32_t ready) {
#pragma unroll 1
  for (int j = 0; j < 8; j++) {
    uint32_t spin = 0;
#pragma unroll 1
    while (((ready >> (2 * j)) & 3) != 3 && ++spin < SPIN_LIMIT) ready = kv_poll(flag, prev);
    const uint32_t st = (j < 6 ? 4 * (j >> 1) : 0) + (j & 1) + 2 * kind;
    mbar_wait(SM_BASE + SM_EMPTY + st * 8, j < 6);
    asm volatile("{\n.reg .pred p;\nelect.sync _|p, 0xffffffff;\n"
                 "@p mbarrier.arrive.expect_tx.shared::cta.b64 _, [%1], 16384;\n"
                 "@p cp.async.bulk.shared::cluster.global.mbarrier::complete_tx::bytes [%0], [%2], 16384, [%1];\n}"
                 :: "r"(SM_BASE + st * STAGE_BYTES), "r"(SM_BASE + SM_FULL + st * 8), "l"(sc->kv[bh][kind][2 * j]) : "memory");
    PROF_AT(256 + 512 + (10 + kind * 8 + j) * 4);
  }
}
__device__ __forceinline__ void l2_prefetch(const void* p, uint32_t total, int b) {
  const uint32_t part = total / NCTA;
  asm volatile("cp.async.bulk.prefetch.L2.global [%0], %1;" :: "l"((const char*)p + (size_t)b * part), "r"(part) : "memory");
}

__global__ void __launch_bounds__(384, 1) conformer_kernel(Scratch* __restrict__ sc, __nv_bfloat16* __restrict__ out,
                                                           const __nv_bfloat16* __restrict__ dw, const __nv_bfloat16* __restrict__ xin,
                                                           const __nv_bfloat16* __restrict__ w_ff1a, const __grid_constant__ Params p) {
  extern __shared__ __align__(1024) uint8_t smem[];
  const int tid = threadIdx.x, lane = tid & 31;
  if (tid == 0) {
    l2_prefetch(xin, 2 * T_SEQ * DM * 2, blockIdx.x);
    l2_prefetch(w_ff1a, 256 * 1024 * 2, blockIdx.x);
  }
  const int cw = __shfl_sync(0xffffffffu, tid >> 5, 0), wg = cw >> 2, w = cw & 3;
  const int b = blockIdx.x, r = b & 3, batch = b >> 6, t = (b >> 2) & 15;
  if ((uint32_t)__cvta_generic_to_shared(smem) != SM_BASE) return;
  PROF_MARK(0);
  PROF_TIME(30);

  if (wg == 2) {
    asm volatile("setmaxnreg.dec.sync.aligned.u32 40;");
    if (cw == 8) {
      if (lane == 0) {
        asm volatile("prefetch.tensormap [%0];" :: "l"(&p.map[M_X]) : "memory");
        asm volatile("prefetch.tensormap [%0];" :: "l"(&p.map[M_FF1A]) : "memory");
#pragma unroll
        for (int i = 0; i < 4; i++) mbar_init(SM_BASE + SM_XBAR + i * 8, 1);
#pragma unroll
        for (int i = 0; i < NSTAGE; i++) mbar_init(SM_BASE + SM_FULL + i * 8, 1);
        fence_async_smem();
      }
      __syncwarp();
      bar_arrive(0, 320);
      PROF_MARK(9);
#pragma unroll
      for (int f = 0; f < 8; f++) {
        const uint32_t x = 256 * r + ((0xE2u >> f) & 1) * 128, y = (r ^ ((0xE790u >> (2 * f)) & 3)) * 64;
#pragma unroll
        for (int c = 0; c < (f == 0 ? 4 : 0); c++)
          asm volatile("{\n.reg .pred p;\nelect.sync _|p, 0xffffffff;\n"
                       "@p mbarrier.arrive.expect_tx.shared::cta.b64 _, [%1], 8192;\n"
                       "@p cp.async.bulk.tensor.3d.shared::cluster.global.mbarrier::complete_tx::bytes [%0], [%2, {%3, %4, %5}], [%1];\n}"
                       :: "r"(SM_BASE + SM_STG + (3 - c) * TILE_BYTES), "r"(SM_BASE + SM_XBAR + c * 8), "l"(&p.map[M_X]),
                          "r"((r ^ c) * 64), "r"(t * 64), "r"(batch) : "memory");
        tma_fill(f, &p.map[M_FF1A], x, y, x + 64, y);
      }
      PROF_MARK(1);
      uint32_t entry[2];
#pragma unroll 1
      for (int i = 0; i < 2; i++) { entry[1] = fill_entry(8 + i * 32 + lane, r); if (i == 0) entry[0] = entry[1]; }
      bar_sync(BAR_INIT, 64);
      weight_fills<8, F_KV - 8>(p, entry[0]);
      mbar_wait(SM_BASE + SM_EMPTY + (F_WO % NSTAGE) * 8, 1);
      weight_fills<F_WO, F_TOTAL - F_WO>(p, entry[1]);
    } else if (here(cw) != 11) {
      const int kind = w - 1;
      const uint32_t prev = ((volatile uint32_t*)sc->epoch)[b];
      if (kind == 0) {
        if (lane == 0) {
#pragma unroll
          for (int i = 0; i < NSTAGE; i++) mbar_init(SM_BASE + SM_EMPTY + i * 8, 4);
        }
        __syncwarp();
        bar_arrive(0, 320);
        bar_arrive(BAR_INIT, 64);
      } else {
        uint32_t v, spin = 0;
#pragma unroll 1
        do {
          asm volatile("ld.relaxed.gpu.global.u32 %0, [%1];" : "=r"(v) : "l"(sc->ready[(b & ~3) + (lane & 3)]) : "memory");
        } while (__any_sync(0xffffffffu, v - 1 != prev) && ++spin < SPIN_LIMIT);
        bar_arrive(BAR_RDY, 160);
PROF_MARK(3);
      }
      const uint32_t* flag = sc->flag[batch * 4 + r][kind * 16 + (lane & 15)];
      const uint32_t ready = kv_poll(flag, prev);
      if (kind == 0) bar_sync(BAR_K, 160); else bar_sync(BAR_V, 160);
      if (lane == 0) {
        asm volatile("cp.async.bulk.global.shared::cta.bulk_group [%0], [%1], %2;"
                     :: "l"(&sc->kv[batch * 4 + r][kind][t][0]), "r"(SM_BASE + SM_STG + kind * TILE_BYTES), "r"(TILE_BYTES) : "memory");
PROF_MARK(4 + kind * 2);
        asm volatile("cp.async.bulk.commit_group;\ncp.async.bulk.wait_group 0;" ::: "memory");
PROF_MARK(5 + kind * 2);
        asm volatile("st.relaxed.gpu.global.u32 [%0], %1;" :: "l"(sc->flag[batch * 4 + r][kind * 16 + t]), "r"(prev + 1) : "memory");
      }
      __syncwarp();
      kv_fills(sc, batch * 4 + r, kind, prev, flag, ready);
    } else {
      const uint32_t epoch = ((volatile uint32_t*)sc->epoch)[b] + 1;
      if (lane == 0 && epoch) {
        asm volatile("prefetch.tensormap [%0];" :: "l"(&p.map[M_FF1B]) : "memory");
        l2_prefetch(p.w_ff1b, 1024 * 256 * 2, b);
        l2_prefetch(p.w_qkv, 256 * 768 * 2, b);
        l2_prefetch(p.w_pw1, 256 * 512 * 2, b);
        l2_prefetch(p.w_ff2a, 256 * 1024 * 2, b);
      }
#pragma unroll 1
      for (int i = 0; i < 22; i++) {
        const uint32_t t0 = clock_now();
        uint4* dst = &sc->x[b][i * 96 + lane];
        st_vec(dst, 0u, 0u, 0u, 0u); st_vec(dst + 32, 0u, 0u, 0u, 0u); st_vec(dst + 64, 0u, 0u, 0u, 0u);
        while (clock_now() - t0 < 60) {}
      }
PROF_MARK(28);
      asm volatile("fence.acq_rel.gpu;" ::: "memory");
      __syncwarp();
      if (lane == 0) {
        asm volatile("st.relaxed.gpu.global.u32 [%0], %1;" :: "l"(sc->ready[b]), "r"(epoch) : "memory");
        l2_prefetch(p.w_o, 256 * 256 * 2, b);
        l2_prefetch(p.w_pw2, 256 * 256 * 2, b);
        l2_prefetch(p.w_ff2b, 1024 * 256 * 2, b);
#pragma unroll
        for (int i = M_QKV; i < M_X; i++) asm volatile("prefetch.tensormap [%0];" :: "l"(&p.map[i]) : "memory");
      }
      PROF_MARK(2);
    }
  } else {
    asm volatile("setmaxnreg.inc.sync.aligned.u32 232;");
    const int q = lane & 3, th = tid & 127;
    constexpr uint32_t stg = SM_BASE + SM_STG;
    const uint32_t mrow = 16 * w + (lane & 15);
    const uint32_t maddr = stg + mrow * 128 + (((lane >> 4) ^ (lane & 7)) << 4);
    const uint32_t qslot = stg + 2 * TILE_BYTES + w * 2048 + lane * 16;
    uint4* const xp = &sc->x[b][th];
    const int nvalid = T_SEQ - t * 64, row0 = 16 * w + (lane >> 2);

    uint32_t A[4][16];
    uint32_t sent = 0;
    uint32_t st[4];
    if (tid < 144) sts128(SM_BASE + SM_CS + tid * 16, 0, 0, 0, 0);
    if (wg == 1) sts32(SM_BASE + SM_EYE + th * 4, th >= 96 ? 0x3F803F80u : ((th & 32) == 0 && (th & 3) == ((th >> 3) & 3)) ? (0x3F00u << ((th & 4) * 4)) : 0u);
    fence_async_smem();
    bar_sync(0, 320);
    if (wg == 0) {
      RowAcc ra = {};
      mbar_wait(SM_BASE + SM_XBAR, 0);
      PROF_MARK0(45);
      tile_load(maddr + 3 * TILE_BYTES, A[0]);
#pragma unroll
      for (int c = 1; c < 4; c++) {
        mbar_wait(SM_BASE + SM_XBAR + c * 8, 0);
        tile_load(maddr + (3 - c) * TILE_BYTES, A[c]);
        row_acc(ra, A[c - 1]);
      }
      PROF_MARK(1);
      row_acc(ra, A[3]);
      PROF_MARK0(46);
      const float m0 = ra.s[0] * (1.f / DM), m1 = ra.s[2] * (1.f / DM);
      st[0] = pack2(m0, m0); st[1] = pack2(m1, m1);
      centre(A[0], st[0], st[1]);
      const float2 sq = row_squares(ra, lane & 4);
      st[2] = __float_as_uint(fmaf(-m0, m0, sq.x * (1.f / DM))); st[3] = __float_as_uint(fmaf(-m1, m1, sq.y * (1.f / DM)));
    } else {
      const uint32_t epoch = ((volatile uint32_t*)sc->epoch)[b] + 1, tag = epoch & 1;
      mbar_wait(SM_BASE + SM_FULL + 4 * 8, 0);
      PROF_MARK(5);
      if (b < 72) {
        const __nv_bfloat16* wp; int ld, col;
        if (b < 24) { wp = p.w_qkv; ld = 768; col = b * 32; }
        else if (b < 40) { wp = p.w_pw1; ld = 512; col = (b - 24) * 32; }
        else { wp = p.w_ff2a; ld = 1024; col = (b - 40) * 32; }
        const uint4* src = (const uint4*)(wp + (size_t)(th >> 2) * ld + col + q * 8);
        float c[8] = {0.f, 0.f, 0.f, 0.f, 0.f, 0.f, 0.f, 0.f};
#pragma unroll 1
        for (int h = 0; h < 2; h++, src += 16 * ld) {
#pragma unroll
          for (int i = 0; i < 4; i++) {
            const uint4 v = __ldg(src + i * 4 * ld);
            c[0] += bf_lo(v.x); c[1] += bf_hi(v.x); c[2] += bf_lo(v.y); c[3] += bf_hi(v.y);
            c[4] += bf_lo(v.z); c[5] += bf_hi(v.z); c[6] += bf_lo(v.w); c[7] += bf_hi(v.w);
          }
        }
#pragma unroll 1
        for (int m = 4; m <= 16; m <<= 1)
#pragma unroll
          for (int k = 0; k < 8; k++) c[k] += __shfl_xor_sync(0xffffffffu, c[k], m);
        if (lane < 4) {
          const uint32_t a = SM_BASE + SM_CS + 1792 + w * 128 + lane * 32;
          sts128(a, __float_as_uint(c[0]), __float_as_uint(c[1]), __float_as_uint(c[2]), __float_as_uint(c[3]));
          sts128(a + 16, __float_as_uint(c[4]), __float_as_uint(c[5]), __float_as_uint(c[6]), __float_as_uint(c[7]));
        }
        bar_sync(BAR_WG1, 128);
        if (th < 8) {
          float o[4] = {0.f, 0.f, 0.f, 0.f};
#pragma unroll 1
          for (int k = 0; k < 4; k++) {
            uint32_t e[4];
            lds128(SM_BASE + SM_CS + 1792 + k * 128 + th * 16, e[0], e[1], e[2], e[3]);
#pragma unroll
            for (int i = 0; i < 4; i++) o[i] += __uint_as_float(e[i]);
          }
          st_vec(&sc->cs[b * 8 + th], (__float_as_uint(o[0]) & ~1u) | tag, __float_as_uint(o[1]), __float_as_uint(o[2]), __float_as_uint(o[3]));
        }
      }
      bar_sync(BAR_WG1, 128);
      PROF_MARK(2);
      if (th < 72) {
        const int j = th >> 3, i = (th & 7) * 2;
        int src;
        if (j < CS_PW1) src = 320 + 64 * r + 16 * j;
        else if (j < CS_QKV) src = 192 + (j - CS_PW1) * 64 + 16 * r;
        else src = ((j - CS_QKV + 1) % 3) * 64 + 16 * r;
        uint32_t e[8], hi[4], lo[4], spin = 0;
#pragma unroll 1
        do {
          ld_vec(&sc->cs[src + i], e[0], e[1], e[2], e[3]);
          ld_vec(&sc->cs[src + i + 1], e[4], e[5], e[6], e[7]);
        } while ((((e[0] ^ tag) | (e[4] ^ tag)) & 1u) && ++spin < SPIN_LIMIT);
        e[0] &= ~1u; e[4] &= ~1u;
#pragma unroll
        for (int k = 0; k < 4; k++) {
          const float c0 = __uint_as_float(e[2 * k]), c1 = __uint_as_float(e[2 * k + 1]);
          hi[k] = pack2(c0, c1);
          lo[k] = pack2(c0 - bf_lo(hi[k]), c1 - bf_hi(hi[k]));
        }
        const uint32_t a = SM_BASE + SM_CS + j * 256 + i * 8;
        sts128(a ^ ((a >> 3) & 0x70), hi[0], hi[1], hi[2], hi[3]);
        sts128((a + 128) ^ (((a + 128) >> 3) & 0x70), lo[0], lo[1], lo[2], lo[3]);
      }
      fence_async_smem();
      PROF_MARK(4);
      bar_arrive(BAR_CS, 256);
    }

#pragma unroll 1
    for (uint32_t pass = 0; pass < 2; pass++) {
      uint32_t Q[16];
      if (wg == 0) {
        float acc[4][32];
        uint32_t H[4][16];
        if (!pass) { PROF_MARK(47); ACQUIRE(0); }
        mma_tile<true>(acc[0], A[0], LO(0)); mma_tile<true>(acc[1], A[0], HI(0));
        if (!pass) ACQUIRE(1);
        mma_tile<true>(acc[2], A[0], LO(1)); mma_tile<true>(acc[3], A[0], HI(1));
        if (pass) {
          gather_first<1, X_AG0>(A, st, sc, xp, 1, sent);
        } else {
          centre(A[1], st[0], st[1]);
          acquire_n<2, 3>();
        }
        mma_tile<false>(acc[0], A[1], LO(2)); mma_tile<false>(acc[1], A[1], HI(2));
        if (pass) {
          gather_rest<1, X_AG0>(A, xp, 1);
          RELEASE(F_PW2, F_PW2 + 1);
        } else {
          centre(A[2], st[0], st[1]); centre(A[3], st[0], st[1]);
        }
        PROF_MARK2(2, 18);
        mma_tile<false>(acc[0], A[2], LO(3)); mma_tile<false>(acc[0], A[3], LO(4));
        WG_WAIT(4);
        RELEASE(0, 1);
        uint32_t mu[4] = {0u, 0u, 0u, 0u};
        float rs0, rs1, tn[2][4];
        if (pass) {
          const RowNorm n = stat_finish(sc, st, 1, 0.5f);
          rs0 = n.rs0; rs1 = n.rs1;
          mean_frag(mu, n, q == 0);
        } else {
          const int src = (lane & 28) | (lane >> 3);
          rs0 = 0.5f * rsqrt_hw(fmaxf(__uint_as_float(__shfl_sync(0xffffffffu, st[2], src)), 0.f) + LN_EPS);
          rs1 = 0.5f * rsqrt_hw(fmaxf(__uint_as_float(__shfl_sync(0xffffffffu, st[3], src)), 0.f) + LN_EPS);
        }
        pin(mu);
        mma_fold<2 * CS_FF2>(acc[0], mu);
        mma_tile<false>(acc[1], A[2], HI(3));
#define SEGS(a, b) silu_segs<a, b>(acc, tn, H, rs0, rs1)
        WG_WAIT(1); pin(acc[0]);
        SEGS(0, 1);
        mma_tile_fold<2 * CS_FF2 + 2>(acc[1], A[3], HI(4), mu);
        SEGS(1, 3);
        uint32_t ok = probe_n<5, 3>();
        SEGS(3, 4);
        settle_n<5, 3>(ok);
        mma_tile<false>(acc[2], A[1], LO(5));
        SEGS(4, 6);
        mma_tile<false>(acc[2], A[2], LO(6));
        SEGS(6, 8);
        WG_WAIT(2); pin(acc[1]);
        RELEASE(2, 4);
        SEGS(8, 9);
        mma_tile_fold<2 * CS_FF2 + 4>(acc[2], A[3], LO(7), mu);
        SEGS(9, 12);
        mma_tile<false>(acc[3], A[1], HI(5));
        SEGS(12, 14);
        mma_tile<false>(acc[3], A[2], HI(6));
        SEGS(14, 16);
        WG_WAIT(2); pin(acc[2]);
        SEGS(16, 17);
        mma_tile_fold<2 * CS_FF2 + 6>(acc[3], A[3], HI(7), mu);
        SEGS(17, 19);
        ok = probe_n<8, 2>();
        SEGS(19, 20);
        settle_n<8, 2>(ok);
        mma_tile_reuse(acc[1], H[0], LO(8));
        SEGS(20, 22);
        mma_tile<false>(acc[1], H[1], HI(8));
        SEGS(22, 24);
        WG_WAIT(2); pin(acc[3]);
        RELEASE(5, 7);
        SEGS(24, 26);
        mma_tile<false>(acc[1], H[2], LO(9));
        SEGS(26, 27);
        ok = probe_n<10, 2>();
        SEGS(27, 28);
        settle_n<10, 2>(ok);
        mma_tile_reuse(acc[2], H[0], LO(10));
        SEGS(28, 31);
        mma_tile<false>(acc[2], H[1], HI(10));
        SEGS(31, 34);
#undef SEGS
        PROF_MARK2(3, 19);
        const uint32_t rtag = here(pass ^ 1);
        const uint4* rs_in = xp + X_RS;
        mma_tile<false>(acc[1], H[3], HI(9));
        mma_tile<false>(acc[2], H[2], LO(11));
        ok = probe_n<12, 2>();
        uint4* rs_out = peer<1>(xp) + X_RS;
        mma_tile<false>(acc[2], H[3], HI(11));
        settle_n<12, 2>(ok);
        if (!pass) bar_sync(BAR_RDY, 160);
        WG_WAIT(2); pin(acc[1]);
        RELEASE(8, 9);
        send_half<0>(rs_out, acc[1], rtag);
        mma_tile_reuse(acc[3], H[0], LO(12));
        SCHED();
        send_half<1>(rs_out, acc[1], rtag);
        mma_tile<false>(acc[3], H[1], HI(12));
        rs_out = peer<2>(xp) + X_RS + 512;
        WG_WAIT(2); pin(acc[2]);
        send_half<0>(rs_out, acc[2], rtag);
        mma_tile<false>(acc[3], H[2], LO(13));
        SCHED();
        ok = probe_n<14, 2>();
        send_half<1>(rs_out, acc[2], rtag);
        mma_tile<false>(acc[3], H[3], HI(13));
        settle_n<14, 2>(ok);
        mma_tile_reuse(acc[1], H[0], LO(14));
        rs_out = peer<3>(xp) + X_RS + 1024;
        fetch(rs_in, A[1]);
        SCHED();
        mma_tile<false>(acc[1], H[1], HI(14));
        WG_WAIT(2); pin(acc[3]);
        send_half<0>(rs_out, acc[3], rtag);
        send_half<1>(rs_out, acc[3], rtag);
        sent = clock_now();
        mma_tile<false>(acc[1], H[2], LO(15)); mma_tile<false>(acc[1], H[3], HI(15));
        SCHED();
        fetch(rs_in + 512, A[2]);
        SCHED();
        res_load(maddr, acc[2]);
        while (clock_now() - sent < SCATTER_DELAY) {}
        fetch(rs_in + 1024, A[3]);
        if (!pass) acquire_n<F_QKV, 3>();
        {
          uint32_t spin = 0;
          while (__builtin_expect(stale(miss(A[1], rtag) | miss(A[2], rtag) | miss(A[3], rtag)), 0) && ++spin < SPIN_LIMIT) {
            if (stale(miss(A[1], rtag) | miss(A[2], rtag))) { fetch(rs_in, A[1]); fetch(rs_in + 512, A[2]); }
            fetch(rs_in + 1024, A[3]);
          }
        }
        mma_add_half(acc[2], A[1]);
        mma_add_half(acc[2], A[2]);
        mma_add_half(acc[2], A[3]);
        PROF_MARK2(4, 20);
        WG_WAIT(0); pin(acc[2]); pin(acc[1]);
#pragma unroll
        for (int i = 0; i < 16; i++) A[0][i] = pack2(fmaf(acc[1][2 * i], 0.5f, acc[2][2 * i]), fmaf(acc[1][2 * i + 1], 0.5f, acc[2][2 * i + 1]));
        if (pass) {
          PROF_MARK(21);
          stat_publish(A[0], sc, here(th), 0);
          stat_fetch(sc, st);
          const RowNorm fn = stat_finish(sc, st, 0, 1.f);
          const float nm0 = -fn.m0 * fn.rs0, nm1 = -fn.m1 * fn.rs1;
#pragma unroll
          for (int i = 0; i < 16; i++) {
            const float rs = (i & 1) ? fn.rs1 : fn.rs0, nm = (i & 1) ? nm1 : nm0;
            A[0][i] = pack2(fmaf(bf_lo(A[0][i]), rs, nm), fmaf(bf_hi(A[0][i]), rs, nm));
          }
          tile_store(here(maddr), A[0]);
          __syncwarp();
          const int row = 16 * w + (lane >> 3);
          uint4* dst = (uint4*)(out + ((size_t)batch * T_SEQ + t * 64 + row) * DM + 64 * r) + (lane & 7);
          const uint32_t src = stg + row * 128 + (((lane & 7) ^ (lane >> 3)) << 4);
#pragma unroll
          for (int i = 0; i < 4; i++) {
            uint4 v;
            lds128((src ^ ((i & 1) << 6)) + i * 512, v.x, v.y, v.z, v.w);
            if (row + 4 * i < nvalid) dst[i * 4 * (DM / 8)] = v;
          }
          PROF_MARK(22);
          PROF_TIME(31);
          break;
        }
        sent = send_residual(A[0], sc, xp, maddr, 1);
        PROF_MARK(5);
        mma_tile<true>(acc[0], A[0], LO(F_QKV)); mma_tile<true>(acc[1], A[0], HI(F_QKV));
        mma_tile<true>(acc[2], A[0], LO(F_QKV + 1));
        gather_first<1, X_AG0>(A, st, sc, xp, 1, sent);
        mma_tile<false>(acc[0], A[1], LO(F_QKV + 2)); mma_tile<false>(acc[1], A[1], HI(F_QKV + 2));
        acquire_n<F_QKV + 3, 3>();
        bar_sync(BAR_CS, 256);
        gather_rest<1, X_AG0>(A, xp, 1);
        PROF_MARK(6);
        mma_tile<false>(acc[0], A[2], LO(F_QKV + 3)); mma_tile<false>(acc[0], A[3], LO(F_QKV + 4));
        SCHED();
        {
          const RowNorm n = stat_finish(sc, st, 1, 1.f);
          rs0 = row0 < nvalid ? n.rs0 : 0.f; rs1 = row0 + 8 < nvalid ? n.rs1 : 0.f;
          mean_frag(mu, n, q == 3);
        }
        mma_fold<2 * CS_QKV - 6>(acc[0], mu);
        RELEASE(10, 15);
        WG_WAIT(0); pin(acc[0]);
        scale_pack(acc[0], Q, rs0, rs1);
        tile_store(here(maddr), Q);
        SCHED();
        mma_tile<false>(acc[1], A[2], HI(F_QKV + 3));
        fence_async_smem();
        bar_arrive(BAR_K, 160);
        mma_tile_fold<2 * CS_QKV - 4>(acc[1], A[3], HI(F_QKV + 4), mu);
        mma_tile<false>(acc[2], A[1], HI(F_QKV + 1)); mma_tile<false>(acc[2], A[2], LO(F_QKV + 5));
        WG_WAIT(2); pin(acc[1]);
        scale_pack(acc[1], Q, rs0, rs1);
        tile_store(here(maddr) + TILE_BYTES, Q);
        fence_async_smem();
        bar_arrive(BAR_V, 160);
        mma_tile_fold<2 * CS_QKV - 2>(acc[2], A[3], HI(F_QKV + 5), mu);
        WG_WAIT(0); pin(acc[2]);
        scale_pack(acc[2], Q, rs0 * SM_SCALE_LOG2, rs1 * SM_SCALE_LOG2);
        frag_store(here(qslot), Q);
        bar_arrive(BAR_Q, 256);
        RELEASE(F_QKV, F_QKV + 5);
      } else {
        bar_sync(BAR_Q, 256);
#pragma unroll
        for (int s = 0; s < 4; s++) lds128(qslot + s * 512, Q[4 * s], Q[4 * s + 1], Q[4 * s + 2], Q[4 * s + 3]);
        if (w < 2) {
          const uint32_t v = w ? 0u : 0x3F803F80u;
#pragma unroll
          for (int s = 0; s < 4; s++) sts128(qslot + s * 512, v, v, v, v);
          fence_async_smem();
        }
      }
      bar_sync(BAR_ATT, 256);
      PROF_MARK(7);

      const int dir = cw == 0 ? -1 : 1;
      uint32_t tap[15];
      {
        const uint32_t* dwp = (const uint32_t*)(dw + 64 * r) + lane + 7 * (DM / 2);
#pragma unroll
        for (int k = 0; k < 15; k++) tap[k] = __ldg(dwp + dir * (k - 7) * (DM / 2));
      }

      float O[36];
      {
        float S[2][32];
        uint32_t P[2][16], nm[4];
#pragma unroll
        for (int i = 0; i < 32; i++) { S[0][i] = 0.f; S[1][i] = 0.f; }
        pin(Q); pin(S[0]);
        WG_FENCE();
        qk_tile(S[0], Q, RING_K + (SM_STG >> 4));
        WG_COMMIT();
#pragma unroll
        for (int i = 0; i < 36; i++) O[i] = 0.f;
#pragma unroll
        for (int i = 0; i < 16; i++) P[1][i] = 0u;
        WG_WAIT(0); pin(S[0]);
        const float m0 = tile_max<0>(S[0]), m1 = tile_max<2>(S[0]);
        nm[0] = pack2(q ? 0.f : -m0, 0.f); nm[1] = pack2(q ? 0.f : -m1, 0.f); nm[2] = 0u; nm[3] = 0u;
#pragma unroll
        for (int k = 0; k < 15; k++) asm("mul.rn.bf16x2 %0, %0, %1;" : "+r"(tap[k]) : "r"(0x3F003F00u));
        pin(nm); pin(O); pin(P[1]); pin(tap);
        uint32_t sk = wg, sv = F_SPARE % NSTAGE + wg;
        mbar_wait(SM_BASE + SM_FULL + sv * 8, 1);
        mbar_wait(SM_BASE + SM_FULL + sk * 8, 0);
        PROF_MARK(8);
        WG_FENCE();
        qk_tile(S[0], Q, RING_K + sk * 1024);
        qk_shift(S[0], nm);
        WG_COMMIT();
        WG_WAIT(0); pin(S[0]); pin(S[1]);
#pragma unroll 1
        for (int it = 0; it < 4; it++) {
          const uint32_t sn = it >= 2 ? wg : sk + 4;
          uint32_t ok = 1;
          mbar_probe(ok, SM_BASE + SM_FULL + sn * 8, it >= 2);
          mbar_probe(ok, SM_BASE + SM_FULL + (sk + 2) * 8, it == 3);
          attn_step(S[0], S[1], P[0], P[1], O, Q, nm, RING_K + sk * 1024 + 512, RING_V + (sv * 1024 + 512) * V_STEP, true, it > 0);
          PROF_MARK(24 + it * 3);
          if (__builtin_expect(!ok, 0)) {
            mbar_wait(SM_BASE + SM_FULL + sn * 8, it >= 2);
            mbar_wait(SM_BASE + SM_FULL + (sk + 2) * 8, it == 3);
          }
          WG_WAIT(0); pin(O); pin(S[1]); pin(P[1]);
          asm volatile("{\n.reg .pred p;\nsetp.eq.u32 p, %2, 0;\n@p mbarrier.arrive.shared::cta.b64 _, [%0];\n@p mbarrier.arrive.shared::cta.b64 _, [%1];\n}"
                       :: "r"(SM_BASE + SM_EMPTY + sk * 8), "r"(SM_BASE + SM_EMPTY + sv * 8), "r"(lane) : "memory");
          PROF_MARK(25 + it * 3);
          sv = sk + 2; sk = sn;
          attn_step(S[1], S[0], P[1], P[0], O, Q, nm, RING_K + sk * 1024, RING_V + (sv * 1024) * V_STEP, it < 3, true);
          WG_WAIT(0); pin(O); pin(S[0]); pin(P[0]);
          PROF_MARK(26 + it * 3);
        }
        WG_FENCE();
        pv_tile(O, P[1], RING_V + (sv * 1024 + 512) * V_STEP, wg << 22);
        WG_COMMIT();
        WG_WAIT(0); pin(O);
      }
      PROF_MARK(9);

      {
        const uint32_t mo = stg + here(th) * 16;
        sts64(mo + 5 * 4096 + wg * 8, __float_as_uint(O[32]), __float_as_uint(O[34]));
        if (wg == 0) {
#pragma unroll
          for (int i = 4; i < 8; i++)
            sts128(mo + i * 2048, __float_as_uint(O[4 * i]), __float_as_uint(O[4 * i + 1]), __float_as_uint(O[4 * i + 2]), __float_as_uint(O[4 * i + 3]));
        } else {
#pragma unroll
          for (int i = 0; i < 4; i++)
            sts128(mo + i * 2048, __float_as_uint(O[4 * i]), __float_as_uint(O[4 * i + 1]), __float_as_uint(O[4 * i + 2]), __float_as_uint(O[4 * i + 3]));
#pragma unroll
          for (int i = 0; i < 16; i++) O[i] = O[16 + i];
        }
        bar_sync(BAR_MERGE, 256);
        uint32_t e[4];
        lds128(mo + 5 * 4096, e[0], e[1], e[2], e[3]);
        O[32] = __uint_as_float(e[0]) + __uint_as_float(e[2]); O[34] = __uint_as_float(e[1]) + __uint_as_float(e[3]);
#pragma unroll
        for (int i = 0; i < 4; i++) {
          lds128(mo + wg * TILE_BYTES + i * 2048, e[0], e[1], e[2], e[3]);
#pragma unroll
          for (int k = 0; k < 4; k++) O[4 * i + k] += __uint_as_float(e[k]);
        }
        const bool safe = O[32] > 0x1p-60f && O[32] < 0x1p60f && O[34] > 0x1p-60f && O[34] < 0x1p60f;
        if (__builtin_expect(__any_sync(0xffffffffu, !safe), 0)) attention_exact(O, Q, sc, batch * 4 + r, lane, wg);
        const float i0 = rcp_hw(O[32]), i1 = rcp_hw(O[34]);
#pragma unroll
        for (int i = 0; i < 8; i++) { const float v = (i & 1) ? i1 : i0; A[0][i] = pack2(O[2 * i] * v, O[2 * i + 1] * v); }
        A[0][0] &= ~1u; A[0][4] &= ~1u;
        uint4* dst = xp + X_AG1 + wg * 256;
        SCHED();
        st_vec(dst, A[0][0], A[0][1], A[0][2], A[0][3]);
        st_vec(dst + 128, A[0][4], A[0][5], A[0][6], A[0][7]);
        SCHED();
        sent = clock_now();
      }
      if (wg == 1) {
        const uint32_t mo = stg + TILE_BYTES + here(th) * 16;
        sts128(mo, A[0][0], A[0][1], A[0][2], A[0][3]);
        sts128(mo + 2048, A[0][4], A[0][5], A[0][6], A[0][7]);
        bar_arrive(BAR_HALF, 256);
      } else {
        PROF_MARK(10);
        const uint32_t mo = stg + TILE_BYTES + here(th) * 16;
        bar_sync(BAR_HALF, 256);
        lds128(mo, A[0][8], A[0][9], A[0][10], A[0][11]);
        lds128(mo + 2048, A[0][12], A[0][13], A[0][14], A[0][15]);
        sent = proj_residual<F_WO, 6>(A, sc, xp, maddr, 0, sent, lane);
        PROF_MARK(12);
        float acc[2][32];
        mma_tile<true>(acc[0], A[0], LO(F_PW1)); mma_tile<true>(acc[1], A[0], HI(F_PW1));
        gather_first<1, X_AG0>(A, st, sc, xp, 0, sent);
        mma_tile<false>(acc[1], A[1], HI(F_PW1 + 1)); mma_tile<false>(acc[0], A[1], LO(F_PW1 + 1));
        gather_rest<1, X_AG0>(A, xp, 0);
        PROF_MARK(13);
        mma_tile<false>(acc[1], A[2], HI(F_PW1 + 2)); mma_tile<false>(acc[1], A[3], HI(F_PW1 + 3));
        WG_WAIT(2);
        RELEASE(F_WO, F_PW1 + 1);
        SCHED();
        uint32_t mu[4];
        const RowNorm n = stat_finish(sc, st, 0, 0.5f);
        const float rs0 = row0 < nvalid ? n.rs0 : 0.f, rs1 = row0 + 8 < nvalid ? n.rs1 : 0.f;
        mean_frag(mu, n, q == 0);
        mma_fold<2 * CS_PW1 + 2>(acc[1], mu);
        mma_tile<false>(acc[0], A[2], LO(F_PW1 + 2));
        mma_tile_fold<2 * CS_PW1>(acc[0], A[3], LO(F_PW1 + 3), mu);
        WG_WAIT(2); pin(acc[1]);
#pragma unroll
        for (int i = 0; i < 32; i++) acc[1][i] = tanh_hw(acc[1][i] * ((i & 2) ? rs1 : rs0));
#pragma unroll
        for (int i = 0; i < 32; i++) { const float rs = (i & 2) ? rs1 : rs0; acc[1][i] = fmaf(acc[1][i], rs, rs); }
        pin(acc[1]);
        SCHED();
        WG_WAIT(0); pin(acc[0]);
#pragma unroll
        for (int i = 0; i < 16; i++) A[0][i] = pack2(acc[0][2 * i] * acc[1][2 * i], acc[0][2 * i + 1] * acc[1][2 * i + 1]);
        const uint32_t ga = stg + TILE_BYTES + here(mrow) * G_PITCH + (lane >> 4) * 16;
#pragma unroll
        for (int s = 0; s < 4; s++) stsm4(ga + s * 32, &A[0][4 * s]);
      }
      {
        const uint32_t gsrc = stg + TILE_BYTES + (8 * cw - 7) * G_PITCH + lane * 4;
        const bool edge = cw == 0 || cw == 7;
        const bool nbr = cw == 0 ? t > 0 : t < 15;
        uint4* const hdst = &sc->x[b + 4 * dir][X_HALO + (cw == 0 ? 96 : 0) + lane];
        uint32_t in[22];
        bar_sync(BAR_G, 256);
        PROF_MARK(14);
        if (cw == 0) {
#pragma unroll
          for (int i = 14; i >= 0; i--) in[i] = lds32(gsrc + (21 - i) * G_PITCH);
        } else {
#pragma unroll
          for (int i = 14; i >= 0; i--) in[i] = lds32(gsrc + i * G_PITCH);
        }
        if (edge) {
          if (nbr) {
            st_vec(hdst, HALO_TAG, in[14], in[13], in[12]);
            st_vec(hdst + 32, HALO_TAG, in[11], in[10], in[9]);
            st_vec(hdst + 64, HALO_TAG, in[8], 0u, 0u);
          }
        } else {
#pragma unroll
          for (int i = 15; i < 22; i++) in[i] = lds32(gsrc + i * G_PITCH);
        }
        if (cw == 0) PROF_MARK0(40);
        uint32_t cv[8];
#pragma unroll
        for (int i = 0; i < 15; i++)
#pragma unroll
          for (int o = 0; o < 8; o++) {
            if (i == o) asm("mul.rn.bf16x2 %0, %1, %2;" : "=r"(cv[o]) : "r"(in[i]), "r"(tap[0]));
            if (i > o) asm("fma.rn.bf16x2 %0, %1, %2, %0;" : "+r"(cv[o]) : "r"(in[i]), "r"(tap[i - o]));
          }
        pin(cv);
        if (cw == 0) PROF_MARK0(41);
        if (edge) {
#pragma unroll
          for (int i = 15; i < 22; i++) in[i] = 0u;
          if (nbr) {
            const uint4* src = &sc->x[b][X_HALO + (cw == 0 ? 0 : 96) + lane];
            uint32_t e0, e1, e2, u0, u1, spin = 0;
#pragma unroll 1
            do {
              ld_vec(src, e0, in[15], in[16], in[17]);
              ld_vec(src + 32, e1, in[18], in[19], in[20]);
              ld_vec(src + 64, e2, in[21], u0, u1);
            } while (__any_sync(0xffffffffu, ((e0 ^ HALO_TAG) | (e1 ^ HALO_TAG) | (e2 ^ HALO_TAG)) != 0) && ++spin < SPIN_LIMIT);
          }
        }
#pragma unroll
        for (int i = 15; i < 22; i++)
#pragma unroll
          for (int o = 0; o < 8; o++)
            if (i - o <= 14) asm("fma.rn.bf16x2 %0, %1, %2, %0;" : "+r"(cv[o]) : "r"(in[i]), "r"(tap[i - o]));
        if (cw == 0) PROF_MARK0(42);
        if (cw == 7) PROF_MARK0(43);
        const uint32_t fl = cw == 0 ? 7 : 0;
        const uint32_t cdst = (stg + cw * 1024 + lane * 4) ^ (fl * 144);
#pragma unroll
        for (int o = 0; o < 8; o++) {
          const float a = bf_lo(cv[o]), c = bf_hi(cv[o]);
          sts32(cdst ^ (o * 144), pack2(fmaf(a, tanh_hw(a), a), fmaf(c, tanh_hw(c), c)));
        }
      }
      if (wg == 1) {
        bar_arrive(BAR_C, 256);
        if (th == 0) ((volatile uint32_t*)sc->epoch)[b] += 1;
        break;
      }
      bar_sync(BAR_C, 256);
      tile_load(here(maddr), A[0]);
      PROF_MARK(15);
      publish(xp + X_AG1, A[0], 1);
      sent = proj_residual<F_PW2, 2>(A, sc, xp, maddr, 1, clock_now(), lane);
      PROF_MARK(17);
    }
  }
}

typedef CUresult (*EncodeFn)(CUtensorMap*, CUtensorMapDataType, cuuint32_t, void*, const cuuint64_t*, const cuuint64_t*,
                             const cuuint32_t*, const cuuint32_t*, CUtensorMapInterleave, CUtensorMapSwizzle,
                             CUtensorMapL2promotion, CUtensorMapFloatOOBfill);

void make_map(EncodeFn fn, CUtensorMap* m, const void* w, int rows, int cols, CUtensorMapSwizzle swz) {
  const cuuint64_t dims[2] = {(cuuint64_t)cols, (cuuint64_t)rows}, strides[1] = {(cuuint64_t)cols * 2};
  const cuuint32_t box[2] = {64, 64}, es[2] = {1, 1};
  fn(m, CU_TENSOR_MAP_DATA_TYPE_BFLOAT16, 2, const_cast<void*>(w), dims, strides, box, es, CU_TENSOR_MAP_INTERLEAVE_NONE,
     swz, CU_TENSOR_MAP_L2_PROMOTION_L2_128B, CU_TENSOR_MAP_FLOAT_OOB_FILL_NONE);
}

}

extern "C" void kernel_launch(void* const* d_in, const int* in_sizes, int n_in, void* d_out, int out_size) {
  static EncodeFn fn = nullptr;
  static Scratch* sc = nullptr;
  if (!fn) {
    void* f = nullptr;
    cudaDriverEntryPointQueryResult st;
    cudaGetDriverEntryPoint("cuTensorMapEncodeTiled", &f, cudaEnableDefault, &st);
    fn = (EncodeFn)f;
    void* raw = nullptr;
    cudaGetSymbolAddress(&raw, g_scratch);
    sc = (Scratch*)(((uintptr_t)raw + X_ALIGN - 1) & ~(uintptr_t)(X_ALIGN - 1));
    cudaFuncSetAttribute(conformer_kernel, cudaFuncAttributeMaxDynamicSharedMemorySize, SM_TOTAL);
  }
  typedef const __nv_bfloat16* W;
  const CUtensorMapSwizzle S = CU_TENSOR_MAP_SWIZZLE_128B;
  Params p;
  {
    const cuuint64_t dims[3] = {DM, T_SEQ, 2}, strides[2] = {DM * 2, T_SEQ * DM * 2};
    const cuuint32_t box[3] = {64, 64, 1}, es[3] = {1, 1, 1};
    fn(&p.map[M_X], CU_TENSOR_MAP_DATA_TYPE_BFLOAT16, 3, d_in[0], dims, strides, box, es, CU_TENSOR_MAP_INTERLEAVE_NONE, S,
       CU_TENSOR_MAP_L2_PROMOTION_L2_128B, CU_TENSOR_MAP_FLOAT_OOB_FILL_NONE);
  }
  make_map(fn, &p.map[M_FF1A], d_in[1], 256, 1024, S);
  make_map(fn, &p.map[M_FF1B], d_in[2], 1024, 256, S);
  make_map(fn, &p.map[M_QKV], d_in[3], 256, 768, S);
  make_map(fn, &p.map[M_WO], d_in[4], 256, 256, S);
  make_map(fn, &p.map[M_PW1], d_in[5], 256, 512, S);
  make_map(fn, &p.map[M_PW2], d_in[7], 256, 256, S);
  make_map(fn, &p.map[M_FF2A], d_in[8], 256, 1024, S);
  make_map(fn, &p.map[M_FF2B], d_in[9], 1024, 256, S);
  p.w_ff1b = (W)d_in[2]; p.w_qkv = (W)d_in[3]; p.w_o = (W)d_in[4]; p.w_pw1 = (W)d_in[5];
  p.w_pw2 = (W)d_in[7]; p.w_ff2a = (W)d_in[8]; p.w_ff2b = (W)d_in[9];

  cudaLaunchConfig_t cfg = {};
  cfg.gridDim = dim3(NCTA);
  cfg.blockDim = dim3(384);
  cfg.dynamicSmemBytes = SM_TOTAL;
  cfg.stream = cudaStreamPerThread;
  cudaLaunchAttribute at[1];
  at[0].id = cudaLaunchAttributeCooperative;
  at[0].val.cooperative = 1;
  cfg.attrs = at;
  cfg.numAttrs = 1;
  cudaLaunchKernelEx(&cfg, conformer_kernel, sc, (__nv_bfloat16*)d_out, (W)d_in[6], (W)d_in[0], (W)d_in[1], p);
}
```

```cpp
#include <cuda_runtime.h>
#include <cuda_bf16.h>
#include <cuda.h>
#include <stdint.h>

namespace {

constexpr int T_SEQ = 1000;
constexpr int DM = 256;
constexpr int NCTA = 128;
constexpr int NSTAGE = 12;
constexpr uint32_t STAGE_BYTES = 16384;
constexpr uint32_t TILE_BYTES = 8192;
constexpr uint32_t SM_BASE = 1024;
constexpr uint32_t SM_STG = NSTAGE * STAGE_BYTES;
constexpr uint32_t SM_FULL = SM_STG + 32768;
constexpr uint32_t SM_EMPTY = SM_FULL + 96;
constexpr uint32_t SM_XBAR = SM_FULL + 192;
constexpr uint32_t SM_EYE = SM_FULL + 256;
constexpr uint32_t SM_ONE = SM_FULL + 640;
constexpr uint32_t SM_CS = SM_FULL + 768;
constexpr uint32_t SM_TOTAL = SM_FULL + 3072;
constexpr int CS_FF2 = 0, CS_PW1 = 4, CS_QKV = 6;
constexpr uint32_t SPIN_LIMIT = 1u << 16;
constexpr float LN_EPS = 1e-5f;
constexpr float SM_SCALE_LOG2 = 0.125f * 1.4426950408889634f;
constexpr uint32_t G_PITCH = 144;
#define PF_AT 4
#define CLR_PACE 60

constexpr int F_QKV = 16, F_SPARE = 22, F_KV = 24, F_WO = 40, F_PW1 = 42, F_PW2 = 46, F_TOTAL = 64;
enum { M_FF1A, M_FF1B, M_QKV, M_WO, M_PW1, M_PW2, M_FF2A, M_FF2B, M_X, M_COUNT };
enum { BAR_K = 1, BAR_V, BAR_Q, BAR_MERGE, BAR_G, BAR_C, BAR_WG1, BAR_GO, BAR_CS, BAR_ATT, BAR_INIT, BAR_HALF };

struct Params {
  CUtensorMap map[M_COUNT];
  const __nv_bfloat16 *w_ff1b, *w_qkv, *w_o, *w_pw1, *w_pw2, *w_ff2a, *w_ff2b;
};

constexpr int X_RS = 0, X_AG1 = X_RS, X_HALO = X_RS + 512, X_AG0 = 1536, X_ST = 2048, X_SIZE = 4096;
constexpr uint32_t HALO_TAG = 0xFFFF0001u;
struct Scratch {
  uint4 x[NCTA][X_SIZE];
  uint4 kv[8][2][16][512];
  uint4 cs[576];
  uint32_t flag[8][32][32];
  uint32_t step[NCTA][32];
};
constexpr size_t X_ALIGN = 4 * X_SIZE * sizeof(uint4);
__device__ uint8_t g_scratch[sizeof(Scratch) + X_ALIGN];
#define PROF_TIME(i)
#define PROF_MARK(i)
#define PROF_MARK2(i, j)
#define PROF_MARK0(i)
#define PROF_AT(a)

__device__ __forceinline__ void mbar_init(uint32_t bar, uint32_t cnt) {
  asm volatile("mbarrier.init.shared::cta.b64 [%0], %1;" :: "r"(bar), "r"(cnt) : "memory");
}
__device__ __forceinline__ void mbar_wait(uint32_t bar, uint32_t parity) {
  asm volatile("{\n.reg .pred p;\n.reg .u32 c;\nmov.u32 c, 0;\n"
               "WAIT_LOOP:\nmbarrier.try_wait.parity.shared::cta.b64 p, [%0], %1;\n@p bra WAIT_DONE;\n"
               "add.u32 c, c, 1;\nsetp.lt.u32 p, c, %2;\n@p bra WAIT_LOOP;\nWAIT_DONE:\n}"
               :: "r"(bar), "r"(parity), "n"(SPIN_LIMIT) : "memory");
}
__device__ __forceinline__ void mbar_arrive(uint32_t bar) {
  asm volatile("mbarrier.arrive.shared::cta.b64 _, [%0];" :: "r"(bar) : "memory");
}
#define bar_sync(id, n) asm volatile("bar.sync %0, %1;" :: "n"((int)(id)), "n"(n) : "memory")
#define bar_arrive(id, n) asm volatile("bar.arrive %0, %1;" :: "n"((int)(id)), "n"(n) : "memory")
__device__ __forceinline__ void fence_async_smem() { asm volatile("fence.proxy.async.shared::cta;" ::: "memory"); }

__device__ __forceinline__ void st_vec(uint4* p, uint32_t a, uint32_t b, uint32_t c, uint32_t d) {
  asm volatile("{\n.reg .b128 v;\n.reg .b64 lo, hi;\nmov.b64 lo, {%1, %2};\nmov.b64 hi, {%3, %4};\nmov.b128 v, {lo, hi};\n"
               "st.relaxed.gpu.global.b128 [%0], v;\n}" :: "l"(p), "r"(a), "r"(b), "r"(c), "r"(d) : "memory");
}
__device__ __forceinline__ void ld_vec(const uint4* p, uint32_t& a, uint32_t& b, uint32_t& c, uint32_t& d) {
  asm volatile("{\n.reg .b128 v;\n.reg .b64 lo, hi;\nld.relaxed.gpu.global.b128 v, [%4];\nmov.b128 {lo, hi}, v;\n"
               "mov.b64 {%0, %1}, lo;\nmov.b64 {%2, %3}, hi;\n}" : "=r"(a), "=r"(b), "=r"(c), "=r"(d) : "l"(p) : "memory");
}
__device__ __forceinline__ void sts128(uint32_t a, uint32_t x, uint32_t y, uint32_t z, uint32_t w) {
  asm volatile("st.shared.v4.u32 [%0], {%1, %2, %3, %4};" :: "r"(a), "r"(x), "r"(y), "r"(z), "r"(w) : "memory");
}
__device__ __forceinline__ void lds128(uint32_t a, uint32_t& x, uint32_t& y, uint32_t& z, uint32_t& w) {
  asm volatile("ld.shared.v4.u32 {%0, %1, %2, %3}, [%4];" : "=r"(x), "=r"(y), "=r"(z), "=r"(w) : "r"(a) : "memory");
}
__device__ __forceinline__ uint32_t lds32(uint32_t a) {
  uint32_t x; asm volatile("ld.shared.u32 %0, [%1];" : "=r"(x) : "r"(a) : "memory"); return x;
}
__device__ __forceinline__ void sts32(uint32_t a, uint32_t x) { asm volatile("st.shared.u32 [%0], %1;" :: "r"(a), "r"(x) : "memory"); }
__device__ __forceinline__ void sts64(uint32_t a, uint32_t x, uint32_t y) {
  asm volatile("st.shared.v2.u32 [%0], {%1, %2};" :: "r"(a), "r"(x), "r"(y) : "memory");
}
__device__ __forceinline__ void stsm4(uint32_t a, const uint32_t* r) {
  asm volatile("stmatrix.sync.aligned.m8n8.x4.shared.b16 [%0], {%1, %2, %3, %4};" :: "r"(a), "r"(r[0]), "r"(r[1]), "r"(r[2]), "r"(r[3]) : "memory");
}
__device__ __forceinline__ void ldsm4(uint32_t a, uint32_t* r) {
  asm volatile("ldmatrix.sync.aligned.m8n8.x4.shared.b16 {%0, %1, %2, %3}, [%4];" : "=r"(r[0]), "=r"(r[1]), "=r"(r[2]), "=r"(r[3]) : "r"(a) : "memory");
}
__device__ __forceinline__ uint32_t pack2(float lo, float hi) {
  uint32_t r; asm("cvt.rn.bf16x2.f32 %0, %1, %2;" : "=r"(r) : "f"(hi), "f"(lo)); return r;
}
__device__ __forceinline__ float bf_lo(uint32_t w) { return __uint_as_float(w << 16); }
__device__ __forceinline__ float bf_hi(uint32_t w) { return __uint_as_float(w & 0xffff0000u); }
__device__ __forceinline__ float tanh_hw(float x) { float y; asm volatile("tanh.approx.f32 %0, %1;" : "=f"(y) : "f"(x)); return y; }
__device__ __forceinline__ float rcp_hw(float x) { float y; asm("rcp.approx.ftz.f32 %0, %1;" : "=f"(y) : "f"(x)); return y; }
__device__ __forceinline__ float rsqrt_hw(float x) { float y; asm("rsqrt.approx.ftz.f32 %0, %1;" : "=f"(y) : "f"(x)); return y; }
__device__ __forceinline__ float ex2_hw(float x) { float y; asm("ex2.approx.ftz.f32 %0, %1;" : "=f"(y) : "f"(x)); return y; }

__device__ __forceinline__ uint32_t here(uint32_t v) { asm volatile("" : "+r"(v)); return v; }

#define SCHED() asm volatile("pmevent 1;" ::: "memory")
#define WG_FENCE() asm volatile("wgmma.fence.sync.aligned;" ::: "memory")
#define WG_COMMIT() asm volatile("wgmma.commit_group.sync.aligned;" ::: "memory")
#define WG_WAIT(n) asm volatile("wgmma.wait_group.sync.aligned %0;" :: "n"(n) : "memory")

template <int N> __device__ __forceinline__ void pin(float (&d)[N]) {
#pragma unroll
  for (int i = 0; i < N; i++) asm volatile("" : "+f"(d[i]) :: "memory");
}
template <int N> __device__ __forceinline__ void pin(uint32_t (&d)[N]) {
#pragma unroll
  for (int i = 0; i < N; i++) asm volatile("" : "+r"(d[i]) :: "memory");
}

#define WG_D32 "{%0, %1, %2, %3, %4, %5, %6, %7, %8, %9, %10, %11, %12, %13, %14, %15, %16, %17, %18, %19, %20, %21, %22, %23, %24, %25, %26, %27, %28, %29, %30, %31}"
template <int TB> __device__ __forceinline__ void wgmma64_acc(float (&d)[32], const uint32_t* a, uint64_t db) {
  asm volatile("wgmma.mma_async.sync.aligned.m64n64k16.f32.bf16.bf16 " WG_D32 ", {%32, %33, %34, %35}, %36, 1, 1, 1, %37;"
    : "+f"(d[0]), "+f"(d[1]), "+f"(d[2]), "+f"(d[3]), "+f"(d[4]), "+f"(d[5]), "+f"(d[6]), "+f"(d[7]),
      "+f"(d[8]), "+f"(d[9]), "+f"(d[10]), "+f"(d[11]), "+f"(d[12]), "+f"(d[13]), "+f"(d[14]), "+f"(d[15]),
      "+f"(d[16]), "+f"(d[17]), "+f"(d[18]), "+f"(d[19]), "+f"(d[20]), "+f"(d[21]), "+f"(d[22]), "+f"(d[23]),
      "+f"(d[24]), "+f"(d[25]), "+f"(d[26]), "+f"(d[27]), "+f"(d[28]), "+f"(d[29]), "+f"(d[30]), "+f"(d[31])
    : "r"(a[0]), "r"(a[1]), "r"(a[2]), "r"(a[3]), "l"(db), "n"(TB));
}
template <int TB> __device__ __forceinline__ void wgmma64_reuse(float (&d)[32], const uint32_t* a, uint64_t db, uint32_t zero) {
  asm volatile("{\n.reg .pred p;\nsetp.ne.u32 p, %37, 0;\nwgmma.mma_async.sync.aligned.m64n64k16.f32.bf16.bf16 " WG_D32 ", {%32, %33, %34, %35}, %36, p, 1, 1, %38;\n}"
    : "+f"(d[0]), "+f"(d[1]), "+f"(d[2]), "+f"(d[3]), "+f"(d[4]), "+f"(d[5]), "+f"(d[6]), "+f"(d[7]),
      "+f"(d[8]), "+f"(d[9]), "+f"(d[10]), "+f"(d[11]), "+f"(d[12]), "+f"(d[13]), "+f"(d[14]), "+f"(d[15]),
      "+f"(d[16]), "+f"(d[17]), "+f"(d[18]), "+f"(d[19]), "+f"(d[20]), "+f"(d[21]), "+f"(d[22]), "+f"(d[23]),
      "+f"(d[24]), "+f"(d[25]), "+f"(d[26]), "+f"(d[27]), "+f"(d[28]), "+f"(d[29]), "+f"(d[30]), "+f"(d[31])
    : "r"(a[0]), "r"(a[1]), "r"(a[2]), "r"(a[3]), "l"(db), "r"(zero), "n"(TB));
}
template <int TB> __device__ __forceinline__ void wgmma64_set(float (&d)[32], const uint32_t* a, uint64_t db) {
  asm volatile("wgmma.mma_async.sync.aligned.m64n64k16.f32.bf16.bf16 " WG_D32 ", {%32, %33, %34, %35}, %36, 0, 1, 1, %37;"
    : "=f"(d[0]), "=f"(d[1]), "=f"(d[2]), "=f"(d[3]), "=f"(d[4]), "=f"(d[5]), "=f"(d[6]), "=f"(d[7]),
      "=f"(d[8]), "=f"(d[9]), "=f"(d[10]), "=f"(d[11]), "=f"(d[12]), "=f"(d[13]), "=f"(d[14]), "=f"(d[15]),
      "=f"(d[16]), "=f"(d[17]), "=f"(d[18]), "=f"(d[19]), "=f"(d[20]), "=f"(d[21]), "=f"(d[22]), "=f"(d[23]),
      "=f"(d[24]), "=f"(d[25]), "=f"(d[26]), "=f"(d[27]), "=f"(d[28]), "=f"(d[29]), "=f"(d[30]), "=f"(d[31])
    : "r"(a[0]), "r"(a[1]), "r"(a[2]), "r"(a[3]), "l"(db), "n"(TB));
}

__device__ __forceinline__ void wgmma72_acc(float (&d)[36], const uint32_t* a, uint64_t db) {
  asm volatile("wgmma.mma_async.sync.aligned.m64n72k16.f32.bf16.bf16 {%0, %1, %2, %3, %4, %5, %6, %7, %8, %9, %10, %11, %12, %13, %14, %15, %16, %17, %18, %19, %20, %21, %22, %23, %24, %25, %26, %27, %28, %29, %30, %31, %32, %33, %34, %35}, {%36, %37, %38, %39}, %40, 1, 1, 1, 1;"
    : "+f"(d[0]), "+f"(d[1]), "+f"(d[2]), "+f"(d[3]), "+f"(d[4]), "+f"(d[5]), "+f"(d[6]), "+f"(d[7]), "+f"(d[8]),
      "+f"(d[9]), "+f"(d[10]), "+f"(d[11]), "+f"(d[12]), "+f"(d[13]), "+f"(d[14]), "+f"(d[15]), "+f"(d[16]), "+f"(d[17]),
      "+f"(d[18]), "+f"(d[19]), "+f"(d[20]), "+f"(d[21]), "+f"(d[22]), "+f"(d[23]), "+f"(d[24]), "+f"(d[25]), "+f"(d[26]),
      "+f"(d[27]), "+f"(d[28]), "+f"(d[29]), "+f"(d[30]), "+f"(d[31]), "+f"(d[32]), "+f"(d[33]), "+f"(d[34]), "+f"(d[35])
    : "r"(a[0]), "r"(a[1]), "r"(a[2]), "r"(a[3]), "l"(db));
}
__device__ __forceinline__ void wgmma16_acc(float* d, const uint32_t* a, uint64_t db) {
  asm volatile("wgmma.mma_async.sync.aligned.m64n16k16.f32.bf16.bf16 {%0, %1, %2, %3, %4, %5, %6, %7}, {%8, %9, %10, %11}, %12, 1, 1, 1, 0;"
    : "+f"(d[0]), "+f"(d[1]), "+f"(d[2]), "+f"(d[3]), "+f"(d[4]), "+f"(d[5]), "+f"(d[6]), "+f"(d[7])
    : "r"(a[0]), "r"(a[1]), "r"(a[2]), "r"(a[3]), "l"(db));
}
__device__ __forceinline__ void hmma(float (&d)[4], const uint32_t* a, uint32_t b0, uint32_t b1) {
  asm("mma.sync.aligned.m16n8k16.row.col.f32.bf16.bf16.f32 {%0, %1, %2, %3}, {%4, %5, %6, %7}, {%8, %9}, {%0, %1, %2, %3};"
    : "+f"(d[0]), "+f"(d[1]), "+f"(d[2]), "+f"(d[3]) : "r"(a[0]), "r"(a[1]), "r"(a[2]), "r"(a[3]), "r"(b0), "r"(b1));
}

__device__ __forceinline__ void hmma8(float (&d)[4], const uint32_t* a, uint32_t b0) {
  asm("mma.sync.aligned.m16n8k8.row.col.f32.bf16.bf16.f32 {%0, %1, %2, %3}, {%4, %5}, {%6}, {%0, %1, %2, %3};"
    : "+f"(d[0]), "+f"(d[1]), "+f"(d[2]), "+f"(d[3]) : "r"(a[0]), "r"(a[1]), "r"(b0));
}

template <bool FIRST> __device__ __forceinline__ void mma_tile(float (&d)[32], const uint32_t (&a)[16], uint64_t db) {
  WG_FENCE();
#pragma unroll
  for (int s = 0; s < 4; s++) {
    if (FIRST && s == 0) wgmma64_set<1>(d, &a[0], db); else wgmma64_acc<1>(d, &a[4 * s], db + s * 128);
  }
  WG_COMMIT();
}
__device__ __forceinline__ void mma_tile_reuse(float (&d)[32], const uint32_t (&a)[16], uint64_t db) {
  WG_FENCE();
  wgmma64_reuse<1>(d, &a[0], db, blockIdx.y);
#pragma unroll
  for (int s = 1; s < 4; s++) wgmma64_acc<1>(d, &a[4 * s], db + s * 128);
  WG_COMMIT();
}
template <int ROW> __device__ __forceinline__ void fold_step(float (&d)[32], const uint32_t (&mu)[4]) {
  wgmma64_acc<1>(d, mu, (uint64_t)((SM_BASE + SM_CS + ROW * 128) >> 4) | (uint64_t(1) << 16) | (uint64_t(1) << 62));
}
template <int ROW> __device__ __forceinline__ void mma_fold(float (&d)[32], const uint32_t (&mu)[4]) {
  WG_FENCE();
  fold_step<ROW>(d, mu);
  WG_COMMIT();
}
template <int ROW> __device__ __forceinline__ void mma_tile_fold(float (&d)[32], const uint32_t (&a)[16], uint64_t db, const uint32_t (&mu)[4]) {
  WG_FENCE();
#pragma unroll
  for (int s = 0; s < 4; s++) wgmma64_acc<1>(d, &a[4 * s], db + s * 128);
  fold_step<ROW>(d, mu);
  WG_COMMIT();
}
__device__ __forceinline__ void mma_add_half(float (&d)[32], const uint32_t (&a)[16]) {
  const uint64_t db = (uint64_t)((SM_BASE + SM_EYE) >> 4) | (uint64_t(8) << 16) | (uint64_t(8) << 32);
  WG_FENCE();
#pragma unroll
  for (int s = 0; s < 4; s++) wgmma16_acc(&d[8 * s], &a[4 * s], db);
  WG_COMMIT();
}
#define ACQUIRE(f) mbar_wait(SM_BASE + SM_FULL + ((f) % NSTAGE) * 8, ((f) / NSTAGE) & 1)
__device__ __forceinline__ void mbar_probe(uint32_t& ok, uint32_t bar, uint32_t parity) {
  asm volatile("{\n.reg .pred p;\nmbarrier.test_wait.parity.shared::cta.b64 p, [%1], %2;\nselp.u32 %0, %0, 0, p;\n}"
               : "+r"(ok) : "r"(bar), "r"(parity) : "memory");
}
template <int F, int N> __device__ __forceinline__ uint32_t probe_n() {
  static_assert(F % NSTAGE + N <= NSTAGE, "stages must not wrap");
  uint32_t ok = 1;
#pragma unroll
  for (int i = 0; i < N; i++) mbar_probe(ok, SM_BASE + SM_FULL + (F % NSTAGE + i) * 8, (F / NSTAGE) & 1);
  return ok;
}
template <int F, int N> __device__ __forceinline__ void settle_n(uint32_t ok) {
  if (__builtin_expect(!ok, 0)) {
#pragma unroll 1
    for (int i = 0; i < N; i++) mbar_wait(SM_BASE + SM_FULL + (F % NSTAGE + i) * 8, (F / NSTAGE) & 1);
  }
}
template <int F, int N> __device__ __forceinline__ void acquire_n() { settle_n<F, N>(probe_n<F, N>()); }
#define RELEASE(f0, f1) do { if (lane == 0) { _Pragma("unroll") for (int f_ = (f0); f_ <= (f1); f_++) mbar_arrive(SM_BASE + SM_EMPTY + (f_ % NSTAGE) * 8); } } while (0)
constexpr uint64_t RING = (uint64_t)(SM_BASE >> 4) | (uint64_t(1) << 16) | (uint64_t(64) << 32) | (uint64_t(1) << 62);
#define LO(f) (RING + ((f) % NSTAGE) * 1024)
#define HI(f) (RING + ((f) % NSTAGE) * 1024 + 512)

template <int C> __device__ __forceinline__ uint4* peer(uint4* p) {
  asm volatile("" : "+l"(p));
  return (uint4*)((uintptr_t)p ^ (C * X_SIZE * sizeof(uint4)));
}
__device__ __forceinline__ uint32_t clock_now() { uint32_t c; asm volatile("mov.u32 %0, %%clock;" : "=r"(c) :: "memory"); return c; }
__device__ __forceinline__ void publish(uint4* dst, uint32_t (&a)[16], uint32_t tag) {
#pragma unroll
  for (int s = 0; s < 4; s++) a[4 * s] = (a[4 * s] & ~1u) | tag;
  pin(a);
  SCHED();
#pragma unroll
  for (int s = 0; s < 4; s++) st_vec(dst + s * 128, a[4 * s], a[4 * s + 1], a[4 * s + 2], a[4 * s + 3]);
  SCHED();
}
__device__ __forceinline__ void fetch(const uint4* src, uint32_t (&a)[16]) {
#pragma unroll
  for (int s = 0; s < 4; s++) ld_vec(src + s * 128, a[4 * s], a[4 * s + 1], a[4 * s + 2], a[4 * s + 3]);
}
__device__ __forceinline__ uint32_t miss(const uint32_t (&a)[16], uint32_t tag) {
  return (a[0] ^ tag) | (a[4] ^ tag) | (a[8] ^ tag) | (a[12] ^ tag);
}
__device__ __forceinline__ bool stale(uint32_t v) { return __any_sync(0xffffffffu, here(v) & 1u); }
__device__ __forceinline__ void announce(Scratch* sc, bool leader) {
  asm volatile("{\n.reg .pred p;\nsetp.ne.u32 p, %1, 0;\n@p red.relaxed.gpu.global.add.u32 [%0], 1;\n}" :: "l"(sc->step[blockIdx.x]), "r"((uint32_t)leader) : "memory");
}
__device__ __forceinline__ uint32_t launch_index(const Scratch* sc) { return *(const volatile uint32_t*)sc->step[blockIdx.x] >> 3; }
__device__ __forceinline__ void stat_fetch(const Scratch* sc, uint32_t (&st)[4]) {
  const uint32_t th = here(threadIdx.x);
  ld_vec(&sc->x[(blockIdx.x & ~3u) + (th & 3)][X_ST + (th >> 2)], st[0], st[1], st[2], st[3]);
}
template <int C, int SLOT> __device__ __forceinline__ void gather_first(uint32_t (&A)[4][16], uint32_t (&st)[4], const Scratch* sc, uint4* xp, uint32_t tag) {
  bar_sync(BAR_GO, 160);
  fetch(peer<1>(xp) + SLOT, A[1]); fetch(peer<2>(xp) + SLOT, A[2]); fetch(peer<3>(xp) + SLOT, A[3]);
  if (SLOT == X_AG0) stat_fetch(sc, st);
  uint32_t spin = 0;
  while (__builtin_expect(stale(miss(A[1], tag) | miss(A[C], tag)), 0) && ++spin < SPIN_LIMIT) {
    fetch(peer<1>(xp) + SLOT, A[1]);
    if (C == 2) fetch(peer<2>(xp) + SLOT, A[2]);
  }
}
template <int C, int SLOT> __device__ __forceinline__ void gather_rest(uint32_t (&A)[4][16], uint4* xp, uint32_t tag) {
  SCHED();
  uint32_t spin = 0;
  while (__builtin_expect(stale(miss(A[C + 1], tag) | miss(A[3], tag)), 0) && ++spin < SPIN_LIMIT) {
    if (C == 1) fetch(peer<2>(xp) + SLOT, A[2]);
    fetch(peer<3>(xp) + SLOT, A[3]);
  }
}
__device__ __forceinline__ void pack_acc(const float (&d)[32], uint32_t (&a)[16]) {
#pragma unroll
  for (int i = 0; i < 16; i++) a[i] = pack2(d[2 * i], d[2 * i + 1]);
}
__device__ __forceinline__ void frag_store(uint32_t slot, const uint32_t (&a)[16]) {
#pragma unroll
  for (int s = 0; s < 4; s++) sts128(slot + s * 512, a[4 * s], a[4 * s + 1], a[4 * s + 2], a[4 * s + 3]);
}
__device__ __forceinline__ void tile_store(uint32_t maddr, const uint32_t (&a)[16]) {
#pragma unroll
  for (int s = 0; s < 4; s++) stsm4(maddr ^ (s << 5), &a[4 * s]);
}
__device__ __forceinline__ void tile_load(uint32_t maddr, uint32_t (&a)[16]) {
#pragma unroll
  for (int s = 0; s < 4; s++) ldsm4(maddr ^ (s << 5), &a[4 * s]);
}

__device__ __forceinline__ void res_load(uint32_t maddr, float (&d)[32]) {
  uint32_t a[16];
  tile_load(here(maddr) + 3 * TILE_BYTES, a);
#pragma unroll
  for (int i = 0; i < 16; i++) { d[2 * i] = bf_lo(a[i]); d[2 * i + 1] = bf_hi(a[i]); }
  pin(d);
}

struct RowAcc { float s[4], u[2][4], v[2][4]; };
__device__ __forceinline__ void row_acc(RowAcc& t, const uint32_t (&a)[16]) {
#pragma unroll
  for (int s = 0; s < 8; s++) {
    if ((s & 1) == 0) hmma(t.s, &a[2 * s], 0x3F803F80u, 0x3F803F80u);
    hmma8(t.u[s & 1], &a[2 * s], a[2 * s]);
    hmma8(t.v[s & 1], &a[2 * s], a[2 * s + 1]);
  }
}
__device__ __forceinline__ float2 row_squares(const RowAcc& t, bool odd) {
  return make_float2(odd ? t.u[0][1] + t.u[1][1] : t.u[0][0] + t.u[1][0], odd ? t.v[0][3] + t.v[1][3] : t.v[0][2] + t.v[1][2]);
}
__device__ __forceinline__ void stat_publish(const uint32_t (&a)[16], Scratch* sc, uint32_t th, uint32_t tag) {
  RowAcc t = {};
  row_acc(t, a);
  const float2 q = row_squares(t, th & 4);
  if ((th & 3) == ((th >> 3) & 3))
    st_vec(&sc->x[blockIdx.x][X_ST + (th >> 2)], (__float_as_uint(t.s[0]) & ~1u) | tag, __float_as_uint(q.x), __float_as_uint(t.s[2]), __float_as_uint(q.y));
}
struct RowNorm { float m0, rs0, m1, rs1; };
__device__ __forceinline__ RowNorm row_norm(float s0, float q0, float s1, float q1, float scale) {
  RowNorm n;
  n.m0 = s0 * (1.f / DM); n.m1 = s1 * (1.f / DM);
  n.rs0 = scale * rsqrt_hw(fmaxf(fmaf(-n.m0, n.m0, q0 * (1.f / DM)), 0.f) + LN_EPS);
  n.rs1 = scale * rsqrt_hw(fmaxf(fmaf(-n.m1, n.m1, q1 * (1.f / DM)), 0.f) + LN_EPS);
  return n;
}
__device__ __forceinline__ RowNorm stat_finish(const Scratch* sc, uint32_t (&st)[4], uint32_t tag, float scale) {
  uint32_t spin = 0;
  while (__builtin_expect(stale(st[0] ^ tag), 0) && ++spin < SPIN_LIMIT) stat_fetch(sc, st);
  float f[4];
#pragma unroll
  for (int i = 0; i < 4; i++) {
    f[i] = __uint_as_float(st[i]);
    f[i] += __shfl_xor_sync(0xffffffffu, f[i], 1);
    f[i] += __shfl_xor_sync(0xffffffffu, f[i], 2);
  }
  return row_norm(f[0], f[1], f[2], f[3], scale);
}
__device__ __forceinline__ void mean_frag(uint32_t (&mu)[4], const RowNorm& n, bool sel) {
  const float a = sel ? -n.m0 : 0.f, c = sel ? -n.m1 : 0.f;
  mu[0] = pack2(a, a); mu[1] = pack2(c, c);
  const float al = a - bf_lo(mu[0]), cl = c - bf_lo(mu[1]);
  mu[2] = pack2(al, al); mu[3] = pack2(cl, cl);
  pin(mu);
}
__device__ __forceinline__ void centre(uint32_t (&a)[16], uint32_t m0, uint32_t m1) {
#pragma unroll
  for (int i = 0; i < 16; i++) asm("sub.rn.bf16x2 %0, %0, %1;" : "+r"(a[i]) : "r"((i & 1) ? m1 : m0));
  pin(a);
}
__device__ __forceinline__ void scale_pack(const float (&d)[32], uint32_t (&a)[16], float rs0, float rs1) {
#pragma unroll
  for (int i = 0; i < 16; i++) { const float rs = (i & 1) ? rs1 : rs0; a[i] = pack2(d[2 * i] * rs, d[2 * i + 1] * rs); }
}
template <int S> __device__ __forceinline__ void silu_seg(float (&acc)[4][32], float (&tn)[2][4], uint32_t (&H)[4][16], float rs0, float rs1) {
  if (S >= 2) {
    const float* h = &acc[(S - 2) >> 3][4 * ((S - 2) & 7)];
    const float* v = tn[S & 1];
    uint32_t* o = &H[(S - 2) >> 3][2 * ((S - 2) & 7)];
    o[0] = pack2(fmaf(h[0], v[0], h[0]), fmaf(h[1], v[1], h[1]));
    o[1] = pack2(fmaf(h[2], v[2], h[2]), fmaf(h[3], v[3], h[3]));
    asm volatile("" : "+r"(o[0]), "+r"(o[1]));
  }
  if (S >= 1 && S <= 32) {
#pragma unroll
    for (int k = 0; k < 4; k++) tn[(S - 1) & 1][k] = tanh_hw(acc[((S - 1) >> 3) & 3][4 * ((S - 1) & 7) + k]);
  }
  if (S < 32) {
    float* h = &acc[(S >> 3) & 3][4 * (S & 7)];
    h[0] *= rs0; h[1] *= rs0; h[2] *= rs1; h[3] *= rs1;
    asm volatile("" : "+f"(h[0]), "+f"(h[1]), "+f"(h[2]), "+f"(h[3]));
  }
  SCHED();
}
template <int S0, int S1> __device__ __forceinline__ void silu_segs(float (&acc)[4][32], float (&tn)[2][4], uint32_t (&H)[4][16], float rs0, float rs1) {
  silu_seg<S0>(acc, tn, H, rs0, rs1);
  if constexpr (S0 + 1 < S1) silu_segs<S0 + 1, S1>(acc, tn, H, rs0, rs1);
}
template <int HALF> __device__ __forceinline__ void send_half(uint4* dst, const float (&d)[32], uint32_t tag) {
  uint32_t o[8];
#pragma unroll
  for (int i = 0; i < 8; i++) o[i] = pack2(d[16 * HALF + 2 * i], d[16 * HALF + 2 * i + 1]);
  o[0] = (o[0] & ~1u) | tag; o[4] = (o[4] & ~1u) | tag;
  pin(o);
  SCHED();
  st_vec(dst + HALF * 256, o[0], o[1], o[2], o[3]);
  st_vec(dst + HALF * 256 + 128, o[4], o[5], o[6], o[7]);
  SCHED();
}
__device__ __forceinline__ void send_residual(uint32_t (&a)[16], Scratch* sc, uint4* xp, uint32_t maddr, uint32_t tag) {
  const uint32_t exact[4] = {a[0], a[4], a[8], a[12]};
  publish(xp + X_AG0, a, tag);
  const uint32_t th = here(threadIdx.x);
  stat_publish(a, sc, th, tag);
  tile_store(here(maddr) + 3 * TILE_BYTES, a);
  stsm4(SM_BASE + SM_STG + 3 * TILE_BYTES + (th >> 5) * 2048 + (th & 7) * 128 + ((((th >> 2) & 6) ^ (th & 7)) << 4), exact);
}
template <int F, int N> __device__ __forceinline__ void proj_residual(uint32_t (&A)[4][16], Scratch* sc, uint4* xp, uint32_t maddr,
                                                                      uint32_t tag, int lane) {
  float acc[32];
  uint32_t st[4];
  acquire_n<F, N>();
  if (F == F_PW2) acquire_n<0, 5>();
  res_load(maddr, acc);
  mma_tile<false>(acc, A[0], LO(F));
  gather_first<2, X_AG1>(A, st, sc, xp, tag);
  mma_tile<false>(acc, A[1], HI(F));
  mma_tile<false>(acc, A[2], LO(F + 1));
  gather_rest<2, X_AG1>(A, xp, tag);
  PROF_MARK0(F == F_WO ? 11 : 16);
  mma_tile<false>(acc, A[3], HI(F + 1));
  announce(sc, threadIdx.x == 0);
  RELEASE(F - 2, F - 1);
  WG_WAIT(0); pin(acc);
  pack_acc(acc, A[0]);
  send_residual(A[0], sc, xp, maddr, tag);
}

__device__ __forceinline__ uint64_t ring_desc(uint32_t lo) { return (RING & ~uint64_t(0xFFFFFFFFu)) | lo; }
__device__ __forceinline__ void qk_tile(float (&S)[32], const uint32_t (&Q)[16], uint32_t dk) {
  wgmma64_reuse<0>(S, &Q[0], ring_desc(dk), blockIdx.y);
#pragma unroll
  for (int s = 1; s < 4; s++) wgmma64_acc<0>(S, &Q[4 * s], ring_desc(dk + s * 2));
}
__device__ __forceinline__ void qk_shift(float (&S)[32], const uint32_t (&nm)[4]) { wgmma64_acc<0>(S, nm, (uint64_t)((SM_BASE + SM_ONE) >> 4)); }
constexpr uint32_t RING_K = (uint32_t)RING, V_STEP = 1u - (1u << 16);
constexpr uint32_t RING_V = (SM_BASE >> 4) | (((SM_STG + 2 * TILE_BYTES) >> 4) << 16);
__device__ __forceinline__ void pv_tile(float (&O)[36], const uint32_t (&P)[16], uint32_t dv, uint32_t pad) {
#pragma unroll
  for (int s = 0; s < 4; s++) wgmma72_acc(O, &P[4 * s], ring_desc(dv + s * 128 * V_STEP + (s < 2 ? 0 : (s - 1) * pad)));
}
__device__ __forceinline__ void attn_step(const float (&Sc)[32], float (&Sn)[32], uint32_t (&Pc)[16], uint32_t (&Pp)[16], float (&O)[36],
                                          const uint32_t (&Q)[16], const uint32_t (&nm)[4], uint32_t dk, uint32_t dv, bool next, bool prev) {
  if (next) {
    WG_FENCE();
    qk_tile(Sn, Q, dk);
    qk_shift(Sn, nm);
  }
  if (prev) {
    WG_FENCE();
    pv_tile(O, Pp, dv, 0);
  }
  WG_COMMIT();
  SCHED();
#pragma unroll
  for (int i = 0; i < 16; i++) Pc[i] = pack2(ex2_hw(Sc[2 * i]), ex2_hw(Sc[2 * i + 1]));
  pin(Pc);
  SCHED();
}
template <int R> __device__ __forceinline__ float tile_max(const float (&S)[32]) {
  float t[4];
#pragma unroll
  for (int j = 0; j < 4; j++) t[j] = fmaxf(fmaxf(S[8 * j + R], S[8 * j + R + 1]), fmaxf(S[8 * j + R + 4], S[8 * j + R + 5]));
  float n = fmaxf(fmaxf(t[0], t[1]), fmaxf(t[2], t[3]));
  n = fmaxf(n, __shfl_xor_sync(0xffffffffu, n, 1));
  return fmaxf(n, __shfl_xor_sync(0xffffffffu, n, 2));
}
__device__ __forceinline__ void attention_exact(float (&O)[36], const uint32_t (&Q)[16], const Scratch* sc, int bh, int lane, int half) {
  const char* kb = (const char*)&sc->kv[bh][0][0][0];
  const char* vb = (const char*)&sc->kv[bh][1][0][0];
  const int g = lane >> 2, q = lane & 3;
  float m0 = -INFINITY, m1 = -INFINITY, l0 = 0.f, l1 = 0.f;
  float o[4][4] = {};
#pragma unroll 1
  for (int k0 = 0; k0 < T_SEQ; k0 += 8) {
    float s[4] = {0.f, 0.f, 0.f, 0.f};
#pragma unroll
    for (int c = 0; c < 8; c++) hmma8(s, &Q[2 * c], __ldcg((const uint32_t*)(kb + (k0 + g) * 128 + ((c ^ g) << 4) + q * 4)));
    float n0 = fmaxf(s[0], s[1]), n1 = fmaxf(s[2], s[3]);
    n0 = fmaxf(n0, __shfl_xor_sync(0xffffffffu, n0, 1)); n1 = fmaxf(n1, __shfl_xor_sync(0xffffffffu, n1, 1));
    n0 = fmaxf(m0, fmaxf(n0, __shfl_xor_sync(0xffffffffu, n0, 2))); n1 = fmaxf(m1, fmaxf(n1, __shfl_xor_sync(0xffffffffu, n1, 2)));
    const float a0 = ex2_hw(m0 - n0), a1 = ex2_hw(m1 - n1);
    m0 = n0; m1 = n1;
    const uint32_t pp[2] = {pack2(ex2_hw(s[0] - n0), ex2_hw(s[1] - n0)), pack2(ex2_hw(s[2] - n1), ex2_hw(s[3] - n1))};
    l0 = fmaf(l0, a0, bf_lo(pp[0]) + bf_hi(pp[0])); l1 = fmaf(l1, a1, bf_lo(pp[1]) + bf_hi(pp[1]));
#pragma unroll
    for (int j = 0; j < 4; j++) {
      const int c = 4 * half + j;
      const uint32_t v0 = __ldcg((const uint16_t*)(vb + (k0 + 2 * q) * 128 + ((c ^ (2 * q)) << 4) + g * 2));
      const uint32_t v1 = __ldcg((const uint16_t*)(vb + (k0 + 2 * q + 1) * 128 + ((c ^ (2 * q + 1)) << 4) + g * 2));
      o[j][0] *= a0; o[j][1] *= a0; o[j][2] *= a1; o[j][3] *= a1;
      hmma8(o[j], pp, v0 | (v1 << 16));
    }
  }
  l0 += __shfl_xor_sync(0xffffffffu, l0, 1); l1 += __shfl_xor_sync(0xffffffffu, l1, 1);
  O[32] = l0 + __shfl_xor_sync(0xffffffffu, l0, 2); O[34] = l1 + __shfl_xor_sync(0xffffffffu, l1, 2);
#pragma unroll
  for (int i = 0; i < 16; i++) O[i] = o[i >> 2][i & 3];
}

__device__ __forceinline__ uint32_t fill_entry(int f, int r) {
  int m, x = r, y, dx = 0;
  if (f < F_QKV || f >= 48) {
    const int i = f & 15;
    m = f < F_QKV ? M_FF1A : M_FF2A;
    if (i < 8) { x = 4 * r + ((0xE2u >> i) & 1) * 2; y = r ^ ((0xE790u >> (2 * i)) & 3); dx = 1; }
    else { m++; x = r ^ (((i >> 1) - 3) & 3); y = 4 * r + 2 * (i & 1); }
  } else if (f < F_KV) {
    const int i = f - F_QKV;
    m = M_QKV;
    if (i == 1 || i >= 5) { y = r ^ (i == 1 ? 0 : 2); }
    else { x = 4 + r; y = r ^ (i ? i - 1 : 0); dx = 4; }
  } else if (f >= F_PW1 && f < F_PW2) {
    m = M_PW1; y = r ^ (f - F_PW1); dx = 4;
  } else {
    m = f < F_PW1 ? M_WO : M_PW2; y = r ^ ((f & 1) * 2);
  }
  return m | (x << 4) | (y << 8) | (dx << 16);
}
__device__ __forceinline__ void tma_fill(uint32_t st, const CUtensorMap* map, uint32_t x, uint32_t y, uint32_t x2, uint32_t y2) {
  asm volatile("{\n.reg .pred p;\nelect.sync _|p, 0xffffffff;\n"
               "@p mbarrier.arrive.expect_tx.shared::cta.b64 _, [%1], 16384;\n"
               "@p cp.async.bulk.tensor.2d.shared::cluster.global.mbarrier::complete_tx::bytes [%0], [%2, {%3, %4}], [%1];\n"
               "@p cp.async.bulk.tensor.2d.shared::cluster.global.mbarrier::complete_tx::bytes [%0 + 8192], [%2, {%5, %6}], [%1];\n}"
               :: "r"(SM_BASE + st * STAGE_BYTES), "r"(SM_BASE + SM_FULL + st * 8), "l"(map), "r"(x), "r"(y), "r"(x2), "r"(y2) : "memory");
}
template <int F0, int N> __device__ __forceinline__ void weight_fills(const Params& p, uint32_t entry) {
  uint32_t st = F0 % NSTAGE, parity = ((F0 / NSTAGE) & 1) ^ 1, e = __shfl_sync(0xffffffffu, entry, 0);
#pragma unroll 1
  for (int i = 1; i <= N; i++) {
    const uint32_t x = (e << 2) & 0x3C0, y = (e >> 2) & 0x3FC0, dx = (e >> 16) << 6;
    const CUtensorMap* map = &p.map[e & 15];
    e = __shfl_sync(0xffffffffu, entry, i);
    mbar_wait(SM_BASE + SM_EMPTY + st * 8, parity);
    tma_fill(st, map, x, y, x + dx, dx ? y : y ^ 64);
    if (++st == NSTAGE) { st = 0; parity ^= 1; }
  }
}
__device__ __forceinline__ uint32_t kv_poll(const uint32_t* flag, uint32_t prev) {
  uint32_t v;
  asm volatile("ld.relaxed.gpu.global.u32 %0, [%1];" : "=r"(v) : "l"(flag) : "memory");
  return __ballot_sync(0xffffffffu, v - 1 == prev);
}
__device__ __forceinline__ void kv_fills(const Scratch* sc, int bh, int kind, uint32_t prev, const uint32_t* flag, uint32_t ready) {
#pragma unroll 1
  for (int j = 0; j < 8; j++) {
    uint32_t spin = 0;
#pragma unroll 1
    while (((ready >> (2 * j)) & 3) != 3 && ++spin < SPIN_LIMIT) ready = kv_poll(flag, prev);
    const uint32_t st = (j < 6 ? 4 * (j >> 1) : 0) + (j & 1) + 2 * kind;
    mbar_wait(SM_BASE + SM_EMPTY + st * 8, j < 6);
    asm volatile("{\n.reg .pred p;\nelect.sync _|p, 0xffffffff;\n"
                 "@p mbarrier.arrive.expect_tx.shared::cta.b64 _, [%1], 16384;\n"
                 "@p cp.async.bulk.shared::cluster.global.mbarrier::complete_tx::bytes [%0], [%2], 16384, [%1];\n}"
                 :: "r"(SM_BASE + st * STAGE_BYTES), "r"(SM_BASE + SM_FULL + st * 8), "l"(sc->kv[bh][kind][2 * j]) : "memory");
    PROF_AT(256 + 512 + (10 + kind * 8 + j) * 4);
  }
}
__device__ __forceinline__ void l2_prefetch(const void* p, uint32_t total, int b) {
  const uint32_t part = total / NCTA;
  asm volatile("cp.async.bulk.prefetch.L2.global [%0], %1;" :: "l"((const char*)p + (size_t)b * part), "r"(part) : "memory");
}

__global__ void __launch_bounds__(384, 1) conformer_kernel(Scratch* __restrict__ sc, __nv_bfloat16* __restrict__ out,
                                                           const __nv_bfloat16* __restrict__ dw, const __nv_bfloat16* __restrict__ xin,
                                                           const __nv_bfloat16* __restrict__ w_ff1a, const __grid_constant__ Params p) {
  extern __shared__ __align__(1024) uint8_t smem[];
  const int tid = threadIdx.x, lane = tid & 31;
  if (tid == 0) {
    l2_prefetch(xin, 2 * T_SEQ * DM * 2, blockIdx.x);
    l2_prefetch(w_ff1a, 256 * 1024 * 2, blockIdx.x);
  }
  const int cw = __shfl_sync(0xffffffffu, tid >> 5, 0), wg = cw >> 2, w = cw & 3;
  const int b = blockIdx.x, r = b & 3, batch = b >> 6, t = (b >> 2) & 15;
  if ((uint32_t)__cvta_generic_to_shared(smem) != SM_BASE) return;
  PROF_MARK(0);
  PROF_TIME(30);

  if (wg == 2) {
    asm volatile("setmaxnreg.dec.sync.aligned.u32 40;");
    if (cw == 8) {
      if (lane == 0) {
        asm volatile("prefetch.tensormap [%0];" :: "l"(&p.map[M_X]) : "memory");
        asm volatile("prefetch.tensormap [%0];" :: "l"(&p.map[M_FF1A]) : "memory");
#pragma unroll
        for (int i = 0; i < 4; i++) mbar_init(SM_BASE + SM_XBAR + i * 8, 1);
#pragma unroll
        for (int i = 0; i < NSTAGE; i++) mbar_init(SM_BASE + SM_FULL + i * 8, 1);
        fence_async_smem();
      }
      __syncwarp();
      bar_arrive(0, 320);
      PROF_MARK(9);
#pragma unroll
      for (int f = 0; f < 8; f++) {
        const uint32_t x = 256 * r + ((0xE2u >> f) & 1) * 128, y = (r ^ ((0xE790u >> (2 * f)) & 3)) * 64;
#pragma unroll
        for (int c = 0; c < (f == 0 ? 4 : 0); c++)
          asm volatile("{\n.reg .pred p;\nelect.sync _|p, 0xffffffff;\n"
                       "@p mbarrier.arrive.expect_tx.shared::cta.b64 _, [%1], 8192;\n"
                       "@p cp.async.bulk.tensor.3d.shared::cluster.global.mbarrier::complete_tx::bytes [%0], [%2, {%3, %4, %5}], [%1];\n}"
                       :: "r"(SM_BASE + SM_STG + (3 - c) * TILE_BYTES), "r"(SM_BASE + SM_XBAR + c * 8), "l"(&p.map[M_X]),
                          "r"((r ^ c) * 64), "r"(t * 64), "r"(batch) : "memory");
        tma_fill(f, &p.map[M_FF1A], x, y, x + 64, y);
      }
      PROF_MARK(1);
      uint32_t entry[2];
#pragma unroll 1
      for (int i = 0; i < 2; i++) { entry[1] = fill_entry(8 + i * 32 + lane, r); if (i == 0) entry[0] = entry[1]; }
      bar_sync(BAR_INIT, 64);
      weight_fills<8, F_KV - 8>(p, entry[0]);
      mbar_wait(SM_BASE + SM_EMPTY + (F_WO % NSTAGE) * 8, 1);
      weight_fills<F_WO, F_TOTAL - F_WO>(p, entry[1]);
    } else if (here(cw) != 11) {
      const int kind = w - 1;
      const uint32_t prev = launch_index(sc);
      if (kind == 0) {
        if (lane == 0) {
#pragma unroll
          for (int i = 0; i < NSTAGE; i++) mbar_init(SM_BASE + SM_EMPTY + i * 8, 4);
        }
        __syncwarp();
        bar_arrive(0, 320);
        bar_arrive(BAR_INIT, 64);
      }
      const uint32_t* flag = sc->flag[batch * 4 + r][kind * 16 + (lane & 15)];
      const uint32_t ready = kv_poll(flag, prev);
      if (kind == 0) bar_sync(BAR_K, 160); else bar_sync(BAR_V, 160);
      if (lane == 0) {
        asm volatile("cp.async.bulk.global.shared::cta.bulk_group [%0], [%1], %2;"
                     :: "l"(&sc->kv[batch * 4 + r][kind][t][0]), "r"(SM_BASE + SM_STG + kind * TILE_BYTES), "r"(TILE_BYTES) : "memory");
PROF_MARK(4 + kind * 2);
        asm volatile("cp.async.bulk.commit_group;\ncp.async.bulk.wait_group 0;" ::: "memory");
PROF_MARK(5 + kind * 2);
        asm volatile("st.relaxed.gpu.global.u32 [%0], %1;" :: "l"(sc->flag[batch * 4 + r][kind * 16 + t]), "r"(prev + 1) : "memory");
      }
      __syncwarp();
      kv_fills(sc, batch * 4 + r, kind, prev, flag, ready);
    } else {
      const uint32_t* watch = sc->step[(b & ~3) + (lane & 3)];
      uint32_t seen;
      asm volatile("ld.relaxed.gpu.global.u32 %0, [%1];" : "=r"(seen) : "l"(watch) : "memory");
#pragma unroll 1
      for (int i = 0; i < 22; i++) {
        const uint32_t t0 = clock_now();
        uint4* dst = &sc->x[b][i * 96 + lane];
        st_vec(dst, 0u, 0u, 0u, 0u); st_vec(dst + 32, 0u, 0u, 0u, 0u); st_vec(dst + 64, 0u, 0u, 0u, 0u);
        if (i == PF_AT && lane == 0) {
          asm volatile("prefetch.tensormap [%0];" :: "l"(&p.map[M_FF1B]) : "memory");
          l2_prefetch(p.w_ff1b, 1024 * 256 * 2, b);
          l2_prefetch(p.w_qkv, 256 * 768 * 2, b);
          l2_prefetch(p.w_pw1, 256 * 512 * 2, b);
          l2_prefetch(p.w_ff2a, 256 * 1024 * 2, b);
        }
        while (clock_now() - t0 < CLR_PACE) {}
      }
      PROF_MARK(28);
      asm volatile("fence.acq_rel.gpu;" ::: "memory");
      __syncwarp();
      announce(sc, lane == 0);
      if (lane == 0) {
        l2_prefetch(p.w_o, 256 * 256 * 2, b);
        l2_prefetch(p.w_pw2, 256 * 256 * 2, b);
        l2_prefetch(p.w_ff2b, 1024 * 256 * 2, b);
#pragma unroll
        for (int i = M_QKV; i < M_X; i++) asm volatile("prefetch.tensormap [%0];" :: "l"(&p.map[i]) : "memory");
      }
      PROF_MARK(2);
      uint32_t want = seen & ~7u;
#pragma unroll 1
      for (int k = 0; k < 8; k++) {
        want++;
        uint32_t spin = 0;
#pragma unroll 1
        while (__any_sync(0xffffffffu, (int)(seen - want) < 0) && ++spin < SPIN_LIMIT)
          asm volatile("ld.relaxed.gpu.global.u32 %0, [%1];" : "=r"(seen) : "l"(watch) : "memory");
        bar_arrive(BAR_GO, 160);
        PROF_MARK(32 + k);
      }
    }
  } else {
    asm volatile("setmaxnreg.inc.sync.aligned.u32 232;");
    const int q = lane & 3, th = tid & 127;
    constexpr uint32_t stg = SM_BASE + SM_STG;
    const uint32_t mrow = 16 * w + (lane & 15);
    const uint32_t maddr = stg + mrow * 128 + (((lane >> 4) ^ (lane & 7)) << 4);
    const uint32_t qslot = stg + 2 * TILE_BYTES + w * 2048 + lane * 16;
    uint4* const xp = &sc->x[b][th];
    const int nvalid = T_SEQ - t * 64, row0 = 16 * w + (lane >> 2);

    uint32_t A[4][16];
    uint32_t st[4];
    if (tid < 144) sts128(SM_BASE + SM_CS + tid * 16, 0, 0, 0, 0);
    if (wg == 1) sts32(SM_BASE + SM_EYE + th * 4, th >= 96 ? 0x3F803F80u : ((th & 32) == 0 && (th & 3) == ((th >> 3) & 3)) ? (0x3F00u << ((th & 4) * 4)) : 0u);
    fence_async_smem();
    bar_sync(0, 320);
    if (wg == 0) {
      RowAcc ra = {};
      mbar_wait(SM_BASE + SM_XBAR, 0);
      PROF_MARK0(45);
      tile_load(maddr + 3 * TILE_BYTES, A[0]);
#pragma unroll
      for (int c = 1; c < 4; c++) {
        mbar_wait(SM_BASE + SM_XBAR + c * 8, 0);
        tile_load(maddr + (3 - c) * TILE_BYTES, A[c]);
        row_acc(ra, A[c - 1]);
      }
      PROF_MARK(1);
      row_acc(ra, A[3]);
      PROF_MARK0(46);
      const float m0 = ra.s[0] * (1.f / DM), m1 = ra.s[2] * (1.f / DM);
      st[0] = pack2(m0, m0); st[1] = pack2(m1, m1);
      centre(A[0], st[0], st[1]);
      const float2 sq = row_squares(ra, lane & 4);
      st[2] = __float_as_uint(fmaf(-m0, m0, sq.x * (1.f / DM))); st[3] = __float_as_uint(fmaf(-m1, m1, sq.y * (1.f / DM)));
    } else {
      const uint32_t tag = ~launch_index(sc) & 1;
      mbar_wait(SM_BASE + SM_FULL + 4 * 8, 0);
      PROF_MARK(5);
      if (b < 72) {
        const __nv_bfloat16* wp; int ld, col;
        if (b < 24) { wp = p.w_qkv; ld = 768; col = b * 32; }
        else if (b < 40) { wp = p.w_pw1; ld = 512; col = (b - 24) * 32; }
        else { wp = p.w_ff2a; ld = 1024; col = (b - 40) * 32; }
        const uint4* src = (const uint4*)(wp + (size_t)(th >> 2) * ld + col + q * 8);
        float c[8] = {0.f, 0.f, 0.f, 0.f, 0.f, 0.f, 0.f, 0.f};
#pragma unroll 1
        for (int h = 0; h < 2; h++, src += 16 * ld) {
#pragma unroll
          for (int i = 0; i < 4; i++) {
            const uint4 v = __ldg(src + i * 4 * ld);
            c[0] += bf_lo(v.x); c[1] += bf_hi(v.x); c[2] += bf_lo(v.y); c[3] += bf_hi(v.y);
            c[4] += bf_lo(v.z); c[5] += bf_hi(v.z); c[6] += bf_lo(v.w); c[7] += bf_hi(v.w);
          }
        }
#pragma unroll 1
        for (int m = 4; m <= 16; m <<= 1)
#pragma unroll
          for (int k = 0; k < 8; k++) c[k] += __shfl_xor_sync(0xffffffffu, c[k], m);
        if (lane < 4) {
          const uint32_t a = SM_BASE + SM_CS + 1792 + w * 128 + lane * 32;
          sts128(a, __float_as_uint(c[0]), __float_as_uint(c[1]), __float_as_uint(c[2]), __float_as_uint(c[3]));
          sts128(a + 16, __float_as_uint(c[4]), __float_as_uint(c[5]), __float_as_uint(c[6]), __float_as_uint(c[7]));
        }
        bar_sync(BAR_WG1, 128);
        if (th < 8) {
          float o[4] = {0.f, 0.f, 0.f, 0.f};
#pragma unroll 1
          for (int k = 0; k < 4; k++) {
            uint32_t e[4];
            lds128(SM_BASE + SM_CS + 1792 + k * 128 + th * 16, e[0], e[1], e[2], e[3]);
#pragma unroll
            for (int i = 0; i < 4; i++) o[i] += __uint_as_float(e[i]);
          }
          st_vec(&sc->cs[b * 8 + th], (__float_as_uint(o[0]) & ~1u) | tag, __float_as_uint(o[1]), __float_as_uint(o[2]), __float_as_uint(o[3]));
        }
      }
      bar_sync(BAR_WG1, 128);
      PROF_MARK(2);
      if (th < 72) {
        const int j = th >> 3, i = (th & 7) * 2;
        int src;
        if (j < CS_PW1) src = 320 + 64 * r + 16 * j;
        else if (j < CS_QKV) src = 192 + (j - CS_PW1) * 64 + 16 * r;
        else src = ((j - CS_QKV + 1) % 3) * 64 + 16 * r;
        uint32_t e[8], hi[4], lo[4], spin = 0;
#pragma unroll 1
        do {
          ld_vec(&sc->cs[src + i], e[0], e[1], e[2], e[3]);
          ld_vec(&sc->cs[src + i + 1], e[4], e[5], e[6], e[7]);
        } while ((((e[0] ^ tag) | (e[4] ^ tag)) & 1u) && ++spin < SPIN_LIMIT);
        e[0] &= ~1u; e[4] &= ~1u;
#pragma unroll
        for (int k = 0; k < 4; k++) {
          const float c0 = __uint_as_float(e[2 * k]), c1 = __uint_as_float(e[2 * k + 1]);
          hi[k] = pack2(c0, c1);
          lo[k] = pack2(c0 - bf_lo(hi[k]), c1 - bf_hi(hi[k]));
        }
        const uint32_t a = SM_BASE + SM_CS + j * 256 + i * 8;
        sts128(a ^ ((a >> 3) & 0x70), hi[0], hi[1], hi[2], hi[3]);
        sts128((a + 128) ^ (((a + 128) >> 3) & 0x70), lo[0], lo[1], lo[2], lo[3]);
      }
      fence_async_smem();
      PROF_MARK(4);
      bar_arrive(BAR_CS, 256);
    }

#pragma unroll 1
    for (uint32_t pass = 0; pass < 2; pass++) {
      uint32_t Q[16];
      if (wg == 0) {
        float acc[4][32];
        uint32_t H[4][16];
        if (!pass) { PROF_MARK(47); ACQUIRE(0); }
        mma_tile<true>(acc[0], A[0], LO(0)); mma_tile<true>(acc[1], A[0], HI(0));
        if (!pass) ACQUIRE(1);
        mma_tile<true>(acc[2], A[0], LO(1)); mma_tile<true>(acc[3], A[0], HI(1));
        if (pass) {
          gather_first<1, X_AG0>(A, st, sc, xp, 1);
        } else {
          centre(A[1], st[0], st[1]);
          acquire_n<2, 3>();
        }
        mma_tile<false>(acc[0], A[1], LO(2)); mma_tile<false>(acc[1], A[1], HI(2));
        if (pass) {
          gather_rest<1, X_AG0>(A, xp, 1);
          RELEASE(F_PW2, F_PW2 + 1);
        } else {
          centre(A[2], st[0], st[1]); centre(A[3], st[0], st[1]);
        }
        PROF_MARK2(2, 18);
        mma_tile<false>(acc[0], A[2], LO(3)); mma_tile<false>(acc[0], A[3], LO(4));
        WG_WAIT(4);
        RELEASE(0, 1);
        uint32_t mu[4] = {0u, 0u, 0u, 0u};
        float rs0, rs1, tn[2][4];
        if (pass) {
          const RowNorm n = stat_finish(sc, st, 1, 0.5f);
          rs0 = n.rs0; rs1 = n.rs1;
          mean_frag(mu, n, q == 0);
        } else {
          const int src = (lane & 28) | (lane >> 3);
          rs0 = 0.5f * rsqrt_hw(fmaxf(__uint_as_float(__shfl_sync(0xffffffffu, st[2], src)), 0.f) + LN_EPS);
          rs1 = 0.5f * rsqrt_hw(fmaxf(__uint_as_float(__shfl_sync(0xffffffffu, st[3], src)), 0.f) + LN_EPS);
        }
        pin(mu);
        mma_fold<2 * CS_FF2>(acc[0], mu);
        mma_tile<false>(acc[1], A[2], HI(3));
#define SEGS(a, b) silu_segs<a, b>(acc, tn, H, rs0, rs1)
        WG_WAIT(1); pin(acc[0]);
        SEGS(0, 1);
        mma_tile_fold<2 * CS_FF2 + 2>(acc[1], A[3], HI(4), mu);
        SEGS(1, 3);
        uint32_t ok = probe_n<5, 3>();
        SEGS(3, 4);
        settle_n<5, 3>(ok);
        mma_tile<false>(acc[2], A[1], LO(5));
        SEGS(4, 6);
        mma_tile<false>(acc[2], A[2], LO(6));
        SEGS(6, 8);
        WG_WAIT(2); pin(acc[1]);
        RELEASE(2, 4);
        SEGS(8, 9);
        mma_tile_fold<2 * CS_FF2 + 4>(acc[2], A[3], LO(7), mu);
        SEGS(9, 12);
        mma_tile<false>(acc[3], A[1], HI(5));
        SEGS(12, 14);
        mma_tile<false>(acc[3], A[2], HI(6));
        SEGS(14, 16);
        WG_WAIT(2); pin(acc[2]);
        SEGS(16, 17);
        mma_tile_fold<2 * CS_FF2 + 6>(acc[3], A[3], HI(7), mu);
        SEGS(17, 19);
        ok = probe_n<8, 2>();
        SEGS(19, 20);
        settle_n<8, 2>(ok);
        mma_tile_reuse(acc[1], H[0], LO(8));
        SEGS(20, 22);
        mma_tile<false>(acc[1], H[1], HI(8));
        SEGS(22, 24);
        WG_WAIT(2); pin(acc[3]);
        RELEASE(5, 7);
        SEGS(24, 26);
        mma_tile<false>(acc[1], H[2], LO(9));
        SEGS(26, 27);
        ok = probe_n<10, 2>();
        SEGS(27, 28);
        settle_n<10, 2>(ok);
        mma_tile_reuse(acc[2], H[0], LO(10));
        SEGS(28, 31);
        mma_tile<false>(acc[2], H[1], HI(10));
        SEGS(31, 34);
#undef SEGS
        PROF_MARK2(3, 19);
        const uint32_t rtag = here(pass ^ 1);
        const uint4* rs_in = xp + X_RS;
        mma_tile<false>(acc[1], H[3], HI(9));
        mma_tile<false>(acc[2], H[2], LO(11));
        ok = probe_n<12, 2>();
        uint4* rs_out = peer<1>(xp) + X_RS;
        mma_tile<false>(acc[2], H[3], HI(11));
        settle_n<12, 2>(ok);
        if (!pass) bar_sync(BAR_GO, 160);
        WG_WAIT(2); pin(acc[1]);
        RELEASE(8, 9);
        send_half<0>(rs_out, acc[1], rtag);
        mma_tile_reuse(acc[3], H[0], LO(12));
        SCHED();
        send_half<1>(rs_out, acc[1], rtag);
        mma_tile<false>(acc[3], H[1], HI(12));
        rs_out = peer<2>(xp) + X_RS + 512;
        WG_WAIT(2); pin(acc[2]);
        send_half<0>(rs_out, acc[2], rtag);
        mma_tile<false>(acc[3], H[2], LO(13));
        SCHED();
        ok = probe_n<14, 2>();
        send_half<1>(rs_out, acc[2], rtag);
        mma_tile<false>(acc[3], H[3], HI(13));
        settle_n<14, 2>(ok);
        mma_tile_reuse(acc[1], H[0], LO(14));
        rs_out = peer<3>(xp) + X_RS + 1024;
        fetch(rs_in, A[1]);
        SCHED();
        mma_tile<false>(acc[1], H[1], HI(14));
        WG_WAIT(2); pin(acc[3]);
        announce(sc, tid == 0);
        send_half<0>(rs_out, acc[3], rtag);
        send_half<1>(rs_out, acc[3], rtag);
        mma_tile<false>(acc[1], H[2], LO(15)); mma_tile<false>(acc[1], H[3], HI(15));
        SCHED();
        fetch(rs_in + 512, A[2]);
        SCHED();
        res_load(maddr, acc[2]);
        bar_sync(BAR_GO, 160);
        fetch(rs_in + 1024, A[3]);
        if (!pass) acquire_n<F_QKV, 3>();
        {
          uint32_t spin = 0;
          while (__builtin_expect(stale(miss(A[1], rtag) | miss(A[2], rtag) | miss(A[3], rtag)), 0) && ++spin < SPIN_LIMIT) {
            if (stale(miss(A[1], rtag) | miss(A[2], rtag))) { fetch(rs_in, A[1]); fetch(rs_in + 512, A[2]); }
            fetch(rs_in + 1024, A[3]);
          }
        }
        announce(sc, tid == 0 && !pass);
        mma_add_half(acc[2], A[1]);
        mma_add_half(acc[2], A[2]);
        mma_add_half(acc[2], A[3]);
        PROF_MARK2(4, 20);
        WG_WAIT(0); pin(acc[2]); pin(acc[1]);
#pragma unroll
        for (int i = 0; i < 16; i++) A[0][i] = pack2(fmaf(acc[1][2 * i], 0.5f, acc[2][2 * i]), fmaf(acc[1][2 * i + 1], 0.5f, acc[2][2 * i + 1]));
        if (pass) {
          PROF_MARK(21);
          stat_publish(A[0], sc, here(th), 0);
          stat_fetch(sc, st);
          const RowNorm fn = stat_finish(sc, st, 0, 1.f);
          const float nm0 = -fn.m0 * fn.rs0, nm1 = -fn.m1 * fn.rs1;
#pragma unroll
          for (int i = 0; i < 16; i++) {
            const float rs = (i & 1) ? fn.rs1 : fn.rs0, nm = (i & 1) ? nm1 : nm0;
            A[0][i] = pack2(fmaf(bf_lo(A[0][i]), rs, nm), fmaf(bf_hi(A[0][i]), rs, nm));
          }
          tile_store(here(maddr), A[0]);
          __syncwarp();
          const int row = 16 * w + (lane >> 3);
          uint4* dst = (uint4*)(out + ((size_t)batch * T_SEQ + t * 64 + row) * DM + 64 * r) + (lane & 7);
          const uint32_t src = stg + row * 128 + (((lane & 7) ^ (lane >> 3)) << 4);
#pragma unroll
          for (int i = 0; i < 4; i++) {
            uint4 v;
            lds128((src ^ ((i & 1) << 6)) + i * 512, v.x, v.y, v.z, v.w);
            if (row + 4 * i < nvalid) dst[i * 4 * (DM / 8)] = v;
          }
          PROF_MARK(22);
          PROF_TIME(31);
          break;
        }
        send_residual(A[0], sc, xp, maddr, 1);
        PROF_MARK(5);
        mma_tile<true>(acc[0], A[0], LO(F_QKV)); mma_tile<true>(acc[1], A[0], HI(F_QKV));
        mma_tile<true>(acc[2], A[0], LO(F_QKV + 1));
        gather_first<1, X_AG0>(A, st, sc, xp, 1);
        mma_tile<false>(acc[0], A[1], LO(F_QKV + 2)); mma_tile<false>(acc[1], A[1], HI(F_QKV + 2));
        acquire_n<F_QKV + 3, 3>();
        bar_sync(BAR_CS, 256);
        gather_rest<1, X_AG0>(A, xp, 1);
        PROF_MARK(6);
        mma_tile<false>(acc[0], A[2], LO(F_QKV + 3)); mma_tile<false>(acc[0], A[3], LO(F_QKV + 4));
        SCHED();
        {
          const RowNorm n = stat_finish(sc, st, 1, 1.f);
          rs0 = row0 < nvalid ? n.rs0 : 0.f; rs1 = row0 + 8 < nvalid ? n.rs1 : 0.f;
          mean_frag(mu, n, q == 3);
        }
        mma_fold<2 * CS_QKV - 6>(acc[0], mu);
        RELEASE(10, 15);
        WG_WAIT(0); pin(acc[0]);
        scale_pack(acc[0], Q, rs0, rs1);
        tile_store(here(maddr), Q);
        SCHED();
        mma_tile<false>(acc[1], A[2], HI(F_QKV + 3));
        fence_async_smem();
        bar_arrive(BAR_K, 160);
        mma_tile_fold<2 * CS_QKV - 4>(acc[1], A[3], HI(F_QKV + 4), mu);
        mma_tile<false>(acc[2], A[1], HI(F_QKV + 1)); mma_tile<false>(acc[2], A[2], LO(F_QKV + 5));
        WG_WAIT(2); pin(acc[1]);
        scale_pack(acc[1], Q, rs0, rs1);
        tile_store(here(maddr) + TILE_BYTES, Q);
        fence_async_smem();
        bar_arrive(BAR_V, 160);
        mma_tile_fold<2 * CS_QKV - 2>(acc[2], A[3], HI(F_QKV + 5), mu);
        WG_WAIT(0); pin(acc[2]);
        scale_pack(acc[2], Q, rs0 * SM_SCALE_LOG2, rs1 * SM_SCALE_LOG2);
        frag_store(here(qslot), Q);
        bar_arrive(BAR_Q, 256);
        RELEASE(F_QKV, F_QKV + 5);
      } else {
        bar_sync(BAR_Q, 256);
#pragma unroll
        for (int s = 0; s < 4; s++) lds128(qslot + s * 512, Q[4 * s], Q[4 * s + 1], Q[4 * s + 2], Q[4 * s + 3]);
        if (w < 2) {
          const uint32_t v = w ? 0u : 0x3F803F80u;
#pragma unroll
          for (int s = 0; s < 4; s++) sts128(qslot + s * 512, v, v, v, v);
          fence_async_smem();
        }
      }
      bar_sync(BAR_ATT, 256);
      PROF_MARK(7);

      const int dir = cw == 0 ? -1 : 1;
      uint32_t tap[15];
      {
        const uint32_t* dwp = (const uint32_t*)(dw + 64 * r) + lane + 7 * (DM / 2);
#pragma unroll
        for (int k = 0; k < 15; k++) tap[k] = __ldg(dwp + dir * (k - 7) * (DM / 2));
      }

      float O[36];
      {
        float S[2][32];
        uint32_t P[2][16], nm[4];
#pragma unroll
        for (int i = 0; i < 32; i++) { S[0][i] = 0.f; S[1][i] = 0.f; }
        pin(Q); pin(S[0]);
        WG_FENCE();
        qk_tile(S[0], Q, RING_K + (SM_STG >> 4));
        WG_COMMIT();
#pragma unroll
        for (int i = 0; i < 36; i++) O[i] = 0.f;
#pragma unroll
        for (int i = 0; i < 16; i++) P[1][i] = 0u;
        WG_WAIT(0); pin(S[0]);
        const float m0 = tile_max<0>(S[0]), m1 = tile_max<2>(S[0]);
        nm[0] = pack2(q ? 0.f : -m0, 0.f); nm[1] = pack2(q ? 0.f : -m1, 0.f); nm[2] = 0u; nm[3] = 0u;
#pragma unroll
        for (int k = 0; k < 15; k++) asm("mul.rn.bf16x2 %0, %0, %1;" : "+r"(tap[k]) : "r"(0x3F003F00u));
        pin(nm); pin(O); pin(P[1]); pin(tap);
        uint32_t sk = wg, sv = F_SPARE % NSTAGE + wg;
        mbar_wait(SM_BASE + SM_FULL + sv * 8, 1);
        mbar_wait(SM_BASE + SM_FULL + sk * 8, 0);
        PROF_MARK(8);
        WG_FENCE();
        qk_tile(S[0], Q, RING_K + sk * 1024);
        qk_shift(S[0], nm);
        WG_COMMIT();
        WG_WAIT(0); pin(S[0]); pin(S[1]);
#pragma unroll 1
        for (int it = 0; it < 4; it++) {
          const uint32_t sn = it >= 2 ? wg : sk + 4;
          uint32_t ok = 1;
          mbar_probe(ok, SM_BASE + SM_FULL + sn * 8, it >= 2);
          mbar_probe(ok, SM_BASE + SM_FULL + (sk + 2) * 8, it == 3);
          attn_step(S[0], S[1], P[0], P[1], O, Q, nm, RING_K + sk * 1024 + 512, RING_V + (sv * 1024 + 512) * V_STEP, true, it > 0);
          PROF_MARK(24 + it * 3);
          if (__builtin_expect(!ok, 0)) {
            mbar_wait(SM_BASE + SM_FULL + sn * 8, it >= 2);
            mbar_wait(SM_BASE + SM_FULL + (sk + 2) * 8, it == 3);
          }
          WG_WAIT(0); pin(O); pin(S[1]); pin(P[1]);
          asm volatile("{\n.reg .pred p;\nsetp.eq.u32 p, %2, 0;\n@p mbarrier.arrive.shared::cta.b64 _, [%0];\n@p mbarrier.arrive.shared::cta.b64 _, [%1];\n}"
                       :: "r"(SM_BASE + SM_EMPTY + sk * 8), "r"(SM_BASE + SM_EMPTY + sv * 8), "r"(lane) : "memory");
          PROF_MARK(25 + it * 3);
          sv = sk + 2; sk = sn;
          attn_step(S[1], S[0], P[1], P[0], O, Q, nm, RING_K + sk * 1024, RING_V + (sv * 1024) * V_STEP, it < 3, true);
          WG_WAIT(0); pin(O); pin(S[0]); pin(P[0]);
          PROF_MARK(26 + it * 3);
        }
        WG_FENCE();
        pv_tile(O, P[1], RING_V + (sv * 1024 + 512) * V_STEP, wg << 22);
        WG_COMMIT();
        WG_WAIT(0); pin(O);
      }
      PROF_MARK(9);

      {
        const uint32_t mo = stg + here(th) * 16;
        sts64(mo + 5 * 4096 + wg * 8, __float_as_uint(O[32]), __float_as_uint(O[34]));
        if (wg == 0) {
#pragma unroll
          for (int i = 4; i < 8; i++)
            sts128(mo + i * 2048, __float_as_uint(O[4 * i]), __float_as_uint(O[4 * i + 1]), __float_as_uint(O[4 * i + 2]), __float_as_uint(O[4 * i + 3]));
        } else {
#pragma unroll
          for (int i = 0; i < 4; i++)
            sts128(mo + i * 2048, __float_as_uint(O[4 * i]), __float_as_uint(O[4 * i + 1]), __float_as_uint(O[4 * i + 2]), __float_as_uint(O[4 * i + 3]));
#pragma unroll
          for (int i = 0; i < 16; i++) O[i] = O[16 + i];
        }
        bar_sync(BAR_MERGE, 256);
        announce(sc, tid == 0);
        uint32_t e[4];
        lds128(mo + 5 * 4096, e[0], e[1], e[2], e[3]);
        O[32] = __uint_as_float(e[0]) + __uint_as_float(e[2]); O[34] = __uint_as_float(e[1]) + __uint_as_float(e[3]);
#pragma unroll
        for (int i = 0; i < 4; i++) {
          lds128(mo + wg * TILE_BYTES + i * 2048, e[0], e[1], e[2], e[3]);
#pragma unroll
          for (int k = 0; k < 4; k++) O[4 * i + k] += __uint_as_float(e[k]);
        }
        const bool safe = O[32] > 0x1p-60f && O[32] < 0x1p60f && O[34] > 0x1p-60f && O[34] < 0x1p60f;
        if (__builtin_expect(__any_sync(0xffffffffu, !safe), 0)) attention_exact(O, Q, sc, batch * 4 + r, lane, wg);
        const float i0 = rcp_hw(O[32]), i1 = rcp_hw(O[34]);
#pragma unroll
        for (int i = 0; i < 8; i++) { const float v = (i & 1) ? i1 : i0; A[0][i] = pack2(O[2 * i] * v, O[2 * i + 1] * v); }
        A[0][0] &= ~1u; A[0][4] &= ~1u;
        uint4* dst = xp + X_AG1 + wg * 256;
        SCHED();
        st_vec(dst, A[0][0], A[0][1], A[0][2], A[0][3]);
        st_vec(dst + 128, A[0][4], A[0][5], A[0][6], A[0][7]);
        SCHED();
      }
      if (wg == 1) {
        const uint32_t mo = stg + TILE_BYTES + here(th) * 16;
        sts128(mo, A[0][0], A[0][1], A[0][2], A[0][3]);
        sts128(mo + 2048, A[0][4], A[0][5], A[0][6], A[0][7]);
        bar_arrive(BAR_HALF, 256);
      } else {
        PROF_MARK(10);
        const uint32_t mo = stg + TILE_BYTES + here(th) * 16;
        bar_sync(BAR_HALF, 256);
        lds128(mo, A[0][8], A[0][9], A[0][10], A[0][11]);
        lds128(mo + 2048, A[0][12], A[0][13], A[0][14], A[0][15]);
        proj_residual<F_WO, 6>(A, sc, xp, maddr, 0, lane);
        PROF_MARK(12);
        float acc[2][32];
        mma_tile<true>(acc[0], A[0], LO(F_PW1)); mma_tile<true>(acc[1], A[0], HI(F_PW1));
        gather_first<1, X_AG0>(A, st, sc, xp, 0);
        mma_tile<false>(acc[1], A[1], HI(F_PW1 + 1)); mma_tile<false>(acc[0], A[1], LO(F_PW1 + 1));
        gather_rest<1, X_AG0>(A, xp, 0);
        PROF_MARK(13);
        mma_tile<false>(acc[1], A[2], HI(F_PW1 + 2)); mma_tile<false>(acc[1], A[3], HI(F_PW1 + 3));
        WG_WAIT(2);
        RELEASE(F_WO, F_PW1 + 1);
        SCHED();
        uint32_t mu[4];
        const RowNorm n = stat_finish(sc, st, 0, 0.5f);
        const float rs0 = row0 < nvalid ? n.rs0 : 0.f, rs1 = row0 + 8 < nvalid ? n.rs1 : 0.f;
        mean_frag(mu, n, q == 0);
        mma_fold<2 * CS_PW1 + 2>(acc[1], mu);
        mma_tile<false>(acc[0], A[2], LO(F_PW1 + 2));
        mma_tile_fold<2 * CS_PW1>(acc[0], A[3], LO(F_PW1 + 3), mu);
        WG_WAIT(2); pin(acc[1]);
#pragma unroll
        for (int i = 0; i < 32; i++) acc[1][i] = tanh_hw(acc[1][i] * ((i & 2) ? rs1 : rs0));
#pragma unroll
        for (int i = 0; i < 32; i++) { const float rs = (i & 2) ? rs1 : rs0; acc[1][i] = fmaf(acc[1][i], rs, rs); }
        pin(acc[1]);
        SCHED();
        WG_WAIT(0); pin(acc[0]);
#pragma unroll
        for (int i = 0; i < 16; i++) A[0][i] = pack2(acc[0][2 * i] * acc[1][2 * i], acc[0][2 * i + 1] * acc[1][2 * i + 1]);
        const uint32_t ga = stg + TILE_BYTES + here(mrow) * G_PITCH + (lane >> 4) * 16;
#pragma unroll
        for (int s = 0; s < 4; s++) stsm4(ga + s * 32, &A[0][4 * s]);
      }
      {
        const uint32_t gsrc = stg + TILE_BYTES + (8 * cw - 7) * G_PITCH + lane * 4;
        const bool edge = cw == 0 || cw == 7;
        const bool nbr = cw == 0 ? t > 0 : t < 15;
        uint4* const hdst = &sc->x[b + 4 * dir][X_HALO + (cw == 0 ? 96 : 0) + lane];
        uint32_t in[22];
        bar_sync(BAR_G, 256);
        PROF_MARK(14);
        if (cw == 0) {
#pragma unroll
          for (int i = 14; i >= 0; i--) in[i] = lds32(gsrc + (21 - i) * G_PITCH);
        } else {
#pragma unroll
          for (int i = 14; i >= 0; i--) in[i] = lds32(gsrc + i * G_PITCH);
        }
        if (edge) {
          if (nbr) {
            st_vec(hdst, HALO_TAG, in[14], in[13], in[12]);
            st_vec(hdst + 32, HALO_TAG, in[11], in[10], in[9]);
            st_vec(hdst + 64, HALO_TAG, in[8], 0u, 0u);
          }
        } else {
#pragma unroll
          for (int i = 15; i < 22; i++) in[i] = lds32(gsrc + i * G_PITCH);
        }
        if (cw == 0) PROF_MARK0(40);
        uint32_t cv[8];
#pragma unroll
        for (int i = 0; i < 15; i++)
#pragma unroll
          for (int o = 0; o < 8; o++) {
            if (i == o) asm("mul.rn.bf16x2 %0, %1, %2;" : "=r"(cv[o]) : "r"(in[i]), "r"(tap[0]));
            if (i > o) asm("fma.rn.bf16x2 %0, %1, %2, %0;" : "+r"(cv[o]) : "r"(in[i]), "r"(tap[i - o]));
          }
        pin(cv);
        if (cw == 0) PROF_MARK0(41);
        if (edge) {
#pragma unroll
          for (int i = 15; i < 22; i++) in[i] = 0u;
          if (nbr) {
            const uint4* src = &sc->x[b][X_HALO + (cw == 0 ? 0 : 96) + lane];
            uint32_t e0, e1, e2, u0, u1, spin = 0;
#pragma unroll 1
            do {
              ld_vec(src, e0, in[15], in[16], in[17]);
              ld_vec(src + 32, e1, in[18], in[19], in[20]);
              ld_vec(src + 64, e2, in[21], u0, u1);
            } while (__any_sync(0xffffffffu, ((e0 ^ HALO_TAG) | (e1 ^ HALO_TAG) | (e2 ^ HALO_TAG)) != 0) && ++spin < SPIN_LIMIT);
          }
        }
#pragma unroll
        for (int i = 15; i < 22; i++)
#pragma unroll
          for (int o = 0; o < 8; o++)
            if (i - o <= 14) asm("fma.rn.bf16x2 %0, %1, %2, %0;" : "+r"(cv[o]) : "r"(in[i]), "r"(tap[i - o]));
        if (cw == 0) PROF_MARK0(42);
        if (cw == 7) PROF_MARK0(43);
        const uint32_t fl = cw == 0 ? 7 : 0;
        const uint32_t cdst = (stg + cw * 1024 + lane * 4) ^ (fl * 144);
#pragma unroll
        for (int o = 0; o < 8; o++) {
          const float a = bf_lo(cv[o]), c = bf_hi(cv[o]);
          sts32(cdst ^ (o * 144), pack2(fmaf(a, tanh_hw(a), a), fmaf(c, tanh_hw(c), c)));
        }
      }
      if (wg == 1) {
        bar_arrive(BAR_C, 256);
        break;
      }
      bar_sync(BAR_C, 256);
      announce(sc, tid == 0);
      tile_load(here(maddr), A[0]);
      PROF_MARK(15);
      publish(xp + X_AG1, A[0], 1);
      proj_residual<F_PW2, 2>(A, sc, xp, maddr, 1, lane);
      PROF_MARK(17);
    }
  }
}

typedef CUresult (*EncodeFn)(CUtensorMap*, CUtensorMapDataType, cuuint32_t, void*, const cuuint64_t*, const cuuint64_t*,
                             const cuuint32_t*, const cuuint32_t*, CUtensorMapInterleave, CUtensorMapSwizzle,
                             CUtensorMapL2promotion, CUtensorMapFloatOOBfill);

void make_map(EncodeFn fn, CUtensorMap* m, const void* w, int rows, int cols, CUtensorMapSwizzle swz) {
  const cuuint64_t dims[2] = {(cuuint64_t)cols, (cuuint64_t)rows}, strides[1] = {(cuuint64_t)cols * 2};
  const cuuint32_t box[2] = {64, 64}, es[2] = {1, 1};
  fn(m, CU_TENSOR_MAP_DATA_TYPE_BFLOAT16, 2, const_cast<void*>(w), dims, strides, box, es, CU_TENSOR_MAP_INTERLEAVE_NONE,
     swz, CU_TENSOR_MAP_L2_PROMOTION_L2_128B, CU_TENSOR_MAP_FLOAT_OOB_FILL_NONE);
}

}

extern "C" void kernel_launch(void* const* d_in, const int* in_sizes, int n_in, void* d_out, int out_size) {
  static EncodeFn fn = nullptr;
  static Scratch* sc = nullptr;
  if (!fn) {
    void* f = nullptr;
    cudaDriverEntryPointQueryResult st;
    cudaGetDriverEntryPoint("cuTensorMapEncodeTiled", &f, cudaEnableDefault, &st);
    fn = (EncodeFn)f;
    void* raw = nullptr;
    cudaGetSymbolAddress(&raw, g_scratch);
    sc = (Scratch*)(((uintptr_t)raw + X_ALIGN - 1) & ~(uintptr_t)(X_ALIGN - 1));
    cudaFuncSetAttribute(conformer_kernel, cudaFuncAttributeMaxDynamicSharedMemorySize, SM_TOTAL);
  }
  typedef const __nv_bfloat16* W;
  const CUtensorMapSwizzle S = CU_TENSOR_MAP_SWIZZLE_128B;
  Params p;
  {
    const cuuint64_t dims[3] = {DM, T_SEQ, 2}, strides[2] = {DM * 2, T_SEQ * DM * 2};
    const cuuint32_t box[3] = {64, 64, 1}, es[3] = {1, 1, 1};
    fn(&p.map[M_X], CU_TENSOR_MAP_DATA_TYPE_BFLOAT16, 3, d_in[0], dims, strides, box, es, CU_TENSOR_MAP_INTERLEAVE_NONE, S,
       CU_TENSOR_MAP_L2_PROMOTION_L2_128B, CU_TENSOR_MAP_FLOAT_OOB_FILL_NONE);
  }
  make_map(fn, &p.map[M_FF1A], d_in[1], 256, 1024, S);
  make_map(fn, &p.map[M_FF1B], d_in[2], 1024, 256, S);
  make_map(fn, &p.map[M_QKV], d_in[3], 256, 768, S);
  make_map(fn, &p.map[M_WO], d_in[4], 256, 256, S);
  make_map(fn, &p.map[M_PW1], d_in[5], 256, 512, S);
  make_map(fn, &p.map[M_PW2], d_in[7], 256, 256, S);
  make_map(fn, &p.map[M_FF2A], d_in[8], 256, 1024, S);
  make_map(fn, &p.map[M_FF2B], d_in[9], 1024, 256, S);
  p.w_ff1b = (W)d_in[2]; p.w_qkv = (W)d_in[3]; p.w_o = (W)d_in[4]; p.w_pw1 = (W)d_in[5];
  p.w_pw2 = (W)d_in[7]; p.w_ff2a = (W)d_in[8]; p.w_ff2b = (W)d_in[9];

  cudaLaunchConfig_t cfg = {};
  cfg.gridDim = dim3(NCTA);
  cfg.blockDim = dim3(384);
  cfg.dynamicSmemBytes = SM_TOTAL;
  cfg.stream = cudaStreamPerThread;
  cudaLaunchAttribute at[1];
  at[0].id = cudaLaunchAttributeCooperative;
  at[0].val.cooperative = 1;
  cfg.attrs = at;
  cfg.numAttrs = 1;
  cudaLaunchKernelEx(&cfg, conformer_kernel, sc, (__nv_bfloat16*)d_out, (W)d_in[6], (W)d_in[0], (W)d_in[1], p);
}
```

```cpp
#include <cuda_runtime.h>
#include <cuda_bf16.h>
#include <cuda.h>
#include <stdint.h>

namespace {

constexpr int T_SEQ = 1000;
constexpr int DM = 256;
constexpr int NCTA = 128;
constexpr int NSTAGE = 12;
constexpr uint32_t STAGE_BYTES = 16384;
constexpr uint32_t TILE_BYTES = 8192;
constexpr uint32_t SM_BASE = 1024;
constexpr uint32_t SM_STG = NSTAGE * STAGE_BYTES;
constexpr uint32_t SM_FULL = SM_STG + 32768;
constexpr uint32_t SM_EMPTY = SM_FULL + 96;
constexpr uint32_t SM_XBAR = SM_FULL + 192;
constexpr uint32_t SM_EYE = SM_FULL + 256;
constexpr uint32_t SM_ONE = SM_FULL + 640;
constexpr uint32_t SM_CS = SM_FULL + 768;
constexpr uint32_t SM_TOTAL = SM_FULL + 3072;
constexpr int CS_FF2 = 0, CS_PW1 = 4, CS_QKV = 6;
constexpr uint32_t SPIN_LIMIT = 1u << 16;
constexpr float LN_EPS = 1e-5f;
constexpr float SM_SCALE_LOG2 = 0.125f * 1.4426950408889634f;
constexpr uint32_t G_PITCH = 144;
#define PF_AT 4
#define CLR_PACE 60

constexpr int F_QKV = 16, F_SPARE = 22, F_KV = 24, F_WO = 40, F_PW1 = 42, F_PW2 = 46, F_TOTAL = 64;
enum { M_FF1A, M_FF1B, M_QKV, M_WO, M_PW1, M_PW2, M_FF2A, M_FF2B, M_X, M_COUNT };
enum { BAR_K = 1, BAR_V, BAR_Q, BAR_MERGE, BAR_G, BAR_C, BAR_WG1, BAR_GO, BAR_CS, BAR_ATT, BAR_INIT, BAR_HALF };

struct Params {
  CUtensorMap map[M_COUNT];
  const __nv_bfloat16 *w_ff1b, *w_qkv, *w_o, *w_pw1, *w_pw2, *w_ff2a, *w_ff2b;
};

constexpr int X_RS = 0, X_AG1 = X_RS, X_HALO = X_RS + 512, X_AG0 = 1536, X_ST = 2048, X_SIZE = 4096;
constexpr uint32_t HALO_TAG = 0xFFFF0001u;
struct Scratch {
  uint4 x[NCTA][X_SIZE];
  uint4 kv[8][2][16][512];
  uint4 cs[576];
  uint32_t flag[8][32][32];
  uint32_t step[NCTA][32];
};
constexpr size_t X_ALIGN = 4 * X_SIZE * sizeof(uint4);
__device__ uint8_t g_scratch[sizeof(Scratch) + X_ALIGN];
#define PROF_TIME(i)
#define PROF_MARK(i)
#define PROF_MARK2(i, j)
#define PROF_MARK0(i)
#define PROF_AT(a)

__device__ __forceinline__ void mbar_init(uint32_t bar, uint32_t cnt) {
  asm volatile("mbarrier.init.shared::cta.b64 [%0], %1;" :: "r"(bar), "r"(cnt) : "memory");
}
__device__ __forceinline__ void mbar_wait(uint32_t bar, uint32_t parity) {
  asm volatile("{\n.reg .pred p;\n.reg .u32 c;\nmov.u32 c, 0;\n"
               "WAIT_LOOP:\nmbarrier.try_wait.parity.shared::cta.b64 p, [%0], %1;\n@p bra WAIT_DONE;\n"
               "add.u32 c, c, 1;\nsetp.lt.u32 p, c, %2;\n@p bra WAIT_LOOP;\nWAIT_DONE:\n}"
               :: "r"(bar), "r"(parity), "n"(SPIN_LIMIT) : "memory");
}
__device__ __forceinline__ void mbar_arrive(uint32_t bar) {
  asm volatile("mbarrier.arrive.shared::cta.b64 _, [%0];" :: "r"(bar) : "memory");
}
#define bar_sync(id, n) asm volatile("bar.sync %0, %1;" :: "n"((int)(id)), "n"(n) : "memory")
#define bar_arrive(id, n) asm volatile("bar.arrive %0, %1;" :: "n"((int)(id)), "n"(n) : "memory")
__device__ __forceinline__ void fence_async_smem() { asm volatile("fence.proxy.async.shared::cta;" ::: "memory"); }

__device__ __forceinline__ void st_vec(uint4* p, uint32_t a, uint32_t b, uint32_t c, uint32_t d) {
  asm volatile("{\n.reg .b128 v;\n.reg .b64 lo, hi;\nmov.b64 lo, {%1, %2};\nmov.b64 hi, {%3, %4};\nmov.b128 v, {lo, hi};\n"
               "st.relaxed.gpu.global.b128 [%0], v;\n}" :: "l"(p), "r"(a), "r"(b), "r"(c), "r"(d) : "memory");
}
__device__ __forceinline__ void ld_vec(const uint4* p, uint32_t& a, uint32_t& b, uint32_t& c, uint32_t& d) {
  asm volatile("{\n.reg .b128 v;\n.reg .b64 lo, hi;\nld.relaxed.gpu.global.b128 v, [%4];\nmov.b128 {lo, hi}, v;\n"
               "mov.b64 {%0, %1}, lo;\nmov.b64 {%2, %3}, hi;\n}" : "=r"(a), "=r"(b), "=r"(c), "=r"(d) : "l"(p) : "memory");
}
__device__ __forceinline__ void sts128(uint32_t a, uint32_t x, uint32_t y, uint32_t z, uint32_t w) {
  asm volatile("st.shared.v4.u32 [%0], {%1, %2, %3, %4};" :: "r"(a), "r"(x), "r"(y), "r"(z), "r"(w) : "memory");
}
__device__ __forceinline__ void lds128(uint32_t a, uint32_t& x, uint32_t& y, uint32_t& z, uint32_t& w) {
  asm volatile("ld.shared.v4.u32 {%0, %1, %2, %3}, [%4];" : "=r"(x), "=r"(y), "=r"(z), "=r"(w) : "r"(a) : "memory");
}
__device__ __forceinline__ uint32_t lds32(uint32_t a) {
  uint32_t x; asm volatile("ld.shared.u32 %0, [%1];" : "=r"(x) : "r"(a) : "memory"); return x;
}
__device__ __forceinline__ void sts32(uint32_t a, uint32_t x) { asm volatile("st.shared.u32 [%0], %1;" :: "r"(a), "r"(x) : "memory"); }
__device__ __forceinline__ void sts64(uint32_t a, uint32_t x, uint32_t y) {
  asm volatile("st.shared.v2.u32 [%0], {%1, %2};" :: "r"(a), "r"(x), "r"(y) : "memory");
}
__device__ __forceinline__ void stsm4(uint32_t a, const uint32_t* r) {
  asm volatile("stmatrix.sync.aligned.m8n8.x4.shared.b16 [%0], {%1, %2, %3, %4};" :: "r"(a), "r"(r[0]), "r"(r[1]), "r"(r[2]), "r"(r[3]) : "memory");
}
__device__ __forceinline__ void ldsm4(uint32_t a, uint32_t* r) {
  asm volatile("ldmatrix.sync.aligned.m8n8.x4.shared.b16 {%0, %1, %2, %3}, [%4];" : "=r"(r[0]), "=r"(r[1]), "=r"(r[2]), "=r"(r[3]) : "r"(a) : "memory");
}
__device__ __forceinline__ uint32_t pack2(float lo, float hi) {
  uint32_t r; asm("cvt.rn.bf16x2.f32 %0, %1, %2;" : "=r"(r) : "f"(hi), "f"(lo)); return r;
}
__device__ __forceinline__ float bf_lo(uint32_t w) { return __uint_as_float(w << 16); }
__device__ __forceinline__ float bf_hi(uint32_t w) { return __uint_as_float(w & 0xffff0000u); }
__device__ __forceinline__ float tanh_hw(float x) { float y; asm volatile("tanh.approx.f32 %0, %1;" : "=f"(y) : "f"(x)); return y; }
__device__ __forceinline__ float rcp_hw(float x) { float y; asm("rcp.approx.ftz.f32 %0, %1;" : "=f"(y) : "f"(x)); return y; }
__device__ __forceinline__ float rsqrt_hw(float x) { float y; asm("rsqrt.approx.ftz.f32 %0, %1;" : "=f"(y) : "f"(x)); return y; }
__device__ __forceinline__ float ex2_hw(float x) { float y; asm("ex2.approx.ftz.f32 %0, %1;" : "=f"(y) : "f"(x)); return y; }

__device__ __forceinline__ uint32_t here(uint32_t v) { asm volatile("" : "+r"(v)); return v; }

#define SCHED() asm volatile("pmevent 1;" ::: "memory")
#define WG_FENCE() asm volatile("wgmma.fence.sync.aligned;" ::: "memory")
#define WG_COMMIT() asm volatile("wgmma.commit_group.sync.aligned;" ::: "memory")
#define WG_WAIT(n) asm volatile("wgmma.wait_group.sync.aligned %0;" :: "n"(n) : "memory")

template <int N> __device__ __forceinline__ void pin(float (&d)[N]) {
#pragma unroll
  for (int i = 0; i < N; i++) asm volatile("" : "+f"(d[i]) :: "memory");
}
template <int N> __device__ __forceinline__ void pin(uint32_t (&d)[N]) {
#pragma unroll
  for (int i = 0; i < N; i++) asm volatile("" : "+r"(d[i]) :: "memory");
}

#define WG_D32 "{%0, %1, %2, %3, %4, %5, %6, %7, %8, %9, %10, %11, %12, %13, %14, %15, %16, %17, %18, %19, %20, %21, %22, %23, %24, %25, %26, %27, %28, %29, %30, %31}"
template <int TB> __device__ __forceinline__ void wgmma64_acc(float (&d)[32], const uint32_t* a, uint64_t db) {
  asm volatile("wgmma.mma_async.sync.aligned.m64n64k16.f32.bf16.bf16 " WG_D32 ", {%32, %33, %34, %35}, %36, 1, 1, 1, %37;"
    : "+f"(d[0]), "+f"(d[1]), "+f"(d[2]), "+f"(d[3]), "+f"(d[4]), "+f"(d[5]), "+f"(d[6]), "+f"(d[7]),
      "+f"(d[8]), "+f"(d[9]), "+f"(d[10]), "+f"(d[11]), "+f"(d[12]), "+f"(d[13]), "+f"(d[14]), "+f"(d[15]),
      "+f"(d[16]), "+f"(d[17]), "+f"(d[18]), "+f"(d[19]), "+f"(d[20]), "+f"(d[21]), "+f"(d[22]), "+f"(d[23]),
      "+f"(d[24]), "+f"(d[25]), "+f"(d[26]), "+f"(d[27]), "+f"(d[28]), "+f"(d[29]), "+f"(d[30]), "+f"(d[31])
    : "r"(a[0]), "r"(a[1]), "r"(a[2]), "r"(a[3]), "l"(db), "n"(TB));
}
template <int TB> __device__ __forceinline__ void wgmma64_reuse(float (&d)[32], const uint32_t* a, uint64_t db, uint32_t zero) {
  asm volatile("{\n.reg .pred p;\nsetp.ne.u32 p, %37, 0;\nwgmma.mma_async.sync.aligned.m64n64k16.f32.bf16.bf16 " WG_D32 ", {%32, %33, %34, %35}, %36, p, 1, 1, %38;\n}"
    : "+f"(d[0]), "+f"(d[1]), "+f"(d[2]), "+f"(d[3]), "+f"(d[4]), "+f"(d[5]), "+f"(d[6]), "+f"(d[7]),
      "+f"(d[8]), "+f"(d[9]), "+f"(d[10]), "+f"(d[11]), "+f"(d[12]), "+f"(d[13]), "+f"(d[14]), "+f"(d[15]),
      "+f"(d[16]), "+f"(d[17]), "+f"(d[18]), "+f"(d[19]), "+f"(d[20]), "+f"(d[21]), "+f"(d[22]), "+f"(d[23]),
      "+f"(d[24]), "+f"(d[25]), "+f"(d[26]), "+f"(d[27]), "+f"(d[28]), "+f"(d[29]), "+f"(d[30]), "+f"(d[31])
    : "r"(a[0]), "r"(a[1]), "r"(a[2]), "r"(a[3]), "l"(db), "r"(zero), "n"(TB));
}
template <int TB> __device__ __forceinline__ void wgmma64_set(float (&d)[32], const uint32_t* a, uint64_t db) {
  asm volatile("wgmma.mma_async.sync.aligned.m64n64k16.f32.bf16.bf16 " WG_D32 ", {%32, %33, %34, %35}, %36, 0, 1, 1, %37;"
    : "=f"(d[0]), "=f"(d[1]), "=f"(d[2]), "=f"(d[3]), "=f"(d[4]), "=f"(d[5]), "=f"(d[6]), "=f"(d[7]),
      "=f"(d[8]), "=f"(d[9]), "=f"(d[10]), "=f"(d[11]), "=f"(d[12]), "=f"(d[13]), "=f"(d[14]), "=f"(d[15]),
      "=f"(d[16]), "=f"(d[17]), "=f"(d[18]), "=f"(d[19]), "=f"(d[20]), "=f"(d[21]), "=f"(d[22]), "=f"(d[23]),
      "=f"(d[24]), "=f"(d[25]), "=f"(d[26]), "=f"(d[27]), "=f"(d[28]), "=f"(d[29]), "=f"(d[30]), "=f"(d[31])
    : "r"(a[0]), "r"(a[1]), "r"(a[2]), "r"(a[3]), "l"(db), "n"(TB));
}

__device__ __forceinline__ void wgmma72_acc(float (&d)[36], const uint32_t* a, uint64_t db) {
  asm volatile("wgmma.mma_async.sync.aligned.m64n72k16.f32.bf16.bf16 {%0, %1, %2, %3, %4, %5, %6, %7, %8, %9, %10, %11, %12, %13, %14, %15, %16, %17, %18, %19, %20, %21, %22, %23, %24, %25, %26, %27, %28, %29, %30, %31, %32, %33, %34, %35}, {%36, %37, %38, %39}, %40, 1, 1, 1, 1;"
    : "+f"(d[0]), "+f"(d[1]), "+f"(d[2]), "+f"(d[3]), "+f"(d[4]), "+f"(d[5]), "+f"(d[6]), "+f"(d[7]), "+f"(d[8]),
      "+f"(d[9]), "+f"(d[10]), "+f"(d[11]), "+f"(d[12]), "+f"(d[13]), "+f"(d[14]), "+f"(d[15]), "+f"(d[16]), "+f"(d[17]),
      "+f"(d[18]), "+f"(d[19]), "+f"(d[20]), "+f"(d[21]), "+f"(d[22]), "+f"(d[23]), "+f"(d[24]), "+f"(d[25]), "+f"(d[26]),
      "+f"(d[27]), "+f"(d[28]), "+f"(d[29]), "+f"(d[30]), "+f"(d[31]), "+f"(d[32]), "+f"(d[33]), "+f"(d[34]), "+f"(d[35])
    : "r"(a[0]), "r"(a[1]), "r"(a[2]), "r"(a[3]), "l"(db));
}
__device__ __forceinline__ void wgmma16_acc(float* d, const uint32_t* a, uint64_t db) {
  asm volatile("wgmma.mma_async.sync.aligned.m64n16k16.f32.bf16.bf16 {%0, %1, %2, %3, %4, %5, %6, %7}, {%8, %9, %10, %11}, %12, 1, 1, 1, 0;"
    : "+f"(d[0]), "+f"(d[1]), "+f"(d[2]), "+f"(d[3]), "+f"(d[4]), "+f"(d[5]), "+f"(d[6]), "+f"(d[7])
    : "r"(a[0]), "r"(a[1]), "r"(a[2]), "r"(a[3]), "l"(db));
}
__device__ __forceinline__ void hmma(float (&d)[4], const uint32_t* a, uint32_t b0, uint32_t b1) {
  asm("mma.sync.aligned.m16n8k16.row.col.f32.bf16.bf16.f32 {%0, %1, %2, %3}, {%4, %5, %6, %7}, {%8, %9}, {%0, %1, %2, %3};"
    : "+f"(d[0]), "+f"(d[1]), "+f"(d[2]), "+f"(d[3]) : "r"(a[0]), "r"(a[1]), "r"(a[2]), "r"(a[3]), "r"(b0), "r"(b1));
}

__device__ __forceinline__ void hmma8(float (&d)[4], const uint32_t* a, uint32_t b0) {
  asm("mma.sync.aligned.m16n8k8.row.col.f32.bf16.bf16.f32 {%0, %1, %2, %3}, {%4, %5}, {%6}, {%0, %1, %2, %3};"
    : "+f"(d[0]), "+f"(d[1]), "+f"(d[2]), "+f"(d[3]) : "r"(a[0]), "r"(a[1]), "r"(b0));
}

template <bool FIRST> __device__ __forceinline__ void mma_tile(float (&d)[32], const uint32_t (&a)[16], uint64_t db) {
  WG_FENCE();
#pragma unroll
  for (int s = 0; s < 4; s++) {
    if (FIRST && s == 0) wgmma64_set<1>(d, &a[0], db); else wgmma64_acc<1>(d, &a[4 * s], db + s * 128);
  }
  WG_COMMIT();
}
__device__ __forceinline__ void mma_tile_reuse(float (&d)[32], const uint32_t (&a)[16], uint64_t db) {
  WG_FENCE();
  wgmma64_reuse<1>(d, &a[0], db, blockIdx.y);
#pragma unroll
  for (int s = 1; s < 4; s++) wgmma64_acc<1>(d, &a[4 * s], db + s * 128);
  WG_COMMIT();
}
template <int ROW> __device__ __forceinline__ void fold_step(float (&d)[32], const uint32_t (&mu)[4]) {
  wgmma64_acc<1>(d, mu, (uint64_t)((SM_BASE + SM_CS + ROW * 128) >> 4) | (uint64_t(1) << 16) | (uint64_t(1) << 62));
}
template <int ROW> __device__ __forceinline__ void mma_fold(float (&d)[32], const uint32_t (&mu)[4]) {
  WG_FENCE();
  fold_step<ROW>(d, mu);
  WG_COMMIT();
}
template <int ROW> __device__ __forceinline__ void mma_tile_fold(float (&d)[32], const uint32_t (&a)[16], uint64_t db, const uint32_t (&mu)[4]) {
  WG_FENCE();
#pragma unroll
  for (int s = 0; s < 4; s++) wgmma64_acc<1>(d, &a[4 * s], db + s * 128);
  fold_step<ROW>(d, mu);
  WG_COMMIT();
}
__device__ __forceinline__ void mma_add_half(float (&d)[32], const uint32_t (&a)[16]) {
  const uint64_t db = (uint64_t)((SM_BASE + SM_EYE) >> 4) | (uint64_t(8) << 16) | (uint64_t(8) << 32);
  WG_FENCE();
#pragma unroll
  for (int s = 0; s < 4; s++) wgmma16_acc(&d[8 * s], &a[4 * s], db);
  WG_COMMIT();
}
#define ACQUIRE(f) mbar_wait(SM_BASE + SM_FULL + ((f) % NSTAGE) * 8, ((f) / NSTAGE) & 1)
__device__ __forceinline__ void mbar_probe(uint32_t& ok, uint32_t bar, uint32_t parity) {
  asm volatile("{\n.reg .pred p;\nmbarrier.test_wait.parity.shared::cta.b64 p, [%1], %2;\nselp.u32 %0, %0, 0, p;\n}"
               : "+r"(ok) : "r"(bar), "r"(parity) : "memory");
}
template <int F, int N> __device__ __forceinline__ uint32_t probe_n() {
  static_assert(F % NSTAGE + N <= NSTAGE, "stages must not wrap");
  uint32_t ok = 1;
#pragma unroll
  for (int i = 0; i < N; i++) mbar_probe(ok, SM_BASE + SM_FULL + (F % NSTAGE + i) * 8, (F / NSTAGE) & 1);
  return ok;
}
template <int F, int N> __device__ __forceinline__ void settle_n(uint32_t ok) {
  if (__builtin_expect(!ok, 0)) {
#pragma unroll 1
    for (int i = 0; i < N; i++) mbar_wait(SM_BASE + SM_FULL + (F % NSTAGE + i) * 8, (F / NSTAGE) & 1);
  }
}
template <int F, int N> __device__ __forceinline__ void acquire_n() { settle_n<F, N>(probe_n<F, N>()); }
#define RELEASE(f0, f1) do { if (lane == 0) { _Pragma("unroll") for (int f_ = (f0); f_ <= (f1); f_++) mbar_arrive(SM_BASE + SM_EMPTY + (f_ % NSTAGE) * 8); } } while (0)
constexpr uint64_t RING = (uint64_t)(SM_BASE >> 4) | (uint64_t(1) << 16) | (uint64_t(64) << 32) | (uint64_t(1) << 62);
#define LO(f) (RING + ((f) % NSTAGE) * 1024)
#define HI(f) (RING + ((f) % NSTAGE) * 1024 + 512)

template <int C> __device__ __forceinline__ uint4* peer(uint4* p) {
  asm volatile("" : "+l"(p));
  return (uint4*)((uintptr_t)p ^ (C * X_SIZE * sizeof(uint4)));
}
__device__ __forceinline__ uint32_t clock_now() { uint32_t c; asm volatile("mov.u32 %0, %%clock;" : "=r"(c) :: "memory"); return c; }
__device__ __forceinline__ void publish(uint4* dst, uint32_t (&a)[16], uint32_t tag) {
#pragma unroll
  for (int s = 0; s < 4; s++) a[4 * s] = (a[4 * s] & ~1u) | tag;
  pin(a);
  SCHED();
#pragma unroll
  for (int s = 0; s < 4; s++) st_vec(dst + s * 128, a[4 * s], a[4 * s + 1], a[4 * s + 2], a[4 * s + 3]);
  SCHED();
}
__device__ __forceinline__ void fetch(const uint4* src, uint32_t (&a)[16]) {
#pragma unroll
  for (int s = 0; s < 4; s++) ld_vec(src + s * 128, a[4 * s], a[4 * s + 1], a[4 * s + 2], a[4 * s + 3]);
}
__device__ __forceinline__ uint32_t miss(const uint32_t (&a)[16], uint32_t tag) {
  return (a[0] ^ tag) | (a[4] ^ tag) | (a[8] ^ tag) | (a[12] ^ tag);
}
__device__ __forceinline__ bool stale(uint32_t v) { return __any_sync(0xffffffffu, here(v) & 1u); }
template <int N = 2> __device__ __forceinline__ void announce(Scratch* sc, bool leader) {
  asm volatile("{\n.reg .pred p;\nsetp.ne.u32 p, %1, 0;\n@p red.relaxed.gpu.global.add.u32 [%0], %2;\n}"
               :: "l"(sc->step[blockIdx.x]), "r"((uint32_t)leader), "n"(N) : "memory");
}
__device__ __forceinline__ uint32_t launch_index(const Scratch* sc) { return *(const volatile uint32_t*)sc->step[blockIdx.x] >> 4; }
__device__ __forceinline__ void stat_fetch(const Scratch* sc, uint32_t (&st)[4]) {
  const uint32_t th = here(threadIdx.x);
  ld_vec(&sc->x[(blockIdx.x & ~3u) + (th & 3)][X_ST + (th >> 2)], st[0], st[1], st[2], st[3]);
}
template <int C, int SLOT> __device__ __forceinline__ void gather_first(uint32_t (&A)[4][16], uint32_t (&st)[4], const Scratch* sc, uint4* xp, uint32_t tag) {
  bar_sync(BAR_GO, 160);
  fetch(peer<1>(xp) + SLOT, A[1]); fetch(peer<2>(xp) + SLOT, A[2]); fetch(peer<3>(xp) + SLOT, A[3]);
  if (SLOT == X_AG0) stat_fetch(sc, st);
  uint32_t spin = 0;
  while (__builtin_expect(stale(miss(A[1], tag) | miss(A[C], tag)), 0) && ++spin < SPIN_LIMIT) {
    fetch(peer<1>(xp) + SLOT, A[1]);
    if (C == 2) fetch(peer<2>(xp) + SLOT, A[2]);
  }
}
template <int C, int SLOT> __device__ __forceinline__ void gather_rest(uint32_t (&A)[4][16], uint4* xp, uint32_t tag) {
  SCHED();
  uint32_t spin = 0;
  while (__builtin_expect(stale(miss(A[C + 1], tag) | miss(A[3], tag)), 0) && ++spin < SPIN_LIMIT) {
    if (C == 1) fetch(peer<2>(xp) + SLOT, A[2]);
    fetch(peer<3>(xp) + SLOT, A[3]);
  }
}
__device__ __forceinline__ void pack_acc(const float (&d)[32], uint32_t (&a)[16]) {
#pragma unroll
  for (int i = 0; i < 16; i++) a[i] = pack2(d[2 * i], d[2 * i + 1]);
}
__device__ __forceinline__ void frag_store(uint32_t slot, const uint32_t (&a)[16]) {
#pragma unroll
  for (int s = 0; s < 4; s++) sts128(slot + s * 512, a[4 * s], a[4 * s + 1], a[4 * s + 2], a[4 * s + 3]);
}
__device__ __forceinline__ void tile_store(uint32_t maddr, const uint32_t (&a)[16]) {
#pragma unroll
  for (int s = 0; s < 4; s++) stsm4(maddr ^ (s << 5), &a[4 * s]);
}
__device__ __forceinline__ void tile_load(uint32_t maddr, uint32_t (&a)[16]) {
#pragma unroll
  for (int s = 0; s < 4; s++) ldsm4(maddr ^ (s << 5), &a[4 * s]);
}

__device__ __forceinline__ void res_load(uint32_t maddr, float (&d)[32]) {
  uint32_t a[16];
  tile_load(here(maddr) + 3 * TILE_BYTES, a);
#pragma unroll
  for (int i = 0; i < 16; i++) { d[2 * i] = bf_lo(a[i]); d[2 * i + 1] = bf_hi(a[i]); }
  pin(d);
}

struct RowAcc { float s[4], u[2][4], v[2][4]; };
__device__ __forceinline__ void row_acc(RowAcc& t, const uint32_t (&a)[16]) {
#pragma unroll
  for (int s = 0; s < 8; s++) {
    if ((s & 1) == 0) hmma(t.s, &a[2 * s], 0x3F803F80u, 0x3F803F80u);
    hmma8(t.u[s & 1], &a[2 * s], a[2 * s]);
    hmma8(t.v[s & 1], &a[2 * s], a[2 * s + 1]);
  }
}
__device__ __forceinline__ float2 row_squares(const RowAcc& t, bool odd) {
  return make_float2(odd ? t.u[0][1] + t.u[1][1] : t.u[0][0] + t.u[1][0], odd ? t.v[0][3] + t.v[1][3] : t.v[0][2] + t.v[1][2]);
}
__device__ __forceinline__ void stat_publish(const uint32_t (&a)[16], Scratch* sc, uint32_t th, uint32_t tag) {
  RowAcc t = {};
  row_acc(t, a);
  const float2 q = row_squares(t, th & 4);
  if ((th & 3) == ((th >> 3) & 3))
    st_vec(&sc->x[blockIdx.x][X_ST + (th >> 2)], (__float_as_uint(t.s[0]) & ~1u) | tag, __float_as_uint(q.x), __float_as_uint(t.s[2]), __float_as_uint(q.y));
}
struct RowNorm { float m0, rs0, m1, rs1; };
__device__ __forceinline__ RowNorm row_norm(float s0, float q0, float s1, float q1, float scale) {
  RowNorm n;
  n.m0 = s0 * (1.f / DM); n.m1 = s1 * (1.f / DM);
  n.rs0 = scale * rsqrt_hw(fmaxf(fmaf(-n.m0, n.m0, q0 * (1.f / DM)), 0.f) + LN_EPS);
  n.rs1 = scale * rsqrt_hw(fmaxf(fmaf(-n.m1, n.m1, q1 * (1.f / DM)), 0.f) + LN_EPS);
  return n;
}
__device__ __forceinline__ RowNorm stat_finish(const Scratch* sc, uint32_t (&st)[4], uint32_t tag, float scale) {
  uint32_t spin = 0;
  while (__builtin_expect(stale(st[0] ^ tag), 0) && ++spin < SPIN_LIMIT) stat_fetch(sc, st);
  float f[4];
#pragma unroll
  for (int i = 0; i < 4; i++) {
    f[i] = __uint_as_float(st[i]);
    f[i] += __shfl_xor_sync(0xffffffffu, f[i], 1);
    f[i] += __shfl_xor_sync(0xffffffffu, f[i], 2);
  }
  return row_norm(f[0], f[1], f[2], f[3], scale);
}
__device__ __forceinline__ void mean_frag(uint32_t (&mu)[4], const RowNorm& n, bool sel) {
  const float a = sel ? -n.m0 : 0.f, c = sel ? -n.m1 : 0.f;
  mu[0] = pack2(a, a); mu[1] = pack2(c, c);
  const float al = a - bf_lo(mu[0]), cl = c - bf_lo(mu[1]);
  mu[2] = pack2(al, al); mu[3] = pack2(cl, cl);
  pin(mu);
}
__device__ __forceinline__ void centre(uint32_t (&a)[16], uint32_t m0, uint32_t m1) {
#pragma unroll
  for (int i = 0; i < 16; i++) asm("sub.rn.bf16x2 %0, %0, %1;" : "+r"(a[i]) : "r"((i & 1) ? m1 : m0));
  pin(a);
}
__device__ __forceinline__ void scale_pack(const float (&d)[32], uint32_t (&a)[16], float rs0, float rs1) {
#pragma unroll
  for (int i = 0; i < 16; i++) { const float rs = (i & 1) ? rs1 : rs0; a[i] = pack2(d[2 * i] * rs, d[2 * i + 1] * rs); }
}
template <int S> __device__ __forceinline__ void silu_seg(float (&acc)[4][32], float (&tn)[2][4], uint32_t (&H)[4][16], float rs0, float rs1) {
  if (S >= 2) {
    const float* h = &acc[(S - 2) >> 3][4 * ((S - 2) & 7)];
    const float* v = tn[S & 1];
    uint32_t* o = &H[(S - 2) >> 3][2 * ((S - 2) & 7)];
    o[0] = pack2(fmaf(h[0], v[0], h[0]), fmaf(h[1], v[1], h[1]));
    o[1] = pack2(fmaf(h[2], v[2], h[2]), fmaf(h[3], v[3], h[3]));
    asm volatile("" : "+r"(o[0]), "+r"(o[1]));
  }
  if (S >= 1 && S <= 32) {
#pragma unroll
    for (int k = 0; k < 4; k++) tn[(S - 1) & 1][k] = tanh_hw(acc[((S - 1) >> 3) & 3][4 * ((S - 1) & 7) + k]);
  }
  if (S < 32) {
    float* h = &acc[(S >> 3) & 3][4 * (S & 7)];
    h[0] *= rs0; h[1] *= rs0; h[2] *= rs1; h[3] *= rs1;
    asm volatile("" : "+f"(h[0]), "+f"(h[1]), "+f"(h[2]), "+f"(h[3]));
  }
  SCHED();
}
template <int S0, int S1> __device__ __forceinline__ void silu_segs(float (&acc)[4][32], float (&tn)[2][4], uint32_t (&H)[4][16], float rs0, float rs1) {
  silu_seg<S0>(acc, tn, H, rs0, rs1);
  if constexpr (S0 + 1 < S1) silu_segs<S0 + 1, S1>(acc, tn, H, rs0, rs1);
}
template <int HALF> __device__ __forceinline__ void send_half(uint4* dst, const float (&d)[32], uint32_t tag) {
  uint32_t o[8];
#pragma unroll
  for (int i = 0; i < 8; i++) o[i] = pack2(d[16 * HALF + 2 * i], d[16 * HALF + 2 * i + 1]);
  o[0] = (o[0] & ~1u) | tag; o[4] = (o[4] & ~1u) | tag;
  pin(o);
  SCHED();
  st_vec(dst + HALF * 256, o[0], o[1], o[2], o[3]);
  st_vec(dst + HALF * 256 + 128, o[4], o[5], o[6], o[7]);
  SCHED();
}
__device__ __forceinline__ void send_residual(uint32_t (&a)[16], Scratch* sc, uint4* xp, uint32_t maddr, uint32_t tag) {
  const uint32_t exact[4] = {a[0], a[4], a[8], a[12]};
  publish(xp + X_AG0, a, tag);
  const uint32_t th = here(threadIdx.x);
  stat_publish(a, sc, th, tag);
  tile_store(here(maddr) + 3 * TILE_BYTES, a);
  stsm4(SM_BASE + SM_STG + 3 * TILE_BYTES + (th >> 5) * 2048 + (th & 7) * 128 + ((((th >> 2) & 6) ^ (th & 7)) << 4), exact);
}
template <int F, int N> __device__ __forceinline__ void proj_residual(uint32_t (&A)[4][16], Scratch* sc, uint4* xp, uint32_t maddr,
                                                                      uint32_t tag, int lane) {
  float acc[32];
  uint32_t st[4];
  acquire_n<F, N>();
  if (F == F_PW2) acquire_n<0, 5>();
  res_load(maddr, acc);
  mma_tile<false>(acc, A[0], LO(F));
  gather_first<2, X_AG1>(A, st, sc, xp, tag);
  announce(sc, threadIdx.x == 0);
  mma_tile<false>(acc, A[1], HI(F));
  mma_tile<false>(acc, A[2], LO(F + 1));
  gather_rest<2, X_AG1>(A, xp, tag);
  PROF_MARK0(F == F_WO ? 11 : 16);
  mma_tile<false>(acc, A[3], HI(F + 1));
  RELEASE(F - 2, F - 1);
  WG_WAIT(0); pin(acc);
  pack_acc(acc, A[0]);
  send_residual(A[0], sc, xp, maddr, tag);
}

__device__ __forceinline__ uint64_t ring_desc(uint32_t lo) { return (RING & ~uint64_t(0xFFFFFFFFu)) | lo; }
__device__ __forceinline__ void qk_tile(float (&S)[32], const uint32_t (&Q)[16], uint32_t dk) {
  wgmma64_reuse<0>(S, &Q[0], ring_desc(dk), blockIdx.y);
#pragma unroll
  for (int s = 1; s < 4; s++) wgmma64_acc<0>(S, &Q[4 * s], ring_desc(dk + s * 2));
}
__device__ __forceinline__ void qk_shift(float (&S)[32], const uint32_t (&nm)[4]) { wgmma64_acc<0>(S, nm, (uint64_t)((SM_BASE + SM_ONE) >> 4)); }
constexpr uint32_t RING_K = (uint32_t)RING, V_STEP = 1u - (1u << 16);
constexpr uint32_t RING_V = (SM_BASE >> 4) | (((SM_STG + 2 * TILE_BYTES) >> 4) << 16);
__device__ __forceinline__ void pv_tile(float (&O)[36], const uint32_t (&P)[16], uint32_t dv, uint32_t pad) {
#pragma unroll
  for (int s = 0; s < 4; s++) wgmma72_acc(O, &P[4 * s], ring_desc(dv + s * 128 * V_STEP + (s < 2 ? 0 : (s - 1) * pad)));
}
__device__ __forceinline__ void attn_step(const float (&Sc)[32], float (&Sn)[32], uint32_t (&Pc)[16], uint32_t (&Pp)[16], float (&O)[36],
                                          const uint32_t (&Q)[16], const uint32_t (&nm)[4], uint32_t dk, uint32_t dv, bool next, bool prev) {
  if (next) {
    WG_FENCE();
    qk_tile(Sn, Q, dk);
    qk_shift(Sn, nm);
  }
  if (prev) {
    WG_FENCE();
    pv_tile(O, Pp, dv, 0);
  }
  WG_COMMIT();
  SCHED();
#pragma unroll
  for (int i = 0; i < 16; i++) Pc[i] = pack2(ex2_hw(Sc[2 * i]), ex2_hw(Sc[2 * i + 1]));
  pin(Pc);
  SCHED();
}
template <int R> __device__ __forceinline__ float tile_max(const float (&S)[32]) {
  float t[4];
#pragma unroll
  for (int j = 0; j < 4; j++) t[j] = fmaxf(fmaxf(S[8 * j + R], S[8 * j + R + 1]), fmaxf(S[8 * j + R + 4], S[8 * j + R + 5]));
  float n = fmaxf(fmaxf(t[0], t[1]), fmaxf(t[2], t[3]));
  n = fmaxf(n, __shfl_xor_sync(0xffffffffu, n, 1));
  return fmaxf(n, __shfl_xor_sync(0xffffffffu, n, 2));
}
__device__ __forceinline__ void attention_exact(float (&O)[36], const uint32_t (&Q)[16], const Scratch* sc, int bh, int lane, int half) {
  const char* kb = (const char*)&sc->kv[bh][0][0][0];
  const char* vb = (const char*)&sc->kv[bh][1][0][0];
  const int g = lane >> 2, q = lane & 3;
  float m0 = -INFINITY, m1 = -INFINITY, l0 = 0.f, l1 = 0.f;
  float o[4][4] = {};
#pragma unroll 1
  for (int k0 = 0; k0 < T_SEQ; k0 += 8) {
    float s[4] = {0.f, 0.f, 0.f, 0.f};
#pragma unroll
    for (int c = 0; c < 8; c++) hmma8(s, &Q[2 * c], __ldcg((const uint32_t*)(kb + (k0 + g) * 128 + ((c ^ g) << 4) + q * 4)));
    float n0 = fmaxf(s[0], s[1]), n1 = fmaxf(s[2], s[3]);
    n0 = fmaxf(n0, __shfl_xor_sync(0xffffffffu, n0, 1)); n1 = fmaxf(n1, __shfl_xor_sync(0xffffffffu, n1, 1));
    n0 = fmaxf(m0, fmaxf(n0, __shfl_xor_sync(0xffffffffu, n0, 2))); n1 = fmaxf(m1, fmaxf(n1, __shfl_xor_sync(0xffffffffu, n1, 2)));
    const float a0 = ex2_hw(m0 - n0), a1 = ex2_hw(m1 - n1);
    m0 = n0; m1 = n1;
    const uint32_t pp[2] = {pack2(ex2_hw(s[0] - n0), ex2_hw(s[1] - n0)), pack2(ex2_hw(s[2] - n1), ex2_hw(s[3] - n1))};
    l0 = fmaf(l0, a0, bf_lo(pp[0]) + bf_hi(pp[0])); l1 = fmaf(l1, a1, bf_lo(pp[1]) + bf_hi(pp[1]));
#pragma unroll
    for (int j = 0; j < 4; j++) {
      const int c = 4 * half + j;
      const uint32_t v0 = __ldcg((const uint16_t*)(vb + (k0 + 2 * q) * 128 + ((c ^ (2 * q)) << 4) + g * 2));
      const uint32_t v1 = __ldcg((const uint16_t*)(vb + (k0 + 2 * q + 1) * 128 + ((c ^ (2 * q + 1)) << 4) + g * 2));
      o[j][0] *= a0; o[j][1] *= a0; o[j][2] *= a1; o[j][3] *= a1;
      hmma8(o[j], pp, v0 | (v1 << 16));
    }
  }
  l0 += __shfl_xor_sync(0xffffffffu, l0, 1); l1 += __shfl_xor_sync(0xffffffffu, l1, 1);
  O[32] = l0 + __shfl_xor_sync(0xffffffffu, l0, 2); O[34] = l1 + __shfl_xor_sync(0xffffffffu, l1, 2);
#pragma unroll
  for (int i = 0; i < 16; i++) O[i] = o[i >> 2][i & 3];
}

__device__ __forceinline__ uint32_t fill_entry(int f, int r) {
  int m, x = r, y, dx = 0;
  if (f < F_QKV || f >= 48) {
    const int i = f & 15;
    m = f < F_QKV ? M_FF1A : M_FF2A;
    if (i < 8) { x = 4 * r + ((0xE2u >> i) & 1) * 2; y = r ^ ((0xE790u >> (2 * i)) & 3); dx = 1; }
    else { m++; x = r ^ (((i >> 1) - 3) & 3); y = 4 * r + 2 * (i & 1); }
  } else if (f < F_KV) {
    const int i = f - F_QKV;
    m = M_QKV;
    if (i == 1 || i >= 5) { y = r ^ (i == 1 ? 0 : 2); }
    else { x = 4 + r; y = r ^ (i ? i - 1 : 0); dx = 4; }
  } else if (f >= F_PW1 && f < F_PW2) {
    m = M_PW1; y = r ^ (f - F_PW1); dx = 4;
  } else {
    m = f < F_PW1 ? M_WO : M_PW2; y = r ^ ((f & 1) * 2);
  }
  return m | (x << 4) | (y << 8) | (dx << 16);
}
__device__ __forceinline__ void tma_fill(uint32_t st, const CUtensorMap* map, uint32_t x, uint32_t y, uint32_t x2, uint32_t y2) {
  asm volatile("{\n.reg .pred p;\nelect.sync _|p, 0xffffffff;\n"
               "@p mbarrier.arrive.expect_tx.shared::cta.b64 _, [%1], 16384;\n"
               "@p cp.async.bulk.tensor.2d.shared::cluster.global.mbarrier::complete_tx::bytes [%0], [%2, {%3, %4}], [%1];\n"
               "@p cp.async.bulk.tensor.2d.shared::cluster.global.mbarrier::complete_tx::bytes [%0 + 8192], [%2, {%5, %6}], [%1];\n}"
               :: "r"(SM_BASE + st * STAGE_BYTES), "r"(SM_BASE + SM_FULL + st * 8), "l"(map), "r"(x), "r"(y), "r"(x2), "r"(y2) : "memory");
}
template <int F0, int N> __device__ __forceinline__ void weight_fills(const Params& p, uint32_t entry) {
  uint32_t st = F0 % NSTAGE, parity = ((F0 / NSTAGE) & 1) ^ 1, e = __shfl_sync(0xffffffffu, entry, 0);
#pragma unroll 1
  for (int i = 1; i <= N; i++) {
    const uint32_t x = (e << 2) & 0x3C0, y = (e >> 2) & 0x3FC0, dx = (e >> 16) << 6;
    const CUtensorMap* map = &p.map[e & 15];
    e = __shfl_sync(0xffffffffu, entry, i);
    mbar_wait(SM_BASE + SM_EMPTY + st * 8, parity);
    tma_fill(st, map, x, y, x + dx, dx ? y : y ^ 64);
    if (++st == NSTAGE) { st = 0; parity ^= 1; }
  }
}
__device__ __forceinline__ uint32_t kv_poll(const uint32_t* flag, uint32_t prev) {
  uint32_t v;
  asm volatile("ld.relaxed.gpu.global.u32 %0, [%1];" : "=r"(v) : "l"(flag) : "memory");
  return __ballot_sync(0xffffffffu, v - 1 == prev);
}
__device__ __forceinline__ void kv_fills(const Scratch* sc, int bh, int kind, uint32_t prev, const uint32_t* flag, uint32_t ready) {
#pragma unroll 1
  for (int j = 0; j < 8; j++) {
    uint32_t spin = 0;
#pragma unroll 1
    while (((ready >> (2 * j)) & 3) != 3 && ++spin < SPIN_LIMIT) ready = kv_poll(flag, prev);
    const uint32_t st = (j < 6 ? 4 * (j >> 1) : 0) + (j & 1) + 2 * kind;
    mbar_wait(SM_BASE + SM_EMPTY + st * 8, j < 6);
    asm volatile("{\n.reg .pred p;\nelect.sync _|p, 0xffffffff;\n"
                 "@p mbarrier.arrive.expect_tx.shared::cta.b64 _, [%1], 16384;\n"
                 "@p cp.async.bulk.shared::cluster.global.mbarrier::complete_tx::bytes [%0], [%2], 16384, [%1];\n}"
                 :: "r"(SM_BASE + st * STAGE_BYTES), "r"(SM_BASE + SM_FULL + st * 8), "l"(sc->kv[bh][kind][2 * j]) : "memory");
    PROF_AT(256 + 512 + (10 + kind * 8 + j) * 4);
  }
}
__device__ __forceinline__ void l2_prefetch(const void* p, uint32_t total, int b) {
  const uint32_t part = total / NCTA;
  asm volatile("cp.async.bulk.prefetch.L2.global [%0], %1;" :: "l"((const char*)p + (size_t)b * part), "r"(part) : "memory");
}

__global__ void __launch_bounds__(384, 1) conformer_kernel(Scratch* __restrict__ sc, __nv_bfloat16* __restrict__ out,
                                                           const __nv_bfloat16* __restrict__ dw, const __nv_bfloat16* __restrict__ xin,
                                                           const __nv_bfloat16* __restrict__ w_ff1a, const __grid_constant__ Params p) {
  extern __shared__ __align__(1024) uint8_t smem[];
  const int tid = threadIdx.x, lane = tid & 31;
  if (tid == 0) {
    l2_prefetch(xin, 2 * T_SEQ * DM * 2, blockIdx.x);
    l2_prefetch(w_ff1a, 256 * 1024 * 2, blockIdx.x);
  }
  const int cw = __shfl_sync(0xffffffffu, tid >> 5, 0), wg = cw >> 2, w = cw & 3;
  const int b = blockIdx.x, r = b & 3, batch = b >> 6, t = (b >> 2) & 15;
  if ((uint32_t)__cvta_generic_to_shared(smem) != SM_BASE) return;
  PROF_MARK(0);
  PROF_TIME(30);

  if (wg == 2) {
    asm volatile("setmaxnreg.dec.sync.aligned.u32 40;");
    if (cw == 8) {
      if (lane == 0) {
        asm volatile("prefetch.tensormap [%0];" :: "l"(&p.map[M_X]) : "memory");
        asm volatile("prefetch.tensormap [%0];" :: "l"(&p.map[M_FF1A]) : "memory");
#pragma unroll
        for (int i = 0; i < 4; i++) mbar_init(SM_BASE + SM_XBAR + i * 8, 1);
#pragma unroll
        for (int i = 0; i < NSTAGE; i++) mbar_init(SM_BASE + SM_FULL + i * 8, 1);
        fence_async_smem();
      }
      __syncwarp();
      bar_arrive(0, 320);
      PROF_MARK(9);
#pragma unroll
      for (int f = 0; f < 8; f++) {
        const uint32_t x = 256 * r + ((0xE2u >> f) & 1) * 128, y = (r ^ ((0xE790u >> (2 * f)) & 3)) * 64;
#pragma unroll
        for (int c = 0; c < (f == 0 ? 4 : 0); c++)
          asm volatile("{\n.reg .pred p;\nelect.sync _|p, 0xffffffff;\n"
                       "@p mbarrier.arrive.expect_tx.shared::cta.b64 _, [%1], 8192;\n"
                       "@p cp.async.bulk.tensor.3d.shared::cluster.global.mbarrier::complete_tx::bytes [%0], [%2, {%3, %4, %5}], [%1];\n}"
                       :: "r"(SM_BASE + SM_STG + (3 - c) * TILE_BYTES), "r"(SM_BASE + SM_XBAR + c * 8), "l"(&p.map[M_X]),
                          "r"((r ^ c) * 64), "r"(t * 64), "r"(batch) : "memory");
        tma_fill(f, &p.map[M_FF1A], x, y, x + 64, y);
      }
      PROF_MARK(1);
      uint32_t entry[2];
#pragma unroll 1
      for (int i = 0; i < 2; i++) { entry[1] = fill_entry(8 + i * 32 + lane, r); if (i == 0) entry[0] = entry[1]; }
      bar_sync(BAR_INIT, 64);
      weight_fills<8, F_KV - 8>(p, entry[0]);
      mbar_wait(SM_BASE + SM_EMPTY + (F_WO % NSTAGE) * 8, 1);
      weight_fills<F_WO, F_TOTAL - F_WO>(p, entry[1]);
    } else if (here(cw) != 11) {
      const int kind = w - 1;
      const uint32_t prev = launch_index(sc);
      if (kind == 0) {
        if (lane == 0) {
#pragma unroll
          for (int i = 0; i < NSTAGE; i++) mbar_init(SM_BASE + SM_EMPTY + i * 8, 4);
        }
        __syncwarp();
        bar_arrive(0, 320);
        bar_arrive(BAR_INIT, 64);
      }
      const uint32_t* flag = sc->flag[batch * 4 + r][kind * 16 + (lane & 15)];
      const uint32_t ready = kv_poll(flag, prev);
      if (kind == 0) bar_sync(BAR_K, 160); else bar_sync(BAR_V, 160);
      if (lane == 0) {
        asm volatile("cp.async.bulk.global.shared::cta.bulk_group [%0], [%1], %2;"
                     :: "l"(&sc->kv[batch * 4 + r][kind][t][0]), "r"(SM_BASE + SM_STG + kind * TILE_BYTES), "r"(TILE_BYTES) : "memory");
PROF_MARK(4 + kind * 2);
        asm volatile("cp.async.bulk.commit_group;\ncp.async.bulk.wait_group 0;" ::: "memory");
PROF_MARK(5 + kind * 2);
        asm volatile("st.relaxed.gpu.global.u32 [%0], %1;" :: "l"(sc->flag[batch * 4 + r][kind * 16 + t]), "r"(prev + 1) : "memory");
      }
      __syncwarp();
      kv_fills(sc, batch * 4 + r, kind, prev, flag, ready);
    } else {
      const uint32_t* watch = sc->step[(b & ~3) + (lane & 3)];
      uint32_t seen;
      asm volatile("ld.relaxed.gpu.global.u32 %0, [%1];" : "=r"(seen) : "l"(watch) : "memory");
#pragma unroll 1
      for (int i = 0; i < 22; i++) {
        const uint32_t t0 = clock_now();
        uint4* dst = &sc->x[b][i * 96 + lane];
        st_vec(dst, 0u, 0u, 0u, 0u); st_vec(dst + 32, 0u, 0u, 0u, 0u); st_vec(dst + 64, 0u, 0u, 0u, 0u);
        if (i == PF_AT && lane == 0) {
          asm volatile("prefetch.tensormap [%0];" :: "l"(&p.map[M_FF1B]) : "memory");
          l2_prefetch(p.w_ff1b, 1024 * 256 * 2, b);
          l2_prefetch(p.w_qkv, 256 * 768 * 2, b);
          l2_prefetch(p.w_pw1, 256 * 512 * 2, b);
          l2_prefetch(p.w_ff2a, 256 * 1024 * 2, b);
        }
        while (clock_now() - t0 < CLR_PACE) {}
      }
      PROF_MARK(28);
      asm volatile("fence.acq_rel.gpu;" ::: "memory");
      __syncwarp();
      announce(sc, lane == 0);
      if (lane == 0) {
        l2_prefetch(p.w_o, 256 * 256 * 2, b);
        l2_prefetch(p.w_pw2, 256 * 256 * 2, b);
        l2_prefetch(p.w_ff2b, 1024 * 256 * 2, b);
#pragma unroll
        for (int i = M_QKV; i < M_X; i++) asm volatile("prefetch.tensormap [%0];" :: "l"(&p.map[i]) : "memory");
      }
      PROF_MARK(2);
      uint32_t want = seen & ~15u;
#pragma unroll 1
      for (int k = 0; k < 8; k++) {
        want += 2;
        uint32_t spin = 0;
#pragma unroll 1
        while (__any_sync(0xffffffffu, (int)(seen - want) < 0) && ++spin < SPIN_LIMIT)
          asm volatile("ld.relaxed.gpu.global.u32 %0, [%1];" : "=r"(seen) : "l"(watch) : "memory");
        bar_arrive(BAR_GO, 160);
        PROF_MARK(32 + k);
      }
    }
  } else {
    asm volatile("setmaxnreg.inc.sync.aligned.u32 232;");
    const int q = lane & 3, th = tid & 127;
    constexpr uint32_t stg = SM_BASE + SM_STG;
    const uint32_t mrow = 16 * w + (lane & 15);
    const uint32_t maddr = stg + mrow * 128 + (((lane >> 4) ^ (lane & 7)) << 4);
    const uint32_t qslot = stg + 2 * TILE_BYTES + w * 2048 + lane * 16;
    uint4* const xp = &sc->x[b][th];
    const int nvalid = T_SEQ - t * 64, row0 = 16 * w + (lane >> 2);

    uint32_t A[4][16];
    uint32_t st[4];
    if (tid < 144) sts128(SM_BASE + SM_CS + tid * 16, 0, 0, 0, 0);
    if (wg == 1) sts32(SM_BASE + SM_EYE + th * 4, th >= 96 ? 0x3F803F80u : ((th & 32) == 0 && (th & 3) == ((th >> 3) & 3)) ? (0x3F00u << ((th & 4) * 4)) : 0u);
    fence_async_smem();
    bar_sync(0, 320);
    if (wg == 0) {
      RowAcc ra = {};
      mbar_wait(SM_BASE + SM_XBAR, 0);
      PROF_MARK0(45);
      tile_load(maddr + 3 * TILE_BYTES, A[0]);
#pragma unroll
      for (int c = 1; c < 4; c++) {
        mbar_wait(SM_BASE + SM_XBAR + c * 8, 0);
        tile_load(maddr + (3 - c) * TILE_BYTES, A[c]);
        row_acc(ra, A[c - 1]);
      }
      PROF_MARK(1);
      row_acc(ra, A[3]);
      PROF_MARK0(46);
      const float m0 = ra.s[0] * (1.f / DM), m1 = ra.s[2] * (1.f / DM);
      st[0] = pack2(m0, m0); st[1] = pack2(m1, m1);
      centre(A[0], st[0], st[1]);
      const float2 sq = row_squares(ra, lane & 4);
      st[2] = __float_as_uint(fmaf(-m0, m0, sq.x * (1.f / DM))); st[3] = __float_as_uint(fmaf(-m1, m1, sq.y * (1.f / DM)));
    } else {
      const uint32_t tag = ~launch_index(sc) & 1;
      mbar_wait(SM_BASE + SM_FULL + 4 * 8, 0);
      PROF_MARK(5);
      if (b < 72) {
        const __nv_bfloat16* wp; int ld, col;
        if (b < 24) { wp = p.w_qkv; ld = 768; col = b * 32; }
        else if (b < 40) { wp = p.w_pw1; ld = 512; col = (b - 24) * 32; }
        else { wp = p.w_ff2a; ld = 1024; col = (b - 40) * 32; }
        const uint4* src = (const uint4*)(wp + (size_t)(th >> 2) * ld + col + q * 8);
        float c[8] = {0.f, 0.f, 0.f, 0.f, 0.f, 0.f, 0.f, 0.f};
#pragma unroll 1
        for (int h = 0; h < 2; h++, src += 16 * ld) {
#pragma unroll
          for (int i = 0; i < 4; i++) {
            const uint4 v = __ldg(src + i * 4 * ld);
            c[0] += bf_lo(v.x); c[1] += bf_hi(v.x); c[2] += bf_lo(v.y); c[3] += bf_hi(v.y);
            c[4] += bf_lo(v.z); c[5] += bf_hi(v.z); c[6] += bf_lo(v.w); c[7] += bf_hi(v.w);
          }
        }
#pragma unroll 1
        for (int m = 4; m <= 16; m <<= 1)
#pragma unroll
          for (int k = 0; k < 8; k++) c[k] += __shfl_xor_sync(0xffffffffu, c[k], m);
        if (lane < 4) {
          const uint32_t a = SM_BASE + SM_CS + 1792 + w * 128 + lane * 32;
          sts128(a, __float_as_uint(c[0]), __float_as_uint(c[1]), __float_as_uint(c[2]), __float_as_uint(c[3]));
          sts128(a + 16, __float_as_uint(c[4]), __float_as_uint(c[5]), __float_as_uint(c[6]), __float_as_uint(c[7]));
        }
        bar_sync(BAR_WG1, 128);
        if (th < 8) {
          float o[4] = {0.f, 0.f, 0.f, 0.f};
#pragma unroll 1
          for (int k = 0; k < 4; k++) {
            uint32_t e[4];
            lds128(SM_BASE + SM_CS + 1792 + k * 128 + th * 16, e[0], e[1], e[2], e[3]);
#pragma unroll
            for (int i = 0; i < 4; i++) o[i] += __uint_as_float(e[i]);
          }
          st_vec(&sc->cs[b * 8 + th], (__float_as_uint(o[0]) & ~1u) | tag, __float_as_uint(o[1]), __float_as_uint(o[2]), __float_as_uint(o[3]));
        }
      }
      bar_sync(BAR_WG1, 128);
      PROF_MARK(2);
      if (th < 72) {
        const int j = th >> 3, i = (th & 7) * 2;
        int src;
        if (j < CS_PW1) src = 320 + 64 * r + 16 * j;
        else if (j < CS_QKV) src = 192 + (j - CS_PW1) * 64 + 16 * r;
        else src = ((j - CS_QKV + 1) % 3) * 64 + 16 * r;
        uint32_t e[8], hi[4], lo[4], spin = 0;
#pragma unroll 1
        do {
          ld_vec(&sc->cs[src + i], e[0], e[1], e[2], e[3]);
          ld_vec(&sc->cs[src + i + 1], e[4], e[5], e[6], e[7]);
        } while ((((e[0] ^ tag) | (e[4] ^ tag)) & 1u) && ++spin < SPIN_LIMIT);
        e[0] &= ~1u; e[4] &= ~1u;
#pragma unroll
        for (int k = 0; k < 4; k++) {
          const float c0 = __uint_as_float(e[2 * k]), c1 = __uint_as_float(e[2 * k + 1]);
          hi[k] = pack2(c0, c1);
          lo[k] = pack2(c0 - bf_lo(hi[k]), c1 - bf_hi(hi[k]));
        }
        const uint32_t a = SM_BASE + SM_CS + j * 256 + i * 8;
        sts128(a ^ ((a >> 3) & 0x70), hi[0], hi[1], hi[2], hi[3]);
        sts128((a + 128) ^ (((a + 128) >> 3) & 0x70), lo[0], lo[1], lo[2], lo[3]);
      }
      fence_async_smem();
      PROF_MARK(4);
      bar_arrive(BAR_CS, 256);
    }

#pragma unroll 1
    for (uint32_t pass = 0; pass < 2; pass++) {
      uint32_t Q[16];
      if (wg == 0) {
        float acc[4][32];
        uint32_t H[4][16];
        if (!pass) { PROF_MARK(47); ACQUIRE(0); }
        mma_tile<true>(acc[0], A[0], LO(0)); mma_tile<true>(acc[1], A[0], HI(0));
        if (!pass) ACQUIRE(1);
        mma_tile<true>(acc[2], A[0], LO(1)); mma_tile<true>(acc[3], A[0], HI(1));
        if (pass) {
          gather_first<1, X_AG0>(A, st, sc, xp, 1);
        } else {
          centre(A[1], st[0], st[1]);
          acquire_n<2, 3>();
        }
        mma_tile<false>(acc[0], A[1], LO(2)); mma_tile<false>(acc[1], A[1], HI(2));
        if (pass) {
          gather_rest<1, X_AG0>(A, xp, 1);
          RELEASE(F_PW2, F_PW2 + 1);
        } else {
          centre(A[2], st[0], st[1]); centre(A[3], st[0], st[1]);
        }
        PROF_MARK2(2, 18);
        mma_tile<false>(acc[0], A[2], LO(3)); mma_tile<false>(acc[0], A[3], LO(4));
        WG_WAIT(4);
        RELEASE(0, 1);
        uint32_t mu[4] = {0u, 0u, 0u, 0u};
        float rs0, rs1, tn[2][4];
        if (pass) {
          const RowNorm n = stat_finish(sc, st, 1, 0.5f);
          rs0 = n.rs0; rs1 = n.rs1;
          mean_frag(mu, n, q == 0);
        } else {
          const int src = (lane & 28) | (lane >> 3);
          rs0 = 0.5f * rsqrt_hw(fmaxf(__uint_as_float(__shfl_sync(0xffffffffu, st[2], src)), 0.f) + LN_EPS);
          rs1 = 0.5f * rsqrt_hw(fmaxf(__uint_as_float(__shfl_sync(0xffffffffu, st[3], src)), 0.f) + LN_EPS);
        }
        pin(mu);
        mma_fold<2 * CS_FF2>(acc[0], mu);
        mma_tile<false>(acc[1], A[2], HI(3));
#define SEGS(a, b) silu_segs<a, b>(acc, tn, H, rs0, rs1)
        WG_WAIT(1); pin(acc[0]);
        SEGS(0, 1);
        mma_tile_fold<2 * CS_FF2 + 2>(acc[1], A[3], HI(4), mu);
        SEGS(1, 3);
        uint32_t ok = probe_n<5, 3>();
        SEGS(3, 4);
        settle_n<5, 3>(ok);
        mma_tile<false>(acc[2], A[1], LO(5));
        SEGS(4, 6);
        mma_tile<false>(acc[2], A[2], LO(6));
        SEGS(6, 8);
        WG_WAIT(2); pin(acc[1]);
        RELEASE(2, 4);
        SEGS(8, 9);
        mma_tile_fold<2 * CS_FF2 + 4>(acc[2], A[3], LO(7), mu);
        SEGS(9, 12);
        mma_tile<false>(acc[3], A[1], HI(5));
        SEGS(12, 14);
        mma_tile<false>(acc[3], A[2], HI(6));
        SEGS(14, 16);
        WG_WAIT(2); pin(acc[2]);
        SEGS(16, 17);
        mma_tile_fold<2 * CS_FF2 + 6>(acc[3], A[3], HI(7), mu);
        SEGS(17, 19);
        ok = probe_n<8, 2>();
        SEGS(19, 20);
        settle_n<8, 2>(ok);
        mma_tile_reuse(acc[1], H[0], LO(8));
        SEGS(20, 22);
        mma_tile<false>(acc[1], H[1], HI(8));
        SEGS(22, 24);
        WG_WAIT(2); pin(acc[3]);
        RELEASE(5, 7);
        SEGS(24, 26);
        mma_tile<false>(acc[1], H[2], LO(9));
        SEGS(26, 27);
        ok = probe_n<10, 2>();
        SEGS(27, 28);
        settle_n<10, 2>(ok);
        mma_tile_reuse(acc[2], H[0], LO(10));
        SEGS(28, 31);
        mma_tile<false>(acc[2], H[1], HI(10));
        SEGS(31, 34);
#undef SEGS
        PROF_MARK2(3, 19);
        const uint32_t rtag = here(pass ^ 1);
        const uint4* rs_in = xp + X_RS;
        mma_tile<false>(acc[1], H[3], HI(9));
        mma_tile<false>(acc[2], H[2], LO(11));
        ok = probe_n<12, 2>();
        uint4* rs_out = peer<1>(xp) + X_RS;
        mma_tile<false>(acc[2], H[3], HI(11));
        settle_n<12, 2>(ok);
        if (!pass) bar_sync(BAR_GO, 160);
        WG_WAIT(2); pin(acc[1]);
        RELEASE(8, 9);
        send_half<0>(rs_out, acc[1], rtag);
        mma_tile_reuse(acc[3], H[0], LO(12));
        SCHED();
        send_half<1>(rs_out, acc[1], rtag);
        mma_tile<false>(acc[3], H[1], HI(12));
        rs_out = peer<2>(xp) + X_RS + 512;
        WG_WAIT(2); pin(acc[2]);
        send_half<0>(rs_out, acc[2], rtag);
        mma_tile<false>(acc[3], H[2], LO(13));
        SCHED();
        ok = probe_n<14, 2>();
        send_half<1>(rs_out, acc[2], rtag);
        mma_tile<false>(acc[3], H[3], HI(13));
        settle_n<14, 2>(ok);
        mma_tile_reuse(acc[1], H[0], LO(14));
        rs_out = peer<3>(xp) + X_RS + 1024;
        announce(sc, tid == 0);
        fetch(rs_in, A[1]);
        SCHED();
        mma_tile<false>(acc[1], H[1], HI(14));
        WG_WAIT(2); pin(acc[3]);
        send_half<0>(rs_out, acc[3], rtag);
        send_half<1>(rs_out, acc[3], rtag);
        mma_tile<false>(acc[1], H[2], LO(15)); mma_tile<false>(acc[1], H[3], HI(15));
        SCHED();
        fetch(rs_in + 512, A[2]);
        SCHED();
        res_load(maddr, acc[2]);
        bar_sync(BAR_GO, 160);
        fetch(rs_in + 1024, A[3]);
        if (!pass) acquire_n<F_QKV, 3>();
        {
          uint32_t spin = 0;
          while (__builtin_expect(stale(miss(A[1], rtag) | miss(A[2], rtag) | miss(A[3], rtag)), 0) && ++spin < SPIN_LIMIT) {
            if (stale(miss(A[1], rtag) | miss(A[2], rtag))) { fetch(rs_in, A[1]); fetch(rs_in + 512, A[2]); }
            fetch(rs_in + 1024, A[3]);
          }
        }
        announce(sc, tid == 0 && !pass);
        mma_add_half(acc[2], A[1]);
        mma_add_half(acc[2], A[2]);
        mma_add_half(acc[2], A[3]);
        PROF_MARK2(4, 20);
        WG_WAIT(0); pin(acc[2]); pin(acc[1]);
#pragma unroll
        for (int i = 0; i < 16; i++) A[0][i] = pack2(fmaf(acc[1][2 * i], 0.5f, acc[2][2 * i]), fmaf(acc[1][2 * i + 1], 0.5f, acc[2][2 * i + 1]));
        if (pass) {
          PROF_MARK(21);
          stat_publish(A[0], sc, here(th), 0);
          stat_fetch(sc, st);
          const RowNorm fn = stat_finish(sc, st, 0, 1.f);
          const float nm0 = -fn.m0 * fn.rs0, nm1 = -fn.m1 * fn.rs1;
#pragma unroll
          for (int i = 0; i < 16; i++) {
            const float rs = (i & 1) ? fn.rs1 : fn.rs0, nm = (i & 1) ? nm1 : nm0;
            A[0][i] = pack2(fmaf(bf_lo(A[0][i]), rs, nm), fmaf(bf_hi(A[0][i]), rs, nm));
          }
          tile_store(here(maddr), A[0]);
          __syncwarp();
          const int row = 16 * w + (lane >> 3);
          uint4* dst = (uint4*)(out + ((size_t)batch * T_SEQ + t * 64 + row) * DM + 64 * r) + (lane & 7);
          const uint32_t src = stg + row * 128 + (((lane & 7) ^ (lane >> 3)) << 4);
#pragma unroll
          for (int i = 0; i < 4; i++) {
            uint4 v;
            lds128((src ^ ((i & 1) << 6)) + i * 512, v.x, v.y, v.z, v.w);
            if (row + 4 * i < nvalid) dst[i * 4 * (DM / 8)] = v;
          }
          PROF_MARK(22);
          PROF_TIME(31);
          break;
        }
        send_residual(A[0], sc, xp, maddr, 1);
        PROF_MARK(5);
        mma_tile<true>(acc[0], A[0], LO(F_QKV)); mma_tile<true>(acc[1], A[0], HI(F_QKV));
        mma_tile<true>(acc[2], A[0], LO(F_QKV + 1));
        gather_first<1, X_AG0>(A, st, sc, xp, 1);
        mma_tile<false>(acc[0], A[1], LO(F_QKV + 2)); mma_tile<false>(acc[1], A[1], HI(F_QKV + 2));
        acquire_n<F_QKV + 3, 3>();
        bar_sync(BAR_CS, 256);
        gather_rest<1, X_AG0>(A, xp, 1);
        PROF_MARK(6);
        mma_tile<false>(acc[0], A[2], LO(F_QKV + 3)); mma_tile<false>(acc[0], A[3], LO(F_QKV + 4));
        SCHED();
        {
          const RowNorm n = stat_finish(sc, st, 1, 1.f);
          rs0 = row0 < nvalid ? n.rs0 : 0.f; rs1 = row0 + 8 < nvalid ? n.rs1 : 0.f;
          mean_frag(mu, n, q == 3);
        }
        mma_fold<2 * CS_QKV - 6>(acc[0], mu);
        RELEASE(10, 15);
        WG_WAIT(0); pin(acc[0]);
        scale_pack(acc[0], Q, rs0, rs1);
        tile_store(here(maddr), Q);
        SCHED();
        mma_tile<false>(acc[1], A[2], HI(F_QKV + 3));
        fence_async_smem();
        bar_arrive(BAR_K, 160);
        mma_tile_fold<2 * CS_QKV - 4>(acc[1], A[3], HI(F_QKV + 4), mu);
        mma_tile<false>(acc[2], A[1], HI(F_QKV + 1)); mma_tile<false>(acc[2], A[2], LO(F_QKV + 5));
        WG_WAIT(2); pin(acc[1]);
        scale_pack(acc[1], Q, rs0, rs1);
        tile_store(here(maddr) + TILE_BYTES, Q);
        fence_async_smem();
        bar_arrive(BAR_V, 160);
        mma_tile_fold<2 * CS_QKV - 2>(acc[2], A[3], HI(F_QKV + 5), mu);
        WG_WAIT(0); pin(acc[2]);
        scale_pack(acc[2], Q, rs0 * SM_SCALE_LOG2, rs1 * SM_SCALE_LOG2);
        frag_store(here(qslot), Q);
        bar_arrive(BAR_Q, 256);
        RELEASE(F_QKV, F_QKV + 5);
      } else {
        bar_sync(BAR_Q, 256);
#pragma unroll
        for (int s = 0; s < 4; s++) lds128(qslot + s * 512, Q[4 * s], Q[4 * s + 1], Q[4 * s + 2], Q[4 * s + 3]);
        if (w < 2) {
          const uint32_t v = w ? 0u : 0x3F803F80u;
#pragma unroll
          for (int s = 0; s < 4; s++) sts128(qslot + s * 512, v, v, v, v);
          fence_async_smem();
        }
      }
      bar_sync(BAR_ATT, 256);
      PROF_MARK(7);

      const int dir = cw == 0 ? -1 : 1;
      uint32_t tap[15];
      {
        const uint32_t* dwp = (const uint32_t*)(dw + 64 * r) + lane + 7 * (DM / 2);
#pragma unroll
        for (int k = 0; k < 15; k++) tap[k] = __ldg(dwp + dir * (k - 7) * (DM / 2));
      }

      float O[36];
      {
        float S[2][32];
        uint32_t P[2][16], nm[4];
#pragma unroll
        for (int i = 0; i < 32; i++) { S[0][i] = 0.f; S[1][i] = 0.f; }
        pin(Q); pin(S[0]);
        WG_FENCE();
        qk_tile(S[0], Q, RING_K + (SM_STG >> 4));
        WG_COMMIT();
#pragma unroll
        for (int i = 0; i < 36; i++) O[i] = 0.f;
#pragma unroll
        for (int i = 0; i < 16; i++) P[1][i] = 0u;
        WG_WAIT(0); pin(S[0]);
        const float m0 = tile_max<0>(S[0]), m1 = tile_max<2>(S[0]);
        nm[0] = pack2(q ? 0.f : -m0, 0.f); nm[1] = pack2(q ? 0.f : -m1, 0.f); nm[2] = 0u; nm[3] = 0u;
#pragma unroll
        for (int k = 0; k < 15; k++) asm("mul.rn.bf16x2 %0, %0, %1;" : "+r"(tap[k]) : "r"(0x3F003F00u));
        pin(nm); pin(O); pin(P[1]); pin(tap);
        uint32_t sk = wg, sv = F_SPARE % NSTAGE + wg;
        mbar_wait(SM_BASE + SM_FULL + sv * 8, 1);
        mbar_wait(SM_BASE + SM_FULL + sk * 8, 0);
        PROF_MARK(8);
        WG_FENCE();
        qk_tile(S[0], Q, RING_K + sk * 1024);
        qk_shift(S[0], nm);
        WG_COMMIT();
        WG_WAIT(0); pin(S[0]); pin(S[1]);
#pragma unroll 1
        for (int it = 0; it < 4; it++) {
          const uint32_t sn = it >= 2 ? wg : sk + 4;
          uint32_t ok = 1;
          mbar_probe(ok, SM_BASE + SM_FULL + sn * 8, it >= 2);
          mbar_probe(ok, SM_BASE + SM_FULL + (sk + 2) * 8, it == 3);
          attn_step(S[0], S[1], P[0], P[1], O, Q, nm, RING_K + sk * 1024 + 512, RING_V + (sv * 1024 + 512) * V_STEP, true, it > 0);
          PROF_MARK(24 + it * 3);
          if (__builtin_expect(!ok, 0)) {
            mbar_wait(SM_BASE + SM_FULL + sn * 8, it >= 2);
            mbar_wait(SM_BASE + SM_FULL + (sk + 2) * 8, it == 3);
          }
          WG_WAIT(0); pin(O); pin(S[1]); pin(P[1]);
          asm volatile("{\n.reg .pred p;\nsetp.eq.u32 p, %2, 0;\n@p mbarrier.arrive.shared::cta.b64 _, [%0];\n@p mbarrier.arrive.shared::cta.b64 _, [%1];\n}"
                       :: "r"(SM_BASE + SM_EMPTY + sk * 8), "r"(SM_BASE + SM_EMPTY + sv * 8), "r"(lane) : "memory");
          PROF_MARK(25 + it * 3);
          sv = sk + 2; sk = sn;
          attn_step(S[1], S[0], P[1], P[0], O, Q, nm, RING_K + sk * 1024, RING_V + (sv * 1024) * V_STEP, it < 3, true);
          WG_WAIT(0); pin(O); pin(S[0]); pin(P[0]);
          PROF_MARK(26 + it * 3);
        }
        WG_FENCE();
        pv_tile(O, P[1], RING_V + (sv * 1024 + 512) * V_STEP, wg << 22);
        WG_COMMIT();
        announce<1>(sc, th == 0);
        WG_WAIT(0); pin(O);
      }
      PROF_MARK(9);

      {
        const uint32_t mo = stg + here(th) * 16;
        sts64(mo + 5 * 4096 + wg * 8, __float_as_uint(O[32]), __float_as_uint(O[34]));
        if (wg == 0) {
#pragma unroll
          for (int i = 4; i < 8; i++)
            sts128(mo + i * 2048, __float_as_uint(O[4 * i]), __float_as_uint(O[4 * i + 1]), __float_as_uint(O[4 * i + 2]), __float_as_uint(O[4 * i + 3]));
        } else {
#pragma unroll
          for (int i = 0; i < 4; i++)
            sts128(mo + i * 2048, __float_as_uint(O[4 * i]), __float_as_uint(O[4 * i + 1]), __float_as_uint(O[4 * i + 2]), __float_as_uint(O[4 * i + 3]));
#pragma unroll
          for (int i = 0; i < 16; i++) O[i] = O[16 + i];
        }
        bar_sync(BAR_MERGE, 256);
        uint32_t e[4];
        lds128(mo + 5 * 4096, e[0], e[1], e[2], e[3]);
        O[32] = __uint_as_float(e[0]) + __uint_as_float(e[2]); O[34] = __uint_as_float(e[1]) + __uint_as_float(e[3]);
#pragma unroll
        for (int i = 0; i < 4; i++) {
          lds128(mo + wg * TILE_BYTES + i * 2048, e[0], e[1], e[2], e[3]);
#pragma unroll
          for (int k = 0; k < 4; k++) O[4 * i + k] += __uint_as_float(e[k]);
        }
        const bool safe = O[32] > 0x1p-60f && O[32] < 0x1p60f && O[34] > 0x1p-60f && O[34] < 0x1p60f;
        if (__builtin_expect(__any_sync(0xffffffffu, !safe), 0)) attention_exact(O, Q, sc, batch * 4 + r, lane, wg);
        const float i0 = rcp_hw(O[32]), i1 = rcp_hw(O[34]);
#pragma unroll
        for (int i = 0; i < 8; i++) { const float v = (i & 1) ? i1 : i0; A[0][i] = pack2(O[2 * i] * v, O[2 * i + 1] * v); }
        A[0][0] &= ~1u; A[0][4] &= ~1u;
        uint4* dst = xp + X_AG1 + wg * 256;
        SCHED();
        st_vec(dst, A[0][0], A[0][1], A[0][2], A[0][3]);
        st_vec(dst + 128, A[0][4], A[0][5], A[0][6], A[0][7]);
        SCHED();
      }
      if (wg == 1) {
        const uint32_t mo = stg + TILE_BYTES + here(th) * 16;
        sts128(mo, A[0][0], A[0][1], A[0][2], A[0][3]);
        sts128(mo + 2048, A[0][4], A[0][5], A[0][6], A[0][7]);
        bar_arrive(BAR_HALF, 256);
      } else {
        PROF_MARK(10);
        const uint32_t mo = stg + TILE_BYTES + here(th) * 16;
        bar_sync(BAR_HALF, 256);
        lds128(mo, A[0][8], A[0][9], A[0][10], A[0][11]);
        lds128(mo + 2048, A[0][12], A[0][13], A[0][14], A[0][15]);
        proj_residual<F_WO, 6>(A, sc, xp, maddr, 0, lane);
        PROF_MARK(12);
        float acc[2][32];
        mma_tile<true>(acc[0], A[0], LO(F_PW1)); mma_tile<true>(acc[1], A[0], HI(F_PW1));
        gather_first<1, X_AG0>(A, st, sc, xp, 0);
        mma_tile<false>(acc[1], A[1], HI(F_PW1 + 1)); mma_tile<false>(acc[0], A[1], LO(F_PW1 + 1));
        gather_rest<1, X_AG0>(A, xp, 0);
        PROF_MARK(13);
        mma_tile<false>(acc[1], A[2], HI(F_PW1 + 2)); mma_tile<false>(acc[1], A[3], HI(F_PW1 + 3));
        WG_WAIT(2);
        RELEASE(F_WO, F_PW1 + 1);
        SCHED();
        uint32_t mu[4];
        const RowNorm n = stat_finish(sc, st, 0, 0.5f);
        const float rs0 = row0 < nvalid ? n.rs0 : 0.f, rs1 = row0 + 8 < nvalid ? n.rs1 : 0.f;
        mean_frag(mu, n, q == 0);
        mma_fold<2 * CS_PW1 + 2>(acc[1], mu);
        mma_tile<false>(acc[0], A[2], LO(F_PW1 + 2));
        mma_tile_fold<2 * CS_PW1>(acc[0], A[3], LO(F_PW1 + 3), mu);
        WG_WAIT(2); pin(acc[1]);
#pragma unroll
        for (int i = 0; i < 32; i++) acc[1][i] = tanh_hw(acc[1][i] * ((i & 2) ? rs1 : rs0));
#pragma unroll
        for (int i = 0; i < 32; i++) { const float rs = (i & 2) ? rs1 : rs0; acc[1][i] = fmaf(acc[1][i], rs, rs); }
        pin(acc[1]);
        SCHED();
        WG_WAIT(0); pin(acc[0]);
#pragma unroll
        for (int i = 0; i < 16; i++) A[0][i] = pack2(acc[0][2 * i] * acc[1][2 * i], acc[0][2 * i + 1] * acc[1][2 * i + 1]);
        const uint32_t ga = stg + TILE_BYTES + here(mrow) * G_PITCH + (lane >> 4) * 16;
#pragma unroll
        for (int s = 0; s < 4; s++) stsm4(ga + s * 32, &A[0][4 * s]);
      }
      {
        const uint32_t gsrc = stg + TILE_BYTES + (8 * cw - 7) * G_PITCH + lane * 4;
        const bool edge = cw == 0 || cw == 7;
        const bool nbr = cw == 0 ? t > 0 : t < 15;
        uint4* const hdst = &sc->x[b + 4 * dir][X_HALO + (cw == 0 ? 96 : 0) + lane];
        uint32_t in[22];
        bar_sync(BAR_G, 256);
        PROF_MARK(14);
        if (cw == 0) {
#pragma unroll
          for (int i = 14; i >= 0; i--) in[i] = lds32(gsrc + (21 - i) * G_PITCH);
        } else {
#pragma unroll
          for (int i = 14; i >= 0; i--) in[i] = lds32(gsrc + i * G_PITCH);
        }
        if (edge) {
          if (nbr) {
            st_vec(hdst, HALO_TAG, in[14], in[13], in[12]);
            st_vec(hdst + 32, HALO_TAG, in[11], in[10], in[9]);
            st_vec(hdst + 64, HALO_TAG, in[8], 0u, 0u);
          }
        } else {
#pragma unroll
          for (int i = 15; i < 22; i++) in[i] = lds32(gsrc + i * G_PITCH);
        }
        if (cw == 0) PROF_MARK0(40);
        uint32_t cv[8];
#pragma unroll
        for (int i = 0; i < 15; i++)
#pragma unroll
          for (int o = 0; o < 8; o++) {
            if (i == o) asm("mul.rn.bf16x2 %0, %1, %2;" : "=r"(cv[o]) : "r"(in[i]), "r"(tap[0]));
            if (i > o) asm("fma.rn.bf16x2 %0, %1, %2, %0;" : "+r"(cv[o]) : "r"(in[i]), "r"(tap[i - o]));
          }
        pin(cv);
        if (cw == 0) PROF_MARK0(41);
        if (edge) {
#pragma unroll
          for (int i = 15; i < 22; i++) in[i] = 0u;
          if (nbr) {
            const uint4* src = &sc->x[b][X_HALO + (cw == 0 ? 0 : 96) + lane];
            uint32_t e0, e1, e2, u0, u1, spin = 0;
#pragma unroll 1
            do {
              ld_vec(src, e0, in[15], in[16], in[17]);
              ld_vec(src + 32, e1, in[18], in[19], in[20]);
              ld_vec(src + 64, e2, in[21], u0, u1);
            } while (__any_sync(0xffffffffu, ((e0 ^ HALO_TAG) | (e1 ^ HALO_TAG) | (e2 ^ HALO_TAG)) != 0) && ++spin < SPIN_LIMIT);
          }
          announce<1>(sc, lane == 0);
        }
#pragma unroll
        for (int i = 15; i < 22; i++)
#pragma unroll
          for (int o = 0; o < 8; o++)
            if (i - o <= 14) asm("fma.rn.bf16x2 %0, %1, %2, %0;" : "+r"(cv[o]) : "r"(in[i]), "r"(tap[i - o]));
        if (cw == 0) PROF_MARK0(42);
        if (cw == 7) PROF_MARK0(43);
        const uint32_t fl = cw == 0 ? 7 : 0;
        const uint32_t cdst = (stg + cw * 1024 + lane * 4) ^ (fl * 144);
#pragma unroll
        for (int o = 0; o < 8; o++) {
          const float a = bf_lo(cv[o]), c = bf_hi(cv[o]);
          sts32(cdst ^ (o * 144), pack2(fmaf(a, tanh_hw(a), a), fmaf(c, tanh_hw(c), c)));
        }
      }
      if (wg == 1) {
        bar_arrive(BAR_C, 256);
        break;
      }
      bar_sync(BAR_C, 256);
      tile_load(here(maddr), A[0]);
      PROF_MARK(15);
      publish(xp + X_AG1, A[0], 1);
      proj_residual<F_PW2, 2>(A, sc, xp, maddr, 1, lane);
      PROF_MARK(17);
    }
  }
}

typedef CUresult (*EncodeFn)(CUtensorMap*, CUtensorMapDataType, cuuint32_t, void*, const cuuint64_t*, const cuuint64_t*,
                             const cuuint32_t*, const cuuint32_t*, CUtensorMapInterleave, CUtensorMapSwizzle,
                             CUtensorMapL2promotion, CUtensorMapFloatOOBfill);

void make_map(EncodeFn fn, CUtensorMap* m, const void* w, int rows, int cols, CUtensorMapSwizzle swz) {
  const cuuint64_t dims[2] = {(cuuint64_t)cols, (cuuint64_t)rows}, strides[1] = {(cuuint64_t)cols * 2};
  const cuuint32_t box[2] = {64, 64}, es[2] = {1, 1};
  fn(m, CU_TENSOR_MAP_DATA_TYPE_BFLOAT16, 2, const_cast<void*>(w), dims, strides, box, es, CU_TENSOR_MAP_INTERLEAVE_NONE,
     swz, CU_TENSOR_MAP_L2_PROMOTION_L2_128B, CU_TENSOR_MAP_FLOAT_OOB_FILL_NONE);
}

}

extern "C" void kernel_launch(void* const* d_in, const int* in_sizes, int n_in, void* d_out, int out_size) {
  static EncodeFn fn = nullptr;
  static Scratch* sc = nullptr;
  if (!fn) {
    void* f = nullptr;
    cudaDriverEntryPointQueryResult st;
    cudaGetDriverEntryPoint("cuTensorMapEncodeTiled", &f, cudaEnableDefault, &st);
    fn = (EncodeFn)f;
    void* raw = nullptr;
    cudaGetSymbolAddress(&raw, g_scratch);
    sc = (Scratch*)(((uintptr_t)raw + X_ALIGN - 1) & ~(uintptr_t)(X_ALIGN - 1));
    cudaFuncSetAttribute(conformer_kernel, cudaFuncAttributeMaxDynamicSharedMemorySize, SM_TOTAL);
  }
  typedef const __nv_bfloat16* W;
  const CUtensorMapSwizzle S = CU_TENSOR_MAP_SWIZZLE_128B;
  Params p;
  {
    const cuuint64_t dims[3] = {DM, T_SEQ, 2}, strides[2] = {DM * 2, T_SEQ * DM * 2};
    const cuuint32_t box[3] = {64, 64, 1}, es[3] = {1, 1, 1};
    fn(&p.map[M_X], CU_TENSOR_MAP_DATA_TYPE_BFLOAT16, 3, d_in[0], dims, strides, box, es, CU_TENSOR_MAP_INTERLEAVE_NONE, S,
       CU_TENSOR_MAP_L2_PROMOTION_L2_128B, CU_TENSOR_MAP_FLOAT_OOB_FILL_NONE);
  }
  make_map(fn, &p.map[M_FF1A], d_in[1], 256, 1024, S);
  make_map(fn, &p.map[M_FF1B], d_in[2], 1024, 256, S);
  make_map(fn, &p.map[M_QKV], d_in[3], 256, 768, S);
  make_map(fn, &p.map[M_WO], d_in[4], 256, 256, S);
  make_map(fn, &p.map[M_PW1], d_in[5], 256, 512, S);
  make_map(fn, &p.map[M_PW2], d_in[7], 256, 256, S);
  make_map(fn, &p.map[M_FF2A], d_in[8], 256, 1024, S);
  make_map(fn, &p.map[M_FF2B], d_in[9], 1024, 256, S);
  p.w_ff1b = (W)d_in[2]; p.w_qkv = (W)d_in[3]; p.w_o = (W)d_in[4]; p.w_pw1 = (W)d_in[5];
  p.w_pw2 = (W)d_in[7]; p.w_ff2a = (W)d_in[8]; p.w_ff2b = (W)d_in[9];

  cudaLaunchConfig_t cfg = {};
  cfg.gridDim = dim3(NCTA);
  cfg.blockDim = dim3(384);
  cfg.dynamicSmemBytes = SM_TOTAL;
  cfg.stream = cudaStreamPerThread;
  cudaLaunchAttribute at[1];
  at[0].id = cudaLaunchAttributeCooperative;
  at[0].val.cooperative = 1;
  cfg.attrs = at;
  cfg.numAttrs = 1;
  cudaLaunchKernelEx(&cfg, conformer_kernel, sc, (__nv_bfloat16*)d_out, (W)d_in[6], (W)d_in[0], (W)d_in[1], p);
}
```

```cpp
#include <cuda_runtime.h>
#include <cuda_bf16.h>
#include <cuda.h>
#include <stdint.h>

namespace {

constexpr int T_SEQ = 1000;
constexpr int DM = 256;
constexpr int NCTA = 128;
constexpr int NSTAGE = 12;
constexpr uint32_t STAGE_BYTES = 16384;
constexpr uint32_t TILE_BYTES = 8192;
constexpr uint32_t SM_BASE = 1024;
constexpr uint32_t SM_STG = NSTAGE * STAGE_BYTES;
constexpr uint32_t SM_FULL = SM_STG + 32768;
constexpr uint32_t SM_EMPTY = SM_FULL + 96;
constexpr uint32_t SM_EYE = SM_FULL + 256;
constexpr uint32_t SM_ONE = SM_FULL + 640;
constexpr uint32_t SM_CS = SM_FULL + 768;
constexpr uint32_t SM_TOTAL = SM_FULL + 3072;
constexpr int CS_FF2 = 0, CS_PW1 = 4, CS_QKV = 6;
constexpr uint32_t SPIN_LIMIT = 1u << 16;
constexpr float LN_EPS = 1e-5f;
constexpr float SM_SCALE_LOG2 = 0.125f * 1.4426950408889634f;
constexpr uint32_t G_PITCH = 144;
#define PF_AT 4
#define CLR_PACE 60

constexpr int F_QKV = 16, F_SPARE = 22, F_KV = 24, F_WO = 40, F_PW1 = 42, F_PW2 = 46, F_TOTAL = 64;
enum { M_FF1A, M_FF1B, M_QKV, M_WO, M_PW1, M_PW2, M_FF2A, M_FF2B, M_COUNT };
enum { BAR_K = 1, BAR_V, BAR_Q, BAR_MERGE, BAR_G, BAR_C, BAR_WG1, BAR_GO, BAR_CS, BAR_ATT, BAR_INIT, BAR_HALF };

struct Params {
  CUtensorMap map[M_COUNT];
  const __nv_bfloat16 *w_ff1b, *w_qkv, *w_o, *w_pw1, *w_pw2, *w_ff2a, *w_ff2b;
};

constexpr int X_RS = 0, X_AG1 = X_RS, X_HALO = X_RS + 512, X_AG0 = 1536, X_ST = 2048, X_SIZE = 4096;
constexpr uint32_t HALO_TAG = 0xFFFF0001u;
struct Scratch {
  uint4 x[NCTA][X_SIZE];
  uint4 kv[8][2][16][512];
  uint4 cs[576];
  uint32_t flag[8][32][32];
  uint32_t step[NCTA][32];
};
constexpr size_t X_ALIGN = 4 * X_SIZE * sizeof(uint4);
__device__ uint8_t g_scratch[sizeof(Scratch) + X_ALIGN];
#define PROF_TIME(i)
#define PROF_MARK(i)
#define PROF_MARK2(i, j)
#define PROF_MARK0(i)
#define PROF_AT(a)

__device__ __forceinline__ void mbar_init(uint32_t bar, uint32_t cnt) {
  asm volatile("mbarrier.init.shared::cta.b64 [%0], %1;" :: "r"(bar), "r"(cnt) : "memory");
}
__device__ __forceinline__ void mbar_wait(uint32_t bar, uint32_t parity) {
  asm volatile("{\n.reg .pred p;\n.reg .u32 c;\nmov.u32 c, 0;\n"
               "WAIT_LOOP:\nmbarrier.try_wait.parity.shared::cta.b64 p, [%0], %1;\n@p bra WAIT_DONE;\n"
               "add.u32 c, c, 1;\nsetp.lt.u32 p, c, %2;\n@p bra WAIT_LOOP;\nWAIT_DONE:\n}"
               :: "r"(bar), "r"(parity), "n"(SPIN_LIMIT) : "memory");
}
__device__ __forceinline__ void mbar_arrive(uint32_t bar) {
  asm volatile("mbarrier.arrive.shared::cta.b64 _, [%0];" :: "r"(bar) : "memory");
}
#define bar_sync(id, n) asm volatile("bar.sync %0, %1;" :: "n"((int)(id)), "n"(n) : "memory")
#define bar_arrive(id, n) asm volatile("bar.arrive %0, %1;" :: "n"((int)(id)), "n"(n) : "memory")
__device__ __forceinline__ void fence_async_smem() { asm volatile("fence.proxy.async.shared::cta;" ::: "memory"); }

__device__ __forceinline__ void st_vec(uint4* p, uint32_t a, uint32_t b, uint32_t c, uint32_t d) {
  asm volatile("{\n.reg .b128 v;\n.reg .b64 lo, hi;\nmov.b64 lo, {%1, %2};\nmov.b64 hi, {%3, %4};\nmov.b128 v, {lo, hi};\n"
               "st.relaxed.gpu.global.b128 [%0], v;\n}" :: "l"(p), "r"(a), "r"(b), "r"(c), "r"(d) : "memory");
}
__device__ __forceinline__ void ld_vec(const uint4* p, uint32_t& a, uint32_t& b, uint32_t& c, uint32_t& d) {
  asm volatile("{\n.reg .b128 v;\n.reg .b64 lo, hi;\nld.relaxed.gpu.global.b128 v, [%4];\nmov.b128 {lo, hi}, v;\n"
               "mov.b64 {%0, %1}, lo;\nmov.b64 {%2, %3}, hi;\n}" : "=r"(a), "=r"(b), "=r"(c), "=r"(d) : "l"(p) : "memory");
}
__device__ __forceinline__ void sts128(uint32_t a, uint32_t x, uint32_t y, uint32_t z, uint32_t w) {
  asm volatile("st.shared.v4.u32 [%0], {%1, %2, %3, %4};" :: "r"(a), "r"(x), "r"(y), "r"(z), "r"(w) : "memory");
}
__device__ __forceinline__ void lds128(uint32_t a, uint32_t& x, uint32_t& y, uint32_t& z, uint32_t& w) {
  asm volatile("ld.shared.v4.u32 {%0, %1, %2, %3}, [%4];" : "=r"(x), "=r"(y), "=r"(z), "=r"(w) : "r"(a) : "memory");
}
__device__ __forceinline__ uint32_t lds32(uint32_t a) {
  uint32_t x; asm volatile("ld.shared.u32 %0, [%1];" : "=r"(x) : "r"(a) : "memory"); return x;
}
__device__ __forceinline__ void sts32(uint32_t a, uint32_t x) { asm volatile("st.shared.u32 [%0], %1;" :: "r"(a), "r"(x) : "memory"); }
__device__ __forceinline__ void sts64(uint32_t a, uint32_t x, uint32_t y) {
  asm volatile("st.shared.v2.u32 [%0], {%1, %2};" :: "r"(a), "r"(x), "r"(y) : "memory");
}
__device__ __forceinline__ void stsm4(uint32_t a, const uint32_t* r) {
  asm volatile("stmatrix.sync.aligned.m8n8.x4.shared.b16 [%0], {%1, %2, %3, %4};" :: "r"(a), "r"(r[0]), "r"(r[1]), "r"(r[2]), "r"(r[3]) : "memory");
}
__device__ __forceinline__ void ldsm4(uint32_t a, uint32_t* r) {
  asm volatile("ldmatrix.sync.aligned.m8n8.x4.shared.b16 {%0, %1, %2, %3}, [%4];" : "=r"(r[0]), "=r"(r[1]), "=r"(r[2]), "=r"(r[3]) : "r"(a) : "memory");
}
__device__ __forceinline__ uint32_t pack2(float lo, float hi) {
  uint32_t r; asm("cvt.rn.bf16x2.f32 %0, %1, %2;" : "=r"(r) : "f"(hi), "f"(lo)); return r;
}
__device__ __forceinline__ float bf_lo(uint32_t w) { return __uint_as_float(w << 16); }
__device__ __forceinline__ float bf_hi(uint32_t w) { return __uint_as_float(w & 0xffff0000u); }
__device__ __forceinline__ float tanh_hw(float x) { float y; asm volatile("tanh.approx.f32 %0, %1;" : "=f"(y) : "f"(x)); return y; }
__device__ __forceinline__ float rcp_hw(float x) { float y; asm("rcp.approx.ftz.f32 %0, %1;" : "=f"(y) : "f"(x)); return y; }
__device__ __forceinline__ float rsqrt_hw(float x) { float y; asm("rsqrt.approx.ftz.f32 %0, %1;" : "=f"(y) : "f"(x)); return y; }
__device__ __forceinline__ float ex2_hw(float x) { float y; asm("ex2.approx.ftz.f32 %0, %1;" : "=f"(y) : "f"(x)); return y; }

__device__ __forceinline__ uint32_t here(uint32_t v) { asm volatile("" : "+r"(v)); return v; }

#define SCHED() asm volatile("pmevent 1;" ::: "memory")
__device__ __forceinline__ void cp_async_wait(int n) {
  if (n == 0) asm volatile("cp.async.wait_group 0;" ::: "memory");
  if (n == 1) asm volatile("cp.async.wait_group 1;" ::: "memory");
  if (n == 2) asm volatile("cp.async.wait_group 2;" ::: "memory");
  if (n == 3) asm volatile("cp.async.wait_group 3;" ::: "memory");
}
#define WG_FENCE() asm volatile("wgmma.fence.sync.aligned;" ::: "memory")
#define WG_COMMIT() asm volatile("wgmma.commit_group.sync.aligned;" ::: "memory")
#define WG_WAIT(n) asm volatile("wgmma.wait_group.sync.aligned %0;" :: "n"(n) : "memory")

template <int N> __device__ __forceinline__ void pin(float (&d)[N]) {
#pragma unroll
  for (int i = 0; i < N; i++) asm volatile("" : "+f"(d[i]) :: "memory");
}
template <int N> __device__ __forceinline__ void pin(uint32_t (&d)[N]) {
#pragma unroll
  for (int i = 0; i < N; i++) asm volatile("" : "+r"(d[i]) :: "memory");
}

#define WG_D32 "{%0, %1, %2, %3, %4, %5, %6, %7, %8, %9, %10, %11, %12, %13, %14, %15, %16, %17, %18, %19, %20, %21, %22, %23, %24, %25, %26, %27, %28, %29, %30, %31}"
template <int TB> __device__ __forceinline__ void wgmma64_acc(float (&d)[32], const uint32_t* a, uint64_t db) {
  asm volatile("wgmma.mma_async.sync.aligned.m64n64k16.f32.bf16.bf16 " WG_D32 ", {%32, %33, %34, %35}, %36, 1, 1, 1, %37;"
    : "+f"(d[0]), "+f"(d[1]), "+f"(d[2]), "+f"(d[3]), "+f"(d[4]), "+f"(d[5]), "+f"(d[6]), "+f"(d[7]),
      "+f"(d[8]), "+f"(d[9]), "+f"(d[10]), "+f"(d[11]), "+f"(d[12]), "+f"(d[13]), "+f"(d[14]), "+f"(d[15]),
      "+f"(d[16]), "+f"(d[17]), "+f"(d[18]), "+f"(d[19]), "+f"(d[20]), "+f"(d[21]), "+f"(d[22]), "+f"(d[23]),
      "+f"(d[24]), "+f"(d[25]), "+f"(d[26]), "+f"(d[27]), "+f"(d[28]), "+f"(d[29]), "+f"(d[30]), "+f"(d[31])
    : "r"(a[0]), "r"(a[1]), "r"(a[2]), "r"(a[3]), "l"(db), "n"(TB));
}
template <int TB> __device__ __forceinline__ void wgmma64_reuse(float (&d)[32], const uint32_t* a, uint64_t db, uint32_t zero) {
  asm volatile("{\n.reg .pred p;\nsetp.ne.u32 p, %37, 0;\nwgmma.mma_async.sync.aligned.m64n64k16.f32.bf16.bf16 " WG_D32 ", {%32, %33, %34, %35}, %36, p, 1, 1, %38;\n}"
    : "+f"(d[0]), "+f"(d[1]), "+f"(d[2]), "+f"(d[3]), "+f"(d[4]), "+f"(d[5]), "+f"(d[6]), "+f"(d[7]),
      "+f"(d[8]), "+f"(d[9]), "+f"(d[10]), "+f"(d[11]), "+f"(d[12]), "+f"(d[13]), "+f"(d[14]), "+f"(d[15]),
      "+f"(d[16]), "+f"(d[17]), "+f"(d[18]), "+f"(d[19]), "+f"(d[20]), "+f"(d[21]), "+f"(d[22]), "+f"(d[23]),
      "+f"(d[24]), "+f"(d[25]), "+f"(d[26]), "+f"(d[27]), "+f"(d[28]), "+f"(d[29]), "+f"(d[30]), "+f"(d[31])
    : "r"(a[0]), "r"(a[1]), "r"(a[2]), "r"(a[3]), "l"(db), "r"(zero), "n"(TB));
}
template <int TB> __device__ __forceinline__ void wgmma64_set(float (&d)[32], const uint32_t* a, uint64_t db) {
  asm volatile("wgmma.mma_async.sync.aligned.m64n64k16.f32.bf16.bf16 " WG_D32 ", {%32, %33, %34, %35}, %36, 0, 1, 1, %37;"
    : "=f"(d[0]), "=f"(d[1]), "=f"(d[2]), "=f"(d[3]), "=f"(d[4]), "=f"(d[5]), "=f"(d[6]), "=f"(d[7]),
      "=f"(d[8]), "=f"(d[9]), "=f"(d[10]), "=f"(d[11]), "=f"(d[12]), "=f"(d[13]), "=f"(d[14]), "=f"(d[15]),
      "=f"(d[16]), "=f"(d[17]), "=f"(d[18]), "=f"(d[19]), "=f"(d[20]), "=f"(d[21]), "=f"(d[22]), "=f"(d[23]),
      "=f"(d[24]), "=f"(d[25]), "=f"(d[26]), "=f"(d[27]), "=f"(d[28]), "=f"(d[29]), "=f"(d[30]), "=f"(d[31])
    : "r"(a[0]), "r"(a[1]), "r"(a[2]), "r"(a[3]), "l"(db), "n"(TB));
}

__device__ __forceinline__ void wgmma72_acc(float (&d)[36], const uint32_t* a, uint64_t db) {
  asm volatile("wgmma.mma_async.sync.aligned.m64n72k16.f32.bf16.bf16 {%0, %1, %2, %3, %4, %5, %6, %7, %8, %9, %10, %11, %12, %13, %14, %15, %16, %17, %18, %19, %20, %21, %22, %23, %24, %25, %26, %27, %28, %29, %30, %31, %32, %33, %34, %35}, {%36, %37, %38, %39}, %40, 1, 1, 1, 1;"
    : "+f"(d[0]), "+f"(d[1]), "+f"(d[2]), "+f"(d[3]), "+f"(d[4]), "+f"(d[5]), "+f"(d[6]), "+f"(d[7]), "+f"(d[8]),
      "+f"(d[9]), "+f"(d[10]), "+f"(d[11]), "+f"(d[12]), "+f"(d[13]), "+f"(d[14]), "+f"(d[15]), "+f"(d[16]), "+f"(d[17]),
      "+f"(d[18]), "+f"(d[19]), "+f"(d[20]), "+f"(d[21]), "+f"(d[22]), "+f"(d[23]), "+f"(d[24]), "+f"(d[25]), "+f"(d[26]),
      "+f"(d[27]), "+f"(d[28]), "+f"(d[29]), "+f"(d[30]), "+f"(d[31]), "+f"(d[32]), "+f"(d[33]), "+f"(d[34]), "+f"(d[35])
    : "r"(a[0]), "r"(a[1]), "r"(a[2]), "r"(a[3]), "l"(db));
}
__device__ __forceinline__ void wgmma16_acc(float* d, const uint32_t* a, uint64_t db) {
  asm volatile("wgmma.mma_async.sync.aligned.m64n16k16.f32.bf16.bf16 {%0, %1, %2, %3, %4, %5, %6, %7}, {%8, %9, %10, %11}, %12, 1, 1, 1, 0;"
    : "+f"(d[0]), "+f"(d[1]), "+f"(d[2]), "+f"(d[3]), "+f"(d[4]), "+f"(d[5]), "+f"(d[6]), "+f"(d[7])
    : "r"(a[0]), "r"(a[1]), "r"(a[2]), "r"(a[3]), "l"(db));
}
__device__ __forceinline__ void hmma(float (&d)[4], const uint32_t* a, uint32_t b0, uint32_t b1) {
  asm("mma.sync.aligned.m16n8k16.row.col.f32.bf16.bf16.f32 {%0, %1, %2, %3}, {%4, %5, %6, %7}, {%8, %9}, {%0, %1, %2, %3};"
    : "+f"(d[0]), "+f"(d[1]), "+f"(d[2]), "+f"(d[3]) : "r"(a[0]), "r"(a[1]), "r"(a[2]), "r"(a[3]), "r"(b0), "r"(b1));
}

__device__ __forceinline__ void hmma8(float (&d)[4], const uint32_t* a, uint32_t b0) {
  asm("mma.sync.aligned.m16n8k8.row.col.f32.bf16.bf16.f32 {%0, %1, %2, %3}, {%4, %5}, {%6}, {%0, %1, %2, %3};"
    : "+f"(d[0]), "+f"(d[1]), "+f"(d[2]), "+f"(d[3]) : "r"(a[0]), "r"(a[1]), "r"(b0));
}

template <bool FIRST> __device__ __forceinline__ void mma_tile(float (&d)[32], const uint32_t (&a)[16], uint64_t db) {
  WG_FENCE();
#pragma unroll
  for (int s = 0; s < 4; s++) {
    if (FIRST && s == 0) wgmma64_set<1>(d, &a[0], db); else wgmma64_acc<1>(d, &a[4 * s], db + s * 128);
  }
  WG_COMMIT();
}
__device__ __forceinline__ void mma_tile_reuse(float (&d)[32], const uint32_t (&a)[16], uint64_t db) {
  WG_FENCE();
  wgmma64_reuse<1>(d, &a[0], db, blockIdx.y);
#pragma unroll
  for (int s = 1; s < 4; s++) wgmma64_acc<1>(d, &a[4 * s], db + s * 128);
  WG_COMMIT();
}
template <int ROW> __device__ __forceinline__ void fold_step(float (&d)[32], const uint32_t (&mu)[4]) {
  wgmma64_acc<1>(d, mu, (uint64_t)((SM_BASE + SM_CS + ROW * 128) >> 4) | (uint64_t(1) << 16) | (uint64_t(1) << 62));
}
template <int ROW> __device__ __forceinline__ void mma_fold(float (&d)[32], const uint32_t (&mu)[4]) {
  WG_FENCE();
  fold_step<ROW>(d, mu);
  WG_COMMIT();
}
template <int ROW> __device__ __forceinline__ void mma_tile_fold(float (&d)[32], const uint32_t (&a)[16], uint64_t db, const uint32_t (&mu)[4]) {
  WG_FENCE();
#pragma unroll
  for (int s = 0; s < 4; s++) wgmma64_acc<1>(d, &a[4 * s], db + s * 128);
  fold_step<ROW>(d, mu);
  WG_COMMIT();
}
__device__ __forceinline__ void mma_add_half(float (&d)[32], const uint32_t (&a)[16]) {
  const uint64_t db = (uint64_t)((SM_BASE + SM_EYE) >> 4) | (uint64_t(8) << 16) | (uint64_t(8) << 32);
  WG_FENCE();
#pragma unroll
  for (int s = 0; s < 4; s++) wgmma16_acc(&d[8 * s], &a[4 * s], db);
  WG_COMMIT();
}
#define ACQUIRE(f) mbar_wait(SM_BASE + SM_FULL + ((f) % NSTAGE) * 8, ((f) / NSTAGE) & 1)
__device__ __forceinline__ void mbar_probe(uint32_t& ok, uint32_t bar, uint32_t parity) {
  asm volatile("{\n.reg .pred p;\nmbarrier.test_wait.parity.shared::cta.b64 p, [%1], %2;\nselp.u32 %0, %0, 0, p;\n}"
               : "+r"(ok) : "r"(bar), "r"(parity) : "memory");
}
template <int F, int N> __device__ __forceinline__ uint32_t probe_n() {
  static_assert(F % NSTAGE + N <= NSTAGE, "stages must not wrap");
  uint32_t ok = 1;
#pragma unroll
  for (int i = 0; i < N; i++) mbar_probe(ok, SM_BASE + SM_FULL + (F % NSTAGE + i) * 8, (F / NSTAGE) & 1);
  return ok;
}
template <int F, int N> __device__ __forceinline__ void settle_n(uint32_t ok) {
  if (__builtin_expect(!ok, 0)) {
#pragma unroll 1
    for (int i = 0; i < N; i++) mbar_wait(SM_BASE + SM_FULL + (F % NSTAGE + i) * 8, (F / NSTAGE) & 1);
  }
}
template <int F, int N> __device__ __forceinline__ void acquire_n() { settle_n<F, N>(probe_n<F, N>()); }
#define RELEASE(f0, f1) do { if (lane == 0) { _Pragma("unroll") for (int f_ = (f0); f_ <= (f1); f_++) mbar_arrive(SM_BASE + SM_EMPTY + (f_ % NSTAGE) * 8); } } while (0)
constexpr uint64_t RING = (uint64_t)(SM_BASE >> 4) | (uint64_t(1) << 16) | (uint64_t(64) << 32) | (uint64_t(1) << 62);
#define LO(f) (RING + ((f) % NSTAGE) * 1024)
#define HI(f) (RING + ((f) % NSTAGE) * 1024 + 512)

template <int C> __device__ __forceinline__ uint4* peer(uint4* p) {
  asm volatile("" : "+l"(p));
  return (uint4*)((uintptr_t)p ^ (C * X_SIZE * sizeof(uint4)));
}
__device__ __forceinline__ uint32_t clock_now() { uint32_t c; asm volatile("mov.u32 %0, %%clock;" : "=r"(c) :: "memory"); return c; }
__device__ __forceinline__ void publish(uint4* dst, uint32_t (&a)[16], uint32_t tag) {
#pragma unroll
  for (int s = 0; s < 4; s++) a[4 * s] = (a[4 * s] & ~1u) | tag;
  pin(a);
  SCHED();
#pragma unroll
  for (int s = 0; s < 4; s++) st_vec(dst + s * 128, a[4 * s], a[4 * s + 1], a[4 * s + 2], a[4 * s + 3]);
  SCHED();
}
__device__ __forceinline__ void fetch(const uint4* src, uint32_t (&a)[16]) {
#pragma unroll
  for (int s = 0; s < 4; s++) ld_vec(src + s * 128, a[4 * s], a[4 * s + 1], a[4 * s + 2], a[4 * s + 3]);
}
__device__ __forceinline__ uint32_t miss(const uint32_t (&a)[16], uint32_t tag) {
  return (a[0] ^ tag) | (a[4] ^ tag) | (a[8] ^ tag) | (a[12] ^ tag);
}
__device__ __forceinline__ bool stale(uint32_t v) { return __any_sync(0xffffffffu, here(v) & 1u); }
template <int N = 2> __device__ __forceinline__ void announce(Scratch* sc, bool leader) {
  asm volatile("{\n.reg .pred p;\nsetp.ne.u32 p, %1, 0;\n@p red.relaxed.gpu.global.add.u32 [%0], %2;\n}"
               :: "l"(sc->step[blockIdx.x]), "r"((uint32_t)leader), "n"(N) : "memory");
}
__device__ __forceinline__ uint32_t launch_index(const Scratch* sc) { return *(const volatile uint32_t*)sc->step[blockIdx.x] >> 4; }
__device__ __forceinline__ void stat_fetch(const Scratch* sc, uint32_t (&st)[4]) {
  const uint32_t th = here(threadIdx.x);
  ld_vec(&sc->x[(blockIdx.x & ~3u) + (th & 3)][X_ST + (th >> 2)], st[0], st[1], st[2], st[3]);
}
template <int C, int SLOT> __device__ __forceinline__ void gather_first(uint32_t (&A)[4][16], uint32_t (&st)[4], const Scratch* sc, uint4* xp, uint32_t tag) {
  bar_sync(BAR_GO, 160);
  fetch(peer<1>(xp) + SLOT, A[1]); fetch(peer<2>(xp) + SLOT, A[2]); fetch(peer<3>(xp) + SLOT, A[3]);
  if (SLOT == X_AG0) stat_fetch(sc, st);
  uint32_t spin = 0;
  while (__builtin_expect(stale(miss(A[1], tag) | miss(A[C], tag)), 0) && ++spin < SPIN_LIMIT) {
    fetch(peer<1>(xp) + SLOT, A[1]);
    if (C == 2) fetch(peer<2>(xp) + SLOT, A[2]);
  }
}
template <int C, int SLOT> __device__ __forceinline__ void gather_rest(uint32_t (&A)[4][16], uint4* xp, uint32_t tag) {
  SCHED();
  uint32_t spin = 0;
  while (__builtin_expect(stale(miss(A[C + 1], tag) | miss(A[3], tag)), 0) && ++spin < SPIN_LIMIT) {
    if (C == 1) fetch(peer<2>(xp) + SLOT, A[2]);
    fetch(peer<3>(xp) + SLOT, A[3]);
  }
}
__device__ __forceinline__ void pack_acc(const float (&d)[32], uint32_t (&a)[16]) {
#pragma unroll
  for (int i = 0; i < 16; i++) a[i] = pack2(d[2 * i], d[2 * i + 1]);
}
__device__ __forceinline__ void frag_store(uint32_t slot, const uint32_t (&a)[16]) {
#pragma unroll
  for (int s = 0; s < 4; s++) sts128(slot + s * 512, a[4 * s], a[4 * s + 1], a[4 * s + 2], a[4 * s + 3]);
}
__device__ __forceinline__ void tile_store(uint32_t maddr, const uint32_t (&a)[16]) {
#pragma unroll
  for (int s = 0; s < 4; s++) stsm4(maddr ^ (s << 5), &a[4 * s]);
}
__device__ __forceinline__ void tile_load(uint32_t maddr, uint32_t (&a)[16]) {
#pragma unroll
  for (int s = 0; s < 4; s++) ldsm4(maddr ^ (s << 5), &a[4 * s]);
}

__device__ __forceinline__ void res_load(uint32_t maddr, float (&d)[32]) {
  uint32_t a[16];
  tile_load(here(maddr) + 3 * TILE_BYTES, a);
#pragma unroll
  for (int i = 0; i < 16; i++) { d[2 * i] = bf_lo(a[i]); d[2 * i + 1] = bf_hi(a[i]); }
  pin(d);
}

struct RowAcc { float s[4], u[2][4], v[2][4]; };
__device__ __forceinline__ void row_acc(RowAcc& t, const uint32_t (&a)[16]) {
#pragma unroll
  for (int s = 0; s < 8; s++) {
    if ((s & 1) == 0) hmma(t.s, &a[2 * s], 0x3F803F80u, 0x3F803F80u);
    hmma8(t.u[s & 1], &a[2 * s], a[2 * s]);
    hmma8(t.v[s & 1], &a[2 * s], a[2 * s + 1]);
  }
}
__device__ __forceinline__ float2 row_squares(const RowAcc& t, bool odd) {
  return make_float2(odd ? t.u[0][1] + t.u[1][1] : t.u[0][0] + t.u[1][0], odd ? t.v[0][3] + t.v[1][3] : t.v[0][2] + t.v[1][2]);
}
__device__ __forceinline__ void stat_publish(const uint32_t (&a)[16], Scratch* sc, uint32_t th, uint32_t tag) {
  RowAcc t = {};
  row_acc(t, a);
  const float2 q = row_squares(t, th & 4);
  if ((th & 3) == ((th >> 3) & 3))
    st_vec(&sc->x[blockIdx.x][X_ST + (th >> 2)], (__float_as_uint(t.s[0]) & ~1u) | tag, __float_as_uint(q.x), __float_as_uint(t.s[2]), __float_as_uint(q.y));
}
struct RowNorm { float m0, rs0, m1, rs1; };
__device__ __forceinline__ RowNorm row_norm(float s0, float q0, float s1, float q1, float scale) {
  RowNorm n;
  n.m0 = s0 * (1.f / DM); n.m1 = s1 * (1.f / DM);
  n.rs0 = scale * rsqrt_hw(fmaxf(fmaf(-n.m0, n.m0, q0 * (1.f / DM)), 0.f) + LN_EPS);
  n.rs1 = scale * rsqrt_hw(fmaxf(fmaf(-n.m1, n.m1, q1 * (1.f / DM)), 0.f) + LN_EPS);
  return n;
}
__device__ __forceinline__ RowNorm stat_finish(const Scratch* sc, uint32_t (&st)[4], uint32_t tag, float scale) {
  uint32_t spin = 0;
  while (__builtin_expect(stale(st[0] ^ tag), 0) && ++spin < SPIN_LIMIT) stat_fetch(sc, st);
  float f[4];
#pragma unroll
  for (int i = 0; i < 4; i++) {
    f[i] = __uint_as_float(st[i]);
    f[i] += __shfl_xor_sync(0xffffffffu, f[i], 1);
    f[i] += __shfl_xor_sync(0xffffffffu, f[i], 2);
  }
  return row_norm(f[0], f[1], f[2], f[3], scale);
}
__device__ __forceinline__ void mean_frag(uint32_t (&mu)[4], const RowNorm& n, bool sel) {
  const float a = sel ? -n.m0 : 0.f, c = sel ? -n.m1 : 0.f;
  mu[0] = pack2(a, a); mu[1] = pack2(c, c);
  const float al = a - bf_lo(mu[0]), cl = c - bf_lo(mu[1]);
  mu[2] = pack2(al, al); mu[3] = pack2(cl, cl);
  pin(mu);
}
__device__ __forceinline__ void centre(uint32_t (&a)[16], uint32_t m0, uint32_t m1) {
#pragma unroll
  for (int i = 0; i < 16; i++) asm("sub.rn.bf16x2 %0, %0, %1;" : "+r"(a[i]) : "r"((i & 1) ? m1 : m0));
  pin(a);
}
__device__ __forceinline__ void scale_pack(const float (&d)[32], uint32_t (&a)[16], float rs0, float rs1) {
#pragma unroll
  for (int i = 0; i < 16; i++) { const float rs = (i & 1) ? rs1 : rs0; a[i] = pack2(d[2 * i] * rs, d[2 * i + 1] * rs); }
}
template <int S> __device__ __forceinline__ void silu_seg(float (&acc)[4][32], float (&tn)[2][4], uint32_t (&H)[4][16], float rs0, float rs1) {
  if (S >= 2) {
    const float* h = &acc[(S - 2) >> 3][4 * ((S - 2) & 7)];
    const float* v = tn[S & 1];
    uint32_t* o = &H[(S - 2) >> 3][2 * ((S - 2) & 7)];
    o[0] = pack2(fmaf(h[0], v[0], h[0]), fmaf(h[1], v[1], h[1]));
    o[1] = pack2(fmaf(h[2], v[2], h[2]), fmaf(h[3], v[3], h[3]));
    asm volatile("" : "+r"(o[0]), "+r"(o[1]));
  }
  if (S >= 1 && S <= 32) {
#pragma unroll
    for (int k = 0; k < 4; k++) tn[(S - 1) & 1][k] = tanh_hw(acc[((S - 1) >> 3) & 3][4 * ((S - 1) & 7) + k]);
  }
  if (S < 32) {
    float* h = &acc[(S >> 3) & 3][4 * (S & 7)];
    h[0] *= rs0; h[1] *= rs0; h[2] *= rs1; h[3] *= rs1;
    asm volatile("" : "+f"(h[0]), "+f"(h[1]), "+f"(h[2]), "+f"(h[3]));
  }
  SCHED();
}
template <int S0, int S1> __device__ __forceinline__ void silu_segs(float (&acc)[4][32], float (&tn)[2][4], uint32_t (&H)[4][16], float rs0, float rs1) {
  silu_seg<S0>(acc, tn, H, rs0, rs1);
  if constexpr (S0 + 1 < S1) silu_segs<S0 + 1, S1>(acc, tn, H, rs0, rs1);
}
template <int HALF> __device__ __forceinline__ void send_half(uint4* dst, const float (&d)[32], uint32_t tag) {
  uint32_t o[8];
#pragma unroll
  for (int i = 0; i < 8; i++) o[i] = pack2(d[16 * HALF + 2 * i], d[16 * HALF + 2 * i + 1]);
  o[0] = (o[0] & ~1u) | tag; o[4] = (o[4] & ~1u) | tag;
  pin(o);
  SCHED();
  st_vec(dst + HALF * 256, o[0], o[1], o[2], o[3]);
  st_vec(dst + HALF * 256 + 128, o[4], o[5], o[6], o[7]);
  SCHED();
}
__device__ __forceinline__ void send_residual(uint32_t (&a)[16], Scratch* sc, uint4* xp, uint32_t maddr, uint32_t tag) {
  const uint32_t exact[4] = {a[0], a[4], a[8], a[12]};
  publish(xp + X_AG0, a, tag);
  const uint32_t th = here(threadIdx.x);
  stat_publish(a, sc, th, tag);
  tile_store(here(maddr) + 3 * TILE_BYTES, a);
  stsm4(SM_BASE + SM_STG + 3 * TILE_BYTES + (th >> 5) * 2048 + (th & 7) * 128 + ((((th >> 2) & 6) ^ (th & 7)) << 4), exact);
}
template <int F, int N> __device__ __forceinline__ void proj_residual(uint32_t (&A)[4][16], Scratch* sc, uint4* xp, uint32_t maddr,
                                                                      uint32_t tag, int lane) {
  float acc[32];
  uint32_t st[4];
  acquire_n<F, N>();
  if (F == F_PW2) acquire_n<0, 5>();
  res_load(maddr, acc);
  mma_tile<false>(acc, A[0], LO(F));
  gather_first<2, X_AG1>(A, st, sc, xp, tag);
  announce(sc, threadIdx.x == 0);
  mma_tile<false>(acc, A[1], HI(F));
  mma_tile<false>(acc, A[2], LO(F + 1));
  gather_rest<2, X_AG1>(A, xp, tag);
  PROF_MARK0(F == F_WO ? 11 : 16);
  mma_tile<false>(acc, A[3], HI(F + 1));
  RELEASE(F - 2, F - 1);
  WG_WAIT(0); pin(acc);
  pack_acc(acc, A[0]);
  send_residual(A[0], sc, xp, maddr, tag);
}

__device__ __forceinline__ uint64_t ring_desc(uint32_t lo) { return (RING & ~uint64_t(0xFFFFFFFFu)) | lo; }
__device__ __forceinline__ void qk_tile(float (&S)[32], const uint32_t (&Q)[16], uint32_t dk) {
  wgmma64_reuse<0>(S, &Q[0], ring_desc(dk), blockIdx.y);
#pragma unroll
  for (int s = 1; s < 4; s++) wgmma64_acc<0>(S, &Q[4 * s], ring_desc(dk + s * 2));
}
__device__ __forceinline__ void qk_shift(float (&S)[32], const uint32_t (&nm)[4]) { wgmma64_acc<0>(S, nm, (uint64_t)((SM_BASE + SM_ONE) >> 4)); }
constexpr uint32_t RING_K = (uint32_t)RING, V_STEP = 1u - (1u << 16);
constexpr uint32_t RING_V = (SM_BASE >> 4) | (((SM_STG + 2 * TILE_BYTES) >> 4) << 16);
__device__ __forceinline__ void pv_tile(float (&O)[36], const uint32_t (&P)[16], uint32_t dv, uint32_t pad) {
#pragma unroll
  for (int s = 0; s < 4; s++) wgmma72_acc(O, &P[4 * s], ring_desc(dv + s * 128 * V_STEP + (s < 2 ? 0 : (s - 1) * pad)));
}
__device__ __forceinline__ void attn_step(const float (&Sc)[32], float (&Sn)[32], uint32_t (&Pc)[16], uint32_t (&Pp)[16], float (&O)[36],
                                          const uint32_t (&Q)[16], const uint32_t (&nm)[4], uint32_t dk, uint32_t dv, bool next, bool prev) {
  if (next) {
    WG_FENCE();
    qk_tile(Sn, Q, dk);
    qk_shift(Sn, nm);
  }
  if (prev) {
    WG_FENCE();
    pv_tile(O, Pp, dv, 0);
  }
  WG_COMMIT();
  SCHED();
#pragma unroll
  for (int i = 0; i < 16; i++) Pc[i] = pack2(ex2_hw(Sc[2 * i]), ex2_hw(Sc[2 * i + 1]));
  pin(Pc);
  SCHED();
}
template <int R> __device__ __forceinline__ float tile_max(const float (&S)[32]) {
  float t[4];
#pragma unroll
  for (int j = 0; j < 4; j++) t[j] = fmaxf(fmaxf(S[8 * j + R], S[8 * j + R + 1]), fmaxf(S[8 * j + R + 4], S[8 * j + R + 5]));
  float n = fmaxf(fmaxf(t[0], t[1]), fmaxf(t[2], t[3]));
  n = fmaxf(n, __shfl_xor_sync(0xffffffffu, n, 1));
  return fmaxf(n, __shfl_xor_sync(0xffffffffu, n, 2));
}
__device__ __forceinline__ void attention_exact(float (&O)[36], const uint32_t (&Q)[16], const Scratch* sc, int bh, int lane, int half) {
  const char* kb = (const char*)&sc->kv[bh][0][0][0];
  const char* vb = (const char*)&sc->kv[bh][1][0][0];
  const int g = lane >> 2, q = lane & 3;
  float m0 = -INFINITY, m1 = -INFINITY, l0 = 0.f, l1 = 0.f;
  float o[4][4] = {};
#pragma unroll 1
  for (int k0 = 0; k0 < T_SEQ; k0 += 8) {
    float s[4] = {0.f, 0.f, 0.f, 0.f};
#pragma unroll
    for (int c = 0; c < 8; c++) hmma8(s, &Q[2 * c], __ldcg((const uint32_t*)(kb + (k0 + g) * 128 + ((c ^ g) << 4) + q * 4)));
    float n0 = fmaxf(s[0], s[1]), n1 = fmaxf(s[2], s[3]);
    n0 = fmaxf(n0, __shfl_xor_sync(0xffffffffu, n0, 1)); n1 = fmaxf(n1, __shfl_xor_sync(0xffffffffu, n1, 1));
    n0 = fmaxf(m0, fmaxf(n0, __shfl_xor_sync(0xffffffffu, n0, 2))); n1 = fmaxf(m1, fmaxf(n1, __shfl_xor_sync(0xffffffffu, n1, 2)));
    const float a0 = ex2_hw(m0 - n0), a1 = ex2_hw(m1 - n1);
    m0 = n0; m1 = n1;
    const uint32_t pp[2] = {pack2(ex2_hw(s[0] - n0), ex2_hw(s[1] - n0)), pack2(ex2_hw(s[2] - n1), ex2_hw(s[3] - n1))};
    l0 = fmaf(l0, a0, bf_lo(pp[0]) + bf_hi(pp[0])); l1 = fmaf(l1, a1, bf_lo(pp[1]) + bf_hi(pp[1]));
#pragma unroll
    for (int j = 0; j < 4; j++) {
      const int c = 4 * half + j;
      const uint32_t v0 = __ldcg((const uint16_t*)(vb + (k0 + 2 * q) * 128 + ((c ^ (2 * q)) << 4) + g * 2));
      const uint32_t v1 = __ldcg((const uint16_t*)(vb + (k0 + 2 * q + 1) * 128 + ((c ^ (2 * q + 1)) << 4) + g * 2));
      o[j][0] *= a0; o[j][1] *= a0; o[j][2] *= a1; o[j][3] *= a1;
      hmma8(o[j], pp, v0 | (v1 << 16));
    }
  }
  l0 += __shfl_xor_sync(0xffffffffu, l0, 1); l1 += __shfl_xor_sync(0xffffffffu, l1, 1);
  O[32] = l0 + __shfl_xor_sync(0xffffffffu, l0, 2); O[34] = l1 + __shfl_xor_sync(0xffffffffu, l1, 2);
#pragma unroll
  for (int i = 0; i < 16; i++) O[i] = o[i >> 2][i & 3];
}

__device__ __forceinline__ uint32_t fill_entry(int f, int r) {
  int m, x = r, y, dx = 0;
  if (f < F_QKV || f >= 48) {
    const int i = f & 15;
    m = f < F_QKV ? M_FF1A : M_FF2A;
    if (i < 8) { x = 4 * r + ((0xE2u >> i) & 1) * 2; y = r ^ ((0xE790u >> (2 * i)) & 3); dx = 1; }
    else { m++; x = r ^ (((i >> 1) - 3) & 3); y = 4 * r + 2 * (i & 1); }
  } else if (f < F_KV) {
    const int i = f - F_QKV;
    m = M_QKV;
    if (i == 1 || i >= 5) { y = r ^ (i == 1 ? 0 : 2); }
    else { x = 4 + r; y = r ^ (i ? i - 1 : 0); dx = 4; }
  } else if (f >= F_PW1 && f < F_PW2) {
    m = M_PW1; y = r ^ (f - F_PW1); dx = 4;
  } else {
    m = f < F_PW1 ? M_WO : M_PW2; y = r ^ ((f & 1) * 2);
  }
  return m | (x << 4) | (y << 8) | (dx << 16);
}
__device__ __forceinline__ void tma_fill(uint32_t st, const CUtensorMap* map, uint32_t x, uint32_t y, uint32_t x2, uint32_t y2) {
  asm volatile("{\n.reg .pred p;\nelect.sync _|p, 0xffffffff;\n"
               "@p mbarrier.arrive.expect_tx.shared::cta.b64 _, [%1], 16384;\n"
               "@p cp.async.bulk.tensor.2d.shared::cluster.global.mbarrier::complete_tx::bytes [%0], [%2, {%3, %4}], [%1];\n"
               "@p cp.async.bulk.tensor.2d.shared::cluster.global.mbarrier::complete_tx::bytes [%0 + 8192], [%2, {%5, %6}], [%1];\n}"
               :: "r"(SM_BASE + st * STAGE_BYTES), "r"(SM_BASE + SM_FULL + st * 8), "l"(map), "r"(x), "r"(y), "r"(x2), "r"(y2) : "memory");
}
template <int F0, int N> __device__ __forceinline__ void weight_fills(const Params& p, uint32_t entry) {
  uint32_t st = F0 % NSTAGE, parity = ((F0 / NSTAGE) & 1) ^ 1, e = __shfl_sync(0xffffffffu, entry, 0);
#pragma unroll 1
  for (int i = 1; i <= N; i++) {
    const uint32_t x = (e << 2) & 0x3C0, y = (e >> 2) & 0x3FC0, dx = (e >> 16) << 6;
    const CUtensorMap* map = &p.map[e & 15];
    e = __shfl_sync(0xffffffffu, entry, i);
    mbar_wait(SM_BASE + SM_EMPTY + st * 8, parity);
    tma_fill(st, map, x, y, x + dx, dx ? y : y ^ 64);
    if (++st == NSTAGE) { st = 0; parity ^= 1; }
  }
}
__device__ __forceinline__ uint32_t kv_poll(const uint32_t* flag, uint32_t prev) {
  uint32_t v;
  asm volatile("ld.relaxed.gpu.global.u32 %0, [%1];" : "=r"(v) : "l"(flag) : "memory");
  return __ballot_sync(0xffffffffu, v - 1 == prev);
}
__device__ __forceinline__ void kv_fills(const Scratch* sc, int bh, int kind, uint32_t prev, const uint32_t* flag, uint32_t ready) {
#pragma unroll 1
  for (int j = 0; j < 8; j++) {
    uint32_t spin = 0;
#pragma unroll 1
    while (((ready >> (2 * j)) & 3) != 3 && ++spin < SPIN_LIMIT) ready = kv_poll(flag, prev);
    const uint32_t st = (j < 6 ? 4 * (j >> 1) : 0) + (j & 1) + 2 * kind;
    mbar_wait(SM_BASE + SM_EMPTY + st * 8, j < 6);
    asm volatile("{\n.reg .pred p;\nelect.sync _|p, 0xffffffff;\n"
                 "@p mbarrier.arrive.expect_tx.shared::cta.b64 _, [%1], 16384;\n"
                 "@p cp.async.bulk.shared::cluster.global.mbarrier::complete_tx::bytes [%0], [%2], 16384, [%1];\n}"
                 :: "r"(SM_BASE + st * STAGE_BYTES), "r"(SM_BASE + SM_FULL + st * 8), "l"(sc->kv[bh][kind][2 * j]) : "memory");
    PROF_AT(256 + 512 + (10 + kind * 8 + j) * 4);
  }
}
__device__ __forceinline__ void l2_prefetch(const void* p, uint32_t total, int b) {
  const uint32_t part = total / NCTA;
  asm volatile("cp.async.bulk.prefetch.L2.global [%0], %1;" :: "l"((const char*)p + (size_t)b * part), "r"(part) : "memory");
}

__global__ void __launch_bounds__(384, 1) conformer_kernel(Scratch* __restrict__ sc, __nv_bfloat16* __restrict__ out,
                                                           const __nv_bfloat16* __restrict__ dw, const __nv_bfloat16* __restrict__ xin,
                                                           const __nv_bfloat16* __restrict__ w_ff1a, const __grid_constant__ Params p) {
  extern __shared__ __align__(1024) uint8_t smem[];
  const int tid = threadIdx.x, lane = tid & 31;
  const int b = blockIdx.x, r = b & 3, batch = b >> 6, t = (b >> 2) & 15;
  if ((uint32_t)__cvta_generic_to_shared(smem) != SM_BASE) return;
  if (tid < 256) {
    const int row = ((tid >> 1) & 48) + (lane >> 3), col = lane & 7;
    const bool isx = tid < 128;
    const char* src = isx ? (const char*)xin + ((size_t)batch * T_SEQ + t * 64 + row) * 512 : (const char*)w_ff1a + (64 * r + row) * 2048 + r * 512;
    const int pitch = isx ? 2048 : 8192, left = isx ? T_SEQ - t * 64 - row : 64;
#pragma unroll
    for (int c = 0; c < 4; c++) {
#pragma unroll
      for (int i = 0; i < 4; i++) {
        const bool in = 4 * i < left;
        asm volatile("cp.async.cg.shared.global [%0], [%1], 16, %2;"
                     :: "r"(SM_BASE + (isx ? SM_STG + (3 - c) * TILE_BYTES : c * TILE_BYTES) + (row + 4 * i) * 128 + ((col ^ ((row + 4 * i) & 7)) << 4)),
                        "l"(src + (in ? i * pitch + (isx ? r ^ c : c) * 128 + col * 16 : 0) - (left > 0 ? 0 : 32 * 512)), "r"(in ? 16 : 0) : "memory");
      }
      asm volatile("cp.async.commit_group;" ::: "memory");
    }
  } else if (tid == 352) {
    l2_prefetch(w_ff1a, 256 * 1024 * 2, b);
  }
  const int cw = __shfl_sync(0xffffffffu, tid >> 5, 0), wg = cw >> 2, w = cw & 3;
  PROF_MARK(0);
  PROF_TIME(30);

  if (wg == 2) {
    asm volatile("setmaxnreg.dec.sync.aligned.u32 40;");
    if (cw == 8) {
      if (lane == 0) {
        asm volatile("prefetch.tensormap [%0];" :: "l"(&p.map[M_FF1A]) : "memory");
#pragma unroll
        for (int i = 0; i < NSTAGE; i++) mbar_init(SM_BASE + SM_FULL + i * 8, 1);
        fence_async_smem();
      }
      __syncwarp();
      bar_arrive(0, 320);
      PROF_MARK(9);
#pragma unroll
      for (int f = 2; f < 8; f++) {
        const uint32_t x = 256 * r + ((0xE2u >> f) & 1) * 128, y = (r ^ ((0xE790u >> (2 * f)) & 3)) * 64;
        tma_fill(f, &p.map[M_FF1A], x, y, x + 64, y);
      }
      PROF_MARK(1);
      uint32_t entry[2];
#pragma unroll 1
      for (int i = 0; i < 2; i++) { entry[1] = fill_entry(8 + i * 32 + lane, r); if (i == 0) entry[0] = entry[1]; }
      bar_sync(BAR_INIT, 64);
      weight_fills<8, F_KV - 8>(p, entry[0]);
      mbar_wait(SM_BASE + SM_EMPTY + (F_WO % NSTAGE) * 8, 1);
      weight_fills<F_WO, F_TOTAL - F_WO>(p, entry[1]);
    } else if (here(cw) != 11) {
      const int kind = w - 1;
      const uint32_t prev = launch_index(sc);
      if (kind == 0) {
        if (lane == 0) {
#pragma unroll
          for (int i = 0; i < NSTAGE; i++) mbar_init(SM_BASE + SM_EMPTY + i * 8, 4);
        }
        __syncwarp();
        bar_arrive(0, 320);
        bar_arrive(BAR_INIT, 64);
      }
      const uint32_t* flag = sc->flag[batch * 4 + r][kind * 16 + (lane & 15)];
      const uint32_t ready = kv_poll(flag, prev);
      if (kind == 0) bar_sync(BAR_K, 160); else bar_sync(BAR_V, 160);
      if (lane == 0) {
        asm volatile("cp.async.bulk.global.shared::cta.bulk_group [%0], [%1], %2;"
                     :: "l"(&sc->kv[batch * 4 + r][kind][t][0]), "r"(SM_BASE + SM_STG + kind * TILE_BYTES), "r"(TILE_BYTES) : "memory");
PROF_MARK(4 + kind * 2);
        asm volatile("cp.async.bulk.commit_group;\ncp.async.bulk.wait_group 0;" ::: "memory");
PROF_MARK(5 + kind * 2);
        asm volatile("st.relaxed.gpu.global.u32 [%0], %1;" :: "l"(sc->flag[batch * 4 + r][kind * 16 + t]), "r"(prev + 1) : "memory");
      }
      __syncwarp();
      kv_fills(sc, batch * 4 + r, kind, prev, flag, ready);
    } else {
      const uint32_t* watch = sc->step[(b & ~3) + (lane & 3)];
      uint32_t seen;
      asm volatile("ld.relaxed.gpu.global.u32 %0, [%1];" : "=r"(seen) : "l"(watch) : "memory");
#pragma unroll 1
      for (int i = 0; i < 22; i++) {
        const uint32_t t0 = clock_now();
        uint4* dst = &sc->x[b][i * 96 + lane];
        st_vec(dst, 0u, 0u, 0u, 0u); st_vec(dst + 32, 0u, 0u, 0u, 0u); st_vec(dst + 64, 0u, 0u, 0u, 0u);
        if (i == PF_AT && lane == 0) {
          asm volatile("prefetch.tensormap [%0];" :: "l"(&p.map[M_FF1B]) : "memory");
          l2_prefetch(p.w_ff1b, 1024 * 256 * 2, b);
          l2_prefetch(p.w_qkv, 256 * 768 * 2, b);
          l2_prefetch(p.w_pw1, 256 * 512 * 2, b);
          l2_prefetch(p.w_ff2a, 256 * 1024 * 2, b);
        }
        while (clock_now() - t0 < CLR_PACE) {}
      }
      PROF_MARK(28);
      asm volatile("fence.acq_rel.gpu;" ::: "memory");
      __syncwarp();
      announce(sc, lane == 0);
      if (lane == 0) {
        l2_prefetch(p.w_o, 256 * 256 * 2, b);
        l2_prefetch(p.w_pw2, 256 * 256 * 2, b);
        l2_prefetch(p.w_ff2b, 1024 * 256 * 2, b);
#pragma unroll
        for (int i = M_QKV; i < M_COUNT; i++) asm volatile("prefetch.tensormap [%0];" :: "l"(&p.map[i]) : "memory");
      }
      PROF_MARK(2);
      uint32_t want = seen & ~15u;
#pragma unroll 1
      for (int k = 0; k < 8; k++) {
        want += 2;
        uint32_t spin = 0;
#pragma unroll 1
        while (__any_sync(0xffffffffu, (int)(seen - want) < 0) && ++spin < SPIN_LIMIT)
          asm volatile("ld.relaxed.gpu.global.u32 %0, [%1];" : "=r"(seen) : "l"(watch) : "memory");
        bar_arrive(BAR_GO, 160);
        PROF_MARK(32 + k);
      }
    }
  } else {
    asm volatile("setmaxnreg.inc.sync.aligned.u32 232;");
    const int q = lane & 3, th = tid & 127;
    constexpr uint32_t stg = SM_BASE + SM_STG;
    const uint32_t mrow = 16 * w + (lane & 15);
    const uint32_t maddr = stg + mrow * 128 + (((lane >> 4) ^ (lane & 7)) << 4);
    const uint32_t qslot = stg + 2 * TILE_BYTES + w * 2048 + lane * 16;
    uint4* const xp = &sc->x[b][th];
    const int nvalid = T_SEQ - t * 64, row0 = 16 * w + (lane >> 2);

    uint32_t A[4][16];
    uint32_t st[4];
    bar_sync(0, 320);
    if (wg == 0) {
      RowAcc ra = {};
      cp_async_wait(3);
      __syncwarp();
      PROF_MARK0(45);
      tile_load(maddr + 3 * TILE_BYTES, A[0]);
#pragma unroll
      for (int c = 1; c < 4; c++) {
        cp_async_wait(3 - c);
        __syncwarp();
        tile_load(maddr + (3 - c) * TILE_BYTES, A[c]);
        row_acc(ra, A[c - 1]);
      }
      PROF_MARK(1);
      row_acc(ra, A[3]);
      PROF_MARK0(46);
      const float m0 = ra.s[0] * (1.f / DM), m1 = ra.s[2] * (1.f / DM);
      st[0] = pack2(m0, m0); st[1] = pack2(m1, m1);
      centre(A[0], st[0], st[1]);
      const float2 sq = row_squares(ra, lane & 4);
      st[2] = __float_as_uint(fmaf(-m0, m0, sq.x * (1.f / DM))); st[3] = __float_as_uint(fmaf(-m1, m1, sq.y * (1.f / DM)));
    } else {
      if (th < 112) sts128(SM_BASE + SM_CS + th * 16, 0, 0, 0, 0);
      sts32(SM_BASE + SM_EYE + th * 4, th >= 96 ? 0x3F803F80u : ((th & 32) == 0 && (th & 3) == ((th >> 3) & 3)) ? (0x3F00u << ((th & 4) * 4)) : 0u);
#pragma unroll
      for (int i = 0; i < 2; i++) {
        cp_async_wait(2 - 2 * i);
        fence_async_smem();
        bar_sync(BAR_WG1, 128);
        if (th == 0) mbar_arrive(SM_BASE + SM_FULL + i * 8);
      }
      PROF_MARK(6);
      const uint32_t tag = ~launch_index(sc) & 1;
      mbar_wait(SM_BASE + SM_FULL + 4 * 8, 0);
      PROF_MARK(5);
      if (b < 72) {
        const __nv_bfloat16* wp; int ld, col;
        if (b < 24) { wp = p.w_qkv; ld = 768; col = b * 32; }
        else if (b < 40) { wp = p.w_pw1; ld = 512; col = (b - 24) * 32; }
        else { wp = p.w_ff2a; ld = 1024; col = (b - 40) * 32; }
        const uint4* src = (const uint4*)(wp + (size_t)(th >> 2) * ld + col + q * 8);
        float c[8] = {0.f, 0.f, 0.f, 0.f, 0.f, 0.f, 0.f, 0.f};
#pragma unroll 1
        for (int h = 0; h < 2; h++, src += 16 * ld) {
#pragma unroll
          for (int i = 0; i < 4; i++) {
            const uint4 v = __ldg(src + i * 4 * ld);
            c[0] += bf_lo(v.x); c[1] += bf_hi(v.x); c[2] += bf_lo(v.y); c[3] += bf_hi(v.y);
            c[4] += bf_lo(v.z); c[5] += bf_hi(v.z); c[6] += bf_lo(v.w); c[7] += bf_hi(v.w);
          }
        }
#pragma unroll 1
        for (int m = 4; m <= 16; m <<= 1)
#pragma unroll
          for (int k = 0; k < 8; k++) c[k] += __shfl_xor_sync(0xffffffffu, c[k], m);
        if (lane < 4) {
          const uint32_t a = SM_BASE + SM_CS + 1792 + w * 128 + lane * 32;
          sts128(a, __float_as_uint(c[0]), __float_as_uint(c[1]), __float_as_uint(c[2]), __float_as_uint(c[3]));
          sts128(a + 16, __float_as_uint(c[4]), __float_as_uint(c[5]), __float_as_uint(c[6]), __float_as_uint(c[7]));
        }
        bar_sync(BAR_WG1, 128);
        if (th < 8) {
          float o[4] = {0.f, 0.f, 0.f, 0.f};
#pragma unroll 1
          for (int k = 0; k < 4; k++) {
            uint32_t e[4];
            lds128(SM_BASE + SM_CS + 1792 + k * 128 + th * 16, e[0], e[1], e[2], e[3]);
#pragma unroll
            for (int i = 0; i < 4; i++) o[i] += __uint_as_float(e[i]);
          }
          st_vec(&sc->cs[b * 8 + th], (__float_as_uint(o[0]) & ~1u) | tag, __float_as_uint(o[1]), __float_as_uint(o[2]), __float_as_uint(o[3]));
        }
      }
      bar_sync(BAR_WG1, 128);
      PROF_MARK(2);
      if (th < 72) {
        const int j = th >> 3, i = (th & 7) * 2;
        int src;
        if (j < CS_PW1) src = 320 + 64 * r + 16 * j;
        else if (j < CS_QKV) src = 192 + (j - CS_PW1) * 64 + 16 * r;
        else src = ((j - CS_QKV + 1) % 3) * 64 + 16 * r;
        uint32_t e[8], hi[4], lo[4], spin = 0;
#pragma unroll 1
        do {
          ld_vec(&sc->cs[src + i], e[0], e[1], e[2], e[3]);
          ld_vec(&sc->cs[src + i + 1], e[4], e[5], e[6], e[7]);
        } while ((((e[0] ^ tag) | (e[4] ^ tag)) & 1u) && ++spin < SPIN_LIMIT);
        e[0] &= ~1u; e[4] &= ~1u;
#pragma unroll
        for (int k = 0; k < 4; k++) {
          const float c0 = __uint_as_float(e[2 * k]), c1 = __uint_as_float(e[2 * k + 1]);
          hi[k] = pack2(c0, c1);
          lo[k] = pack2(c0 - bf_lo(hi[k]), c1 - bf_hi(hi[k]));
        }
        const uint32_t a = SM_BASE + SM_CS + j * 256 + i * 8;
        sts128(a ^ ((a >> 3) & 0x70), hi[0], hi[1], hi[2], hi[3]);
        sts128((a + 128) ^ (((a + 128) >> 3) & 0x70), lo[0], lo[1], lo[2], lo[3]);
      }
      fence_async_smem();
      PROF_MARK(4);
      bar_arrive(BAR_CS, 256);
    }

#pragma unroll 1
    for (uint32_t pass = 0; pass < 2; pass++) {
      uint32_t Q[16];
      if (wg == 0) {
        float acc[4][32];
        uint32_t H[4][16];
        if (!pass) { PROF_MARK(47); ACQUIRE(0); }
        mma_tile<true>(acc[0], A[0], LO(0)); mma_tile<true>(acc[1], A[0], HI(0));
        if (!pass) ACQUIRE(1);
        mma_tile<true>(acc[2], A[0], LO(1)); mma_tile<true>(acc[3], A[0], HI(1));
        if (pass) {
          gather_first<1, X_AG0>(A, st, sc, xp, 1);
        } else {
          centre(A[1], st[0], st[1]);
          acquire_n<2, 3>();
        }
        mma_tile<false>(acc[0], A[1], LO(2)); mma_tile<false>(acc[1], A[1], HI(2));
        if (pass) {
          gather_rest<1, X_AG0>(A, xp, 1);
          RELEASE(F_PW2, F_PW2 + 1);
        } else {
          centre(A[2], st[0], st[1]); centre(A[3], st[0], st[1]);
        }
        PROF_MARK2(2, 18);
        mma_tile<false>(acc[0], A[2], LO(3)); mma_tile<false>(acc[0], A[3], LO(4));
        WG_WAIT(4);
        RELEASE(0, 1);
        uint32_t mu[4] = {0u, 0u, 0u, 0u};
        float rs0, rs1, tn[2][4];
        if (pass) {
          const RowNorm n = stat_finish(sc, st, 1, 0.5f);
          rs0 = n.rs0; rs1 = n.rs1;
          mean_frag(mu, n, q == 0);
        } else {
          const int src = (lane & 28) | (lane >> 3);
          rs0 = 0.5f * rsqrt_hw(fmaxf(__uint_as_float(__shfl_sync(0xffffffffu, st[2], src)), 0.f) + LN_EPS);
          rs1 = 0.5f * rsqrt_hw(fmaxf(__uint_as_float(__shfl_sync(0xffffffffu, st[3], src)), 0.f) + LN_EPS);
        }
        pin(mu);
        mma_fold<2 * CS_FF2>(acc[0], mu);
        mma_tile<false>(acc[1], A[2], HI(3));
#define SEGS(a, b) silu_segs<a, b>(acc, tn, H, rs0, rs1)
        WG_WAIT(1); pin(acc[0]);
        SEGS(0, 1);
        mma_tile_fold<2 * CS_FF2 + 2>(acc[1], A[3], HI(4), mu);
        SEGS(1, 3);
        uint32_t ok = probe_n<5, 3>();
        SEGS(3, 4);
        settle_n<5, 3>(ok);
        mma_tile<false>(acc[2], A[1], LO(5));
        SEGS(4, 6);
        mma_tile<false>(acc[2], A[2], LO(6));
        SEGS(6, 8);
        WG_WAIT(2); pin(acc[1]);
        RELEASE(2, 4);
        SEGS(8, 9);
        mma_tile_fold<2 * CS_FF2 + 4>(acc[2], A[3], LO(7), mu);
        SEGS(9, 12);
        mma_tile<false>(acc[3], A[1], HI(5));
        SEGS(12, 14);
        mma_tile<false>(acc[3], A[2], HI(6));
        SEGS(14, 16);
        WG_WAIT(2); pin(acc[2]);
        SEGS(16, 17);
        mma_tile_fold<2 * CS_FF2 + 6>(acc[3], A[3], HI(7), mu);
        SEGS(17, 19);
        ok = probe_n<8, 2>();
        SEGS(19, 20);
        settle_n<8, 2>(ok);
        mma_tile_reuse(acc[1], H[0], LO(8));
        SEGS(20, 22);
        mma_tile<false>(acc[1], H[1], HI(8));
        SEGS(22, 24);
        WG_WAIT(2); pin(acc[3]);
        RELEASE(5, 7);
        SEGS(24, 26);
        mma_tile<false>(acc[1], H[2], LO(9));
        SEGS(26, 27);
        ok = probe_n<10, 2>();
        SEGS(27, 28);
        settle_n<10, 2>(ok);
        mma_tile_reuse(acc[2], H[0], LO(10));
        SEGS(28, 31);
        mma_tile<false>(acc[2], H[1], HI(10));
        SEGS(31, 34);
#undef SEGS
        PROF_MARK2(3, 19);
        const uint32_t rtag = here(pass ^ 1);
        const uint4* rs_in = xp + X_RS;
        mma_tile<false>(acc[1], H[3], HI(9));
        mma_tile<false>(acc[2], H[2], LO(11));
        ok = probe_n<12, 2>();
        uint4* rs_out = peer<1>(xp) + X_RS;
        mma_tile<false>(acc[2], H[3], HI(11));
        settle_n<12, 2>(ok);
        if (!pass) bar_sync(BAR_GO, 160);
        WG_WAIT(2); pin(acc[1]);
        RELEASE(8, 9);
        send_half<0>(rs_out, acc[1], rtag);
        mma_tile_reuse(acc[3], H[0], LO(12));
        SCHED();
        send_half<1>(rs_out, acc[1], rtag);
        mma_tile<false>(acc[3], H[1], HI(12));
        rs_out = peer<2>(xp) + X_RS + 512;
        WG_WAIT(2); pin(acc[2]);
        send_half<0>(rs_out, acc[2], rtag);
        mma_tile<false>(acc[3], H[2], LO(13));
        SCHED();
        ok = probe_n<14, 2>();
        send_half<1>(rs_out, acc[2], rtag);
        mma_tile<false>(acc[3], H[3], HI(13));
        settle_n<14, 2>(ok);
        mma_tile_reuse(acc[1], H[0], LO(14));
        rs_out = peer<3>(xp) + X_RS + 1024;
        announce(sc, tid == 0);
        fetch(rs_in, A[1]);
        SCHED();
        mma_tile<false>(acc[1], H[1], HI(14));
        WG_WAIT(2); pin(acc[3]);
        send_half<0>(rs_out, acc[3], rtag);
        send_half<1>(rs_out, acc[3], rtag);
        mma_tile<false>(acc[1], H[2], LO(15)); mma_tile<false>(acc[1], H[3], HI(15));
        SCHED();
        fetch(rs_in + 512, A[2]);
        SCHED();
        res_load(maddr, acc[2]);
        bar_sync(BAR_GO, 160);
        fetch(rs_in + 1024, A[3]);
        if (!pass) acquire_n<F_QKV, 3>();
        {
          uint32_t spin = 0;
          while (__builtin_expect(stale(miss(A[1], rtag) | miss(A[2], rtag) | miss(A[3], rtag)), 0) && ++spin < SPIN_LIMIT) {
            if (stale(miss(A[1], rtag) | miss(A[2], rtag))) { fetch(rs_in, A[1]); fetch(rs_in + 512, A[2]); }
            fetch(rs_in + 1024, A[3]);
          }
        }
        announce(sc, tid == 0 && !pass);
        mma_add_half(acc[2], A[1]);
        mma_add_half(acc[2], A[2]);
        mma_add_half(acc[2], A[3]);
        PROF_MARK2(4, 20);
        WG_WAIT(0); pin(acc[2]); pin(acc[1]);
#pragma unroll
        for (int i = 0; i < 16; i++) A[0][i] = pack2(fmaf(acc[1][2 * i], 0.5f, acc[2][2 * i]), fmaf(acc[1][2 * i + 1], 0.5f, acc[2][2 * i + 1]));
        if (pass) {
          PROF_MARK(21);
          stat_publish(A[0], sc, here(th), 0);
          stat_fetch(sc, st);
          const RowNorm fn = stat_finish(sc, st, 0, 1.f);
          const float nm0 = -fn.m0 * fn.rs0, nm1 = -fn.m1 * fn.rs1;
#pragma unroll
          for (int i = 0; i < 16; i++) {
            const float rs = (i & 1) ? fn.rs1 : fn.rs0, nm = (i & 1) ? nm1 : nm0;
            A[0][i] = pack2(fmaf(bf_lo(A[0][i]), rs, nm), fmaf(bf_hi(A[0][i]), rs, nm));
          }
          tile_store(here(maddr), A[0]);
          __syncwarp();
          const int row = 16 * w + (lane >> 3);
          uint4* dst = (uint4*)(out + ((size_t)batch * T_SEQ + t * 64 + row) * DM + 64 * r) + (lane & 7);
          const uint32_t src = stg + row * 128 + (((lane & 7) ^ (lane >> 3)) << 4);
#pragma unroll
          for (int i = 0; i < 4; i++) {
            uint4 v;
            lds128((src ^ ((i & 1) << 6)) + i * 512, v.x, v.y, v.z, v.w);
            if (row + 4 * i < nvalid) dst[i * 4 * (DM / 8)] = v;
          }
          PROF_MARK(22);
          PROF_TIME(31);
          break;
        }
        send_residual(A[0], sc, xp, maddr, 1);
        PROF_MARK(5);
        mma_tile<true>(acc[0], A[0], LO(F_QKV)); mma_tile<true>(acc[1], A[0], HI(F_QKV));
        mma_tile<true>(acc[2], A[0], LO(F_QKV + 1));
        gather_first<1, X_AG0>(A, st, sc, xp, 1);
        mma_tile<false>(acc[0], A[1], LO(F_QKV + 2)); mma_tile<false>(acc[1], A[1], HI(F_QKV + 2));
        acquire_n<F_QKV + 3, 3>();
        bar_sync(BAR_CS, 256);
        gather_rest<1, X_AG0>(A, xp, 1);
        PROF_MARK(6);
        mma_tile<false>(acc[0], A[2], LO(F_QKV + 3)); mma_tile<false>(acc[0], A[3], LO(F_QKV + 4));
        SCHED();
        {
          const RowNorm n = stat_finish(sc, st, 1, 1.f);
          rs0 = row0 < nvalid ? n.rs0 : 0.f; rs1 = row0 + 8 < nvalid ? n.rs1 : 0.f;
          mean_frag(mu, n, q == 3);
        }
        mma_fold<2 * CS_QKV - 6>(acc[0], mu);
        RELEASE(10, 15);
        WG_WAIT(0); pin(acc[0]);
        scale_pack(acc[0], Q, rs0, rs1);
        tile_store(here(maddr), Q);
        SCHED();
        mma_tile<false>(acc[1], A[2], HI(F_QKV + 3));
        fence_async_smem();
        bar_arrive(BAR_K, 160);
        mma_tile_fold<2 * CS_QKV - 4>(acc[1], A[3], HI(F_QKV + 4), mu);
        mma_tile<false>(acc[2], A[1], HI(F_QKV + 1)); mma_tile<false>(acc[2], A[2], LO(F_QKV + 5));
        WG_WAIT(2); pin(acc[1]);
        scale_pack(acc[1], Q, rs0, rs1);
        tile_store(here(maddr) + TILE_BYTES, Q);
        fence_async_smem();
        bar_arrive(BAR_V, 160);
        mma_tile_fold<2 * CS_QKV - 2>(acc[2], A[3], HI(F_QKV + 5), mu);
        WG_WAIT(0); pin(acc[2]);
        scale_pack(acc[2], Q, rs0 * SM_SCALE_LOG2, rs1 * SM_SCALE_LOG2);
        frag_store(here(qslot), Q);
        bar_arrive(BAR_Q, 256);
        RELEASE(F_QKV, F_QKV + 5);
      } else {
        bar_sync(BAR_Q, 256);
#pragma unroll
        for (int s = 0; s < 4; s++) lds128(qslot + s * 512, Q[4 * s], Q[4 * s + 1], Q[4 * s + 2], Q[4 * s + 3]);
        if (w < 2) {
          const uint32_t v = w ? 0u : 0x3F803F80u;
#pragma unroll
          for (int s = 0; s < 4; s++) sts128(qslot + s * 512, v, v, v, v);
          fence_async_smem();
        }
      }
      bar_sync(BAR_ATT, 256);
      PROF_MARK(7);

      const int dir = cw == 0 ? -1 : 1;
      uint32_t tap[15];
      {
        const uint32_t* dwp = (const uint32_t*)(dw + 64 * r) + lane + 7 * (DM / 2);
#pragma unroll
        for (int k = 0; k < 15; k++) tap[k] = __ldg(dwp + dir * (k - 7) * (DM / 2));
      }

      float O[36];
      {
        float S[2][32];
        uint32_t P[2][16], nm[4];
#pragma unroll
        for (int i = 0; i < 32; i++) { S[0][i] = 0.f; S[1][i] = 0.f; }
        pin(Q); pin(S[0]);
        WG_FENCE();
        qk_tile(S[0], Q, RING_K + (SM_STG >> 4));
        WG_COMMIT();
#pragma unroll
        for (int i = 0; i < 36; i++) O[i] = 0.f;
#pragma unroll
        for (int i = 0; i < 16; i++) P[1][i] = 0u;
        WG_WAIT(0); pin(S[0]);
        const float m0 = tile_max<0>(S[0]), m1 = tile_max<2>(S[0]);
        nm[0] = pack2(q ? 0.f : -m0, 0.f); nm[1] = pack2(q ? 0.f : -m1, 0.f); nm[2] = 0u; nm[3] = 0u;
#pragma unroll
        for (int k = 0; k < 15; k++) asm("mul.rn.bf16x2 %0, %0, %1;" : "+r"(tap[k]) : "r"(0x3F003F00u));
        pin(nm); pin(O); pin(P[1]); pin(tap);
        uint32_t sk = wg, sv = F_SPARE % NSTAGE + wg;
        mbar_wait(SM_BASE + SM_FULL + sv * 8, 1);
        mbar_wait(SM_BASE + SM_FULL + sk * 8, 0);
        if (wg == 1) bar_sync(BAR_ATT, 256);
        PROF_MARK(8);
        WG_FENCE();
        qk_tile(S[0], Q, RING_K + sk * 1024);
        qk_shift(S[0], nm);
        WG_COMMIT();
        WG_WAIT(0); pin(S[0]); pin(S[1]);
        if (wg == 0) bar_arrive(BAR_ATT, 256);
#pragma unroll 1
        for (int it = 0; it < 4; it++) {
          const uint32_t sn = it >= 2 ? wg : sk + 4;
          uint32_t ok = 1;
          mbar_probe(ok, SM_BASE + SM_FULL + sn * 8, it >= 2);
          mbar_probe(ok, SM_BASE + SM_FULL + (sk + 2) * 8, it == 3);
          attn_step(S[0], S[1], P[0], P[1], O, Q, nm, RING_K + sk * 1024 + 512, RING_V + (sv * 1024 + 512) * V_STEP, true, it > 0);
          PROF_MARK(24 + it * 3);
          if (__builtin_expect(!ok, 0)) {
            mbar_wait(SM_BASE + SM_FULL + sn * 8, it >= 2);
            mbar_wait(SM_BASE + SM_FULL + (sk + 2) * 8, it == 3);
          }
          WG_WAIT(0); pin(O); pin(S[1]); pin(P[1]);
          asm volatile("{\n.reg .pred p;\nsetp.eq.u32 p, %2, 0;\n@p mbarrier.arrive.shared::cta.b64 _, [%0];\n@p mbarrier.arrive.shared::cta.b64 _, [%1];\n}"
                       :: "r"(SM_BASE + SM_EMPTY + sk * 8), "r"(SM_BASE + SM_EMPTY + sv * 8), "r"(lane) : "memory");
          PROF_MARK(25 + it * 3);
          sv = sk + 2; sk = sn;
          attn_step(S[1], S[0], P[1], P[0], O, Q, nm, RING_K + sk * 1024, RING_V + (sv * 1024) * V_STEP, it < 3, true);
          WG_WAIT(0); pin(O); pin(S[0]); pin(P[0]);
          PROF_MARK(26 + it * 3);
        }
        WG_FENCE();
        pv_tile(O, P[1], RING_V + (sv * 1024 + 512) * V_STEP, wg << 22);
        WG_COMMIT();
        announce<1>(sc, th == 0);
        WG_WAIT(0); pin(O);
      }
      PROF_MARK(9);

      {
        const uint32_t mo = stg + here(th) * 16;
        sts64(mo + 5 * 4096 + wg * 8, __float_as_uint(O[32]), __float_as_uint(O[34]));
        if (wg == 0) {
#pragma unroll
          for (int i = 4; i < 8; i++)
            sts128(mo + i * 2048, __float_as_uint(O[4 * i]), __float_as_uint(O[4 * i + 1]), __float_as_uint(O[4 * i + 2]), __float_as_uint(O[4 * i + 3]));
        } else {
#pragma unroll
          for (int i = 0; i < 4; i++)
            sts128(mo + i * 2048, __float_as_uint(O[4 * i]), __float_as_uint(O[4 * i + 1]), __float_as_uint(O[4 * i + 2]), __float_as_uint(O[4 * i + 3]));
#pragma unroll
          for (int i = 0; i < 16; i++) O[i] = O[16 + i];
        }
        bar_sync(BAR_MERGE, 256);
        uint32_t e[4];
        lds128(mo + 5 * 4096, e[0], e[1], e[2], e[3]);
        O[32] = __uint_as_float(e[0]) + __uint_as_float(e[2]); O[34] = __uint_as_float(e[1]) + __uint_as_float(e[3]);
#pragma unroll
        for (int i = 0; i < 4; i++) {
          lds128(mo + wg * TILE_BYTES + i * 2048, e[0], e[1], e[2], e[3]);
#pragma unroll
          for (int k = 0; k < 4; k++) O[4 * i + k] += __uint_as_float(e[k]);
        }
        const bool safe = O[32] > 0x1p-60f && O[32] < 0x1p60f && O[34] > 0x1p-60f && O[34] < 0x1p60f;
        if (__builtin_expect(__any_sync(0xffffffffu, !safe), 0)) attention_exact(O, Q, sc, batch * 4 + r, lane, wg);
        const float i0 = rcp_hw(O[32]), i1 = rcp_hw(O[34]);
#pragma unroll
        for (int i = 0; i < 8; i++) { const float v = (i & 1) ? i1 : i0; A[0][i] = pack2(O[2 * i] * v, O[2 * i + 1] * v); }
        A[0][0] &= ~1u; A[0][4] &= ~1u;
        uint4* dst = xp + X_AG1 + wg * 256;
        SCHED();
        st_vec(dst, A[0][0], A[0][1], A[0][2], A[0][3]);
        st_vec(dst + 128, A[0][4], A[0][5], A[0][6], A[0][7]);
        SCHED();
      }
      if (wg == 1) {
        const uint32_t mo = stg + TILE_BYTES + here(th) * 16;
        sts128(mo, A[0][0], A[0][1], A[0][2], A[0][3]);
        sts128(mo + 2048, A[0][4], A[0][5], A[0][6], A[0][7]);
        bar_arrive(BAR_HALF, 256);
      } else {
        PROF_MARK(10);
        const uint32_t mo = stg + TILE_BYTES + here(th) * 16;
        bar_sync(BAR_HALF, 256);
        lds128(mo, A[0][8], A[0][9], A[0][10], A[0][11]);
        lds128(mo + 2048, A[0][12], A[0][13], A[0][14], A[0][15]);
        proj_residual<F_WO, 6>(A, sc, xp, maddr, 0, lane);
        PROF_MARK(12);
        float acc[2][32];
        mma_tile<true>(acc[0], A[0], LO(F_PW1)); mma_tile<true>(acc[1], A[0], HI(F_PW1));
        gather_first<1, X_AG0>(A, st, sc, xp, 0);
        mma_tile<false>(acc[1], A[1], HI(F_PW1 + 1)); mma_tile<false>(acc[0], A[1], LO(F_PW1 + 1));
        gather_rest<1, X_AG0>(A, xp, 0);
        PROF_MARK(13);
        mma_tile<false>(acc[1], A[2], HI(F_PW1 + 2)); mma_tile<false>(acc[1], A[3], HI(F_PW1 + 3));
        WG_WAIT(2);
        RELEASE(F_WO, F_PW1 + 1);
        SCHED();
        uint32_t mu[4];
        const RowNorm n = stat_finish(sc, st, 0, 0.5f);
        const float rs0 = row0 < nvalid ? n.rs0 : 0.f, rs1 = row0 + 8 < nvalid ? n.rs1 : 0.f;
        mean_frag(mu, n, q == 0);
        mma_fold<2 * CS_PW1 + 2>(acc[1], mu);
        mma_tile<false>(acc[0], A[2], LO(F_PW1 + 2));
        mma_tile_fold<2 * CS_PW1>(acc[0], A[3], LO(F_PW1 + 3), mu);
        WG_WAIT(2); pin(acc[1]);
#pragma unroll
        for (int i = 0; i < 32; i++) acc[1][i] = tanh_hw(acc[1][i] * ((i & 2) ? rs1 : rs0));
#pragma unroll
        for (int i = 0; i < 32; i++) { const float rs = (i & 2) ? rs1 : rs0; acc[1][i] = fmaf(acc[1][i], rs, rs); }
        pin(acc[1]);
        SCHED();
        WG_WAIT(0); pin(acc[0]);
#pragma unroll
        for (int i = 0; i < 16; i++) A[0][i] = pack2(acc[0][2 * i] * acc[1][2 * i], acc[0][2 * i + 1] * acc[1][2 * i + 1]);
        const uint32_t ga = stg + TILE_BYTES + here(mrow) * G_PITCH + (lane >> 4) * 16;
#pragma unroll
        for (int s = 0; s < 4; s++) stsm4(ga + s * 32, &A[0][4 * s]);
      }
      {
        const uint32_t gsrc = stg + TILE_BYTES + (8 * cw - 7) * G_PITCH + lane * 4;
        const bool edge = cw == 0 || cw == 7;
        const bool nbr = cw == 0 ? t > 0 : t < 15;
        uint4* const hdst = &sc->x[b + 4 * dir][X_HALO + (cw == 0 ? 96 : 0) + lane];
        uint32_t in[22];
        bar_sync(BAR_G, 256);
        PROF_MARK(14);
        if (cw == 0) {
#pragma unroll
          for (int i = 14; i >= 0; i--) in[i] = lds32(gsrc + (21 - i) * G_PITCH);
        } else {
#pragma unroll
          for (int i = 14; i >= 0; i--) in[i] = lds32(gsrc + i * G_PITCH);
        }
        if (edge) {
          if (nbr) {
            st_vec(hdst, HALO_TAG, in[14], in[13], in[12]);
            st_vec(hdst + 32, HALO_TAG, in[11], in[10], in[9]);
            st_vec(hdst + 64, HALO_TAG, in[8], 0u, 0u);
          }
        } else {
#pragma unroll
          for (int i = 15; i < 22; i++) in[i] = lds32(gsrc + i * G_PITCH);
        }
        if (cw == 0) PROF_MARK0(40);
        uint32_t cv[8];
#pragma unroll
        for (int i = 0; i < 15; i++)
#pragma unroll
          for (int o = 0; o < 8; o++) {
            if (i == o) asm("mul.rn.bf16x2 %0, %1, %2;" : "=r"(cv[o]) : "r"(in[i]), "r"(tap[0]));
            if (i > o) asm("fma.rn.bf16x2 %0, %1, %2, %0;" : "+r"(cv[o]) : "r"(in[i]), "r"(tap[i - o]));
          }
        pin(cv);
        if (cw == 0) PROF_MARK0(41);
        if (edge) {
#pragma unroll
          for (int i = 15; i < 22; i++) in[i] = 0u;
          if (nbr) {
            const uint4* src = &sc->x[b][X_HALO + (cw == 0 ? 0 : 96) + lane];
            uint32_t e0, e1, e2, u0, u1, spin = 0;
#pragma unroll 1
            do {
              ld_vec(src, e0, in[15], in[16], in[17]);
              ld_vec(src + 32, e1, in[18], in[19], in[20]);
              ld_vec(src + 64, e2, in[21], u0, u1);
            } while (__any_sync(0xffffffffu, ((e0 ^ HALO_TAG) | (e1 ^ HALO_TAG) | (e2 ^ HALO_TAG)) != 0) && ++spin < SPIN_LIMIT);
          }
          announce<1>(sc, lane == 0);
        }
#pragma unroll
        for (int i = 15; i < 22; i++)
#pragma unroll
          for (int o = 0; o < 8; o++)
            if (i - o <= 14) asm("fma.rn.bf16x2 %0, %1, %2, %0;" : "+r"(cv[o]) : "r"(in[i]), "r"(tap[i - o]));
        if (cw == 0) PROF_MARK0(42);
        if (cw == 7) PROF_MARK0(43);
        const uint32_t fl = cw == 0 ? 7 : 0;
        const uint32_t cdst = (stg + cw * 1024 + lane * 4) ^ (fl * 144);
#pragma unroll
        for (int o = 0; o < 8; o++) {
          const float a = bf_lo(cv[o]), c = bf_hi(cv[o]);
          sts32(cdst ^ (o * 144), pack2(fmaf(a, tanh_hw(a), a), fmaf(c, tanh_hw(c), c)));
        }
      }
      if (wg == 1) {
        bar_arrive(BAR_C, 256);
        break;
      }
      bar_sync(BAR_C, 256);
      tile_load(here(maddr), A[0]);
      PROF_MARK(15);
      publish(xp + X_AG1, A[0], 1);
      proj_residual<F_PW2, 2>(A, sc, xp, maddr, 1, lane);
      PROF_MARK(17);
    }
  }
}

typedef CUresult (*EncodeFn)(CUtensorMap*, CUtensorMapDataType, cuuint32_t, void*, const cuuint64_t*, const cuuint64_t*,
                             const cuuint32_t*, const cuuint32_t*, CUtensorMapInterleave, CUtensorMapSwizzle,
                             CUtensorMapL2promotion, CUtensorMapFloatOOBfill);

void make_map(EncodeFn fn, CUtensorMap* m, const void* w, int rows, int cols, CUtensorMapSwizzle swz) {
  const cuuint64_t dims[2] = {(cuuint64_t)cols, (cuuint64_t)rows}, strides[1] = {(cuuint64_t)cols * 2};
  const cuuint32_t box[2] = {64, 64}, es[2] = {1, 1};
  fn(m, CU_TENSOR_MAP_DATA_TYPE_BFLOAT16, 2, const_cast<void*>(w), dims, strides, box, es, CU_TENSOR_MAP_INTERLEAVE_NONE,
     swz, CU_TENSOR_MAP_L2_PROMOTION_L2_128B, CU_TENSOR_MAP_FLOAT_OOB_FILL_NONE);
}

}

extern "C" void kernel_launch(void* const* d_in, const int* in_sizes, int n_in, void* d_out, int out_size) {
  static EncodeFn fn = nullptr;
  static Scratch* sc = nullptr;
  if (!fn) {
    void* f = nullptr;
    cudaDriverEntryPointQueryResult st;
    cudaGetDriverEntryPoint("cuTensorMapEncodeTiled", &f, cudaEnableDefault, &st);
    fn = (EncodeFn)f;
    void* raw = nullptr;
    cudaGetSymbolAddress(&raw, g_scratch);
    sc = (Scratch*)(((uintptr_t)raw + X_ALIGN - 1) & ~(uintptr_t)(X_ALIGN - 1));
    cudaFuncSetAttribute(conformer_kernel, cudaFuncAttributeMaxDynamicSharedMemorySize, SM_TOTAL);
  }
  typedef const __nv_bfloat16* W;
  const CUtensorMapSwizzle S = CU_TENSOR_MAP_SWIZZLE_128B;
  Params p;
  make_map(fn, &p.map[M_FF1A], d_in[1], 256, 1024, S);
  make_map(fn, &p.map[M_FF1B], d_in[2], 1024, 256, S);
  make_map(fn, &p.map[M_QKV], d_in[3], 256, 768, S);
  make_map(fn, &p.map[M_WO], d_in[4], 256, 256, S);
  make_map(fn, &p.map[M_PW1], d_in[5], 256, 512, S);
  make_map(fn, &p.map[M_PW2], d_in[7], 256, 256, S);
  make_map(fn, &p.map[M_FF2A], d_in[8], 256, 1024, S);
  make_map(fn, &p.map[M_FF2B], d_in[9], 1024, 256, S);
  p.w_ff1b = (W)d_in[2]; p.w_qkv = (W)d_in[3]; p.w_o = (W)d_in[4]; p.w_pw1 = (W)d_in[5];
  p.w_pw2 = (W)d_in[7]; p.w_ff2a = (W)d_in[8]; p.w_ff2b = (W)d_in[9];

  cudaLaunchConfig_t cfg = {};
  cfg.gridDim = dim3(NCTA);
  cfg.blockDim = dim3(384);
  cfg.dynamicSmemBytes = SM_TOTAL;
  cfg.stream = cudaStreamPerThread;
  cudaLaunchAttribute at[1];
  at[0].id = cudaLaunchAttributeCooperative;
  at[0].val.cooperative = 1;
  cfg.attrs = at;
  cfg.numAttrs = 1;
  cudaLaunchKernelEx(&cfg, conformer_kernel, sc, (__nv_bfloat16*)d_out, (W)d_in[6], (W)d_in[0], (W)d_in[1], p);
}
```

```cpp
#include <cuda_runtime.h>
#include <cuda_bf16.h>
#include <cuda.h>
#include <stdint.h>

namespace {

constexpr int T_SEQ = 1000;
constexpr int DM = 256;
constexpr int NCTA = 128;
constexpr int NSTAGE = 12;
constexpr uint32_t STAGE_BYTES = 16384;
constexpr uint32_t TILE_BYTES = 8192;
constexpr uint32_t SM_BASE = 1024;
constexpr uint32_t SM_STG = NSTAGE * STAGE_BYTES;
constexpr uint32_t SM_FULL = SM_STG + 32768;
constexpr uint32_t SM_EMPTY = SM_FULL + 96;
constexpr uint32_t SM_EYE = SM_FULL + 256;
constexpr uint32_t SM_ONE = SM_FULL + 640;
constexpr uint32_t SM_CS = SM_FULL + 768;
constexpr uint32_t SM_TOTAL = SM_FULL + 3072;
constexpr int CS_FF2 = 0, CS_PW1 = 4, CS_QKV = 6;
constexpr uint32_t SPIN_LIMIT = 1u << 16;
constexpr float LN_EPS = 1e-5f;
constexpr float SM_SCALE_LOG2 = 0.125f * 1.4426950408889634f;
constexpr uint32_t G_PITCH = 144;
#define PF_AT 4
#define CLR_PACE 60

constexpr int F_QKV = 16, F_SPARE = 22, F_KV = 24, F_WO = 40, F_PW1 = 42, F_PW2 = 46, F_TOTAL = 64;
enum { M_FF1A, M_FF1B, M_QKV, M_WO, M_PW1, M_PW2, M_FF2A, M_FF2B, M_COUNT };
enum { BAR_K = 1, BAR_V, BAR_Q, BAR_MERGE, BAR_G, BAR_C, BAR_WG1, BAR_GO, BAR_CS, BAR_ATT, BAR_INIT, BAR_HALF };

struct Params {
  CUtensorMap map[M_COUNT];
  const __nv_bfloat16 *w_ff1b, *w_qkv, *w_o, *w_pw1, *w_pw2, *w_ff2a, *w_ff2b;
};

constexpr int X_RS = 0, X_AG1 = X_RS, X_HALO = X_RS + 512, X_AG0 = 1536, X_ST = 2048, X_SIZE = 4096;
constexpr uint32_t HALO_TAG = 0xFFFF0001u;
struct Scratch {
  uint4 x[NCTA][X_SIZE];
  uint4 kv[8][2][16][512];
  uint4 cs[576];
  uint32_t flag[8][32][32];
  uint32_t step[NCTA][32];
};
constexpr size_t X_ALIGN = 4 * X_SIZE * sizeof(uint4);
__device__ uint8_t g_scratch[sizeof(Scratch) + X_ALIGN];
#define PROF_TIME(i)
#define PROF_MARK(i)
#define PROF_MARK2(i, j)
#define PROF_MARK0(i)
#define PROF_AT(a)

__device__ __forceinline__ void mbar_init(uint32_t bar, uint32_t cnt) {
  asm volatile("mbarrier.init.shared::cta.b64 [%0], %1;" :: "r"(bar), "r"(cnt) : "memory");
}
__device__ __forceinline__ void mbar_wait(uint32_t bar, uint32_t parity) {
  asm volatile("{\n.reg .pred p;\n.reg .u32 c;\nmov.u32 c, 0;\n"
               "WAIT_LOOP:\nmbarrier.try_wait.parity.shared::cta.b64 p, [%0], %1;\n@p bra WAIT_DONE;\n"
               "add.u32 c, c, 1;\nsetp.lt.u32 p, c, %2;\n@p bra WAIT_LOOP;\nWAIT_DONE:\n}"
               :: "r"(bar), "r"(parity), "n"(SPIN_LIMIT) : "memory");
}
__device__ __forceinline__ void mbar_arrive(uint32_t bar) {
  asm volatile("mbarrier.arrive.shared::cta.b64 _, [%0];" :: "r"(bar) : "memory");
}
#define bar_sync(id, n) asm volatile("bar.sync %0, %1;" :: "n"((int)(id)), "n"(n) : "memory")
#define bar_arrive(id, n) asm volatile("bar.arrive %0, %1;" :: "n"((int)(id)), "n"(n) : "memory")
__device__ __forceinline__ void fence_async_smem() { asm volatile("fence.proxy.async.shared::cta;" ::: "memory"); }

__device__ __forceinline__ void st_vec(uint4* p, uint32_t a, uint32_t b, uint32_t c, uint32_t d) {
  asm volatile("{\n.reg .b128 v;\n.reg .b64 lo, hi;\nmov.b64 lo, {%1, %2};\nmov.b64 hi, {%3, %4};\nmov.b128 v, {lo, hi};\n"
               "st.relaxed.gpu.global.b128 [%0], v;\n}" :: "l"(p), "r"(a), "r"(b), "r"(c), "r"(d) : "memory");
}
__device__ __forceinline__ void ld_vec(const uint4* p, uint32_t& a, uint32_t& b, uint32_t& c, uint32_t& d) {
  asm volatile("{\n.reg .b128 v;\n.reg .b64 lo, hi;\nld.relaxed.gpu.global.b128 v, [%4];\nmov.b128 {lo, hi}, v;\n"
               "mov.b64 {%0, %1}, lo;\nmov.b64 {%2, %3}, hi;\n}" : "=r"(a), "=r"(b), "=r"(c), "=r"(d) : "l"(p) : "memory");
}
__device__ __forceinline__ void sts128(uint32_t a, uint32_t x, uint32_t y, uint32_t z, uint32_t w) {
  asm volatile("st.shared.v4.u32 [%0], {%1, %2, %3, %4};" :: "r"(a), "r"(x), "r"(y), "r"(z), "r"(w) : "memory");
}
__device__ __forceinline__ void lds128(uint32_t a, uint32_t& x, uint32_t& y, uint32_t& z, uint32_t& w) {
  asm volatile("ld.shared.v4.u32 {%0, %1, %2, %3}, [%4];" : "=r"(x), "=r"(y), "=r"(z), "=r"(w) : "r"(a) : "memory");
}
__device__ __forceinline__ uint32_t lds32(uint32_t a) {
  uint32_t x; asm volatile("ld.shared.u32 %0, [%1];" : "=r"(x) : "r"(a) : "memory"); return x;
}
__device__ __forceinline__ void sts32(uint32_t a, uint32_t x) { asm volatile("st.shared.u32 [%0], %1;" :: "r"(a), "r"(x) : "memory"); }
__device__ __forceinline__ void sts64(uint32_t a, uint32_t x, uint32_t y) {
  asm volatile("st.shared.v2.u32 [%0], {%1, %2};" :: "r"(a), "r"(x), "r"(y) : "memory");
}
__device__ __forceinline__ void stsm4(uint32_t a, const uint32_t* r) {
  asm volatile("stmatrix.sync.aligned.m8n8.x4.shared.b16 [%0], {%1, %2, %3, %4};" :: "r"(a), "r"(r[0]), "r"(r[1]), "r"(r[2]), "r"(r[3]) : "memory");
}
__device__ __forceinline__ void ldsm4(uint32_t a, uint32_t* r) {
  asm volatile("ldmatrix.sync.aligned.m8n8.x4.shared.b16 {%0, %1, %2, %3}, [%4];" : "=r"(r[0]), "=r"(r[1]), "=r"(r[2]), "=r"(r[3]) : "r"(a) : "memory");
}
__device__ __forceinline__ uint32_t pack2(float lo, float hi) {
  uint32_t r; asm("cvt.rn.bf16x2.f32 %0, %1, %2;" : "=r"(r) : "f"(hi), "f"(lo)); return r;
}
__device__ __forceinline__ float bf_lo(uint32_t w) { return __uint_as_float(w << 16); }
__device__ __forceinline__ float bf_hi(uint32_t w) { return __uint_as_float(w & 0xffff0000u); }
__device__ __forceinline__ float tanh_hw(float x) { float y; asm volatile("tanh.approx.f32 %0, %1;" : "=f"(y) : "f"(x)); return y; }
__device__ __forceinline__ float rcp_hw(float x) { float y; asm("rcp.approx.ftz.f32 %0, %1;" : "=f"(y) : "f"(x)); return y; }
__device__ __forceinline__ float rsqrt_hw(float x) { float y; asm("rsqrt.approx.ftz.f32 %0, %1;" : "=f"(y) : "f"(x)); return y; }
__device__ __forceinline__ float ex2_hw(float x) { float y; asm("ex2.approx.ftz.f32 %0, %1;" : "=f"(y) : "f"(x)); return y; }

__device__ __forceinline__ uint32_t here(uint32_t v) { asm volatile("" : "+r"(v)); return v; }

#define SCHED() asm volatile("pmevent 1;" ::: "memory")
__device__ __forceinline__ void cp_async16(uint32_t dst, const void* src) {
  asm volatile("cp.async.cg.shared.global [%0], [%1], 16;" :: "r"(dst), "l"(src) : "memory");
}
__device__ __forceinline__ void cp_async_wait(int n) {
  if (n == 0) asm volatile("cp.async.wait_group 0;" ::: "memory");
  if (n == 1) asm volatile("cp.async.wait_group 1;" ::: "memory");
  if (n == 2) asm volatile("cp.async.wait_group 2;" ::: "memory");
  if (n == 3) asm volatile("cp.async.wait_group 3;" ::: "memory");
}
#define WG_FENCE() asm volatile("wgmma.fence.sync.aligned;" ::: "memory")
#define WG_COMMIT() asm volatile("wgmma.commit_group.sync.aligned;" ::: "memory")
#define WG_WAIT(n) asm volatile("wgmma.wait_group.sync.aligned %0;" :: "n"(n) : "memory")

template <int N> __device__ __forceinline__ void pin(float (&d)[N]) {
#pragma unroll
  for (int i = 0; i < N; i++) asm volatile("" : "+f"(d[i]) :: "memory");
}
template <int N> __device__ __forceinline__ void pin(uint32_t (&d)[N]) {
#pragma unroll
  for (int i = 0; i < N; i++) asm volatile("" : "+r"(d[i]) :: "memory");
}

#define WG_D32 "{%0, %1, %2, %3, %4, %5, %6, %7, %8, %9, %10, %11, %12, %13, %14, %15, %16, %17, %18, %19, %20, %21, %22, %23, %24, %25, %26, %27, %28, %29, %30, %31}"
template <int TB> __device__ __forceinline__ void wgmma64_acc(float (&d)[32], const uint32_t* a, uint64_t db) {
  asm volatile("wgmma.mma_async.sync.aligned.m64n64k16.f32.bf16.bf16 " WG_D32 ", {%32, %33, %34, %35}, %36, 1, 1, 1, %37;"
    : "+f"(d[0]), "+f"(d[1]), "+f"(d[2]), "+f"(d[3]), "+f"(d[4]), "+f"(d[5]), "+f"(d[6]), "+f"(d[7]),
      "+f"(d[8]), "+f"(d[9]), "+f"(d[10]), "+f"(d[11]), "+f"(d[12]), "+f"(d[13]), "+f"(d[14]), "+f"(d[15]),
      "+f"(d[16]), "+f"(d[17]), "+f"(d[18]), "+f"(d[19]), "+f"(d[20]), "+f"(d[21]), "+f"(d[22]), "+f"(d[23]),
      "+f"(d[24]), "+f"(d[25]), "+f"(d[26]), "+f"(d[27]), "+f"(d[28]), "+f"(d[29]), "+f"(d[30]), "+f"(d[31])
    : "r"(a[0]), "r"(a[1]), "r"(a[2]), "r"(a[3]), "l"(db), "n"(TB));
}
template <int TB> __device__ __forceinline__ void wgmma64_reuse(float (&d)[32], const uint32_t* a, uint64_t db, uint32_t zero) {
  asm volatile("{\n.reg .pred p;\nsetp.ne.u32 p, %37, 0;\nwgmma.mma_async.sync.aligned.m64n64k16.f32.bf16.bf16 " WG_D32 ", {%32, %33, %34, %35}, %36, p, 1, 1, %38;\n}"
    : "+f"(d[0]), "+f"(d[1]), "+f"(d[2]), "+f"(d[3]), "+f"(d[4]), "+f"(d[5]), "+f"(d[6]), "+f"(d[7]),
      "+f"(d[8]), "+f"(d[9]), "+f"(d[10]), "+f"(d[11]), "+f"(d[12]), "+f"(d[13]), "+f"(d[14]), "+f"(d[15]),
      "+f"(d[16]), "+f"(d[17]), "+f"(d[18]), "+f"(d[19]), "+f"(d[20]), "+f"(d[21]), "+f"(d[22]), "+f"(d[23]),
      "+f"(d[24]), "+f"(d[25]), "+f"(d[26]), "+f"(d[27]), "+f"(d[28]), "+f"(d[29]), "+f"(d[30]), "+f"(d[31])
    : "r"(a[0]), "r"(a[1]), "r"(a[2]), "r"(a[3]), "l"(db), "r"(zero), "n"(TB));
}
template <int TB> __device__ __forceinline__ void wgmma64_set(float (&d)[32], const uint32_t* a, uint64_t db) {
  asm volatile("wgmma.mma_async.sync.aligned.m64n64k16.f32.bf16.bf16 " WG_D32 ", {%32, %33, %34, %35}, %36, 0, 1, 1, %37;"
    : "=f"(d[0]), "=f"(d[1]), "=f"(d[2]), "=f"(d[3]), "=f"(d[4]), "=f"(d[5]), "=f"(d[6]), "=f"(d[7]),
      "=f"(d[8]), "=f"(d[9]), "=f"(d[10]), "=f"(d[11]), "=f"(d[12]), "=f"(d[13]), "=f"(d[14]), "=f"(d[15]),
      "=f"(d[16]), "=f"(d[17]), "=f"(d[18]), "=f"(d[19]), "=f"(d[20]), "=f"(d[21]), "=f"(d[22]), "=f"(d[23]),
      "=f"(d[24]), "=f"(d[25]), "=f"(d[26]), "=f"(d[27]), "=f"(d[28]), "=f"(d[29]), "=f"(d[30]), "=f"(d[31])
    : "r"(a[0]), "r"(a[1]), "r"(a[2]), "r"(a[3]), "l"(db), "n"(TB));
}

__device__ __forceinline__ void wgmma72_acc(float (&d)[36], const uint32_t* a, uint64_t db) {
  asm volatile("wgmma.mma_async.sync.aligned.m64n72k16.f32.bf16.bf16 {%0, %1, %2, %3, %4, %5, %6, %7, %8, %9, %10, %11, %12, %13, %14, %15, %16, %17, %18, %19, %20, %21, %22, %23, %24, %25, %26, %27, %28, %29, %30, %31, %32, %33, %34, %35}, {%36, %37, %38, %39}, %40, 1, 1, 1, 1;"
    : "+f"(d[0]), "+f"(d[1]), "+f"(d[2]), "+f"(d[3]), "+f"(d[4]), "+f"(d[5]), "+f"(d[6]), "+f"(d[7]), "+f"(d[8]),
      "+f"(d[9]), "+f"(d[10]), "+f"(d[11]), "+f"(d[12]), "+f"(d[13]), "+f"(d[14]), "+f"(d[15]), "+f"(d[16]), "+f"(d[17]),
      "+f"(d[18]), "+f"(d[19]), "+f"(d[20]), "+f"(d[21]), "+f"(d[22]), "+f"(d[23]), "+f"(d[24]), "+f"(d[25]), "+f"(d[26]),
      "+f"(d[27]), "+f"(d[28]), "+f"(d[29]), "+f"(d[30]), "+f"(d[31]), "+f"(d[32]), "+f"(d[33]), "+f"(d[34]), "+f"(d[35])
    : "r"(a[0]), "r"(a[1]), "r"(a[2]), "r"(a[3]), "l"(db));
}
__device__ __forceinline__ void wgmma16_acc(float* d, const uint32_t* a, uint64_t db) {
  asm volatile("wgmma.mma_async.sync.aligned.m64n16k16.f32.bf16.bf16 {%0, %1, %2, %3, %4, %5, %6, %7}, {%8, %9, %10, %11}, %12, 1, 1, 1, 0;"
    : "+f"(d[0]), "+f"(d[1]), "+f"(d[2]), "+f"(d[3]), "+f"(d[4]), "+f"(d[5]), "+f"(d[6]), "+f"(d[7])
    : "r"(a[0]), "r"(a[1]), "r"(a[2]), "r"(a[3]), "l"(db));
}
__device__ __forceinline__ void hmma(float (&d)[4], const uint32_t* a, uint32_t b0, uint32_t b1) {
  asm("mma.sync.aligned.m16n8k16.row.col.f32.bf16.bf16.f32 {%0, %1, %2, %3}, {%4, %5, %6, %7}, {%8, %9}, {%0, %1, %2, %3};"
    : "+f"(d[0]), "+f"(d[1]), "+f"(d[2]), "+f"(d[3]) : "r"(a[0]), "r"(a[1]), "r"(a[2]), "r"(a[3]), "r"(b0), "r"(b1));
}

__device__ __forceinline__ void hmma8(float (&d)[4], const uint32_t* a, uint32_t b0) {
  asm("mma.sync.aligned.m16n8k8.row.col.f32.bf16.bf16.f32 {%0, %1, %2, %3}, {%4, %5}, {%6}, {%0, %1, %2, %3};"
    : "+f"(d[0]), "+f"(d[1]), "+f"(d[2]), "+f"(d[3]) : "r"(a[0]), "r"(a[1]), "r"(b0));
}

template <bool FIRST> __device__ __forceinline__ void mma_tile(float (&d)[32], const uint32_t (&a)[16], uint64_t db) {
  WG_FENCE();
#pragma unroll
  for (int s = 0; s < 4; s++) {
    if (FIRST && s == 0) wgmma64_set<1>(d, &a[0], db); else wgmma64_acc<1>(d, &a[4 * s], db + s * 128);
  }
  WG_COMMIT();
}
__device__ __forceinline__ void mma_tile_reuse(float (&d)[32], const uint32_t (&a)[16], uint64_t db) {
  WG_FENCE();
  wgmma64_reuse<1>(d, &a[0], db, blockIdx.y);
#pragma unroll
  for (int s = 1; s < 4; s++) wgmma64_acc<1>(d, &a[4 * s], db + s * 128);
  WG_COMMIT();
}
template <int ROW> __device__ __forceinline__ void fold_step(float (&d)[32], const uint32_t (&mu)[4]) {
  wgmma64_acc<1>(d, mu, (uint64_t)((SM_BASE + SM_CS + ROW * 128) >> 4) | (uint64_t(1) << 16) | (uint64_t(1) << 62));
}
template <int ROW> __device__ __forceinline__ void mma_fold(float (&d)[32], const uint32_t (&mu)[4]) {
  WG_FENCE();
  fold_step<ROW>(d, mu);
  WG_COMMIT();
}
template <int ROW> __device__ __forceinline__ void mma_tile_fold(float (&d)[32], const uint32_t (&a)[16], uint64_t db, const uint32_t (&mu)[4]) {
  WG_FENCE();
#pragma unroll
  for (int s = 0; s < 4; s++) wgmma64_acc<1>(d, &a[4 * s], db + s * 128);
  fold_step<ROW>(d, mu);
  WG_COMMIT();
}
__device__ __forceinline__ void mma_add_half(float (&d)[32], const uint32_t (&a)[16]) {
  const uint64_t db = (uint64_t)((SM_BASE + SM_EYE) >> 4) | (uint64_t(8) << 16) | (uint64_t(8) << 32);
  WG_FENCE();
#pragma unroll
  for (int s = 0; s < 4; s++) wgmma16_acc(&d[8 * s], &a[4 * s], db);
  WG_COMMIT();
}
#define ACQUIRE(f) mbar_wait(SM_BASE + SM_FULL + ((f) % NSTAGE) * 8, ((f) / NSTAGE) & 1)
__device__ __forceinline__ void mbar_probe(uint32_t& ok, uint32_t bar, uint32_t parity) {
  asm volatile("{\n.reg .pred p;\nmbarrier.test_wait.parity.shared::cta.b64 p, [%1], %2;\nselp.u32 %0, %0, 0, p;\n}"
               : "+r"(ok) : "r"(bar), "r"(parity) : "memory");
}
template <int F, int N> __device__ __forceinline__ uint32_t probe_n() {
  static_assert(F % NSTAGE + N <= NSTAGE, "stages must not wrap");
  uint32_t ok = 1;
#pragma unroll
  for (int i = 0; i < N; i++) mbar_probe(ok, SM_BASE + SM_FULL + (F % NSTAGE + i) * 8, (F / NSTAGE) & 1);
  return ok;
}
template <int F, int N> __device__ __forceinline__ void settle_n(uint32_t ok) {
  if (__builtin_expect(!ok, 0)) {
#pragma unroll 1
    for (int i = 0; i < N; i++) mbar_wait(SM_BASE + SM_FULL + (F % NSTAGE + i) * 8, (F / NSTAGE) & 1);
  }
}
template <int F, int N> __device__ __forceinline__ void acquire_n() { settle_n<F, N>(probe_n<F, N>()); }
#define RELEASE(f0, f1) do { if (lane == 0) { _Pragma("unroll") for (int f_ = (f0); f_ <= (f1); f_++) mbar_arrive(SM_BASE + SM_EMPTY + (f_ % NSTAGE) * 8); } } while (0)
constexpr uint64_t RING = (uint64_t)(SM_BASE >> 4) | (uint64_t(1) << 16) | (uint64_t(64) << 32) | (uint64_t(1) << 62);
#define LO(f) (RING + ((f) % NSTAGE) * 1024)
#define HI(f) (RING + ((f) % NSTAGE) * 1024 + 512)

template <int C> __device__ __forceinline__ uint4* peer(uint4* p) {
  asm volatile("" : "+l"(p));
  return (uint4*)((uintptr_t)p ^ (C * X_SIZE * sizeof(uint4)));
}
__device__ __forceinline__ uint32_t clock_now() { uint32_t c; asm volatile("mov.u32 %0, %%clock;" : "=r"(c) :: "memory"); return c; }
__device__ __forceinline__ void publish(uint4* dst, uint32_t (&a)[16], uint32_t tag) {
#pragma unroll
  for (int s = 0; s < 4; s++) a[4 * s] = (a[4 * s] & ~1u) | tag;
  pin(a);
  SCHED();
#pragma unroll
  for (int s = 0; s < 4; s++) st_vec(dst + s * 128, a[4 * s], a[4 * s + 1], a[4 * s + 2], a[4 * s + 3]);
  SCHED();
}
__device__ __forceinline__ void fetch(const uint4* src, uint32_t (&a)[16]) {
#pragma unroll
  for (int s = 0; s < 4; s++) ld_vec(src + s * 128, a[4 * s], a[4 * s + 1], a[4 * s + 2], a[4 * s + 3]);
}
__device__ __forceinline__ uint32_t miss(const uint32_t (&a)[16], uint32_t tag) {
  return (a[0] ^ tag) | (a[4] ^ tag) | (a[8] ^ tag) | (a[12] ^ tag);
}
__device__ __forceinline__ bool stale(uint32_t v) { return __any_sync(0xffffffffu, here(v) & 1u); }
template <int N = 2> __device__ __forceinline__ void announce(Scratch* sc, bool leader) {
  asm volatile("{\n.reg .pred p;\nsetp.ne.u32 p, %1, 0;\n@p red.relaxed.gpu.global.add.u32 [%0], %2;\n}"
               :: "l"(sc->step[blockIdx.x]), "r"((uint32_t)leader), "n"(N) : "memory");
}
__device__ __forceinline__ uint32_t launch_index(const Scratch* sc) { return *(const volatile uint32_t*)sc->step[blockIdx.x] >> 4; }
__device__ __forceinline__ void stat_fetch(const Scratch* sc, uint32_t (&st)[4]) {
  const uint32_t th = here(threadIdx.x);
  ld_vec(&sc->x[(blockIdx.x & ~3u) + (th & 3)][X_ST + (th >> 2)], st[0], st[1], st[2], st[3]);
}
template <int C, int SLOT> __device__ __forceinline__ void gather_first(uint32_t (&A)[4][16], uint32_t (&st)[4], const Scratch* sc, uint4* xp, uint32_t tag) {
  bar_sync(BAR_GO, 160);
  fetch(peer<1>(xp) + SLOT, A[1]); fetch(peer<2>(xp) + SLOT, A[2]); fetch(peer<3>(xp) + SLOT, A[3]);
  if (SLOT == X_AG0) stat_fetch(sc, st);
  uint32_t spin = 0;
  while (__builtin_expect(stale(miss(A[1], tag) | miss(A[C], tag)), 0) && ++spin < SPIN_LIMIT) {
    fetch(peer<1>(xp) + SLOT, A[1]);
    if (C == 2) fetch(peer<2>(xp) + SLOT, A[2]);
  }
}
template <int C, int SLOT> __device__ __forceinline__ void gather_rest(uint32_t (&A)[4][16], uint4* xp, uint32_t tag) {
  SCHED();
  uint32_t spin = 0;
  while (__builtin_expect(stale(miss(A[C + 1], tag) | miss(A[3], tag)), 0) && ++spin < SPIN_LIMIT) {
    if (C == 1) fetch(peer<2>(xp) + SLOT, A[2]);
    fetch(peer<3>(xp) + SLOT, A[3]);
  }
}
__device__ __forceinline__ void pack_acc(const float (&d)[32], uint32_t (&a)[16]) {
#pragma unroll
  for (int i = 0; i < 16; i++) a[i] = pack2(d[2 * i], d[2 * i + 1]);
}
__device__ __forceinline__ void frag_store(uint32_t slot, const uint32_t (&a)[16]) {
#pragma unroll
  for (int s = 0; s < 4; s++) sts128(slot + s * 512, a[4 * s], a[4 * s + 1], a[4 * s + 2], a[4 * s + 3]);
}
__device__ __forceinline__ void tile_store(uint32_t maddr, const uint32_t (&a)[16]) {
#pragma unroll
  for (int s = 0; s < 4; s++) stsm4(maddr ^ (s << 5), &a[4 * s]);
}
__device__ __forceinline__ void tile_load(uint32_t maddr, uint32_t (&a)[16]) {
#pragma unroll
  for (int s = 0; s < 4; s++) ldsm4(maddr ^ (s << 5), &a[4 * s]);
}

__device__ __forceinline__ void res_load(uint32_t maddr, float (&d)[32]) {
  uint32_t a[16];
  tile_load(here(maddr) + 3 * TILE_BYTES, a);
#pragma unroll
  for (int i = 0; i < 16; i++) { d[2 * i] = bf_lo(a[i]); d[2 * i + 1] = bf_hi(a[i]); }
  pin(d);
}

struct RowAcc { float s[4], u[2][4], v[2][4]; };
__device__ __forceinline__ void row_acc(RowAcc& t, const uint32_t (&a)[16]) {
#pragma unroll
  for (int s = 0; s < 8; s++) {
    if ((s & 1) == 0) hmma(t.s, &a[2 * s], 0x3F803F80u, 0x3F803F80u);
    hmma8(t.u[s & 1], &a[2 * s], a[2 * s]);
    hmma8(t.v[s & 1], &a[2 * s], a[2 * s + 1]);
  }
}
__device__ __forceinline__ float2 row_squares(const RowAcc& t, bool odd) {
  return make_float2(odd ? t.u[0][1] + t.u[1][1] : t.u[0][0] + t.u[1][0], odd ? t.v[0][3] + t.v[1][3] : t.v[0][2] + t.v[1][2]);
}
__device__ __forceinline__ void stat_publish(const uint32_t (&a)[16], Scratch* sc, uint32_t th, uint32_t tag) {
  RowAcc t = {};
  row_acc(t, a);
  const float2 q = row_squares(t, th & 4);
  if ((th & 3) == ((th >> 3) & 3))
    st_vec(&sc->x[blockIdx.x][X_ST + (th >> 2)], (__float_as_uint(t.s[0]) & ~1u) | tag, __float_as_uint(q.x), __float_as_uint(t.s[2]), __float_as_uint(q.y));
}
struct RowNorm { float m0, rs0, m1, rs1; };
__device__ __forceinline__ RowNorm row_norm(float s0, float q0, float s1, float q1, float scale) {
  RowNorm n;
  n.m0 = s0 * (1.f / DM); n.m1 = s1 * (1.f / DM);
  n.rs0 = scale * rsqrt_hw(fmaxf(fmaf(-n.m0, n.m0, q0 * (1.f / DM)), 0.f) + LN_EPS);
  n.rs1 = scale * rsqrt_hw(fmaxf(fmaf(-n.m1, n.m1, q1 * (1.f / DM)), 0.f) + LN_EPS);
  return n;
}
__device__ __forceinline__ RowNorm stat_finish(const Scratch* sc, uint32_t (&st)[4], uint32_t tag, float scale) {
  uint32_t spin = 0;
  while (__builtin_expect(stale(st[0] ^ tag), 0) && ++spin < SPIN_LIMIT) stat_fetch(sc, st);
  float f[4];
#pragma unroll
  for (int i = 0; i < 4; i++) {
    f[i] = __uint_as_float(st[i]);
    f[i] += __shfl_xor_sync(0xffffffffu, f[i], 1);
    f[i] += __shfl_xor_sync(0xffffffffu, f[i], 2);
  }
  return row_norm(f[0], f[1], f[2], f[3], scale);
}
__device__ __forceinline__ void mean_frag(uint32_t (&mu)[4], const RowNorm& n, bool sel) {
  const float a = sel ? -n.m0 : 0.f, c = sel ? -n.m1 : 0.f;
  mu[0] = pack2(a, a); mu[1] = pack2(c, c);
  const float al = a - bf_lo(mu[0]), cl = c - bf_lo(mu[1]);
  mu[2] = pack2(al, al); mu[3] = pack2(cl, cl);
  pin(mu);
}
__device__ __forceinline__ void centre(uint32_t (&a)[16], uint32_t m0, uint32_t m1) {
#pragma unroll
  for (int i = 0; i < 16; i++) asm("sub.rn.bf16x2 %0, %0, %1;" : "+r"(a[i]) : "r"((i & 1) ? m1 : m0));
  pin(a);
}
__device__ __forceinline__ void scale_pack(const float (&d)[32], uint32_t (&a)[16], float rs0, float rs1) {
#pragma unroll
  for (int i = 0; i < 16; i++) { const float rs = (i & 1) ? rs1 : rs0; a[i] = pack2(d[2 * i] * rs, d[2 * i + 1] * rs); }
}
template <int S> __device__ __forceinline__ void silu_seg(float (&acc)[4][32], float (&tn)[2][4], uint32_t (&H)[4][16], float rs0, float rs1) {
  if (S >= 2) {
    const float* h = &acc[(S - 2) >> 3][4 * ((S - 2) & 7)];
    const float* v = tn[S & 1];
    uint32_t* o = &H[(S - 2) >> 3][2 * ((S - 2) & 7)];
    o[0] = pack2(fmaf(h[0], v[0], h[0]), fmaf(h[1], v[1], h[1]));
    o[1] = pack2(fmaf(h[2], v[2], h[2]), fmaf(h[3], v[3], h[3]));
    asm volatile("" : "+r"(o[0]), "+r"(o[1]));
  }
  if (S >= 1 && S <= 32) {
#pragma unroll
    for (int k = 0; k < 4; k++) tn[(S - 1) & 1][k] = tanh_hw(acc[((S - 1) >> 3) & 3][4 * ((S - 1) & 7) + k]);
  }
  if (S < 32) {
    float* h = &acc[(S >> 3) & 3][4 * (S & 7)];
    h[0] *= rs0; h[1] *= rs0; h[2] *= rs1; h[3] *= rs1;
    asm volatile("" : "+f"(h[0]), "+f"(h[1]), "+f"(h[2]), "+f"(h[3]));
  }
  SCHED();
}
template <int S0, int S1> __device__ __forceinline__ void silu_segs(float (&acc)[4][32], float (&tn)[2][4], uint32_t (&H)[4][16], float rs0, float rs1) {
  silu_seg<S0>(acc, tn, H, rs0, rs1);
  if constexpr (S0 + 1 < S1) silu_segs<S0 + 1, S1>(acc, tn, H, rs0, rs1);
}
template <int HALF> __device__ __forceinline__ void send_half(uint4* dst, const float (&d)[32], uint32_t tag) {
  uint32_t o[8];
#pragma unroll
  for (int i = 0; i < 8; i++) o[i] = pack2(d[16 * HALF + 2 * i], d[16 * HALF + 2 * i + 1]);
  o[0] = (o[0] & ~1u) | tag; o[4] = (o[4] & ~1u) | tag;
  pin(o);
  SCHED();
  st_vec(dst + HALF * 256, o[0], o[1], o[2], o[3]);
  st_vec(dst + HALF * 256 + 128, o[4], o[5], o[6], o[7]);
  SCHED();
}
__device__ __forceinline__ void send_residual(uint32_t (&a)[16], Scratch* sc, uint4* xp, uint32_t maddr, uint32_t tag) {
  const uint32_t exact[4] = {a[0], a[4], a[8], a[12]};
  publish(xp + X_AG0, a, tag);
  const uint32_t th = here(threadIdx.x);
  stat_publish(a, sc, th, tag);
  tile_store(here(maddr) + 3 * TILE_BYTES, a);
  stsm4(SM_BASE + SM_STG + 3 * TILE_BYTES + (th >> 5) * 2048 + (th & 7) * 128 + ((((th >> 2) & 6) ^ (th & 7)) << 4), exact);
}
template <int F, int N> __device__ __forceinline__ void proj_residual(uint32_t (&A)[4][16], Scratch* sc, uint4* xp, uint32_t maddr,
                                                                      uint32_t tag, int lane) {
  float acc[32];
  uint32_t st[4];
  acquire_n<F, N>();
  if (F == F_PW2) acquire_n<0, 5>();
  res_load(maddr, acc);
  mma_tile<false>(acc, A[0], LO(F));
  gather_first<2, X_AG1>(A, st, sc, xp, tag);
  announce(sc, threadIdx.x == 0);
  mma_tile<false>(acc, A[1], HI(F));
  mma_tile<false>(acc, A[2], LO(F + 1));
  gather_rest<2, X_AG1>(A, xp, tag);
  PROF_MARK0(F == F_WO ? 11 : 16);
  mma_tile<false>(acc, A[3], HI(F + 1));
  RELEASE(F - 2, F - 1);
  WG_WAIT(0); pin(acc);
  pack_acc(acc, A[0]);
  send_residual(A[0], sc, xp, maddr, tag);
}

__device__ __forceinline__ uint64_t ring_desc(uint32_t lo) { return (RING & ~uint64_t(0xFFFFFFFFu)) | lo; }
__device__ __forceinline__ void qk_tile(float (&S)[32], const uint32_t (&Q)[16], uint32_t dk) {
  wgmma64_reuse<0>(S, &Q[0], ring_desc(dk), blockIdx.y);
#pragma unroll
  for (int s = 1; s < 4; s++) wgmma64_acc<0>(S, &Q[4 * s], ring_desc(dk + s * 2));
}
__device__ __forceinline__ void qk_shift(float (&S)[32], const uint32_t (&nm)[4]) { wgmma64_acc<0>(S, nm, (uint64_t)((SM_BASE + SM_ONE) >> 4)); }
constexpr uint32_t RING_K = (uint32_t)RING, V_STEP = 1u - (1u << 16);
constexpr uint32_t RING_V = (SM_BASE >> 4) | (((SM_STG + 2 * TILE_BYTES) >> 4) << 16);
__device__ __forceinline__ void pv_tile(float (&O)[36], const uint32_t (&P)[16], uint32_t dv, uint32_t pad) {
#pragma unroll
  for (int s = 0; s < 4; s++) wgmma72_acc(O, &P[4 * s], ring_desc(dv + s * 128 * V_STEP + (s < 2 ? 0 : (s - 1) * pad)));
}
__device__ __forceinline__ void attn_step(const float (&Sc)[32], float (&Sn)[32], uint32_t (&Pc)[16], uint32_t (&Pp)[16], float (&O)[36],
                                          const uint32_t (&Q)[16], const uint32_t (&nm)[4], uint32_t dk, uint32_t dv, bool next, bool prev) {
  if (next) {
    WG_FENCE();
    qk_tile(Sn, Q, dk);
    qk_shift(Sn, nm);
  }
  if (prev) {
    WG_FENCE();
    pv_tile(O, Pp, dv, 0);
  }
  WG_COMMIT();
  SCHED();
#pragma unroll
  for (int i = 0; i < 16; i++) Pc[i] = pack2(ex2_hw(Sc[2 * i]), ex2_hw(Sc[2 * i + 1]));
  pin(Pc);
  SCHED();
}
template <int R> __device__ __forceinline__ float tile_max(const float (&S)[32]) {
  float t[4];
#pragma unroll
  for (int j = 0; j < 4; j++) t[j] = fmaxf(fmaxf(S[8 * j + R], S[8 * j + R + 1]), fmaxf(S[8 * j + R + 4], S[8 * j + R + 5]));
  float n = fmaxf(fmaxf(t[0], t[1]), fmaxf(t[2], t[3]));
  n = fmaxf(n, __shfl_xor_sync(0xffffffffu, n, 1));
  return fmaxf(n, __shfl_xor_sync(0xffffffffu, n, 2));
}
__device__ __forceinline__ void attention_exact(float (&O)[36], const uint32_t (&Q)[16], const Scratch* sc, int bh, int lane, int half) {
  const char* kb = (const char*)&sc->kv[bh][0][0][0];
  const char* vb = (const char*)&sc->kv[bh][1][0][0];
  const int g = lane >> 2, q = lane & 3;
  float m0 = -INFINITY, m1 = -INFINITY, l0 = 0.f, l1 = 0.f;
  float o[4][4] = {};
#pragma unroll 1
  for (int k0 = 0; k0 < T_SEQ; k0 += 8) {
    float s[4] = {0.f, 0.f, 0.f, 0.f};
#pragma unroll
    for (int c = 0; c < 8; c++) hmma8(s, &Q[2 * c], __ldcg((const uint32_t*)(kb + (k0 + g) * 128 + ((c ^ g) << 4) + q * 4)));
    float n0 = fmaxf(s[0], s[1]), n1 = fmaxf(s[2], s[3]);
    n0 = fmaxf(n0, __shfl_xor_sync(0xffffffffu, n0, 1)); n1 = fmaxf(n1, __shfl_xor_sync(0xffffffffu, n1, 1));
    n0 = fmaxf(m0, fmaxf(n0, __shfl_xor_sync(0xffffffffu, n0, 2))); n1 = fmaxf(m1, fmaxf(n1, __shfl_xor_sync(0xffffffffu, n1, 2)));
    const float a0 = ex2_hw(m0 - n0), a1 = ex2_hw(m1 - n1);
    m0 = n0; m1 = n1;
    const uint32_t pp[2] = {pack2(ex2_hw(s[0] - n0), ex2_hw(s[1] - n0)), pack2(ex2_hw(s[2] - n1), ex2_hw(s[3] - n1))};
    l0 = fmaf(l0, a0, bf_lo(pp[0]) + bf_hi(pp[0])); l1 = fmaf(l1, a1, bf_lo(pp[1]) + bf_hi(pp[1]));
#pragma unroll
    for (int j = 0; j < 4; j++) {
      const int c = 4 * half + j;
      const uint32_t v0 = __ldcg((const uint16_t*)(vb + (k0 + 2 * q) * 128 + ((c ^ (2 * q)) << 4) + g * 2));
      const uint32_t v1 = __ldcg((const uint16_t*)(vb + (k0 + 2 * q + 1) * 128 + ((c ^ (2 * q + 1)) << 4) + g * 2));
      o[j][0] *= a0; o[j][1] *= a0; o[j][2] *= a1; o[j][3] *= a1;
      hmma8(o[j], pp, v0 | (v1 << 16));
    }
  }
  l0 += __shfl_xor_sync(0xffffffffu, l0, 1); l1 += __shfl_xor_sync(0xffffffffu, l1, 1);
  O[32] = l0 + __shfl_xor_sync(0xffffffffu, l0, 2); O[34] = l1 + __shfl_xor_sync(0xffffffffu, l1, 2);
#pragma unroll
  for (int i = 0; i < 16; i++) O[i] = o[i >> 2][i & 3];
}

__device__ __forceinline__ uint32_t fill_entry(int f, int r) {
  int m, x = r, y, dx = 0;
  if (f < F_QKV || f >= 48) {
    const int i = f & 15;
    m = f < F_QKV ? M_FF1A : M_FF2A;
    if (i < 8) { x = 4 * r + ((0xE2u >> i) & 1) * 2; y = r ^ ((0xE790u >> (2 * i)) & 3); dx = 1; }
    else { m++; x = r ^ (((i >> 1) - 3) & 3); y = 4 * r + 2 * (i & 1); }
  } else if (f < F_KV) {
    const int i = f - F_QKV;
    m = M_QKV;
    if (i == 1 || i >= 5) { y = r ^ (i == 1 ? 0 : 2); }
    else { x = 4 + r; y = r ^ (i ? i - 1 : 0); dx = 4; }
  } else if (f >= F_PW1 && f < F_PW2) {
    m = M_PW1; y = r ^ (f - F_PW1); dx = 4;
  } else {
    m = f < F_PW1 ? M_WO : M_PW2; y = r ^ ((f & 1) * 2);
  }
  return m | (x << 4) | (y << 8) | (dx << 16);
}
__device__ __forceinline__ void tma_fill(uint32_t st, const CUtensorMap* map, uint32_t x, uint32_t y, uint32_t x2, uint32_t y2) {
  asm volatile("{\n.reg .pred p;\nelect.sync _|p, 0xffffffff;\n"
               "@p mbarrier.arrive.expect_tx.shared::cta.b64 _, [%1], 16384;\n"
               "@p cp.async.bulk.tensor.2d.shared::cluster.global.mbarrier::complete_tx::bytes [%0], [%2, {%3, %4}], [%1];\n"
               "@p cp.async.bulk.tensor.2d.shared::cluster.global.mbarrier::complete_tx::bytes [%0 + 8192], [%2, {%5, %6}], [%1];\n}"
               :: "r"(SM_BASE + st * STAGE_BYTES), "r"(SM_BASE + SM_FULL + st * 8), "l"(map), "r"(x), "r"(y), "r"(x2), "r"(y2) : "memory");
}
template <int F0, int N> __device__ __forceinline__ void weight_fills(const Params& p, uint32_t entry) {
  uint32_t st = F0 % NSTAGE, parity = ((F0 / NSTAGE) & 1) ^ 1, e = __shfl_sync(0xffffffffu, entry, 0);
#pragma unroll 1
  for (int i = 1; i <= N; i++) {
    const uint32_t x = (e << 2) & 0x3C0, y = (e >> 2) & 0x3FC0, dx = (e >> 16) << 6;
    const CUtensorMap* map = &p.map[e & 15];
    e = __shfl_sync(0xffffffffu, entry, i);
    mbar_wait(SM_BASE + SM_EMPTY + st * 8, parity);
    tma_fill(st, map, x, y, x + dx, dx ? y : y ^ 64);
    if (++st == NSTAGE) { st = 0; parity ^= 1; }
  }
}
__device__ __forceinline__ uint32_t kv_poll(const uint32_t* flag, uint32_t prev) {
  uint32_t v;
  asm volatile("ld.relaxed.gpu.global.u32 %0, [%1];" : "=r"(v) : "l"(flag) : "memory");
  return __ballot_sync(0xffffffffu, v - 1 == prev);
}
__device__ __forceinline__ void kv_fills(const Scratch* sc, int bh, int kind, uint32_t prev, const uint32_t* flag, uint32_t ready) {
#pragma unroll 1
  for (int j = 0; j < 8; j++) {
    uint32_t spin = 0;
#pragma unroll 1
    while (((ready >> (2 * j)) & 3) != 3 && ++spin < SPIN_LIMIT) ready = kv_poll(flag, prev);
    const uint32_t st = (j < 6 ? 4 * (j >> 1) : 0) + (j & 1) + 2 * kind;
    mbar_wait(SM_BASE + SM_EMPTY + st * 8, j < 6);
    asm volatile("{\n.reg .pred p;\nelect.sync _|p, 0xffffffff;\n"
                 "@p mbarrier.arrive.expect_tx.shared::cta.b64 _, [%1], 16384;\n"
                 "@p cp.async.bulk.shared::cluster.global.mbarrier::complete_tx::bytes [%0], [%2], 16384, [%1];\n}"
                 :: "r"(SM_BASE + st * STAGE_BYTES), "r"(SM_BASE + SM_FULL + st * 8), "l"(sc->kv[bh][kind][2 * j]) : "memory");
    PROF_AT(256 + 512 + (10 + kind * 8 + j) * 4);
  }
}
__device__ __forceinline__ void l2_prefetch(const void* p, uint32_t total, int b) {
  const uint32_t part = total / NCTA;
  asm volatile("cp.async.bulk.prefetch.L2.global [%0], %1;" :: "l"((const char*)p + (size_t)b * part), "r"(part) : "memory");
}

__global__ void __launch_bounds__(384, 1) conformer_kernel(Scratch* __restrict__ sc, __nv_bfloat16* __restrict__ out,
                                                           const __nv_bfloat16* __restrict__ dw, const __nv_bfloat16* __restrict__ xin,
                                                           const __nv_bfloat16* __restrict__ w_ff1a, const __grid_constant__ Params p) {
  extern __shared__ __align__(1024) uint8_t smem[];
  const int tid = threadIdx.x, lane = tid & 31;
  const int b = blockIdx.x, r = b & 3, batch = b >> 6, t = (b >> 2) & 15;
  if ((uint32_t)__cvta_generic_to_shared(smem) != SM_BASE) return;
  PROF_AT(256 + (tid >> 7) * 256);
  PROF_TIME(30);
  const uint32_t crow = ((tid >> 1) & 48) + (lane >> 3);
  const uint32_t cdst = SM_BASE + crow * 128 + (((lane & 7) ^ (lane >> 3)) << 4);
  if (tid < 128) {
    const uint32_t g0 = batch * T_SEQ + t * 64 + crow, o = r * 128 + (lane & 7) * 16;
    const uint32_t lo = min(g0, 2 * T_SEQ - 5) * 512 + o, hi = min(g0 + 8, 2 * T_SEQ - 5) * 512 + o;
#pragma unroll
    for (int c = 0; c < 4; c++) {
#pragma unroll
      for (int i = 0; i < 4; i++)
        cp_async16((cdst ^ ((i & 1) << 6)) + SM_STG + (3 - c) * TILE_BYTES + i * 512, (const char*)xin + (((i & 2) ? hi : lo) ^ (c << 7)) + (i & 1) * 2048);
      asm volatile("cp.async.commit_group;" ::: "memory");
    }
  } else if (tid < 256) {
    const char* src = (const char*)w_ff1a + (64 * r + crow) * 2048 + r * 512 + (lane & 7) * 16;
#pragma unroll
    for (int c = 0; c < 4; c++) {
#pragma unroll
      for (int i = 0; i < 4; i++) cp_async16((cdst ^ ((i & 1) << 6)) + c * TILE_BYTES + i * 512, src + i * 8192 + c * 128);
      asm volatile("cp.async.commit_group;" ::: "memory");
    }
  } else if (tid == 352) {
    l2_prefetch(w_ff1a, 256 * 1024 * 2, b);
  }
  const int cw = __shfl_sync(0xffffffffu, tid >> 5, 0), wg = cw >> 2, w = cw & 3;

  if (wg == 2) {
    asm volatile("setmaxnreg.dec.sync.aligned.u32 40;");
    if (cw == 8) {
      if (lane == 0) {
        asm volatile("prefetch.tensormap [%0];" :: "l"(&p.map[M_FF1A]) : "memory");
#pragma unroll
        for (int i = 0; i < NSTAGE; i++) mbar_init(SM_BASE + SM_FULL + i * 8, 1);
        fence_async_smem();
      }
      __syncwarp();
      bar_arrive(0, 320);
      PROF_MARK(9);
#pragma unroll
      for (int f = 2; f < 8; f++) {
        const uint32_t x = 256 * r + ((0xE2u >> f) & 1) * 128, y = (r ^ ((0xE790u >> (2 * f)) & 3)) * 64;
        tma_fill(f, &p.map[M_FF1A], x, y, x + 64, y);
      }
      PROF_MARK(1);
      uint32_t entry[2];
#pragma unroll 1
      for (int i = 0; i < 2; i++) { entry[1] = fill_entry(8 + i * 32 + lane, r); if (i == 0) entry[0] = entry[1]; }
      bar_sync(BAR_INIT, 64);
      weight_fills<8, F_KV - 8>(p, entry[0]);
      mbar_wait(SM_BASE + SM_EMPTY + (F_WO % NSTAGE) * 8, 1);
      weight_fills<F_WO, F_TOTAL - F_WO>(p, entry[1]);
    } else if (here(cw) != 11) {
      const int kind = w - 1;
      const uint32_t prev = launch_index(sc);
      if (kind == 0) {
        if (lane == 0) {
#pragma unroll
          for (int i = 0; i < NSTAGE; i++) mbar_init(SM_BASE + SM_EMPTY + i * 8, 4);
        }
        __syncwarp();
        bar_arrive(0, 320);
        bar_arrive(BAR_INIT, 64);
      }
      const uint32_t* flag = sc->flag[batch * 4 + r][kind * 16 + (lane & 15)];
      const uint32_t ready = kv_poll(flag, prev);
      if (kind == 0) bar_sync(BAR_K, 160); else bar_sync(BAR_V, 160);
      if (lane == 0) {
        asm volatile("cp.async.bulk.global.shared::cta.bulk_group [%0], [%1], %2;"
                     :: "l"(&sc->kv[batch * 4 + r][kind][t][0]), "r"(SM_BASE + SM_STG + kind * TILE_BYTES), "r"(TILE_BYTES) : "memory");
PROF_MARK(4 + kind * 2);
        asm volatile("cp.async.bulk.commit_group;\ncp.async.bulk.wait_group 0;" ::: "memory");
PROF_MARK(5 + kind * 2);
        asm volatile("st.relaxed.gpu.global.u32 [%0], %1;" :: "l"(sc->flag[batch * 4 + r][kind * 16 + t]), "r"(prev + 1) : "memory");
      }
      __syncwarp();
      kv_fills(sc, batch * 4 + r, kind, prev, flag, ready);
    } else {
      const uint32_t* watch = sc->step[(b & ~3) + (lane & 3)];
      uint32_t seen;
      asm volatile("ld.relaxed.gpu.global.u32 %0, [%1];" : "=r"(seen) : "l"(watch) : "memory");
#pragma unroll 1
      for (int i = 0; i < 22; i++) {
        const uint32_t t0 = clock_now();
        uint4* dst = &sc->x[b][i * 96 + lane];
        st_vec(dst, 0u, 0u, 0u, 0u); st_vec(dst + 32, 0u, 0u, 0u, 0u); st_vec(dst + 64, 0u, 0u, 0u, 0u);
        if (i == PF_AT && lane == 0) {
          asm volatile("prefetch.tensormap [%0];" :: "l"(&p.map[M_FF1B]) : "memory");
          l2_prefetch(p.w_ff1b, 1024 * 256 * 2, b);
          l2_prefetch(p.w_qkv, 256 * 768 * 2, b);
          l2_prefetch(p.w_pw1, 256 * 512 * 2, b);
          l2_prefetch(p.w_ff2a, 256 * 1024 * 2, b);
        }
        while (clock_now() - t0 < CLR_PACE) {}
      }
      PROF_MARK(28);
      asm volatile("fence.acq_rel.gpu;" ::: "memory");
      __syncwarp();
      announce(sc, lane == 0);
      if (lane == 0) {
        l2_prefetch(p.w_o, 256 * 256 * 2, b);
        l2_prefetch(p.w_pw2, 256 * 256 * 2, b);
        l2_prefetch(p.w_ff2b, 1024 * 256 * 2, b);
#pragma unroll
        for (int i = M_QKV; i < M_COUNT; i++) asm volatile("prefetch.tensormap [%0];" :: "l"(&p.map[i]) : "memory");
      }
      PROF_MARK(2);
      uint32_t want = seen & ~15u;
#pragma unroll 1
      for (int k = 0; k < 8; k++) {
        want += 2;
        uint32_t spin = 0;
#pragma unroll 1
        while (__any_sync(0xffffffffu, (int)(seen - want) < 0) && ++spin < SPIN_LIMIT)
          asm volatile("ld.relaxed.gpu.global.u32 %0, [%1];" : "=r"(seen) : "l"(watch) : "memory");
        bar_arrive(BAR_GO, 160);
        PROF_MARK(32 + k);
      }
    }
  } else {
    asm volatile("setmaxnreg.inc.sync.aligned.u32 232;");
    const int q = lane & 3, th = tid & 127;
    constexpr uint32_t stg = SM_BASE + SM_STG;
    const uint32_t mrow = 16 * w + (lane & 15);
    const uint32_t maddr = stg + mrow * 128 + (((lane >> 4) ^ (lane & 7)) << 4);
    const uint32_t qslot = stg + 2 * TILE_BYTES + w * 2048 + lane * 16;
    uint4* const xp = &sc->x[b][th];
    const int nvalid = T_SEQ - t * 64, row0 = 16 * w + (lane >> 2);

    uint32_t A[4][16];
    uint32_t st[4];
    bar_sync(0, 320);
    if (wg == 0) {
      RowAcc ra = {};
      cp_async_wait(3);
      __syncwarp();
      PROF_MARK0(45);
      tile_load(maddr + 3 * TILE_BYTES, A[0]);
#pragma unroll
      for (int c = 1; c < 4; c++) {
        cp_async_wait(3 - c);
        __syncwarp();
        tile_load(maddr + (3 - c) * TILE_BYTES, A[c]);
        row_acc(ra, A[c - 1]);
      }
      PROF_MARK(1);
      row_acc(ra, A[3]);
      PROF_MARK0(46);
      const float m0 = ra.s[0] * (1.f / DM), m1 = ra.s[2] * (1.f / DM);
      st[0] = pack2(m0, m0); st[1] = pack2(m1, m1);
      centre(A[0], st[0], st[1]);
      const float2 sq = row_squares(ra, lane & 4);
      st[2] = __float_as_uint(fmaf(-m0, m0, sq.x * (1.f / DM))); st[3] = __float_as_uint(fmaf(-m1, m1, sq.y * (1.f / DM)));
    } else {
      if (th < 112) sts128(SM_BASE + SM_CS + th * 16, 0, 0, 0, 0);
      sts32(SM_BASE + SM_EYE + th * 4, th >= 96 ? 0x3F803F80u : ((th & 32) == 0 && (th & 3) == ((th >> 3) & 3)) ? (0x3F00u << ((th & 4) * 4)) : 0u);
#pragma unroll
      for (int i = 0; i < 2; i++) {
        cp_async_wait(2 - 2 * i);
        fence_async_smem();
        bar_sync(BAR_WG1, 128);
        if (th == 0) mbar_arrive(SM_BASE + SM_FULL + i * 8);
      }
      PROF_MARK(6);
      const uint32_t tag = ~launch_index(sc) & 1;
      mbar_wait(SM_BASE + SM_FULL + 4 * 8, 0);
      PROF_MARK(5);
      if (b < 72) {
        const __nv_bfloat16* wp; int ld, col;
        if (b < 24) { wp = p.w_qkv; ld = 768; col = b * 32; }
        else if (b < 40) { wp = p.w_pw1; ld = 512; col = (b - 24) * 32; }
        else { wp = p.w_ff2a; ld = 1024; col = (b - 40) * 32; }
        const uint4* src = (const uint4*)(wp + (size_t)(th >> 2) * ld + col + q * 8);
        float c[8] = {0.f, 0.f, 0.f, 0.f, 0.f, 0.f, 0.f, 0.f};
#pragma unroll 1
        for (int h = 0; h < 2; h++, src += 16 * ld) {
#pragma unroll
          for (int i = 0; i < 4; i++) {
            const uint4 v = __ldg(src + i * 4 * ld);
            c[0] += bf_lo(v.x); c[1] += bf_hi(v.x); c[2] += bf_lo(v.y); c[3] += bf_hi(v.y);
            c[4] += bf_lo(v.z); c[5] += bf_hi(v.z); c[6] += bf_lo(v.w); c[7] += bf_hi(v.w);
          }
        }
#pragma unroll 1
        for (int m = 4; m <= 16; m <<= 1)
#pragma unroll
          for (int k = 0; k < 8; k++) c[k] += __shfl_xor_sync(0xffffffffu, c[k], m);
        if (lane < 4) {
          const uint32_t a = SM_BASE + SM_CS + 1792 + w * 128 + lane * 32;
          sts128(a, __float_as_uint(c[0]), __float_as_uint(c[1]), __float_as_uint(c[2]), __float_as_uint(c[3]));
          sts128(a + 16, __float_as_uint(c[4]), __float_as_uint(c[5]), __float_as_uint(c[6]), __float_as_uint(c[7]));
        }
        bar_sync(BAR_WG1, 128);
        if (th < 8) {
          float o[4] = {0.f, 0.f, 0.f, 0.f};
#pragma unroll 1
          for (int k = 0; k < 4; k++) {
            uint32_t e[4];
            lds128(SM_BASE + SM_CS + 1792 + k * 128 + th * 16, e[0], e[1], e[2], e[3]);
#pragma unroll
            for (int i = 0; i < 4; i++) o[i] += __uint_as_float(e[i]);
          }
          st_vec(&sc->cs[b * 8 + th], (__float_as_uint(o[0]) & ~1u) | tag, __float_as_uint(o[1]), __float_as_uint(o[2]), __float_as_uint(o[3]));
        }
      }
      bar_sync(BAR_WG1, 128);
      PROF_MARK(2);
      if (th < 72) {
        const int j = th >> 3, i = (th & 7) * 2;
        int src;
        if (j < CS_PW1) src = 320 + 64 * r + 16 * j;
        else if (j < CS_QKV) src = 192 + (j - CS_PW1) * 64 + 16 * r;
        else src = ((j - CS_QKV + 1) % 3) * 64 + 16 * r;
        uint32_t e[8], hi[4], lo[4], spin = 0;
#pragma unroll 1
        do {
          ld_vec(&sc->cs[src + i], e[0], e[1], e[2], e[3]);
          ld_vec(&sc->cs[src + i + 1], e[4], e[5], e[6], e[7]);
        } while ((((e[0] ^ tag) | (e[4] ^ tag)) & 1u) && ++spin < SPIN_LIMIT);
        e[0] &= ~1u; e[4] &= ~1u;
#pragma unroll
        for (int k = 0; k < 4; k++) {
          const float c0 = __uint_as_float(e[2 * k]), c1 = __uint_as_float(e[2 * k + 1]);
          hi[k] = pack2(c0, c1);
          lo[k] = pack2(c0 - bf_lo(hi[k]), c1 - bf_hi(hi[k]));
        }
        const uint32_t a = SM_BASE + SM_CS + j * 256 + i * 8;
        sts128(a ^ ((a >> 3) & 0x70), hi[0], hi[1], hi[2], hi[3]);
        sts128((a + 128) ^ (((a + 128) >> 3) & 0x70), lo[0], lo[1], lo[2], lo[3]);
      }
      fence_async_smem();
      PROF_MARK(4);
      bar_arrive(BAR_CS, 256);
    }

#pragma unroll 1
    for (uint32_t pass = 0; pass < 2; pass++) {
      uint32_t Q[16];
      if (wg == 0) {
        float acc[4][32];
        uint32_t H[4][16];
        if (!pass) { PROF_MARK(47); ACQUIRE(0); }
        mma_tile<true>(acc[0], A[0], LO(0)); mma_tile<true>(acc[1], A[0], HI(0));
        if (!pass) ACQUIRE(1);
        mma_tile<true>(acc[2], A[0], LO(1)); mma_tile<true>(acc[3], A[0], HI(1));
        if (pass) {
          gather_first<1, X_AG0>(A, st, sc, xp, 1);
        } else {
          centre(A[1], st[0], st[1]);
          acquire_n<2, 3>();
        }
        mma_tile<false>(acc[0], A[1], LO(2)); mma_tile<false>(acc[1], A[1], HI(2));
        if (pass) {
          gather_rest<1, X_AG0>(A, xp, 1);
          RELEASE(F_PW2, F_PW2 + 1);
        } else {
          centre(A[2], st[0], st[1]); centre(A[3], st[0], st[1]);
        }
        PROF_MARK2(2, 18);
        mma_tile<false>(acc[0], A[2], LO(3)); mma_tile<false>(acc[0], A[3], LO(4));
        WG_WAIT(4);
        RELEASE(0, 1);
        uint32_t mu[4] = {0u, 0u, 0u, 0u};
        float rs0, rs1, tn[2][4];
        if (pass) {
          const RowNorm n = stat_finish(sc, st, 1, 0.5f);
          rs0 = n.rs0; rs1 = n.rs1;
          mean_frag(mu, n, q == 0);
        } else {
          const int src = (lane & 28) | (lane >> 3);
          rs0 = 0.5f * rsqrt_hw(fmaxf(__uint_as_float(__shfl_sync(0xffffffffu, st[2], src)), 0.f) + LN_EPS);
          rs1 = 0.5f * rsqrt_hw(fmaxf(__uint_as_float(__shfl_sync(0xffffffffu, st[3], src)), 0.f) + LN_EPS);
        }
        pin(mu);
        mma_fold<2 * CS_FF2>(acc[0], mu);
        mma_tile<false>(acc[1], A[2], HI(3));
#define SEGS(a, b) silu_segs<a, b>(acc, tn, H, rs0, rs1)
        WG_WAIT(1); pin(acc[0]);
        SEGS(0, 1);
        mma_tile_fold<2 * CS_FF2 + 2>(acc[1], A[3], HI(4), mu);
        SEGS(1, 3);
        uint32_t ok = probe_n<5, 3>();
        SEGS(3, 4);
        settle_n<5, 3>(ok);
        mma_tile<false>(acc[2], A[1], LO(5));
        SEGS(4, 6);
        mma_tile<false>(acc[2], A[2], LO(6));
        SEGS(6, 8);
        WG_WAIT(2); pin(acc[1]);
        RELEASE(2, 4);
        SEGS(8, 9);
        mma_tile_fold<2 * CS_FF2 + 4>(acc[2], A[3], LO(7), mu);
        SEGS(9, 12);
        mma_tile<false>(acc[3], A[1], HI(5));
        SEGS(12, 14);
        mma_tile<false>(acc[3], A[2], HI(6));
        SEGS(14, 16);
        WG_WAIT(2); pin(acc[2]);
        SEGS(16, 17);
        mma_tile_fold<2 * CS_FF2 + 6>(acc[3], A[3], HI(7), mu);
        SEGS(17, 19);
        ok = probe_n<8, 2>();
        SEGS(19, 20);
        settle_n<8, 2>(ok);
        mma_tile_reuse(acc[1], H[0], LO(8));
        SEGS(20, 22);
        mma_tile<false>(acc[1], H[1], HI(8));
        SEGS(22, 24);
        WG_WAIT(2); pin(acc[3]);
        RELEASE(5, 7);
        SEGS(24, 26);
        mma_tile<false>(acc[1], H[2], LO(9));
        SEGS(26, 27);
        ok = probe_n<10, 2>();
        SEGS(27, 28);
        settle_n<10, 2>(ok);
        mma_tile_reuse(acc[2], H[0], LO(10));
        SEGS(28, 31);
        mma_tile<false>(acc[2], H[1], HI(10));
        SEGS(31, 34);
#undef SEGS
        PROF_MARK2(3, 19);
        const uint32_t rtag = here(pass ^ 1);
        const uint4* rs_in = xp + X_RS;
        mma_tile<false>(acc[1], H[3], HI(9));
        mma_tile<false>(acc[2], H[2], LO(11));
        ok = probe_n<12, 2>();
        uint4* rs_out = peer<1>(xp) + X_RS;
        mma_tile<false>(acc[2], H[3], HI(11));
        settle_n<12, 2>(ok);
        if (!pass) bar_sync(BAR_GO, 160);
        WG_WAIT(2); pin(acc[1]);
        RELEASE(8, 9);
        send_half<0>(rs_out, acc[1], rtag);
        mma_tile_reuse(acc[3], H[0], LO(12));
        SCHED();
        send_half<1>(rs_out, acc[1], rtag);
        mma_tile<false>(acc[3], H[1], HI(12));
        rs_out = peer<2>(xp) + X_RS + 512;
        WG_WAIT(2); pin(acc[2]);
        send_half<0>(rs_out, acc[2], rtag);
        mma_tile<false>(acc[3], H[2], LO(13));
        SCHED();
        ok = probe_n<14, 2>();
        send_half<1>(rs_out, acc[2], rtag);
        mma_tile<false>(acc[3], H[3], HI(13));
        settle_n<14, 2>(ok);
        mma_tile_reuse(acc[1], H[0], LO(14));
        rs_out = peer<3>(xp) + X_RS + 1024;
        announce(sc, tid == 0);
        fetch(rs_in, A[1]);
        SCHED();
        mma_tile<false>(acc[1], H[1], HI(14));
        WG_WAIT(2); pin(acc[3]);
        send_half<0>(rs_out, acc[3], rtag);
        send_half<1>(rs_out, acc[3], rtag);
        mma_tile<false>(acc[1], H[2], LO(15)); mma_tile<false>(acc[1], H[3], HI(15));
        SCHED();
        fetch(rs_in + 512, A[2]);
        SCHED();
        res_load(maddr, acc[2]);
        bar_sync(BAR_GO, 160);
        fetch(rs_in + 1024, A[3]);
        if (!pass) acquire_n<F_QKV, 3>();
        {
          uint32_t spin = 0;
          while (__builtin_expect(stale(miss(A[1], rtag) | miss(A[2], rtag) | miss(A[3], rtag)), 0) && ++spin < SPIN_LIMIT) {
            if (stale(miss(A[1], rtag) | miss(A[2], rtag))) { fetch(rs_in, A[1]); fetch(rs_in + 512, A[2]); }
            fetch(rs_in + 1024, A[3]);
          }
        }
        announce(sc, tid == 0 && !pass);
        mma_add_half(acc[2], A[1]);
        mma_add_half(acc[2], A[2]);
        mma_add_half(acc[2], A[3]);
        PROF_MARK2(4, 20);
        WG_WAIT(0); pin(acc[2]); pin(acc[1]);
#pragma unroll
        for (int i = 0; i < 16; i++) A[0][i] = pack2(fmaf(acc[1][2 * i], 0.5f, acc[2][2 * i]), fmaf(acc[1][2 * i + 1], 0.5f, acc[2][2 * i + 1]));
        if (pass) {
          PROF_MARK(21);
          stat_publish(A[0], sc, here(th), 0);
          stat_fetch(sc, st);
          const RowNorm fn = stat_finish(sc, st, 0, 1.f);
          const float nm0 = -fn.m0 * fn.rs0, nm1 = -fn.m1 * fn.rs1;
#pragma unroll
          for (int i = 0; i < 16; i++) {
            const float rs = (i & 1) ? fn.rs1 : fn.rs0, nm = (i & 1) ? nm1 : nm0;
            A[0][i] = pack2(fmaf(bf_lo(A[0][i]), rs, nm), fmaf(bf_hi(A[0][i]), rs, nm));
          }
          tile_store(here(maddr), A[0]);
          __syncwarp();
          const int row = 16 * w + (lane >> 3);
          uint4* dst = (uint4*)(out + ((size_t)batch * T_SEQ + t * 64 + row) * DM + 64 * r) + (lane & 7);
          const uint32_t src = stg + row * 128 + (((lane & 7) ^ (lane >> 3)) << 4);
#pragma unroll
          for (int i = 0; i < 4; i++) {
            uint4 v;
            lds128((src ^ ((i & 1) << 6)) + i * 512, v.x, v.y, v.z, v.w);
            if (row + 4 * i < nvalid) dst[i * 4 * (DM / 8)] = v;
          }
          PROF_MARK(22);
          PROF_TIME(31);
          break;
        }
        send_residual(A[0], sc, xp, maddr, 1);
        PROF_MARK(5);
        mma_tile<true>(acc[0], A[0], LO(F_QKV)); mma_tile<true>(acc[1], A[0], HI(F_QKV));
        mma_tile<true>(acc[2], A[0], LO(F_QKV + 1));
        gather_first<1, X_AG0>(A, st, sc, xp, 1);
        mma_tile<false>(acc[0], A[1], LO(F_QKV + 2)); mma_tile<false>(acc[1], A[1], HI(F_QKV + 2));
        acquire_n<F_QKV + 3, 3>();
        bar_sync(BAR_CS, 256);
        gather_rest<1, X_AG0>(A, xp, 1);
        PROF_MARK(6);
        mma_tile<false>(acc[0], A[2], LO(F_QKV + 3)); mma_tile<false>(acc[0], A[3], LO(F_QKV + 4));
        SCHED();
        {
          const RowNorm n = stat_finish(sc, st, 1, 1.f);
          rs0 = row0 < nvalid ? n.rs0 : 0.f; rs1 = row0 + 8 < nvalid ? n.rs1 : 0.f;
          mean_frag(mu, n, q == 3);
        }
        mma_fold<2 * CS_QKV - 6>(acc[0], mu);
        RELEASE(10, 15);
        WG_WAIT(0); pin(acc[0]);
        scale_pack(acc[0], Q, rs0, rs1);
        tile_store(here(maddr), Q);
        SCHED();
        mma_tile<false>(acc[1], A[2], HI(F_QKV + 3));
        fence_async_smem();
        bar_arrive(BAR_K, 160);
        mma_tile_fold<2 * CS_QKV - 4>(acc[1], A[3], HI(F_QKV + 4), mu);
        mma_tile<false>(acc[2], A[1], HI(F_QKV + 1)); mma_tile<false>(acc[2], A[2], LO(F_QKV + 5));
        WG_WAIT(2); pin(acc[1]);
        scale_pack(acc[1], Q, rs0, rs1);
        tile_store(here(maddr) + TILE_BYTES, Q);
        fence_async_smem();
        bar_arrive(BAR_V, 160);
        mma_tile_fold<2 * CS_QKV - 2>(acc[2], A[3], HI(F_QKV + 5), mu);
        WG_WAIT(0); pin(acc[2]);
        scale_pack(acc[2], Q, rs0 * SM_SCALE_LOG2, rs1 * SM_SCALE_LOG2);
        frag_store(here(qslot), Q);
        bar_arrive(BAR_Q, 256);
        RELEASE(F_QKV, F_QKV + 5);
      } else {
        bar_sync(BAR_Q, 256);
#pragma unroll
        for (int s = 0; s < 4; s++) lds128(qslot + s * 512, Q[4 * s], Q[4 * s + 1], Q[4 * s + 2], Q[4 * s + 3]);
        if (w < 2) {
          const uint32_t v = w ? 0u : 0x3F803F80u;
#pragma unroll
          for (int s = 0; s < 4; s++) sts128(qslot + s * 512, v, v, v, v);
          fence_async_smem();
        }
      }
      bar_sync(BAR_ATT, 256);
      PROF_MARK(7);

      const int dir = cw == 0 ? -1 : 1;
      uint32_t tap[15];
      {
        const uint32_t* dwp = (const uint32_t*)(dw + 64 * r) + lane + 7 * (DM / 2);
#pragma unroll
        for (int k = 0; k < 15; k++) tap[k] = __ldg(dwp + dir * (k - 7) * (DM / 2));
      }

      float O[36];
      {
        float S[2][32];
        uint32_t P[2][16], nm[4];
#pragma unroll
        for (int i = 0; i < 32; i++) { S[0][i] = 0.f; S[1][i] = 0.f; }
        pin(Q); pin(S[0]);
        WG_FENCE();
        qk_tile(S[0], Q, RING_K + (SM_STG >> 4));
        WG_COMMIT();
#pragma unroll
        for (int i = 0; i < 36; i++) O[i] = 0.f;
#pragma unroll
        for (int i = 0; i < 16; i++) P[1][i] = 0u;
        WG_WAIT(0); pin(S[0]);
        const float m0 = tile_max<0>(S[0]), m1 = tile_max<2>(S[0]);
        nm[0] = pack2(q ? 0.f : -m0, 0.f); nm[1] = pack2(q ? 0.f : -m1, 0.f); nm[2] = 0u; nm[3] = 0u;
#pragma unroll
        for (int k = 0; k < 15; k++) asm("mul.rn.bf16x2 %0, %0, %1;" : "+r"(tap[k]) : "r"(0x3F003F00u));
        pin(nm); pin(O); pin(P[1]); pin(tap);
        uint32_t sk = wg, sv = F_SPARE % NSTAGE + wg;
        mbar_wait(SM_BASE + SM_FULL + sv * 8, 1);
        mbar_wait(SM_BASE + SM_FULL + sk * 8, 0);
        if (wg == 1) bar_sync(BAR_ATT, 256);
        PROF_MARK(8);
        WG_FENCE();
        qk_tile(S[0], Q, RING_K + sk * 1024);
        qk_shift(S[0], nm);
        WG_COMMIT();
        WG_WAIT(0); pin(S[0]); pin(S[1]);
        if (wg == 0) bar_arrive(BAR_ATT, 256);
#pragma unroll 1
        for (int it = 0; it < 4; it++) {
          const uint32_t sn = it >= 2 ? wg : sk + 4;
          uint32_t ok = 1;
          mbar_probe(ok, SM_BASE + SM_FULL + sn * 8, it >= 2);
          mbar_probe(ok, SM_BASE + SM_FULL + (sk + 2) * 8, it == 3);
          attn_step(S[0], S[1], P[0], P[1], O, Q, nm, RING_K + sk * 1024 + 512, RING_V + (sv * 1024 + 512) * V_STEP, true, it > 0);
          PROF_MARK(24 + it * 3);
          if (__builtin_expect(!ok, 0)) {
            mbar_wait(SM_BASE + SM_FULL + sn * 8, it >= 2);
            mbar_wait(SM_BASE + SM_FULL + (sk + 2) * 8, it == 3);
          }
          WG_WAIT(0); pin(O); pin(S[1]); pin(P[1]);
          asm volatile("{\n.reg .pred p;\nsetp.eq.u32 p, %2, 0;\n@p mbarrier.arrive.shared::cta.b64 _, [%0];\n@p mbarrier.arrive.shared::cta.b64 _, [%1];\n}"
                       :: "r"(SM_BASE + SM_EMPTY + sk * 8), "r"(SM_BASE + SM_EMPTY + sv * 8), "r"(lane) : "memory");
          PROF_MARK(25 + it * 3);
          sv = sk + 2; sk = sn;
          attn_step(S[1], S[0], P[1], P[0], O, Q, nm, RING_K + sk * 1024, RING_V + (sv * 1024) * V_STEP, it < 3, true);
          WG_WAIT(0); pin(O); pin(S[0]); pin(P[0]);
          PROF_MARK(26 + it * 3);
        }
        WG_FENCE();
        pv_tile(O, P[1], RING_V + (sv * 1024 + 512) * V_STEP, wg << 22);
        WG_COMMIT();
        announce<1>(sc, th == 0);
        WG_WAIT(0); pin(O);
      }
      PROF_MARK(9);

      {
        const uint32_t mo = stg + here(th) * 16;
        sts64(mo + 5 * 4096 + wg * 8, __float_as_uint(O[32]), __float_as_uint(O[34]));
        if (wg == 0) {
#pragma unroll
          for (int i = 4; i < 8; i++)
            sts128(mo + i * 2048, __float_as_uint(O[4 * i]), __float_as_uint(O[4 * i + 1]), __float_as_uint(O[4 * i + 2]), __float_as_uint(O[4 * i + 3]));
        } else {
#pragma unroll
          for (int i = 0; i < 4; i++)
            sts128(mo + i * 2048, __float_as_uint(O[4 * i]), __float_as_uint(O[4 * i + 1]), __float_as_uint(O[4 * i + 2]), __float_as_uint(O[4 * i + 3]));
#pragma unroll
          for (int i = 0; i < 16; i++) O[i] = O[16 + i];
        }
        bar_sync(BAR_MERGE, 256);
        uint32_t e[4];
        lds128(mo + 5 * 4096, e[0], e[1], e[2], e[3]);
        O[32] = __uint_as_float(e[0]) + __uint_as_float(e[2]); O[34] = __uint_as_float(e[1]) + __uint_as_float(e[3]);
#pragma unroll
        for (int i = 0; i < 4; i++) {
          lds128(mo + wg * TILE_BYTES + i * 2048, e[0], e[1], e[2], e[3]);
#pragma unroll
          for (int k = 0; k < 4; k++) O[4 * i + k] += __uint_as_float(e[k]);
        }
        const bool safe = O[32] > 0x1p-60f && O[32] < 0x1p60f && O[34] > 0x1p-60f && O[34] < 0x1p60f;
        if (__builtin_expect(__any_sync(0xffffffffu, !safe), 0)) attention_exact(O, Q, sc, batch * 4 + r, lane, wg);
        const float i0 = rcp_hw(O[32]), i1 = rcp_hw(O[34]);
#pragma unroll
        for (int i = 0; i < 8; i++) { const float v = (i & 1) ? i1 : i0; A[0][i] = pack2(O[2 * i] * v, O[2 * i + 1] * v); }
        A[0][0] &= ~1u; A[0][4] &= ~1u;
        uint4* dst = xp + X_AG1 + wg * 256;
        SCHED();
        st_vec(dst, A[0][0], A[0][1], A[0][2], A[0][3]);
        st_vec(dst + 128, A[0][4], A[0][5], A[0][6], A[0][7]);
        SCHED();
      }
      if (wg == 1) {
        const uint32_t mo = stg + TILE_BYTES + here(th) * 16;
        sts128(mo, A[0][0], A[0][1], A[0][2], A[0][3]);
        sts128(mo + 2048, A[0][4], A[0][5], A[0][6], A[0][7]);
        bar_arrive(BAR_HALF, 256);
      } else {
        PROF_MARK(10);
        const uint32_t mo = stg + TILE_BYTES + here(th) * 16;
        bar_sync(BAR_HALF, 256);
        lds128(mo, A[0][8], A[0][9], A[0][10], A[0][11]);
        lds128(mo + 2048, A[0][12], A[0][13], A[0][14], A[0][15]);
        proj_residual<F_WO, 6>(A, sc, xp, maddr, 0, lane);
        PROF_MARK(12);
        float acc[2][32];
        mma_tile<true>(acc[0], A[0], LO(F_PW1)); mma_tile<true>(acc[1], A[0], HI(F_PW1));
        gather_first<1, X_AG0>(A, st, sc, xp, 0);
        mma_tile<false>(acc[1], A[1], HI(F_PW1 + 1)); mma_tile<false>(acc[0], A[1], LO(F_PW1 + 1));
        gather_rest<1, X_AG0>(A, xp, 0);
        PROF_MARK(13);
        mma_tile<false>(acc[1], A[2], HI(F_PW1 + 2)); mma_tile<false>(acc[1], A[3], HI(F_PW1 + 3));
        WG_WAIT(2);
        RELEASE(F_WO, F_PW1 + 1);
        SCHED();
        uint32_t mu[4];
        const RowNorm n = stat_finish(sc, st, 0, 0.5f);
        const float rs0 = row0 < nvalid ? n.rs0 : 0.f, rs1 = row0 + 8 < nvalid ? n.rs1 : 0.f;
        mean_frag(mu, n, q == 0);
        mma_fold<2 * CS_PW1 + 2>(acc[1], mu);
        mma_tile<false>(acc[0], A[2], LO(F_PW1 + 2));
        mma_tile_fold<2 * CS_PW1>(acc[0], A[3], LO(F_PW1 + 3), mu);
        WG_WAIT(2); pin(acc[1]);
#pragma unroll
        for (int i = 0; i < 32; i++) acc[1][i] = tanh_hw(acc[1][i] * ((i & 2) ? rs1 : rs0));
#pragma unroll
        for (int i = 0; i < 32; i++) { const float rs = (i & 2) ? rs1 : rs0; acc[1][i] = fmaf(acc[1][i], rs, rs); }
        pin(acc[1]);
        SCHED();
        WG_WAIT(0); pin(acc[0]);
#pragma unroll
        for (int i = 0; i < 16; i++) A[0][i] = pack2(acc[0][2 * i] * acc[1][2 * i], acc[0][2 * i + 1] * acc[1][2 * i + 1]);
        const uint32_t ga = stg + TILE_BYTES + here(mrow) * G_PITCH + (lane >> 4) * 16;
#pragma unroll
        for (int s = 0; s < 4; s++) stsm4(ga + s * 32, &A[0][4 * s]);
      }
      {
        const uint32_t gsrc = stg + TILE_BYTES + (8 * cw - 7) * G_PITCH + lane * 4;
        const bool edge = cw == 0 || cw == 7;
        const bool nbr = cw == 0 ? t > 0 : t < 15;
        uint4* const hdst = &sc->x[b + 4 * dir][X_HALO + (cw == 0 ? 96 : 0) + lane];
        uint32_t in[22];
        bar_sync(BAR_G, 256);
        PROF_MARK(14);
        if (cw == 0) {
#pragma unroll
          for (int i = 14; i >= 0; i--) in[i] = lds32(gsrc + (21 - i) * G_PITCH);
        } else {
#pragma unroll
          for (int i = 14; i >= 0; i--) in[i] = lds32(gsrc + i * G_PITCH);
        }
        if (edge) {
          if (nbr) {
            st_vec(hdst, HALO_TAG, in[14], in[13], in[12]);
            st_vec(hdst + 32, HALO_TAG, in[11], in[10], in[9]);
            st_vec(hdst + 64, HALO_TAG, in[8], 0u, 0u);
          }
        } else {
#pragma unroll
          for (int i = 15; i < 22; i++) in[i] = lds32(gsrc + i * G_PITCH);
        }
        if (cw == 0) PROF_MARK0(40);
        uint32_t cv[8];
#pragma unroll
        for (int i = 0; i < 15; i++)
#pragma unroll
          for (int o = 0; o < 8; o++) {
            if (i == o) asm("mul.rn.bf16x2 %0, %1, %2;" : "=r"(cv[o]) : "r"(in[i]), "r"(tap[0]));
            if (i > o) asm("fma.rn.bf16x2 %0, %1, %2, %0;" : "+r"(cv[o]) : "r"(in[i]), "r"(tap[i - o]));
          }
        pin(cv);
        if (cw == 0) PROF_MARK0(41);
        if (edge) {
#pragma unroll
          for (int i = 15; i < 22; i++) in[i] = 0u;
          if (nbr) {
            const uint4* src = &sc->x[b][X_HALO + (cw == 0 ? 0 : 96) + lane];
            uint32_t e0, e1, e2, u0, u1, spin = 0;
#pragma unroll 1
            do {
              ld_vec(src, e0, in[15], in[16], in[17]);
              ld_vec(src + 32, e1, in[18], in[19], in[20]);
              ld_vec(src + 64, e2, in[21], u0, u1);
            } while (__any_sync(0xffffffffu, ((e0 ^ HALO_TAG) | (e1 ^ HALO_TAG) | (e2 ^ HALO_TAG)) != 0) && ++spin < SPIN_LIMIT);
          }
          announce<1>(sc, lane == 0);
        }
#pragma unroll
        for (int i = 15; i < 22; i++)
#pragma unroll
          for (int o = 0; o < 8; o++)
            if (i - o <= 14) asm("fma.rn.bf16x2 %0, %1, %2, %0;" : "+r"(cv[o]) : "r"(in[i]), "r"(tap[i - o]));
        if (cw == 0) PROF_MARK0(42);
        if (cw == 7) PROF_MARK0(43);
        const uint32_t fl = cw == 0 ? 7 : 0;
        const uint32_t cdst = (stg + cw * 1024 + lane * 4) ^ (fl * 144);
#pragma unroll
        for (int o = 0; o < 8; o++) {
          const float a = bf_lo(cv[o]), c = bf_hi(cv[o]);
          sts32(cdst ^ (o * 144), pack2(fmaf(a, tanh_hw(a), a), fmaf(c, tanh_hw(c), c)));
        }
      }
      if (wg == 1) {
        bar_arrive(BAR_C, 256);
        break;
      }
      bar_sync(BAR_C, 256);
      tile_load(here(maddr), A[0]);
      PROF_MARK(15);
      publish(xp + X_AG1, A[0], 1);
      proj_residual<F_PW2, 2>(A, sc, xp, maddr, 1, lane);
      PROF_MARK(17);
    }
  }
}

typedef CUresult (*EncodeFn)(CUtensorMap*, CUtensorMapDataType, cuuint32_t, void*, const cuuint64_t*, const cuuint64_t*,
                             const cuuint32_t*, const cuuint32_t*, CUtensorMapInterleave, CUtensorMapSwizzle,
                             CUtensorMapL2promotion, CUtensorMapFloatOOBfill);

void make_map(EncodeFn fn, CUtensorMap* m, const void* w, int rows, int cols, CUtensorMapSwizzle swz) {
  const cuuint64_t dims[2] = {(cuuint64_t)cols, (cuuint64_t)rows}, strides[1] = {(cuuint64_t)cols * 2};
  const cuuint32_t box[2] = {64, 64}, es[2] = {1, 1};
  fn(m, CU_TENSOR_MAP_DATA_TYPE_BFLOAT16, 2, const_cast<void*>(w), dims, strides, box, es, CU_TENSOR_MAP_INTERLEAVE_NONE,
     swz, CU_TENSOR_MAP_L2_PROMOTION_L2_128B, CU_TENSOR_MAP_FLOAT_OOB_FILL_NONE);
}

}

extern "C" void kernel_launch(void* const* d_in, const int* in_sizes, int n_in, void* d_out, int out_size) {
  static EncodeFn fn = nullptr;
  static Scratch* sc = nullptr;
  if (!fn) {
    void* f = nullptr;
    cudaDriverEntryPointQueryResult st;
    cudaGetDriverEntryPoint("cuTensorMapEncodeTiled", &f, cudaEnableDefault, &st);
    fn = (EncodeFn)f;
    void* raw = nullptr;
    cudaGetSymbolAddress(&raw, g_scratch);
    sc = (Scratch*)(((uintptr_t)raw + X_ALIGN - 1) & ~(uintptr_t)(X_ALIGN - 1));
    cudaFuncSetAttribute(conformer_kernel, cudaFuncAttributeMaxDynamicSharedMemorySize, SM_TOTAL);
  }
  typedef const __nv_bfloat16* W;
  const CUtensorMapSwizzle S = CU_TENSOR_MAP_SWIZZLE_128B;
  Params p;
  make_map(fn, &p.map[M_FF1A], d_in[1], 256, 1024, S);
  make_map(fn, &p.map[M_FF1B], d_in[2], 1024, 256, S);
  make_map(fn, &p.map[M_QKV], d_in[3], 256, 768, S);
  make_map(fn, &p.map[M_WO], d_in[4], 256, 256, S);
  make_map(fn, &p.map[M_PW1], d_in[5], 256, 512, S);
  make_map(fn, &p.map[M_PW2], d_in[7], 256, 256, S);
  make_map(fn, &p.map[M_FF2A], d_in[8], 256, 1024, S);
  make_map(fn, &p.map[M_FF2B], d_in[9], 1024, 256, S);
  p.w_ff1b = (W)d_in[2]; p.w_qkv = (W)d_in[3]; p.w_o = (W)d_in[4]; p.w_pw1 = (W)d_in[5];
  p.w_pw2 = (W)d_in[7]; p.w_ff2a = (W)d_in[8]; p.w_ff2b = (W)d_in[9];

  cudaLaunchConfig_t cfg = {};
  cfg.gridDim = dim3(NCTA);
  cfg.blockDim = dim3(384);
  cfg.dynamicSmemBytes = SM_TOTAL;
  cfg.stream = cudaStreamPerThread;
  cudaLaunchAttribute at[1];
  at[0].id = cudaLaunchAttributeCooperative;
  at[0].val.cooperative = 1;
  cfg.attrs = at;
  cfg.numAttrs = 1;
  cudaLaunchKernelEx(&cfg, conformer_kernel, sc, (__nv_bfloat16*)d_out, (W)d_in[6], (W)d_in[0], (W)d_in[1], p);
}
```

```cpp
#include <cuda_runtime.h>
#include <cuda_bf16.h>
#include <cuda.h>
#include <stdint.h>

namespace {

constexpr int T_SEQ = 1000;
constexpr int DM = 256;
constexpr int NCTA = 128;
constexpr int NSTAGE = 12;
constexpr uint32_t STAGE_BYTES = 16384;
constexpr uint32_t TILE_BYTES = 8192;
constexpr uint32_t SM_BASE = 1024;
constexpr uint32_t SM_STG = NSTAGE * STAGE_BYTES;
constexpr uint32_t SM_FULL = SM_STG + 32768;
constexpr uint32_t SM_EMPTY = SM_FULL + 96;
constexpr uint32_t SM_EYE = SM_FULL + 256;
constexpr uint32_t SM_ONE = SM_FULL + 640;
constexpr uint32_t SM_CS = SM_FULL + 768;
constexpr uint32_t SM_TOTAL = SM_FULL + 3072;
constexpr int CS_FF2 = 0, CS_PW1 = 4, CS_QKV = 6;
constexpr uint32_t SPIN_LIMIT = 1u << 16;
constexpr float LN_EPS = 1e-5f;
constexpr float SM_SCALE_LOG2 = 0.125f * 1.4426950408889634f;
constexpr uint32_t G_PITCH = 144;
#define PF1 600
#define PF2 1200
#define PF3 3000
#define CLR_PACE 100

constexpr int F_QKV = 16, F_SPARE = 22, F_KV = 24, F_WO = 40, F_PW1 = 42, F_PW2 = 46, F_TOTAL = 64;
enum { M_FF1A, M_FF1B, M_QKV, M_WO, M_PW1, M_PW2, M_FF2A, M_FF2B, M_COUNT };
enum { BAR_K = 1, BAR_V, BAR_Q, BAR_MERGE, BAR_G, BAR_C, BAR_WG1, BAR_GO, BAR_CS, BAR_ATT, BAR_INIT, BAR_HALF };

struct Params {
  CUtensorMap map[M_COUNT];
  const __nv_bfloat16 *w_ff1b, *w_qkv, *w_o, *w_pw1, *w_pw2, *w_ff2a, *w_ff2b;
};

constexpr int X_RS = 0, X_AG1 = X_RS, X_HALO = X_RS + 512, X_AG0 = 1536, X_ST = 2048, X_SIZE = 4096;
constexpr uint32_t HALO_TAG = 0xFFFF0001u;
struct Scratch {
  uint4 x[NCTA][X_SIZE];
  uint4 kv[8][2][16][512];
  uint4 cs[576];
  uint32_t flag[8][32][32];
  uint32_t step[NCTA][32];
};
constexpr size_t X_ALIGN = 4 * X_SIZE * sizeof(uint4);
__device__ uint8_t g_scratch[sizeof(Scratch) + X_ALIGN];
#define PROF_TIME(i)
#define PROF_MARK(i)
#define PROF_MARK2(i, j)
#define PROF_MARK0(i)
#define PROF_AT(a)

__device__ __forceinline__ void mbar_init(uint32_t bar, uint32_t cnt) {
  asm volatile("mbarrier.init.shared::cta.b64 [%0], %1;" :: "r"(bar), "r"(cnt) : "memory");
}
__device__ __forceinline__ void mbar_wait(uint32_t bar, uint32_t parity) {
  asm volatile("{\n.reg .pred p;\n.reg .u32 c;\nmov.u32 c, 0;\n"
               "WAIT_LOOP:\nmbarrier.try_wait.parity.shared::cta.b64 p, [%0], %1;\n@p bra WAIT_DONE;\n"
               "add.u32 c, c, 1;\nsetp.lt.u32 p, c, %2;\n@p bra WAIT_LOOP;\nWAIT_DONE:\n}"
               :: "r"(bar), "r"(parity), "n"(SPIN_LIMIT) : "memory");
}
__device__ __forceinline__ void mbar_arrive(uint32_t bar) {
  asm volatile("mbarrier.arrive.shared::cta.b64 _, [%0];" :: "r"(bar) : "memory");
}
#define bar_sync(id, n) asm volatile("bar.sync %0, %1;" :: "n"((int)(id)), "n"(n) : "memory")
#define bar_arrive(id, n) asm volatile("bar.arrive %0, %1;" :: "n"((int)(id)), "n"(n) : "memory")
__device__ __forceinline__ void fence_async_smem() { asm volatile("fence.proxy.async.shared::cta;" ::: "memory"); }

__device__ __forceinline__ void st_vec(uint4* p, uint32_t a, uint32_t b, uint32_t c, uint32_t d) {
  asm volatile("{\n.reg .b128 v;\n.reg .b64 lo, hi;\nmov.b64 lo, {%1, %2};\nmov.b64 hi, {%3, %4};\nmov.b128 v, {lo, hi};\n"
               "st.relaxed.gpu.global.b128 [%0], v;\n}" :: "l"(p), "r"(a), "r"(b), "r"(c), "r"(d) : "memory");
}
__device__ __forceinline__ void ld_vec(const uint4* p, uint32_t& a, uint32_t& b, uint32_t& c, uint32_t& d) {
  asm volatile("{\n.reg .b128 v;\n.reg .b64 lo, hi;\nld.relaxed.gpu.global.b128 v, [%4];\nmov.b128 {lo, hi}, v;\n"
               "mov.b64 {%0, %1}, lo;\nmov.b64 {%2, %3}, hi;\n}" : "=r"(a), "=r"(b), "=r"(c), "=r"(d) : "l"(p) : "memory");
}
__device__ __forceinline__ void sts128(uint32_t a, uint32_t x, uint32_t y, uint32_t z, uint32_t w) {
  asm volatile("st.shared.v4.u32 [%0], {%1, %2, %3, %4};" :: "r"(a), "r"(x), "r"(y), "r"(z), "r"(w) : "memory");
}
__device__ __forceinline__ void lds128(uint32_t a, uint32_t& x, uint32_t& y, uint32_t& z, uint32_t& w) {
  asm volatile("ld.shared.v4.u32 {%0, %1, %2, %3}, [%4];" : "=r"(x), "=r"(y), "=r"(z), "=r"(w) : "r"(a) : "memory");
}
__device__ __forceinline__ uint32_t lds32(uint32_t a) {
  uint32_t x; asm volatile("ld.shared.u32 %0, [%1];" : "=r"(x) : "r"(a) : "memory"); return x;
}
__device__ __forceinline__ void sts32(uint32_t a, uint32_t x) { asm volatile("st.shared.u32 [%0], %1;" :: "r"(a), "r"(x) : "memory"); }
__device__ __forceinline__ void sts64(uint32_t a, uint32_t x, uint32_t y) {
  asm volatile("st.shared.v2.u32 [%0], {%1, %2};" :: "r"(a), "r"(x), "r"(y) : "memory");
}
__device__ __forceinline__ void stsm4(uint32_t a, const uint32_t* r) {
  asm volatile("stmatrix.sync.aligned.m8n8.x4.shared.b16 [%0], {%1, %2, %3, %4};" :: "r"(a), "r"(r[0]), "r"(r[1]), "r"(r[2]), "r"(r[3]) : "memory");
}
__device__ __forceinline__ void ldsm4(uint32_t a, uint32_t* r) {
  asm volatile("ldmatrix.sync.aligned.m8n8.x4.shared.b16 {%0, %1, %2, %3}, [%4];" : "=r"(r[0]), "=r"(r[1]), "=r"(r[2]), "=r"(r[3]) : "r"(a) : "memory");
}
__device__ __forceinline__ uint32_t pack2(float lo, float hi) {
  uint32_t r; asm("cvt.rn.bf16x2.f32 %0, %1, %2;" : "=r"(r) : "f"(hi), "f"(lo)); return r;
}
__device__ __forceinline__ float bf_lo(uint32_t w) { return __uint_as_float(w << 16); }
__device__ __forceinline__ float bf_hi(uint32_t w) { return __uint_as_float(w & 0xffff0000u); }
__device__ __forceinline__ float tanh_hw(float x) { float y; asm volatile("tanh.approx.f32 %0, %1;" : "=f"(y) : "f"(x)); return y; }
__device__ __forceinline__ float rcp_hw(float x) { float y; asm("rcp.approx.ftz.f32 %0, %1;" : "=f"(y) : "f"(x)); return y; }
__device__ __forceinline__ float rsqrt_hw(float x) { float y; asm("rsqrt.approx.ftz.f32 %0, %1;" : "=f"(y) : "f"(x)); return y; }
__device__ __forceinline__ float ex2_hw(float x) { float y; asm("ex2.approx.ftz.f32 %0, %1;" : "=f"(y) : "f"(x)); return y; }

__device__ __forceinline__ uint32_t here(uint32_t v) { asm volatile("" : "+r"(v)); return v; }

#define SCHED() asm volatile("pmevent 1;" ::: "memory")
__device__ __forceinline__ void cp_async16(uint32_t dst, const void* src) {
  asm volatile("cp.async.cg.shared.global [%0], [%1], 16;" :: "r"(dst), "l"(src) : "memory");
}
__device__ __forceinline__ void cp_async_wait(int n) {
  if (n == 0) asm volatile("cp.async.wait_group 0;" ::: "memory");
  if (n == 1) asm volatile("cp.async.wait_group 1;" ::: "memory");
  if (n == 2) asm volatile("cp.async.wait_group 2;" ::: "memory");
  if (n == 3) asm volatile("cp.async.wait_group 3;" ::: "memory");
}
#define WG_FENCE() asm volatile("wgmma.fence.sync.aligned;" ::: "memory")
#define WG_COMMIT() asm volatile("wgmma.commit_group.sync.aligned;" ::: "memory")
#define WG_WAIT(n) asm volatile("wgmma.wait_group.sync.aligned %0;" :: "n"(n) : "memory")

template <int N> __device__ __forceinline__ void pin(float (&d)[N]) {
#pragma unroll
  for (int i = 0; i < N; i++) asm volatile("" : "+f"(d[i]) :: "memory");
}
template <int N> __device__ __forceinline__ void pin(uint32_t (&d)[N]) {
#pragma unroll
  for (int i = 0; i < N; i++) asm volatile("" : "+r"(d[i]) :: "memory");
}

#define WG_D32 "{%0, %1, %2, %3, %4, %5, %6, %7, %8, %9, %10, %11, %12, %13, %14, %15, %16, %17, %18, %19, %20, %21, %22, %23, %24, %25, %26, %27, %28, %29, %30, %31}"
template <int TB> __device__ __forceinline__ void wgmma64_acc(float (&d)[32], const uint32_t* a, uint64_t db) {
  asm volatile("wgmma.mma_async.sync.aligned.m64n64k16.f32.bf16.bf16 " WG_D32 ", {%32, %33, %34, %35}, %36, 1, 1, 1, %37;"
    : "+f"(d[0]), "+f"(d[1]), "+f"(d[2]), "+f"(d[3]), "+f"(d[4]), "+f"(d[5]), "+f"(d[6]), "+f"(d[7]),
      "+f"(d[8]), "+f"(d[9]), "+f"(d[10]), "+f"(d[11]), "+f"(d[12]), "+f"(d[13]), "+f"(d[14]), "+f"(d[15]),
      "+f"(d[16]), "+f"(d[17]), "+f"(d[18]), "+f"(d[19]), "+f"(d[20]), "+f"(d[21]), "+f"(d[22]), "+f"(d[23]),
      "+f"(d[24]), "+f"(d[25]), "+f"(d[26]), "+f"(d[27]), "+f"(d[28]), "+f"(d[29]), "+f"(d[30]), "+f"(d[31])
    : "r"(a[0]), "r"(a[1]), "r"(a[2]), "r"(a[3]), "l"(db), "n"(TB));
}
template <int TB> __device__ __forceinline__ void wgmma64_reuse(float (&d)[32], const uint32_t* a, uint64_t db, uint32_t zero) {
  asm volatile("{\n.reg .pred p;\nsetp.ne.u32 p, %37, 0;\nwgmma.mma_async.sync.aligned.m64n64k16.f32.bf16.bf16 " WG_D32 ", {%32, %33, %34, %35}, %36, p, 1, 1, %38;\n}"
    : "+f"(d[0]), "+f"(d[1]), "+f"(d[2]), "+f"(d[3]), "+f"(d[4]), "+f"(d[5]), "+f"(d[6]), "+f"(d[7]),
      "+f"(d[8]), "+f"(d[9]), "+f"(d[10]), "+f"(d[11]), "+f"(d[12]), "+f"(d[13]), "+f"(d[14]), "+f"(d[15]),
      "+f"(d[16]), "+f"(d[17]), "+f"(d[18]), "+f"(d[19]), "+f"(d[20]), "+f"(d[21]), "+f"(d[22]), "+f"(d[23]),
      "+f"(d[24]), "+f"(d[25]), "+f"(d[26]), "+f"(d[27]), "+f"(d[28]), "+f"(d[29]), "+f"(d[30]), "+f"(d[31])
    : "r"(a[0]), "r"(a[1]), "r"(a[2]), "r"(a[3]), "l"(db), "r"(zero), "n"(TB));
}
template <int TB> __device__ __forceinline__ void wgmma64_set(float (&d)[32], const uint32_t* a, uint64_t db) {
  asm volatile("wgmma.mma_async.sync.aligned.m64n64k16.f32.bf16.bf16 " WG_D32 ", {%32, %33, %34, %35}, %36, 0, 1, 1, %37;"
    : "=f"(d[0]), "=f"(d[1]), "=f"(d[2]), "=f"(d[3]), "=f"(d[4]), "=f"(d[5]), "=f"(d[6]), "=f"(d[7]),
      "=f"(d[8]), "=f"(d[9]), "=f"(d[10]), "=f"(d[11]), "=f"(d[12]), "=f"(d[13]), "=f"(d[14]), "=f"(d[15]),
      "=f"(d[16]), "=f"(d[17]), "=f"(d[18]), "=f"(d[19]), "=f"(d[20]), "=f"(d[21]), "=f"(d[22]), "=f"(d[23]),
      "=f"(d[24]), "=f"(d[25]), "=f"(d[26]), "=f"(d[27]), "=f"(d[28]), "=f"(d[29]), "=f"(d[30]), "=f"(d[31])
    : "r"(a[0]), "r"(a[1]), "r"(a[2]), "r"(a[3]), "l"(db), "n"(TB));
}

__device__ __forceinline__ void wgmma72_acc(float (&d)[36], const uint32_t* a, uint64_t db) {
  asm volatile("wgmma.mma_async.sync.aligned.m64n72k16.f32.bf16.bf16 {%0, %1, %2, %3, %4, %5, %6, %7, %8, %9, %10, %11, %12, %13, %14, %15, %16, %17, %18, %19, %20, %21, %22, %23, %24, %25, %26, %27, %28, %29, %30, %31, %32, %33, %34, %35}, {%36, %37, %38, %39}, %40, 1, 1, 1, 1;"
    : "+f"(d[0]), "+f"(d[1]), "+f"(d[2]), "+f"(d[3]), "+f"(d[4]), "+f"(d[5]), "+f"(d[6]), "+f"(d[7]), "+f"(d[8]),
      "+f"(d[9]), "+f"(d[10]), "+f"(d[11]), "+f"(d[12]), "+f"(d[13]), "+f"(d[14]), "+f"(d[15]), "+f"(d[16]), "+f"(d[17]),
      "+f"(d[18]), "+f"(d[19]), "+f"(d[20]), "+f"(d[21]), "+f"(d[22]), "+f"(d[23]), "+f"(d[24]), "+f"(d[25]), "+f"(d[26]),
      "+f"(d[27]), "+f"(d[28]), "+f"(d[29]), "+f"(d[30]), "+f"(d[31]), "+f"(d[32]), "+f"(d[33]), "+f"(d[34]), "+f"(d[35])
    : "r"(a[0]), "r"(a[1]), "r"(a[2]), "r"(a[3]), "l"(db));
}
__device__ __forceinline__ void wgmma16_acc(float* d, const uint32_t* a, uint64_t db) {
  asm volatile("wgmma.mma_async.sync.aligned.m64n16k16.f32.bf16.bf16 {%0, %1, %2, %3, %4, %5, %6, %7}, {%8, %9, %10, %11}, %12, 1, 1, 1, 0;"
    : "+f"(d[0]), "+f"(d[1]), "+f"(d[2]), "+f"(d[3]), "+f"(d[4]), "+f"(d[5]), "+f"(d[6]), "+f"(d[7])
    : "r"(a[0]), "r"(a[1]), "r"(a[2]), "r"(a[3]), "l"(db));
}
__device__ __forceinline__ void hmma(float (&d)[4], const uint32_t* a, uint32_t b0, uint32_t b1) {
  asm("mma.sync.aligned.m16n8k16.row.col.f32.bf16.bf16.f32 {%0, %1, %2, %3}, {%4, %5, %6, %7}, {%8, %9}, {%0, %1, %2, %3};"
    : "+f"(d[0]), "+f"(d[1]), "+f"(d[2]), "+f"(d[3]) : "r"(a[0]), "r"(a[1]), "r"(a[2]), "r"(a[3]), "r"(b0), "r"(b1));
}

__device__ __forceinline__ void hmma8(float (&d)[4], const uint32_t* a, uint32_t b0) {
  asm("mma.sync.aligned.m16n8k8.row.col.f32.bf16.bf16.f32 {%0, %1, %2, %3}, {%4, %5}, {%6}, {%0, %1, %2, %3};"
    : "+f"(d[0]), "+f"(d[1]), "+f"(d[2]), "+f"(d[3]) : "r"(a[0]), "r"(a[1]), "r"(b0));
}

template <bool FIRST> __device__ __forceinline__ void mma_tile(float (&d)[32], const uint32_t (&a)[16], uint64_t db) {
  WG_FENCE();
#pragma unroll
  for (int s = 0; s < 4; s++) {
    if (FIRST && s == 0) wgmma64_set<1>(d, &a[0], db); else wgmma64_acc<1>(d, &a[4 * s], db + s * 128);
  }
  WG_COMMIT();
}
__device__ __forceinline__ void mma_tile_reuse(float (&d)[32], const uint32_t (&a)[16], uint64_t db) {
  WG_FENCE();
  wgmma64_reuse<1>(d, &a[0], db, blockIdx.y);
#pragma unroll
  for (int s = 1; s < 4; s++) wgmma64_acc<1>(d, &a[4 * s], db + s * 128);
  WG_COMMIT();
}
template <int ROW> __device__ __forceinline__ void fold_step(float (&d)[32], const uint32_t (&mu)[4]) {
  wgmma64_acc<1>(d, mu, (uint64_t)((SM_BASE + SM_CS + ROW * 128) >> 4) | (uint64_t(1) << 16) | (uint64_t(1) << 62));
}
template <int ROW> __device__ __forceinline__ void mma_fold(float (&d)[32], const uint32_t (&mu)[4]) {
  WG_FENCE();
  fold_step<ROW>(d, mu);
  WG_COMMIT();
}
template <int ROW> __device__ __forceinline__ void mma_tile_fold(float (&d)[32], const uint32_t (&a)[16], uint64_t db, const uint32_t (&mu)[4]) {
  WG_FENCE();
#pragma unroll
  for (int s = 0; s < 4; s++) wgmma64_acc<1>(d, &a[4 * s], db + s * 128);
  fold_step<ROW>(d, mu);
  WG_COMMIT();
}
__device__ __forceinline__ void mma_add_half(float (&d)[32], const uint32_t (&a)[16]) {
  const uint64_t db = (uint64_t)((SM_BASE + SM_EYE) >> 4) | (uint64_t(8) << 16) | (uint64_t(8) << 32);
  WG_FENCE();
#pragma unroll
  for (int s = 0; s < 4; s++) wgmma16_acc(&d[8 * s], &a[4 * s], db);
  WG_COMMIT();
}
#define ACQUIRE(f) mbar_wait(SM_BASE + SM_FULL + ((f) % NSTAGE) * 8, ((f) / NSTAGE) & 1)
__device__ __forceinline__ void mbar_probe(uint32_t& ok, uint32_t bar, uint32_t parity) {
  asm volatile("{\n.reg .pred p;\nmbarrier.test_wait.parity.shared::cta.b64 p, [%1], %2;\nselp.u32 %0, %0, 0, p;\n}"
               : "+r"(ok) : "r"(bar), "r"(parity) : "memory");
}
template <int F, int N> __device__ __forceinline__ uint32_t probe_n() {
  static_assert(F % NSTAGE + N <= NSTAGE, "stages must not wrap");
  uint32_t ok = 1;
#pragma unroll
  for (int i = 0; i < N; i++) mbar_probe(ok, SM_BASE + SM_FULL + (F % NSTAGE + i) * 8, (F / NSTAGE) & 1);
  return ok;
}
template <int F, int N> __device__ __forceinline__ void settle_n(uint32_t ok) {
  if (__builtin_expect(!ok, 0)) {
#pragma unroll 1
    for (int i = 0; i < N; i++) mbar_wait(SM_BASE + SM_FULL + (F % NSTAGE + i) * 8, (F / NSTAGE) & 1);
  }
}
template <int F, int N> __device__ __forceinline__ void acquire_n() { settle_n<F, N>(probe_n<F, N>()); }
#define RELEASE(f0, f1) do { if (lane == 0) { _Pragma("unroll") for (int f_ = (f0); f_ <= (f1); f_++) mbar_arrive(SM_BASE + SM_EMPTY + (f_ % NSTAGE) * 8); } } while (0)
constexpr uint64_t RING = (uint64_t)(SM_BASE >> 4) | (uint64_t(1) << 16) | (uint64_t(64) << 32) | (uint64_t(1) << 62);
#define LO(f) (RING + ((f) % NSTAGE) * 1024)
#define HI(f) (RING + ((f) % NSTAGE) * 1024 + 512)

template <int C> __device__ __forceinline__ uint4* peer(uint4* p) {
  asm volatile("" : "+l"(p));
  return (uint4*)((uintptr_t)p ^ (C * X_SIZE * sizeof(uint4)));
}
__device__ __forceinline__ uint32_t clock_now() { uint32_t c; asm volatile("mov.u32 %0, %%clock;" : "=r"(c) :: "memory"); return c; }
__device__ __forceinline__ void publish(uint4* dst, uint32_t (&a)[16], uint32_t tag) {
#pragma unroll
  for (int s = 0; s < 4; s++) a[4 * s] = (a[4 * s] & ~1u) | tag;
  pin(a);
  SCHED();
#pragma unroll
  for (int s = 0; s < 4; s++) st_vec(dst + s * 128, a[4 * s], a[4 * s + 1], a[4 * s + 2], a[4 * s + 3]);
  SCHED();
}
__device__ __forceinline__ void fetch(const uint4* src, uint32_t (&a)[16]) {
#pragma unroll
  for (int s = 0; s < 4; s++) ld_vec(src + s * 128, a[4 * s], a[4 * s + 1], a[4 * s + 2], a[4 * s + 3]);
}
__device__ __forceinline__ uint32_t miss(const uint32_t (&a)[16], uint32_t tag) {
  return (a[0] ^ tag) | (a[4] ^ tag) | (a[8] ^ tag) | (a[12] ^ tag);
}
__device__ __forceinline__ bool stale(uint32_t v) { return __any_sync(0xffffffffu, here(v) & 1u); }
template <int N = 2> __device__ __forceinline__ void announce(Scratch* sc, bool leader) {
  asm volatile("{\n.reg .pred p;\nsetp.ne.u32 p, %1, 0;\n@p red.relaxed.gpu.global.add.u32 [%0], %2;\n}"
               :: "l"(sc->step[blockIdx.x]), "r"((uint32_t)leader), "n"(N) : "memory");
}
__device__ __forceinline__ uint32_t launch_index(const Scratch* sc) { return *(const volatile uint32_t*)sc->step[blockIdx.x] >> 4; }
__device__ __forceinline__ void stat_fetch(const Scratch* sc, uint32_t (&st)[4]) {
  const uint32_t th = here(threadIdx.x);
  ld_vec(&sc->x[(blockIdx.x & ~3u) + (th & 3)][X_ST + (th >> 2)], st[0], st[1], st[2], st[3]);
}
template <int C, int SLOT> __device__ __forceinline__ void gather_first(uint32_t (&A)[4][16], uint32_t (&st)[4], const Scratch* sc, uint4* xp, uint32_t tag) {
  bar_sync(BAR_GO, 160);
  fetch(peer<1>(xp) + SLOT, A[1]); fetch(peer<2>(xp) + SLOT, A[2]); fetch(peer<3>(xp) + SLOT, A[3]);
  if (SLOT == X_AG0) stat_fetch(sc, st);
  uint32_t spin = 0;
  while (__builtin_expect(stale(miss(A[1], tag) | miss(A[C], tag)), 0) && ++spin < SPIN_LIMIT) {
    fetch(peer<1>(xp) + SLOT, A[1]);
    if (C == 2) fetch(peer<2>(xp) + SLOT, A[2]);
  }
}
template <int C, int SLOT> __device__ __forceinline__ void gather_rest(uint32_t (&A)[4][16], uint4* xp, uint32_t tag) {
  SCHED();
  uint32_t spin = 0;
  while (__builtin_expect(stale(miss(A[C + 1], tag) | miss(A[3], tag)), 0) && ++spin < SPIN_LIMIT) {
    if (C == 1) fetch(peer<2>(xp) + SLOT, A[2]);
    fetch(peer<3>(xp) + SLOT, A[3]);
  }
}
__device__ __forceinline__ void pack_acc(const float (&d)[32], uint32_t (&a)[16]) {
#pragma unroll
  for (int i = 0; i < 16; i++) a[i] = pack2(d[2 * i], d[2 * i + 1]);
}
__device__ __forceinline__ void frag_store(uint32_t slot, const uint32_t (&a)[16]) {
#pragma unroll
  for (int s = 0; s < 4; s++) sts128(slot + s * 512, a[4 * s], a[4 * s + 1], a[4 * s + 2], a[4 * s + 3]);
}
__device__ __forceinline__ void tile_store(uint32_t maddr, const uint32_t (&a)[16]) {
#pragma unroll
  for (int s = 0; s < 4; s++) stsm4(maddr ^ (s << 5), &a[4 * s]);
}
__device__ __forceinline__ void tile_load(uint32_t maddr, uint32_t (&a)[16]) {
#pragma unroll
  for (int s = 0; s < 4; s++) ldsm4(maddr ^ (s << 5), &a[4 * s]);
}

__device__ __forceinline__ void res_load(uint32_t maddr, float (&d)[32]) {
  uint32_t a[16];
  tile_load(here(maddr) + 3 * TILE_BYTES, a);
#pragma unroll
  for (int i = 0; i < 16; i++) { d[2 * i] = bf_lo(a[i]); d[2 * i + 1] = bf_hi(a[i]); }
  pin(d);
}

struct RowAcc { float s[2][4], u[2][4], v[2][4]; };
__device__ __forceinline__ void row_sums(RowAcc& t, const uint32_t (&a)[16]) {
#pragma unroll
  for (int s = 0; s < 4; s++) hmma(t.s[s & 1], &a[4 * s], 0x3F803F80u, 0x3F803F80u);
}
__device__ __forceinline__ void row_gram(RowAcc& t, const uint32_t (&a)[16]) {
#pragma unroll
  for (int s = 0; s < 8; s++) {
    hmma8(t.u[s & 1], &a[2 * s], a[2 * s]);
    hmma8(t.v[s & 1], &a[2 * s], a[2 * s + 1]);
  }
}
__device__ __forceinline__ float2 row_squares(const RowAcc& t, bool odd) {
  return make_float2(odd ? t.u[0][1] + t.u[1][1] : t.u[0][0] + t.u[1][0], odd ? t.v[0][3] + t.v[1][3] : t.v[0][2] + t.v[1][2]);
}
__device__ __forceinline__ void stat_publish(const uint32_t (&a)[16], Scratch* sc, uint32_t th, uint32_t tag) {
  RowAcc t = {};
  row_sums(t, a);
  row_gram(t, a);
  const float2 q = row_squares(t, th & 4);
  if ((th & 3) == ((th >> 3) & 3))
    st_vec(&sc->x[blockIdx.x][X_ST + (th >> 2)], (__float_as_uint(t.s[0][0] + t.s[1][0]) & ~1u) | tag, __float_as_uint(q.x),
           __float_as_uint(t.s[0][2] + t.s[1][2]), __float_as_uint(q.y));
}
struct RowNorm { float m0, rs0, m1, rs1; };
__device__ __forceinline__ RowNorm row_norm(float s0, float q0, float s1, float q1, float scale) {
  RowNorm n;
  n.m0 = s0 * (1.f / DM); n.m1 = s1 * (1.f / DM);
  n.rs0 = scale * rsqrt_hw(fmaxf(fmaf(-n.m0, n.m0, q0 * (1.f / DM)), 0.f) + LN_EPS);
  n.rs1 = scale * rsqrt_hw(fmaxf(fmaf(-n.m1, n.m1, q1 * (1.f / DM)), 0.f) + LN_EPS);
  return n;
}
__device__ __forceinline__ RowNorm stat_finish(const Scratch* sc, uint32_t (&st)[4], uint32_t tag, float scale) {
  uint32_t spin = 0;
  while (__builtin_expect(stale(st[0] ^ tag), 0) && ++spin < SPIN_LIMIT) stat_fetch(sc, st);
  float f[4];
#pragma unroll
  for (int i = 0; i < 4; i++) {
    f[i] = __uint_as_float(st[i]);
    f[i] += __shfl_xor_sync(0xffffffffu, f[i], 1);
    f[i] += __shfl_xor_sync(0xffffffffu, f[i], 2);
  }
  return row_norm(f[0], f[1], f[2], f[3], scale);
}
__device__ __forceinline__ void mean_frag(uint32_t (&mu)[4], const RowNorm& n, bool sel) {
  const float a = sel ? -n.m0 : 0.f, c = sel ? -n.m1 : 0.f;
  mu[0] = pack2(a, a); mu[1] = pack2(c, c);
  const float al = a - bf_lo(mu[0]), cl = c - bf_lo(mu[1]);
  mu[2] = pack2(al, al); mu[3] = pack2(cl, cl);
  pin(mu);
}
__device__ __forceinline__ void centre(uint32_t (&a)[16], uint32_t m0, uint32_t m1) {
#pragma unroll
  for (int i = 0; i < 16; i++) asm("sub.rn.bf16x2 %0, %0, %1;" : "+r"(a[i]) : "r"((i & 1) ? m1 : m0));
  pin(a);
}
__device__ __forceinline__ void scale_pack(const float (&d)[32], uint32_t (&a)[16], float rs0, float rs1) {
#pragma unroll
  for (int i = 0; i < 16; i++) { const float rs = (i & 1) ? rs1 : rs0; a[i] = pack2(d[2 * i] * rs, d[2 * i + 1] * rs); }
}
template <int S> __device__ __forceinline__ void silu_seg(float (&acc)[4][32], float (&tn)[2][4], uint32_t (&H)[4][16], float rs0, float rs1) {
  if (S >= 2) {
    const float* h = &acc[(S - 2) >> 3][4 * ((S - 2) & 7)];
    const float* v = tn[S & 1];
    uint32_t* o = &H[(S - 2) >> 3][2 * ((S - 2) & 7)];
    o[0] = pack2(fmaf(h[0], v[0], h[0]), fmaf(h[1], v[1], h[1]));
    o[1] = pack2(fmaf(h[2], v[2], h[2]), fmaf(h[3], v[3], h[3]));
    asm volatile("" : "+r"(o[0]), "+r"(o[1]));
  }
  if (S >= 1 && S <= 32) {
#pragma unroll
    for (int k = 0; k < 4; k++) tn[(S - 1) & 1][k] = tanh_hw(acc[((S - 1) >> 3) & 3][4 * ((S - 1) & 7) + k]);
  }
  if (S < 32) {
    float* h = &acc[(S >> 3) & 3][4 * (S & 7)];
    h[0] *= rs0; h[1] *= rs0; h[2] *= rs1; h[3] *= rs1;
    asm volatile("" : "+f"(h[0]), "+f"(h[1]), "+f"(h[2]), "+f"(h[3]));
  }
  SCHED();
}
template <int S0, int S1> __device__ __forceinline__ void silu_segs(float (&acc)[4][32], float (&tn)[2][4], uint32_t (&H)[4][16], float rs0, float rs1) {
  silu_seg<S0>(acc, tn, H, rs0, rs1);
  if constexpr (S0 + 1 < S1) silu_segs<S0 + 1, S1>(acc, tn, H, rs0, rs1);
}
template <int HALF> __device__ __forceinline__ void send_half(uint4* dst, const float (&d)[32], uint32_t tag) {
  uint32_t o[8];
#pragma unroll
  for (int i = 0; i < 8; i++) o[i] = pack2(d[16 * HALF + 2 * i], d[16 * HALF + 2 * i + 1]);
  o[0] = (o[0] & ~1u) | tag; o[4] = (o[4] & ~1u) | tag;
  pin(o);
  SCHED();
  st_vec(dst + HALF * 256, o[0], o[1], o[2], o[3]);
  st_vec(dst + HALF * 256 + 128, o[4], o[5], o[6], o[7]);
  SCHED();
}
__device__ __forceinline__ void send_residual(uint32_t (&a)[16], Scratch* sc, uint4* xp, uint32_t maddr, uint32_t tag) {
  const uint32_t exact[4] = {a[0], a[4], a[8], a[12]};
  publish(xp + X_AG0, a, tag);
  const uint32_t th = here(threadIdx.x);
  stat_publish(a, sc, th, tag);
  tile_store(here(maddr) + 3 * TILE_BYTES, a);
  stsm4(SM_BASE + SM_STG + 3 * TILE_BYTES + (th >> 5) * 2048 + (th & 7) * 128 + ((((th >> 2) & 6) ^ (th & 7)) << 4), exact);
}
template <int F, int N> __device__ __forceinline__ void proj_residual(uint32_t (&A)[4][16], Scratch* sc, uint4* xp, uint32_t maddr,
                                                                      uint32_t tag, int lane) {
  float acc[32];
  uint32_t st[4];
  acquire_n<F, N>();
  if (F == F_PW2) acquire_n<0, 5>();
  res_load(maddr, acc);
  mma_tile<false>(acc, A[0], LO(F));
  gather_first<2, X_AG1>(A, st, sc, xp, tag);
  announce(sc, threadIdx.x == 0);
  mma_tile<false>(acc, A[1], HI(F));
  mma_tile<false>(acc, A[2], LO(F + 1));
  gather_rest<2, X_AG1>(A, xp, tag);
  PROF_MARK0(F == F_WO ? 11 : 16);
  mma_tile<false>(acc, A[3], HI(F + 1));
  RELEASE(F - 2, F - 1);
  WG_WAIT(0); pin(acc);
  pack_acc(acc, A[0]);
  send_residual(A[0], sc, xp, maddr, tag);
}

__device__ __forceinline__ uint64_t ring_desc(uint32_t lo) { return (RING & ~uint64_t(0xFFFFFFFFu)) | lo; }
__device__ __forceinline__ void qk_tile(float (&S)[32], const uint32_t (&Q)[16], uint32_t dk) {
  wgmma64_reuse<0>(S, &Q[0], ring_desc(dk), blockIdx.y);
#pragma unroll
  for (int s = 1; s < 4; s++) wgmma64_acc<0>(S, &Q[4 * s], ring_desc(dk + s * 2));
}
__device__ __forceinline__ void qk_shift(float (&S)[32], const uint32_t (&nm)[4]) { wgmma64_acc<0>(S, nm, (uint64_t)((SM_BASE + SM_ONE) >> 4)); }
constexpr uint32_t RING_K = (uint32_t)RING, V_STEP = 1u - (1u << 16);
constexpr uint32_t RING_V = (SM_BASE >> 4) | (((SM_STG + 2 * TILE_BYTES) >> 4) << 16);
__device__ __forceinline__ void pv_tile(float (&O)[36], const uint32_t (&P)[16], uint32_t dv, uint32_t pad) {
#pragma unroll
  for (int s = 0; s < 4; s++) wgmma72_acc(O, &P[4 * s], ring_desc(dv + s * 128 * V_STEP + (s < 2 ? 0 : (s - 1) * pad)));
}
__device__ __forceinline__ void attn_step(const float (&Sc)[32], float (&Sn)[32], uint32_t (&Pc)[16], uint32_t (&Pp)[16], float (&O)[36],
                                          const uint32_t (&Q)[16], const uint32_t (&nm)[4], uint32_t dk, uint32_t dv, bool next, bool prev) {
  if (next) {
    WG_FENCE();
    qk_tile(Sn, Q, dk);
    qk_shift(Sn, nm);
  }
  if (prev) {
    WG_FENCE();
    pv_tile(O, Pp, dv, 0);
  }
  WG_COMMIT();
  SCHED();
#pragma unroll
  for (int i = 0; i < 16; i++) Pc[i] = pack2(ex2_hw(Sc[2 * i]), ex2_hw(Sc[2 * i + 1]));
  pin(Pc);
  SCHED();
}
template <int R> __device__ __forceinline__ float tile_max(const float (&S)[32]) {
  float t[4];
#pragma unroll
  for (int j = 0; j < 4; j++) t[j] = fmaxf(fmaxf(S[8 * j + R], S[8 * j + R + 1]), fmaxf(S[8 * j + R + 4], S[8 * j + R + 5]));
  float n = fmaxf(fmaxf(t[0], t[1]), fmaxf(t[2], t[3]));
  n = fmaxf(n, __shfl_xor_sync(0xffffffffu, n, 1));
  return fmaxf(n, __shfl_xor_sync(0xffffffffu, n, 2));
}
__device__ __forceinline__ void attention_exact(float (&O)[36], const uint32_t (&Q)[16], const Scratch* sc, int bh, int lane, int half) {
  const char* kb = (const char*)&sc->kv[bh][0][0][0];
  const char* vb = (const char*)&sc->kv[bh][1][0][0];
  const int g = lane >> 2, q = lane & 3;
  float m0 = -INFINITY, m1 = -INFINITY, l0 = 0.f, l1 = 0.f;
  float o[4][4] = {};
#pragma unroll 1
  for (int k0 = 0; k0 < T_SEQ; k0 += 8) {
    float s[4] = {0.f, 0.f, 0.f, 0.f};
#pragma unroll
    for (int c = 0; c < 8; c++) hmma8(s, &Q[2 * c], __ldcg((const uint32_t*)(kb + (k0 + g) * 128 + ((c ^ g) << 4) + q * 4)));
    float n0 = fmaxf(s[0], s[1]), n1 = fmaxf(s[2], s[3]);
    n0 = fmaxf(n0, __shfl_xor_sync(0xffffffffu, n0, 1)); n1 = fmaxf(n1, __shfl_xor_sync(0xffffffffu, n1, 1));
    n0 = fmaxf(m0, fmaxf(n0, __shfl_xor_sync(0xffffffffu, n0, 2))); n1 = fmaxf(m1, fmaxf(n1, __shfl_xor_sync(0xffffffffu, n1, 2)));
    const float a0 = ex2_hw(m0 - n0), a1 = ex2_hw(m1 - n1);
    m0 = n0; m1 = n1;
    const uint32_t pp[2] = {pack2(ex2_hw(s[0] - n0), ex2_hw(s[1] - n0)), pack2(ex2_hw(s[2] - n1), ex2_hw(s[3] - n1))};
    l0 = fmaf(l0, a0, bf_lo(pp[0]) + bf_hi(pp[0])); l1 = fmaf(l1, a1, bf_lo(pp[1]) + bf_hi(pp[1]));
#pragma unroll
    for (int j = 0; j < 4; j++) {
      const int c = 4 * half + j;
      const uint32_t v0 = __ldcg((const uint16_t*)(vb + (k0 + 2 * q) * 128 + ((c ^ (2 * q)) << 4) + g * 2));
      const uint32_t v1 = __ldcg((const uint16_t*)(vb + (k0 + 2 * q + 1) * 128 + ((c ^ (2 * q + 1)) << 4) + g * 2));
      o[j][0] *= a0; o[j][1] *= a0; o[j][2] *= a1; o[j][3] *= a1;
      hmma8(o[j], pp, v0 | (v1 << 16));
    }
  }
  l0 += __shfl_xor_sync(0xffffffffu, l0, 1); l1 += __shfl_xor_sync(0xffffffffu, l1, 1);
  O[32] = l0 + __shfl_xor_sync(0xffffffffu, l0, 2); O[34] = l1 + __shfl_xor_sync(0xffffffffu, l1, 2);
#pragma unroll
  for (int i = 0; i < 16; i++) O[i] = o[i >> 2][i & 3];
}

__device__ __forceinline__ uint32_t fill_entry(int f, int r) {
  int m, x = r, y, dx = 0;
  if (f < F_QKV || f >= 48) {
    const int i = f & 15;
    m = f < F_QKV ? M_FF1A : M_FF2A;
    if (i < 8) { x = 4 * r + ((0xE2u >> i) & 1) * 2; y = r ^ ((0xE790u >> (2 * i)) & 3); dx = 1; }
    else { m++; x = r ^ (((i >> 1) - 3) & 3); y = 4 * r + 2 * (i & 1); }
  } else if (f < F_KV) {
    const int i = f - F_QKV;
    m = M_QKV;
    if (i == 1 || i >= 5) { y = r ^ (i == 1 ? 0 : 2); }
    else { x = 4 + r; y = r ^ (i ? i - 1 : 0); dx = 4; }
  } else if (f >= F_PW1 && f < F_PW2) {
    m = M_PW1; y = r ^ (f - F_PW1); dx = 4;
  } else {
    m = f < F_PW1 ? M_WO : M_PW2; y = r ^ ((f & 1) * 2);
  }
  return m | (x << 4) | (y << 8) | (dx << 16);
}
__device__ __forceinline__ void tma_fill(uint32_t st, const CUtensorMap* map, uint32_t x, uint32_t y, uint32_t x2, uint32_t y2) {
  asm volatile("{\n.reg .pred p;\nelect.sync _|p, 0xffffffff;\n"
               "@p mbarrier.arrive.expect_tx.shared::cta.b64 _, [%1], 16384;\n"
               "@p cp.async.bulk.tensor.2d.shared::cluster.global.mbarrier::complete_tx::bytes [%0], [%2, {%3, %4}], [%1];\n"
               "@p cp.async.bulk.tensor.2d.shared::cluster.global.mbarrier::complete_tx::bytes [%0 + 8192], [%2, {%5, %6}], [%1];\n}"
               :: "r"(SM_BASE + st * STAGE_BYTES), "r"(SM_BASE + SM_FULL + st * 8), "l"(map), "r"(x), "r"(y), "r"(x2), "r"(y2) : "memory");
}
template <int F0, int N> __device__ __forceinline__ void weight_fills(const Params& p, uint32_t entry) {
  uint32_t st = F0 % NSTAGE, parity = ((F0 / NSTAGE) & 1) ^ 1, e = __shfl_sync(0xffffffffu, entry, 0);
#pragma unroll 1
  for (int i = 1; i <= N; i++) {
    const uint32_t x = (e << 2) & 0x3C0, y = (e >> 2) & 0x3FC0, dx = (e >> 16) << 6;
    const CUtensorMap* map = &p.map[e & 15];
    e = __shfl_sync(0xffffffffu, entry, i);
    mbar_wait(SM_BASE + SM_EMPTY + st * 8, parity);
    tma_fill(st, map, x, y, x + dx, dx ? y : y ^ 64);
    if (++st == NSTAGE) { st = 0; parity ^= 1; }
  }
}
__device__ __forceinline__ uint32_t kv_poll(const uint32_t* flag, uint32_t prev) {
  uint32_t v;
  asm volatile("ld.relaxed.gpu.global.u32 %0, [%1];" : "=r"(v) : "l"(flag) : "memory");
  return __ballot_sync(0xffffffffu, v - 1 == prev);
}
__device__ __forceinline__ void kv_fills(const Scratch* sc, int bh, int kind, uint32_t prev, const uint32_t* flag, uint32_t ready) {
#pragma unroll 1
  for (int j = 0; j < 8; j++) {
    uint32_t spin = 0;
#pragma unroll 1
    while (((ready >> (2 * j)) & 3) != 3 && ++spin < SPIN_LIMIT) ready = kv_poll(flag, prev);
    const uint32_t st = (j < 6 ? 4 * (j >> 1) : 0) + (j & 1) + 2 * kind;
    mbar_wait(SM_BASE + SM_EMPTY + st * 8, j < 6);
    asm volatile("{\n.reg .pred p;\nelect.sync _|p, 0xffffffff;\n"
                 "@p mbarrier.arrive.expect_tx.shared::cta.b64 _, [%1], 16384;\n"
                 "@p cp.async.bulk.shared::cluster.global.mbarrier::complete_tx::bytes [%0], [%2], 16384, [%1];\n}"
                 :: "r"(SM_BASE + st * STAGE_BYTES), "r"(SM_BASE + SM_FULL + st * 8), "l"(sc->kv[bh][kind][2 * j]) : "memory");
    PROF_AT(256 + 512 + (10 + kind * 8 + j) * 4);
  }
}
__device__ __forceinline__ void reset_mailboxes(Scratch* sc, int half, int lane) {
  uint4* dst = &sc->x[blockIdx.x][half * 1056 + lane];
#pragma unroll 1
  for (int i = 0; i < 11; i++, dst += 96) {
    const uint32_t t0 = clock_now();
    st_vec(dst, 0u, 0u, 0u, 0u); st_vec(dst + 32, 0u, 0u, 0u, 0u); st_vec(dst + 64, 0u, 0u, 0u, 0u);
    while (clock_now() - t0 < CLR_PACE) {}
  }
  PROF_AT(256 + 512 + 28 * 4);
  asm volatile("fence.acq_rel.gpu;" ::: "memory");
  __syncwarp();
  announce<1>(sc, lane == 0);
  PROF_AT(256 + 512 + 2 * 4);
}
__device__ __forceinline__ void l2_prefetch(const void* p, uint32_t total, int b) {
  const uint32_t part = total / NCTA;
  asm volatile("cp.async.bulk.prefetch.L2.global [%0], %1;" :: "l"((const char*)p + (size_t)b * part), "r"(part) : "memory");
}

__global__ void __launch_bounds__(384, 1) conformer_kernel(Scratch* __restrict__ sc, __nv_bfloat16* __restrict__ out,
                                                           const __nv_bfloat16* __restrict__ dw, const __nv_bfloat16* __restrict__ xin,
                                                           const __nv_bfloat16* __restrict__ w_ff1a, const __grid_constant__ Params p) {
  extern __shared__ __align__(1024) uint8_t smem[];
  const int tid = threadIdx.x, lane = tid & 31;
  const int b = blockIdx.x, r = b & 3, batch = b >> 6, t = (b >> 2) & 15;
  if ((uint32_t)__cvta_generic_to_shared(smem) != SM_BASE) return;
  PROF_AT(256 + (tid >> 7) * 256);
  PROF_TIME(30);
  const uint32_t crow = ((tid >> 1) & 48) + (lane >> 3);
  const uint32_t cdst = SM_BASE + crow * 128 + (((lane & 7) ^ (lane >> 3)) << 4);
  if (tid < 128) {
    const uint32_t g0 = batch * T_SEQ + t * 64 + crow, o = r * 128 + (lane & 7) * 16;
    const uint32_t lo = min(g0, 2 * T_SEQ - 5) * 512 + o, hi = min(g0 + 8, 2 * T_SEQ - 5) * 512 + o;
#pragma unroll
    for (int c = 0; c < 4; c++) {
#pragma unroll
      for (int i = 0; i < 4; i++)
        cp_async16((cdst ^ ((i & 1) << 6)) + SM_STG + (3 - c) * TILE_BYTES + i * 512, (const char*)xin + (((i & 2) ? hi : lo) ^ (c << 7)) + (i & 1) * 2048);
      asm volatile("cp.async.commit_group;" ::: "memory");
    }
  } else if (tid < 256) {
    const char* src = (const char*)w_ff1a + (64 * r + crow) * 2048 + r * 512 + (lane & 7) * 16;
#pragma unroll
    for (int c = 0; c < 4; c++) {
#pragma unroll
      for (int i = 0; i < 4; i++) cp_async16((cdst ^ ((i & 1) << 6)) + c * TILE_BYTES + i * 512, src + i * 8192 + c * 128);
      asm volatile("cp.async.commit_group;" ::: "memory");
    }
  }
  const int cw = __shfl_sync(0xffffffffu, tid >> 5, 0), wg = cw >> 2, w = cw & 3;

  if (wg == 2) {
    asm volatile("setmaxnreg.dec.sync.aligned.u32 40;");
    if (cw == 8) {
      if (lane == 0) {
        asm volatile("prefetch.tensormap [%0];" :: "l"(&p.map[M_FF1A]) : "memory");
#pragma unroll
        for (int i = 0; i < NSTAGE; i++) mbar_init(SM_BASE + SM_FULL + i * 8, 1);
        fence_async_smem();
      }
      __syncwarp();
      bar_arrive(0, 320);
      PROF_MARK(9);
#pragma unroll
      for (int f = 2; f < 8; f++) {
        const uint32_t x = 256 * r + ((0xE2u >> f) & 1) * 128, y = (r ^ ((0xE790u >> (2 * f)) & 3)) * 64;
        tma_fill(f, &p.map[M_FF1A], x, y, x + 64, y);
      }
      PROF_MARK(1);
      uint32_t entry[2];
#pragma unroll 1
      for (int i = 0; i < 2; i++) { entry[1] = fill_entry(8 + i * 32 + lane, r); if (i == 0) entry[0] = entry[1]; }
      bar_sync(BAR_INIT, 64);
      weight_fills<8, F_KV - 8>(p, entry[0]);
      mbar_wait(SM_BASE + SM_EMPTY + (F_WO % NSTAGE) * 8, 1);
      weight_fills<F_WO, F_TOTAL - F_WO>(p, entry[1]);
    } else if (here(cw) != 11) {
      const int kind = w - 1;
      const uint32_t prev = launch_index(sc);
      if (kind == 0) {
        if (lane == 0) {
#pragma unroll
          for (int i = 0; i < NSTAGE; i++) mbar_init(SM_BASE + SM_EMPTY + i * 8, 4);
        }
        __syncwarp();
        bar_arrive(0, 320);
        bar_arrive(BAR_INIT, 64);
        if (lane == 0) {
          const uint32_t t0 = clock_now();
          while (clock_now() - t0 < PF1) {}
          asm volatile("prefetch.tensormap [%0];" :: "l"(&p.map[M_FF1B]) : "memory");
          l2_prefetch(p.w_ff1b, 1024 * 256 * 2, b);
          while (clock_now() - t0 < PF2) {}
          l2_prefetch(p.w_qkv, 256 * 768 * 2, b);
          l2_prefetch(p.w_pw1, 256 * 512 * 2, b);
          l2_prefetch(p.w_ff2a, 256 * 1024 * 2, b);
          while (clock_now() - t0 < PF3) {}
          l2_prefetch(p.w_o, 256 * 256 * 2, b);
          l2_prefetch(p.w_pw2, 256 * 256 * 2, b);
          l2_prefetch(p.w_ff2b, 1024 * 256 * 2, b);
#pragma unroll
          for (int i = M_QKV; i < M_COUNT; i++) asm volatile("prefetch.tensormap [%0];" :: "l"(&p.map[i]) : "memory");
        }
        __syncwarp();
      } else {
        reset_mailboxes(sc, 1, lane);
      }
      const uint32_t* flag = sc->flag[batch * 4 + r][kind * 16 + (lane & 15)];
      const uint32_t ready = kv_poll(flag, prev);
      if (kind == 0) bar_sync(BAR_K, 160); else bar_sync(BAR_V, 160);
      if (lane == 0) {
        asm volatile("cp.async.bulk.global.shared::cta.bulk_group [%0], [%1], %2;"
                     :: "l"(&sc->kv[batch * 4 + r][kind][t][0]), "r"(SM_BASE + SM_STG + kind * TILE_BYTES), "r"(TILE_BYTES) : "memory");
PROF_MARK(4 + kind * 2);
        asm volatile("cp.async.bulk.commit_group;\ncp.async.bulk.wait_group 0;" ::: "memory");
PROF_MARK(5 + kind * 2);
        asm volatile("st.relaxed.gpu.global.u32 [%0], %1;" :: "l"(sc->flag[batch * 4 + r][kind * 16 + t]), "r"(prev + 1) : "memory");
      }
      __syncwarp();
      kv_fills(sc, batch * 4 + r, kind, prev, flag, ready);
    } else {
      const uint32_t* watch = sc->step[(b & ~3) + (lane & 3)];
      uint32_t seen;
      asm volatile("ld.relaxed.gpu.global.u32 %0, [%1];" : "=r"(seen) : "l"(watch) : "memory");
      reset_mailboxes(sc, 0, lane);
      uint32_t want = seen & ~15u;
#pragma unroll 1
      for (int k = 0; k < 8; k++) {
        want += 2;
        uint32_t spin = 0;
#pragma unroll 1
        while (__any_sync(0xffffffffu, (int)(seen - want) < 0) && ++spin < SPIN_LIMIT)
          asm volatile("ld.relaxed.gpu.global.u32 %0, [%1];" : "=r"(seen) : "l"(watch) : "memory");
        bar_arrive(BAR_GO, 160);
        PROF_MARK(32 + k);
      }
    }
  } else {
    asm volatile("setmaxnreg.inc.sync.aligned.u32 232;");
    const int q = lane & 3, th = tid & 127;
    constexpr uint32_t stg = SM_BASE + SM_STG;
    const uint32_t mrow = 16 * w + (lane & 15);
    const uint32_t maddr = stg + mrow * 128 + (((lane >> 4) ^ (lane & 7)) << 4);
    const uint32_t qslot = stg + 2 * TILE_BYTES + w * 2048 + lane * 16;
    uint4* const xp = &sc->x[b][th];
    const int nvalid = T_SEQ - t * 64, row0 = 16 * w + (lane >> 2);

    uint32_t A[4][16];
    uint32_t st[4];
    bar_sync(0, 320);
    if (wg == 0) {
      RowAcc ra = {};
      cp_async_wait(0);
      __syncwarp();
      PROF_MARK0(45);
      tile_load(maddr + 3 * TILE_BYTES, A[0]);
#pragma unroll
      for (int c = 0; c < 4; c++) {
        row_sums(ra, A[c]);
        pin(ra.s[0]); pin(ra.s[1]);
        SCHED();
        if (c < 3) tile_load(maddr + (2 - c) * TILE_BYTES, A[c + 1]);
        row_gram(ra, A[c]);
        if (c < 3) { pin(ra.u[0]); pin(ra.u[1]); pin(ra.v[0]); pin(ra.v[1]); SCHED(); }
      }
      const float m0 = (ra.s[0][0] + ra.s[1][0]) * (1.f / DM), m1 = (ra.s[0][2] + ra.s[1][2]) * (1.f / DM);
      st[0] = pack2(m0, m0); st[1] = pack2(m1, m1);
      centre(A[0], st[0], st[1]);
      const float2 sq = row_squares(ra, lane & 4);
      st[2] = __float_as_uint(fmaf(-m0, m0, sq.x * (1.f / DM))); st[3] = __float_as_uint(fmaf(-m1, m1, sq.y * (1.f / DM)));
    } else {
      if (th < 112) sts128(SM_BASE + SM_CS + th * 16, 0, 0, 0, 0);
      sts32(SM_BASE + SM_EYE + th * 4, th >= 96 ? 0x3F803F80u : ((th & 32) == 0 && (th & 3) == ((th >> 3) & 3)) ? (0x3F00u << ((th & 4) * 4)) : 0u);
#pragma unroll
      for (int i = 0; i < 2; i++) {
        cp_async_wait(2 - 2 * i);
        fence_async_smem();
        bar_sync(BAR_WG1, 128);
        if (th == 0) mbar_arrive(SM_BASE + SM_FULL + i * 8);
      }
      PROF_MARK(6);
      const uint32_t tag = ~launch_index(sc) & 1;
      mbar_wait(SM_BASE + SM_FULL + 4 * 8, 0);
      PROF_MARK(5);
      if (b < 72) {
        const __nv_bfloat16* wp; int ld, col;
        if (b < 24) { wp = p.w_qkv; ld = 768; col = b * 32; }
        else if (b < 40) { wp = p.w_pw1; ld = 512; col = (b - 24) * 32; }
        else { wp = p.w_ff2a; ld = 1024; col = (b - 40) * 32; }
        const uint4* src = (const uint4*)(wp + (size_t)(th >> 2) * ld + col + q * 8);
        float c[8] = {0.f, 0.f, 0.f, 0.f, 0.f, 0.f, 0.f, 0.f};
#pragma unroll 1
        for (int h = 0; h < 2; h++, src += 16 * ld) {
#pragma unroll
          for (int i = 0; i < 4; i++) {
            const uint4 v = __ldg(src + i * 4 * ld);
            c[0] += bf_lo(v.x); c[1] += bf_hi(v.x); c[2] += bf_lo(v.y); c[3] += bf_hi(v.y);
            c[4] += bf_lo(v.z); c[5] += bf_hi(v.z); c[6] += bf_lo(v.w); c[7] += bf_hi(v.w);
          }
        }
#pragma unroll 1
        for (int m = 4; m <= 16; m <<= 1)
#pragma unroll
          for (int k = 0; k < 8; k++) c[k] += __shfl_xor_sync(0xffffffffu, c[k], m);
        if (lane < 4) {
          const uint32_t a = SM_BASE + SM_CS + 1792 + w * 128 + lane * 32;
          sts128(a, __float_as_uint(c[0]), __float_as_uint(c[1]), __float_as_uint(c[2]), __float_as_uint(c[3]));
          sts128(a + 16, __float_as_uint(c[4]), __float_as_uint(c[5]), __float_as_uint(c[6]), __float_as_uint(c[7]));
        }
        bar_sync(BAR_WG1, 128);
        if (th < 8) {
          float o[4] = {0.f, 0.f, 0.f, 0.f};
#pragma unroll 1
          for (int k = 0; k < 4; k++) {
            uint32_t e[4];
            lds128(SM_BASE + SM_CS + 1792 + k * 128 + th * 16, e[0], e[1], e[2], e[3]);
#pragma unroll
            for (int i = 0; i < 4; i++) o[i] += __uint_as_float(e[i]);
          }
          st_vec(&sc->cs[b * 8 + th], (__float_as_uint(o[0]) & ~1u) | tag, __float_as_uint(o[1]), __float_as_uint(o[2]), __float_as_uint(o[3]));
        }
      }
      bar_sync(BAR_WG1, 128);
      PROF_MARK(2);
      if (th < 72) {
        const int j = th >> 3, i = (th & 7) * 2;
        int src;
        if (j < CS_PW1) src = 320 + 64 * r + 16 * j;
        else if (j < CS_QKV) src = 192 + (j - CS_PW1) * 64 + 16 * r;
        else src = ((j - CS_QKV + 1) % 3) * 64 + 16 * r;
        uint32_t e[8], hi[4], lo[4], spin = 0;
#pragma unroll 1
        do {
          ld_vec(&sc->cs[src + i], e[0], e[1], e[2], e[3]);
          ld_vec(&sc->cs[src + i + 1], e[4], e[5], e[6], e[7]);
        } while ((((e[0] ^ tag) | (e[4] ^ tag)) & 1u) && ++spin < SPIN_LIMIT);
        e[0] &= ~1u; e[4] &= ~1u;
#pragma unroll
        for (int k = 0; k < 4; k++) {
          const float c0 = __uint_as_float(e[2 * k]), c1 = __uint_as_float(e[2 * k + 1]);
          hi[k] = pack2(c0, c1);
          lo[k] = pack2(c0 - bf_lo(hi[k]), c1 - bf_hi(hi[k]));
        }
        const uint32_t a = SM_BASE + SM_CS + j * 256 + i * 8;
        sts128(a ^ ((a >> 3) & 0x70), hi[0], hi[1], hi[2], hi[3]);
        sts128((a + 128) ^ (((a + 128) >> 3) & 0x70), lo[0], lo[1], lo[2], lo[3]);
      }
      fence_async_smem();
      PROF_MARK(4);
      bar_arrive(BAR_CS, 256);
    }

#pragma unroll 1
    for (uint32_t pass = 0; pass < 2; pass++) {
      uint32_t Q[16];
      if (wg == 0) {
        float acc[4][32];
        uint32_t H[4][16];
        if (!pass) { PROF_MARK(47); ACQUIRE(0); }
        mma_tile<true>(acc[0], A[0], LO(0)); mma_tile<true>(acc[1], A[0], HI(0));
        if (!pass) ACQUIRE(1);
        mma_tile<true>(acc[2], A[0], LO(1)); mma_tile<true>(acc[3], A[0], HI(1));
        if (pass) {
          gather_first<1, X_AG0>(A, st, sc, xp, 1);
        } else {
          centre(A[1], st[0], st[1]);
          acquire_n<2, 3>();
        }
        mma_tile<false>(acc[0], A[1], LO(2)); mma_tile<false>(acc[1], A[1], HI(2));
        if (pass) {
          gather_rest<1, X_AG0>(A, xp, 1);
          RELEASE(F_PW2, F_PW2 + 1);
        } else {
          centre(A[2], st[0], st[1]); centre(A[3], st[0], st[1]);
        }
        PROF_MARK2(2, 18);
        mma_tile<false>(acc[0], A[2], LO(3)); mma_tile<false>(acc[0], A[3], LO(4));
        WG_WAIT(4);
        RELEASE(0, 1);
        uint32_t mu[4] = {0u, 0u, 0u, 0u};
        float rs0, rs1, tn[2][4];
        if (pass) {
          const RowNorm n = stat_finish(sc, st, 1, 0.5f);
          rs0 = n.rs0; rs1 = n.rs1;
          mean_frag(mu, n, q == 0);
        } else {
          const int src = (lane & 28) | (lane >> 3);
          rs0 = 0.5f * rsqrt_hw(fmaxf(__uint_as_float(__shfl_sync(0xffffffffu, st[2], src)), 0.f) + LN_EPS);
          rs1 = 0.5f * rsqrt_hw(fmaxf(__uint_as_float(__shfl_sync(0xffffffffu, st[3], src)), 0.f) + LN_EPS);
        }
        pin(mu);
        mma_fold<2 * CS_FF2>(acc[0], mu);
        mma_tile<false>(acc[1], A[2], HI(3));
#define SEGS(a, b) silu_segs<a, b>(acc, tn, H, rs0, rs1)
        WG_WAIT(1); pin(acc[0]);
        SEGS(0, 1);
        mma_tile_fold<2 * CS_FF2 + 2>(acc[1], A[3], HI(4), mu);
        SEGS(1, 3);
        uint32_t ok = probe_n<5, 3>();
        SEGS(3, 4);
        settle_n<5, 3>(ok);
        mma_tile<false>(acc[2], A[1], LO(5));
        SEGS(4, 6);
        mma_tile<false>(acc[2], A[2], LO(6));
        SEGS(6, 8);
        WG_WAIT(2); pin(acc[1]);
        RELEASE(2, 4);
        SEGS(8, 9);
        mma_tile_fold<2 * CS_FF2 + 4>(acc[2], A[3], LO(7), mu);
        SEGS(9, 12);
        mma_tile<false>(acc[3], A[1], HI(5));
        SEGS(12, 14);
        mma_tile<false>(acc[3], A[2], HI(6));
        SEGS(14, 16);
        WG_WAIT(2); pin(acc[2]);
        SEGS(16, 17);
        mma_tile_fold<2 * CS_FF2 + 6>(acc[3], A[3], HI(7), mu);
        SEGS(17, 19);
        ok = probe_n<8, 2>();
        SEGS(19, 20);
        settle_n<8, 2>(ok);
        mma_tile_reuse(acc[1], H[0], LO(8));
        SEGS(20, 22);
        mma_tile<false>(acc[1], H[1], HI(8));
        SEGS(22, 24);
        WG_WAIT(2); pin(acc[3]);
        RELEASE(5, 7);
        SEGS(24, 26);
        mma_tile<false>(acc[1], H[2], LO(9));
        SEGS(26, 27);
        ok = probe_n<10, 2>();
        SEGS(27, 28);
        settle_n<10, 2>(ok);
        mma_tile_reuse(acc[2], H[0], LO(10));
        SEGS(28, 31);
        mma_tile<false>(acc[2], H[1], HI(10));
        SEGS(31, 34);
#undef SEGS
        PROF_MARK2(3, 19);
        const uint32_t rtag = here(pass ^ 1);
        const uint4* rs_in = xp + X_RS;
        mma_tile<false>(acc[1], H[3], HI(9));
        mma_tile<false>(acc[2], H[2], LO(11));
        ok = probe_n<12, 2>();
        uint4* rs_out = peer<1>(xp) + X_RS;
        mma_tile<false>(acc[2], H[3], HI(11));
        settle_n<12, 2>(ok);
        if (!pass) bar_sync(BAR_GO, 160);
        WG_WAIT(2); pin(acc[1]);
        RELEASE(8, 9);
        send_half<0>(rs_out, acc[1], rtag);
        mma_tile_reuse(acc[3], H[0], LO(12));
        SCHED();
        send_half<1>(rs_out, acc[1], rtag);
        mma_tile<false>(acc[3], H[1], HI(12));
        rs_out = peer<2>(xp) + X_RS + 512;
        WG_WAIT(2); pin(acc[2]);
        send_half<0>(rs_out, acc[2], rtag);
        mma_tile<false>(acc[3], H[2], LO(13));
        SCHED();
        ok = probe_n<14, 2>();
        send_half<1>(rs_out, acc[2], rtag);
        mma_tile<false>(acc[3], H[3], HI(13));
        settle_n<14, 2>(ok);
        mma_tile_reuse(acc[1], H[0], LO(14));
        rs_out = peer<3>(xp) + X_RS + 1024;
        announce(sc, tid == 0);
        fetch(rs_in, A[1]);
        SCHED();
        mma_tile<false>(acc[1], H[1], HI(14));
        WG_WAIT(2); pin(acc[3]);
        send_half<0>(rs_out, acc[3], rtag);
        send_half<1>(rs_out, acc[3], rtag);
        mma_tile<false>(acc[1], H[2], LO(15)); mma_tile<false>(acc[1], H[3], HI(15));
        SCHED();
        fetch(rs_in + 512, A[2]);
        SCHED();
        res_load(maddr, acc[2]);
        bar_sync(BAR_GO, 160);
        fetch(rs_in + 1024, A[3]);
        if (!pass) acquire_n<F_QKV, 3>();
        {
          uint32_t spin = 0;
          while (__builtin_expect(stale(miss(A[1], rtag) | miss(A[2], rtag) | miss(A[3], rtag)), 0) && ++spin < SPIN_LIMIT) {
            if (stale(miss(A[1], rtag) | miss(A[2], rtag))) { fetch(rs_in, A[1]); fetch(rs_in + 512, A[2]); }
            fetch(rs_in + 1024, A[3]);
          }
        }
        announce(sc, tid == 0 && !pass);
        mma_add_half(acc[2], A[1]);
        mma_add_half(acc[2], A[2]);
        mma_add_half(acc[2], A[3]);
        PROF_MARK2(4, 20);
        WG_WAIT(0); pin(acc[2]); pin(acc[1]);
#pragma unroll
        for (int i = 0; i < 16; i++) A[0][i] = pack2(fmaf(acc[1][2 * i], 0.5f, acc[2][2 * i]), fmaf(acc[1][2 * i + 1], 0.5f, acc[2][2 * i + 1]));
        if (pass) {
          PROF_MARK(21);
          stat_publish(A[0], sc, here(th), 0);
          stat_fetch(sc, st);
          const RowNorm fn = stat_finish(sc, st, 0, 1.f);
          const float nm0 = -fn.m0 * fn.rs0, nm1 = -fn.m1 * fn.rs1;
#pragma unroll
          for (int i = 0; i < 16; i++) {
            const float rs = (i & 1) ? fn.rs1 : fn.rs0, nm = (i & 1) ? nm1 : nm0;
            A[0][i] = pack2(fmaf(bf_lo(A[0][i]), rs, nm), fmaf(bf_hi(A[0][i]), rs, nm));
          }
          tile_store(here(maddr), A[0]);
          __syncwarp();
          const int row = 16 * w + (lane >> 3);
          uint4* dst = (uint4*)(out + ((size_t)batch * T_SEQ + t * 64 + row) * DM + 64 * r) + (lane & 7);
          const uint32_t src = stg + row * 128 + (((lane & 7) ^ (lane >> 3)) << 4);
#pragma unroll
          for (int i = 0; i < 4; i++) {
            uint4 v;
            lds128((src ^ ((i & 1) << 6)) + i * 512, v.x, v.y, v.z, v.w);
            if (row + 4 * i < nvalid) dst[i * 4 * (DM / 8)] = v;
          }
          PROF_MARK(22);
          PROF_TIME(31);
          break;
        }
        send_residual(A[0], sc, xp, maddr, 1);
        PROF_MARK(5);
        mma_tile<true>(acc[0], A[0], LO(F_QKV)); mma_tile<true>(acc[1], A[0], HI(F_QKV));
        mma_tile<true>(acc[2], A[0], LO(F_QKV + 1));
        gather_first<1, X_AG0>(A, st, sc, xp, 1);
        mma_tile<false>(acc[0], A[1], LO(F_QKV + 2)); mma_tile<false>(acc[1], A[1], HI(F_QKV + 2));
        acquire_n<F_QKV + 3, 3>();
        bar_sync(BAR_CS, 256);
        gather_rest<1, X_AG0>(A, xp, 1);
        PROF_MARK(6);
        mma_tile<false>(acc[0], A[2], LO(F_QKV + 3)); mma_tile<false>(acc[0], A[3], LO(F_QKV + 4));
        SCHED();
        {
          const RowNorm n = stat_finish(sc, st, 1, 1.f);
          rs0 = row0 < nvalid ? n.rs0 : 0.f; rs1 = row0 + 8 < nvalid ? n.rs1 : 0.f;
          mean_frag(mu, n, q == 3);
        }
        mma_fold<2 * CS_QKV - 6>(acc[0], mu);
        RELEASE(10, 15);
        WG_WAIT(0); pin(acc[0]);
        scale_pack(acc[0], Q, rs0, rs1);
        tile_store(here(maddr), Q);
        SCHED();
        mma_tile<false>(acc[1], A[2], HI(F_QKV + 3));
        fence_async_smem();
        bar_arrive(BAR_K, 160);
        mma_tile_fold<2 * CS_QKV - 4>(acc[1], A[3], HI(F_QKV + 4), mu);
        mma_tile<false>(acc[2], A[1], HI(F_QKV + 1)); mma_tile<false>(acc[2], A[2], LO(F_QKV + 5));
        WG_WAIT(2); pin(acc[1]);
        scale_pack(acc[1], Q, rs0, rs1);
        tile_store(here(maddr) + TILE_BYTES, Q);
        fence_async_smem();
        bar_arrive(BAR_V, 160);
        mma_tile_fold<2 * CS_QKV - 2>(acc[2], A[3], HI(F_QKV + 5), mu);
        WG_WAIT(0); pin(acc[2]);
        scale_pack(acc[2], Q, rs0 * SM_SCALE_LOG2, rs1 * SM_SCALE_LOG2);
        frag_store(here(qslot), Q);
        bar_arrive(BAR_Q, 256);
        RELEASE(F_QKV, F_QKV + 5);
      } else {
        bar_sync(BAR_Q, 256);
#pragma unroll
        for (int s = 0; s < 4; s++) lds128(qslot + s * 512, Q[4 * s], Q[4 * s + 1], Q[4 * s + 2], Q[4 * s + 3]);
        if (w < 2) {
          const uint32_t v = w ? 0u : 0x3F803F80u;
#pragma unroll
          for (int s = 0; s < 4; s++) sts128(qslot + s * 512, v, v, v, v);
          fence_async_smem();
        }
      }
      bar_sync(BAR_ATT, 256);
      PROF_MARK(7);

      const int dir = cw == 0 ? -1 : 1;
      uint32_t tap[15];
      {
        const uint32_t* dwp = (const uint32_t*)(dw + 64 * r) + lane + 7 * (DM / 2);
#pragma unroll
        for (int k = 0; k < 15; k++) tap[k] = __ldg(dwp + dir * (k - 7) * (DM / 2));
      }

      float O[36];
      {
        float S[2][32];
        uint32_t P[2][16], nm[4];
#pragma unroll
        for (int i = 0; i < 32; i++) { S[0][i] = 0.f; S[1][i] = 0.f; }
        pin(Q); pin(S[0]);
        WG_FENCE();
        qk_tile(S[0], Q, RING_K + (SM_STG >> 4));
        WG_COMMIT();
#pragma unroll
        for (int i = 0; i < 36; i++) O[i] = 0.f;
#pragma unroll
        for (int i = 0; i < 16; i++) P[1][i] = 0u;
        WG_WAIT(0); pin(S[0]);
        const float m0 = tile_max<0>(S[0]), m1 = tile_max<2>(S[0]);
        nm[0] = pack2(q ? 0.f : -m0, 0.f); nm[1] = pack2(q ? 0.f : -m1, 0.f); nm[2] = 0u; nm[3] = 0u;
#pragma unroll
        for (int k = 0; k < 15; k++) asm("mul.rn.bf16x2 %0, %0, %1;" : "+r"(tap[k]) : "r"(0x3F003F00u));
        pin(nm); pin(O); pin(P[1]); pin(tap);
        uint32_t sk = wg, sv = F_SPARE % NSTAGE + wg;
        mbar_wait(SM_BASE + SM_FULL + sv * 8, 1);
        mbar_wait(SM_BASE + SM_FULL + sk * 8, 0);
        if (wg == 1) bar_sync(BAR_ATT, 256);
        PROF_MARK(8);
        WG_FENCE();
        qk_tile(S[0], Q, RING_K + sk * 1024);
        qk_shift(S[0], nm);
        WG_COMMIT();
        WG_WAIT(0); pin(S[0]); pin(S[1]);
        if (wg == 0) bar_arrive(BAR_ATT, 256);
#pragma unroll 1
        for (int it = 0; it < 4; it++) {
          const uint32_t sn = it >= 2 ? wg : sk + 4;
          uint32_t ok = 1;
          mbar_probe(ok, SM_BASE + SM_FULL + sn * 8, it >= 2);
          mbar_probe(ok, SM_BASE + SM_FULL + (sk + 2) * 8, it == 3);
          attn_step(S[0], S[1], P[0], P[1], O, Q, nm, RING_K + sk * 1024 + 512, RING_V + (sv * 1024 + 512) * V_STEP, true, it > 0);
          PROF_MARK(24 + it * 3);
          if (__builtin_expect(!ok, 0)) {
            mbar_wait(SM_BASE + SM_FULL + sn * 8, it >= 2);
            mbar_wait(SM_BASE + SM_FULL + (sk + 2) * 8, it == 3);
          }
          WG_WAIT(0); pin(O); pin(S[1]); pin(P[1]);
          asm volatile("{\n.reg .pred p;\nsetp.eq.u32 p, %2, 0;\n@p mbarrier.arrive.shared::cta.b64 _, [%0];\n@p mbarrier.arrive.shared::cta.b64 _, [%1];\n}"
                       :: "r"(SM_BASE + SM_EMPTY + sk * 8), "r"(SM_BASE + SM_EMPTY + sv * 8), "r"(lane) : "memory");
          PROF_MARK(25 + it * 3);
          sv = sk + 2; sk = sn;
          attn_step(S[1], S[0], P[1], P[0], O, Q, nm, RING_K + sk * 1024, RING_V + (sv * 1024) * V_STEP, it < 3, true);
          WG_WAIT(0); pin(O); pin(S[0]); pin(P[0]);
          PROF_MARK(26 + it * 3);
        }
        WG_FENCE();
        pv_tile(O, P[1], RING_V + (sv * 1024 + 512) * V_STEP, wg << 22);
        WG_COMMIT();
        announce<1>(sc, th == 0);
        WG_WAIT(0); pin(O);
      }
      PROF_MARK(9);

      {
        const uint32_t mo = stg + here(th) * 16;
        sts64(mo + 5 * 4096 + wg * 8, __float_as_uint(O[32]), __float_as_uint(O[34]));
        if (wg == 0) {
#pragma unroll
          for (int i = 4; i < 8; i++)
            sts128(mo + i * 2048, __float_as_uint(O[4 * i]), __float_as_uint(O[4 * i + 1]), __float_as_uint(O[4 * i + 2]), __float_as_uint(O[4 * i + 3]));
        } else {
#pragma unroll
          for (int i = 0; i < 4; i++)
            sts128(mo + i * 2048, __float_as_uint(O[4 * i]), __float_as_uint(O[4 * i + 1]), __float_as_uint(O[4 * i + 2]), __float_as_uint(O[4 * i + 3]));
#pragma unroll
          for (int i = 0; i < 16; i++) O[i] = O[16 + i];
        }
        bar_sync(BAR_MERGE, 256);
        uint32_t e[4];
        lds128(mo + 5 * 4096, e[0], e[1], e[2], e[3]);
        O[32] = __uint_as_float(e[0]) + __uint_as_float(e[2]); O[34] = __uint_as_float(e[1]) + __uint_as_float(e[3]);
#pragma unroll
        for (int i = 0; i < 4; i++) {
          lds128(mo + wg * TILE_BYTES + i * 2048, e[0], e[1], e[2], e[3]);
#pragma unroll
          for (int k = 0; k < 4; k++) O[4 * i + k] += __uint_as_float(e[k]);
        }
        const bool safe = O[32] > 0x1p-60f && O[32] < 0x1p60f && O[34] > 0x1p-60f && O[34] < 0x1p60f;
        if (__builtin_expect(__any_sync(0xffffffffu, !safe), 0)) attention_exact(O, Q, sc, batch * 4 + r, lane, wg);
        const float i0 = rcp_hw(O[32]), i1 = rcp_hw(O[34]);
#pragma unroll
        for (int i = 0; i < 8; i++) { const float v = (i & 1) ? i1 : i0; A[0][i] = pack2(O[2 * i] * v, O[2 * i + 1] * v); }
        A[0][0] &= ~1u; A[0][4] &= ~1u;
        uint4* dst = xp + X_AG1 + wg * 256;
        SCHED();
        st_vec(dst, A[0][0], A[0][1], A[0][2], A[0][3]);
        st_vec(dst + 128, A[0][4], A[0][5], A[0][6], A[0][7]);
        SCHED();
      }
      if (wg == 1) {
        const uint32_t mo = stg + TILE_BYTES + here(th) * 16;
        sts128(mo, A[0][0], A[0][1], A[0][2], A[0][3]);
        sts128(mo + 2048, A[0][4], A[0][5], A[0][6], A[0][7]);
        bar_arrive(BAR_HALF, 256);
      } else {
        PROF_MARK(10);
        const uint32_t mo = stg + TILE_BYTES + here(th) * 16;
        bar_sync(BAR_HALF, 256);
        lds128(mo, A[0][8], A[0][9], A[0][10], A[0][11]);
        lds128(mo + 2048, A[0][12], A[0][13], A[0][14], A[0][15]);
        proj_residual<F_WO, 6>(A, sc, xp, maddr, 0, lane);
        PROF_MARK(12);
        float acc[2][32];
        mma_tile<true>(acc[0], A[0], LO(F_PW1)); mma_tile<true>(acc[1], A[0], HI(F_PW1));
        gather_first<1, X_AG0>(A, st, sc, xp, 0);
        mma_tile<false>(acc[1], A[1], HI(F_PW1 + 1)); mma_tile<false>(acc[0], A[1], LO(F_PW1 + 1));
        gather_rest<1, X_AG0>(A, xp, 0);
        PROF_MARK(13);
        mma_tile<false>(acc[1], A[2], HI(F_PW1 + 2)); mma_tile<false>(acc[1], A[3], HI(F_PW1 + 3));
        WG_WAIT(2);
        RELEASE(F_WO, F_PW1 + 1);
        SCHED();
        uint32_t mu[4];
        const RowNorm n = stat_finish(sc, st, 0, 0.5f);
        const float rs0 = row0 < nvalid ? n.rs0 : 0.f, rs1 = row0 + 8 < nvalid ? n.rs1 : 0.f;
        mean_frag(mu, n, q == 0);
        mma_fold<2 * CS_PW1 + 2>(acc[1], mu);
        mma_tile<false>(acc[0], A[2], LO(F_PW1 + 2));
        mma_tile_fold<2 * CS_PW1>(acc[0], A[3], LO(F_PW1 + 3), mu);
        WG_WAIT(2); pin(acc[1]);
#pragma unroll
        for (int i = 0; i < 32; i++) acc[1][i] = tanh_hw(acc[1][i] * ((i & 2) ? rs1 : rs0));
#pragma unroll
        for (int i = 0; i < 32; i++) { const float rs = (i & 2) ? rs1 : rs0; acc[1][i] = fmaf(acc[1][i], rs, rs); }
        pin(acc[1]);
        SCHED();
        WG_WAIT(0); pin(acc[0]);
#pragma unroll
        for (int i = 0; i < 16; i++) A[0][i] = pack2(acc[0][2 * i] * acc[1][2 * i], acc[0][2 * i + 1] * acc[1][2 * i + 1]);
        const uint32_t ga = stg + TILE_BYTES + here(mrow) * G_PITCH + (lane >> 4) * 16;
#pragma unroll
        for (int s = 0; s < 4; s++) stsm4(ga + s * 32, &A[0][4 * s]);
      }
      {
        const uint32_t gsrc = stg + TILE_BYTES + (8 * cw - 7) * G_PITCH + lane * 4;
        const bool edge = cw == 0 || cw == 7;
        const bool nbr = cw == 0 ? t > 0 : t < 15;
        uint4* const hdst = &sc->x[b + 4 * dir][X_HALO + (cw == 0 ? 96 : 0) + lane];
        uint32_t in[22];
        bar_sync(BAR_G, 256);
        PROF_MARK(14);
        if (cw == 0) {
#pragma unroll
          for (int i = 14; i >= 0; i--) in[i] = lds32(gsrc + (21 - i) * G_PITCH);
        } else {
#pragma unroll
          for (int i = 14; i >= 0; i--) in[i] = lds32(gsrc + i * G_PITCH);
        }
        if (edge) {
          if (nbr) {
            st_vec(hdst, HALO_TAG, in[14], in[13], in[12]);
            st_vec(hdst + 32, HALO_TAG, in[11], in[10], in[9]);
            st_vec(hdst + 64, HALO_TAG, in[8], 0u, 0u);
          }
        } else {
#pragma unroll
          for (int i = 15; i < 22; i++) in[i] = lds32(gsrc + i * G_PITCH);
        }
        if (cw == 0) PROF_MARK0(40);
        uint32_t cv[8];
#pragma unroll
        for (int i = 0; i < 15; i++)
#pragma unroll
          for (int o = 0; o < 8; o++) {
            if (i == o) asm("mul.rn.bf16x2 %0, %1, %2;" : "=r"(cv[o]) : "r"(in[i]), "r"(tap[0]));
            if (i > o) asm("fma.rn.bf16x2 %0, %1, %2, %0;" : "+r"(cv[o]) : "r"(in[i]), "r"(tap[i - o]));
          }
        pin(cv);
        if (cw == 0) PROF_MARK0(41);
        if (edge) {
#pragma unroll
          for (int i = 15; i < 22; i++) in[i] = 0u;
          if (nbr) {
            const uint4* src = &sc->x[b][X_HALO + (cw == 0 ? 0 : 96) + lane];
            uint32_t e0, e1, e2, u0, u1, spin = 0;
#pragma unroll 1
            do {
              ld_vec(src, e0, in[15], in[16], in[17]);
              ld_vec(src + 32, e1, in[18], in[19], in[20]);
              ld_vec(src + 64, e2, in[21], u0, u1);
            } while (__any_sync(0xffffffffu, ((e0 ^ HALO_TAG) | (e1 ^ HALO_TAG) | (e2 ^ HALO_TAG)) != 0) && ++spin < SPIN_LIMIT);
          }
          announce<1>(sc, lane == 0);
        }
#pragma unroll
        for (int i = 15; i < 22; i++)
#pragma unroll
          for (int o = 0; o < 8; o++)
            if (i - o <= 14) asm("fma.rn.bf16x2 %0, %1, %2, %0;" : "+r"(cv[o]) : "r"(in[i]), "r"(tap[i - o]));
        if (cw == 0) PROF_MARK0(42);
        if (cw == 7) PROF_MARK0(43);
        const uint32_t fl = cw == 0 ? 7 : 0;
        const uint32_t cdst = (stg + cw * 1024 + lane * 4) ^ (fl * 144);
#pragma unroll
        for (int o = 0; o < 8; o++) {
          const float a = bf_lo(cv[o]), c = bf_hi(cv[o]);
          sts32(cdst ^ (o * 144), pack2(fmaf(a, tanh_hw(a), a), fmaf(c, tanh_hw(c), c)));
        }
      }
      if (wg == 1) {
        bar_arrive(BAR_C, 256);
        break;
      }
      bar_sync(BAR_C, 256);
      tile_load(here(maddr), A[0]);
      PROF_MARK(15);
      publish(xp + X_AG1, A[0], 1);
      proj_residual<F_PW2, 2>(A, sc, xp, maddr, 1, lane);
      PROF_MARK(17);
    }
  }
}

typedef CUresult (*EncodeFn)(CUtensorMap*, CUtensorMapDataType, cuuint32_t, void*, const cuuint64_t*, const cuuint64_t*,
                             const cuuint32_t*, const cuuint32_t*, CUtensorMapInterleave, CUtensorMapSwizzle,
                             CUtensorMapL2promotion, CUtensorMapFloatOOBfill);

void make_map(EncodeFn fn, CUtensorMap* m, const void* w, int rows, int cols, CUtensorMapSwizzle swz) {
  const cuuint64_t dims[2] = {(cuuint64_t)cols, (cuuint64_t)rows}, strides[1] = {(cuuint64_t)cols * 2};
  const cuuint32_t box[2] = {64, 64}, es[2] = {1, 1};
  fn(m, CU_TENSOR_MAP_DATA_TYPE_BFLOAT16, 2, const_cast<void*>(w), dims, strides, box, es, CU_TENSOR_MAP_INTERLEAVE_NONE,
     swz, CU_TENSOR_MAP_L2_PROMOTION_L2_128B, CU_TENSOR_MAP_FLOAT_OOB_FILL_NONE);
}

}

extern "C" void kernel_launch(void* const* d_in, const int* in_sizes, int n_in, void* d_out, int out_size) {
  static EncodeFn fn = nullptr;
  static Scratch* sc = nullptr;
  if (!fn) {
    void* f = nullptr;
    cudaDriverEntryPointQueryResult st;
    cudaGetDriverEntryPoint("cuTensorMapEncodeTiled", &f, cudaEnableDefault, &st);
    fn = (EncodeFn)f;
    void* raw = nullptr;
    cudaGetSymbolAddress(&raw, g_scratch);
    sc = (Scratch*)(((uintptr_t)raw + X_ALIGN - 1) & ~(uintptr_t)(X_ALIGN - 1));
    cudaFuncSetAttribute(conformer_kernel, cudaFuncAttributeMaxDynamicSharedMemorySize, SM_TOTAL);
  }
  typedef const __nv_bfloat16* W;
  const CUtensorMapSwizzle S = CU_TENSOR_MAP_SWIZZLE_128B;
  Params p;
  make_map(fn, &p.map[M_FF1A], d_in[1], 256, 1024, S);
  make_map(fn, &p.map[M_FF1B], d_in[2], 1024, 256, S);
  make_map(fn, &p.map[M_QKV], d_in[3], 256, 768, S);
  make_map(fn, &p.map[M_WO], d_in[4], 256, 256, S);
  make_map(fn, &p.map[M_PW1], d_in[5], 256, 512, S);
  make_map(fn, &p.map[M_PW2], d_in[7], 256, 256, S);
  make_map(fn, &p.map[M_FF2A], d_in[8], 256, 1024, S);
  make_map(fn, &p.map[M_FF2B], d_in[9], 1024, 256, S);
  p.w_ff1b = (W)d_in[2]; p.w_qkv = (W)d_in[3]; p.w_o = (W)d_in[4]; p.w_pw1 = (W)d_in[5];
  p.w_pw2 = (W)d_in[7]; p.w_ff2a = (W)d_in[8]; p.w_ff2b = (W)d_in[9];

  cudaLaunchConfig_t cfg = {};
  cfg.gridDim = dim3(NCTA);
  cfg.blockDim = dim3(384);
  cfg.dynamicSmemBytes = SM_TOTAL;
  cfg.stream = cudaStreamPerThread;
  cudaLaunchAttribute at[1];
  at[0].id = cudaLaunchAttributeCooperative;
  at[0].val.cooperative = 1;
  cfg.attrs = at;
  cfg.numAttrs = 1;
  cudaLaunchKernelEx(&cfg, conformer_kernel, sc, (__nv_bfloat16*)d_out, (W)d_in[6], (W)d_in[0], (W)d_in[1], p);
}
```

```cpp
#include <cuda_runtime.h>
#include <cuda_bf16.h>
#include <cuda.h>
#include <stdint.h>

namespace {

constexpr int T_SEQ = 1000;
constexpr int DM = 256;
constexpr int NCTA = 128;
constexpr int NSTAGE = 12;
constexpr uint32_t STAGE_BYTES = 16384;
constexpr uint32_t TILE_BYTES = 8192;
constexpr uint32_t SM_BASE = 1024;
constexpr uint32_t SM_STG = NSTAGE * STAGE_BYTES;
constexpr uint32_t SM_FULL = SM_STG + 32768;
constexpr uint32_t SM_EMPTY = SM_FULL + 96;
constexpr uint32_t SM_EYE = SM_FULL + 256;
constexpr uint32_t SM_ONE = SM_FULL + 640;
constexpr uint32_t SM_CS = SM_FULL + 768;
constexpr uint32_t SM_TOTAL = SM_FULL + 3072;
constexpr int CS_FF2 = 0, CS_PW1 = 4, CS_QKV = 6;
constexpr uint32_t SPIN_LIMIT = 1u << 16;
constexpr float LN_EPS = 1e-5f;
constexpr float SM_SCALE_LOG2 = 0.125f * 1.4426950408889634f;
constexpr uint32_t G_PITCH = 144;
#define PF0 1
#define TF 1
#define TC 1
#define PF1 1400
#define PF2 2000
#define PF3 3500
#define CLR_PACE 150

constexpr int F_QKV = 16, F_SPARE = 22, F_KV = 24, F_WO = 40, F_PW1 = 42, F_PW2 = 46, F_TOTAL = 64;
enum { M_FF1A, M_FF1B, M_QKV, M_WO, M_PW1, M_PW2, M_FF2A, M_FF2B, M_COUNT };
enum { BAR_K = 1, BAR_V, BAR_Q, BAR_MERGE, BAR_G, BAR_C, BAR_WG1, BAR_GO, BAR_CS, BAR_ATT, BAR_INIT, BAR_HALF, BAR_RST };

struct Params {
  CUtensorMap map[M_COUNT];
  const __nv_bfloat16 *w_ff1b, *w_qkv, *w_o, *w_pw1, *w_pw2, *w_ff2a, *w_ff2b;
};

constexpr int X_RS = 0, X_AG1 = X_RS, X_HALO = X_RS + 512, X_AG0 = 1536, X_ST = 2048, X_SIZE = 4096;
constexpr uint32_t HALO_TAG = 0xFFFF0001u;
struct Scratch {
  uint4 x[NCTA][X_SIZE];
  uint4 kv[8][2][16][512];
  uint4 cs[576];
  uint32_t flag[8][32][32];
  uint32_t step[NCTA][32];
};
constexpr size_t X_ALIGN = 4 * X_SIZE * sizeof(uint4);
__device__ uint8_t g_scratch[sizeof(Scratch) + X_ALIGN];
#define PROF_TIME(i)
#define PROF_MARK(i)
#define PROF_MARK2(i, j)
#define PROF_MARK0(i)
#define PROF_AT(a)

__device__ __forceinline__ void mbar_init(uint32_t bar, uint32_t cnt) {
  asm volatile("mbarrier.init.shared::cta.b64 [%0], %1;" :: "r"(bar), "r"(cnt) : "memory");
}
__device__ __forceinline__ void mbar_wait(uint32_t bar, uint32_t parity) {
  asm volatile("{\n.reg .pred p;\n.reg .u32 c;\nmov.u32 c, 0;\n"
               "WAIT_LOOP:\nmbarrier.try_wait.parity.shared::cta.b64 p, [%0], %1;\n@p bra WAIT_DONE;\n"
               "add.u32 c, c, 1;\nsetp.lt.u32 p, c, %2;\n@p bra WAIT_LOOP;\nWAIT_DONE:\n}"
               :: "r"(bar), "r"(parity), "n"(SPIN_LIMIT) : "memory");
}
__device__ __forceinline__ void mbar_arrive(uint32_t bar) {
  asm volatile("mbarrier.arrive.shared::cta.b64 _, [%0];" :: "r"(bar) : "memory");
}
#define bar_sync(id, n) asm volatile("bar.sync %0, %1;" :: "n"((int)(id)), "n"(n) : "memory")
#define bar_arrive(id, n) asm volatile("bar.arrive %0, %1;" :: "n"((int)(id)), "n"(n) : "memory")
__device__ __forceinline__ void fence_async_smem() { asm volatile("fence.proxy.async.shared::cta;" ::: "memory"); }

__device__ __forceinline__ void st_vec(uint4* p, uint32_t a, uint32_t b, uint32_t c, uint32_t d) {
  asm volatile("{\n.reg .b128 v;\n.reg .b64 lo, hi;\nmov.b64 lo, {%1, %2};\nmov.b64 hi, {%3, %4};\nmov.b128 v, {lo, hi};\n"
               "st.relaxed.gpu.global.b128 [%0], v;\n}" :: "l"(p), "r"(a), "r"(b), "r"(c), "r"(d) : "memory");
}
__device__ __forceinline__ void ld_vec(const uint4* p, uint32_t& a, uint32_t& b, uint32_t& c, uint32_t& d) {
  asm volatile("{\n.reg .b128 v;\n.reg .b64 lo, hi;\nld.relaxed.gpu.global.b128 v, [%4];\nmov.b128 {lo, hi}, v;\n"
               "mov.b64 {%0, %1}, lo;\nmov.b64 {%2, %3}, hi;\n}" : "=r"(a), "=r"(b), "=r"(c), "=r"(d) : "l"(p) : "memory");
}
__device__ __forceinline__ void sts128(uint32_t a, uint32_t x, uint32_t y, uint32_t z, uint32_t w) {
  asm volatile("st.shared.v4.u32 [%0], {%1, %2, %3, %4};" :: "r"(a), "r"(x), "r"(y), "r"(z), "r"(w) : "memory");
}
__device__ __forceinline__ void lds128(uint32_t a, uint32_t& x, uint32_t& y, uint32_t& z, uint32_t& w) {
  asm volatile("ld.shared.v4.u32 {%0, %1, %2, %3}, [%4];" : "=r"(x), "=r"(y), "=r"(z), "=r"(w) : "r"(a) : "memory");
}
__device__ __forceinline__ uint32_t lds32(uint32_t a) {
  uint32_t x; asm volatile("ld.shared.u32 %0, [%1];" : "=r"(x) : "r"(a) : "memory"); return x;
}
__device__ __forceinline__ void sts32(uint32_t a, uint32_t x) { asm volatile("st.shared.u32 [%0], %1;" :: "r"(a), "r"(x) : "memory"); }
__device__ __forceinline__ void sts64(uint32_t a, uint32_t x, uint32_t y) {
  asm volatile("st.shared.v2.u32 [%0], {%1, %2};" :: "r"(a), "r"(x), "r"(y) : "memory");
}
__device__ __forceinline__ void stsm4(uint32_t a, const uint32_t* r) {
  asm volatile("stmatrix.sync.aligned.m8n8.x4.shared.b16 [%0], {%1, %2, %3, %4};" :: "r"(a), "r"(r[0]), "r"(r[1]), "r"(r[2]), "r"(r[3]) : "memory");
}
__device__ __forceinline__ void ldsm4(uint32_t a, uint32_t* r) {
  asm volatile("ldmatrix.sync.aligned.m8n8.x4.shared.b16 {%0, %1, %2, %3}, [%4];" : "=r"(r[0]), "=r"(r[1]), "=r"(r[2]), "=r"(r[3]) : "r"(a) : "memory");
}
__device__ __forceinline__ uint32_t pack2(float lo, float hi) {
  uint32_t r; asm("cvt.rn.bf16x2.f32 %0, %1, %2;" : "=r"(r) : "f"(hi), "f"(lo)); return r;
}
__device__ __forceinline__ float bf_lo(uint32_t w) { return __uint_as_float(w << 16); }
__device__ __forceinline__ float bf_hi(uint32_t w) { return __uint_as_float(w & 0xffff0000u); }
__device__ __forceinline__ float tanh_hw(float x) { float y; asm volatile("tanh.approx.f32 %0, %1;" : "=f"(y) : "f"(x)); return y; }
__device__ __forceinline__ float rcp_hw(float x) { float y; asm("rcp.approx.ftz.f32 %0, %1;" : "=f"(y) : "f"(x)); return y; }
__device__ __forceinline__ float rsqrt_hw(float x) { float y; asm("rsqrt.approx.ftz.f32 %0, %1;" : "=f"(y) : "f"(x)); return y; }
__device__ __forceinline__ float ex2_hw(float x) { float y; asm("ex2.approx.ftz.f32 %0, %1;" : "=f"(y) : "f"(x)); return y; }

__device__ __forceinline__ uint32_t here(uint32_t v) { asm volatile("" : "+r"(v)); return v; }

#define SCHED() asm volatile("pmevent 1;" ::: "memory")
__device__ __forceinline__ void cp_async16(uint32_t dst, const void* src) {
  asm volatile("cp.async.cg.shared.global [%0], [%1], 16;" :: "r"(dst), "l"(src) : "memory");
}
__device__ __forceinline__ void cp_async_wait(int n) {
  if (n == 0) asm volatile("cp.async.wait_group 0;" ::: "memory");
  if (n == 1) asm volatile("cp.async.wait_group 1;" ::: "memory");
  if (n == 2) asm volatile("cp.async.wait_group 2;" ::: "memory");
  if (n == 3) asm volatile("cp.async.wait_group 3;" ::: "memory");
}
#define WG_FENCE() asm volatile("wgmma.fence.sync.aligned;" ::: "memory")
#define WG_COMMIT() asm volatile("wgmma.commit_group.sync.aligned;" ::: "memory")
#define WG_WAIT(n) asm volatile("wgmma.wait_group.sync.aligned %0;" :: "n"(n) : "memory")

template <int N> __device__ __forceinline__ void pin(float (&d)[N]) {
#pragma unroll
  for (int i = 0; i < N; i++) asm volatile("" : "+f"(d[i]) :: "memory");
}
template <int N> __device__ __forceinline__ void pin(uint32_t (&d)[N]) {
#pragma unroll
  for (int i = 0; i < N; i++) asm volatile("" : "+r"(d[i]) :: "memory");
}

#define WG_D32 "{%0, %1, %2, %3, %4, %5, %6, %7, %8, %9, %10, %11, %12, %13, %14, %15, %16, %17, %18, %19, %20, %21, %22, %23, %24, %25, %26, %27, %28, %29, %30, %31}"
template <int TB> __device__ __forceinline__ void wgmma64_acc(float (&d)[32], const uint32_t* a, uint64_t db) {
  asm volatile("wgmma.mma_async.sync.aligned.m64n64k16.f32.bf16.bf16 " WG_D32 ", {%32, %33, %34, %35}, %36, 1, 1, 1, %37;"
    : "+f"(d[0]), "+f"(d[1]), "+f"(d[2]), "+f"(d[3]), "+f"(d[4]), "+f"(d[5]), "+f"(d[6]), "+f"(d[7]),
      "+f"(d[8]), "+f"(d[9]), "+f"(d[10]), "+f"(d[11]), "+f"(d[12]), "+f"(d[13]), "+f"(d[14]), "+f"(d[15]),
      "+f"(d[16]), "+f"(d[17]), "+f"(d[18]), "+f"(d[19]), "+f"(d[20]), "+f"(d[21]), "+f"(d[22]), "+f"(d[23]),
      "+f"(d[24]), "+f"(d[25]), "+f"(d[26]), "+f"(d[27]), "+f"(d[28]), "+f"(d[29]), "+f"(d[30]), "+f"(d[31])
    : "r"(a[0]), "r"(a[1]), "r"(a[2]), "r"(a[3]), "l"(db), "n"(TB));
}
template <int TB> __device__ __forceinline__ void wgmma64_reuse(float (&d)[32], const uint32_t* a, uint64_t db, uint32_t zero) {
  asm volatile("{\n.reg .pred p;\nsetp.ne.u32 p, %37, 0;\nwgmma.mma_async.sync.aligned.m64n64k16.f32.bf16.bf16 " WG_D32 ", {%32, %33, %34, %35}, %36, p, 1, 1, %38;\n}"
    : "+f"(d[0]), "+f"(d[1]), "+f"(d[2]), "+f"(d[3]), "+f"(d[4]), "+f"(d[5]), "+f"(d[6]), "+f"(d[7]),
      "+f"(d[8]), "+f"(d[9]), "+f"(d[10]), "+f"(d[11]), "+f"(d[12]), "+f"(d[13]), "+f"(d[14]), "+f"(d[15]),
      "+f"(d[16]), "+f"(d[17]), "+f"(d[18]), "+f"(d[19]), "+f"(d[20]), "+f"(d[21]), "+f"(d[22]), "+f"(d[23]),
      "+f"(d[24]), "+f"(d[25]), "+f"(d[26]), "+f"(d[27]), "+f"(d[28]), "+f"(d[29]), "+f"(d[30]), "+f"(d[31])
    : "r"(a[0]), "r"(a[1]), "r"(a[2]), "r"(a[3]), "l"(db), "r"(zero), "n"(TB));
}
template <int TB> __device__ __forceinline__ void wgmma64_set(float (&d)[32], const uint32_t* a, uint64_t db) {
  asm volatile("wgmma.mma_async.sync.aligned.m64n64k16.f32.bf16.bf16 " WG_D32 ", {%32, %33, %34, %35}, %36, 0, 1, 1, %37;"
    : "=f"(d[0]), "=f"(d[1]), "=f"(d[2]), "=f"(d[3]), "=f"(d[4]), "=f"(d[5]), "=f"(d[6]), "=f"(d[7]),
      "=f"(d[8]), "=f"(d[9]), "=f"(d[10]), "=f"(d[11]), "=f"(d[12]), "=f"(d[13]), "=f"(d[14]), "=f"(d[15]),
      "=f"(d[16]), "=f"(d[17]), "=f"(d[18]), "=f"(d[19]), "=f"(d[20]), "=f"(d[21]), "=f"(d[22]), "=f"(d[23]),
      "=f"(d[24]), "=f"(d[25]), "=f"(d[26]), "=f"(d[27]), "=f"(d[28]), "=f"(d[29]), "=f"(d[30]), "=f"(d[31])
    : "r"(a[0]), "r"(a[1]), "r"(a[2]), "r"(a[3]), "l"(db), "n"(TB));
}

__device__ __forceinline__ void wgmma72_acc(float (&d)[36], const uint32_t* a, uint64_t db) {
  asm volatile("wgmma.mma_async.sync.aligned.m64n72k16.f32.bf16.bf16 {%0, %1, %2, %3, %4, %5, %6, %7, %8, %9, %10, %11, %12, %13, %14, %15, %16, %17, %18, %19, %20, %21, %22, %23, %24, %25, %26, %27, %28, %29, %30, %31, %32, %33, %34, %35}, {%36, %37, %38, %39}, %40, 1, 1, 1, 1;"
    : "+f"(d[0]), "+f"(d[1]), "+f"(d[2]), "+f"(d[3]), "+f"(d[4]), "+f"(d[5]), "+f"(d[6]), "+f"(d[7]), "+f"(d[8]),
      "+f"(d[9]), "+f"(d[10]), "+f"(d[11]), "+f"(d[12]), "+f"(d[13]), "+f"(d[14]), "+f"(d[15]), "+f"(d[16]), "+f"(d[17]),
      "+f"(d[18]), "+f"(d[19]), "+f"(d[20]), "+f"(d[21]), "+f"(d[22]), "+f"(d[23]), "+f"(d[24]), "+f"(d[25]), "+f"(d[26]),
      "+f"(d[27]), "+f"(d[28]), "+f"(d[29]), "+f"(d[30]), "+f"(d[31]), "+f"(d[32]), "+f"(d[33]), "+f"(d[34]), "+f"(d[35])
    : "r"(a[0]), "r"(a[1]), "r"(a[2]), "r"(a[3]), "l"(db));
}
__device__ __forceinline__ void wgmma16_acc(float* d, const uint32_t* a, uint64_t db) {
  asm volatile("wgmma.mma_async.sync.aligned.m64n16k16.f32.bf16.bf16 {%0, %1, %2, %3, %4, %5, %6, %7}, {%8, %9, %10, %11}, %12, 1, 1, 1, 0;"
    : "+f"(d[0]), "+f"(d[1]), "+f"(d[2]), "+f"(d[3]), "+f"(d[4]), "+f"(d[5]), "+f"(d[6]), "+f"(d[7])
    : "r"(a[0]), "r"(a[1]), "r"(a[2]), "r"(a[3]), "l"(db));
}
__device__ __forceinline__ void hmma(float (&d)[4], const uint32_t* a, uint32_t b0, uint32_t b1) {
  asm("mma.sync.aligned.m16n8k16.row.col.f32.bf16.bf16.f32 {%0, %1, %2, %3}, {%4, %5, %6, %7}, {%8, %9}, {%0, %1, %2, %3};"
    : "+f"(d[0]), "+f"(d[1]), "+f"(d[2]), "+f"(d[3]) : "r"(a[0]), "r"(a[1]), "r"(a[2]), "r"(a[3]), "r"(b0), "r"(b1));
}

__device__ __forceinline__ void hmma8(float (&d)[4], const uint32_t* a, uint32_t b0) {
  asm("mma.sync.aligned.m16n8k8.row.col.f32.bf16.bf16.f32 {%0, %1, %2, %3}, {%4, %5}, {%6}, {%0, %1, %2, %3};"
    : "+f"(d[0]), "+f"(d[1]), "+f"(d[2]), "+f"(d[3]) : "r"(a[0]), "r"(a[1]), "r"(b0));
}

template <bool FIRST> __device__ __forceinline__ void mma_tile(float (&d)[32], const uint32_t (&a)[16], uint64_t db) {
  WG_FENCE();
#pragma unroll
  for (int s = 0; s < 4; s++) {
    if (FIRST && s == 0) wgmma64_set<1>(d, &a[0], db); else wgmma64_acc<1>(d, &a[4 * s], db + s * 128);
  }
  WG_COMMIT();
}
__device__ __forceinline__ void mma_tile_reuse(float (&d)[32], const uint32_t (&a)[16], uint64_t db) {
  WG_FENCE();
  wgmma64_reuse<1>(d, &a[0], db, blockIdx.y);
#pragma unroll
  for (int s = 1; s < 4; s++) wgmma64_acc<1>(d, &a[4 * s], db + s * 128);
  WG_COMMIT();
}
template <int ROW> __device__ __forceinline__ void fold_step(float (&d)[32], const uint32_t (&mu)[4]) {
  wgmma64_acc<1>(d, mu, (uint64_t)((SM_BASE + SM_CS + ROW * 128) >> 4) | (uint64_t(1) << 16) | (uint64_t(1) << 62));
}
template <int ROW> __device__ __forceinline__ void mma_fold(float (&d)[32], const uint32_t (&mu)[4]) {
  WG_FENCE();
  fold_step<ROW>(d, mu);
  WG_COMMIT();
}
template <int ROW> __device__ __forceinline__ void mma_tile_fold(float (&d)[32], const uint32_t (&a)[16], uint64_t db, const uint32_t (&mu)[4]) {
  WG_FENCE();
#pragma unroll
  for (int s = 0; s < 4; s++) wgmma64_acc<1>(d, &a[4 * s], db + s * 128);
  fold_step<ROW>(d, mu);
  WG_COMMIT();
}
__device__ __forceinline__ void mma_add_half(float (&d)[32], const uint32_t (&a)[16]) {
  const uint64_t db = (uint64_t)((SM_BASE + SM_EYE) >> 4) | (uint64_t(8) << 16) | (uint64_t(8) << 32);
  WG_FENCE();
#pragma unroll
  for (int s = 0; s < 4; s++) wgmma16_acc(&d[8 * s], &a[4 * s], db);
  WG_COMMIT();
}
#define ACQUIRE(f) mbar_wait(SM_BASE + SM_FULL + ((f) % NSTAGE) * 8, ((f) / NSTAGE) & 1)
__device__ __forceinline__ void mbar_probe(uint32_t& ok, uint32_t bar, uint32_t parity) {
  asm volatile("{\n.reg .pred p;\nmbarrier.test_wait.parity.shared::cta.b64 p, [%1], %2;\nselp.u32 %0, %0, 0, p;\n}"
               : "+r"(ok) : "r"(bar), "r"(parity) : "memory");
}
template <int F, int N> __device__ __forceinline__ uint32_t probe_n() {
  static_assert(F % NSTAGE + N <= NSTAGE, "stages must not wrap");
  uint32_t ok = 1;
#pragma unroll
  for (int i = 0; i < N; i++) mbar_probe(ok, SM_BASE + SM_FULL + (F % NSTAGE + i) * 8, (F / NSTAGE) & 1);
  return ok;
}
template <int F, int N> __device__ __forceinline__ void settle_n(uint32_t ok) {
  if (__builtin_expect(!ok, 0)) {
#pragma unroll 1
    for (int i = 0; i < N; i++) mbar_wait(SM_BASE + SM_FULL + (F % NSTAGE + i) * 8, (F / NSTAGE) & 1);
  }
}
template <int F, int N> __device__ __forceinline__ void acquire_n() { settle_n<F, N>(probe_n<F, N>()); }
#define RELEASE(f0, f1) do { if (lane == 0) { _Pragma("unroll") for (int f_ = (f0); f_ <= (f1); f_++) mbar_arrive(SM_BASE + SM_EMPTY + (f_ % NSTAGE) * 8); } } while (0)
constexpr uint64_t RING = (uint64_t)(SM_BASE >> 4) | (uint64_t(1) << 16) | (uint64_t(64) << 32) | (uint64_t(1) << 62);
#define LO(f) (RING + ((f) % NSTAGE) * 1024)
#define HI(f) (RING + ((f) % NSTAGE) * 1024 + 512)

template <int C> __device__ __forceinline__ uint4* peer(uint4* p) {
  asm volatile("" : "+l"(p));
  return (uint4*)((uintptr_t)p ^ (C * X_SIZE * sizeof(uint4)));
}
__device__ __forceinline__ uint32_t clock_now() { uint32_t c; asm volatile("mov.u32 %0, %%clock;" : "=r"(c) :: "memory"); return c; }
__device__ __forceinline__ void publish(uint4* dst, uint32_t (&a)[16], uint32_t tag) {
#pragma unroll
  for (int s = 0; s < 4; s++) a[4 * s] = (a[4 * s] & ~1u) | tag;
  pin(a);
  SCHED();
#pragma unroll
  for (int s = 0; s < 4; s++) st_vec(dst + s * 128, a[4 * s], a[4 * s + 1], a[4 * s + 2], a[4 * s + 3]);
  SCHED();
}
__device__ __forceinline__ void fetch(const uint4* src, uint32_t (&a)[16]) {
#pragma unroll
  for (int s = 0; s < 4; s++) ld_vec(src + s * 128, a[4 * s], a[4 * s + 1], a[4 * s + 2], a[4 * s + 3]);
}
__device__ __forceinline__ uint32_t miss(const uint32_t (&a)[16], uint32_t tag) {
  return (a[0] ^ tag) | (a[4] ^ tag) | (a[8] ^ tag) | (a[12] ^ tag);
}
__device__ __forceinline__ bool stale(uint32_t v) { return __any_sync(0xffffffffu, here(v) & 1u); }
template <int N = 2> __device__ __forceinline__ void announce(Scratch* sc, bool leader) {
  asm volatile("{\n.reg .pred p;\nsetp.ne.u32 p, %1, 0;\n@p red.relaxed.gpu.global.add.u32 [%0], %2;\n}"
               :: "l"(sc->step[blockIdx.x]), "r"((uint32_t)leader), "n"(N) : "memory");
}
__device__ __forceinline__ uint32_t launch_index(const Scratch* sc) { return *(const volatile uint32_t*)sc->step[blockIdx.x] >> 4; }
__device__ __forceinline__ void stat_fetch(const Scratch* sc, uint32_t (&st)[4]) {
  const uint32_t th = here(threadIdx.x);
  ld_vec(&sc->x[(blockIdx.x & ~3u) + (th & 3)][X_ST + (th >> 2)], st[0], st[1], st[2], st[3]);
}
template <int C, int SLOT> __device__ __forceinline__ void gather_first(uint32_t (&A)[4][16], uint32_t (&st)[4], const Scratch* sc, uint4* xp, uint32_t tag) {
  bar_sync(BAR_GO, 160);
  fetch(peer<1>(xp) + SLOT, A[1]); fetch(peer<2>(xp) + SLOT, A[2]); fetch(peer<3>(xp) + SLOT, A[3]);
  if (SLOT == X_AG0) stat_fetch(sc, st);
  uint32_t spin = 0;
  while (__builtin_expect(stale(miss(A[1], tag) | miss(A[C], tag)), 0) && ++spin < SPIN_LIMIT) {
    fetch(peer<1>(xp) + SLOT, A[1]);
    if (C == 2) fetch(peer<2>(xp) + SLOT, A[2]);
  }
}
template <int C, int SLOT> __device__ __forceinline__ void gather_rest(uint32_t (&A)[4][16], uint4* xp, uint32_t tag) {
  SCHED();
  uint32_t spin = 0;
  while (__builtin_expect(stale(miss(A[C + 1], tag) | miss(A[3], tag)), 0) && ++spin < SPIN_LIMIT) {
    if (C == 1) fetch(peer<2>(xp) + SLOT, A[2]);
    fetch(peer<3>(xp) + SLOT, A[3]);
  }
}
__device__ __forceinline__ void pack_acc(const float (&d)[32], uint32_t (&a)[16]) {
#pragma unroll
  for (int i = 0; i < 16; i++) a[i] = pack2(d[2 * i], d[2 * i + 1]);
}
__device__ __forceinline__ void frag_store(uint32_t slot, const uint32_t (&a)[16]) {
#pragma unroll
  for (int s = 0; s < 4; s++) sts128(slot + s * 512, a[4 * s], a[4 * s + 1], a[4 * s + 2], a[4 * s + 3]);
}
__device__ __forceinline__ void tile_store(uint32_t maddr, const uint32_t (&a)[16]) {
#pragma unroll
  for (int s = 0; s < 4; s++) stsm4(maddr ^ (s << 5), &a[4 * s]);
}
__device__ __forceinline__ void tile_load(uint32_t maddr, uint32_t (&a)[16]) {
#pragma unroll
  for (int s = 0; s < 4; s++) ldsm4(maddr ^ (s << 5), &a[4 * s]);
}

__device__ __forceinline__ void res_load(uint32_t maddr, float (&d)[32]) {
  uint32_t a[16];
  tile_load(here(maddr) + 3 * TILE_BYTES, a);
#pragma unroll
  for (int i = 0; i < 16; i++) { d[2 * i] = bf_lo(a[i]); d[2 * i + 1] = bf_hi(a[i]); }
  pin(d);
}

struct RowAcc { float s[2][4], u[2][4], v[2][4]; };
__device__ __forceinline__ void row_sums(RowAcc& t, const uint32_t (&a)[16]) {
#pragma unroll
  for (int s = 0; s < 4; s++) hmma(t.s[s & 1], &a[4 * s], 0x3F803F80u, 0x3F803F80u);
}
__device__ __forceinline__ void row_gram(RowAcc& t, const uint32_t (&a)[16]) {
#pragma unroll
  for (int s = 0; s < 8; s++) {
    hmma8(t.u[s & 1], &a[2 * s], a[2 * s]);
    hmma8(t.v[s & 1], &a[2 * s], a[2 * s + 1]);
  }
}
__device__ __forceinline__ float2 row_squares(const RowAcc& t, bool odd) {
  return make_float2(odd ? t.u[0][1] + t.u[1][1] : t.u[0][0] + t.u[1][0], odd ? t.v[0][3] + t.v[1][3] : t.v[0][2] + t.v[1][2]);
}
__device__ __forceinline__ void stat_publish(const uint32_t (&a)[16], Scratch* sc, uint32_t th, uint32_t tag) {
  RowAcc t = {};
  row_sums(t, a);
  row_gram(t, a);
  const float2 q = row_squares(t, th & 4);
  if ((th & 3) == ((th >> 3) & 3))
    st_vec(&sc->x[blockIdx.x][X_ST + (th >> 2)], (__float_as_uint(t.s[0][0] + t.s[1][0]) & ~1u) | tag, __float_as_uint(q.x),
           __float_as_uint(t.s[0][2] + t.s[1][2]), __float_as_uint(q.y));
}
struct RowNorm { float m0, rs0, m1, rs1; };
__device__ __forceinline__ RowNorm row_norm(float s0, float q0, float s1, float q1, float scale) {
  RowNorm n;
  n.m0 = s0 * (1.f / DM); n.m1 = s1 * (1.f / DM);
  n.rs0 = scale * rsqrt_hw(fmaxf(fmaf(-n.m0, n.m0, q0 * (1.f / DM)), 0.f) + LN_EPS);
  n.rs1 = scale * rsqrt_hw(fmaxf(fmaf(-n.m1, n.m1, q1 * (1.f / DM)), 0.f) + LN_EPS);
  return n;
}
__device__ __forceinline__ RowNorm stat_finish(const Scratch* sc, uint32_t (&st)[4], uint32_t tag, float scale) {
  uint32_t spin = 0;
  while (__builtin_expect(stale(st[0] ^ tag), 0) && ++spin < SPIN_LIMIT) stat_fetch(sc, st);
  float f[4];
#pragma unroll
  for (int i = 0; i < 4; i++) {
    f[i] = __uint_as_float(st[i]);
    f[i] += __shfl_xor_sync(0xffffffffu, f[i], 1);
    f[i] += __shfl_xor_sync(0xffffffffu, f[i], 2);
  }
  return row_norm(f[0], f[1], f[2], f[3], scale);
}
__device__ __forceinline__ void mean_frag(uint32_t (&mu)[4], const RowNorm& n, bool sel) {
  const float a = sel ? -n.m0 : 0.f, c = sel ? -n.m1 : 0.f;
  mu[0] = pack2(a, a); mu[1] = pack2(c, c);
  const float al = a - bf_lo(mu[0]), cl = c - bf_lo(mu[1]);
  mu[2] = pack2(al, al); mu[3] = pack2(cl, cl);
  pin(mu);
}
__device__ __forceinline__ void centre(uint32_t (&a)[16], uint32_t m0, uint32_t m1) {
#pragma unroll
  for (int i = 0; i < 16; i++) asm("sub.rn.bf16x2 %0, %0, %1;" : "+r"(a[i]) : "r"((i & 1) ? m1 : m0));
  pin(a);
}
__device__ __forceinline__ void scale_pack(const float (&d)[32], uint32_t (&a)[16], float rs0, float rs1) {
#pragma unroll
  for (int i = 0; i < 16; i++) { const float rs = (i & 1) ? rs1 : rs0; a[i] = pack2(d[2 * i] * rs, d[2 * i + 1] * rs); }
}
template <int S> __device__ __forceinline__ void silu_seg(float (&acc)[4][32], float (&tn)[2][4], uint32_t (&H)[4][16], float rs0, float rs1) {
  if (S >= 2) {
    const float* h = &acc[(S - 2) >> 3][4 * ((S - 2) & 7)];
    const float* v = tn[S & 1];
    uint32_t* o = &H[(S - 2) >> 3][2 * ((S - 2) & 7)];
    o[0] = pack2(fmaf(h[0], v[0], h[0]), fmaf(h[1], v[1], h[1]));
    o[1] = pack2(fmaf(h[2], v[2], h[2]), fmaf(h[3], v[3], h[3]));
    asm volatile("" : "+r"(o[0]), "+r"(o[1]));
  }
  if (S >= 1 && S <= 32) {
#pragma unroll
    for (int k = 0; k < 4; k++) tn[(S - 1) & 1][k] = tanh_hw(acc[((S - 1) >> 3) & 3][4 * ((S - 1) & 7) + k]);
  }
  if (S < 32) {
    float* h = &acc[(S >> 3) & 3][4 * (S & 7)];
    h[0] *= rs0; h[1] *= rs0; h[2] *= rs1; h[3] *= rs1;
    asm volatile("" : "+f"(h[0]), "+f"(h[1]), "+f"(h[2]), "+f"(h[3]));
  }
  SCHED();
}
template <int S0, int S1> __device__ __forceinline__ void silu_segs(float (&acc)[4][32], float (&tn)[2][4], uint32_t (&H)[4][16], float rs0, float rs1) {
  silu_seg<S0>(acc, tn, H, rs0, rs1);
  if constexpr (S0 + 1 < S1) silu_segs<S0 + 1, S1>(acc, tn, H, rs0, rs1);
}
template <int HALF> __device__ __forceinline__ void send_half(uint4* dst, const float (&d)[32], uint32_t tag) {
  uint32_t o[8];
#pragma unroll
  for (int i = 0; i < 8; i++) o[i] = pack2(d[16 * HALF + 2 * i], d[16 * HALF + 2 * i + 1]);
  o[0] = (o[0] & ~1u) | tag; o[4] = (o[4] & ~1u) | tag;
  pin(o);
  SCHED();
  st_vec(dst + HALF * 256, o[0], o[1], o[2], o[3]);
  st_vec(dst + HALF * 256 + 128, o[4], o[5], o[6], o[7]);
  SCHED();
}
__device__ __forceinline__ void send_residual(uint32_t (&a)[16], Scratch* sc, uint4* xp, uint32_t maddr, uint32_t tag) {
  const uint32_t exact[4] = {a[0], a[4], a[8], a[12]};
  publish(xp + X_AG0, a, tag);
  const uint32_t th = here(threadIdx.x);
  stat_publish(a, sc, th, tag);
  tile_store(here(maddr) + 3 * TILE_BYTES, a);
  stsm4(SM_BASE + SM_STG + 3 * TILE_BYTES + (th >> 5) * 2048 + (th & 7) * 128 + ((((th >> 2) & 6) ^ (th & 7)) << 4), exact);
}
template <int F, int N> __device__ __forceinline__ void proj_residual(uint32_t (&A)[4][16], Scratch* sc, uint4* xp, uint32_t maddr,
                                                                      uint32_t tag, int lane) {
  float acc[32];
  uint32_t st[4];
  acquire_n<F, N>();
  if (F == F_PW2) acquire_n<0, 5>();
  res_load(maddr, acc);
  mma_tile<false>(acc, A[0], LO(F));
  gather_first<2, X_AG1>(A, st, sc, xp, tag);
  announce(sc, threadIdx.x == 0);
  mma_tile<false>(acc, A[1], HI(F));
  mma_tile<false>(acc, A[2], LO(F + 1));
  gather_rest<2, X_AG1>(A, xp, tag);
  PROF_MARK0(F == F_WO ? 11 : 16);
  mma_tile<false>(acc, A[3], HI(F + 1));
  RELEASE(F - 2, F - 1);
  WG_WAIT(0); pin(acc);
  pack_acc(acc, A[0]);
  send_residual(A[0], sc, xp, maddr, tag);
}

__device__ __forceinline__ uint64_t ring_desc(uint32_t lo) { return (RING & ~uint64_t(0xFFFFFFFFu)) | lo; }
__device__ __forceinline__ void qk_tile(float (&S)[32], const uint32_t (&Q)[16], uint32_t dk) {
  wgmma64_reuse<0>(S, &Q[0], ring_desc(dk), blockIdx.y);
#pragma unroll
  for (int s = 1; s < 4; s++) wgmma64_acc<0>(S, &Q[4 * s], ring_desc(dk + s * 2));
}
__device__ __forceinline__ void qk_shift(float (&S)[32], const uint32_t (&nm)[4]) { wgmma64_acc<0>(S, nm, (uint64_t)((SM_BASE + SM_ONE) >> 4)); }
constexpr uint32_t RING_K = (uint32_t)RING, V_STEP = 1u - (1u << 16);
constexpr uint32_t RING_V = (SM_BASE >> 4) | (((SM_STG + 2 * TILE_BYTES) >> 4) << 16);
__device__ __forceinline__ void pv_tile(float (&O)[36], const uint32_t (&P)[16], uint32_t dv, uint32_t pad) {
#pragma unroll
  for (int s = 0; s < 4; s++) wgmma72_acc(O, &P[4 * s], ring_desc(dv + s * 128 * V_STEP + (s < 2 ? 0 : (s - 1) * pad)));
}
__device__ __forceinline__ void attn_step(const float (&Sc)[32], float (&Sn)[32], uint32_t (&Pc)[16], uint32_t (&Pp)[16], float (&O)[36],
                                          const uint32_t (&Q)[16], const uint32_t (&nm)[4], uint32_t dk, uint32_t dv, bool next, bool prev) {
  if (next) {
    WG_FENCE();
    qk_tile(Sn, Q, dk);
    qk_shift(Sn, nm);
  }
  if (prev) {
    WG_FENCE();
    pv_tile(O, Pp, dv, 0);
  }
  WG_COMMIT();
  SCHED();
#pragma unroll
  for (int i = 0; i < 16; i++) Pc[i] = pack2(ex2_hw(Sc[2 * i]), ex2_hw(Sc[2 * i + 1]));
  pin(Pc);
  SCHED();
}
template <int R> __device__ __forceinline__ float tile_max(const float (&S)[32]) {
  float t[4];
#pragma unroll
  for (int j = 0; j < 4; j++) t[j] = fmaxf(fmaxf(S[8 * j + R], S[8 * j + R + 1]), fmaxf(S[8 * j + R + 4], S[8 * j + R + 5]));
  float n = fmaxf(fmaxf(t[0], t[1]), fmaxf(t[2], t[3]));
  n = fmaxf(n, __shfl_xor_sync(0xffffffffu, n, 1));
  return fmaxf(n, __shfl_xor_sync(0xffffffffu, n, 2));
}
__device__ __forceinline__ void attention_exact(float (&O)[36], const uint32_t (&Q)[16], const Scratch* sc, int bh, int lane, int half) {
  const char* kb = (const char*)&sc->kv[bh][0][0][0];
  const char* vb = (const char*)&sc->kv[bh][1][0][0];
  const int g = lane >> 2, q = lane & 3;
  float m0 = -INFINITY, m1 = -INFINITY, l0 = 0.f, l1 = 0.f;
  float o[4][4] = {};
#pragma unroll 1
  for (int k0 = 0; k0 < T_SEQ; k0 += 8) {
    float s[4] = {0.f, 0.f, 0.f, 0.f};
#pragma unroll
    for (int c = 0; c < 8; c++) hmma8(s, &Q[2 * c], __ldcg((const uint32_t*)(kb + (k0 + g) * 128 + ((c ^ g) << 4) + q * 4)));
    float n0 = fmaxf(s[0], s[1]), n1 = fmaxf(s[2], s[3]);
    n0 = fmaxf(n0, __shfl_xor_sync(0xffffffffu, n0, 1)); n1 = fmaxf(n1, __shfl_xor_sync(0xffffffffu, n1, 1));
    n0 = fmaxf(m0, fmaxf(n0, __shfl_xor_sync(0xffffffffu, n0, 2))); n1 = fmaxf(m1, fmaxf(n1, __shfl_xor_sync(0xffffffffu, n1, 2)));
    const float a0 = ex2_hw(m0 - n0), a1 = ex2_hw(m1 - n1);
    m0 = n0; m1 = n1;
    const uint32_t pp[2] = {pack2(ex2_hw(s[0] - n0), ex2_hw(s[1] - n0)), pack2(ex2_hw(s[2] - n1), ex2_hw(s[3] - n1))};
    l0 = fmaf(l0, a0, bf_lo(pp[0]) + bf_hi(pp[0])); l1 = fmaf(l1, a1, bf_lo(pp[1]) + bf_hi(pp[1]));
#pragma unroll
    for (int j = 0; j < 4; j++) {
      const int c = 4 * half + j;
      const uint32_t v0 = __ldcg((const uint16_t*)(vb + (k0 + 2 * q) * 128 + ((c ^ (2 * q)) << 4) + g * 2));
      const uint32_t v1 = __ldcg((const uint16_t*)(vb + (k0 + 2 * q + 1) * 128 + ((c ^ (2 * q + 1)) << 4) + g * 2));
      o[j][0] *= a0; o[j][1] *= a0; o[j][2] *= a1; o[j][3] *= a1;
      hmma8(o[j], pp, v0 | (v1 << 16));
    }
  }
  l0 += __shfl_xor_sync(0xffffffffu, l0, 1); l1 += __shfl_xor_sync(0xffffffffu, l1, 1);
  O[32] = l0 + __shfl_xor_sync(0xffffffffu, l0, 2); O[34] = l1 + __shfl_xor_sync(0xffffffffu, l1, 2);
#pragma unroll
  for (int i = 0; i < 16; i++) O[i] = o[i >> 2][i & 3];
}

__device__ __forceinline__ uint32_t fill_entry(int f, int r) {
  int m, x = r, y, dx = 0;
  if (f < F_QKV || f >= 48) {
    const int i = f & 15;
    m = f < F_QKV ? M_FF1A : M_FF2A;
    if (i < 8) { x = 4 * r + ((0xE2u >> i) & 1) * 2; y = r ^ ((0xE790u >> (2 * i)) & 3); dx = 1; }
    else { m++; x = r ^ (((i >> 1) - 3) & 3); y = 4 * r + 2 * (i & 1); }
  } else if (f < F_KV) {
    const int i = f - F_QKV;
    m = M_QKV;
    if (i == 1 || i >= 5) { y = r ^ (i == 1 ? 0 : 2); }
    else { x = 4 + r; y = r ^ (i ? i - 1 : 0); dx = 4; }
  } else if (f >= F_PW1 && f < F_PW2) {
    m = M_PW1; y = r ^ (f - F_PW1); dx = 4;
  } else {
    m = f < F_PW1 ? M_WO : M_PW2; y = r ^ ((f & 1) * 2);
  }
  return m | (x << 4) | (y << 8) | (dx << 16);
}
__device__ __forceinline__ void tma_fill(uint32_t st, const CUtensorMap* map, uint32_t x, uint32_t y, uint32_t x2, uint32_t y2) {
  asm volatile("{\n.reg .pred p;\nelect.sync _|p, 0xffffffff;\n"
               "@p mbarrier.arrive.expect_tx.shared::cta.b64 _, [%1], 16384;\n"
               "@p cp.async.bulk.tensor.2d.shared::cluster.global.mbarrier::complete_tx::bytes [%0], [%2, {%3, %4}], [%1];\n"
               "@p cp.async.bulk.tensor.2d.shared::cluster.global.mbarrier::complete_tx::bytes [%0 + 8192], [%2, {%5, %6}], [%1];\n}"
               :: "r"(SM_BASE + st * STAGE_BYTES), "r"(SM_BASE + SM_FULL + st * 8), "l"(map), "r"(x), "r"(y), "r"(x2), "r"(y2) : "memory");
}
template <int F0, int N> __device__ __forceinline__ void weight_fills(const Params& p, uint32_t entry) {
  uint32_t st = F0 % NSTAGE, parity = ((F0 / NSTAGE) & 1) ^ 1, e = __shfl_sync(0xffffffffu, entry, 0);
#pragma unroll 1
  for (int i = 1; i <= N; i++) {
    const uint32_t x = (e << 2) & 0x3C0, y = (e >> 2) & 0x3FC0, dx = (e >> 16) << 6;
    const CUtensorMap* map = &p.map[e & 15];
    e = __shfl_sync(0xffffffffu, entry, i);
    mbar_wait(SM_BASE + SM_EMPTY + st * 8, parity);
    tma_fill(st, map, x, y, x + dx, dx ? y : y ^ 64);
    if (++st == NSTAGE) { st = 0; parity ^= 1; }
  }
}
__device__ __forceinline__ uint32_t kv_poll(const uint32_t* flag, uint32_t prev) {
  uint32_t v;
  asm volatile("ld.relaxed.gpu.global.u32 %0, [%1];" : "=r"(v) : "l"(flag) : "memory");
  return __ballot_sync(0xffffffffu, v - 1 == prev);
}
__device__ __forceinline__ void kv_fills(const Scratch* sc, int bh, int kind, uint32_t prev, const uint32_t* flag, uint32_t ready) {
#pragma unroll 1
  for (int j = 0; j < 8; j++) {
    uint32_t spin = 0;
#pragma unroll 1
    while (((ready >> (2 * j)) & 3) != 3 && ++spin < SPIN_LIMIT) ready = kv_poll(flag, prev);
    const uint32_t st = (j < 6 ? 4 * (j >> 1) : 0) + (j & 1) + 2 * kind;
    mbar_wait(SM_BASE + SM_EMPTY + st * 8, j < 6);
    asm volatile("{\n.reg .pred p;\nelect.sync _|p, 0xffffffff;\n"
                 "@p mbarrier.arrive.expect_tx.shared::cta.b64 _, [%1], 16384;\n"
                 "@p cp.async.bulk.shared::cluster.global.mbarrier::complete_tx::bytes [%0], [%2], 16384, [%1];\n}"
                 :: "r"(SM_BASE + st * STAGE_BYTES), "r"(SM_BASE + SM_FULL + st * 8), "l"(sc->kv[bh][kind][2 * j]) : "memory");
    PROF_AT(256 + 512 + (10 + kind * 8 + j) * 4);
  }
}
__device__ __forceinline__ void reset_mailboxes(Scratch* sc, int half, int lane, uint32_t t_start) {
  while (clock_now() - t_start < TC) {}
#pragma unroll 1
  for (int i = half * 8; i < half * 9 + 8; i++) {
    const uint32_t t0 = clock_now();
    uint4* dst = &sc->x[blockIdx.x ^ (i < 12 ? (i >> 2) + 1 : 0)][i * 128 + lane];
#pragma unroll
    for (int k = 0; k < 4; k++) st_vec(dst + 32 * k, 0u, 0u, 0u, 0u);
    while (clock_now() - t0 < CLR_PACE) {}
  }
  bar_arrive(BAR_RST, 192);
  PROF_AT(256 + 512 + 28 * 4);
  asm volatile("fence.acq_rel.gpu;" ::: "memory");
  __syncwarp();
  announce<1>(sc, lane == 0);
  PROF_AT(256 + 512 + 2 * 4);
}
__device__ __forceinline__ void l2_prefetch(const void* p, uint32_t total, int b) {
  const uint32_t part = total / NCTA;
  asm volatile("cp.async.bulk.prefetch.L2.global [%0], %1;" :: "l"((const char*)p + (size_t)b * part), "r"(part) : "memory");
}

__global__ void __launch_bounds__(384, 1) conformer_kernel(Scratch* __restrict__ sc, __nv_bfloat16* __restrict__ out,
                                                           const __nv_bfloat16* __restrict__ dw, const __nv_bfloat16* __restrict__ xin,
                                                           const __nv_bfloat16* __restrict__ w_ff1a, const __grid_constant__ Params p) {
  extern __shared__ __align__(1024) uint8_t smem[];
  const int tid = threadIdx.x, lane = tid & 31;
  const uint32_t t_start = clock_now();
  const int b = blockIdx.x, r = b & 3, batch = b >> 6, t = (b >> 2) & 15;
  if ((uint32_t)__cvta_generic_to_shared(smem) != SM_BASE) return;
  PROF_AT(256 + (tid >> 7) * 256);
  PROF_TIME(30);
  const uint32_t crow = ((tid >> 1) & 48) + (lane >> 3);
  const uint32_t cdst = SM_BASE + crow * 128 + (((lane & 7) ^ (lane >> 3)) << 4);
  if (tid < 128) {
    const uint32_t g0 = batch * T_SEQ + t * 64 + crow, o = r * 128 + (lane & 7) * 16;
    const uint32_t lo = min(g0, 2 * T_SEQ - 5) * 512 + o, hi = min(g0 + 8, 2 * T_SEQ - 5) * 512 + o;
#pragma unroll
    for (int c = 0; c < 4; c++) {
#pragma unroll
      for (int i = 0; i < 4; i++)
        cp_async16((cdst ^ ((i & 1) << 6)) + SM_STG + (3 - c) * TILE_BYTES + i * 512, (const char*)xin + (((i & 2) ? hi : lo) ^ (c << 7)) + (i & 1) * 2048);
      asm volatile("cp.async.commit_group;" ::: "memory");
    }
  } else if (tid < 256) {
    const char* src = (const char*)w_ff1a + (64 * r + crow) * 2048 + r * 512 + (lane & 7) * 16;
#pragma unroll
    for (int c = 0; c < 4; c++) {
#pragma unroll
      for (int i = 0; i < 4; i++) cp_async16((cdst ^ ((i & 1) << 6)) + c * TILE_BYTES + i * 512, src + i * 8192 + c * 128);
      asm volatile("cp.async.commit_group;" ::: "memory");
    }
  }
  const int cw = __shfl_sync(0xffffffffu, tid >> 5, 0), wg = cw >> 2, w = cw & 3;

  if (wg == 2) {
    asm volatile("setmaxnreg.dec.sync.aligned.u32 40;");
    if (cw == 8) {
      if (lane == 0) {
        asm volatile("prefetch.tensormap [%0];" :: "l"(&p.map[M_FF1A]) : "memory");
#pragma unroll
        for (int i = 0; i < NSTAGE; i++) mbar_init(SM_BASE + SM_FULL + i * 8, 1);
        fence_async_smem();
      }
      __syncwarp();
      bar_arrive(0, 320);
      while (clock_now() - t_start < TF) {}
      PROF_MARK(9);
#pragma unroll
      for (int f = 2; f < 8; f++) {
        const uint32_t x = 256 * r + ((0xE2u >> f) & 1) * 128, y = (r ^ ((0xE790u >> (2 * f)) & 3)) * 64;
        tma_fill(f, &p.map[M_FF1A], x, y, x + 64, y);
      }
      PROF_MARK(1);
      uint32_t entry[2];
#pragma unroll 1
      for (int i = 0; i < 2; i++) { entry[1] = fill_entry(8 + i * 32 + lane, r); if (i == 0) entry[0] = entry[1]; }
      bar_sync(BAR_INIT, 64);
      weight_fills<8, F_KV - 8>(p, entry[0]);
      mbar_wait(SM_BASE + SM_EMPTY + (F_WO % NSTAGE) * 8, 1);
      weight_fills<F_WO, F_TOTAL - F_WO>(p, entry[1]);
    } else if (here(cw) != 11) {
      const int kind = w - 1;
      const uint32_t prev = launch_index(sc);
      if (kind == 0) {
        if (lane == 0) {
#pragma unroll
          for (int i = 0; i < NSTAGE; i++) mbar_init(SM_BASE + SM_EMPTY + i * 8, 4);
        }
        __syncwarp();
        bar_arrive(0, 320);
        bar_arrive(BAR_INIT, 64);
        if (lane == 0) {
          const uint32_t t0 = t_start;
          while (clock_now() - t0 < PF0) {}
          while (clock_now() - t0 < PF1) {}
          asm volatile("prefetch.tensormap [%0];" :: "l"(&p.map[M_FF1B]) : "memory");
          l2_prefetch(p.w_ff1b, 1024 * 256 * 2, b);
          while (clock_now() - t0 < PF2) {}
          l2_prefetch(p.w_qkv, 256 * 768 * 2, b);
          l2_prefetch(p.w_pw1, 256 * 512 * 2, b);
          l2_prefetch(p.w_ff2a, 256 * 1024 * 2, b);
          while (clock_now() - t0 < PF3) {}
          l2_prefetch(p.w_o, 256 * 256 * 2, b);
          l2_prefetch(p.w_pw2, 256 * 256 * 2, b);
          l2_prefetch(p.w_ff2b, 1024 * 256 * 2, b);
#pragma unroll
          for (int i = M_QKV; i < M_COUNT; i++) asm volatile("prefetch.tensormap [%0];" :: "l"(&p.map[i]) : "memory");
        }
        __syncwarp();
      } else {
        reset_mailboxes(sc, 1, lane, t_start);
      }
      const uint32_t* flag = sc->flag[batch * 4 + r][kind * 16 + (lane & 15)];
      const uint32_t ready = kv_poll(flag, prev);
      if (kind == 0) bar_sync(BAR_K, 160); else bar_sync(BAR_V, 160);
      if (lane == 0) {
        asm volatile("cp.async.bulk.global.shared::cta.bulk_group [%0], [%1], %2;"
                     :: "l"(&sc->kv[batch * 4 + r][kind][t][0]), "r"(SM_BASE + SM_STG + kind * TILE_BYTES), "r"(TILE_BYTES) : "memory");
PROF_MARK(4 + kind * 2);
        asm volatile("cp.async.bulk.commit_group;\ncp.async.bulk.wait_group 0;" ::: "memory");
PROF_MARK(5 + kind * 2);
        asm volatile("st.relaxed.gpu.global.u32 [%0], %1;" :: "l"(sc->flag[batch * 4 + r][kind * 16 + t]), "r"(prev + 1) : "memory");
      }
      __syncwarp();
      kv_fills(sc, batch * 4 + r, kind, prev, flag, ready);
    } else {
      const uint32_t* watch = sc->step[(b & ~3) + (lane & 3)];
      uint32_t seen;
      asm volatile("ld.relaxed.gpu.global.u32 %0, [%1];" : "=r"(seen) : "l"(watch) : "memory");
      reset_mailboxes(sc, 0, lane, t_start);
      uint32_t want = seen & ~15u;
#pragma unroll 1
      for (int k = 0; k < 8; k++) {
        want += 2;
        uint32_t spin = 0;
#pragma unroll 1
        while (__any_sync(0xffffffffu, (int)(seen - want) < 0) && ++spin < SPIN_LIMIT)
          asm volatile("ld.relaxed.gpu.global.u32 %0, [%1];" : "=r"(seen) : "l"(watch) : "memory");
        bar_arrive(BAR_GO, 160);
        PROF_MARK(32 + k);
      }
    }
  } else {
    asm volatile("setmaxnreg.inc.sync.aligned.u32 232;");
    const int q = lane & 3, th = tid & 127;
    constexpr uint32_t stg = SM_BASE + SM_STG;
    const uint32_t mrow = 16 * w + (lane & 15);
    const uint32_t maddr = stg + mrow * 128 + (((lane >> 4) ^ (lane & 7)) << 4);
    const uint32_t qslot = stg + 2 * TILE_BYTES + w * 2048 + lane * 16;
    uint4* const xp = &sc->x[b][th];
    const int nvalid = T_SEQ - t * 64, row0 = 16 * w + (lane >> 2);

    uint32_t A[4][16];
    uint32_t st[4];
    bar_sync(0, 320);
    if (wg == 0) {
      RowAcc ra = {};
      cp_async_wait(0);
      __syncwarp();
      PROF_MARK0(45);
#pragma unroll
      for (int c = 0; c < 4; c++) tile_load(maddr + (3 - c) * TILE_BYTES, A[c]);
      row_sums(ra, A[0]); row_gram(ra, A[0]); row_sums(ra, A[1]); row_gram(ra, A[1]);
      pin(ra.s[0]); pin(ra.s[1]); pin(ra.u[0]); pin(ra.u[1]); pin(ra.v[0]); pin(ra.v[1]);
      SCHED();
      row_sums(ra, A[2]); row_sums(ra, A[3]); row_gram(ra, A[2]); row_gram(ra, A[3]);
      const float m0 = (ra.s[0][0] + ra.s[1][0]) * (1.f / DM), m1 = (ra.s[0][2] + ra.s[1][2]) * (1.f / DM);
      st[0] = pack2(m0, m0); st[1] = pack2(m1, m1);
      centre(A[0], st[0], st[1]);
      const float2 sq = row_squares(ra, lane & 4);
      st[2] = __float_as_uint(fmaf(-m0, m0, sq.x * (1.f / DM))); st[3] = __float_as_uint(fmaf(-m1, m1, sq.y * (1.f / DM)));
    } else {
      if (th < 112) sts128(SM_BASE + SM_CS + th * 16, 0, 0, 0, 0);
      sts32(SM_BASE + SM_EYE + th * 4, th >= 96 ? 0x3F803F80u : ((th & 32) == 0 && (th & 3) == ((th >> 3) & 3)) ? (0x3F00u << ((th & 4) * 4)) : 0u);
#pragma unroll
      for (int i = 0; i < 2; i++) {
        cp_async_wait(2 - 2 * i);
        fence_async_smem();
        bar_sync(BAR_WG1, 128);
        if (th == 0) mbar_arrive(SM_BASE + SM_FULL + i * 8);
      }
      PROF_MARK(6);
      const uint32_t tag = ~launch_index(sc) & 1;
      mbar_wait(SM_BASE + SM_FULL + 4 * 8, 0);
      PROF_MARK(5);
      if (b < 72) {
        const __nv_bfloat16* wp; int ld, col;
        if (b < 24) { wp = p.w_qkv; ld = 768; col = b * 32; }
        else if (b < 40) { wp = p.w_pw1; ld = 512; col = (b - 24) * 32; }
        else { wp = p.w_ff2a; ld = 1024; col = (b - 40) * 32; }
        const uint4* src = (const uint4*)(wp + (size_t)(th >> 2) * ld + col + q * 8);
        float c[8] = {0.f, 0.f, 0.f, 0.f, 0.f, 0.f, 0.f, 0.f};
#pragma unroll 1
        for (int h = 0; h < 2; h++, src += 16 * ld) {
#pragma unroll
          for (int i = 0; i < 4; i++) {
            const uint4 v = __ldg(src + i * 4 * ld);
            c[0] += bf_lo(v.x); c[1] += bf_hi(v.x); c[2] += bf_lo(v.y); c[3] += bf_hi(v.y);
            c[4] += bf_lo(v.z); c[5] += bf_hi(v.z); c[6] += bf_lo(v.w); c[7] += bf_hi(v.w);
          }
        }
#pragma unroll 1
        for (int m = 4; m <= 16; m <<= 1)
#pragma unroll
          for (int k = 0; k < 8; k++) c[k] += __shfl_xor_sync(0xffffffffu, c[k], m);
        if (lane < 4) {
          const uint32_t a = SM_BASE + SM_CS + 1792 + w * 128 + lane * 32;
          sts128(a, __float_as_uint(c[0]), __float_as_uint(c[1]), __float_as_uint(c[2]), __float_as_uint(c[3]));
          sts128(a + 16, __float_as_uint(c[4]), __float_as_uint(c[5]), __float_as_uint(c[6]), __float_as_uint(c[7]));
        }
        bar_sync(BAR_WG1, 128);
        if (th < 8) {
          float o[4] = {0.f, 0.f, 0.f, 0.f};
#pragma unroll 1
          for (int k = 0; k < 4; k++) {
            uint32_t e[4];
            lds128(SM_BASE + SM_CS + 1792 + k * 128 + th * 16, e[0], e[1], e[2], e[3]);
#pragma unroll
            for (int i = 0; i < 4; i++) o[i] += __uint_as_float(e[i]);
          }
          st_vec(&sc->cs[b * 8 + th], (__float_as_uint(o[0]) & ~1u) | tag, __float_as_uint(o[1]), __float_as_uint(o[2]), __float_as_uint(o[3]));
        }
      }
      bar_sync(BAR_WG1, 128);
      PROF_MARK(2);
      if (th < 72) {
        const int j = th >> 3, i = (th & 7) * 2;
        int src;
        if (j < CS_PW1) src = 320 + 64 * r + 16 * j;
        else if (j < CS_QKV) src = 192 + (j - CS_PW1) * 64 + 16 * r;
        else src = ((j - CS_QKV + 1) % 3) * 64 + 16 * r;
        uint32_t e[8], hi[4], lo[4], spin = 0;
#pragma unroll 1
        do {
          ld_vec(&sc->cs[src + i], e[0], e[1], e[2], e[3]);
          ld_vec(&sc->cs[src + i + 1], e[4], e[5], e[6], e[7]);
        } while ((((e[0] ^ tag) | (e[4] ^ tag)) & 1u) && ++spin < SPIN_LIMIT);
        e[0] &= ~1u; e[4] &= ~1u;
#pragma unroll
        for (int k = 0; k < 4; k++) {
          const float c0 = __uint_as_float(e[2 * k]), c1 = __uint_as_float(e[2 * k + 1]);
          hi[k] = pack2(c0, c1);
          lo[k] = pack2(c0 - bf_lo(hi[k]), c1 - bf_hi(hi[k]));
        }
        const uint32_t a = SM_BASE + SM_CS + j * 256 + i * 8;
        sts128(a ^ ((a >> 3) & 0x70), hi[0], hi[1], hi[2], hi[3]);
        sts128((a + 128) ^ (((a + 128) >> 3) & 0x70), lo[0], lo[1], lo[2], lo[3]);
      }
      fence_async_smem();
      PROF_MARK(4);
      bar_arrive(BAR_CS, 256);
    }

#pragma unroll 1
    for (uint32_t pass = 0; pass < 2; pass++) {
      uint32_t Q[16];
      if (wg == 0) {
        float acc[4][32];
        uint32_t H[4][16];
        if (!pass) { PROF_MARK(47); ACQUIRE(0); }
        mma_tile<true>(acc[0], A[0], LO(0)); mma_tile<true>(acc[1], A[0], HI(0));
        if (!pass) ACQUIRE(1);
        mma_tile<true>(acc[2], A[0], LO(1)); mma_tile<true>(acc[3], A[0], HI(1));
        if (pass) {
          gather_first<1, X_AG0>(A, st, sc, xp, 1);
        } else {
          centre(A[1], st[0], st[1]);
          acquire_n<2, 3>();
        }
        mma_tile<false>(acc[0], A[1], LO(2)); mma_tile<false>(acc[1], A[1], HI(2));
        if (pass) {
          gather_rest<1, X_AG0>(A, xp, 1);
          RELEASE(F_PW2, F_PW2 + 1);
        } else {
          centre(A[2], st[0], st[1]); centre(A[3], st[0], st[1]);
        }
        PROF_MARK2(2, 18);
        mma_tile<false>(acc[0], A[2], LO(3)); mma_tile<false>(acc[0], A[3], LO(4));
        WG_WAIT(4);
        RELEASE(0, 1);
        uint32_t mu[4] = {0u, 0u, 0u, 0u};
        float rs0, rs1, tn[2][4];
        if (pass) {
          const RowNorm n = stat_finish(sc, st, 1, 0.5f);
          rs0 = n.rs0; rs1 = n.rs1;
          mean_frag(mu, n, q == 0);
        } else {
          const int src = (lane & 28) | (lane >> 3);
          rs0 = 0.5f * rsqrt_hw(fmaxf(__uint_as_float(__shfl_sync(0xffffffffu, st[2], src)), 0.f) + LN_EPS);
          rs1 = 0.5f * rsqrt_hw(fmaxf(__uint_as_float(__shfl_sync(0xffffffffu, st[3], src)), 0.f) + LN_EPS);
        }
        pin(mu);
        mma_fold<2 * CS_FF2>(acc[0], mu);
        mma_tile<false>(acc[1], A[2], HI(3));
#define SEGS(a, b) silu_segs<a, b>(acc, tn, H, rs0, rs1)
        WG_WAIT(1); pin(acc[0]);
        SEGS(0, 1);
        mma_tile_fold<2 * CS_FF2 + 2>(acc[1], A[3], HI(4), mu);
        SEGS(1, 3);
        uint32_t ok = probe_n<5, 3>();
        SEGS(3, 4);
        settle_n<5, 3>(ok);
        mma_tile<false>(acc[2], A[1], LO(5));
        SEGS(4, 6);
        mma_tile<false>(acc[2], A[2], LO(6));
        SEGS(6, 8);
        WG_WAIT(2); pin(acc[1]);
        RELEASE(2, 4);
        SEGS(8, 9);
        mma_tile_fold<2 * CS_FF2 + 4>(acc[2], A[3], LO(7), mu);
        SEGS(9, 12);
        mma_tile<false>(acc[3], A[1], HI(5));
        SEGS(12, 14);
        mma_tile<false>(acc[3], A[2], HI(6));
        SEGS(14, 16);
        WG_WAIT(2); pin(acc[2]);
        SEGS(16, 17);
        mma_tile_fold<2 * CS_FF2 + 6>(acc[3], A[3], HI(7), mu);
        SEGS(17, 19);
        ok = probe_n<8, 2>();
        SEGS(19, 20);
        settle_n<8, 2>(ok);
        mma_tile_reuse(acc[1], H[0], LO(8));
        SEGS(20, 22);
        mma_tile<false>(acc[1], H[1], HI(8));
        SEGS(22, 24);
        WG_WAIT(2); pin(acc[3]);
        RELEASE(5, 7);
        SEGS(24, 26);
        mma_tile<false>(acc[1], H[2], LO(9));
        SEGS(26, 27);
        ok = probe_n<10, 2>();
        SEGS(27, 28);
        settle_n<10, 2>(ok);
        mma_tile_reuse(acc[2], H[0], LO(10));
        SEGS(28, 31);
        mma_tile<false>(acc[2], H[1], HI(10));
        SEGS(31, 34);
#undef SEGS
        PROF_MARK2(3, 19);
        const uint32_t rtag = here(pass ^ 1);
        const uint4* rs_in = xp + X_RS;
        mma_tile<false>(acc[1], H[3], HI(9));
        mma_tile<false>(acc[2], H[2], LO(11));
        ok = probe_n<12, 2>();
        uint4* rs_out = peer<1>(xp) + X_RS;
        mma_tile<false>(acc[2], H[3], HI(11));
        settle_n<12, 2>(ok);
        if (!pass) bar_sync(BAR_RST, 192);
        WG_WAIT(2); pin(acc[1]);
        RELEASE(8, 9);
        send_half<0>(rs_out, acc[1], rtag);
        mma_tile_reuse(acc[3], H[0], LO(12));
        SCHED();
        send_half<1>(rs_out, acc[1], rtag);
        mma_tile<false>(acc[3], H[1], HI(12));
        rs_out = peer<2>(xp) + X_RS + 512;
        WG_WAIT(2); pin(acc[2]);
        send_half<0>(rs_out, acc[2], rtag);
        mma_tile<false>(acc[3], H[2], LO(13));
        SCHED();
        ok = probe_n<14, 2>();
        send_half<1>(rs_out, acc[2], rtag);
        mma_tile<false>(acc[3], H[3], HI(13));
        settle_n<14, 2>(ok);
        mma_tile_reuse(acc[1], H[0], LO(14));
        rs_out = peer<3>(xp) + X_RS + 1024;
        if (!pass) bar_sync(BAR_GO, 160);
        announce(sc, tid == 0);
        fetch(rs_in, A[1]);
        SCHED();
        mma_tile<false>(acc[1], H[1], HI(14));
        WG_WAIT(2); pin(acc[3]);
        send_half<0>(rs_out, acc[3], rtag);
        send_half<1>(rs_out, acc[3], rtag);
        mma_tile<false>(acc[1], H[2], LO(15)); mma_tile<false>(acc[1], H[3], HI(15));
        SCHED();
        fetch(rs_in + 512, A[2]);
        SCHED();
        res_load(maddr, acc[2]);
        bar_sync(BAR_GO, 160);
        fetch(rs_in + 1024, A[3]);
        if (!pass) acquire_n<F_QKV, 3>();
        {
          uint32_t spin = 0;
          while (__builtin_expect(stale(miss(A[1], rtag) | miss(A[2], rtag) | miss(A[3], rtag)), 0) && ++spin < SPIN_LIMIT) {
            if (stale(miss(A[1], rtag) | miss(A[2], rtag))) { fetch(rs_in, A[1]); fetch(rs_in + 512, A[2]); }
            fetch(rs_in + 1024, A[3]);
          }
        }
        announce(sc, tid == 0 && !pass);
        mma_add_half(acc[2], A[1]);
        mma_add_half(acc[2], A[2]);
        mma_add_half(acc[2], A[3]);
        PROF_MARK2(4, 20);
        WG_WAIT(0); pin(acc[2]); pin(acc[1]);
#pragma unroll
        for (int i = 0; i < 16; i++) A[0][i] = pack2(fmaf(acc[1][2 * i], 0.5f, acc[2][2 * i]), fmaf(acc[1][2 * i + 1], 0.5f, acc[2][2 * i + 1]));
        if (pass) {
          PROF_MARK(21);
          stat_publish(A[0], sc, here(th), 0);
          stat_fetch(sc, st);
          const RowNorm fn = stat_finish(sc, st, 0, 1.f);
          const float nm0 = -fn.m0 * fn.rs0, nm1 = -fn.m1 * fn.rs1;
#pragma unroll
          for (int i = 0; i < 16; i++) {
            const float rs = (i & 1) ? fn.rs1 : fn.rs0, nm = (i & 1) ? nm1 : nm0;
            A[0][i] = pack2(fmaf(bf_lo(A[0][i]), rs, nm), fmaf(bf_hi(A[0][i]), rs, nm));
          }
          tile_store(here(maddr), A[0]);
          __syncwarp();
          const int row = 16 * w + (lane >> 3);
          uint4* dst = (uint4*)(out + ((size_t)batch * T_SEQ + t * 64 + row) * DM + 64 * r) + (lane & 7);
          const uint32_t src = stg + row * 128 + (((lane & 7) ^ (lane >> 3)) << 4);
#pragma unroll
          for (int i = 0; i < 4; i++) {
            uint4 v;
            lds128((src ^ ((i & 1) << 6)) + i * 512, v.x, v.y, v.z, v.w);
            if (row + 4 * i < nvalid) dst[i * 4 * (DM / 8)] = v;
          }
          PROF_MARK(22);
          PROF_TIME(31);
          break;
        }
        send_residual(A[0], sc, xp, maddr, 1);
        PROF_MARK(5);
        mma_tile<true>(acc[0], A[0], LO(F_QKV)); mma_tile<true>(acc[1], A[0], HI(F_QKV));
        mma_tile<true>(acc[2], A[0], LO(F_QKV + 1));
        gather_first<1, X_AG0>(A, st, sc, xp, 1);
        mma_tile<false>(acc[0], A[1], LO(F_QKV + 2)); mma_tile<false>(acc[1], A[1], HI(F_QKV + 2));
        acquire_n<F_QKV + 3, 3>();
        bar_sync(BAR_CS, 256);
        gather_rest<1, X_AG0>(A, xp, 1);
        PROF_MARK(6);
        mma_tile<false>(acc[0], A[2], LO(F_QKV + 3)); mma_tile<false>(acc[0], A[3], LO(F_QKV + 4));
        SCHED();
        {
          const RowNorm n = stat_finish(sc, st, 1, 1.f);
          rs0 = row0 < nvalid ? n.rs0 : 0.f; rs1 = row0 + 8 < nvalid ? n.rs1 : 0.f;
          mean_frag(mu, n, q == 3);
        }
        mma_fold<2 * CS_QKV - 6>(acc[0], mu);
        RELEASE(10, 15);
        WG_WAIT(0); pin(acc[0]);
        scale_pack(acc[0], Q, rs0, rs1);
        tile_store(here(maddr), Q);
        SCHED();
        mma_tile<false>(acc[1], A[2], HI(F_QKV + 3));
        fence_async_smem();
        bar_arrive(BAR_K, 160);
        mma_tile_fold<2 * CS_QKV - 4>(acc[1], A[3], HI(F_QKV + 4), mu);
        mma_tile<false>(acc[2], A[1], HI(F_QKV + 1)); mma_tile<false>(acc[2], A[2], LO(F_QKV + 5));
        WG_WAIT(2); pin(acc[1]);
        scale_pack(acc[1], Q, rs0, rs1);
        tile_store(here(maddr) + TILE_BYTES, Q);
        fence_async_smem();
        bar_arrive(BAR_V, 160);
        mma_tile_fold<2 * CS_QKV - 2>(acc[2], A[3], HI(F_QKV + 5), mu);
        WG_WAIT(0); pin(acc[2]);
        scale_pack(acc[2], Q, rs0 * SM_SCALE_LOG2, rs1 * SM_SCALE_LOG2);
        frag_store(here(qslot), Q);
        bar_arrive(BAR_Q, 256);
        RELEASE(F_QKV, F_QKV + 5);
      } else {
        bar_sync(BAR_Q, 256);
#pragma unroll
        for (int s = 0; s < 4; s++) lds128(qslot + s * 512, Q[4 * s], Q[4 * s + 1], Q[4 * s + 2], Q[4 * s + 3]);
        if (w < 2) {
          const uint32_t v = w ? 0u : 0x3F803F80u;
#pragma unroll
          for (int s = 0; s < 4; s++) sts128(qslot + s * 512, v, v, v, v);
          fence_async_smem();
        }
      }
      bar_sync(BAR_ATT, 256);
      PROF_MARK(7);

      const int dir = cw == 0 ? -1 : 1;
      uint32_t tap[15];
      {
        const uint32_t* dwp = (const uint32_t*)(dw + 64 * r) + lane + 7 * (DM / 2);
#pragma unroll
        for (int k = 0; k < 15; k++) tap[k] = __ldg(dwp + dir * (k - 7) * (DM / 2));
      }

      float O[36];
      {
        float S[2][32];
        uint32_t P[2][16], nm[4];
#pragma unroll
        for (int i = 0; i < 32; i++) { S[0][i] = 0.f; S[1][i] = 0.f; }
        pin(Q); pin(S[0]);
        WG_FENCE();
        qk_tile(S[0], Q, RING_K + (SM_STG >> 4));
        WG_COMMIT();
#pragma unroll
        for (int i = 0; i < 36; i++) O[i] = 0.f;
#pragma unroll
        for (int i = 0; i < 16; i++) P[1][i] = 0u;
        WG_WAIT(0); pin(S[0]);
        const float m0 = tile_max<0>(S[0]), m1 = tile_max<2>(S[0]);
        nm[0] = pack2(q ? 0.f : -m0, 0.f); nm[1] = pack2(q ? 0.f : -m1, 0.f); nm[2] = 0u; nm[3] = 0u;
#pragma unroll
        for (int k = 0; k < 15; k++) asm("mul.rn.bf16x2 %0, %0, %1;" : "+r"(tap[k]) : "r"(0x3F003F00u));
        pin(nm); pin(O); pin(P[1]); pin(tap);
        uint32_t sk = wg, sv = F_SPARE % NSTAGE + wg;
        mbar_wait(SM_BASE + SM_FULL + sv * 8, 1);
        mbar_wait(SM_BASE + SM_FULL + sk * 8, 0);
        if (wg == 1) bar_sync(BAR_ATT, 256);
        PROF_MARK(8);
        WG_FENCE();
        qk_tile(S[0], Q, RING_K + sk * 1024);
        qk_shift(S[0], nm);
        WG_COMMIT();
        WG_WAIT(0); pin(S[0]); pin(S[1]);
        if (wg == 0) bar_arrive(BAR_ATT, 256);
#pragma unroll 1
        for (int it = 0; it < 4; it++) {
          const uint32_t sn = it >= 2 ? wg : sk + 4;
          uint32_t ok = 1;
          mbar_probe(ok, SM_BASE + SM_FULL + sn * 8, it >= 2);
          mbar_probe(ok, SM_BASE + SM_FULL + (sk + 2) * 8, it == 3);
          attn_step(S[0], S[1], P[0], P[1], O, Q, nm, RING_K + sk * 1024 + 512, RING_V + (sv * 1024 + 512) * V_STEP, true, it > 0);
          PROF_MARK(24 + it * 3);
          if (__builtin_expect(!ok, 0)) {
            mbar_wait(SM_BASE + SM_FULL + sn * 8, it >= 2);
            mbar_wait(SM_BASE + SM_FULL + (sk + 2) * 8, it == 3);
          }
          WG_WAIT(0); pin(O); pin(S[1]); pin(P[1]);
          asm volatile("{\n.reg .pred p;\nsetp.eq.u32 p, %2, 0;\n@p mbarrier.arrive.shared::cta.b64 _, [%0];\n@p mbarrier.arrive.shared::cta.b64 _, [%1];\n}"
                       :: "r"(SM_BASE + SM_EMPTY + sk * 8), "r"(SM_BASE + SM_EMPTY + sv * 8), "r"(lane) : "memory");
          PROF_MARK(25 + it * 3);
          sv = sk + 2; sk = sn;
          attn_step(S[1], S[0], P[1], P[0], O, Q, nm, RING_K + sk * 1024, RING_V + (sv * 1024) * V_STEP, it < 3, true);
          WG_WAIT(0); pin(O); pin(S[0]); pin(P[0]);
          PROF_MARK(26 + it * 3);
        }
        WG_FENCE();
        pv_tile(O, P[1], RING_V + (sv * 1024 + 512) * V_STEP, wg << 22);
        WG_COMMIT();
        announce<1>(sc, th == 0);
        WG_WAIT(0); pin(O);
      }
      PROF_MARK(9);

      {
        const uint32_t mo = stg + here(th) * 16;
        sts64(mo + 5 * 4096 + wg * 8, __float_as_uint(O[32]), __float_as_uint(O[34]));
        if (wg == 0) {
#pragma unroll
          for (int i = 4; i < 8; i++)
            sts128(mo + i * 2048, __float_as_uint(O[4 * i]), __float_as_uint(O[4 * i + 1]), __float_as_uint(O[4 * i + 2]), __float_as_uint(O[4 * i + 3]));
        } else {
#pragma unroll
          for (int i = 0; i < 4; i++)
            sts128(mo + i * 2048, __float_as_uint(O[4 * i]), __float_as_uint(O[4 * i + 1]), __float_as_uint(O[4 * i + 2]), __float_as_uint(O[4 * i + 3]));
#pragma unroll
          for (int i = 0; i < 16; i++) O[i] = O[16 + i];
        }
        bar_sync(BAR_MERGE, 256);
        uint32_t e[4];
        lds128(mo + 5 * 4096, e[0], e[1], e[2], e[3]);
        O[32] = __uint_as_float(e[0]) + __uint_as_float(e[2]); O[34] = __uint_as_float(e[1]) + __uint_as_float(e[3]);
#pragma unroll
        for (int i = 0; i < 4; i++) {
          lds128(mo + wg * TILE_BYTES + i * 2048, e[0], e[1], e[2], e[3]);
#pragma unroll
          for (int k = 0; k < 4; k++) O[4 * i + k] += __uint_as_float(e[k]);
        }
        const bool safe = O[32] > 0x1p-60f && O[32] < 0x1p60f && O[34] > 0x1p-60f && O[34] < 0x1p60f;
        if (__builtin_expect(__any_sync(0xffffffffu, !safe), 0)) attention_exact(O, Q, sc, batch * 4 + r, lane, wg);
        const float i0 = rcp_hw(O[32]), i1 = rcp_hw(O[34]);
#pragma unroll
        for (int i = 0; i < 8; i++) { const float v = (i & 1) ? i1 : i0; A[0][i] = pack2(O[2 * i] * v, O[2 * i + 1] * v); }
        A[0][0] &= ~1u; A[0][4] &= ~1u;
        uint4* dst = xp + X_AG1 + wg * 256;
        SCHED();
        st_vec(dst, A[0][0], A[0][1], A[0][2], A[0][3]);
        st_vec(dst + 128, A[0][4], A[0][5], A[0][6], A[0][7]);
        SCHED();
      }
      if (wg == 1) {
        const uint32_t mo = stg + TILE_BYTES + here(th) * 16;
        sts128(mo, A[0][0], A[0][1], A[0][2], A[0][3]);
        sts128(mo + 2048, A[0][4], A[0][5], A[0][6], A[0][7]);
        bar_arrive(BAR_HALF, 256);
      } else {
        PROF_MARK(10);
        const uint32_t mo = stg + TILE_BYTES + here(th) * 16;
        bar_sync(BAR_HALF, 256);
        lds128(mo, A[0][8], A[0][9], A[0][10], A[0][11]);
        lds128(mo + 2048, A[0][12], A[0][13], A[0][14], A[0][15]);
        proj_residual<F_WO, 6>(A, sc, xp, maddr, 0, lane);
        PROF_MARK(12);
        float acc[2][32];
        mma_tile<true>(acc[0], A[0], LO(F_PW1)); mma_tile<true>(acc[1], A[0], HI(F_PW1));
        gather_first<1, X_AG0>(A, st, sc, xp, 0);
        mma_tile<false>(acc[1], A[1], HI(F_PW1 + 1)); mma_tile<false>(acc[0], A[1], LO(F_PW1 + 1));
        gather_rest<1, X_AG0>(A, xp, 0);
        PROF_MARK(13);
        mma_tile<false>(acc[1], A[2], HI(F_PW1 + 2)); mma_tile<false>(acc[1], A[3], HI(F_PW1 + 3));
        WG_WAIT(2);
        RELEASE(F_WO, F_PW1 + 1);
        SCHED();
        uint32_t mu[4];
        const RowNorm n = stat_finish(sc, st, 0, 0.5f);
        const float rs0 = row0 < nvalid ? n.rs0 : 0.f, rs1 = row0 + 8 < nvalid ? n.rs1 : 0.f;
        mean_frag(mu, n, q == 0);
        mma_fold<2 * CS_PW1 + 2>(acc[1], mu);
        mma_tile<false>(acc[0], A[2], LO(F_PW1 + 2));
        mma_tile_fold<2 * CS_PW1>(acc[0], A[3], LO(F_PW1 + 3), mu);
        WG_WAIT(2); pin(acc[1]);
#pragma unroll
        for (int i = 0; i < 32; i++) acc[1][i] = tanh_hw(acc[1][i] * ((i & 2) ? rs1 : rs0));
#pragma unroll
        for (int i = 0; i < 32; i++) { const float rs = (i & 2) ? rs1 : rs0; acc[1][i] = fmaf(acc[1][i], rs, rs); }
        pin(acc[1]);
        SCHED();
        WG_WAIT(0); pin(acc[0]);
#pragma unroll
        for (int i = 0; i < 16; i++) A[0][i] = pack2(acc[0][2 * i] * acc[1][2 * i], acc[0][2 * i + 1] * acc[1][2 * i + 1]);
        const uint32_t ga = stg + TILE_BYTES + here(mrow) * G_PITCH + (lane >> 4) * 16;
#pragma unroll
        for (int s = 0; s < 4; s++) stsm4(ga + s * 32, &A[0][4 * s]);
      }
      {
        const uint32_t gsrc = stg + TILE_BYTES + (8 * cw - 7) * G_PITCH + lane * 4;
        const bool edge = cw == 0 || cw == 7;
        const bool nbr = cw == 0 ? t > 0 : t < 15;
        uint4* const hdst = &sc->x[b + 4 * dir][X_HALO + (cw == 0 ? 96 : 0) + lane];
        uint32_t in[22];
        bar_sync(BAR_G, 256);
        PROF_MARK(14);
        if (cw == 0) {
#pragma unroll
          for (int i = 14; i >= 0; i--) in[i] = lds32(gsrc + (21 - i) * G_PITCH);
        } else {
#pragma unroll
          for (int i = 14; i >= 0; i--) in[i] = lds32(gsrc + i * G_PITCH);
        }
        if (edge) {
          if (nbr) {
            st_vec(hdst, HALO_TAG, in[14], in[13], in[12]);
            st_vec(hdst + 32, HALO_TAG, in[11], in[10], in[9]);
            st_vec(hdst + 64, HALO_TAG, in[8], 0u, 0u);
          }
        } else {
#pragma unroll
          for (int i = 15; i < 22; i++) in[i] = lds32(gsrc + i * G_PITCH);
        }
        if (cw == 0) PROF_MARK0(40);
        uint32_t cv[8];
#pragma unroll
        for (int i = 0; i < 15; i++)
#pragma unroll
          for (int o = 0; o < 8; o++) {
            if (i == o) asm("mul.rn.bf16x2 %0, %1, %2;" : "=r"(cv[o]) : "r"(in[i]), "r"(tap[0]));
            if (i > o) asm("fma.rn.bf16x2 %0, %1, %2, %0;" : "+r"(cv[o]) : "r"(in[i]), "r"(tap[i - o]));
          }
        pin(cv);
        if (cw == 0) PROF_MARK0(41);
        if (edge) {
#pragma unroll
          for (int i = 15; i < 22; i++) in[i] = 0u;
          if (nbr) {
            const uint4* src = &sc->x[b][X_HALO + (cw == 0 ? 0 : 96) + lane];
            uint32_t e0, e1, e2, u0, u1, spin = 0;
#pragma unroll 1
            do {
              ld_vec(src, e0, in[15], in[16], in[17]);
              ld_vec(src + 32, e1, in[18], in[19], in[20]);
              ld_vec(src + 64, e2, in[21], u0, u1);
            } while (__any_sync(0xffffffffu, ((e0 ^ HALO_TAG) | (e1 ^ HALO_TAG) | (e2 ^ HALO_TAG)) != 0) && ++spin < SPIN_LIMIT);
          }
          announce<1>(sc, lane == 0);
        }
#pragma unroll
        for (int i = 15; i < 22; i++)
#pragma unroll
          for (int o = 0; o < 8; o++)
            if (i - o <= 14) asm("fma.rn.bf16x2 %0, %1, %2, %0;" : "+r"(cv[o]) : "r"(in[i]), "r"(tap[i - o]));
        if (cw == 0) PROF_MARK0(42);
        if (cw == 7) PROF_MARK0(43);
        const uint32_t fl = cw == 0 ? 7 : 0;
        const uint32_t cdst = (stg + cw * 1024 + lane * 4) ^ (fl * 144);
#pragma unroll
        for (int o = 0; o < 8; o++) {
          const float a = bf_lo(cv[o]), c = bf_hi(cv[o]);
          sts32(cdst ^ (o * 144), pack2(fmaf(a, tanh_hw(a), a), fmaf(c, tanh_hw(c), c)));
        }
      }
      if (wg == 1) {
        bar_arrive(BAR_C, 256);
        break;
      }
      bar_sync(BAR_C, 256);
      tile_load(here(maddr), A[0]);
      PROF_MARK(15);
      publish(xp + X_AG1, A[0], 1);
      proj_residual<F_PW2, 2>(A, sc, xp, maddr, 1, lane);
      PROF_MARK(17);
    }
  }
}

typedef CUresult (*EncodeFn)(CUtensorMap*, CUtensorMapDataType, cuuint32_t, void*, const cuuint64_t*, const cuuint64_t*,
                             const cuuint32_t*, const cuuint32_t*, CUtensorMapInterleave, CUtensorMapSwizzle,
                             CUtensorMapL2promotion, CUtensorMapFloatOOBfill);

void make_map(EncodeFn fn, CUtensorMap* m, const void* w, int rows, int cols, CUtensorMapSwizzle swz) {
  const cuuint64_t dims[2] = {(cuuint64_t)cols, (cuuint64_t)rows}, strides[1] = {(cuuint64_t)cols * 2};
  const cuuint32_t box[2] = {64, 64}, es[2] = {1, 1};
  fn(m, CU_TENSOR_MAP_DATA_TYPE_BFLOAT16, 2, const_cast<void*>(w), dims, strides, box, es, CU_TENSOR_MAP_INTERLEAVE_NONE,
     swz, CU_TENSOR_MAP_L2_PROMOTION_L2_128B, CU_TENSOR_MAP_FLOAT_OOB_FILL_NONE);
}

}

extern "C" void kernel_launch(void* const* d_in, const int* in_sizes, int n_in, void* d_out, int out_size) {
  static EncodeFn fn = nullptr;
  static Scratch* sc = nullptr;
  if (!fn) {
    void* f = nullptr;
    cudaDriverEntryPointQueryResult st;
    cudaGetDriverEntryPoint("cuTensorMapEncodeTiled", &f, cudaEnableDefault, &st);
    fn = (EncodeFn)f;
    void* raw = nullptr;
    cudaGetSymbolAddress(&raw, g_scratch);
    sc = (Scratch*)(((uintptr_t)raw + X_ALIGN - 1) & ~(uintptr_t)(X_ALIGN - 1));
    cudaFuncSetAttribute(conformer_kernel, cudaFuncAttributeMaxDynamicSharedMemorySize, SM_TOTAL);
  }
  typedef const __nv_bfloat16* W;
  const CUtensorMapSwizzle S = CU_TENSOR_MAP_SWIZZLE_128B;
  Params p;
  make_map(fn, &p.map[M_FF1A], d_in[1], 256, 1024, S);
  make_map(fn, &p.map[M_FF1B], d_in[2], 1024, 256, S);
  make_map(fn, &p.map[M_QKV], d_in[3], 256, 768, S);
  make_map(fn, &p.map[M_WO], d_in[4], 256, 256, S);
  make_map(fn, &p.map[M_PW1], d_in[5], 256, 512, S);
  make_map(fn, &p.map[M_PW2], d_in[7], 256, 256, S);
  make_map(fn, &p.map[M_FF2A], d_in[8], 256, 1024, S);
  make_map(fn, &p.map[M_FF2B], d_in[9], 1024, 256, S);
  p.w_ff1b = (W)d_in[2]; p.w_qkv = (W)d_in[3]; p.w_o = (W)d_in[4]; p.w_pw1 = (W)d_in[5];
  p.w_pw2 = (W)d_in[7]; p.w_ff2a = (W)d_in[8]; p.w_ff2b = (W)d_in[9];

  cudaLaunchConfig_t cfg = {};
  cfg.gridDim = dim3(NCTA);
  cfg.blockDim = dim3(384);
  cfg.dynamicSmemBytes = SM_TOTAL;
  cfg.stream = cudaStreamPerThread;
  cudaLaunchAttribute at[1];
  at[0].id = cudaLaunchAttributeCooperative;
  at[0].val.cooperative = 1;
  cfg.attrs = at;
  cfg.numAttrs = 1;
  cudaLaunchKernelEx(&cfg, conformer_kernel, sc, (__nv_bfloat16*)d_out, (W)d_in[6], (W)d_in[0], (W)d_in[1], p);
}
```

```cpp
#include <cuda_runtime.h>
#include <cuda_bf16.h>
#include <cuda.h>
#include <stdint.h>

namespace {

constexpr int T_SEQ = 1000;
constexpr int DM = 256;
constexpr int NCTA = 128;
constexpr int NSTAGE = 12;
constexpr uint32_t STAGE_BYTES = 16384;
constexpr uint32_t TILE_BYTES = 8192;
constexpr uint32_t SM_BASE = 1024;
constexpr uint32_t SM_STG = NSTAGE * STAGE_BYTES;
constexpr uint32_t SM_FULL = SM_STG + 32768;
constexpr uint32_t SM_EMPTY = SM_FULL + 96;
constexpr uint32_t SM_EYE = SM_FULL + 256;
constexpr uint32_t SM_ONE = SM_FULL + 640;
constexpr uint32_t SM_CS = SM_FULL + 768;
constexpr uint32_t SM_TOTAL = SM_FULL + 3072;
constexpr int CS_FF2 = 0, CS_PW1 = 4, CS_QKV = 6;
constexpr uint32_t SPIN_LIMIT = 1u << 16;
constexpr float LN_EPS = 1e-5f;
constexpr float SM_SCALE_LOG2 = 0.125f * 1.4426950408889634f;
constexpr uint32_t G_PITCH = 144;
#define TIMED 0
#define GD 400
#define RD 550
#define NREL 4
#define PF0 1
#define TF 1
#define TC 1
#define PF1 1400
#define PF2 2000
#define PF3 3500
#define CLR_PACE 150

constexpr int F_QKV = 16, F_SPARE = 22, F_KV = 24, F_WO = 40, F_PW1 = 42, F_PW2 = 46, F_TOTAL = 64;
enum { M_FF1A, M_FF1B, M_QKV, M_WO, M_PW1, M_PW2, M_FF2A, M_FF2B, M_COUNT };
enum { BAR_K = 1, BAR_V, BAR_Q, BAR_MERGE, BAR_G, BAR_C, BAR_WG1, BAR_GO, BAR_CS, BAR_ATT, BAR_INIT, BAR_HALF, BAR_RST };

struct Params {
  CUtensorMap map[M_COUNT];
  const __nv_bfloat16 *w_ff1b, *w_qkv, *w_o, *w_pw1, *w_pw2, *w_ff2a, *w_ff2b;
};

constexpr int X_RS = 0, X_AG1 = X_RS, X_HALO = X_RS + 512, X_AG0 = 1536, X_ST = 2048, X_SIZE = 4096;
constexpr uint32_t HALO_TAG = 0xFFFF0001u;
struct Scratch {
  uint4 x[NCTA][X_SIZE];
  uint4 kv[8][2][16][512];
  uint4 cs[576];
  uint32_t flag[8][32][32];
  uint32_t step[NCTA][32];
};
constexpr size_t X_ALIGN = 4 * X_SIZE * sizeof(uint4);
__device__ uint8_t g_scratch[sizeof(Scratch) + X_ALIGN];
#define PROF_TIME(i)
#define PROF_MARK(i)
#define PROF_MARK2(i, j)
#define PROF_MARK0(i)
#define PROF_AT(a)

__device__ __forceinline__ void mbar_init(uint32_t bar, uint32_t cnt) {
  asm volatile("mbarrier.init.shared::cta.b64 [%0], %1;" :: "r"(bar), "r"(cnt) : "memory");
}
__device__ __forceinline__ void mbar_wait(uint32_t bar, uint32_t parity) {
  asm volatile("{\n.reg .pred p;\n.reg .u32 c;\nmov.u32 c, 0;\n"
               "WAIT_LOOP:\nmbarrier.try_wait.parity.shared::cta.b64 p, [%0], %1;\n@p bra WAIT_DONE;\n"
               "add.u32 c, c, 1;\nsetp.lt.u32 p, c, %2;\n@p bra WAIT_LOOP;\nWAIT_DONE:\n}"
               :: "r"(bar), "r"(parity), "n"(SPIN_LIMIT) : "memory");
}
__device__ __forceinline__ void mbar_arrive(uint32_t bar) {
  asm volatile("mbarrier.arrive.shared::cta.b64 _, [%0];" :: "r"(bar) : "memory");
}
#define bar_sync(id, n) asm volatile("bar.sync %0, %1;" :: "n"((int)(id)), "n"(n) : "memory")
#define bar_arrive(id, n) asm volatile("bar.arrive %0, %1;" :: "n"((int)(id)), "n"(n) : "memory")
__device__ __forceinline__ void fence_async_smem() { asm volatile("fence.proxy.async.shared::cta;" ::: "memory"); }

__device__ __forceinline__ void st_vec(uint4* p, uint32_t a, uint32_t b, uint32_t c, uint32_t d) {
  asm volatile("{\n.reg .b128 v;\n.reg .b64 lo, hi;\nmov.b64 lo, {%1, %2};\nmov.b64 hi, {%3, %4};\nmov.b128 v, {lo, hi};\n"
               "st.relaxed.gpu.global.b128 [%0], v;\n}" :: "l"(p), "r"(a), "r"(b), "r"(c), "r"(d) : "memory");
}
__device__ __forceinline__ void ld_vec(const uint4* p, uint32_t& a, uint32_t& b, uint32_t& c, uint32_t& d) {
  asm volatile("{\n.reg .b128 v;\n.reg .b64 lo, hi;\nld.relaxed.gpu.global.b128 v, [%4];\nmov.b128 {lo, hi}, v;\n"
               "mov.b64 {%0, %1}, lo;\nmov.b64 {%2, %3}, hi;\n}" : "=r"(a), "=r"(b), "=r"(c), "=r"(d) : "l"(p) : "memory");
}
__device__ __forceinline__ void sts128(uint32_t a, uint32_t x, uint32_t y, uint32_t z, uint32_t w) {
  asm volatile("st.shared.v4.u32 [%0], {%1, %2, %3, %4};" :: "r"(a), "r"(x), "r"(y), "r"(z), "r"(w) : "memory");
}
__device__ __forceinline__ void lds128(uint32_t a, uint32_t& x, uint32_t& y, uint32_t& z, uint32_t& w) {
  asm volatile("ld.shared.v4.u32 {%0, %1, %2, %3}, [%4];" : "=r"(x), "=r"(y), "=r"(z), "=r"(w) : "r"(a) : "memory");
}
__device__ __forceinline__ uint32_t lds32(uint32_t a) {
  uint32_t x; asm volatile("ld.shared.u32 %0, [%1];" : "=r"(x) : "r"(a) : "memory"); return x;
}
__device__ __forceinline__ void sts32(uint32_t a, uint32_t x) { asm volatile("st.shared.u32 [%0], %1;" :: "r"(a), "r"(x) : "memory"); }
__device__ __forceinline__ void sts64(uint32_t a, uint32_t x, uint32_t y) {
  asm volatile("st.shared.v2.u32 [%0], {%1, %2};" :: "r"(a), "r"(x), "r"(y) : "memory");
}
__device__ __forceinline__ void stsm4(uint32_t a, const uint32_t* r) {
  asm volatile("stmatrix.sync.aligned.m8n8.x4.shared.b16 [%0], {%1, %2, %3, %4};" :: "r"(a), "r"(r[0]), "r"(r[1]), "r"(r[2]), "r"(r[3]) : "memory");
}
__device__ __forceinline__ void ldsm4(uint32_t a, uint32_t* r) {
  asm volatile("ldmatrix.sync.aligned.m8n8.x4.shared.b16 {%0, %1, %2, %3}, [%4];" : "=r"(r[0]), "=r"(r[1]), "=r"(r[2]), "=r"(r[3]) : "r"(a) : "memory");
}
__device__ __forceinline__ uint32_t pack2(float lo, float hi) {
  uint32_t r; asm("cvt.rn.bf16x2.f32 %0, %1, %2;" : "=r"(r) : "f"(hi), "f"(lo)); return r;
}
__device__ __forceinline__ float bf_lo(uint32_t w) { return __uint_as_float(w << 16); }
__device__ __forceinline__ float bf_hi(uint32_t w) { return __uint_as_float(w & 0xffff0000u); }
__device__ __forceinline__ float tanh_hw(float x) { float y; asm volatile("tanh.approx.f32 %0, %1;" : "=f"(y) : "f"(x)); return y; }
__device__ __forceinline__ float rcp_hw(float x) { float y; asm("rcp.approx.ftz.f32 %0, %1;" : "=f"(y) : "f"(x)); return y; }
__device__ __forceinline__ float rsqrt_hw(float x) { float y; asm("rsqrt.approx.ftz.f32 %0, %1;" : "=f"(y) : "f"(x)); return y; }
__device__ __forceinline__ float ex2_hw(float x) { float y; asm("ex2.approx.ftz.f32 %0, %1;" : "=f"(y) : "f"(x)); return y; }

__device__ __forceinline__ uint32_t here(uint32_t v) { asm volatile("" : "+r"(v)); return v; }

#define SCHED() asm volatile("pmevent 1;" ::: "memory")
__device__ __forceinline__ void cp_async16(uint32_t dst, const void* src) {
  asm volatile("cp.async.cg.shared.global [%0], [%1], 16;" :: "r"(dst), "l"(src) : "memory");
}
__device__ __forceinline__ void cp_async_wait(int n) {
  if (n == 0) asm volatile("cp.async.wait_group 0;" ::: "memory");
  if (n == 1) asm volatile("cp.async.wait_group 1;" ::: "memory");
  if (n == 2) asm volatile("cp.async.wait_group 2;" ::: "memory");
  if (n == 3) asm volatile("cp.async.wait_group 3;" ::: "memory");
}
#define WG_FENCE() asm volatile("wgmma.fence.sync.aligned;" ::: "memory")
#define WG_COMMIT() asm volatile("wgmma.commit_group.sync.aligned;" ::: "memory")
#define WG_WAIT(n) asm volatile("wgmma.wait_group.sync.aligned %0;" :: "n"(n) : "memory")

template <int N> __device__ __forceinline__ void pin(float (&d)[N]) {
#pragma unroll
  for (int i = 0; i < N; i++) asm volatile("" : "+f"(d[i]) :: "memory");
}
template <int N> __device__ __forceinline__ void pin(uint32_t (&d)[N]) {
#pragma unroll
  for (int i = 0; i < N; i++) asm volatile("" : "+r"(d[i]) :: "memory");
}

#define WG_D32 "{%0, %1, %2, %3, %4, %5, %6, %7, %8, %9, %10, %11, %12, %13, %14, %15, %16, %17, %18, %19, %20, %21, %22, %23, %24, %25, %26, %27, %28, %29, %30, %31}"
template <int TB> __device__ __forceinline__ void wgmma64_acc(float (&d)[32], const uint32_t* a, uint64_t db) {
  asm volatile("wgmma.mma_async.sync.aligned.m64n64k16.f32.bf16.bf16 " WG_D32 ", {%32, %33, %34, %35}, %36, 1, 1, 1, %37;"
    : "+f"(d[0]), "+f"(d[1]), "+f"(d[2]), "+f"(d[3]), "+f"(d[4]), "+f"(d[5]), "+f"(d[6]), "+f"(d[7]),
      "+f"(d[8]), "+f"(d[9]), "+f"(d[10]), "+f"(d[11]), "+f"(d[12]), "+f"(d[13]), "+f"(d[14]), "+f"(d[15]),
      "+f"(d[16]), "+f"(d[17]), "+f"(d[18]), "+f"(d[19]), "+f"(d[20]), "+f"(d[21]), "+f"(d[22]), "+f"(d[23]),
      "+f"(d[24]), "+f"(d[25]), "+f"(d[26]), "+f"(d[27]), "+f"(d[28]), "+f"(d[29]), "+f"(d[30]), "+f"(d[31])
    : "r"(a[0]), "r"(a[1]), "r"(a[2]), "r"(a[3]), "l"(db), "n"(TB));
}
template <int TB> __device__ __forceinline__ void wgmma64_reuse(float (&d)[32], const uint32_t* a, uint64_t db, uint32_t zero) {
  asm volatile("{\n.reg .pred p;\nsetp.ne.u32 p, %37, 0;\nwgmma.mma_async.sync.aligned.m64n64k16.f32.bf16.bf16 " WG_D32 ", {%32, %33, %34, %35}, %36, p, 1, 1, %38;\n}"
    : "+f"(d[0]), "+f"(d[1]), "+f"(d[2]), "+f"(d[3]), "+f"(d[4]), "+f"(d[5]), "+f"(d[6]), "+f"(d[7]),
      "+f"(d[8]), "+f"(d[9]), "+f"(d[10]), "+f"(d[11]), "+f"(d[12]), "+f"(d[13]), "+f"(d[14]), "+f"(d[15]),
      "+f"(d[16]), "+f"(d[17]), "+f"(d[18]), "+f"(d[19]), "+f"(d[20]), "+f"(d[21]), "+f"(d[22]), "+f"(d[23]),
      "+f"(d[24]), "+f"(d[25]), "+f"(d[26]), "+f"(d[27]), "+f"(d[28]), "+f"(d[29]), "+f"(d[30]), "+f"(d[31])
    : "r"(a[0]), "r"(a[1]), "r"(a[2]), "r"(a[3]), "l"(db), "r"(zero), "n"(TB));
}
template <int TB> __device__ __forceinline__ void wgmma64_set(float (&d)[32], const uint32_t* a, uint64_t db) {
  asm volatile("wgmma.mma_async.sync.aligned.m64n64k16.f32.bf16.bf16 " WG_D32 ", {%32, %33, %34, %35}, %36, 0, 1, 1, %37;"
    : "=f"(d[0]), "=f"(d[1]), "=f"(d[2]), "=f"(d[3]), "=f"(d[4]), "=f"(d[5]), "=f"(d[6]), "=f"(d[7]),
      "=f"(d[8]), "=f"(d[9]), "=f"(d[10]), "=f"(d[11]), "=f"(d[12]), "=f"(d[13]), "=f"(d[14]), "=f"(d[15]),
      "=f"(d[16]), "=f"(d[17]), "=f"(d[18]), "=f"(d[19]), "=f"(d[20]), "=f"(d[21]), "=f"(d[22]), "=f"(d[23]),
      "=f"(d[24]), "=f"(d[25]), "=f"(d[26]), "=f"(d[27]), "=f"(d[28]), "=f"(d[29]), "=f"(d[30]), "=f"(d[31])
    : "r"(a[0]), "r"(a[1]), "r"(a[2]), "r"(a[3]), "l"(db), "n"(TB));
}

__device__ __forceinline__ void wgmma72_acc(float (&d)[36], const uint32_t* a, uint64_t db) {
  asm volatile("wgmma.mma_async.sync.aligned.m64n72k16.f32.bf16.bf16 {%0, %1, %2, %3, %4, %5, %6, %7, %8, %9, %10, %11, %12, %13, %14, %15, %16, %17, %18, %19, %20, %21, %22, %23, %24, %25, %26, %27, %28, %29, %30, %31, %32, %33, %34, %35}, {%36, %37, %38, %39}, %40, 1, 1, 1, 1;"
    : "+f"(d[0]), "+f"(d[1]), "+f"(d[2]), "+f"(d[3]), "+f"(d[4]), "+f"(d[5]), "+f"(d[6]), "+f"(d[7]), "+f"(d[8]),
      "+f"(d[9]), "+f"(d[10]), "+f"(d[11]), "+f"(d[12]), "+f"(d[13]), "+f"(d[14]), "+f"(d[15]), "+f"(d[16]), "+f"(d[17]),
      "+f"(d[18]), "+f"(d[19]), "+f"(d[20]), "+f"(d[21]), "+f"(d[22]), "+f"(d[23]), "+f"(d[24]), "+f"(d[25]), "+f"(d[26]),
      "+f"(d[27]), "+f"(d[28]), "+f"(d[29]), "+f"(d[30]), "+f"(d[31]), "+f"(d[32]), "+f"(d[33]), "+f"(d[34]), "+f"(d[35])
    : "r"(a[0]), "r"(a[1]), "r"(a[2]), "r"(a[3]), "l"(db));
}
__device__ __forceinline__ void wgmma16_acc(float* d, const uint32_t* a, uint64_t db) {
  asm volatile("wgmma.mma_async.sync.aligned.m64n16k16.f32.bf16.bf16 {%0, %1, %2, %3, %4, %5, %6, %7}, {%8, %9, %10, %11}, %12, 1, 1, 1, 0;"
    : "+f"(d[0]), "+f"(d[1]), "+f"(d[2]), "+f"(d[3]), "+f"(d[4]), "+f"(d[5]), "+f"(d[6]), "+f"(d[7])
    : "r"(a[0]), "r"(a[1]), "r"(a[2]), "r"(a[3]), "l"(db));
}
__device__ __forceinline__ void hmma(float (&d)[4], const uint32_t* a, uint32_t b0, uint32_t b1) {
  asm("mma.sync.aligned.m16n8k16.row.col.f32.bf16.bf16.f32 {%0, %1, %2, %3}, {%4, %5, %6, %7}, {%8, %9}, {%0, %1, %2, %3};"
    : "+f"(d[0]), "+f"(d[1]), "+f"(d[2]), "+f"(d[3]) : "r"(a[0]), "r"(a[1]), "r"(a[2]), "r"(a[3]), "r"(b0), "r"(b1));
}

__device__ __forceinline__ void hmma8(float (&d)[4], const uint32_t* a, uint32_t b0) {
  asm("mma.sync.aligned.m16n8k8.row.col.f32.bf16.bf16.f32 {%0, %1, %2, %3}, {%4, %5}, {%6}, {%0, %1, %2, %3};"
    : "+f"(d[0]), "+f"(d[1]), "+f"(d[2]), "+f"(d[3]) : "r"(a[0]), "r"(a[1]), "r"(b0));
}

template <bool FIRST> __device__ __forceinline__ void mma_tile(float (&d)[32], const uint32_t (&a)[16], uint64_t db) {
  WG_FENCE();
#pragma unroll
  for (int s = 0; s < 4; s++) {
    if (FIRST && s == 0) wgmma64_set<1>(d, &a[0], db); else wgmma64_acc<1>(d, &a[4 * s], db + s * 128);
  }
  WG_COMMIT();
}
__device__ __forceinline__ void mma_tile_reuse(float (&d)[32], const uint32_t (&a)[16], uint64_t db) {
  WG_FENCE();
  wgmma64_reuse<1>(d, &a[0], db, blockIdx.y);
#pragma unroll
  for (int s = 1; s < 4; s++) wgmma64_acc<1>(d, &a[4 * s], db + s * 128);
  WG_COMMIT();
}
template <int ROW> __device__ __forceinline__ void fold_step(float (&d)[32], const uint32_t (&mu)[4]) {
  wgmma64_acc<1>(d, mu, (uint64_t)((SM_BASE + SM_CS + ROW * 128) >> 4) | (uint64_t(1) << 16) | (uint64_t(1) << 62));
}
template <int ROW> __device__ __forceinline__ void mma_fold(float (&d)[32], const uint32_t (&mu)[4]) {
  WG_FENCE();
  fold_step<ROW>(d, mu);
  WG_COMMIT();
}
template <int ROW> __device__ __forceinline__ void mma_tile_fold(float (&d)[32], const uint32_t (&a)[16], uint64_t db, const uint32_t (&mu)[4]) {
  WG_FENCE();
#pragma unroll
  for (int s = 0; s < 4; s++) wgmma64_acc<1>(d, &a[4 * s], db + s * 128);
  fold_step<ROW>(d, mu);
  WG_COMMIT();
}
__device__ __forceinline__ void mma_add_half(float (&d)[32], const uint32_t (&a)[16]) {
  const uint64_t db = (uint64_t)((SM_BASE + SM_EYE) >> 4) | (uint64_t(8) << 16) | (uint64_t(8) << 32);
  WG_FENCE();
#pragma unroll
  for (int s = 0; s < 4; s++) wgmma16_acc(&d[8 * s], &a[4 * s], db);
  WG_COMMIT();
}
#define ACQUIRE(f) mbar_wait(SM_BASE + SM_FULL + ((f) % NSTAGE) * 8, ((f) / NSTAGE) & 1)
__device__ __forceinline__ void mbar_probe(uint32_t& ok, uint32_t bar, uint32_t parity) {
  asm volatile("{\n.reg .pred p;\nmbarrier.test_wait.parity.shared::cta.b64 p, [%1], %2;\nselp.u32 %0, %0, 0, p;\n}"
               : "+r"(ok) : "r"(bar), "r"(parity) : "memory");
}
template <int F, int N> __device__ __forceinline__ uint32_t probe_n() {
  static_assert(F % NSTAGE + N <= NSTAGE, "stages must not wrap");
  uint32_t ok = 1;
#pragma unroll
  for (int i = 0; i < N; i++) mbar_probe(ok, SM_BASE + SM_FULL + (F % NSTAGE + i) * 8, (F / NSTAGE) & 1);
  return ok;
}
template <int F, int N> __device__ __forceinline__ void settle_n(uint32_t ok) {
  if (__builtin_expect(!ok, 0)) {
#pragma unroll 1
    for (int i = 0; i < N; i++) mbar_wait(SM_BASE + SM_FULL + (F % NSTAGE + i) * 8, (F / NSTAGE) & 1);
  }
}
template <int F, int N> __device__ __forceinline__ void acquire_n() { settle_n<F, N>(probe_n<F, N>()); }
#define RELEASE(f0, f1) do { if (lane == 0) { _Pragma("unroll") for (int f_ = (f0); f_ <= (f1); f_++) mbar_arrive(SM_BASE + SM_EMPTY + (f_ % NSTAGE) * 8); } } while (0)
constexpr uint64_t RING = (uint64_t)(SM_BASE >> 4) | (uint64_t(1) << 16) | (uint64_t(64) << 32) | (uint64_t(1) << 62);
#define LO(f) (RING + ((f) % NSTAGE) * 1024)
#define HI(f) (RING + ((f) % NSTAGE) * 1024 + 512)

template <int C> __device__ __forceinline__ uint4* peer(uint4* p) {
  asm volatile("" : "+l"(p));
  return (uint4*)((uintptr_t)p ^ (C * X_SIZE * sizeof(uint4)));
}
__device__ __forceinline__ uint32_t clock_now() { uint32_t c; asm volatile("mov.u32 %0, %%clock;" : "=r"(c) :: "memory"); return c; }
__device__ __forceinline__ void publish(uint4* dst, uint32_t (&a)[16], uint32_t tag) {
#pragma unroll
  for (int s = 0; s < 4; s++) a[4 * s] = (a[4 * s] & ~1u) | tag;
  pin(a);
  SCHED();
#pragma unroll
  for (int s = 0; s < 4; s++) st_vec(dst + s * 128, a[4 * s], a[4 * s + 1], a[4 * s + 2], a[4 * s + 3]);
  SCHED();
}
__device__ __forceinline__ void fetch(const uint4* src, uint32_t (&a)[16]) {
#pragma unroll
  for (int s = 0; s < 4; s++) ld_vec(src + s * 128, a[4 * s], a[4 * s + 1], a[4 * s + 2], a[4 * s + 3]);
}
__device__ __forceinline__ uint32_t miss(const uint32_t (&a)[16], uint32_t tag) {
  return (a[0] ^ tag) | (a[4] ^ tag) | (a[8] ^ tag) | (a[12] ^ tag);
}
__device__ __forceinline__ bool stale(uint32_t v) { return __any_sync(0xffffffffu, here(v) & 1u); }
template <int N = 2> __device__ __forceinline__ void announce(Scratch* sc, bool leader) {
  asm volatile("{\n.reg .pred p;\nsetp.ne.u32 p, %1, 0;\n@p red.relaxed.gpu.global.add.u32 [%0], %2;\n}"
               :: "l"(sc->step[blockIdx.x]), "r"((uint32_t)leader), "n"(N) : "memory");
}
__device__ __forceinline__ uint32_t launch_index(const Scratch* sc) { return *(const volatile uint32_t*)sc->step[blockIdx.x] >> 4; }
__device__ __forceinline__ void stat_fetch(const Scratch* sc, uint32_t (&st)[4]) {
  const uint32_t th = here(threadIdx.x);
  ld_vec(&sc->x[(blockIdx.x & ~3u) + (th & 3)][X_ST + (th >> 2)], st[0], st[1], st[2], st[3]);
}
template <int C, int SLOT> __device__ __forceinline__ void gather_first(uint32_t (&A)[4][16], uint32_t (&st)[4], const Scratch* sc, uint4* xp, uint32_t tag, uint32_t sent) {
  if (TIMED) { while (clock_now() - sent < GD) {} } else bar_sync(BAR_GO, 160);
  fetch(peer<1>(xp) + SLOT, A[1]); fetch(peer<2>(xp) + SLOT, A[2]); fetch(peer<3>(xp) + SLOT, A[3]);
  if (SLOT == X_AG0) stat_fetch(sc, st);
  uint32_t spin = 0;
  while (__builtin_expect(stale(miss(A[1], tag) | miss(A[C], tag)), 0) && ++spin < SPIN_LIMIT) {
    fetch(peer<1>(xp) + SLOT, A[1]);
    if (C == 2) fetch(peer<2>(xp) + SLOT, A[2]);
  }
}
template <int C, int SLOT> __device__ __forceinline__ void gather_rest(uint32_t (&A)[4][16], uint4* xp, uint32_t tag) {
  SCHED();
  uint32_t spin = 0;
  while (__builtin_expect(stale(miss(A[C + 1], tag) | miss(A[3], tag)), 0) && ++spin < SPIN_LIMIT) {
    if (C == 1) fetch(peer<2>(xp) + SLOT, A[2]);
    fetch(peer<3>(xp) + SLOT, A[3]);
  }
}
__device__ __forceinline__ void pack_acc(const float (&d)[32], uint32_t (&a)[16]) {
#pragma unroll
  for (int i = 0; i < 16; i++) a[i] = pack2(d[2 * i], d[2 * i + 1]);
}
__device__ __forceinline__ void frag_store(uint32_t slot, const uint32_t (&a)[16]) {
#pragma unroll
  for (int s = 0; s < 4; s++) sts128(slot + s * 512, a[4 * s], a[4 * s + 1], a[4 * s + 2], a[4 * s + 3]);
}
__device__ __forceinline__ void tile_store(uint32_t maddr, const uint32_t (&a)[16]) {
#pragma unroll
  for (int s = 0; s < 4; s++) stsm4(maddr ^ (s << 5), &a[4 * s]);
}
__device__ __forceinline__ void tile_load(uint32_t maddr, uint32_t (&a)[16]) {
#pragma unroll
  for (int s = 0; s < 4; s++) ldsm4(maddr ^ (s << 5), &a[4 * s]);
}

__device__ __forceinline__ void res_load(uint32_t maddr, float (&d)[32]) {
  uint32_t a[16];
  tile_load(here(maddr) + 3 * TILE_BYTES, a);
#pragma unroll
  for (int i = 0; i < 16; i++) { d[2 * i] = bf_lo(a[i]); d[2 * i + 1] = bf_hi(a[i]); }
  pin(d);
}

struct RowAcc { float s[2][4], u[2][4], v[2][4]; };
__device__ __forceinline__ void row_sums(RowAcc& t, const uint32_t (&a)[16]) {
#pragma unroll
  for (int s = 0; s < 4; s++) hmma(t.s[s & 1], &a[4 * s], 0x3F803F80u, 0x3F803F80u);
}
__device__ __forceinline__ void row_gram(RowAcc& t, const uint32_t (&a)[16]) {
#pragma unroll
  for (int s = 0; s < 8; s++) {
    hmma8(t.u[s & 1], &a[2 * s], a[2 * s]);
    hmma8(t.v[s & 1], &a[2 * s], a[2 * s + 1]);
  }
}
__device__ __forceinline__ float2 row_squares(const RowAcc& t, bool odd) {
  return make_float2(odd ? t.u[0][1] + t.u[1][1] : t.u[0][0] + t.u[1][0], odd ? t.v[0][3] + t.v[1][3] : t.v[0][2] + t.v[1][2]);
}
__device__ __forceinline__ void stat_publish(const uint32_t (&a)[16], Scratch* sc, uint32_t th, uint32_t tag) {
  RowAcc t = {};
  row_sums(t, a);
  row_gram(t, a);
  const float2 q = row_squares(t, th & 4);
  if ((th & 3) == ((th >> 3) & 3))
    st_vec(&sc->x[blockIdx.x][X_ST + (th >> 2)], (__float_as_uint(t.s[0][0] + t.s[1][0]) & ~1u) | tag, __float_as_uint(q.x),
           __float_as_uint(t.s[0][2] + t.s[1][2]), __float_as_uint(q.y));
}
struct RowNorm { float m0, rs0, m1, rs1; };
__device__ __forceinline__ RowNorm row_norm(float s0, float q0, float s1, float q1, float scale) {
  RowNorm n;
  n.m0 = s0 * (1.f / DM); n.m1 = s1 * (1.f / DM);
  n.rs0 = scale * rsqrt_hw(fmaxf(fmaf(-n.m0, n.m0, q0 * (1.f / DM)), 0.f) + LN_EPS);
  n.rs1 = scale * rsqrt_hw(fmaxf(fmaf(-n.m1, n.m1, q1 * (1.f / DM)), 0.f) + LN_EPS);
  return n;
}
__device__ __forceinline__ RowNorm stat_finish(const Scratch* sc, uint32_t (&st)[4], uint32_t tag, float scale) {
  uint32_t spin = 0;
  while (__builtin_expect(stale(st[0] ^ tag), 0) && ++spin < SPIN_LIMIT) stat_fetch(sc, st);
  float f[4];
#pragma unroll
  for (int i = 0; i < 4; i++) {
    f[i] = __uint_as_float(st[i]);
    f[i] += __shfl_xor_sync(0xffffffffu, f[i], 1);
    f[i] += __shfl_xor_sync(0xffffffffu, f[i], 2);
  }
  return row_norm(f[0], f[1], f[2], f[3], scale);
}
__device__ __forceinline__ void mean_frag(uint32_t (&mu)[4], const RowNorm& n, bool sel) {
  const float a = sel ? -n.m0 : 0.f, c = sel ? -n.m1 : 0.f;
  mu[0] = pack2(a, a); mu[1] = pack2(c, c);
  const float al = a - bf_lo(mu[0]), cl = c - bf_lo(mu[1]);
  mu[2] = pack2(al, al); mu[3] = pack2(cl, cl);
  pin(mu);
}
__device__ __forceinline__ void centre(uint32_t (&a)[16], uint32_t m0, uint32_t m1) {
#pragma unroll
  for (int i = 0; i < 16; i++) asm("sub.rn.bf16x2 %0, %0, %1;" : "+r"(a[i]) : "r"((i & 1) ? m1 : m0));
  pin(a);
}
__device__ __forceinline__ void scale_pack(const float (&d)[32], uint32_t (&a)[16], float rs0, float rs1) {
#pragma unroll
  for (int i = 0; i < 16; i++) { const float rs = (i & 1) ? rs1 : rs0; a[i] = pack2(d[2 * i] * rs, d[2 * i + 1] * rs); }
}
template <int S> __device__ __forceinline__ void silu_seg(float (&acc)[4][32], float (&tn)[2][4], uint32_t (&H)[4][16], float rs0, float rs1) {
  if (S >= 2) {
    const float* h = &acc[(S - 2) >> 3][4 * ((S - 2) & 7)];
    const float* v = tn[S & 1];
    uint32_t* o = &H[(S - 2) >> 3][2 * ((S - 2) & 7)];
    o[0] = pack2(fmaf(h[0], v[0], h[0]), fmaf(h[1], v[1], h[1]));
    o[1] = pack2(fmaf(h[2], v[2], h[2]), fmaf(h[3], v[3], h[3]));
    asm volatile("" : "+r"(o[0]), "+r"(o[1]));
  }
  if (S >= 1 && S <= 32) {
#pragma unroll
    for (int k = 0; k < 4; k++) tn[(S - 1) & 1][k] = tanh_hw(acc[((S - 1) >> 3) & 3][4 * ((S - 1) & 7) + k]);
  }
  if (S < 32) {
    float* h = &acc[(S >> 3) & 3][4 * (S & 7)];
    h[0] *= rs0; h[1] *= rs0; h[2] *= rs1; h[3] *= rs1;
    asm volatile("" : "+f"(h[0]), "+f"(h[1]), "+f"(h[2]), "+f"(h[3]));
  }
  SCHED();
}
template <int S0, int S1> __device__ __forceinline__ void silu_segs(float (&acc)[4][32], float (&tn)[2][4], uint32_t (&H)[4][16], float rs0, float rs1) {
  silu_seg<S0>(acc, tn, H, rs0, rs1);
  if constexpr (S0 + 1 < S1) silu_segs<S0 + 1, S1>(acc, tn, H, rs0, rs1);
}
template <int HALF> __device__ __forceinline__ void send_half(uint4* dst, const float (&d)[32], uint32_t tag) {
  uint32_t o[8];
#pragma unroll
  for (int i = 0; i < 8; i++) o[i] = pack2(d[16 * HALF + 2 * i], d[16 * HALF + 2 * i + 1]);
  o[0] = (o[0] & ~1u) | tag; o[4] = (o[4] & ~1u) | tag;
  pin(o);
  SCHED();
  st_vec(dst + HALF * 256, o[0], o[1], o[2], o[3]);
  st_vec(dst + HALF * 256 + 128, o[4], o[5], o[6], o[7]);
  SCHED();
}
__device__ __forceinline__ void send_residual(uint32_t (&a)[16], Scratch* sc, uint4* xp, uint32_t maddr, uint32_t tag, uint32_t& sent) {
  const uint32_t exact[4] = {a[0], a[4], a[8], a[12]};
  publish(xp + X_AG0, a, tag);
  if (TIMED) sent = clock_now();
  const uint32_t th = here(threadIdx.x);
  stat_publish(a, sc, th, tag);
  tile_store(here(maddr) + 3 * TILE_BYTES, a);
  stsm4(SM_BASE + SM_STG + 3 * TILE_BYTES + (th >> 5) * 2048 + (th & 7) * 128 + ((((th >> 2) & 6) ^ (th & 7)) << 4), exact);
}
template <int F, int N> __device__ __forceinline__ void proj_residual(uint32_t (&A)[4][16], Scratch* sc, uint4* xp, uint32_t maddr,
                                                                      uint32_t tag, uint32_t& sent) {
  float acc[32];
  if (TIMED && F == F_PW2) sent = clock_now();
  uint32_t st[4];
  acquire_n<F, N>();
  if (F == F_PW2) acquire_n<0, 5>();
  res_load(maddr, acc);
  mma_tile<false>(acc, A[0], LO(F));
  gather_first<2, X_AG1>(A, st, sc, xp, tag, sent);
  announce(sc, threadIdx.x == 0);
  mma_tile<false>(acc, A[1], HI(F));
  mma_tile<false>(acc, A[2], LO(F + 1));
  gather_rest<2, X_AG1>(A, xp, tag);
  PROF_MARK0(F == F_WO ? 11 : 16);
  mma_tile<false>(acc, A[3], HI(F + 1));
  WG_WAIT(0); pin(acc);
  pack_acc(acc, A[0]);
  send_residual(A[0], sc, xp, maddr, tag, sent);
}

__device__ __forceinline__ uint64_t ring_desc(uint32_t lo) { return (RING & ~uint64_t(0xFFFFFFFFu)) | lo; }
__device__ __forceinline__ void qk_tile(float (&S)[32], const uint32_t (&Q)[16], uint32_t dk) {
  wgmma64_reuse<0>(S, &Q[0], ring_desc(dk), blockIdx.y);
#pragma unroll
  for (int s = 1; s < 4; s++) wgmma64_acc<0>(S, &Q[4 * s], ring_desc(dk + s * 2));
}
__device__ __forceinline__ void qk_shift(float (&S)[32], const uint32_t (&nm)[4]) { wgmma64_acc<0>(S, nm, (uint64_t)((SM_BASE + SM_ONE) >> 4)); }
constexpr uint32_t RING_K = (uint32_t)RING, V_STEP = 1u - (1u << 16);
constexpr uint32_t RING_V = (SM_BASE >> 4) | (((SM_STG + 2 * TILE_BYTES) >> 4) << 16);
__device__ __forceinline__ void pv_tile(float (&O)[36], const uint32_t (&P)[16], uint32_t dv, uint32_t pad) {
#pragma unroll
  for (int s = 0; s < 4; s++) wgmma72_acc(O, &P[4 * s], ring_desc(dv + s * 128 * V_STEP + (s < 2 ? 0 : (s - 1) * pad)));
}
__device__ __forceinline__ void attn_step(const float (&Sc)[32], float (&Sn)[32], uint32_t (&Pc)[16], uint32_t (&Pp)[16], float (&O)[36],
                                          const uint32_t (&Q)[16], const uint32_t (&nm)[4], uint32_t dk, uint32_t dv, bool next, bool prev) {
  if (next) {
    WG_FENCE();
    qk_tile(Sn, Q, dk);
    qk_shift(Sn, nm);
  }
  if (prev) {
    WG_FENCE();
    pv_tile(O, Pp, dv, 0);
  }
  WG_COMMIT();
  SCHED();
#pragma unroll
  for (int i = 0; i < 16; i++) Pc[i] = pack2(ex2_hw(Sc[2 * i]), ex2_hw(Sc[2 * i + 1]));
  pin(Pc);
  SCHED();
}
template <int R> __device__ __forceinline__ float tile_max(const float (&S)[32]) {
  float t[4];
#pragma unroll
  for (int j = 0; j < 4; j++) t[j] = fmaxf(fmaxf(S[8 * j + R], S[8 * j + R + 1]), fmaxf(S[8 * j + R + 4], S[8 * j + R + 5]));
  float n = fmaxf(fmaxf(t[0], t[1]), fmaxf(t[2], t[3]));
  n = fmaxf(n, __shfl_xor_sync(0xffffffffu, n, 1));
  return fmaxf(n, __shfl_xor_sync(0xffffffffu, n, 2));
}
__device__ __forceinline__ void attention_exact(float (&O)[36], const uint32_t (&Q)[16], const Scratch* sc, int bh, int lane, int half) {
  const char* kb = (const char*)&sc->kv[bh][0][0][0];
  const char* vb = (const char*)&sc->kv[bh][1][0][0];
  const int g = lane >> 2, q = lane & 3;
  float m0 = -INFINITY, m1 = -INFINITY, l0 = 0.f, l1 = 0.f;
  float o[4][4] = {};
#pragma unroll 1
  for (int k0 = 0; k0 < T_SEQ; k0 += 8) {
    float s[4] = {0.f, 0.f, 0.f, 0.f};
#pragma unroll
    for (int c = 0; c < 8; c++) hmma8(s, &Q[2 * c], __ldcg((const uint32_t*)(kb + (k0 + g) * 128 + ((c ^ g) << 4) + q * 4)));
    float n0 = fmaxf(s[0], s[1]), n1 = fmaxf(s[2], s[3]);
    n0 = fmaxf(n0, __shfl_xor_sync(0xffffffffu, n0, 1)); n1 = fmaxf(n1, __shfl_xor_sync(0xffffffffu, n1, 1));
    n0 = fmaxf(m0, fmaxf(n0, __shfl_xor_sync(0xffffffffu, n0, 2))); n1 = fmaxf(m1, fmaxf(n1, __shfl_xor_sync(0xffffffffu, n1, 2)));
    const float a0 = ex2_hw(m0 - n0), a1 = ex2_hw(m1 - n1);
    m0 = n0; m1 = n1;
    const uint32_t pp[2] = {pack2(ex2_hw(s[0] - n0), ex2_hw(s[1] - n0)), pack2(ex2_hw(s[2] - n1), ex2_hw(s[3] - n1))};
    l0 = fmaf(l0, a0, bf_lo(pp[0]) + bf_hi(pp[0])); l1 = fmaf(l1, a1, bf_lo(pp[1]) + bf_hi(pp[1]));
#pragma unroll
    for (int j = 0; j < 4; j++) {
      const int c = 4 * half + j;
      const uint32_t v0 = __ldcg((const uint16_t*)(vb + (k0 + 2 * q) * 128 + ((c ^ (2 * q)) << 4) + g * 2));
      const uint32_t v1 = __ldcg((const uint16_t*)(vb + (k0 + 2 * q + 1) * 128 + ((c ^ (2 * q + 1)) << 4) + g * 2));
      o[j][0] *= a0; o[j][1] *= a0; o[j][2] *= a1; o[j][3] *= a1;
      hmma8(o[j], pp, v0 | (v1 << 16));
    }
  }
  l0 += __shfl_xor_sync(0xffffffffu, l0, 1); l1 += __shfl_xor_sync(0xffffffffu, l1, 1);
  O[32] = l0 + __shfl_xor_sync(0xffffffffu, l0, 2); O[34] = l1 + __shfl_xor_sync(0xffffffffu, l1, 2);
#pragma unroll
  for (int i = 0; i < 16; i++) O[i] = o[i >> 2][i & 3];
}

__device__ __forceinline__ uint32_t fill_entry(int f, int r) {
  int m, x = r, y, dx = 0;
  if (f < F_QKV || f >= 48) {
    const int i = f & 15;
    m = f < F_QKV ? M_FF1A : M_FF2A;
    if (i < 8) { x = 4 * r + ((0xE2u >> i) & 1) * 2; y = r ^ ((0xE790u >> (2 * i)) & 3); dx = 1; }
    else { m++; x = r ^ (((i >> 1) - 3) & 3); y = 4 * r + 2 * (i & 1); }
  } else if (f < F_KV) {
    const int i = f - F_QKV;
    m = M_QKV;
    if (i == 1 || i >= 5) { y = r ^ (i == 1 ? 0 : 2); }
    else { x = 4 + r; y = r ^ (i ? i - 1 : 0); dx = 4; }
  } else if (f >= F_PW1 && f < F_PW2) {
    m = M_PW1; y = r ^ (f - F_PW1); dx = 4;
  } else {
    m = f < F_PW1 ? M_WO : M_PW2; y = r ^ ((f & 1) * 2);
  }
  return m | (x << 4) | (y << 8) | (dx << 16);
}
__device__ __forceinline__ void tma_fill(uint32_t st, const CUtensorMap* map, uint32_t x, uint32_t y, uint32_t x2, uint32_t y2) {
  asm volatile("{\n.reg .pred p;\nelect.sync _|p, 0xffffffff;\n"
               "@p mbarrier.arrive.expect_tx.shared::cta.b64 _, [%1], 16384;\n"
               "@p cp.async.bulk.tensor.2d.shared::cluster.global.mbarrier::complete_tx::bytes [%0], [%2, {%3, %4}], [%1];\n"
               "@p cp.async.bulk.tensor.2d.shared::cluster.global.mbarrier::complete_tx::bytes [%0 + 8192], [%2, {%5, %6}], [%1];\n}"
               :: "r"(SM_BASE + st * STAGE_BYTES), "r"(SM_BASE + SM_FULL + st * 8), "l"(map), "r"(x), "r"(y), "r"(x2), "r"(y2) : "memory");
}
template <int F0, int N> __device__ __forceinline__ void weight_fills(const Params& p, uint32_t entry) {
  uint32_t st = F0 % NSTAGE, parity = ((F0 / NSTAGE) & 1) ^ 1, e = __shfl_sync(0xffffffffu, entry, 0);
#pragma unroll 1
  for (int i = 1; i <= N; i++) {
    const uint32_t x = (e << 2) & 0x3C0, y = (e >> 2) & 0x3FC0, dx = (e >> 16) << 6;
    const CUtensorMap* map = &p.map[e & 15];
    e = __shfl_sync(0xffffffffu, entry, i);
    mbar_wait(SM_BASE + SM_EMPTY + st * 8, parity);
    tma_fill(st, map, x, y, x + dx, dx ? y : y ^ 64);
    if (++st == NSTAGE) { st = 0; parity ^= 1; }
  }
}
__device__ __forceinline__ uint32_t kv_poll(const uint32_t* flag, uint32_t prev) {
  uint32_t v;
  asm volatile("ld.relaxed.gpu.global.u32 %0, [%1];" : "=r"(v) : "l"(flag) : "memory");
  return __ballot_sync(0xffffffffu, v - 1 == prev);
}
__device__ __forceinline__ void kv_fills(const Scratch* sc, int bh, int kind, uint32_t prev, const uint32_t* flag, uint32_t ready) {
#pragma unroll 1
  for (int j = 0; j < 8; j++) {
    uint32_t spin = 0;
#pragma unroll 1
    while (((ready >> (2 * j)) & 3) != 3 && ++spin < SPIN_LIMIT) ready = kv_poll(flag, prev);
    const uint32_t st = (j < 6 ? 4 * (j >> 1) : 0) + (j & 1) + 2 * kind;
    mbar_wait(SM_BASE + SM_EMPTY + st * 8, j < 6);
    asm volatile("{\n.reg .pred p;\nelect.sync _|p, 0xffffffff;\n"
                 "@p mbarrier.arrive.expect_tx.shared::cta.b64 _, [%1], 16384;\n"
                 "@p cp.async.bulk.shared::cluster.global.mbarrier::complete_tx::bytes [%0], [%2], 16384, [%1];\n}"
                 :: "r"(SM_BASE + st * STAGE_BYTES), "r"(SM_BASE + SM_FULL + st * 8), "l"(sc->kv[bh][kind][2 * j]) : "memory");
    PROF_AT(256 + 512 + (10 + kind * 8 + j) * 4);
  }
}
__device__ __forceinline__ void reset_mailboxes(Scratch* sc, int half, int lane, uint32_t t_start) {
  while (clock_now() - t_start < TC) {}
#pragma unroll 1
  for (int i = half * 8; i < half * 9 + 8; i++) {
    const uint32_t t0 = clock_now();
    uint4* dst = &sc->x[blockIdx.x ^ (i < 12 ? (i >> 2) + 1 : 0)][i * 128 + lane];
#pragma unroll
    for (int k = 0; k < 4; k++) st_vec(dst + 32 * k, 0u, 0u, 0u, 0u);
    while (clock_now() - t0 < CLR_PACE) {}
  }
  bar_arrive(BAR_RST, 192);
  PROF_AT(256 + 512 + 28 * 4);
  asm volatile("fence.acq_rel.gpu;" ::: "memory");
  __syncwarp();
  announce<1>(sc, lane == 0);
  PROF_AT(256 + 512 + 2 * 4);
}
__device__ __forceinline__ void l2_prefetch(const void* p, uint32_t total, int b) {
  const uint32_t part = total / NCTA;
  asm volatile("cp.async.bulk.prefetch.L2.global [%0], %1;" :: "l"((const char*)p + (size_t)b * part), "r"(part) : "memory");
}

__global__ void __launch_bounds__(384, 1) conformer_kernel(Scratch* __restrict__ sc, __nv_bfloat16* __restrict__ out,
                                                           const __nv_bfloat16* __restrict__ dw, const __nv_bfloat16* __restrict__ xin,
                                                           const __nv_bfloat16* __restrict__ w_ff1a, const __grid_constant__ Params p) {
  extern __shared__ __align__(1024) uint8_t smem[];
  const int tid = threadIdx.x, lane = tid & 31;
  const uint32_t t_start = clock_now();
  const int b = blockIdx.x, r = b & 3, batch = b >> 6, t = (b >> 2) & 15;
  if ((uint32_t)__cvta_generic_to_shared(smem) != SM_BASE) return;
  PROF_AT(256 + (tid >> 7) * 256);
  PROF_TIME(30);
  const uint32_t crow = ((tid >> 1) & 48) + (lane >> 3);
  const uint32_t cdst = SM_BASE + crow * 128 + (((lane & 7) ^ (lane >> 3)) << 4);
  if (tid < 128) {
    const uint32_t g0 = batch * T_SEQ + t * 64 + crow, o = r * 128 + (lane & 7) * 16;
    const uint32_t lo = min(g0, 2 * T_SEQ - 5) * 512 + o, hi = min(g0 + 8, 2 * T_SEQ - 5) * 512 + o;
#pragma unroll
    for (int c = 0; c < 4; c++) {
#pragma unroll
      for (int i = 0; i < 4; i++)
        cp_async16((cdst ^ ((i & 1) << 6)) + SM_STG + (3 - c) * TILE_BYTES + i * 512, (const char*)xin + (((i & 2) ? hi : lo) ^ (c << 7)) + (i & 1) * 2048);
      asm volatile("cp.async.commit_group;" ::: "memory");
    }
  } else if (tid < 256) {
    const char* src = (const char*)w_ff1a + (64 * r + crow) * 2048 + r * 512 + (lane & 7) * 16;
#pragma unroll
    for (int c = 0; c < 4; c++) {
#pragma unroll
      for (int i = 0; i < 4; i++) cp_async16((cdst ^ ((i & 1) << 6)) + c * TILE_BYTES + i * 512, src + i * 8192 + c * 128);
      asm volatile("cp.async.commit_group;" ::: "memory");
    }
  }
  const int cw = __shfl_sync(0xffffffffu, tid >> 5, 0), wg = cw >> 2, w = cw & 3;

  if (wg == 2) {
    asm volatile("setmaxnreg.dec.sync.aligned.u32 40;");
    if (cw == 8) {
      if (lane == 0) {
        asm volatile("prefetch.tensormap [%0];" :: "l"(&p.map[M_FF1A]) : "memory");
#pragma unroll
        for (int i = 0; i < NSTAGE; i++) mbar_init(SM_BASE + SM_FULL + i * 8, 1);
        fence_async_smem();
      }
      __syncwarp();
      bar_arrive(0, 320);
      while (clock_now() - t_start < TF) {}
      PROF_MARK(9);
#pragma unroll
      for (int f = 2; f < 8; f++) {
        const uint32_t x = 256 * r + ((0xE2u >> f) & 1) * 128, y = (r ^ ((0xE790u >> (2 * f)) & 3)) * 64;
        tma_fill(f, &p.map[M_FF1A], x, y, x + 64, y);
      }
      PROF_MARK(1);
      uint32_t entry[2];
#pragma unroll 1
      for (int i = 0; i < 2; i++) { entry[1] = fill_entry(8 + i * 32 + lane, r); if (i == 0) entry[0] = entry[1]; }
      bar_sync(BAR_INIT, 64);
      weight_fills<8, F_KV - 8>(p, entry[0]);
      mbar_wait(SM_BASE + SM_EMPTY + (F_WO % NSTAGE) * 8, 1);
      weight_fills<F_WO, F_TOTAL - F_WO>(p, entry[1]);
    } else if (here(cw) != 11) {
      const int kind = w - 1;
      const uint32_t prev = launch_index(sc);
      if (kind == 0) {
        if (lane == 0) {
#pragma unroll
          for (int i = 0; i < NSTAGE; i++) mbar_init(SM_BASE + SM_EMPTY + i * 8, 4);
        }
        __syncwarp();
        bar_arrive(0, 320);
        bar_arrive(BAR_INIT, 64);
        if (lane == 0) {
          const uint32_t t0 = t_start;
          while (clock_now() - t0 < PF0) {}
          while (clock_now() - t0 < PF1) {}
          asm volatile("prefetch.tensormap [%0];" :: "l"(&p.map[M_FF1B]) : "memory");
          l2_prefetch(p.w_ff1b, 1024 * 256 * 2, b);
          while (clock_now() - t0 < PF2) {}
          l2_prefetch(p.w_qkv, 256 * 768 * 2, b);
          l2_prefetch(p.w_pw1, 256 * 512 * 2, b);
          l2_prefetch(p.w_ff2a, 256 * 1024 * 2, b);
          while (clock_now() - t0 < PF3) {}
          l2_prefetch(p.w_o, 256 * 256 * 2, b);
          l2_prefetch(p.w_pw2, 256 * 256 * 2, b);
          l2_prefetch(p.w_ff2b, 1024 * 256 * 2, b);
#pragma unroll
          for (int i = M_QKV; i < M_COUNT; i++) asm volatile("prefetch.tensormap [%0];" :: "l"(&p.map[i]) : "memory");
        }
        __syncwarp();
      } else {
        reset_mailboxes(sc, 1, lane, t_start);
      }
      const uint32_t* flag = sc->flag[batch * 4 + r][kind * 16 + (lane & 15)];
      const uint32_t ready = kv_poll(flag, prev);
      if (kind == 0) bar_sync(BAR_K, 160); else bar_sync(BAR_V, 160);
      if (lane == 0) {
        asm volatile("cp.async.bulk.global.shared::cta.bulk_group [%0], [%1], %2;"
                     :: "l"(&sc->kv[batch * 4 + r][kind][t][0]), "r"(SM_BASE + SM_STG + kind * TILE_BYTES), "r"(TILE_BYTES) : "memory");
PROF_MARK(4 + kind * 2);
        asm volatile("cp.async.bulk.commit_group;\ncp.async.bulk.wait_group 0;" ::: "memory");
PROF_MARK(5 + kind * 2);
        asm volatile("st.relaxed.gpu.global.u32 [%0], %1;" :: "l"(sc->flag[batch * 4 + r][kind * 16 + t]), "r"(prev + 1) : "memory");
      }
      __syncwarp();
      kv_fills(sc, batch * 4 + r, kind, prev, flag, ready);
    } else {
      const uint32_t* watch = sc->step[(b & ~3) + (lane & 3)];
      uint32_t seen;
      asm volatile("ld.relaxed.gpu.global.u32 %0, [%1];" : "=r"(seen) : "l"(watch) : "memory");
      reset_mailboxes(sc, 0, lane, t_start);
      uint32_t want = seen & ~15u;
#pragma unroll 1
      for (int k = 0; k < (TIMED ? 1 : 8); k++) {
        want += 2;
        uint32_t spin = 0;
#pragma unroll 1
        while (__any_sync(0xffffffffu, (int)(seen - want) < 0) && ++spin < SPIN_LIMIT)
          asm volatile("ld.relaxed.gpu.global.u32 %0, [%1];" : "=r"(seen) : "l"(watch) : "memory");
        bar_arrive(BAR_GO, 160);
        PROF_MARK(32 + k);
      }
    }
  } else {
    asm volatile("setmaxnreg.inc.sync.aligned.u32 232;");
    const int q = lane & 3, th = tid & 127;
    constexpr uint32_t stg = SM_BASE + SM_STG;
    const uint32_t mrow = 16 * w + (lane & 15);
    const uint32_t maddr = stg + mrow * 128 + (((lane >> 4) ^ (lane & 7)) << 4);
    const uint32_t qslot = stg + 2 * TILE_BYTES + w * 2048 + lane * 16;
    uint4* const xp = &sc->x[b][th];
    const int nvalid = T_SEQ - t * 64, row0 = 16 * w + (lane >> 2);

    uint32_t A[4][16];
    uint32_t st[4], sent = 0;
    bar_sync(0, 320);
    if (wg == 0) {
      RowAcc ra = {};
      cp_async_wait(0);
      __syncwarp();
      PROF_MARK0(45);
#pragma unroll
      for (int c = 0; c < 4; c++) tile_load(maddr + (3 - c) * TILE_BYTES, A[c]);
      row_sums(ra, A[0]); row_gram(ra, A[0]); row_sums(ra, A[1]); row_gram(ra, A[1]);
      pin(ra.s[0]); pin(ra.s[1]); pin(ra.u[0]); pin(ra.u[1]); pin(ra.v[0]); pin(ra.v[1]);
      SCHED();
      row_sums(ra, A[2]); row_sums(ra, A[3]); row_gram(ra, A[2]); row_gram(ra, A[3]);
      const float m0 = (ra.s[0][0] + ra.s[1][0]) * (1.f / DM), m1 = (ra.s[0][2] + ra.s[1][2]) * (1.f / DM);
      st[0] = pack2(m0, m0); st[1] = pack2(m1, m1);
      centre(A[0], st[0], st[1]);
      const float2 sq = row_squares(ra, lane & 4);
      st[2] = __float_as_uint(fmaf(-m0, m0, sq.x * (1.f / DM))); st[3] = __float_as_uint(fmaf(-m1, m1, sq.y * (1.f / DM)));
    } else {
      if (th < 112) sts128(SM_BASE + SM_CS + th * 16, 0, 0, 0, 0);
      sts32(SM_BASE + SM_EYE + th * 4, th >= 96 ? 0x3F803F80u : ((th & 32) == 0 && (th & 3) == ((th >> 3) & 3)) ? (0x3F00u << ((th & 4) * 4)) : 0u);
#pragma unroll
      for (int i = 0; i < 2; i++) {
        cp_async_wait(2 - 2 * i);
        fence_async_smem();
        bar_sync(BAR_WG1, 128);
        if (th == 0) mbar_arrive(SM_BASE + SM_FULL + i * 8);
      }
      PROF_MARK(6);
      const uint32_t tag = ~launch_index(sc) & 1;
      mbar_wait(SM_BASE + SM_FULL + 4 * 8, 0);
      PROF_MARK(5);
      if (b < 72) {
        const __nv_bfloat16* wp; int ld, col;
        if (b < 24) { wp = p.w_qkv; ld = 768; col = b * 32; }
        else if (b < 40) { wp = p.w_pw1; ld = 512; col = (b - 24) * 32; }
        else { wp = p.w_ff2a; ld = 1024; col = (b - 40) * 32; }
        const uint4* src = (const uint4*)(wp + (size_t)(th >> 2) * ld + col + q * 8);
        float c[8] = {0.f, 0.f, 0.f, 0.f, 0.f, 0.f, 0.f, 0.f};
#pragma unroll 1
        for (int h = 0; h < 2; h++, src += 16 * ld) {
#pragma unroll
          for (int i = 0; i < 4; i++) {
            const uint4 v = __ldg(src + i * 4 * ld);
            c[0] += bf_lo(v.x); c[1] += bf_hi(v.x); c[2] += bf_lo(v.y); c[3] += bf_hi(v.y);
            c[4] += bf_lo(v.z); c[5] += bf_hi(v.z); c[6] += bf_lo(v.w); c[7] += bf_hi(v.w);
          }
        }
#pragma unroll 1
        for (int m = 4; m <= 16; m <<= 1)
#pragma unroll
          for (int k = 0; k < 8; k++) c[k] += __shfl_xor_sync(0xffffffffu, c[k], m);
        if (lane < 4) {
          const uint32_t a = SM_BASE + SM_CS + 1792 + w * 128 + lane * 32;
          sts128(a, __float_as_uint(c[0]), __float_as_uint(c[1]), __float_as_uint(c[2]), __float_as_uint(c[3]));
          sts128(a + 16, __float_as_uint(c[4]), __float_as_uint(c[5]), __float_as_uint(c[6]), __float_as_uint(c[7]));
        }
        bar_sync(BAR_WG1, 128);
        if (th < 8) {
          float o[4] = {0.f, 0.f, 0.f, 0.f};
#pragma unroll 1
          for (int k = 0; k < 4; k++) {
            uint32_t e[4];
            lds128(SM_BASE + SM_CS + 1792 + k * 128 + th * 16, e[0], e[1], e[2], e[3]);
#pragma unroll
            for (int i = 0; i < 4; i++) o[i] += __uint_as_float(e[i]);
          }
          st_vec(&sc->cs[b * 8 + th], (__float_as_uint(o[0]) & ~1u) | tag, __float_as_uint(o[1]), __float_as_uint(o[2]), __float_as_uint(o[3]));
        }
      }
      bar_sync(BAR_WG1, 128);
      PROF_MARK(2);
      if (th < 72) {
        const int j = th >> 3, i = (th & 7) * 2;
        int src;
        if (j < CS_PW1) src = 320 + 64 * r + 16 * j;
        else if (j < CS_QKV) src = 192 + (j - CS_PW1) * 64 + 16 * r;
        else src = ((j - CS_QKV + 1) % 3) * 64 + 16 * r;
        uint32_t e[8], hi[4], lo[4], spin = 0;
#pragma unroll 1
        do {
          ld_vec(&sc->cs[src + i], e[0], e[1], e[2], e[3]);
          ld_vec(&sc->cs[src + i + 1], e[4], e[5], e[6], e[7]);
        } while ((((e[0] ^ tag) | (e[4] ^ tag)) & 1u) && ++spin < SPIN_LIMIT);
        e[0] &= ~1u; e[4] &= ~1u;
#pragma unroll
        for (int k = 0; k < 4; k++) {
          const float c0 = __uint_as_float(e[2 * k]), c1 = __uint_as_float(e[2 * k + 1]);
          hi[k] = pack2(c0, c1);
          lo[k] = pack2(c0 - bf_lo(hi[k]), c1 - bf_hi(hi[k]));
        }
        const uint32_t a = SM_BASE + SM_CS + j * 256 + i * 8;
        sts128(a ^ ((a >> 3) & 0x70), hi[0], hi[1], hi[2], hi[3]);
        sts128((a + 128) ^ (((a + 128) >> 3) & 0x70), lo[0], lo[1], lo[2], lo[3]);
      }
      fence_async_smem();
      PROF_MARK(4);
      bar_arrive(BAR_CS, 256);
    }

#pragma unroll 1
    for (uint32_t pass = 0; pass < 2; pass++) {
      uint32_t Q[16];
      if (wg == 0) {
        float acc[4][32];
        uint32_t H[4][16];
        if (!pass) { PROF_MARK(47); ACQUIRE(0); }
        mma_tile<true>(acc[0], A[0], LO(0)); mma_tile<true>(acc[1], A[0], HI(0));
        if (!pass) ACQUIRE(1);
        mma_tile<true>(acc[2], A[0], LO(1)); mma_tile<true>(acc[3], A[0], HI(1));
        if (pass) {
          gather_first<1, X_AG0>(A, st, sc, xp, 1, sent);
        } else {
          centre(A[1], st[0], st[1]);
          acquire_n<2, 3>();
        }
        mma_tile<false>(acc[0], A[1], LO(2)); mma_tile<false>(acc[1], A[1], HI(2));
        if (pass) {
          gather_rest<1, X_AG0>(A, xp, 1);
          RELEASE(F_WO - 2 + NREL, F_PW2 + 1);
        } else {
          centre(A[2], st[0], st[1]); centre(A[3], st[0], st[1]);
        }
        PROF_MARK2(2, 18);
        mma_tile<false>(acc[0], A[2], LO(3)); mma_tile<false>(acc[0], A[3], LO(4));
        WG_WAIT(4);
        RELEASE(0, 1);
        uint32_t mu[4] = {0u, 0u, 0u, 0u};
        float rs0, rs1, tn[2][4];
        if (pass) {
          const RowNorm n = stat_finish(sc, st, 1, 0.5f);
          rs0 = n.rs0; rs1 = n.rs1;
          mean_frag(mu, n, q == 0);
        } else {
          const int src = (lane & 28) | (lane >> 3);
          rs0 = 0.5f * rsqrt_hw(fmaxf(__uint_as_float(__shfl_sync(0xffffffffu, st[2], src)), 0.f) + LN_EPS);
          rs1 = 0.5f * rsqrt_hw(fmaxf(__uint_as_float(__shfl_sync(0xffffffffu, st[3], src)), 0.f) + LN_EPS);
        }
        pin(mu);
        mma_fold<2 * CS_FF2>(acc[0], mu);
        mma_tile<false>(acc[1], A[2], HI(3));
#define SEGS(a, b) silu_segs<a, b>(acc, tn, H, rs0, rs1)
        WG_WAIT(1); pin(acc[0]);
        SEGS(0, 1);
        mma_tile_fold<2 * CS_FF2 + 2>(acc[1], A[3], HI(4), mu);
        SEGS(1, 3);
        uint32_t ok = probe_n<5, 1>();
        SEGS(3, 4);
        settle_n<5, 1>(ok);
        mma_tile<false>(acc[2], A[1], LO(5));
        SEGS(4, 5);
        ok = probe_n<6, 1>();
        SEGS(5, 6);
        settle_n<6, 1>(ok);
        mma_tile<false>(acc[2], A[2], LO(6));
        SEGS(6, 8);
        WG_WAIT(2); pin(acc[1]);
        RELEASE(2, 4);
        ok = probe_n<7, 1>();
        SEGS(8, 9);
        settle_n<7, 1>(ok);
        mma_tile_fold<2 * CS_FF2 + 4>(acc[2], A[3], LO(7), mu);
        SEGS(9, 12);
        mma_tile<false>(acc[3], A[1], HI(5));
        SEGS(12, 14);
        mma_tile<false>(acc[3], A[2], HI(6));
        SEGS(14, 16);
        WG_WAIT(2); pin(acc[2]);
        SEGS(16, 17);
        mma_tile_fold<2 * CS_FF2 + 6>(acc[3], A[3], HI(7), mu);
        SEGS(17, 19);
        ok = probe_n<8, 2>();
        SEGS(19, 20);
        settle_n<8, 2>(ok);
        mma_tile_reuse(acc[1], H[0], LO(8));
        SEGS(20, 22);
        mma_tile<false>(acc[1], H[1], HI(8));
        SEGS(22, 24);
        WG_WAIT(2); pin(acc[3]);
        RELEASE(5, 7);
        SEGS(24, 26);
        mma_tile<false>(acc[1], H[2], LO(9));
        SEGS(26, 27);
        ok = probe_n<10, 2>();
        SEGS(27, 28);
        settle_n<10, 2>(ok);
        mma_tile_reuse(acc[2], H[0], LO(10));
        SEGS(28, 31);
        mma_tile<false>(acc[2], H[1], HI(10));
        SEGS(31, 34);
#undef SEGS
        PROF_MARK2(3, 19);
        const uint32_t rtag = here(pass ^ 1);
        const uint4* rs_in = xp + X_RS;
        mma_tile<false>(acc[1], H[3], HI(9));
        mma_tile<false>(acc[2], H[2], LO(11));
        ok = probe_n<12, 2>();
        uint4* rs_out = peer<1>(xp) + X_RS;
        mma_tile<false>(acc[2], H[3], HI(11));
        settle_n<12, 2>(ok);
        if (!pass) bar_sync(BAR_RST, 192);
        WG_WAIT(2); pin(acc[1]);
        RELEASE(8, 9);
        send_half<0>(rs_out, acc[1], rtag);
        mma_tile_reuse(acc[3], H[0], LO(12));
        SCHED();
        send_half<1>(rs_out, acc[1], rtag);
        mma_tile<false>(acc[3], H[1], HI(12));
        rs_out = peer<2>(xp) + X_RS + 512;
        WG_WAIT(2); pin(acc[2]);
        send_half<0>(rs_out, acc[2], rtag);
        mma_tile<false>(acc[3], H[2], LO(13));
        SCHED();
        ok = probe_n<14, 2>();
        send_half<1>(rs_out, acc[2], rtag);
        mma_tile<false>(acc[3], H[3], HI(13));
        settle_n<14, 2>(ok);
        mma_tile_reuse(acc[1], H[0], LO(14));
        rs_out = peer<3>(xp) + X_RS + 1024;
        if (!pass) bar_sync(BAR_GO, 160);
        announce(sc, tid == 0);
        fetch(rs_in, A[1]);
        SCHED();
        mma_tile<false>(acc[1], H[1], HI(14));
        WG_WAIT(2); pin(acc[3]);
        send_half<0>(rs_out, acc[3], rtag);
        send_half<1>(rs_out, acc[3], rtag);
        if (TIMED) sent = clock_now();
        mma_tile<false>(acc[1], H[2], LO(15)); mma_tile<false>(acc[1], H[3], HI(15));
        SCHED();
        fetch(rs_in + 512, A[2]);
        SCHED();
        res_load(maddr, acc[2]);
        if (TIMED) { while (clock_now() - sent < RD) {} } else bar_sync(BAR_GO, 160);
        fetch(rs_in + 1024, A[3]);
        if (!pass) acquire_n<F_QKV, 3>();
        {
          uint32_t spin = 0;
          while (__builtin_expect(stale(miss(A[1], rtag) | miss(A[2], rtag) | miss(A[3], rtag)), 0) && ++spin < SPIN_LIMIT) {
            if (stale(miss(A[1], rtag) | miss(A[2], rtag))) { fetch(rs_in, A[1]); fetch(rs_in + 512, A[2]); }
            fetch(rs_in + 1024, A[3]);
          }
        }
        announce(sc, tid == 0 && !pass);
        mma_add_half(acc[2], A[1]);
        mma_add_half(acc[2], A[2]);
        mma_add_half(acc[2], A[3]);
        PROF_MARK2(4, 20);
        WG_WAIT(0); pin(acc[2]); pin(acc[1]);
#pragma unroll
        for (int i = 0; i < 16; i++) A[0][i] = pack2(fmaf(acc[1][2 * i], 0.5f, acc[2][2 * i]), fmaf(acc[1][2 * i + 1], 0.5f, acc[2][2 * i + 1]));
        if (pass) {
          PROF_MARK(21);
          stat_publish(A[0], sc, here(th), 0);
          stat_fetch(sc, st);
          const RowNorm fn = stat_finish(sc, st, 0, 1.f);
          const float nm0 = -fn.m0 * fn.rs0, nm1 = -fn.m1 * fn.rs1;
#pragma unroll
          for (int i = 0; i < 16; i++) {
            const float rs = (i & 1) ? fn.rs1 : fn.rs0, nm = (i & 1) ? nm1 : nm0;
            A[0][i] = pack2(fmaf(bf_lo(A[0][i]), rs, nm), fmaf(bf_hi(A[0][i]), rs, nm));
          }
          tile_store(here(maddr), A[0]);
          __syncwarp();
          const int row = 16 * w + (lane >> 3);
          uint4* dst = (uint4*)(out + ((size_t)batch * T_SEQ + t * 64 + row) * DM + 64 * r) + (lane & 7);
          const uint32_t src = stg + row * 128 + (((lane & 7) ^ (lane >> 3)) << 4);
#pragma unroll
          for (int i = 0; i < 4; i++) {
            uint4 v;
            lds128((src ^ ((i & 1) << 6)) + i * 512, v.x, v.y, v.z, v.w);
            if (row + 4 * i < nvalid) dst[i * 4 * (DM / 8)] = v;
          }
          PROF_MARK(22);
          PROF_TIME(31);
          break;
        }
        send_residual(A[0], sc, xp, maddr, 1, sent);
        PROF_MARK(5);
        mma_tile<true>(acc[0], A[0], LO(F_QKV)); mma_tile<true>(acc[1], A[0], HI(F_QKV));
        mma_tile<true>(acc[2], A[0], LO(F_QKV + 1));
        gather_first<1, X_AG0>(A, st, sc, xp, 1, sent);
        mma_tile<false>(acc[0], A[1], LO(F_QKV + 2)); mma_tile<false>(acc[1], A[1], HI(F_QKV + 2));
        acquire_n<F_QKV + 3, 3>();
        bar_sync(BAR_CS, 256);
        gather_rest<1, X_AG0>(A, xp, 1);
        PROF_MARK(6);
        mma_tile<false>(acc[0], A[2], LO(F_QKV + 3)); mma_tile<false>(acc[0], A[3], LO(F_QKV + 4));
        SCHED();
        {
          const RowNorm n = stat_finish(sc, st, 1, 1.f);
          rs0 = row0 < nvalid ? n.rs0 : 0.f; rs1 = row0 + 8 < nvalid ? n.rs1 : 0.f;
          mean_frag(mu, n, q == 3);
        }
        mma_fold<2 * CS_QKV - 6>(acc[0], mu);
        RELEASE(10, 15);
        WG_WAIT(0); pin(acc[0]);
        scale_pack(acc[0], Q, rs0, rs1);
        tile_store(here(maddr), Q);
        SCHED();
        mma_tile<false>(acc[1], A[2], HI(F_QKV + 3));
        fence_async_smem();
        bar_arrive(BAR_K, 160);
        mma_tile_fold<2 * CS_QKV - 4>(acc[1], A[3], HI(F_QKV + 4), mu);
        mma_tile<false>(acc[2], A[1], HI(F_QKV + 1)); mma_tile<false>(acc[2], A[2], LO(F_QKV + 5));
        WG_WAIT(2); pin(acc[1]);
        scale_pack(acc[1], Q, rs0, rs1);
        tile_store(here(maddr) + TILE_BYTES, Q);
        fence_async_smem();
        bar_arrive(BAR_V, 160);
        mma_tile_fold<2 * CS_QKV - 2>(acc[2], A[3], HI(F_QKV + 5), mu);
        WG_WAIT(0); pin(acc[2]);
        scale_pack(acc[2], Q, rs0 * SM_SCALE_LOG2, rs1 * SM_SCALE_LOG2);
        frag_store(here(qslot), Q);
        bar_arrive(BAR_Q, 256);
        RELEASE(F_QKV, F_QKV + 5);
      } else {
        bar_sync(BAR_Q, 256);
#pragma unroll
        for (int s = 0; s < 4; s++) lds128(qslot + s * 512, Q[4 * s], Q[4 * s + 1], Q[4 * s + 2], Q[4 * s + 3]);
        if (w < 2) {
          const uint32_t v = w ? 0u : 0x3F803F80u;
#pragma unroll
          for (int s = 0; s < 4; s++) sts128(qslot + s * 512, v, v, v, v);
          fence_async_smem();
        }
      }
      bar_sync(BAR_ATT, 256);
      PROF_MARK(7);

      const int dir = cw == 0 ? -1 : 1;
      uint32_t tap[15];
      {
        const uint32_t* dwp = (const uint32_t*)(dw + 64 * r) + lane + 7 * (DM / 2);
#pragma unroll
        for (int k = 0; k < 15; k++) tap[k] = __ldg(dwp + dir * (k - 7) * (DM / 2));
      }

      float O[36];
      {
        float S[2][32];
        uint32_t P[2][16], nm[4];
#pragma unroll
        for (int i = 0; i < 32; i++) { S[0][i] = 0.f; S[1][i] = 0.f; }
        pin(Q); pin(S[0]);
        WG_FENCE();
        qk_tile(S[0], Q, RING_K + (SM_STG >> 4));
        WG_COMMIT();
#pragma unroll
        for (int i = 0; i < 36; i++) O[i] = 0.f;
#pragma unroll
        for (int i = 0; i < 16; i++) P[1][i] = 0u;
        WG_WAIT(0); pin(S[0]);
        const float m0 = tile_max<0>(S[0]), m1 = tile_max<2>(S[0]);
        nm[0] = pack2(q ? 0.f : -m0, 0.f); nm[1] = pack2(q ? 0.f : -m1, 0.f); nm[2] = 0u; nm[3] = 0u;
#pragma unroll
        for (int k = 0; k < 15; k++) asm("mul.rn.bf16x2 %0, %0, %1;" : "+r"(tap[k]) : "r"(0x3F003F00u));
        pin(nm); pin(O); pin(P[1]); pin(tap);
        uint32_t sk = wg, sv = F_SPARE % NSTAGE + wg;
        mbar_wait(SM_BASE + SM_FULL + sv * 8, 1);
        mbar_wait(SM_BASE + SM_FULL + sk * 8, 0);
        if (wg == 1) bar_sync(BAR_ATT, 256);
        PROF_MARK(8);
        WG_FENCE();
        qk_tile(S[0], Q, RING_K + sk * 1024);
        qk_shift(S[0], nm);
        WG_COMMIT();
        WG_WAIT(0); pin(S[0]); pin(S[1]);
        if (wg == 0) bar_arrive(BAR_ATT, 256);
#pragma unroll 1
        for (int it = 0; it < 4; it++) {
          const uint32_t sn = it >= 2 ? wg : sk + 4;
          uint32_t ok = 1;
          mbar_probe(ok, SM_BASE + SM_FULL + sn * 8, it >= 2);
          mbar_probe(ok, SM_BASE + SM_FULL + (sk + 2) * 8, it == 3);
          attn_step(S[0], S[1], P[0], P[1], O, Q, nm, RING_K + sk * 1024 + 512, RING_V + (sv * 1024 + 512) * V_STEP, true, it > 0);
          PROF_MARK(24 + it * 3);
          if (__builtin_expect(!ok, 0)) {
            mbar_wait(SM_BASE + SM_FULL + sn * 8, it >= 2);
            mbar_wait(SM_BASE + SM_FULL + (sk + 2) * 8, it == 3);
          }
          WG_WAIT(0); pin(O); pin(S[1]); pin(P[1]);
          asm volatile("{\n.reg .pred p;\nsetp.eq.u32 p, %2, 0;\n@p mbarrier.arrive.shared::cta.b64 _, [%0];\n@p mbarrier.arrive.shared::cta.b64 _, [%1];\n}"
                       :: "r"(SM_BASE + SM_EMPTY + sk * 8), "r"(SM_BASE + SM_EMPTY + sv * 8), "r"(lane) : "memory");
          PROF_MARK(25 + it * 3);
          sv = sk + 2; sk = sn;
          attn_step(S[1], S[0], P[1], P[0], O, Q, nm, RING_K + sk * 1024, RING_V + (sv * 1024) * V_STEP, it < 3, true);
          WG_WAIT(0); pin(O); pin(S[0]); pin(P[0]);
          PROF_MARK(26 + it * 3);
        }
        WG_FENCE();
        pv_tile(O, P[1], RING_V + (sv * 1024 + 512) * V_STEP, wg << 22);
        WG_COMMIT();
        announce<1>(sc, th == 0);
        WG_WAIT(0); pin(O);
      }
      PROF_MARK(9);

      {
        const uint32_t mo = stg + here(th) * 16;
        sts64(mo + 5 * 4096 + wg * 8, __float_as_uint(O[32]), __float_as_uint(O[34]));
        if (wg == 0) {
#pragma unroll
          for (int i = 4; i < 8; i++)
            sts128(mo + i * 2048, __float_as_uint(O[4 * i]), __float_as_uint(O[4 * i + 1]), __float_as_uint(O[4 * i + 2]), __float_as_uint(O[4 * i + 3]));
        } else {
#pragma unroll
          for (int i = 0; i < 4; i++)
            sts128(mo + i * 2048, __float_as_uint(O[4 * i]), __float_as_uint(O[4 * i + 1]), __float_as_uint(O[4 * i + 2]), __float_as_uint(O[4 * i + 3]));
#pragma unroll
          for (int i = 0; i < 16; i++) O[i] = O[16 + i];
        }
        bar_sync(BAR_MERGE, 256);
        uint32_t e[4];
        lds128(mo + 5 * 4096, e[0], e[1], e[2], e[3]);
        O[32] = __uint_as_float(e[0]) + __uint_as_float(e[2]); O[34] = __uint_as_float(e[1]) + __uint_as_float(e[3]);
#pragma unroll
        for (int i = 0; i < 4; i++) {
          lds128(mo + wg * TILE_BYTES + i * 2048, e[0], e[1], e[2], e[3]);
#pragma unroll
          for (int k = 0; k < 4; k++) O[4 * i + k] += __uint_as_float(e[k]);
        }
        const bool safe = O[32] > 0x1p-60f && O[32] < 0x1p60f && O[34] > 0x1p-60f && O[34] < 0x1p60f;
        if (__builtin_expect(__any_sync(0xffffffffu, !safe), 0)) attention_exact(O, Q, sc, batch * 4 + r, lane, wg);
        const float i0 = rcp_hw(O[32]), i1 = rcp_hw(O[34]);
#pragma unroll
        for (int i = 0; i < 8; i++) { const float v = (i & 1) ? i1 : i0; A[0][i] = pack2(O[2 * i] * v, O[2 * i + 1] * v); }
        A[0][0] &= ~1u; A[0][4] &= ~1u;
        uint4* dst = xp + X_AG1 + wg * 256;
        SCHED();
        st_vec(dst, A[0][0], A[0][1], A[0][2], A[0][3]);
        st_vec(dst + 128, A[0][4], A[0][5], A[0][6], A[0][7]);
        SCHED();
        if (TIMED) sent = clock_now();
      }
      if (wg == 1) {
        const uint32_t mo = stg + TILE_BYTES + here(th) * 16;
        sts128(mo, A[0][0], A[0][1], A[0][2], A[0][3]);
        sts128(mo + 2048, A[0][4], A[0][5], A[0][6], A[0][7]);
        bar_arrive(BAR_HALF, 256);
      } else {
        PROF_MARK(10);
        const uint32_t mo = stg + TILE_BYTES + here(th) * 16;
        bar_sync(BAR_HALF, 256);
        lds128(mo, A[0][8], A[0][9], A[0][10], A[0][11]);
        lds128(mo + 2048, A[0][12], A[0][13], A[0][14], A[0][15]);
        proj_residual<F_WO, 6>(A, sc, xp, maddr, 0, sent);
        PROF_MARK(12);
        float acc[2][32];
        mma_tile<true>(acc[0], A[0], LO(F_PW1)); mma_tile<true>(acc[1], A[0], HI(F_PW1));
        gather_first<1, X_AG0>(A, st, sc, xp, 0, sent);
        mma_tile<false>(acc[1], A[1], HI(F_PW1 + 1)); mma_tile<false>(acc[0], A[1], LO(F_PW1 + 1));
        gather_rest<1, X_AG0>(A, xp, 0);
        RELEASE(F_WO - 2, F_WO + 1);
        PROF_MARK(13);
        mma_tile<false>(acc[1], A[2], HI(F_PW1 + 2)); mma_tile<false>(acc[1], A[3], HI(F_PW1 + 3));
        WG_WAIT(2);
        RELEASE(F_WO + 2, F_WO - 3 + NREL);
        SCHED();
        uint32_t mu[4];
        const RowNorm n = stat_finish(sc, st, 0, 0.5f);
        const float rs0 = row0 < nvalid ? n.rs0 : 0.f, rs1 = row0 + 8 < nvalid ? n.rs1 : 0.f;
        mean_frag(mu, n, q == 0);
        mma_fold<2 * CS_PW1 + 2>(acc[1], mu);
        mma_tile<false>(acc[0], A[2], LO(F_PW1 + 2));
        mma_tile_fold<2 * CS_PW1>(acc[0], A[3], LO(F_PW1 + 3), mu);
        WG_WAIT(2); pin(acc[1]);
#pragma unroll
        for (int i = 0; i < 32; i++) acc[1][i] = tanh_hw(acc[1][i] * ((i & 2) ? rs1 : rs0));
#pragma unroll
        for (int i = 0; i < 32; i++) { const float rs = (i & 2) ? rs1 : rs0; acc[1][i] = fmaf(acc[1][i], rs, rs); }
        pin(acc[1]);
        SCHED();
        WG_WAIT(0); pin(acc[0]);
#pragma unroll
        for (int i = 0; i < 16; i++) A[0][i] = pack2(acc[0][2 * i] * acc[1][2 * i], acc[0][2 * i + 1] * acc[1][2 * i + 1]);
        const uint32_t ga = stg + TILE_BYTES + here(mrow) * G_PITCH + (lane >> 4) * 16;
#pragma unroll
        for (int s = 0; s < 4; s++) stsm4(ga + s * 32, &A[0][4 * s]);
      }
      {
        const uint32_t gsrc = stg + TILE_BYTES + (8 * cw - 7) * G_PITCH + lane * 4;
        const bool edge = cw == 0 || cw == 7;
        const bool nbr = cw == 0 ? t > 0 : t < 15;
        uint4* const hdst = &sc->x[b + 4 * dir][X_HALO + (cw == 0 ? 96 : 0) + lane];
        uint32_t in[22];
        bar_sync(BAR_G, 256);
        PROF_MARK(14);
        if (cw == 0) {
#pragma unroll
          for (int i = 14; i >= 0; i--) in[i] = lds32(gsrc + (21 - i) * G_PITCH);
        } else {
#pragma unroll
          for (int i = 14; i >= 0; i--) in[i] = lds32(gsrc + i * G_PITCH);
        }
        if (edge) {
          if (nbr) {
            st_vec(hdst, HALO_TAG, in[14], in[13], in[12]);
            st_vec(hdst + 32, HALO_TAG, in[11], in[10], in[9]);
            st_vec(hdst + 64, HALO_TAG, in[8], 0u, 0u);
          }
        } else {
#pragma unroll
          for (int i = 15; i < 22; i++) in[i] = lds32(gsrc + i * G_PITCH);
        }
        if (cw == 0) PROF_MARK0(40);
        uint32_t cv[8];
#pragma unroll
        for (int i = 0; i < 15; i++)
#pragma unroll
          for (int o = 0; o < 8; o++) {
            if (i == o) asm("mul.rn.bf16x2 %0, %1, %2;" : "=r"(cv[o]) : "r"(in[i]), "r"(tap[0]));
            if (i > o) asm("fma.rn.bf16x2 %0, %1, %2, %0;" : "+r"(cv[o]) : "r"(in[i]), "r"(tap[i - o]));
          }
        pin(cv);
        if (cw == 0) PROF_MARK0(41);
        if (edge) {
#pragma unroll
          for (int i = 15; i < 22; i++) in[i] = 0u;
          if (nbr) {
            const uint4* src = &sc->x[b][X_HALO + (cw == 0 ? 0 : 96) + lane];
            uint32_t e0, e1, e2, u0, u1, spin = 0;
#pragma unroll 1
            do {
              ld_vec(src, e0, in[15], in[16], in[17]);
              ld_vec(src + 32, e1, in[18], in[19], in[20]);
              ld_vec(src + 64, e2, in[21], u0, u1);
            } while (__any_sync(0xffffffffu, ((e0 ^ HALO_TAG) | (e1 ^ HALO_TAG) | (e2 ^ HALO_TAG)) != 0) && ++spin < SPIN_LIMIT);
          }
          announce<1>(sc, lane == 0);
        }
#pragma unroll
        for (int i = 15; i < 22; i++)
#pragma unroll
          for (int o = 0; o < 8; o++)
            if (i - o <= 14) asm("fma.rn.bf16x2 %0, %1, %2, %0;" : "+r"(cv[o]) : "r"(in[i]), "r"(tap[i - o]));
        if (cw == 0) PROF_MARK0(42);
        if (cw == 7) PROF_MARK0(43);
        const uint32_t fl = cw == 0 ? 7 : 0;
        const uint32_t cdst = (stg + cw * 1024 + lane * 4) ^ (fl * 144);
#pragma unroll
        for (int o = 0; o < 8; o++) {
          const float a = bf_lo(cv[o]), c = bf_hi(cv[o]);
          sts32(cdst ^ (o * 144), pack2(fmaf(a, tanh_hw(a), a), fmaf(c, tanh_hw(c), c)));
        }
      }
      if (wg == 1) {
        bar_arrive(BAR_C, 256);
        break;
      }
      bar_sync(BAR_C, 256);
      tile_load(here(maddr), A[0]);
      PROF_MARK(15);
      publish(xp + X_AG1, A[0], 1);
      proj_residual<F_PW2, 2>(A, sc, xp, maddr, 1, sent);
      PROF_MARK(17);
    }
  }
}

typedef CUresult (*EncodeFn)(CUtensorMap*, CUtensorMapDataType, cuuint32_t, void*, const cuuint64_t*, const cuuint64_t*,
                             const cuuint32_t*, const cuuint32_t*, CUtensorMapInterleave, CUtensorMapSwizzle,
                             CUtensorMapL2promotion, CUtensorMapFloatOOBfill);

void make_map(EncodeFn fn, CUtensorMap* m, const void* w, int rows, int cols, CUtensorMapSwizzle swz) {
  const cuuint64_t dims[2] = {(cuuint64_t)cols, (cuuint64_t)rows}, strides[1] = {(cuuint64_t)cols * 2};
  const cuuint32_t box[2] = {64, 64}, es[2] = {1, 1};
  fn(m, CU_TENSOR_MAP_DATA_TYPE_BFLOAT16, 2, const_cast<void*>(w), dims, strides, box, es, CU_TENSOR_MAP_INTERLEAVE_NONE,
     swz, CU_TENSOR_MAP_L2_PROMOTION_L2_128B, CU_TENSOR_MAP_FLOAT_OOB_FILL_NONE);
}

}

extern "C" void kernel_launch(void* const* d_in, const int* in_sizes, int n_in, void* d_out, int out_size) {
  static EncodeFn fn = nullptr;
  static Scratch* sc = nullptr;
  if (!fn) {
    void* f = nullptr;
    cudaDriverEntryPointQueryResult st;
    cudaGetDriverEntryPoint("cuTensorMapEncodeTiled", &f, cudaEnableDefault, &st);
    fn = (EncodeFn)f;
    void* raw = nullptr;
    cudaGetSymbolAddress(&raw, g_scratch);
    sc = (Scratch*)(((uintptr_t)raw + X_ALIGN - 1) & ~(uintptr_t)(X_ALIGN - 1));
    cudaFuncSetAttribute(conformer_kernel, cudaFuncAttributeMaxDynamicSharedMemorySize, SM_TOTAL);
  }
  typedef const __nv_bfloat16* W;
  const CUtensorMapSwizzle S = CU_TENSOR_MAP_SWIZZLE_128B;
  Params p;
  make_map(fn, &p.map[M_FF1A], d_in[1], 256, 1024, S);
  make_map(fn, &p.map[M_FF1B], d_in[2], 1024, 256, S);
  make_map(fn, &p.map[M_QKV], d_in[3], 256, 768, S);
  make_map(fn, &p.map[M_WO], d_in[4], 256, 256, S);
  make_map(fn, &p.map[M_PW1], d_in[5], 256, 512, S);
  make_map(fn, &p.map[M_PW2], d_in[7], 256, 256, S);
  make_map(fn, &p.map[M_FF2A], d_in[8], 256, 1024, S);
  make_map(fn, &p.map[M_FF2B], d_in[9], 1024, 256, S);
  p.w_ff1b = (W)d_in[2]; p.w_qkv = (W)d_in[3]; p.w_o = (W)d_in[4]; p.w_pw1 = (W)d_in[5];
  p.w_pw2 = (W)d_in[7]; p.w_ff2a = (W)d_in[8]; p.w_ff2b = (W)d_in[9];

  cudaLaunchConfig_t cfg = {};
  cfg.gridDim = dim3(NCTA);
  cfg.blockDim = dim3(384);
  cfg.dynamicSmemBytes = SM_TOTAL;
  cfg.stream = cudaStreamPerThread;
  cudaLaunchAttribute at[1];
  at[0].id = cudaLaunchAttributeCooperative;
  at[0].val.cooperative = 1;
  cfg.attrs = at;
  cfg.numAttrs = 1;
  cudaLaunchKernelEx(&cfg, conformer_kernel, sc, (__nv_bfloat16*)d_out, (W)d_in[6], (W)d_in[0], (W)d_in[1], p);
}
```

```cpp
#include <cuda_runtime.h>
#include <cuda_bf16.h>
#include <cuda.h>
#include <stdint.h>

namespace {

constexpr int T_SEQ = 1000;
constexpr int DM = 256;
constexpr int NCTA = 128;
constexpr int NSTAGE = 12;
constexpr uint32_t STAGE_BYTES = 16384;
constexpr uint32_t TILE_BYTES = 8192;
constexpr uint32_t SM_BASE = 1024;
constexpr uint32_t SM_STG = NSTAGE * STAGE_BYTES;
constexpr uint32_t SM_FULL = SM_STG + 32768;
constexpr uint32_t SM_EMPTY = SM_FULL + 96;
constexpr uint32_t SM_EYE = SM_FULL + 256;
constexpr uint32_t SM_ONE = SM_FULL + 640;
constexpr uint32_t SM_CS = SM_FULL + 768;
constexpr uint32_t SM_TOTAL = SM_FULL + 3072;
constexpr int CS_FF2 = 0, CS_PW1 = 4, CS_QKV = 6;
constexpr uint32_t SPIN_LIMIT = 1u << 16;
constexpr float LN_EPS = 1e-5f;
constexpr float SM_SCALE_LOG2 = 0.125f * 1.4426950408889634f;
constexpr uint32_t G_PITCH = 144;
#define TIMED 0
#define GD 400
#define RD 550
#define NREL 5
#define PF0 1
#define TF 1
#define TC 1
#define PF1 1400
#define PF2 2000
#define PF3 3500
#define CLR_PACE 150

constexpr int F_QKV = 16, F_SPARE = 22, F_KV = 24, F_WO = 40, F_PW1 = 42, F_PW2 = 46, F_TOTAL = 64;
enum { M_FF1A, M_FF1B, M_QKV, M_WO, M_PW1, M_PW2, M_FF2A, M_FF2B, M_COUNT };
enum { BAR_K = 1, BAR_V, BAR_Q, BAR_MERGE, BAR_G, BAR_C, BAR_WG1, BAR_GO, BAR_CS, BAR_ATT, BAR_INIT, BAR_HALF, BAR_RST };

struct Params {
  CUtensorMap map[M_COUNT];
  const __nv_bfloat16 *w_ff1b, *w_qkv, *w_o, *w_pw1, *w_pw2, *w_ff2a, *w_ff2b;
};

constexpr int X_RS = 0, X_AG1 = X_RS, X_HALO = X_RS + 512, X_AG0 = 1536, X_ST = 2048, X_SIZE = 4096;
constexpr uint32_t HALO_TAG = 0xFFFF0001u;
struct Scratch {
  uint4 x[NCTA][X_SIZE];
  uint4 kv[8][2][16][512];
  uint4 cs[576];
  uint32_t flag[8][32][32];
  uint32_t step[NCTA][32];
};
constexpr size_t X_ALIGN = 4 * X_SIZE * sizeof(uint4);
__device__ uint8_t g_scratch[sizeof(Scratch) + X_ALIGN];
#define PROF_TIME(i)
#define PROF_MARK(i)
#define PROF_MARK2(i, j)
#define PROF_MARK0(i)
#define PROF_AT(a)

__device__ __forceinline__ void mbar_init(uint32_t bar, uint32_t cnt) {
  asm volatile("mbarrier.init.shared::cta.b64 [%0], %1;" :: "r"(bar), "r"(cnt) : "memory");
}
__device__ __forceinline__ void mbar_wait(uint32_t bar, uint32_t parity) {
  asm volatile("{\n.reg .pred p;\n.reg .u32 c;\nmov.u32 c, 0;\n"
               "WAIT_LOOP:\nmbarrier.try_wait.parity.shared::cta.b64 p, [%0], %1;\n@p bra WAIT_DONE;\n"
               "add.u32 c, c, 1;\nsetp.lt.u32 p, c, %2;\n@p bra WAIT_LOOP;\nWAIT_DONE:\n}"
               :: "r"(bar), "r"(parity), "n"(SPIN_LIMIT) : "memory");
}
__device__ __forceinline__ void mbar_arrive(uint32_t bar) {
  asm volatile("mbarrier.arrive.shared::cta.b64 _, [%0];" :: "r"(bar) : "memory");
}
#define bar_sync(id, n) asm volatile("bar.sync %0, %1;" :: "n"((int)(id)), "n"(n) : "memory")
#define bar_arrive(id, n) asm volatile("bar.arrive %0, %1;" :: "n"((int)(id)), "n"(n) : "memory")
__device__ __forceinline__ void fence_async_smem() { asm volatile("fence.proxy.async.shared::cta;" ::: "memory"); }

__device__ __forceinline__ void st_vec(uint4* p, uint32_t a, uint32_t b, uint32_t c, uint32_t d) {
  asm volatile("{\n.reg .b128 v;\n.reg .b64 lo, hi;\nmov.b64 lo, {%1, %2};\nmov.b64 hi, {%3, %4};\nmov.b128 v, {lo, hi};\n"
               "st.relaxed.gpu.global.b128 [%0], v;\n}" :: "l"(p), "r"(a), "r"(b), "r"(c), "r"(d) : "memory");
}
__device__ __forceinline__ void ld_vec(const uint4* p, uint32_t& a, uint32_t& b, uint32_t& c, uint32_t& d) {
  asm volatile("{\n.reg .b128 v;\n.reg .b64 lo, hi;\nld.relaxed.gpu.global.b128 v, [%4];\nmov.b128 {lo, hi}, v;\n"
               "mov.b64 {%0, %1}, lo;\nmov.b64 {%2, %3}, hi;\n}" : "=r"(a), "=r"(b), "=r"(c), "=r"(d) : "l"(p) : "memory");
}
__device__ __forceinline__ void sts128(uint32_t a, uint32_t x, uint32_t y, uint32_t z, uint32_t w) {
  asm volatile("st.shared.v4.u32 [%0], {%1, %2, %3, %4};" :: "r"(a), "r"(x), "r"(y), "r"(z), "r"(w) : "memory");
}
__device__ __forceinline__ void lds128(uint32_t a, uint32_t& x, uint32_t& y, uint32_t& z, uint32_t& w) {
  asm volatile("ld.shared.v4.u32 {%0, %1, %2, %3}, [%4];" : "=r"(x), "=r"(y), "=r"(z), "=r"(w) : "r"(a) : "memory");
}
__device__ __forceinline__ uint32_t lds32(uint32_t a) {
  uint32_t x; asm volatile("ld.shared.u32 %0, [%1];" : "=r"(x) : "r"(a) : "memory"); return x;
}
__device__ __forceinline__ void sts32(uint32_t a, uint32_t x) { asm volatile("st.shared.u32 [%0], %1;" :: "r"(a), "r"(x) : "memory"); }
__device__ __forceinline__ void sts64(uint32_t a, uint32_t x, uint32_t y) {
  asm volatile("st.shared.v2.u32 [%0], {%1, %2};" :: "r"(a), "r"(x), "r"(y) : "memory");
}
__device__ __forceinline__ void stsm4(uint32_t a, const uint32_t* r) {
  asm volatile("stmatrix.sync.aligned.m8n8.x4.shared.b16 [%0], {%1, %2, %3, %4};" :: "r"(a), "r"(r[0]), "r"(r[1]), "r"(r[2]), "r"(r[3]) : "memory");
}
__device__ __forceinline__ void ldsm4(uint32_t a, uint32_t* r) {
  asm volatile("ldmatrix.sync.aligned.m8n8.x4.shared.b16 {%0, %1, %2, %3}, [%4];" : "=r"(r[0]), "=r"(r[1]), "=r"(r[2]), "=r"(r[3]) : "r"(a) : "memory");
}
__device__ __forceinline__ uint32_t pack2(float lo, float hi) {
  uint32_t r; asm("cvt.rn.bf16x2.f32 %0, %1, %2;" : "=r"(r) : "f"(hi), "f"(lo)); return r;
}
__device__ __forceinline__ float bf_lo(uint32_t w) { return __uint_as_float(w << 16); }
__device__ __forceinline__ float bf_hi(uint32_t w) { return __uint_as_float(w & 0xffff0000u); }
__device__ __forceinline__ float tanh_hw(float x) { float y; asm volatile("tanh.approx.f32 %0, %1;" : "=f"(y) : "f"(x)); return y; }
__device__ __forceinline__ float rcp_hw(float x) { float y; asm("rcp.approx.ftz.f32 %0, %1;" : "=f"(y) : "f"(x)); return y; }
__device__ __forceinline__ float rsqrt_hw(float x) { float y; asm("rsqrt.approx.ftz.f32 %0, %1;" : "=f"(y) : "f"(x)); return y; }
__device__ __forceinline__ float ex2_hw(float x) { float y; asm("ex2.approx.ftz.f32 %0, %1;" : "=f"(y) : "f"(x)); return y; }

__device__ __forceinline__ uint32_t here(uint32_t v) { asm volatile("" : "+r"(v)); return v; }

#define SCHED() asm volatile("pmevent 1;" ::: "memory")
__device__ __forceinline__ void cp_async16(uint32_t dst, const void* src) {
  asm volatile("cp.async.cg.shared.global [%0], [%1], 16;" :: "r"(dst), "l"(src) : "memory");
}
__device__ __forceinline__ void cp_async_wait(int n) {
  if (n == 0) asm volatile("cp.async.wait_group 0;" ::: "memory");
  if (n == 1) asm volatile("cp.async.wait_group 1;" ::: "memory");
  if (n == 2) asm volatile("cp.async.wait_group 2;" ::: "memory");
  if (n == 3) asm volatile("cp.async.wait_group 3;" ::: "memory");
}
#define WG_FENCE() asm volatile("wgmma.fence.sync.aligned;" ::: "memory")
#define WG_COMMIT() asm volatile("wgmma.commit_group.sync.aligned;" ::: "memory")
#define WG_WAIT(n) asm volatile("wgmma.wait_group.sync.aligned %0;" :: "n"(n) : "memory")

template <int N> __device__ __forceinline__ void pin(float (&d)[N]) {
#pragma unroll
  for (int i = 0; i < N; i++) asm volatile("" : "+f"(d[i]) :: "memory");
}
template <int N> __device__ __forceinline__ void pin(uint32_t (&d)[N]) {
#pragma unroll
  for (int i = 0; i < N; i++) asm volatile("" : "+r"(d[i]) :: "memory");
}

#define WG_D32 "{%0, %1, %2, %3, %4, %5, %6, %7, %8, %9, %10, %11, %12, %13, %14, %15, %16, %17, %18, %19, %20, %21, %22, %23, %24, %25, %26, %27, %28, %29, %30, %31}"
template <int TB> __device__ __forceinline__ void wgmma64_acc(float (&d)[32], const uint32_t* a, uint64_t db) {
  asm volatile("wgmma.mma_async.sync.aligned.m64n64k16.f32.bf16.bf16 " WG_D32 ", {%32, %33, %34, %35}, %36, 1, 1, 1, %37;"
    : "+f"(d[0]), "+f"(d[1]), "+f"(d[2]), "+f"(d[3]), "+f"(d[4]), "+f"(d[5]), "+f"(d[6]), "+f"(d[7]),
      "+f"(d[8]), "+f"(d[9]), "+f"(d[10]), "+f"(d[11]), "+f"(d[12]), "+f"(d[13]), "+f"(d[14]), "+f"(d[15]),
      "+f"(d[16]), "+f"(d[17]), "+f"(d[18]), "+f"(d[19]), "+f"(d[20]), "+f"(d[21]), "+f"(d[22]), "+f"(d[23]),
      "+f"(d[24]), "+f"(d[25]), "+f"(d[26]), "+f"(d[27]), "+f"(d[28]), "+f"(d[29]), "+f"(d[30]), "+f"(d[31])
    : "r"(a[0]), "r"(a[1]), "r"(a[2]), "r"(a[3]), "l"(db), "n"(TB));
}
template <int TB> __device__ __forceinline__ void wgmma64_reuse(float (&d)[32], const uint32_t* a, uint64_t db, uint32_t zero) {
  asm volatile("{\n.reg .pred p;\nsetp.ne.u32 p, %37, 0;\nwgmma.mma_async.sync.aligned.m64n64k16.f32.bf16.bf16 " WG_D32 ", {%32, %33, %34, %35}, %36, p, 1, 1, %38;\n}"
    : "+f"(d[0]), "+f"(d[1]), "+f"(d[2]), "+f"(d[3]), "+f"(d[4]), "+f"(d[5]), "+f"(d[6]), "+f"(d[7]),
      "+f"(d[8]), "+f"(d[9]), "+f"(d[10]), "+f"(d[11]), "+f"(d[12]), "+f"(d[13]), "+f"(d[14]), "+f"(d[15]),
      "+f"(d[16]), "+f"(d[17]), "+f"(d[18]), "+f"(d[19]), "+f"(d[20]), "+f"(d[21]), "+f"(d[22]), "+f"(d[23]),
      "+f"(d[24]), "+f"(d[25]), "+f"(d[26]), "+f"(d[27]), "+f"(d[28]), "+f"(d[29]), "+f"(d[30]), "+f"(d[31])
    : "r"(a[0]), "r"(a[1]), "r"(a[2]), "r"(a[3]), "l"(db), "r"(zero), "n"(TB));
}
template <int TB> __device__ __forceinline__ void wgmma64_set(float (&d)[32], const uint32_t* a, uint64_t db) {
  asm volatile("wgmma.mma_async.sync.aligned.m64n64k16.f32.bf16.bf16 " WG_D32 ", {%32, %33, %34, %35}, %36, 0, 1, 1, %37;"
    : "=f"(d[0]), "=f"(d[1]), "=f"(d[2]), "=f"(d[3]), "=f"(d[4]), "=f"(d[5]), "=f"(d[6]), "=f"(d[7]),
      "=f"(d[8]), "=f"(d[9]), "=f"(d[10]), "=f"(d[11]), "=f"(d[12]), "=f"(d[13]), "=f"(d[14]), "=f"(d[15]),
      "=f"(d[16]), "=f"(d[17]), "=f"(d[18]), "=f"(d[19]), "=f"(d[20]), "=f"(d[21]), "=f"(d[22]), "=f"(d[23]),
      "=f"(d[24]), "=f"(d[25]), "=f"(d[26]), "=f"(d[27]), "=f"(d[28]), "=f"(d[29]), "=f"(d[30]), "=f"(d[31])
    : "r"(a[0]), "r"(a[1]), "r"(a[2]), "r"(a[3]), "l"(db), "n"(TB));
}

__device__ __forceinline__ void wgmma72_acc(float (&d)[36], const uint32_t* a, uint64_t db) {
  asm volatile("wgmma.mma_async.sync.aligned.m64n72k16.f32.bf16.bf16 {%0, %1, %2, %3, %4, %5, %6, %7, %8, %9, %10, %11, %12, %13, %14, %15, %16, %17, %18, %19, %20, %21, %22, %23, %24, %25, %26, %27, %28, %29, %30, %31, %32, %33, %34, %35}, {%36, %37, %38, %39}, %40, 1, 1, 1, 1;"
    : "+f"(d[0]), "+f"(d[1]), "+f"(d[2]), "+f"(d[3]), "+f"(d[4]), "+f"(d[5]), "+f"(d[6]), "+f"(d[7]), "+f"(d[8]),
      "+f"(d[9]), "+f"(d[10]), "+f"(d[11]), "+f"(d[12]), "+f"(d[13]), "+f"(d[14]), "+f"(d[15]), "+f"(d[16]), "+f"(d[17]),
      "+f"(d[18]), "+f"(d[19]), "+f"(d[20]), "+f"(d[21]), "+f"(d[22]), "+f"(d[23]), "+f"(d[24]), "+f"(d[25]), "+f"(d[26]),
      "+f"(d[27]), "+f"(d[28]), "+f"(d[29]), "+f"(d[30]), "+f"(d[31]), "+f"(d[32]), "+f"(d[33]), "+f"(d[34]), "+f"(d[35])
    : "r"(a[0]), "r"(a[1]), "r"(a[2]), "r"(a[3]), "l"(db));
}
__device__ __forceinline__ void wgmma16_acc(float* d, const uint32_t* a, uint64_t db) {
  asm volatile("wgmma.mma_async.sync.aligned.m64n16k16.f32.bf16.bf16 {%0, %1, %2, %3, %4, %5, %6, %7}, {%8, %9, %10, %11}, %12, 1, 1, 1, 0;"
    : "+f"(d[0]), "+f"(d[1]), "+f"(d[2]), "+f"(d[3]), "+f"(d[4]), "+f"(d[5]), "+f"(d[6]), "+f"(d[7])
    : "r"(a[0]), "r"(a[1]), "r"(a[2]), "r"(a[3]), "l"(db));
}
__device__ __forceinline__ void hmma(float (&d)[4], const uint32_t* a, uint32_t b0, uint32_t b1) {
  asm("mma.sync.aligned.m16n8k16.row.col.f32.bf16.bf16.f32 {%0, %1, %2, %3}, {%4, %5, %6, %7}, {%8, %9}, {%0, %1, %2, %3};"
    : "+f"(d[0]), "+f"(d[1]), "+f"(d[2]), "+f"(d[3]) : "r"(a[0]), "r"(a[1]), "r"(a[2]), "r"(a[3]), "r"(b0), "r"(b1));
}

__device__ __forceinline__ void hmma8(float (&d)[4], const uint32_t* a, uint32_t b0) {
  asm("mma.sync.aligned.m16n8k8.row.col.f32.bf16.bf16.f32 {%0, %1, %2, %3}, {%4, %5}, {%6}, {%0, %1, %2, %3};"
    : "+f"(d[0]), "+f"(d[1]), "+f"(d[2]), "+f"(d[3]) : "r"(a[0]), "r"(a[1]), "r"(b0));
}

template <bool FIRST> __device__ __forceinline__ void mma_tile(float (&d)[32], const uint32_t (&a)[16], uint64_t db) {
  WG_FENCE();
#pragma unroll
  for (int s = 0; s < 4; s++) {
    if (FIRST && s == 0) wgmma64_set<1>(d, &a[0], db); else wgmma64_acc<1>(d, &a[4 * s], db + s * 128);
  }
  WG_COMMIT();
}
__device__ __forceinline__ void mma_tile_reuse(float (&d)[32], const uint32_t (&a)[16], uint64_t db) {
  WG_FENCE();
  wgmma64_reuse<1>(d, &a[0], db, blockIdx.y);
#pragma unroll
  for (int s = 1; s < 4; s++) wgmma64_acc<1>(d, &a[4 * s], db + s * 128);
  WG_COMMIT();
}
template <int ROW> __device__ __forceinline__ void fold_step(float (&d)[32], const uint32_t (&mu)[4]) {
  wgmma64_acc<1>(d, mu, (uint64_t)((SM_BASE + SM_CS + ROW * 128) >> 4) | (uint64_t(1) << 16) | (uint64_t(1) << 62));
}
template <int ROW> __device__ __forceinline__ void mma_fold(float (&d)[32], const uint32_t (&mu)[4]) {
  WG_FENCE();
  fold_step<ROW>(d, mu);
  WG_COMMIT();
}
template <int ROW> __device__ __forceinline__ void mma_tile_fold(float (&d)[32], const uint32_t (&a)[16], uint64_t db, const uint32_t (&mu)[4]) {
  WG_FENCE();
#pragma unroll
  for (int s = 0; s < 4; s++) wgmma64_acc<1>(d, &a[4 * s], db + s * 128);
  fold_step<ROW>(d, mu);
  WG_COMMIT();
}
__device__ __forceinline__ void mma_add_half(float (&d)[32], const uint32_t (&a)[16]) {
  const uint64_t db = (uint64_t)((SM_BASE + SM_EYE) >> 4) | (uint64_t(8) << 16) | (uint64_t(8) << 32);
  WG_FENCE();
#pragma unroll
  for (int s = 0; s < 4; s++) wgmma16_acc(&d[8 * s], &a[4 * s], db);
  WG_COMMIT();
}
#define ACQUIRE(f) mbar_wait(SM_BASE + SM_FULL + ((f) % NSTAGE) * 8, ((f) / NSTAGE) & 1)
__device__ __forceinline__ void mbar_probe(uint32_t& ok, uint32_t bar, uint32_t parity) {
  asm volatile("{\n.reg .pred p;\nmbarrier.test_wait.parity.shared::cta.b64 p, [%1], %2;\nselp.u32 %0, %0, 0, p;\n}"
               : "+r"(ok) : "r"(bar), "r"(parity) : "memory");
}
template <int F, int N> __device__ __forceinline__ uint32_t probe_n() {
  static_assert(F % NSTAGE + N <= NSTAGE, "stages must not wrap");
  uint32_t ok = 1;
#pragma unroll
  for (int i = 0; i < N; i++) mbar_probe(ok, SM_BASE + SM_FULL + (F % NSTAGE + i) * 8, (F / NSTAGE) & 1);
  return ok;
}
template <int F, int N> __device__ __forceinline__ void settle_n(uint32_t ok) {
  if (__builtin_expect(!ok, 0)) {
#pragma unroll 1
    for (int i = 0; i < N; i++) mbar_wait(SM_BASE + SM_FULL + (F % NSTAGE + i) * 8, (F / NSTAGE) & 1);
  }
}
template <int F, int N> __device__ __forceinline__ void acquire_n() { settle_n<F, N>(probe_n<F, N>()); }
#define RELEASE(f0, f1) do { if (lane == 0) { _Pragma("unroll") for (int f_ = (f0); f_ <= (f1); f_++) mbar_arrive(SM_BASE + SM_EMPTY + (f_ % NSTAGE) * 8); } } while (0)
constexpr uint64_t RING = (uint64_t)(SM_BASE >> 4) | (uint64_t(1) << 16) | (uint64_t(64) << 32) | (uint64_t(1) << 62);
#define LO(f) (RING + ((f) % NSTAGE) * 1024)
#define HI(f) (RING + ((f) % NSTAGE) * 1024 + 512)

template <int C> __device__ __forceinline__ uint4* peer(uint4* p) {
  asm volatile("" : "+l"(p));
  return (uint4*)((uintptr_t)p ^ (C * X_SIZE * sizeof(uint4)));
}
__device__ __forceinline__ uint32_t clock_now() { uint32_t c; asm volatile("mov.u32 %0, %%clock;" : "=r"(c) :: "memory"); return c; }
__device__ __forceinline__ void publish(uint4* dst, uint32_t (&a)[16], uint32_t tag) {
#pragma unroll
  for (int s = 0; s < 4; s++) a[4 * s] = (a[4 * s] & ~1u) | tag;
  pin(a);
  SCHED();
#pragma unroll
  for (int s = 0; s < 4; s++) st_vec(dst + s * 128, a[4 * s], a[4 * s + 1], a[4 * s + 2], a[4 * s + 3]);
  SCHED();
}
__device__ __forceinline__ void fetch(const uint4* src, uint32_t (&a)[16]) {
#pragma unroll
  for (int s = 0; s < 4; s++) ld_vec(src + s * 128, a[4 * s], a[4 * s + 1], a[4 * s + 2], a[4 * s + 3]);
}
__device__ __forceinline__ uint32_t miss(const uint32_t (&a)[16], uint32_t tag) {
  return (a[0] ^ tag) | (a[4] ^ tag) | (a[8] ^ tag) | (a[12] ^ tag);
}
__device__ __forceinline__ bool stale(uint32_t v) { return __any_sync(0xffffffffu, here(v) & 1u); }
template <int N = 2> __device__ __forceinline__ void announce(Scratch* sc, bool leader) {
  asm volatile("{\n.reg .pred p;\nsetp.ne.u32 p, %1, 0;\n@p red.relaxed.gpu.global.add.u32 [%0], %2;\n}"
               :: "l"(sc->step[blockIdx.x]), "r"((uint32_t)leader), "n"(N) : "memory");
}
__device__ __forceinline__ uint32_t launch_index(const Scratch* sc) { return *(const volatile uint32_t*)sc->step[blockIdx.x] >> 4; }
__device__ __forceinline__ void stat_fetch(const Scratch* sc, uint32_t (&st)[4]) {
  const uint32_t th = here(threadIdx.x);
  ld_vec(&sc->x[(blockIdx.x & ~3u) + (th & 3)][X_ST + (th >> 2)], st[0], st[1], st[2], st[3]);
}
template <int C, int SLOT> __device__ __forceinline__ void gather_first(uint32_t (&A)[4][16], uint32_t (&st)[4], const Scratch* sc, uint4* xp, uint32_t tag, uint32_t sent) {
  if (TIMED) { while (clock_now() - sent < GD) {} } else bar_sync(BAR_GO, 160);
  fetch(peer<1>(xp) + SLOT, A[1]); fetch(peer<2>(xp) + SLOT, A[2]); fetch(peer<3>(xp) + SLOT, A[3]);
  if (SLOT == X_AG0) stat_fetch(sc, st);
  uint32_t spin = 0;
  while (__builtin_expect(stale(miss(A[1], tag) | miss(A[C], tag)), 0) && ++spin < SPIN_LIMIT) {
    fetch(peer<1>(xp) + SLOT, A[1]);
    if (C == 2) fetch(peer<2>(xp) + SLOT, A[2]);
  }
}
template <int C, int SLOT> __device__ __forceinline__ void gather_rest(uint32_t (&A)[4][16], uint4* xp, uint32_t tag) {
  SCHED();
  uint32_t spin = 0;
  while (__builtin_expect(stale(miss(A[C + 1], tag) | miss(A[3], tag)), 0) && ++spin < SPIN_LIMIT) {
    if (C == 1) fetch(peer<2>(xp) + SLOT, A[2]);
    fetch(peer<3>(xp) + SLOT, A[3]);
  }
}
__device__ __forceinline__ void pack_acc(const float (&d)[32], uint32_t (&a)[16]) {
#pragma unroll
  for (int i = 0; i < 16; i++) a[i] = pack2(d[2 * i], d[2 * i + 1]);
}
__device__ __forceinline__ void frag_store(uint32_t slot, const uint32_t (&a)[16]) {
#pragma unroll
  for (int s = 0; s < 4; s++) sts128(slot + s * 512, a[4 * s], a[4 * s + 1], a[4 * s + 2], a[4 * s + 3]);
}
__device__ __forceinline__ void tile_store(uint32_t maddr, const uint32_t (&a)[16]) {
#pragma unroll
  for (int s = 0; s < 4; s++) stsm4(maddr ^ (s << 5), &a[4 * s]);
}
__device__ __forceinline__ void tile_load(uint32_t maddr, uint32_t (&a)[16]) {
#pragma unroll
  for (int s = 0; s < 4; s++) ldsm4(maddr ^ (s << 5), &a[4 * s]);
}

__device__ __forceinline__ void res_load(uint32_t maddr, float (&d)[32]) {
  uint32_t a[16];
  tile_load(here(maddr) + 3 * TILE_BYTES, a);
#pragma unroll
  for (int i = 0; i < 16; i++) { d[2 * i] = bf_lo(a[i]); d[2 * i + 1] = bf_hi(a[i]); }
  pin(d);
}

struct RowAcc { float s[2][4], u[2][4], v[2][4]; };
__device__ __forceinline__ void row_sums(RowAcc& t, const uint32_t (&a)[16]) {
#pragma unroll
  for (int s = 0; s < 4; s++) hmma(t.s[s & 1], &a[4 * s], 0x3F803F80u, 0x3F803F80u);
}
__device__ __forceinline__ void row_gram(RowAcc& t, const uint32_t (&a)[16]) {
#pragma unroll
  for (int s = 0; s < 8; s++) {
    hmma8(t.u[s & 1], &a[2 * s], a[2 * s]);
    hmma8(t.v[s & 1], &a[2 * s], a[2 * s + 1]);
  }
}
__device__ __forceinline__ float2 row_squares(const RowAcc& t, bool odd) {
  return make_float2(odd ? t.u[0][1] + t.u[1][1] : t.u[0][0] + t.u[1][0], odd ? t.v[0][3] + t.v[1][3] : t.v[0][2] + t.v[1][2]);
}
__device__ __forceinline__ void stat_publish(const uint32_t (&a)[16], Scratch* sc, uint32_t th, uint32_t tag) {
  RowAcc t = {};
  row_sums(t, a);
  row_gram(t, a);
  const float2 q = row_squares(t, th & 4);
  if ((th & 3) == ((th >> 3) & 3))
    st_vec(&sc->x[blockIdx.x][X_ST + (th >> 2)], (__float_as_uint(t.s[0][0] + t.s[1][0]) & ~1u) | tag, __float_as_uint(q.x),
           __float_as_uint(t.s[0][2] + t.s[1][2]), __float_as_uint(q.y));
}
struct RowNorm { float m0, rs0, m1, rs1; };
__device__ __forceinline__ RowNorm row_norm(float s0, float q0, float s1, float q1, float scale) {
  RowNorm n;
  n.m0 = s0 * (1.f / DM); n.m1 = s1 * (1.f / DM);
  n.rs0 = scale * rsqrt_hw(fmaxf(fmaf(-n.m0, n.m0, q0 * (1.f / DM)), 0.f) + LN_EPS);
  n.rs1 = scale * rsqrt_hw(fmaxf(fmaf(-n.m1, n.m1, q1 * (1.f / DM)), 0.f) + LN_EPS);
  return n;
}
__device__ __forceinline__ RowNorm stat_finish(const Scratch* sc, uint32_t (&st)[4], uint32_t tag, float scale) {
  uint32_t spin = 0;
  while (__builtin_expect(stale(st[0] ^ tag), 0) && ++spin < SPIN_LIMIT) stat_fetch(sc, st);
  float f[4];
#pragma unroll
  for (int i = 0; i < 4; i++) {
    f[i] = __uint_as_float(st[i]);
    f[i] += __shfl_xor_sync(0xffffffffu, f[i], 1);
    f[i] += __shfl_xor_sync(0xffffffffu, f[i], 2);
  }
  return row_norm(f[0], f[1], f[2], f[3], scale);
}
__device__ __forceinline__ void mean_frag(uint32_t (&mu)[4], const RowNorm& n, bool sel) {
  const float a = sel ? -n.m0 : 0.f, c = sel ? -n.m1 : 0.f;
  mu[0] = pack2(a, a); mu[1] = pack2(c, c);
  const float al = a - bf_lo(mu[0]), cl = c - bf_lo(mu[1]);
  mu[2] = pack2(al, al); mu[3] = pack2(cl, cl);
  pin(mu);
}
__device__ __forceinline__ void centre(uint32_t (&a)[16], uint32_t m0, uint32_t m1) {
#pragma unroll
  for (int i = 0; i < 16; i++) asm("sub.rn.bf16x2 %0, %0, %1;" : "+r"(a[i]) : "r"((i & 1) ? m1 : m0));
  pin(a);
}
__device__ __forceinline__ void scale_pack(const float (&d)[32], uint32_t (&a)[16], float rs0, float rs1) {
#pragma unroll
  for (int i = 0; i < 16; i++) { const float rs = (i & 1) ? rs1 : rs0; a[i] = pack2(d[2 * i] * rs, d[2 * i + 1] * rs); }
}
template <int S> __device__ __forceinline__ void silu_seg(float (&acc)[4][32], float (&tn)[2][4], uint32_t (&H)[4][16], float rs0, float rs1) {
  if (S >= 2) {
    const float* h = &acc[(S - 2) >> 3][4 * ((S - 2) & 7)];
    const float* v = tn[S & 1];
    uint32_t* o = &H[(S - 2) >> 3][2 * ((S - 2) & 7)];
    o[0] = pack2(fmaf(h[0], v[0], h[0]), fmaf(h[1], v[1], h[1]));
    o[1] = pack2(fmaf(h[2], v[2], h[2]), fmaf(h[3], v[3], h[3]));
    asm volatile("" : "+r"(o[0]), "+r"(o[1]));
  }
  if (S >= 1 && S <= 32) {
#pragma unroll
    for (int k = 0; k < 4; k++) tn[(S - 1) & 1][k] = tanh_hw(acc[((S - 1) >> 3) & 3][4 * ((S - 1) & 7) + k]);
  }
  if (S < 32) {
    float* h = &acc[(S >> 3) & 3][4 * (S & 7)];
    h[0] *= rs0; h[1] *= rs0; h[2] *= rs1; h[3] *= rs1;
    asm volatile("" : "+f"(h[0]), "+f"(h[1]), "+f"(h[2]), "+f"(h[3]));
  }
  SCHED();
}
template <int S0, int S1> __device__ __forceinline__ void silu_segs(float (&acc)[4][32], float (&tn)[2][4], uint32_t (&H)[4][16], float rs0, float rs1) {
  silu_seg<S0>(acc, tn, H, rs0, rs1);
  if constexpr (S0 + 1 < S1) silu_segs<S0 + 1, S1>(acc, tn, H, rs0, rs1);
}
template <int HALF> __device__ __forceinline__ void send_half(uint4* dst, const float (&d)[32], uint32_t tag) {
  uint32_t o[8];
#pragma unroll
  for (int i = 0; i < 8; i++) o[i] = pack2(d[16 * HALF + 2 * i], d[16 * HALF + 2 * i + 1]);
  o[0] = (o[0] & ~1u) | tag; o[4] = (o[4] & ~1u) | tag;
  pin(o);
  SCHED();
  st_vec(dst + HALF * 256, o[0], o[1], o[2], o[3]);
  st_vec(dst + HALF * 256 + 128, o[4], o[5], o[6], o[7]);
  SCHED();
}
__device__ __forceinline__ void send_residual(uint32_t (&a)[16], Scratch* sc, uint4* xp, uint32_t maddr, uint32_t tag, uint32_t& sent) {
  const uint32_t exact[4] = {a[0], a[4], a[8], a[12]};
  publish(xp + X_AG0, a, tag);
  if (TIMED) sent = clock_now();
  const uint32_t th = here(threadIdx.x);
  stat_publish(a, sc, th, tag);
  tile_store(here(maddr) + 3 * TILE_BYTES, a);
  stsm4(SM_BASE + SM_STG + 3 * TILE_BYTES + (th >> 5) * 2048 + (th & 7) * 128 + ((((th >> 2) & 6) ^ (th & 7)) << 4), exact);
}
template <int F, int N> __device__ __forceinline__ void proj_residual(uint32_t (&A)[4][16], Scratch* sc, uint4* xp, uint32_t maddr,
                                                                      uint32_t tag, uint32_t& sent) {
  float acc[32];
  if (TIMED && F == F_PW2) sent = clock_now();
  uint32_t st[4];
  acquire_n<F, N>();
  if (F == F_PW2) acquire_n<0, 5>();
  res_load(maddr, acc);
  mma_tile<false>(acc, A[0], LO(F));
  gather_first<2, X_AG1>(A, st, sc, xp, tag, sent);
  announce(sc, threadIdx.x == 0);
  mma_tile<false>(acc, A[1], HI(F));
  mma_tile<false>(acc, A[2], LO(F + 1));
  gather_rest<2, X_AG1>(A, xp, tag);
  PROF_MARK0(F == F_WO ? 11 : 16);
  mma_tile<false>(acc, A[3], HI(F + 1));
  WG_WAIT(0); pin(acc);
  pack_acc(acc, A[0]);
  send_residual(A[0], sc, xp, maddr, tag, sent);
}

__device__ __forceinline__ uint64_t ring_desc(uint32_t lo) { return (RING & ~uint64_t(0xFFFFFFFFu)) | lo; }
__device__ __forceinline__ void qk_tile(float (&S)[32], const uint32_t (&Q)[16], uint32_t dk) {
  wgmma64_reuse<0>(S, &Q[0], ring_desc(dk), blockIdx.y);
#pragma unroll
  for (int s = 1; s < 4; s++) wgmma64_acc<0>(S, &Q[4 * s], ring_desc(dk + s * 2));
}
__device__ __forceinline__ void qk_shift(float (&S)[32], const uint32_t (&nm)[4]) { wgmma64_acc<0>(S, nm, (uint64_t)((SM_BASE + SM_ONE) >> 4)); }
constexpr uint32_t RING_K = (uint32_t)RING, V_STEP = 1u - (1u << 16);
constexpr uint32_t RING_V = (SM_BASE >> 4) | (((SM_STG + 2 * TILE_BYTES) >> 4) << 16);
__device__ __forceinline__ void pv_tile(float (&O)[36], const uint32_t (&P)[16], uint32_t dv, uint32_t pad) {
#pragma unroll
  for (int s = 0; s < 4; s++) wgmma72_acc(O, &P[4 * s], ring_desc(dv + s * 128 * V_STEP + (s < 2 ? 0 : (s - 1) * pad)));
}
__device__ __forceinline__ void attn_step(const float (&Sc)[32], float (&Sn)[32], uint32_t (&Pc)[16], uint32_t (&Pp)[16], float (&O)[36],
                                          const uint32_t (&Q)[16], const uint32_t (&nm)[4], uint32_t dk, uint32_t dv, bool next, bool prev) {
  if (next) {
    WG_FENCE();
    qk_tile(Sn, Q, dk);
    qk_shift(Sn, nm);
  }
  if (prev) {
    WG_FENCE();
    pv_tile(O, Pp, dv, 0);
  }
  WG_COMMIT();
  SCHED();
#pragma unroll
  for (int i = 0; i < 16; i++) Pc[i] = pack2(ex2_hw(Sc[2 * i]), ex2_hw(Sc[2 * i + 1]));
  pin(Pc);
  SCHED();
}
template <int R> __device__ __forceinline__ float tile_max(const float (&S)[32]) {
  float t[4];
#pragma unroll
  for (int j = 0; j < 4; j++) t[j] = fmaxf(fmaxf(S[8 * j + R], S[8 * j + R + 1]), fmaxf(S[8 * j + R + 4], S[8 * j + R + 5]));
  float n = fmaxf(fmaxf(t[0], t[1]), fmaxf(t[2], t[3]));
  n = fmaxf(n, __shfl_xor_sync(0xffffffffu, n, 1));
  return fmaxf(n, __shfl_xor_sync(0xffffffffu, n, 2));
}
__device__ __forceinline__ void attention_exact(float (&O)[36], const uint32_t (&Q)[16], const Scratch* sc, int bh, int lane, int half) {
  const char* kb = (const char*)&sc->kv[bh][0][0][0];
  const char* vb = (const char*)&sc->kv[bh][1][0][0];
  const int g = lane >> 2, q = lane & 3;
  float m0 = -INFINITY, m1 = -INFINITY, l0 = 0.f, l1 = 0.f;
  float o[4][4] = {};
#pragma unroll 1
  for (int k0 = 0; k0 < T_SEQ; k0 += 8) {
    float s[4] = {0.f, 0.f, 0.f, 0.f};
#pragma unroll
    for (int c = 0; c < 8; c++) hmma8(s, &Q[2 * c], __ldcg((const uint32_t*)(kb + (k0 + g) * 128 + ((c ^ g) << 4) + q * 4)));
    float n0 = fmaxf(s[0], s[1]), n1 = fmaxf(s[2], s[3]);
    n0 = fmaxf(n0, __shfl_xor_sync(0xffffffffu, n0, 1)); n1 = fmaxf(n1, __shfl_xor_sync(0xffffffffu, n1, 1));
    n0 = fmaxf(m0, fmaxf(n0, __shfl_xor_sync(0xffffffffu, n0, 2))); n1 = fmaxf(m1, fmaxf(n1, __shfl_xor_sync(0xffffffffu, n1, 2)));
    const float a0 = ex2_hw(m0 - n0), a1 = ex2_hw(m1 - n1);
    m0 = n0; m1 = n1;
    const uint32_t pp[2] = {pack2(ex2_hw(s[0] - n0), ex2_hw(s[1] - n0)), pack2(ex2_hw(s[2] - n1), ex2_hw(s[3] - n1))};
    l0 = fmaf(l0, a0, bf_lo(pp[0]) + bf_hi(pp[0])); l1 = fmaf(l1, a1, bf_lo(pp[1]) + bf_hi(pp[1]));
#pragma unroll
    for (int j = 0; j < 4; j++) {
      const int c = 4 * half + j;
      const uint32_t v0 = __ldcg((const uint16_t*)(vb + (k0 + 2 * q) * 128 + ((c ^ (2 * q)) << 4) + g * 2));
      const uint32_t v1 = __ldcg((const uint16_t*)(vb + (k0 + 2 * q + 1) * 128 + ((c ^ (2 * q + 1)) << 4) + g * 2));
      o[j][0] *= a0; o[j][1] *= a0; o[j][2] *= a1; o[j][3] *= a1;
      hmma8(o[j], pp, v0 | (v1 << 16));
    }
  }
  l0 += __shfl_xor_sync(0xffffffffu, l0, 1); l1 += __shfl_xor_sync(0xffffffffu, l1, 1);
  O[32] = l0 + __shfl_xor_sync(0xffffffffu, l0, 2); O[34] = l1 + __shfl_xor_sync(0xffffffffu, l1, 2);
#pragma unroll
  for (int i = 0; i < 16; i++) O[i] = o[i >> 2][i & 3];
}

__device__ __forceinline__ uint32_t fill_entry(int f, int r) {
  int m, x = r, y, dx = 0;
  if (f < F_QKV || f >= 48) {
    const int i = f & 15;
    m = f < F_QKV ? M_FF1A : M_FF2A;
    if (i < 8) { x = 4 * r + ((0xE2u >> i) & 1) * 2; y = r ^ ((0xE790u >> (2 * i)) & 3); dx = 1; }
    else { m++; x = r ^ (((i >> 1) - 3) & 3); y = 4 * r + 2 * (i & 1); }
  } else if (f < F_KV) {
    const int i = f - F_QKV;
    m = M_QKV;
    if (i == 1 || i >= 5) { y = r ^ (i == 1 ? 0 : 2); }
    else { x = 4 + r; y = r ^ (i ? i - 1 : 0); dx = 4; }
  } else if (f >= F_PW1 && f < F_PW2) {
    m = M_PW1; y = r ^ (f - F_PW1); dx = 4;
  } else {
    m = f < F_PW1 ? M_WO : M_PW2; y = r ^ ((f & 1) * 2);
  }
  return m | (x << 4) | (y << 8) | (dx << 16);
}
__device__ __forceinline__ void tma_fill(uint32_t st, const CUtensorMap* map, uint32_t x, uint32_t y, uint32_t x2, uint32_t y2) {
  asm volatile("{\n.reg .pred p;\nelect.sync _|p, 0xffffffff;\n"
               "@p mbarrier.arrive.expect_tx.shared::cta.b64 _, [%1], 16384;\n"
               "@p cp.async.bulk.tensor.2d.shared::cluster.global.mbarrier::complete_tx::bytes [%0], [%2, {%3, %4}], [%1];\n"
               "@p cp.async.bulk.tensor.2d.shared::cluster.global.mbarrier::complete_tx::bytes [%0 + 8192], [%2, {%5, %6}], [%1];\n}"
               :: "r"(SM_BASE + st * STAGE_BYTES), "r"(SM_BASE + SM_FULL + st * 8), "l"(map), "r"(x), "r"(y), "r"(x2), "r"(y2) : "memory");
}
template <int F0, int N> __device__ __forceinline__ void weight_fills(const Params& p, uint32_t entry) {
  uint32_t st = F0 % NSTAGE, parity = ((F0 / NSTAGE) & 1) ^ 1, e = __shfl_sync(0xffffffffu, entry, 0);
#pragma unroll 1
  for (int i = 1; i <= N; i++) {
    const uint32_t x = (e << 2) & 0x3C0, y = (e >> 2) & 0x3FC0, dx = (e >> 16) << 6;
    const CUtensorMap* map = &p.map[e & 15];
    e = __shfl_sync(0xffffffffu, entry, i);
    mbar_wait(SM_BASE + SM_EMPTY + st * 8, parity);
    tma_fill(st, map, x, y, x + dx, dx ? y : y ^ 64);
    if (++st == NSTAGE) { st = 0; parity ^= 1; }
  }
}
__device__ __forceinline__ uint32_t kv_poll(const uint32_t* flag, uint32_t prev) {
  uint32_t v;
  asm volatile("ld.relaxed.gpu.global.u32 %0, [%1];" : "=r"(v) : "l"(flag) : "memory");
  v = __ballot_sync(0xffffffffu, v - 1 == prev);
  return v & (v >> 1);
}
__device__ __forceinline__ void kv_fills(const Scratch* sc, int bh, uint32_t prev, const uint32_t* flag, uint32_t ready) {
  uint32_t todo = 0x1555, order = 0;
#pragma unroll 1
  for (int i = 0; i < 16; i++) {
    const uint32_t kind = (0xD554u >> i) & 1, j = kind ? (i - 1) >> 1 : (i + 1) >> 1;
    const uint32_t want = kind ? 0x10000u << ((order >> (4 * j)) & 15) : (j == 7 ? 0x4000u : todo);
    uint32_t spin = 0;
#pragma unroll 1
    while (!(ready & want) && ++spin < SPIN_LIMIT) ready = kv_poll(flag, prev);
    const uint32_t tile = __ffs((ready & want) ? (ready & want) : want) - 1;
    if (!kind) { todo &= ~(1u << tile); order |= tile << (4 * j); }
    const uint32_t st = (j < 6 ? 4 * (j >> 1) : 0) + (j & 1) + 2 * kind;
    mbar_wait(SM_BASE + SM_EMPTY + st * 8, j < 6);
    asm volatile("{\n.reg .pred p;\nelect.sync _|p, 0xffffffff;\n"
                 "@p mbarrier.arrive.expect_tx.shared::cta.b64 _, [%1], 16384;\n"
                 "@p cp.async.bulk.shared::cluster.global.mbarrier::complete_tx::bytes [%0], [%2], 16384, [%1];\n}"
                 :: "r"(SM_BASE + st * STAGE_BYTES), "r"(SM_BASE + SM_FULL + st * 8), "l"(&sc->kv[bh][0][0][0] + tile * 512) : "memory");
    PROF_AT(256 + 512 + (10 + i) * 4);
  }
}
__device__ __forceinline__ void reset_mailboxes(Scratch* sc, int half, int lane, uint32_t t_start) {
  while (clock_now() - t_start < TC) {}
#pragma unroll 1
  for (int i = half * 8; i < half * 9 + 8; i++) {
    const uint32_t t0 = clock_now();
    uint4* dst = &sc->x[blockIdx.x ^ (i < 12 ? (i >> 2) + 1 : 0)][i * 128 + lane];
#pragma unroll
    for (int k = 0; k < 4; k++) st_vec(dst + 32 * k, 0u, 0u, 0u, 0u);
    while (clock_now() - t0 < CLR_PACE) {}
  }
  bar_arrive(BAR_RST, 192);
  PROF_AT(256 + 512 + 28 * 4);
  asm volatile("fence.acq_rel.gpu;" ::: "memory");
  __syncwarp();
  announce<1>(sc, lane == 0);
  PROF_AT(256 + 512 + 2 * 4);
}
__device__ __forceinline__ void l2_prefetch(const void* p, uint32_t total, int b) {
  const uint32_t part = total / NCTA;
  asm volatile("cp.async.bulk.prefetch.L2.global [%0], %1;" :: "l"((const char*)p + (size_t)b * part), "r"(part) : "memory");
}

__global__ void __launch_bounds__(384, 1) conformer_kernel(Scratch* __restrict__ sc, __nv_bfloat16* __restrict__ out,
                                                           const __nv_bfloat16* __restrict__ dw, const __nv_bfloat16* __restrict__ xin,
                                                           const __nv_bfloat16* __restrict__ w_ff1a, const __grid_constant__ Params p) {
  extern __shared__ __align__(1024) uint8_t smem[];
  const int tid = threadIdx.x, lane = tid & 31;
  const uint32_t t_start = clock_now();
  const int b = blockIdx.x, r = b & 3, batch = b >> 6, t = (b >> 2) & 15;
  if ((uint32_t)__cvta_generic_to_shared(smem) != SM_BASE) return;
  PROF_AT(256 + (tid >> 7) * 256);
  PROF_TIME(30);
  const uint32_t crow = ((tid >> 1) & 48) + (lane >> 3);
  const uint32_t cdst = SM_BASE + crow * 128 + (((lane & 7) ^ (lane >> 3)) << 4);
  if (tid < 128) {
    const uint32_t g0 = batch * T_SEQ + t * 64 + crow, o = r * 128 + (lane & 7) * 16;
    const uint32_t lo = min(g0, 2 * T_SEQ - 5) * 512 + o, hi = min(g0 + 8, 2 * T_SEQ - 5) * 512 + o;
#pragma unroll
    for (int c = 0; c < 4; c++) {
#pragma unroll
      for (int i = 0; i < 4; i++)
        cp_async16((cdst ^ ((i & 1) << 6)) + SM_STG + (3 - c) * TILE_BYTES + i * 512, (const char*)xin + (((i & 2) ? hi : lo) ^ (c << 7)) + (i & 1) * 2048);
      asm volatile("cp.async.commit_group;" ::: "memory");
    }
  } else if (tid < 256) {
    const char* src = (const char*)w_ff1a + (64 * r + crow) * 2048 + r * 512 + (lane & 7) * 16;
#pragma unroll
    for (int c = 0; c < 4; c++) {
#pragma unroll
      for (int i = 0; i < 4; i++) cp_async16((cdst ^ ((i & 1) << 6)) + c * TILE_BYTES + i * 512, src + i * 8192 + c * 128);
      asm volatile("cp.async.commit_group;" ::: "memory");
    }
  }
  const int cw = __shfl_sync(0xffffffffu, tid >> 5, 0), wg = cw >> 2, w = cw & 3;

  if (wg == 2) {
    asm volatile("setmaxnreg.dec.sync.aligned.u32 40;");
    if (cw == 8) {
      if (lane == 0) {
        asm volatile("prefetch.tensormap [%0];" :: "l"(&p.map[M_FF1A]) : "memory");
#pragma unroll
        for (int i = 0; i < NSTAGE; i++) mbar_init(SM_BASE + SM_FULL + i * 8, 1);
        fence_async_smem();
      }
      __syncwarp();
      bar_arrive(0, 320);
      while (clock_now() - t_start < TF) {}
      PROF_MARK(9);
#pragma unroll
      for (int f = 2; f < 8; f++) {
        const uint32_t x = 256 * r + ((0xE2u >> f) & 1) * 128, y = (r ^ ((0xE790u >> (2 * f)) & 3)) * 64;
        tma_fill(f, &p.map[M_FF1A], x, y, x + 64, y);
      }
      PROF_MARK(1);
      uint32_t entry[2];
#pragma unroll 1
      for (int i = 0; i < 2; i++) { entry[1] = fill_entry(8 + i * 32 + lane, r); if (i == 0) entry[0] = entry[1]; }
      bar_sync(BAR_INIT, 64);
      weight_fills<8, F_KV - 8>(p, entry[0]);
      mbar_wait(SM_BASE + SM_EMPTY + (F_WO % NSTAGE) * 8, 1);
      weight_fills<F_WO, F_TOTAL - F_WO>(p, entry[1]);
    } else if (here(cw) != 11) {
      const int kind = w - 1;
      const uint32_t prev = launch_index(sc);
      if (kind == 0) {
        if (lane == 0) {
#pragma unroll
          for (int i = 0; i < NSTAGE; i++) mbar_init(SM_BASE + SM_EMPTY + i * 8, 4);
        }
        __syncwarp();
        bar_arrive(0, 320);
        bar_arrive(BAR_INIT, 64);
        if (lane == 0) {
          const uint32_t t0 = t_start;
          while (clock_now() - t0 < PF0) {}
          while (clock_now() - t0 < PF1) {}
          asm volatile("prefetch.tensormap [%0];" :: "l"(&p.map[M_FF1B]) : "memory");
          l2_prefetch(p.w_ff1b, 1024 * 256 * 2, b);
          while (clock_now() - t0 < PF2) {}
          l2_prefetch(p.w_qkv, 256 * 768 * 2, b);
          l2_prefetch(p.w_pw1, 256 * 512 * 2, b);
          l2_prefetch(p.w_ff2a, 256 * 1024 * 2, b);
          while (clock_now() - t0 < PF3) {}
          l2_prefetch(p.w_o, 256 * 256 * 2, b);
          l2_prefetch(p.w_pw2, 256 * 256 * 2, b);
          l2_prefetch(p.w_ff2b, 1024 * 256 * 2, b);
#pragma unroll
          for (int i = M_QKV; i < M_COUNT; i++) asm volatile("prefetch.tensormap [%0];" :: "l"(&p.map[i]) : "memory");
        }
        __syncwarp();
      } else {
        reset_mailboxes(sc, 1, lane, t_start);
      }
      if (kind == 0) {
        const uint32_t* flag = sc->flag[batch * 4 + r][lane];
        const uint32_t ready = kv_poll(flag, prev);
        bar_sync(BAR_K, 192);
        kv_fills(sc, batch * 4 + r, prev, flag, ready);
      } else {
#pragma unroll 1
        for (int k = 0; k < 2; k++) {
          if (k == 0) bar_sync(BAR_K, 192); else bar_sync(BAR_V, 160);
          if (lane == 0) {
            PROF_MARK(4 + k * 2);
            asm volatile("cp.async.bulk.global.shared::cta.bulk_group [%0], [%1], %2;"
                         :: "l"(sc->kv[batch * 4 + r][k][t]), "r"(SM_BASE + SM_STG + k * TILE_BYTES), "r"(TILE_BYTES) : "memory");
            asm volatile("cp.async.bulk.commit_group;\ncp.async.bulk.wait_group 0;" ::: "memory");
            asm volatile("st.relaxed.gpu.global.u32 [%0], %1;" :: "l"(sc->flag[batch * 4 + r][k * 16 + t]), "r"(prev + 1) : "memory");
            PROF_MARK(5 + k * 2);
          }
          __syncwarp();
        }
      }
    } else {
      const uint32_t* watch = sc->step[(b & ~3) + (lane & 3)];
      uint32_t seen;
      asm volatile("ld.relaxed.gpu.global.u32 %0, [%1];" : "=r"(seen) : "l"(watch) : "memory");
      reset_mailboxes(sc, 0, lane, t_start);
      uint32_t want = seen & ~15u;
#pragma unroll 1
      for (int k = 0; k < (TIMED ? 1 : 8); k++) {
        want += 2;
        uint32_t spin = 0;
#pragma unroll 1
        while (__any_sync(0xffffffffu, (int)(seen - want) < 0) && ++spin < SPIN_LIMIT)
          asm volatile("ld.relaxed.gpu.global.u32 %0, [%1];" : "=r"(seen) : "l"(watch) : "memory");
        bar_arrive(BAR_GO, 160);
        PROF_MARK(32 + k);
      }
    }
  } else {
    asm volatile("setmaxnreg.inc.sync.aligned.u32 232;");
    const int q = lane & 3, th = tid & 127;
    constexpr uint32_t stg = SM_BASE + SM_STG;
    const uint32_t mrow = 16 * w + (lane & 15);
    const uint32_t maddr = stg + mrow * 128 + (((lane >> 4) ^ (lane & 7)) << 4);
    const uint32_t qslot = stg + 2 * TILE_BYTES + w * 2048 + lane * 16;
    uint4* const xp = &sc->x[b][th];
    const int nvalid = T_SEQ - t * 64, row0 = 16 * w + (lane >> 2);

    uint32_t A[4][16];
    uint32_t st[4], sent = 0;
    bar_sync(0, 320);
    if (wg == 0) {
      RowAcc ra = {};
      cp_async_wait(0);
      __syncwarp();
      PROF_MARK0(45);
#pragma unroll
      for (int c = 0; c < 4; c++) tile_load(maddr + (3 - c) * TILE_BYTES, A[c]);
      row_sums(ra, A[0]); row_gram(ra, A[0]); row_sums(ra, A[1]); row_gram(ra, A[1]);
      pin(ra.s[0]); pin(ra.s[1]); pin(ra.u[0]); pin(ra.u[1]); pin(ra.v[0]); pin(ra.v[1]);
      SCHED();
      row_sums(ra, A[2]); row_sums(ra, A[3]); row_gram(ra, A[2]); row_gram(ra, A[3]);
      const float m0 = (ra.s[0][0] + ra.s[1][0]) * (1.f / DM), m1 = (ra.s[0][2] + ra.s[1][2]) * (1.f / DM);
      st[0] = pack2(m0, m0); st[1] = pack2(m1, m1);
      centre(A[0], st[0], st[1]);
      const float2 sq = row_squares(ra, lane & 4);
      st[2] = __float_as_uint(fmaf(-m0, m0, sq.x * (1.f / DM))); st[3] = __float_as_uint(fmaf(-m1, m1, sq.y * (1.f / DM)));
    } else {
      if (th < 112) sts128(SM_BASE + SM_CS + th * 16, 0, 0, 0, 0);
      sts32(SM_BASE + SM_EYE + th * 4, th >= 96 ? 0x3F803F80u : ((th & 32) == 0 && (th & 3) == ((th >> 3) & 3)) ? (0x3F00u << ((th & 4) * 4)) : 0u);
#pragma unroll
      for (int i = 0; i < 2; i++) {
        cp_async_wait(2 - 2 * i);
        fence_async_smem();
        bar_sync(BAR_WG1, 128);
        if (th == 0) mbar_arrive(SM_BASE + SM_FULL + i * 8);
      }
      PROF_MARK(6);
      const uint32_t tag = ~launch_index(sc) & 1;
      mbar_wait(SM_BASE + SM_FULL + 4 * 8, 0);
      PROF_MARK(5);
      if (b < 72) {
        const __nv_bfloat16* wp; int ld, col;
        if (b < 24) { wp = p.w_qkv; ld = 768; col = b * 32; }
        else if (b < 40) { wp = p.w_pw1; ld = 512; col = (b - 24) * 32; }
        else { wp = p.w_ff2a; ld = 1024; col = (b - 40) * 32; }
        const uint4* src = (const uint4*)(wp + (size_t)(th >> 2) * ld + col + q * 8);
        float c[8] = {0.f, 0.f, 0.f, 0.f, 0.f, 0.f, 0.f, 0.f};
#pragma unroll 1
        for (int h = 0; h < 2; h++, src += 16 * ld) {
#pragma unroll
          for (int i = 0; i < 4; i++) {
            const uint4 v = __ldg(src + i * 4 * ld);
            c[0] += bf_lo(v.x); c[1] += bf_hi(v.x); c[2] += bf_lo(v.y); c[3] += bf_hi(v.y);
            c[4] += bf_lo(v.z); c[5] += bf_hi(v.z); c[6] += bf_lo(v.w); c[7] += bf_hi(v.w);
          }
        }
#pragma unroll 1
        for (int m = 4; m <= 16; m <<= 1)
#pragma unroll
          for (int k = 0; k < 8; k++) c[k] += __shfl_xor_sync(0xffffffffu, c[k], m);
        if (lane < 4) {
          const uint32_t a = SM_BASE + SM_CS + 1792 + w * 128 + lane * 32;
          sts128(a, __float_as_uint(c[0]), __float_as_uint(c[1]), __float_as_uint(c[2]), __float_as_uint(c[3]));
          sts128(a + 16, __float_as_uint(c[4]), __float_as_uint(c[5]), __float_as_uint(c[6]), __float_as_uint(c[7]));
        }
        bar_sync(BAR_WG1, 128);
        if (th < 8) {
          float o[4] = {0.f, 0.f, 0.f, 0.f};
#pragma unroll 1
          for (int k = 0; k < 4; k++) {
            uint32_t e[4];
            lds128(SM_BASE + SM_CS + 1792 + k * 128 + th * 16, e[0], e[1], e[2], e[3]);
#pragma unroll
            for (int i = 0; i < 4; i++) o[i] += __uint_as_float(e[i]);
          }
          st_vec(&sc->cs[b * 8 + th], (__float_as_uint(o[0]) & ~1u) | tag, __float_as_uint(o[1]), __float_as_uint(o[2]), __float_as_uint(o[3]));
        }
      }
      bar_sync(BAR_WG1, 128);
      PROF_MARK(2);
      if (th < 72) {
        const int j = th >> 3, i = (th & 7) * 2;
        int src;
        if (j < CS_PW1) src = 320 + 64 * r + 16 * j;
        else if (j < CS_QKV) src = 192 + (j - CS_PW1) * 64 + 16 * r;
        else src = ((j - CS_QKV + 1) % 3) * 64 + 16 * r;
        uint32_t e[8], hi[4], lo[4], spin = 0;
#pragma unroll 1
        do {
          ld_vec(&sc->cs[src + i], e[0], e[1], e[2], e[3]);
          ld_vec(&sc->cs[src + i + 1], e[4], e[5], e[6], e[7]);
        } while ((((e[0] ^ tag) | (e[4] ^ tag)) & 1u) && ++spin < SPIN_LIMIT);
        e[0] &= ~1u; e[4] &= ~1u;
#pragma unroll
        for (int k = 0; k < 4; k++) {
          const float c0 = __uint_as_float(e[2 * k]), c1 = __uint_as_float(e[2 * k + 1]);
          hi[k] = pack2(c0, c1);
          lo[k] = pack2(c0 - bf_lo(hi[k]), c1 - bf_hi(hi[k]));
        }
        const uint32_t a = SM_BASE + SM_CS + j * 256 + i * 8;
        sts128(a ^ ((a >> 3) & 0x70), hi[0], hi[1], hi[2], hi[3]);
        sts128((a + 128) ^ (((a + 128) >> 3) & 0x70), lo[0], lo[1], lo[2], lo[3]);
      }
      fence_async_smem();
      PROF_MARK(4);
      bar_arrive(BAR_CS, 256);
    }

#pragma unroll 1
    for (uint32_t pass = 0; pass < 2; pass++) {
      uint32_t Q[16];
      if (wg == 0) {
        float acc[4][32];
        uint32_t H[4][16];
        if (!pass) { PROF_MARK(47); ACQUIRE(0); }
        mma_tile<true>(acc[0], A[0], LO(0)); mma_tile<true>(acc[1], A[0], HI(0));
        if (!pass) ACQUIRE(1);
        mma_tile<true>(acc[2], A[0], LO(1)); mma_tile<true>(acc[3], A[0], HI(1));
        if (pass) {
          gather_first<1, X_AG0>(A, st, sc, xp, 1, sent);
        } else {
          centre(A[1], st[0], st[1]);
          acquire_n<2, 3>();
        }
        mma_tile<false>(acc[0], A[1], LO(2)); mma_tile<false>(acc[1], A[1], HI(2));
        if (pass) {
          gather_rest<1, X_AG0>(A, xp, 1);
          RELEASE(F_WO - 2 + NREL, F_PW2 + 1);
        } else {
          centre(A[2], st[0], st[1]); centre(A[3], st[0], st[1]);
        }
        PROF_MARK2(2, 18);
        mma_tile<false>(acc[0], A[2], LO(3)); mma_tile<false>(acc[0], A[3], LO(4));
        WG_WAIT(4);
        RELEASE(0, 1);
        uint32_t mu[4] = {0u, 0u, 0u, 0u};
        float rs0, rs1, tn[2][4];
        if (pass) {
          const RowNorm n = stat_finish(sc, st, 1, 0.5f);
          rs0 = n.rs0; rs1 = n.rs1;
          mean_frag(mu, n, q == 0);
        } else {
          const int src = (lane & 28) | (lane >> 3);
          rs0 = 0.5f * rsqrt_hw(fmaxf(__uint_as_float(__shfl_sync(0xffffffffu, st[2], src)), 0.f) + LN_EPS);
          rs1 = 0.5f * rsqrt_hw(fmaxf(__uint_as_float(__shfl_sync(0xffffffffu, st[3], src)), 0.f) + LN_EPS);
        }
        pin(mu);
        mma_fold<2 * CS_FF2>(acc[0], mu);
        mma_tile<false>(acc[1], A[2], HI(3));
#define SEGS(a, b) silu_segs<a, b>(acc, tn, H, rs0, rs1)
        WG_WAIT(1); pin(acc[0]);
        SEGS(0, 1);
        mma_tile_fold<2 * CS_FF2 + 2>(acc[1], A[3], HI(4), mu);
        SEGS(1, 3);
        uint32_t ok = probe_n<5, 1>();
        SEGS(3, 4);
        settle_n<5, 1>(ok);
        mma_tile<false>(acc[2], A[1], LO(5));
        SEGS(4, 5);
        ok = probe_n<6, 1>();
        SEGS(5, 6);
        settle_n<6, 1>(ok);
        mma_tile<false>(acc[2], A[2], LO(6));
        SEGS(6, 8);
        WG_WAIT(2); pin(acc[1]);
        RELEASE(2, 4);
        ok = probe_n<7, 1>();
        SEGS(8, 9);
        settle_n<7, 1>(ok);
        mma_tile_fold<2 * CS_FF2 + 4>(acc[2], A[3], LO(7), mu);
        SEGS(9, 12);
        mma_tile<false>(acc[3], A[1], HI(5));
        SEGS(12, 14);
        mma_tile<false>(acc[3], A[2], HI(6));
        SEGS(14, 16);
        WG_WAIT(2); pin(acc[2]);
        SEGS(16, 17);
        mma_tile_fold<2 * CS_FF2 + 6>(acc[3], A[3], HI(7), mu);
        SEGS(17, 19);
        ok = probe_n<8, 2>();
        SEGS(19, 20);
        settle_n<8, 2>(ok);
        mma_tile_reuse(acc[1], H[0], LO(8));
        SEGS(20, 22);
        mma_tile<false>(acc[1], H[1], HI(8));
        SEGS(22, 24);
        WG_WAIT(2); pin(acc[3]);
        RELEASE(5, 7);
        SEGS(24, 26);
        mma_tile<false>(acc[1], H[2], LO(9));
        SEGS(26, 27);
        ok = probe_n<10, 2>();
        SEGS(27, 28);
        settle_n<10, 2>(ok);
        mma_tile_reuse(acc[2], H[0], LO(10));
        SEGS(28, 31);
        mma_tile<false>(acc[2], H[1], HI(10));
        SEGS(31, 34);
#undef SEGS
        PROF_MARK2(3, 19);
        const uint32_t rtag = here(pass ^ 1);
        const uint4* rs_in = xp + X_RS;
        mma_tile<false>(acc[1], H[3], HI(9));
        mma_tile<false>(acc[2], H[2], LO(11));
        ok = probe_n<12, 2>();
        uint4* rs_out = peer<1>(xp) + X_RS;
        mma_tile<false>(acc[2], H[3], HI(11));
        settle_n<12, 2>(ok);
        if (!pass) bar_sync(BAR_RST, 192);
        WG_WAIT(2); pin(acc[1]);
        RELEASE(8, 9);
        send_half<0>(rs_out, acc[1], rtag);
        mma_tile_reuse(acc[3], H[0], LO(12));
        SCHED();
        send_half<1>(rs_out, acc[1], rtag);
        mma_tile<false>(acc[3], H[1], HI(12));
        rs_out = peer<2>(xp) + X_RS + 512;
        WG_WAIT(2); pin(acc[2]);
        send_half<0>(rs_out, acc[2], rtag);
        mma_tile<false>(acc[3], H[2], LO(13));
        SCHED();
        ok = probe_n<14, 2>();
        send_half<1>(rs_out, acc[2], rtag);
        mma_tile<false>(acc[3], H[3], HI(13));
        settle_n<14, 2>(ok);
        mma_tile_reuse(acc[1], H[0], LO(14));
        rs_out = peer<3>(xp) + X_RS + 1024;
        if (!pass) bar_sync(BAR_GO, 160);
        announce(sc, tid == 0);
        fetch(rs_in, A[1]);
        SCHED();
        mma_tile<false>(acc[1], H[1], HI(14));
        WG_WAIT(2); pin(acc[3]);
        send_half<0>(rs_out, acc[3], rtag);
        send_half<1>(rs_out, acc[3], rtag);
        if (TIMED) sent = clock_now();
        mma_tile<false>(acc[1], H[2], LO(15)); mma_tile<false>(acc[1], H[3], HI(15));
        SCHED();
        fetch(rs_in + 512, A[2]);
        SCHED();
        res_load(maddr, acc[2]);
        if (TIMED) { while (clock_now() - sent < RD) {} } else bar_sync(BAR_GO, 160);
        fetch(rs_in + 1024, A[3]);
        if (!pass) acquire_n<F_QKV, 3>();
        {
          uint32_t spin = 0;
          while (__builtin_expect(stale(miss(A[1], rtag) | miss(A[2], rtag) | miss(A[3], rtag)), 0) && ++spin < SPIN_LIMIT) {
            if (stale(miss(A[1], rtag) | miss(A[2], rtag))) { fetch(rs_in, A[1]); fetch(rs_in + 512, A[2]); }
            fetch(rs_in + 1024, A[3]);
          }
        }
        announce(sc, tid == 0 && !pass);
        mma_add_half(acc[2], A[1]);
        mma_add_half(acc[2], A[2]);
        mma_add_half(acc[2], A[3]);
        PROF_MARK2(4, 20);
        WG_WAIT(0); pin(acc[2]); pin(acc[1]);
#pragma unroll
        for (int i = 0; i < 16; i++) A[0][i] = pack2(fmaf(acc[1][2 * i], 0.5f, acc[2][2 * i]), fmaf(acc[1][2 * i + 1], 0.5f, acc[2][2 * i + 1]));
        if (pass) {
          PROF_MARK(21);
          stat_publish(A[0], sc, here(th), 0);
          stat_fetch(sc, st);
          const RowNorm fn = stat_finish(sc, st, 0, 1.f);
          const float nm0 = -fn.m0 * fn.rs0, nm1 = -fn.m1 * fn.rs1;
#pragma unroll
          for (int i = 0; i < 16; i++) {
            const float rs = (i & 1) ? fn.rs1 : fn.rs0, nm = (i & 1) ? nm1 : nm0;
            A[0][i] = pack2(fmaf(bf_lo(A[0][i]), rs, nm), fmaf(bf_hi(A[0][i]), rs, nm));
          }
          tile_store(here(maddr), A[0]);
          __syncwarp();
          const int row = 16 * w + (lane >> 3);
          uint4* dst = (uint4*)(out + ((size_t)batch * T_SEQ + t * 64 + row) * DM + 64 * r) + (lane & 7);
          const uint32_t src = stg + row * 128 + (((lane & 7) ^ (lane >> 3)) << 4);
#pragma unroll
          for (int i = 0; i < 4; i++) {
            uint4 v;
            lds128((src ^ ((i & 1) << 6)) + i * 512, v.x, v.y, v.z, v.w);
            if (row + 4 * i < nvalid) dst[i * 4 * (DM / 8)] = v;
          }
          PROF_MARK(22);
          PROF_TIME(31);
          break;
        }
        send_residual(A[0], sc, xp, maddr, 1, sent);
        PROF_MARK(5);
        mma_tile<true>(acc[0], A[0], LO(F_QKV)); mma_tile<true>(acc[1], A[0], HI(F_QKV));
        mma_tile<true>(acc[2], A[0], LO(F_QKV + 1));
        gather_first<1, X_AG0>(A, st, sc, xp, 1, sent);
        mma_tile<false>(acc[0], A[1], LO(F_QKV + 2)); mma_tile<false>(acc[1], A[1], HI(F_QKV + 2));
        acquire_n<F_QKV + 3, 3>();
        bar_sync(BAR_CS, 256);
        gather_rest<1, X_AG0>(A, xp, 1);
        PROF_MARK(6);
        mma_tile<false>(acc[0], A[2], LO(F_QKV + 3)); mma_tile<false>(acc[0], A[3], LO(F_QKV + 4));
        SCHED();
        {
          const RowNorm n = stat_finish(sc, st, 1, 1.f);
          rs0 = row0 < nvalid ? n.rs0 : 0.f; rs1 = row0 + 8 < nvalid ? n.rs1 : 0.f;
          mean_frag(mu, n, q == 3);
        }
        mma_fold<2 * CS_QKV - 6>(acc[0], mu);
        RELEASE(10, 15);
        WG_WAIT(0); pin(acc[0]);
        scale_pack(acc[0], Q, rs0, rs1);
        tile_store(here(maddr), Q);
        SCHED();
        mma_tile<false>(acc[1], A[2], HI(F_QKV + 3));
        fence_async_smem();
        bar_arrive(BAR_K, 192);
        mma_tile_fold<2 * CS_QKV - 4>(acc[1], A[3], HI(F_QKV + 4), mu);
        mma_tile<false>(acc[2], A[1], HI(F_QKV + 1)); mma_tile<false>(acc[2], A[2], LO(F_QKV + 5));
        WG_WAIT(2); pin(acc[1]);
        scale_pack(acc[1], Q, rs0, rs1);
        tile_store(here(maddr) + TILE_BYTES, Q);
        fence_async_smem();
        bar_arrive(BAR_V, 160);
        mma_tile_fold<2 * CS_QKV - 2>(acc[2], A[3], HI(F_QKV + 5), mu);
        WG_WAIT(0); pin(acc[2]);
        scale_pack(acc[2], Q, rs0 * SM_SCALE_LOG2, rs1 * SM_SCALE_LOG2);
        frag_store(here(qslot), Q);
        bar_arrive(BAR_Q, 256);
        RELEASE(F_QKV, F_QKV + 5);
      } else {
        bar_sync(BAR_Q, 256);
#pragma unroll
        for (int s = 0; s < 4; s++) lds128(qslot + s * 512, Q[4 * s], Q[4 * s + 1], Q[4 * s + 2], Q[4 * s + 3]);
        if (w < 2) {
          const uint32_t v = w ? 0u : 0x3F803F80u;
#pragma unroll
          for (int s = 0; s < 4; s++) sts128(qslot + s * 512, v, v, v, v);
          fence_async_smem();
        }
      }
      bar_sync(BAR_ATT, 256);
      PROF_MARK(7);

      const int dir = cw == 0 ? -1 : 1;
      uint32_t tap[15];
      {
        const uint32_t* dwp = (const uint32_t*)(dw + 64 * r) + lane + 7 * (DM / 2);
#pragma unroll
        for (int k = 0; k < 15; k++) tap[k] = __ldg(dwp + dir * (k - 7) * (DM / 2));
      }

      float O[36];
      {
        float S[2][32];
        uint32_t P[2][16], nm[4];
#pragma unroll
        for (int i = 0; i < 32; i++) { S[0][i] = 0.f; S[1][i] = 0.f; }
        pin(Q); pin(S[0]);
        WG_FENCE();
        qk_tile(S[0], Q, RING_K + (SM_STG >> 4));
        WG_COMMIT();
#pragma unroll
        for (int i = 0; i < 36; i++) O[i] = 0.f;
#pragma unroll
        for (int i = 0; i < 16; i++) P[1][i] = 0u;
        WG_WAIT(0); pin(S[0]);
        const float m0 = tile_max<0>(S[0]), m1 = tile_max<2>(S[0]);
        nm[0] = pack2(q ? 0.f : -m0, 0.f); nm[1] = pack2(q ? 0.f : -m1, 0.f); nm[2] = 0u; nm[3] = 0u;
#pragma unroll
        for (int k = 0; k < 15; k++) asm("mul.rn.bf16x2 %0, %0, %1;" : "+r"(tap[k]) : "r"(0x3F003F00u));
        pin(nm); pin(O); pin(P[1]); pin(tap);
        uint32_t sk = wg, sv = F_SPARE % NSTAGE + wg;
        mbar_wait(SM_BASE + SM_FULL + sv * 8, 1);
        mbar_wait(SM_BASE + SM_FULL + sk * 8, 0);
        if (wg == 1) bar_sync(BAR_ATT, 256);
        PROF_MARK(8);
        WG_FENCE();
        qk_tile(S[0], Q, RING_K + sk * 1024);
        qk_shift(S[0], nm);
        WG_COMMIT();
        WG_WAIT(0); pin(S[0]); pin(S[1]);
        if (wg == 0) bar_arrive(BAR_ATT, 256);
#pragma unroll 1
        for (int it = 0; it < 4; it++) {
          const uint32_t sn = it >= 2 ? wg : sk + 4;
          uint32_t ok = 1;
          mbar_probe(ok, SM_BASE + SM_FULL + sn * 8, it >= 2);
          mbar_probe(ok, SM_BASE + SM_FULL + (sk + 2) * 8, it == 3);
          attn_step(S[0], S[1], P[0], P[1], O, Q, nm, RING_K + sk * 1024 + 512, RING_V + (sv * 1024 + 512) * V_STEP, true, it > 0);
          PROF_MARK(24 + it * 3);
          if (__builtin_expect(!ok, 0)) {
            mbar_wait(SM_BASE + SM_FULL + sn * 8, it >= 2);
            mbar_wait(SM_BASE + SM_FULL + (sk + 2) * 8, it == 3);
          }
          WG_WAIT(0); pin(O); pin(S[1]); pin(P[1]);
          asm volatile("{\n.reg .pred p;\nsetp.eq.u32 p, %2, 0;\n@p mbarrier.arrive.shared::cta.b64 _, [%0];\n@p mbarrier.arrive.shared::cta.b64 _, [%1];\n}"
                       :: "r"(SM_BASE + SM_EMPTY + sk * 8), "r"(SM_BASE + SM_EMPTY + sv * 8), "r"(lane) : "memory");
          PROF_MARK(25 + it * 3);
          sv = sk + 2; sk = sn;
          attn_step(S[1], S[0], P[1], P[0], O, Q, nm, RING_K + sk * 1024, RING_V + (sv * 1024) * V_STEP, it < 3, true);
          WG_WAIT(0); pin(O); pin(S[0]); pin(P[0]);
          PROF_MARK(26 + it * 3);
        }
        WG_FENCE();
        pv_tile(O, P[1], RING_V + (sv * 1024 + 512) * V_STEP, wg << 22);
        WG_COMMIT();
        announce<1>(sc, th == 0);
        WG_WAIT(0); pin(O);
      }
      PROF_MARK(9);

      {
        const uint32_t mo = stg + here(th) * 16;
        sts64(mo + 5 * 4096 + wg * 8, __float_as_uint(O[32]), __float_as_uint(O[34]));
        if (wg == 0) {
#pragma unroll
          for (int i = 4; i < 8; i++)
            sts128(mo + i * 2048, __float_as_uint(O[4 * i]), __float_as_uint(O[4 * i + 1]), __float_as_uint(O[4 * i + 2]), __float_as_uint(O[4 * i + 3]));
        } else {
#pragma unroll
          for (int i = 0; i < 4; i++)
            sts128(mo + i * 2048, __float_as_uint(O[4 * i]), __float_as_uint(O[4 * i + 1]), __float_as_uint(O[4 * i + 2]), __float_as_uint(O[4 * i + 3]));
#pragma unroll
          for (int i = 0; i < 16; i++) O[i] = O[16 + i];
        }
        bar_sync(BAR_MERGE, 256);
        uint32_t e[4];
        lds128(mo + 5 * 4096, e[0], e[1], e[2], e[3]);
        O[32] = __uint_as_float(e[0]) + __uint_as_float(e[2]); O[34] = __uint_as_float(e[1]) + __uint_as_float(e[3]);
#pragma unroll
        for (int i = 0; i < 4; i++) {
          lds128(mo + wg * TILE_BYTES + i * 2048, e[0], e[1], e[2], e[3]);
#pragma unroll
          for (int k = 0; k < 4; k++) O[4 * i + k] += __uint_as_float(e[k]);
        }
        const bool safe = O[32] > 0x1p-60f && O[32] < 0x1p60f && O[34] > 0x1p-60f && O[34] < 0x1p60f;
        if (__builtin_expect(__any_sync(0xffffffffu, !safe), 0)) attention_exact(O, Q, sc, batch * 4 + r, lane, wg);
        const float i0 = rcp_hw(O[32]), i1 = rcp_hw(O[34]);
#pragma unroll
        for (int i = 0; i < 8; i++) { const float v = (i & 1) ? i1 : i0; A[0][i] = pack2(O[2 * i] * v, O[2 * i + 1] * v); }
        A[0][0] &= ~1u; A[0][4] &= ~1u;
        uint4* dst = xp + X_AG1 + wg * 256;
        SCHED();
        st_vec(dst, A[0][0], A[0][1], A[0][2], A[0][3]);
        st_vec(dst + 128, A[0][4], A[0][5], A[0][6], A[0][7]);
        SCHED();
        if (TIMED) sent = clock_now();
      }
      if (wg == 1) {
        const uint32_t mo = stg + TILE_BYTES + here(th) * 16;
        sts128(mo, A[0][0], A[0][1], A[0][2], A[0][3]);
        sts128(mo + 2048, A[0][4], A[0][5], A[0][6], A[0][7]);
        bar_arrive(BAR_HALF, 256);
      } else {
        PROF_MARK(10);
        const uint32_t mo = stg + TILE_BYTES + here(th) * 16;
        bar_sync(BAR_HALF, 256);
        lds128(mo, A[0][8], A[0][9], A[0][10], A[0][11]);
        lds128(mo + 2048, A[0][12], A[0][13], A[0][14], A[0][15]);
        proj_residual<F_WO, 6>(A, sc, xp, maddr, 0, sent);
        PROF_MARK(12);
        float acc[2][32];
        mma_tile<true>(acc[0], A[0], LO(F_PW1)); mma_tile<true>(acc[1], A[0], HI(F_PW1));
        gather_first<1, X_AG0>(A, st, sc, xp, 0, sent);
        mma_tile<false>(acc[1], A[1], HI(F_PW1 + 1)); mma_tile<false>(acc[0], A[1], LO(F_PW1 + 1));
        gather_rest<1, X_AG0>(A, xp, 0);
        RELEASE(F_WO - 2, F_WO + 1);
        PROF_MARK(13);
        mma_tile<false>(acc[1], A[2], HI(F_PW1 + 2)); mma_tile<false>(acc[1], A[3], HI(F_PW1 + 3));
        WG_WAIT(2);
        RELEASE(F_WO + 2, F_WO - 3 + NREL);
        SCHED();
        uint32_t mu[4];
        const RowNorm n = stat_finish(sc, st, 0, 0.5f);
        const float rs0 = row0 < nvalid ? n.rs0 : 0.f, rs1 = row0 + 8 < nvalid ? n.rs1 : 0.f;
        mean_frag(mu, n, q == 0);
        mma_fold<2 * CS_PW1 + 2>(acc[1], mu);
        mma_tile<false>(acc[0], A[2], LO(F_PW1 + 2));
        mma_tile_fold<2 * CS_PW1>(acc[0], A[3], LO(F_PW1 + 3), mu);
        WG_WAIT(2); pin(acc[1]);
#pragma unroll
        for (int i = 0; i < 32; i++) acc[1][i] = tanh_hw(acc[1][i] * ((i & 2) ? rs1 : rs0));
#pragma unroll
        for (int i = 0; i < 32; i++) { const float rs = (i & 2) ? rs1 : rs0; acc[1][i] = fmaf(acc[1][i], rs, rs); }
        pin(acc[1]);
        SCHED();
        WG_WAIT(0); pin(acc[0]);
#pragma unroll
        for (int i = 0; i < 16; i++) A[0][i] = pack2(acc[0][2 * i] * acc[1][2 * i], acc[0][2 * i + 1] * acc[1][2 * i + 1]);
        const uint32_t ga = stg + TILE_BYTES + here(mrow) * G_PITCH + (lane >> 4) * 16;
#pragma unroll
        for (int s = 0; s < 4; s++) stsm4(ga + s * 32, &A[0][4 * s]);
      }
      {
        const uint32_t gsrc = stg + TILE_BYTES + (8 * cw - 7) * G_PITCH + lane * 4;
        const bool edge = cw == 0 || cw == 7;
        const bool nbr = cw == 0 ? t > 0 : t < 15;
        uint4* const hdst = &sc->x[b + 4 * dir][X_HALO + (cw == 0 ? 96 : 0) + lane];
        uint32_t in[22];
        bar_sync(BAR_G, 256);
        PROF_MARK(14);
        if (cw == 0) {
#pragma unroll
          for (int i = 14; i >= 0; i--) in[i] = lds32(gsrc + (21 - i) * G_PITCH);
        } else {
#pragma unroll
          for (int i = 14; i >= 0; i--) in[i] = lds32(gsrc + i * G_PITCH);
        }
        if (edge) {
          if (nbr) {
            st_vec(hdst, HALO_TAG, in[14], in[13], in[12]);
            st_vec(hdst + 32, HALO_TAG, in[11], in[10], in[9]);
            st_vec(hdst + 64, HALO_TAG, in[8], 0u, 0u);
          }
        } else {
#pragma unroll
          for (int i = 15; i < 22; i++) in[i] = lds32(gsrc + i * G_PITCH);
        }
        if (cw == 0) PROF_MARK0(40);
        uint32_t cv[8];
#pragma unroll
        for (int i = 0; i < 15; i++)
#pragma unroll
          for (int o = 0; o < 8; o++) {
            if (i == o) asm("mul.rn.bf16x2 %0, %1, %2;" : "=r"(cv[o]) : "r"(in[i]), "r"(tap[0]));
            if (i > o) asm("fma.rn.bf16x2 %0, %1, %2, %0;" : "+r"(cv[o]) : "r"(in[i]), "r"(tap[i - o]));
          }
        pin(cv);
        if (cw == 0) PROF_MARK0(41);
        if (edge) {
#pragma unroll
          for (int i = 15; i < 22; i++) in[i] = 0u;
          if (nbr) {
            const uint4* src = &sc->x[b][X_HALO + (cw == 0 ? 0 : 96) + lane];
            uint32_t e0, e1, e2, u0, u1, spin = 0;
#pragma unroll 1
            do {
              ld_vec(src, e0, in[15], in[16], in[17]);
              ld_vec(src + 32, e1, in[18], in[19], in[20]);
              ld_vec(src + 64, e2, in[21], u0, u1);
            } while (__any_sync(0xffffffffu, ((e0 ^ HALO_TAG) | (e1 ^ HALO_TAG) | (e2 ^ HALO_TAG)) != 0) && ++spin < SPIN_LIMIT);
          }
          announce<1>(sc, lane == 0);
        }
#pragma unroll
        for (int i = 15; i < 22; i++)
#pragma unroll
          for (int o = 0; o < 8; o++)
            if (i - o <= 14) asm("fma.rn.bf16x2 %0, %1, %2, %0;" : "+r"(cv[o]) : "r"(in[i]), "r"(tap[i - o]));
        if (cw == 0) PROF_MARK0(42);
        if (cw == 7) PROF_MARK0(43);
        const uint32_t fl = cw == 0 ? 7 : 0;
        const uint32_t cdst = (stg + cw * 1024 + lane * 4) ^ (fl * 144);
#pragma unroll
        for (int o = 0; o < 8; o++) {
          const float a = bf_lo(cv[o]), c = bf_hi(cv[o]);
          sts32(cdst ^ (o * 144), pack2(fmaf(a, tanh_hw(a), a), fmaf(c, tanh_hw(c), c)));
        }
      }
      if (wg == 1) {
        bar_arrive(BAR_C, 256);
        break;
      }
      bar_sync(BAR_C, 256);
      tile_load(here(maddr), A[0]);
      PROF_MARK(15);
      publish(xp + X_AG1, A[0], 1);
      proj_residual<F_PW2, 2>(A, sc, xp, maddr, 1, sent);
      PROF_MARK(17);
    }
  }
}

typedef CUresult (*EncodeFn)(CUtensorMap*, CUtensorMapDataType, cuuint32_t, void*, const cuuint64_t*, const cuuint64_t*,
                             const cuuint32_t*, const cuuint32_t*, CUtensorMapInterleave, CUtensorMapSwizzle,
                             CUtensorMapL2promotion, CUtensorMapFloatOOBfill);

void make_map(EncodeFn fn, CUtensorMap* m, const void* w, int rows, int cols, CUtensorMapSwizzle swz) {
  const cuuint64_t dims[2] = {(cuuint64_t)cols, (cuuint64_t)rows}, strides[1] = {(cuuint64_t)cols * 2};
  const cuuint32_t box[2] = {64, 64}, es[2] = {1, 1};
  fn(m, CU_TENSOR_MAP_DATA_TYPE_BFLOAT16, 2, const_cast<void*>(w), dims, strides, box, es, CU_TENSOR_MAP_INTERLEAVE_NONE,
     swz, CU_TENSOR_MAP_L2_PROMOTION_L2_128B, CU_TENSOR_MAP_FLOAT_OOB_FILL_NONE);
}

}

extern "C" void kernel_launch(void* const* d_in, const int* in_sizes, int n_in, void* d_out, int out_size) {
  static EncodeFn fn = nullptr;
  static Scratch* sc = nullptr;
  if (!fn) {
    void* f = nullptr;
    cudaDriverEntryPointQueryResult st;
    cudaGetDriverEntryPoint("cuTensorMapEncodeTiled", &f, cudaEnableDefault, &st);
    fn = (EncodeFn)f;
    void* raw = nullptr;
    cudaGetSymbolAddress(&raw, g_scratch);
    sc = (Scratch*)(((uintptr_t)raw + X_ALIGN - 1) & ~(uintptr_t)(X_ALIGN - 1));
    cudaFuncSetAttribute(conformer_kernel, cudaFuncAttributeMaxDynamicSharedMemorySize, SM_TOTAL);
  }
  typedef const __nv_bfloat16* W;
  const CUtensorMapSwizzle S = CU_TENSOR_MAP_SWIZZLE_128B;
  Params p;
  make_map(fn, &p.map[M_FF1A], d_in[1], 256, 1024, S);
  make_map(fn, &p.map[M_FF1B], d_in[2], 1024, 256, S);
  make_map(fn, &p.map[M_QKV], d_in[3], 256, 768, S);
  make_map(fn, &p.map[M_WO], d_in[4], 256, 256, S);
  make_map(fn, &p.map[M_PW1], d_in[5], 256, 512, S);
  make_map(fn, &p.map[M_PW2], d_in[7], 256, 256, S);
  make_map(fn, &p.map[M_FF2A], d_in[8], 256, 1024, S);
  make_map(fn, &p.map[M_FF2B], d_in[9], 1024, 256, S);
  p.w_ff1b = (W)d_in[2]; p.w_qkv = (W)d_in[3]; p.w_o = (W)d_in[4]; p.w_pw1 = (W)d_in[5];
  p.w_pw2 = (W)d_in[7]; p.w_ff2a = (W)d_in[8]; p.w_ff2b = (W)d_in[9];

  cudaLaunchConfig_t cfg = {};
  cfg.gridDim = dim3(NCTA);
  cfg.blockDim = dim3(384);
  cfg.dynamicSmemBytes = SM_TOTAL;
  cfg.stream = cudaStreamPerThread;
  cudaLaunchAttribute at[1];
  at[0].id = cudaLaunchAttributeCooperative;
  at[0].val.cooperative = 1;
  cfg.attrs = at;
  cfg.numAttrs = 1;
  cudaLaunchKernelEx(&cfg, conformer_kernel, sc, (__nv_bfloat16*)d_out, (W)d_in[6], (W)d_in[0], (W)d_in[1], p);
}
```

```cpp
#include <cuda_runtime.h>
#include <cuda_bf16.h>
#include <cuda.h>
#include <stdint.h>

namespace {

constexpr int T_SEQ = 1000;
constexpr int DM = 256;
constexpr int NCTA = 128;
constexpr int NSTAGE = 12;
constexpr uint32_t STAGE_BYTES = 16384;
constexpr uint32_t TILE_BYTES = 8192;
constexpr uint32_t SM_BASE = 1024;
constexpr uint32_t SM_STG = NSTAGE * STAGE_BYTES;
constexpr uint32_t SM_FULL = SM_STG + 32768;
constexpr uint32_t SM_EMPTY = SM_FULL + 96;
constexpr uint32_t SM_KVRDY = SM_FULL + 192;
constexpr uint32_t SM_EYE = SM_FULL + 256;
constexpr uint32_t SM_ONE = SM_FULL + 640;
constexpr uint32_t SM_CS = SM_FULL + 768;
constexpr uint32_t SM_TOTAL = SM_FULL + 3072;
constexpr int CS_FF2 = 0, CS_PW1 = 4, CS_QKV = 6;
constexpr uint32_t SPIN_LIMIT = 1u << 16;
constexpr float LN_EPS = 1e-5f;
constexpr float SM_SCALE_LOG2 = 0.125f * 1.4426950408889634f;
constexpr uint32_t G_PITCH = 144;
#define FSTR 8
#define TIMED 0
#define GD 400
#define RD 550
#define NREL 5
#define PF0 1
#define TF 1
#define TC 1
#define PF1 1400
#define PF2 2000
#define PF3 3500
#define CLR_PACE 150

constexpr int F_QKV = 16, F_SPARE = 22, F_KV = 24, F_WO = 40, F_PW1 = 42, F_PW2 = 46, F_TOTAL = 64;
enum { M_FF1A, M_FF1B, M_QKV, M_WO, M_PW1, M_PW2, M_FF2A, M_FF2B, M_COUNT };
enum { BAR_K = 1, BAR_V, BAR_Q, BAR_MERGE, BAR_G, BAR_C, BAR_WG1, BAR_GO, BAR_CS, BAR_ATT, BAR_INIT, BAR_HALF, BAR_RST };

struct Params {
  CUtensorMap map[M_COUNT];
  const __nv_bfloat16 *w_ff1b, *w_qkv, *w_o, *w_pw1, *w_pw2, *w_ff2a, *w_ff2b;
};

constexpr int X_RS = 0, X_AG1 = X_RS, X_HALO = X_RS + 512, X_AG0 = 1536, X_ST = 2048, X_SIZE = 4096;
constexpr uint32_t HALO_TAG = 0xFFFF0001u;
struct Scratch {
  uint4 x[NCTA][X_SIZE];
  uint4 kv[8][2][16][512];
  uint4 cs[576];
  uint32_t flag[8][32][FSTR];
  uint32_t step[NCTA][32];
};
constexpr size_t X_ALIGN = 4 * X_SIZE * sizeof(uint4);
__device__ uint8_t g_scratch[sizeof(Scratch) + X_ALIGN];
#define PROF_TIME(i)
#define PROF_MARK(i)
#define PROF_MARK2(i, j)
#define PROF_MARK0(i)
#define PROF_AT(a)

__device__ __forceinline__ void mbar_init(uint32_t bar, uint32_t cnt) {
  asm volatile("mbarrier.init.shared::cta.b64 [%0], %1;" :: "r"(bar), "r"(cnt) : "memory");
}
__device__ __forceinline__ void mbar_wait(uint32_t bar, uint32_t parity) {
  asm volatile("{\n.reg .pred p;\n.reg .u32 c;\nmov.u32 c, 0;\n"
               "WAIT_LOOP:\nmbarrier.try_wait.parity.shared::cta.b64 p, [%0], %1;\n@p bra WAIT_DONE;\n"
               "add.u32 c, c, 1;\nsetp.lt.u32 p, c, %2;\n@p bra WAIT_LOOP;\nWAIT_DONE:\n}"
               :: "r"(bar), "r"(parity), "n"(SPIN_LIMIT) : "memory");
}
__device__ __forceinline__ void mbar_arrive(uint32_t bar) {
  asm volatile("mbarrier.arrive.shared::cta.b64 _, [%0];" :: "r"(bar) : "memory");
}
#define bar_sync(id, n) asm volatile("bar.sync %0, %1;" :: "n"((int)(id)), "n"(n) : "memory")
#define bar_arrive(id, n) asm volatile("bar.arrive %0, %1;" :: "n"((int)(id)), "n"(n) : "memory")
__device__ __forceinline__ void fence_async_smem() { asm volatile("fence.proxy.async.shared::cta;" ::: "memory"); }

__device__ __forceinline__ void st_vec(uint4* p, uint32_t a, uint32_t b, uint32_t c, uint32_t d) {
  asm volatile("{\n.reg .b128 v;\n.reg .b64 lo, hi;\nmov.b64 lo, {%1, %2};\nmov.b64 hi, {%3, %4};\nmov.b128 v, {lo, hi};\n"
               "st.relaxed.gpu.global.b128 [%0], v;\n}" :: "l"(p), "r"(a), "r"(b), "r"(c), "r"(d) : "memory");
}
__device__ __forceinline__ void ld_vec(const uint4* p, uint32_t& a, uint32_t& b, uint32_t& c, uint32_t& d) {
  asm volatile("{\n.reg .b128 v;\n.reg .b64 lo, hi;\nld.relaxed.gpu.global.b128 v, [%4];\nmov.b128 {lo, hi}, v;\n"
               "mov.b64 {%0, %1}, lo;\nmov.b64 {%2, %3}, hi;\n}" : "=r"(a), "=r"(b), "=r"(c), "=r"(d) : "l"(p) : "memory");
}
__device__ __forceinline__ void sts128(uint32_t a, uint32_t x, uint32_t y, uint32_t z, uint32_t w) {
  asm volatile("st.shared.v4.u32 [%0], {%1, %2, %3, %4};" :: "r"(a), "r"(x), "r"(y), "r"(z), "r"(w) : "memory");
}
__device__ __forceinline__ void lds128(uint32_t a, uint32_t& x, uint32_t& y, uint32_t& z, uint32_t& w) {
  asm volatile("ld.shared.v4.u32 {%0, %1, %2, %3}, [%4];" : "=r"(x), "=r"(y), "=r"(z), "=r"(w) : "r"(a) : "memory");
}
__device__ __forceinline__ uint32_t lds32(uint32_t a) {
  uint32_t x; asm volatile("ld.shared.u32 %0, [%1];" : "=r"(x) : "r"(a) : "memory"); return x;
}
__device__ __forceinline__ void sts32(uint32_t a, uint32_t x) { asm volatile("st.shared.u32 [%0], %1;" :: "r"(a), "r"(x) : "memory"); }
__device__ __forceinline__ void sts64(uint32_t a, uint32_t x, uint32_t y) {
  asm volatile("st.shared.v2.u32 [%0], {%1, %2};" :: "r"(a), "r"(x), "r"(y) : "memory");
}
__device__ __forceinline__ void stsm4(uint32_t a, const uint32_t* r) {
  asm volatile("stmatrix.sync.aligned.m8n8.x4.shared.b16 [%0], {%1, %2, %3, %4};" :: "r"(a), "r"(r[0]), "r"(r[1]), "r"(r[2]), "r"(r[3]) : "memory");
}
__device__ __forceinline__ void ldsm4(uint32_t a, uint32_t* r) {
  asm volatile("ldmatrix.sync.aligned.m8n8.x4.shared.b16 {%0, %1, %2, %3}, [%4];" : "=r"(r[0]), "=r"(r[1]), "=r"(r[2]), "=r"(r[3]) : "r"(a) : "memory");
}
__device__ __forceinline__ uint32_t pack2(float lo, float hi) {
  uint32_t r; asm("cvt.rn.bf16x2.f32 %0, %1, %2;" : "=r"(r) : "f"(hi), "f"(lo)); return r;
}
__device__ __forceinline__ float bf_lo(uint32_t w) { return __uint_as_float(w << 16); }
__device__ __forceinline__ float bf_hi(uint32_t w) { return __uint_as_float(w & 0xffff0000u); }
__device__ __forceinline__ float tanh_hw(float x) { float y; asm volatile("tanh.approx.f32 %0, %1;" : "=f"(y) : "f"(x)); return y; }
__device__ __forceinline__ float rcp_hw(float x) { float y; asm("rcp.approx.ftz.f32 %0, %1;" : "=f"(y) : "f"(x)); return y; }
__device__ __forceinline__ float rsqrt_hw(float x) { float y; asm("rsqrt.approx.ftz.f32 %0, %1;" : "=f"(y) : "f"(x)); return y; }
__device__ __forceinline__ float ex2_hw(float x) { float y; asm("ex2.approx.ftz.f32 %0, %1;" : "=f"(y) : "f"(x)); return y; }

__device__ __forceinline__ uint32_t here(uint32_t v) { asm volatile("" : "+r"(v)); return v; }

#define SCHED() asm volatile("pmevent 1;" ::: "memory")
__device__ __forceinline__ void cp_async16(uint32_t dst, const void* src) {
  asm volatile("cp.async.cg.shared.global [%0], [%1], 16;" :: "r"(dst), "l"(src) : "memory");
}
__device__ __forceinline__ void cp_async_wait(int n) {
  if (n == 0) asm volatile("cp.async.wait_group 0;" ::: "memory");
  if (n == 1) asm volatile("cp.async.wait_group 1;" ::: "memory");
  if (n == 2) asm volatile("cp.async.wait_group 2;" ::: "memory");
  if (n == 3) asm volatile("cp.async.wait_group 3;" ::: "memory");
}
#define WG_FENCE() asm volatile("wgmma.fence.sync.aligned;" ::: "memory")
#define WG_COMMIT() asm volatile("wgmma.commit_group.sync.aligned;" ::: "memory")
#define WG_WAIT(n) asm volatile("wgmma.wait_group.sync.aligned %0;" :: "n"(n) : "memory")

template <int N> __device__ __forceinline__ void pin(float (&d)[N]) {
#pragma unroll
  for (int i = 0; i < N; i++) asm volatile("" : "+f"(d[i]) :: "memory");
}
template <int N> __device__ __forceinline__ void pin(uint32_t (&d)[N]) {
#pragma unroll
  for (int i = 0; i < N; i++) asm volatile("" : "+r"(d[i]) :: "memory");
}

#define WG_D32 "{%0, %1, %2, %3, %4, %5, %6, %7, %8, %9, %10, %11, %12, %13, %14, %15, %16, %17, %18, %19, %20, %21, %22, %23, %24, %25, %26, %27, %28, %29, %30, %31}"
template <int TB> __device__ __forceinline__ void wgmma64_acc(float (&d)[32], const uint32_t* a, uint64_t db) {
  asm volatile("wgmma.mma_async.sync.aligned.m64n64k16.f32.bf16.bf16 " WG_D32 ", {%32, %33, %34, %35}, %36, 1, 1, 1, %37;"
    : "+f"(d[0]), "+f"(d[1]), "+f"(d[2]), "+f"(d[3]), "+f"(d[4]), "+f"(d[5]), "+f"(d[6]), "+f"(d[7]),
      "+f"(d[8]), "+f"(d[9]), "+f"(d[10]), "+f"(d[11]), "+f"(d[12]), "+f"(d[13]), "+f"(d[14]), "+f"(d[15]),
      "+f"(d[16]), "+f"(d[17]), "+f"(d[18]), "+f"(d[19]), "+f"(d[20]), "+f"(d[21]), "+f"(d[22]), "+f"(d[23]),
      "+f"(d[24]), "+f"(d[25]), "+f"(d[26]), "+f"(d[27]), "+f"(d[28]), "+f"(d[29]), "+f"(d[30]), "+f"(d[31])
    : "r"(a[0]), "r"(a[1]), "r"(a[2]), "r"(a[3]), "l"(db), "n"(TB));
}
template <int TB> __device__ __forceinline__ void wgmma64_reuse(float (&d)[32], const uint32_t* a, uint64_t db, uint32_t zero) {
  asm volatile("{\n.reg .pred p;\nsetp.ne.u32 p, %37, 0;\nwgmma.mma_async.sync.aligned.m64n64k16.f32.bf16.bf16 " WG_D32 ", {%32, %33, %34, %35}, %36, p, 1, 1, %38;\n}"
    : "+f"(d[0]), "+f"(d[1]), "+f"(d[2]), "+f"(d[3]), "+f"(d[4]), "+f"(d[5]), "+f"(d[6]), "+f"(d[7]),
      "+f"(d[8]), "+f"(d[9]), "+f"(d[10]), "+f"(d[11]), "+f"(d[12]), "+f"(d[13]), "+f"(d[14]), "+f"(d[15]),
      "+f"(d[16]), "+f"(d[17]), "+f"(d[18]), "+f"(d[19]), "+f"(d[20]), "+f"(d[21]), "+f"(d[22]), "+f"(d[23]),
      "+f"(d[24]), "+f"(d[25]), "+f"(d[26]), "+f"(d[27]), "+f"(d[28]), "+f"(d[29]), "+f"(d[30]), "+f"(d[31])
    : "r"(a[0]), "r"(a[1]), "r"(a[2]), "r"(a[3]), "l"(db), "r"(zero), "n"(TB));
}
template <int TB> __device__ __forceinline__ void wgmma64_set(float (&d)[32], const uint32_t* a, uint64_t db) {
  asm volatile("wgmma.mma_async.sync.aligned.m64n64k16.f32.bf16.bf16 " WG_D32 ", {%32, %33, %34, %35}, %36, 0, 1, 1, %37;"
    : "=f"(d[0]), "=f"(d[1]), "=f"(d[2]), "=f"(d[3]), "=f"(d[4]), "=f"(d[5]), "=f"(d[6]), "=f"(d[7]),
      "=f"(d[8]), "=f"(d[9]), "=f"(d[10]), "=f"(d[11]), "=f"(d[12]), "=f"(d[13]), "=f"(d[14]), "=f"(d[15]),
      "=f"(d[16]), "=f"(d[17]), "=f"(d[18]), "=f"(d[19]), "=f"(d[20]), "=f"(d[21]), "=f"(d[22]), "=f"(d[23]),
      "=f"(d[24]), "=f"(d[25]), "=f"(d[26]), "=f"(d[27]), "=f"(d[28]), "=f"(d[29]), "=f"(d[30]), "=f"(d[31])
    : "r"(a[0]), "r"(a[1]), "r"(a[2]), "r"(a[3]), "l"(db), "n"(TB));
}

__device__ __forceinline__ void wgmma72_acc(float (&d)[36], const uint32_t* a, uint64_t db) {
  asm volatile("wgmma.mma_async.sync.aligned.m64n72k16.f32.bf16.bf16 {%0, %1, %2, %3, %4, %5, %6, %7, %8, %9, %10, %11, %12, %13, %14, %15, %16, %17, %18, %19, %20, %21, %22, %23, %24, %25, %26, %27, %28, %29, %30, %31, %32, %33, %34, %35}, {%36, %37, %38, %39}, %40, 1, 1, 1, 1;"
    : "+f"(d[0]), "+f"(d[1]), "+f"(d[2]), "+f"(d[3]), "+f"(d[4]), "+f"(d[5]), "+f"(d[6]), "+f"(d[7]), "+f"(d[8]),
      "+f"(d[9]), "+f"(d[10]), "+f"(d[11]), "+f"(d[12]), "+f"(d[13]), "+f"(d[14]), "+f"(d[15]), "+f"(d[16]), "+f"(d[17]),
      "+f"(d[18]), "+f"(d[19]), "+f"(d[20]), "+f"(d[21]), "+f"(d[22]), "+f"(d[23]), "+f"(d[24]), "+f"(d[25]), "+f"(d[26]),
      "+f"(d[27]), "+f"(d[28]), "+f"(d[29]), "+f"(d[30]), "+f"(d[31]), "+f"(d[32]), "+f"(d[33]), "+f"(d[34]), "+f"(d[35])
    : "r"(a[0]), "r"(a[1]), "r"(a[2]), "r"(a[3]), "l"(db));
}
__device__ __forceinline__ void wgmma16_acc(float* d, const uint32_t* a, uint64_t db) {
  asm volatile("wgmma.mma_async.sync.aligned.m64n16k16.f32.bf16.bf16 {%0, %1, %2, %3, %4, %5, %6, %7}, {%8, %9, %10, %11}, %12, 1, 1, 1, 0;"
    : "+f"(d[0]), "+f"(d[1]), "+f"(d[2]), "+f"(d[3]), "+f"(d[4]), "+f"(d[5]), "+f"(d[6]), "+f"(d[7])
    : "r"(a[0]), "r"(a[1]), "r"(a[2]), "r"(a[3]), "l"(db));
}
__device__ __forceinline__ void hmma(float (&d)[4], const uint32_t* a, uint32_t b0, uint32_t b1) {
  asm("mma.sync.aligned.m16n8k16.row.col.f32.bf16.bf16.f32 {%0, %1, %2, %3}, {%4, %5, %6, %7}, {%8, %9}, {%0, %1, %2, %3};"
    : "+f"(d[0]), "+f"(d[1]), "+f"(d[2]), "+f"(d[3]) : "r"(a[0]), "r"(a[1]), "r"(a[2]), "r"(a[3]), "r"(b0), "r"(b1));
}

__device__ __forceinline__ void hmma8(float (&d)[4], const uint32_t* a, uint32_t b0) {
  asm("mma.sync.aligned.m16n8k8.row.col.f32.bf16.bf16.f32 {%0, %1, %2, %3}, {%4, %5}, {%6}, {%0, %1, %2, %3};"
    : "+f"(d[0]), "+f"(d[1]), "+f"(d[2]), "+f"(d[3]) : "r"(a[0]), "r"(a[1]), "r"(b0));
}

template <bool FIRST> __device__ __forceinline__ void mma_tile(float (&d)[32], const uint32_t (&a)[16], uint64_t db) {
  WG_FENCE();
#pragma unroll
  for (int s = 0; s < 4; s++) {
    if (FIRST && s == 0) wgmma64_set<1>(d, &a[0], db); else wgmma64_acc<1>(d, &a[4 * s], db + s * 128);
  }
  WG_COMMIT();
}
__device__ __forceinline__ void mma_tile_reuse(float (&d)[32], const uint32_t (&a)[16], uint64_t db) {
  WG_FENCE();
  wgmma64_reuse<1>(d, &a[0], db, blockIdx.y);
#pragma unroll
  for (int s = 1; s < 4; s++) wgmma64_acc<1>(d, &a[4 * s], db + s * 128);
  WG_COMMIT();
}
template <int ROW> __device__ __forceinline__ void fold_step(float (&d)[32], const uint32_t (&mu)[4]) {
  wgmma64_acc<1>(d, mu, (uint64_t)((SM_BASE + SM_CS + ROW * 128) >> 4) | (uint64_t(1) << 16) | (uint64_t(1) << 62));
}
template <int ROW> __device__ __forceinline__ void mma_fold(float (&d)[32], const uint32_t (&mu)[4]) {
  WG_FENCE();
  fold_step<ROW>(d, mu);
  WG_COMMIT();
}
template <int ROW> __device__ __forceinline__ void mma_tile_fold(float (&d)[32], const uint32_t (&a)[16], uint64_t db, const uint32_t (&mu)[4]) {
  WG_FENCE();
#pragma unroll
  for (int s = 0; s < 4; s++) wgmma64_acc<1>(d, &a[4 * s], db + s * 128);
  fold_step<ROW>(d, mu);
  WG_COMMIT();
}
__device__ __forceinline__ void mma_add_half(float (&d)[32], const uint32_t (&a)[16]) {
  const uint64_t db = (uint64_t)((SM_BASE + SM_EYE) >> 4) | (uint64_t(8) << 16) | (uint64_t(8) << 32);
  WG_FENCE();
#pragma unroll
  for (int s = 0; s < 4; s++) wgmma16_acc(&d[8 * s], &a[4 * s], db);
  WG_COMMIT();
}
#define ACQUIRE(f) mbar_wait(SM_BASE + SM_FULL + ((f) % NSTAGE) * 8, ((f) / NSTAGE) & 1)
__device__ __forceinline__ void mbar_probe(uint32_t& ok, uint32_t bar, uint32_t parity) {
  asm volatile("{\n.reg .pred p;\nmbarrier.test_wait.parity.shared::cta.b64 p, [%1], %2;\nselp.u32 %0, %0, 0, p;\n}"
               : "+r"(ok) : "r"(bar), "r"(parity) : "memory");
}
template <int F, int N> __device__ __forceinline__ uint32_t probe_n() {
  static_assert(F % NSTAGE + N <= NSTAGE, "stages must not wrap");
  uint32_t ok = 1;
#pragma unroll
  for (int i = 0; i < N; i++) mbar_probe(ok, SM_BASE + SM_FULL + (F % NSTAGE + i) * 8, (F / NSTAGE) & 1);
  return ok;
}
template <int F, int N> __device__ __forceinline__ void settle_n(uint32_t ok) {
  if (__builtin_expect(!ok, 0)) {
#pragma unroll 1
    for (int i = 0; i < N; i++) mbar_wait(SM_BASE + SM_FULL + (F % NSTAGE + i) * 8, (F / NSTAGE) & 1);
  }
}
template <int F, int N> __device__ __forceinline__ void acquire_n() { settle_n<F, N>(probe_n<F, N>()); }
#define RELEASE(f0, f1) do { if (lane == 0) { _Pragma("unroll") for (int f_ = (f0); f_ <= (f1); f_++) mbar_arrive(SM_BASE + SM_EMPTY + (f_ % NSTAGE) * 8); } } while (0)
constexpr uint64_t RING = (uint64_t)(SM_BASE >> 4) | (uint64_t(1) << 16) | (uint64_t(64) << 32) | (uint64_t(1) << 62);
#define LO(f) (RING + ((f) % NSTAGE) * 1024)
#define HI(f) (RING + ((f) % NSTAGE) * 1024 + 512)

template <int C> __device__ __forceinline__ uint4* peer(uint4* p) {
  asm volatile("" : "+l"(p));
  return (uint4*)((uintptr_t)p ^ (C * X_SIZE * sizeof(uint4)));
}
__device__ __forceinline__ uint32_t clock_now() { uint32_t c; asm volatile("mov.u32 %0, %%clock;" : "=r"(c) :: "memory"); return c; }
__device__ __forceinline__ void publish(uint4* dst, uint32_t (&a)[16], uint32_t tag) {
#pragma unroll
  for (int s = 0; s < 4; s++) a[4 * s] = (a[4 * s] & ~1u) | tag;
  pin(a);
  SCHED();
#pragma unroll
  for (int s = 0; s < 4; s++) st_vec(dst + s * 128, a[4 * s], a[4 * s + 1], a[4 * s + 2], a[4 * s + 3]);
  SCHED();
}
__device__ __forceinline__ void fetch(const uint4* src, uint32_t (&a)[16]) {
#pragma unroll
  for (int s = 0; s < 4; s++) ld_vec(src + s * 128, a[4 * s], a[4 * s + 1], a[4 * s + 2], a[4 * s + 3]);
}
__device__ __forceinline__ uint32_t miss(const uint32_t (&a)[16], uint32_t tag) {
  return (a[0] ^ tag) | (a[4] ^ tag) | (a[8] ^ tag) | (a[12] ^ tag);
}
__device__ __forceinline__ bool stale(uint32_t v) { return __any_sync(0xffffffffu, here(v) & 1u); }
template <int N = 2> __device__ __forceinline__ void announce(Scratch* sc, bool leader) {
  asm volatile("{\n.reg .pred p;\nsetp.ne.u32 p, %1, 0;\n@p red.relaxed.gpu.global.add.u32 [%0], %2;\n}"
               :: "l"(sc->step[blockIdx.x]), "r"((uint32_t)leader), "n"(N) : "memory");
}
__device__ __forceinline__ uint32_t launch_index(const Scratch* sc) { return *(const volatile uint32_t*)sc->step[blockIdx.x] >> 4; }
__device__ __forceinline__ void stat_fetch(const Scratch* sc, uint32_t (&st)[4]) {
  const uint32_t th = here(threadIdx.x);
  ld_vec(&sc->x[(blockIdx.x & ~3u) + (th & 3)][X_ST + (th >> 2)], st[0], st[1], st[2], st[3]);
}
template <int C, int SLOT> __device__ __forceinline__ void gather_first(uint32_t (&A)[4][16], uint32_t (&st)[4], const Scratch* sc, uint4* xp, uint32_t tag, uint32_t sent) {
  if (TIMED) { while (clock_now() - sent < GD) {} } else bar_sync(BAR_GO, 160);
  fetch(peer<1>(xp) + SLOT, A[1]); fetch(peer<2>(xp) + SLOT, A[2]); fetch(peer<3>(xp) + SLOT, A[3]);
  if (SLOT == X_AG0) stat_fetch(sc, st);
  uint32_t spin = 0;
  while (__builtin_expect(stale(miss(A[1], tag) | miss(A[C], tag)), 0) && ++spin < SPIN_LIMIT) {
    fetch(peer<1>(xp) + SLOT, A[1]);
    if (C == 2) fetch(peer<2>(xp) + SLOT, A[2]);
  }
}
template <int C, int SLOT> __device__ __forceinline__ void gather_rest(uint32_t (&A)[4][16], uint4* xp, uint32_t tag) {
  SCHED();
  uint32_t spin = 0;
  while (__builtin_expect(stale(miss(A[C + 1], tag) | miss(A[3], tag)), 0) && ++spin < SPIN_LIMIT) {
    if (C == 1) fetch(peer<2>(xp) + SLOT, A[2]);
    fetch(peer<3>(xp) + SLOT, A[3]);
  }
}
__device__ __forceinline__ void pack_acc(const float (&d)[32], uint32_t (&a)[16]) {
#pragma unroll
  for (int i = 0; i < 16; i++) a[i] = pack2(d[2 * i], d[2 * i + 1]);
}
__device__ __forceinline__ void frag_store(uint32_t slot, const uint32_t (&a)[16]) {
#pragma unroll
  for (int s = 0; s < 4; s++) sts128(slot + s * 512, a[4 * s], a[4 * s + 1], a[4 * s + 2], a[4 * s + 3]);
}
__device__ __forceinline__ void tile_store(uint32_t maddr, const uint32_t (&a)[16]) {
#pragma unroll
  for (int s = 0; s < 4; s++) stsm4(maddr ^ (s << 5), &a[4 * s]);
}
__device__ __forceinline__ void tile_load(uint32_t maddr, uint32_t (&a)[16]) {
#pragma unroll
  for (int s = 0; s < 4; s++) ldsm4(maddr ^ (s << 5), &a[4 * s]);
}

__device__ __forceinline__ void res_load(uint32_t maddr, float (&d)[32]) {
  uint32_t a[16];
  tile_load(here(maddr) + 3 * TILE_BYTES, a);
#pragma unroll
  for (int i = 0; i < 16; i++) { d[2 * i] = bf_lo(a[i]); d[2 * i + 1] = bf_hi(a[i]); }
  pin(d);
}

struct RowAcc { float s[2][4], u[2][4], v[2][4]; };
__device__ __forceinline__ void row_sums(RowAcc& t, const uint32_t (&a)[16]) {
#pragma unroll
  for (int s = 0; s < 4; s++) hmma(t.s[s & 1], &a[4 * s], 0x3F803F80u, 0x3F803F80u);
}
__device__ __forceinline__ void row_gram(RowAcc& t, const uint32_t (&a)[16]) {
#pragma unroll
  for (int s = 0; s < 8; s++) {
    hmma8(t.u[s & 1], &a[2 * s], a[2 * s]);
    hmma8(t.v[s & 1], &a[2 * s], a[2 * s + 1]);
  }
}
__device__ __forceinline__ float2 row_squares(const RowAcc& t, bool odd) {
  return make_float2(odd ? t.u[0][1] + t.u[1][1] : t.u[0][0] + t.u[1][0], odd ? t.v[0][3] + t.v[1][3] : t.v[0][2] + t.v[1][2]);
}
__device__ __forceinline__ void stat_publish(const uint32_t (&a)[16], Scratch* sc, uint32_t th, uint32_t tag) {
  RowAcc t = {};
  row_sums(t, a);
  row_gram(t, a);
  const float2 q = row_squares(t, th & 4);
  if ((th & 3) == ((th >> 3) & 3))
    st_vec(&sc->x[blockIdx.x][X_ST + (th >> 2)], (__float_as_uint(t.s[0][0] + t.s[1][0]) & ~1u) | tag, __float_as_uint(q.x),
           __float_as_uint(t.s[0][2] + t.s[1][2]), __float_as_uint(q.y));
}
struct RowNorm { float m0, rs0, m1, rs1; };
__device__ __forceinline__ RowNorm row_norm(float s0, float q0, float s1, float q1, float scale) {
  RowNorm n;
  n.m0 = s0 * (1.f / DM); n.m1 = s1 * (1.f / DM);
  n.rs0 = scale * rsqrt_hw(fmaxf(fmaf(-n.m0, n.m0, q0 * (1.f / DM)), 0.f) + LN_EPS);
  n.rs1 = scale * rsqrt_hw(fmaxf(fmaf(-n.m1, n.m1, q1 * (1.f / DM)), 0.f) + LN_EPS);
  return n;
}
__device__ __forceinline__ RowNorm stat_finish(const Scratch* sc, uint32_t (&st)[4], uint32_t tag, float scale) {
  uint32_t spin = 0;
  while (__builtin_expect(stale(st[0] ^ tag), 0) && ++spin < SPIN_LIMIT) stat_fetch(sc, st);
  float f[4];
#pragma unroll
  for (int i = 0; i < 4; i++) {
    f[i] = __uint_as_float(st[i]);
    f[i] += __shfl_xor_sync(0xffffffffu, f[i], 1);
    f[i] += __shfl_xor_sync(0xffffffffu, f[i], 2);
  }
  return row_norm(f[0], f[1], f[2], f[3], scale);
}
__device__ __forceinline__ void mean_frag(uint32_t (&mu)[4], const RowNorm& n, bool sel) {
  const float a = sel ? -n.m0 : 0.f, c = sel ? -n.m1 : 0.f;
  mu[0] = pack2(a, a); mu[1] = pack2(c, c);
  const float al = a - bf_lo(mu[0]), cl = c - bf_lo(mu[1]);
  mu[2] = pack2(al, al); mu[3] = pack2(cl, cl);
  pin(mu);
}
__device__ __forceinline__ void centre(uint32_t (&a)[16], uint32_t m0, uint32_t m1) {
#pragma unroll
  for (int i = 0; i < 16; i++) asm("sub.rn.bf16x2 %0, %0, %1;" : "+r"(a[i]) : "r"((i & 1) ? m1 : m0));
  pin(a);
}
__device__ __forceinline__ void scale_pack(const float (&d)[32], uint32_t (&a)[16], float rs0, float rs1) {
#pragma unroll
  for (int i = 0; i < 16; i++) { const float rs = (i & 1) ? rs1 : rs0; a[i] = pack2(d[2 * i] * rs, d[2 * i + 1] * rs); }
}
template <int S> __device__ __forceinline__ void silu_seg(float (&acc)[4][32], float (&tn)[2][4], uint32_t (&H)[4][16], float rs0, float rs1) {
  if (S >= 2) {
    const float* h = &acc[(S - 2) >> 3][4 * ((S - 2) & 7)];
    const float* v = tn[S & 1];
    uint32_t* o = &H[(S - 2) >> 3][2 * ((S - 2) & 7)];
    o[0] = pack2(fmaf(h[0], v[0], h[0]), fmaf(h[1], v[1], h[1]));
    o[1] = pack2(fmaf(h[2], v[2], h[2]), fmaf(h[3], v[3], h[3]));
    asm volatile("" : "+r"(o[0]), "+r"(o[1]));
  }
  if (S >= 1 && S <= 32) {
#pragma unroll
    for (int k = 0; k < 4; k++) tn[(S - 1) & 1][k] = tanh_hw(acc[((S - 1) >> 3) & 3][4 * ((S - 1) & 7) + k]);
  }
  if (S < 32) {
    float* h = &acc[(S >> 3) & 3][4 * (S & 7)];
    h[0] *= rs0; h[1] *= rs0; h[2] *= rs1; h[3] *= rs1;
    asm volatile("" : "+f"(h[0]), "+f"(h[1]), "+f"(h[2]), "+f"(h[3]));
  }
  SCHED();
}
template <int S0, int S1> __device__ __forceinline__ void silu_segs(float (&acc)[4][32], float (&tn)[2][4], uint32_t (&H)[4][16], float rs0, float rs1) {
  silu_seg<S0>(acc, tn, H, rs0, rs1);
  if constexpr (S0 + 1 < S1) silu_segs<S0 + 1, S1>(acc, tn, H, rs0, rs1);
}
template <int HALF> __device__ __forceinline__ void send_half(uint4* dst, const float (&d)[32], uint32_t tag) {
  uint32_t o[8];
#pragma unroll
  for (int i = 0; i < 8; i++) o[i] = pack2(d[16 * HALF + 2 * i], d[16 * HALF + 2 * i + 1]);
  o[0] = (o[0] & ~1u) | tag; o[4] = (o[4] & ~1u) | tag;
  pin(o);
  SCHED();
  st_vec(dst + HALF * 256, o[0], o[1], o[2], o[3]);
  st_vec(dst + HALF * 256 + 128, o[4], o[5], o[6], o[7]);
  SCHED();
}
__device__ __forceinline__ void send_residual(uint32_t (&a)[16], Scratch* sc, uint4* xp, uint32_t maddr, uint32_t tag, uint32_t& sent) {
  const uint32_t exact[4] = {a[0], a[4], a[8], a[12]};
  publish(xp + X_AG0, a, tag);
  if (TIMED) sent = clock_now();
  const uint32_t th = here(threadIdx.x);
  stat_publish(a, sc, th, tag);
  tile_store(here(maddr) + 3 * TILE_BYTES, a);
  stsm4(SM_BASE + SM_STG + 3 * TILE_BYTES + (th >> 5) * 2048 + (th & 7) * 128 + ((((th >> 2) & 6) ^ (th & 7)) << 4), exact);
}
template <int F, int N> __device__ __forceinline__ void proj_residual(uint32_t (&A)[4][16], Scratch* sc, uint4* xp, uint32_t maddr,
                                                                      uint32_t tag, uint32_t& sent) {
  float acc[32];
  if (TIMED && F == F_PW2) sent = clock_now();
  uint32_t st[4];
  acquire_n<F, N>();
  if (F == F_PW2) acquire_n<0, 5>();
  res_load(maddr, acc);
  mma_tile<false>(acc, A[0], LO(F));
  gather_first<2, X_AG1>(A, st, sc, xp, tag, sent);
  announce(sc, threadIdx.x == 0);
  mma_tile<false>(acc, A[1], HI(F));
  mma_tile<false>(acc, A[2], LO(F + 1));
  gather_rest<2, X_AG1>(A, xp, tag);
  PROF_MARK0(F == F_WO ? 11 : 16);
  mma_tile<false>(acc, A[3], HI(F + 1));
  WG_WAIT(0); pin(acc);
  pack_acc(acc, A[0]);
  send_residual(A[0], sc, xp, maddr, tag, sent);
}

__device__ __forceinline__ uint64_t ring_desc(uint32_t lo) { return (RING & ~uint64_t(0xFFFFFFFFu)) | lo; }
__device__ __forceinline__ void qk_tile(float (&S)[32], const uint32_t (&Q)[16], uint32_t dk) {
  wgmma64_reuse<0>(S, &Q[0], ring_desc(dk), blockIdx.y);
#pragma unroll
  for (int s = 1; s < 4; s++) wgmma64_acc<0>(S, &Q[4 * s], ring_desc(dk + s * 2));
}
__device__ __forceinline__ void qk_shift(float (&S)[32], const uint32_t (&nm)[4]) { wgmma64_acc<0>(S, nm, (uint64_t)((SM_BASE + SM_ONE) >> 4)); }
constexpr uint32_t RING_K = (uint32_t)RING, V_STEP = 1u - (1u << 16);
constexpr uint32_t RING_V = (SM_BASE >> 4) | (((SM_STG + 2 * TILE_BYTES) >> 4) << 16);
__device__ __forceinline__ void pv_tile(float (&O)[36], const uint32_t (&P)[16], uint32_t dv, uint32_t pad) {
#pragma unroll
  for (int s = 0; s < 4; s++) wgmma72_acc(O, &P[4 * s], ring_desc(dv + s * 128 * V_STEP + (s < 2 ? 0 : (s - 1) * pad)));
}
__device__ __forceinline__ void attn_step(const float (&Sc)[32], float (&Sn)[32], uint32_t (&Pc)[16], uint32_t (&Pp)[16], float (&O)[36],
                                          const uint32_t (&Q)[16], const uint32_t (&nm)[4], uint32_t dk, uint32_t dv, bool next, bool prev) {
  if (next) {
    WG_FENCE();
    qk_tile(Sn, Q, dk);
    qk_shift(Sn, nm);
  }
  if (prev) {
    WG_FENCE();
    pv_tile(O, Pp, dv, 0);
  }
  WG_COMMIT();
  SCHED();
#pragma unroll
  for (int i = 0; i < 16; i++) Pc[i] = pack2(ex2_hw(Sc[2 * i]), ex2_hw(Sc[2 * i + 1]));
  pin(Pc);
  SCHED();
}
__device__ __forceinline__ void load_taps(uint32_t (&tap)[15], const __nv_bfloat16* dw, int dir) {
  const uint32_t* src = (const uint32_t*)(dw + 64 * (blockIdx.x & 3)) + (here(threadIdx.x) & 31) + 7 * (DM / 2);
#pragma unroll
  for (int k = 0; k < 15; k++) tap[k] = __ldg(src + dir * (k - 7) * (DM / 2));
}
__device__ __forceinline__ void halve_taps(uint32_t (&tap)[15]) {
#pragma unroll
  for (int k = 0; k < 15; k++) asm("mul.rn.bf16x2 %0, %0, %1;" : "+r"(tap[k]) : "r"(0x3F003F00u));
  pin(tap);
}
__device__ __forceinline__ void attention_exact(float (&O)[36], const uint32_t (&Q)[16], const Scratch* sc, int bh, int lane, int half) {
  const char* kb = (const char*)&sc->kv[bh][0][0][0];
  const char* vb = (const char*)&sc->kv[bh][1][0][0];
  const int g = lane >> 2, q = lane & 3;
  float m0 = -INFINITY, m1 = -INFINITY, l0 = 0.f, l1 = 0.f;
  float o[4][4] = {};
#pragma unroll 1
  for (int k0 = 0; k0 < T_SEQ; k0 += 8) {
    float s[4] = {0.f, 0.f, 0.f, 0.f};
#pragma unroll
    for (int c = 0; c < 8; c++) hmma8(s, &Q[2 * c], __ldcg((const uint32_t*)(kb + (k0 + g) * 128 + ((c ^ g) << 4) + q * 4)));
    float n0 = fmaxf(s[0], s[1]), n1 = fmaxf(s[2], s[3]);
    n0 = fmaxf(n0, __shfl_xor_sync(0xffffffffu, n0, 1)); n1 = fmaxf(n1, __shfl_xor_sync(0xffffffffu, n1, 1));
    n0 = fmaxf(m0, fmaxf(n0, __shfl_xor_sync(0xffffffffu, n0, 2))); n1 = fmaxf(m1, fmaxf(n1, __shfl_xor_sync(0xffffffffu, n1, 2)));
    const float a0 = ex2_hw(m0 - n0), a1 = ex2_hw(m1 - n1);
    m0 = n0; m1 = n1;
    const uint32_t pp[2] = {pack2(ex2_hw(s[0] - n0), ex2_hw(s[1] - n0)), pack2(ex2_hw(s[2] - n1), ex2_hw(s[3] - n1))};
    l0 = fmaf(l0, a0, bf_lo(pp[0]) + bf_hi(pp[0])); l1 = fmaf(l1, a1, bf_lo(pp[1]) + bf_hi(pp[1]));
#pragma unroll
    for (int j = 0; j < 4; j++) {
      const int c = 4 * half + j;
      const uint32_t v0 = __ldcg((const uint16_t*)(vb + (k0 + 2 * q) * 128 + ((c ^ (2 * q)) << 4) + g * 2));
      const uint32_t v1 = __ldcg((const uint16_t*)(vb + (k0 + 2 * q + 1) * 128 + ((c ^ (2 * q + 1)) << 4) + g * 2));
      o[j][0] *= a0; o[j][1] *= a0; o[j][2] *= a1; o[j][3] *= a1;
      hmma8(o[j], pp, v0 | (v1 << 16));
    }
  }
  l0 += __shfl_xor_sync(0xffffffffu, l0, 1); l1 += __shfl_xor_sync(0xffffffffu, l1, 1);
  O[32] = l0 + __shfl_xor_sync(0xffffffffu, l0, 2); O[34] = l1 + __shfl_xor_sync(0xffffffffu, l1, 2);
#pragma unroll
  for (int i = 0; i < 16; i++) O[i] = o[i >> 2][i & 3];
}

__device__ __forceinline__ uint32_t fill_entry(int f, int r) {
  int m, x = r, y, dx = 0;
  if (f < F_QKV || f >= 48) {
    const int i = f & 15;
    m = f < F_QKV ? M_FF1A : M_FF2A;
    if (i < 8) { x = 4 * r + ((0xE2u >> i) & 1) * 2; y = r ^ ((0xE790u >> (2 * i)) & 3); dx = 1; }
    else { m++; x = r ^ (((i >> 1) - 3) & 3); y = 4 * r + 2 * (i & 1); }
  } else if (f < F_KV) {
    const int i = f - F_QKV;
    m = M_QKV;
    if (i == 1 || i >= 5) { y = r ^ (i == 1 ? 0 : 2); }
    else { x = 4 + r; y = r ^ (i ? i - 1 : 0); dx = 4; }
  } else if (f >= F_PW1 && f < F_PW2) {
    m = M_PW1; y = r ^ (f - F_PW1); dx = 4;
  } else {
    m = f < F_PW1 ? M_WO : M_PW2; y = r ^ ((f & 1) * 2);
  }
  return m | (x << 4) | (y << 8) | (dx << 16);
}
__device__ __forceinline__ void tma_fill(uint32_t st, const CUtensorMap* map, uint32_t x, uint32_t y, uint32_t x2, uint32_t y2) {
  asm volatile("{\n.reg .pred p;\nelect.sync _|p, 0xffffffff;\n"
               "@p mbarrier.arrive.expect_tx.shared::cta.b64 _, [%1], 16384;\n"
               "@p cp.async.bulk.tensor.2d.shared::cluster.global.mbarrier::complete_tx::bytes [%0], [%2, {%3, %4}], [%1];\n"
               "@p cp.async.bulk.tensor.2d.shared::cluster.global.mbarrier::complete_tx::bytes [%0 + 8192], [%2, {%5, %6}], [%1];\n}"
               :: "r"(SM_BASE + st * STAGE_BYTES), "r"(SM_BASE + SM_FULL + st * 8), "l"(map), "r"(x), "r"(y), "r"(x2), "r"(y2) : "memory");
}
template <int F0, int N> __device__ __forceinline__ void weight_fills(const Params& p, uint32_t entry) {
  uint32_t st = F0 % NSTAGE, parity = ((F0 / NSTAGE) & 1) ^ 1, e = __shfl_sync(0xffffffffu, entry, 0);
#pragma unroll 1
  for (int i = 1; i <= N; i++) {
    const uint32_t x = (e << 2) & 0x3C0, y = (e >> 2) & 0x3FC0, dx = (e >> 16) << 6;
    const CUtensorMap* map = &p.map[e & 15];
    e = __shfl_sync(0xffffffffu, entry, i);
    mbar_wait(SM_BASE + SM_EMPTY + st * 8, parity);
    tma_fill(st, map, x, y, x + dx, dx ? y : y ^ 64);
    if (++st == NSTAGE) { st = 0; parity ^= 1; }
  }
}
__device__ __forceinline__ void kv_fill(const uint4* src, uint32_t st, uint32_t parity) {
  mbar_wait(SM_BASE + SM_EMPTY + st * 8, parity);
  asm volatile("{\n.reg .pred p;\nelect.sync _|p, 0xffffffff;\n"
               "@p mbarrier.arrive.expect_tx.shared::cta.b64 _, [%1], 16384;\n"
               "@p cp.async.bulk.shared::cluster.global.mbarrier::complete_tx::bytes [%0], [%2], 16384, [%1];\n}"
               :: "r"(SM_BASE + st * STAGE_BYTES), "r"(SM_BASE + SM_FULL + st * 8), "l"(src) : "memory");
}
__device__ __forceinline__ uint32_t kv_pick(uint32_t kind, uint32_t want) {
  uint32_t have, spin = 0;
#pragma unroll 1
  do {
    asm volatile("ld.volatile.shared.u32 %0, [%1];" : "=r"(have) : "r"(SM_BASE + SM_KVRDY + kind * 4) : "memory");
    have &= want;
  } while (!have && ++spin < (SPIN_LIMIT << 4));
  return __ffs(have ? have : want) - 1;
}
__device__ __forceinline__ void kv_fills(const uint4* kv) {
  uint32_t todo = 0x1555, t1 = 0, t2 = 0;
#pragma unroll 1
  for (int j = 0; j < 10; j++) {
    if (j >= 2) {
      kv_pick(1, 1u << t2);
      kv_fill(kv + (16 + t2) * 512, (j < 8 ? 4 * (j >> 1) - 4 : 0) + (j & 1) + 2, j < 8);
      PROF_AT(256 + 512 + (16 + j) * 4);
    }
    t2 = t1;
    if (j < 8) {
      t1 = kv_pick(0, j == 7 ? 0x4000u : todo);
      todo &= ~(1u << t1);
      kv_fill(kv + t1 * 512, (j < 6 ? 4 * (j >> 1) : 0) + (j & 1), j < 6);
      PROF_AT(256 + 512 + (10 + j) * 4);
    }
  }
}
__device__ __forceinline__ void reset_mailboxes(Scratch* sc, int half, int lane, uint32_t t_start) {
  while (clock_now() - t_start < TC) {}
#pragma unroll 1
  for (int i = half * 8; i < half * 9 + 8; i++) {
    const uint32_t t0 = clock_now();
    uint4* dst = &sc->x[blockIdx.x ^ (i < 12 ? (i >> 2) + 1 : 0)][i * 128 + lane];
#pragma unroll
    for (int k = 0; k < 4; k++) st_vec(dst + 32 * k, 0u, 0u, 0u, 0u);
    while (clock_now() - t0 < CLR_PACE) {}
  }
  bar_arrive(BAR_RST, 192);
  PROF_AT(256 + 512 + 28 * 4);
  asm volatile("fence.acq_rel.gpu;" ::: "memory");
  __syncwarp();
  announce<1>(sc, lane == 0);
  PROF_AT(256 + 512 + 2 * 4);
}
__device__ __forceinline__ void l2_prefetch(const void* p, uint32_t total, int b) {
  const uint32_t part = total / NCTA;
  asm volatile("cp.async.bulk.prefetch.L2.global [%0], %1;" :: "l"((const char*)p + (size_t)b * part), "r"(part) : "memory");
}

__global__ void __launch_bounds__(384, 1) conformer_kernel(Scratch* __restrict__ sc, __nv_bfloat16* __restrict__ out,
                                                           const __nv_bfloat16* __restrict__ dw, const __nv_bfloat16* __restrict__ xin,
                                                           const __nv_bfloat16* __restrict__ w_ff1a, const __grid_constant__ Params p) {
  extern __shared__ __align__(1024) uint8_t smem[];
  const int tid = threadIdx.x, lane = tid & 31;
  const uint32_t t_start = clock_now();
  const int b = blockIdx.x, r = b & 3, batch = b >> 6, t = (b >> 2) & 15;
  if ((uint32_t)__cvta_generic_to_shared(smem) != SM_BASE) return;
  PROF_AT(256 + (tid >> 7) * 256);
  PROF_TIME(30);
  const uint32_t crow = ((tid >> 1) & 48) + (lane >> 3);
  const uint32_t cdst = SM_BASE + crow * 128 + (((lane & 7) ^ (lane >> 3)) << 4);
  if (tid < 128) {
    const uint32_t g0 = batch * T_SEQ + t * 64 + crow, o = r * 128 + (lane & 7) * 16;
    const uint32_t lo = min(g0, 2 * T_SEQ - 5) * 512 + o, hi = min(g0 + 8, 2 * T_SEQ - 5) * 512 + o;
#pragma unroll
    for (int c = 0; c < 4; c++) {
#pragma unroll
      for (int i = 0; i < 4; i++)
        cp_async16((cdst ^ ((i & 1) << 6)) + SM_STG + (3 - c) * TILE_BYTES + i * 512, (const char*)xin + (((i & 2) ? hi : lo) ^ (c << 7)) + (i & 1) * 2048);
      asm volatile("cp.async.commit_group;" ::: "memory");
    }
  } else if (tid < 256) {
    const char* src = (const char*)w_ff1a + (64 * r + crow) * 2048 + r * 512 + (lane & 7) * 16;
#pragma unroll
    for (int c = 0; c < 4; c++) {
#pragma unroll
      for (int i = 0; i < 4; i++) cp_async16((cdst ^ ((i & 1) << 6)) + c * TILE_BYTES + i * 512, src + i * 8192 + c * 128);
      asm volatile("cp.async.commit_group;" ::: "memory");
    }
  }
  const int cw = __shfl_sync(0xffffffffu, tid >> 5, 0), wg = cw >> 2, w = cw & 3;

  if (wg == 2) {
    asm volatile("setmaxnreg.dec.sync.aligned.u32 40;");
    if (cw == 8) {
      if (lane == 0) {
        asm volatile("prefetch.tensormap [%0];" :: "l"(&p.map[M_FF1A]) : "memory");
#pragma unroll
        for (int i = 0; i < NSTAGE; i++) mbar_init(SM_BASE + SM_FULL + i * 8, 1);
        fence_async_smem();
      }
      __syncwarp();
      bar_arrive(0, 320);
      while (clock_now() - t_start < TF) {}
      PROF_MARK(9);
#pragma unroll
      for (int f = 2; f < 8; f++) {
        const uint32_t x = 256 * r + ((0xE2u >> f) & 1) * 128, y = (r ^ ((0xE790u >> (2 * f)) & 3)) * 64;
        tma_fill(f, &p.map[M_FF1A], x, y, x + 64, y);
      }
      PROF_MARK(1);
      uint32_t entry[2];
#pragma unroll 1
      for (int i = 0; i < 2; i++) { entry[1] = fill_entry(8 + i * 32 + lane, r); if (i == 0) entry[0] = entry[1]; }
      bar_sync(BAR_INIT, 64);
      weight_fills<8, F_KV - 8>(p, entry[0]);
      kv_fills(sc->kv[batch * 4 + r][0][0]);
      weight_fills<F_WO, F_TOTAL - F_WO>(p, entry[1]);
    } else if (here(cw) != 11) {
      const int kind = w - 1;
      const uint32_t prev = launch_index(sc);
      if (kind == 0) {
        if (lane == 0) {
#pragma unroll
            for (int i = 0; i < NSTAGE; i++) mbar_init(SM_BASE + SM_EMPTY + i * 8, 4);
          sts64(SM_BASE + SM_KVRDY, 0u, 0u);
        }
        __syncwarp();
        bar_arrive(0, 320);
        bar_arrive(BAR_INIT, 64);
        if (lane == 0) {
          const uint32_t t0 = t_start;
          while (clock_now() - t0 < PF0) {}
          while (clock_now() - t0 < PF1) {}
          asm volatile("prefetch.tensormap [%0];" :: "l"(&p.map[M_FF1B]) : "memory");
          l2_prefetch(p.w_ff1b, 1024 * 256 * 2, b);
          while (clock_now() - t0 < PF2) {}
          l2_prefetch(p.w_qkv, 256 * 768 * 2, b);
          l2_prefetch(p.w_pw1, 256 * 512 * 2, b);
          l2_prefetch(p.w_ff2a, 256 * 1024 * 2, b);
          while (clock_now() - t0 < PF3) {}
          if (b < 15) l2_prefetch(dw, 512 * NCTA, b);
          l2_prefetch(p.w_o, 256 * 256 * 2, b);
          l2_prefetch(p.w_pw2, 256 * 256 * 2, b);
          l2_prefetch(p.w_ff2b, 1024 * 256 * 2, b);
#pragma unroll
          for (int i = M_QKV; i < M_COUNT; i++) asm volatile("prefetch.tensormap [%0];" :: "l"(&p.map[i]) : "memory");
        }
        __syncwarp();
      } else {
        reset_mailboxes(sc, 1, lane, t_start);
      }
      const uint32_t* flag = sc->flag[batch * 4 + r][kind * 16 + (lane & 15)];
      uint32_t spin = 0, ready;
#pragma unroll 1
      do {
        uint32_t v;
        asm volatile("ld.relaxed.gpu.global.u32 %0, [%1];" : "=r"(v) : "l"(flag) : "memory");
        ready = __ballot_sync(0xffffffffu, v - 1 == prev);
        asm volatile("st.volatile.shared.u32 [%0], %1;" :: "r"(SM_BASE + SM_KVRDY + kind * 4), "r"(ready & (ready >> 1)) : "memory");
        if (spin == 0) {
          if (kind == 0) bar_sync(BAR_K, 160); else bar_sync(BAR_V, 160);
          if (lane == 0) {
            PROF_MARK(4 + kind * 2);
            asm volatile("cp.async.bulk.global.shared::cta.bulk_group [%0], [%1], %2;"
                         :: "l"(sc->kv[batch * 4 + r][kind][t]), "r"(SM_BASE + SM_STG + kind * TILE_BYTES), "r"(TILE_BYTES) : "memory");
            asm volatile("cp.async.bulk.commit_group;\ncp.async.bulk.wait_group 0;" ::: "memory");
            asm volatile("st.relaxed.gpu.global.u32 [%0], %1;" :: "l"(sc->flag[batch * 4 + r][kind * 16 + t]), "r"(prev + 1) : "memory");
            PROF_MARK(5 + kind * 2);
          }
          __syncwarp();
        }
      } while (ready != 0xffffffffu && ++spin < SPIN_LIMIT);
    } else {
      const uint32_t* watch = sc->step[(b & ~3) + (lane & 3)];
      uint32_t seen;
      asm volatile("ld.relaxed.gpu.global.u32 %0, [%1];" : "=r"(seen) : "l"(watch) : "memory");
      reset_mailboxes(sc, 0, lane, t_start);
      uint32_t want = seen & ~15u;
#pragma unroll 1
      for (int k = 0; k < (TIMED ? 1 : 8); k++) {
        want += 2;
        uint32_t spin = 0;
#pragma unroll 1
        while (__any_sync(0xffffffffu, (int)(seen - want) < 0) && ++spin < SPIN_LIMIT)
          asm volatile("ld.relaxed.gpu.global.u32 %0, [%1];" : "=r"(seen) : "l"(watch) : "memory");
        bar_arrive(BAR_GO, 160);
        PROF_MARK(32 + k);
      }
    }
  } else {
    asm volatile("setmaxnreg.inc.sync.aligned.u32 232;");
    const int q = lane & 3, th = tid & 127;
    constexpr uint32_t stg = SM_BASE + SM_STG;
    const uint32_t mrow = 16 * w + (lane & 15);
    const uint32_t maddr = stg + mrow * 128 + (((lane >> 4) ^ (lane & 7)) << 4);
    const uint32_t qslot = stg + 2 * TILE_BYTES + w * 2048 + lane * 16;
    uint4* const xp = &sc->x[b][th];
    const int nvalid = T_SEQ - t * 64, row0 = 16 * w + (lane >> 2);

    uint32_t A[4][16];
    uint32_t st[4], sent = 0;
    bar_sync(0, 320);
    if (wg == 0) {
      RowAcc ra = {};
      cp_async_wait(0);
      __syncwarp();
      PROF_MARK0(45);
#pragma unroll
      for (int c = 0; c < 4; c++) tile_load(maddr + (3 - c) * TILE_BYTES, A[c]);
      row_sums(ra, A[0]); row_gram(ra, A[0]); row_sums(ra, A[1]); row_gram(ra, A[1]);
      pin(ra.s[0]); pin(ra.s[1]); pin(ra.u[0]); pin(ra.u[1]); pin(ra.v[0]); pin(ra.v[1]);
      SCHED();
      row_sums(ra, A[2]); row_sums(ra, A[3]); row_gram(ra, A[2]); row_gram(ra, A[3]);
      const float m0 = (ra.s[0][0] + ra.s[1][0]) * (1.f / DM), m1 = (ra.s[0][2] + ra.s[1][2]) * (1.f / DM);
      st[0] = pack2(m0, m0); st[1] = pack2(m1, m1);
      centre(A[0], st[0], st[1]);
      const float2 sq = row_squares(ra, lane & 4);
      st[2] = __float_as_uint(fmaf(-m0, m0, sq.x * (1.f / DM))); st[3] = __float_as_uint(fmaf(-m1, m1, sq.y * (1.f / DM)));
    } else {
      if (th < 112) sts128(SM_BASE + SM_CS + th * 16, 0, 0, 0, 0);
      sts32(SM_BASE + SM_EYE + th * 4, th >= 96 ? 0x3F803F80u : ((th & 32) == 0 && (th & 3) == ((th >> 3) & 3)) ? (0x3F00u << ((th & 4) * 4)) : 0u);
#pragma unroll
      for (int i = 0; i < 2; i++) {
        cp_async_wait(2 - 2 * i);
        fence_async_smem();
        bar_sync(BAR_WG1, 128);
        if (th == 0) mbar_arrive(SM_BASE + SM_FULL + i * 8);
      }
      PROF_MARK(6);
      const uint32_t tag = ~launch_index(sc) & 1;
      mbar_wait(SM_BASE + SM_FULL + 4 * 8, 0);
      PROF_MARK(5);
      if (b < 72) {
        const __nv_bfloat16* wp; int ld, col;
        if (b < 24) { wp = p.w_qkv; ld = 768; col = b * 32; }
        else if (b < 40) { wp = p.w_pw1; ld = 512; col = (b - 24) * 32; }
        else { wp = p.w_ff2a; ld = 1024; col = (b - 40) * 32; }
        const uint4* src = (const uint4*)(wp + (size_t)(th >> 2) * ld + col + q * 8);
        float c[8] = {0.f, 0.f, 0.f, 0.f, 0.f, 0.f, 0.f, 0.f};
#pragma unroll 1
        for (int h = 0; h < 2; h++, src += 16 * ld) {
#pragma unroll
          for (int i = 0; i < 4; i++) {
            const uint4 v = __ldg(src + i * 4 * ld);
            c[0] += bf_lo(v.x); c[1] += bf_hi(v.x); c[2] += bf_lo(v.y); c[3] += bf_hi(v.y);
            c[4] += bf_lo(v.z); c[5] += bf_hi(v.z); c[6] += bf_lo(v.w); c[7] += bf_hi(v.w);
          }
        }
#pragma unroll 1
        for (int m = 4; m <= 16; m <<= 1)
#pragma unroll
          for (int k = 0; k < 8; k++) c[k] += __shfl_xor_sync(0xffffffffu, c[k], m);
        if (lane < 4) {
          const uint32_t a = SM_BASE + SM_CS + 1792 + w * 128 + lane * 32;
          sts128(a, __float_as_uint(c[0]), __float_as_uint(c[1]), __float_as_uint(c[2]), __float_as_uint(c[3]));
          sts128(a + 16, __float_as_uint(c[4]), __float_as_uint(c[5]), __float_as_uint(c[6]), __float_as_uint(c[7]));
        }
        bar_sync(BAR_WG1, 128);
        if (th < 8) {
          float o[4] = {0.f, 0.f, 0.f, 0.f};
#pragma unroll 1
          for (int k = 0; k < 4; k++) {
            uint32_t e[4];
            lds128(SM_BASE + SM_CS + 1792 + k * 128 + th * 16, e[0], e[1], e[2], e[3]);
#pragma unroll
            for (int i = 0; i < 4; i++) o[i] += __uint_as_float(e[i]);
          }
          st_vec(&sc->cs[b * 8 + th], (__float_as_uint(o[0]) & ~1u) | tag, __float_as_uint(o[1]), __float_as_uint(o[2]), __float_as_uint(o[3]));
        }
      }
      bar_sync(BAR_WG1, 128);
      PROF_MARK(2);
      if (th < 72) {
        const int j = th >> 3, i = (th & 7) * 2;
        int src;
        if (j < CS_PW1) src = 320 + 64 * r + 16 * j;
        else if (j < CS_QKV) src = 192 + (j - CS_PW1) * 64 + 16 * r;
        else src = ((j - CS_QKV + 1) % 3) * 64 + 16 * r;
        uint32_t e[8], hi[4], lo[4], spin = 0;
#pragma unroll 1
        do {
          ld_vec(&sc->cs[src + i], e[0], e[1], e[2], e[3]);
          ld_vec(&sc->cs[src + i + 1], e[4], e[5], e[6], e[7]);
        } while ((((e[0] ^ tag) | (e[4] ^ tag)) & 1u) && ++spin < SPIN_LIMIT);
        e[0] &= ~1u; e[4] &= ~1u;
#pragma unroll
        for (int k = 0; k < 4; k++) {
          const float c0 = __uint_as_float(e[2 * k]), c1 = __uint_as_float(e[2 * k + 1]);
          hi[k] = pack2(c0, c1);
          lo[k] = pack2(c0 - bf_lo(hi[k]), c1 - bf_hi(hi[k]));
        }
        const uint32_t a = SM_BASE + SM_CS + j * 256 + i * 8;
        sts128(a ^ ((a >> 3) & 0x70), hi[0], hi[1], hi[2], hi[3]);
        sts128((a + 128) ^ (((a + 128) >> 3) & 0x70), lo[0], lo[1], lo[2], lo[3]);
      }
      fence_async_smem();
      PROF_MARK(4);
      bar_arrive(BAR_CS, 256);
    }

#pragma unroll 1
    for (uint32_t pass = 0; pass < 2; pass++) {
      uint32_t Q[16], shift;
      if (wg == 0) {
        float acc[4][32];
        uint32_t H[4][16];
        if (!pass) { PROF_MARK(47); ACQUIRE(0); }
        mma_tile<true>(acc[0], A[0], LO(0)); mma_tile<true>(acc[1], A[0], HI(0));
        if (!pass) ACQUIRE(1);
        mma_tile<true>(acc[2], A[0], LO(1)); mma_tile<true>(acc[3], A[0], HI(1));
        if (pass) {
          gather_first<1, X_AG0>(A, st, sc, xp, 1, sent);
        } else {
          centre(A[1], st[0], st[1]);
          acquire_n<2, 3>();
        }
        mma_tile<false>(acc[0], A[1], LO(2)); mma_tile<false>(acc[1], A[1], HI(2));
        if (pass) {
          gather_rest<1, X_AG0>(A, xp, 1);
          RELEASE(F_WO - 2 + NREL, F_PW2 + 1);
        } else {
          centre(A[2], st[0], st[1]); centre(A[3], st[0], st[1]);
        }
        PROF_MARK2(2, 18);
        mma_tile<false>(acc[0], A[2], LO(3)); mma_tile<false>(acc[0], A[3], LO(4));
        WG_WAIT(4);
        RELEASE(0, 1);
        uint32_t mu[4] = {0u, 0u, 0u, 0u};
        float rs0, rs1, tn[2][4];
        if (pass) {
          const RowNorm n = stat_finish(sc, st, 1, 0.5f);
          rs0 = n.rs0; rs1 = n.rs1;
          mean_frag(mu, n, q == 0);
        } else {
          const int src = (lane & 28) | (lane >> 3);
          rs0 = 0.5f * rsqrt_hw(fmaxf(__uint_as_float(__shfl_sync(0xffffffffu, st[2], src)), 0.f) + LN_EPS);
          rs1 = 0.5f * rsqrt_hw(fmaxf(__uint_as_float(__shfl_sync(0xffffffffu, st[3], src)), 0.f) + LN_EPS);
        }
        pin(mu);
        mma_fold<2 * CS_FF2>(acc[0], mu);
        mma_tile<false>(acc[1], A[2], HI(3));
#define SEGS(a, b) silu_segs<a, b>(acc, tn, H, rs0, rs1)
        WG_WAIT(1); pin(acc[0]);
        SEGS(0, 1);
        mma_tile_fold<2 * CS_FF2 + 2>(acc[1], A[3], HI(4), mu);
        SEGS(1, 3);
        uint32_t ok = probe_n<5, 1>();
        SEGS(3, 4);
        settle_n<5, 1>(ok);
        mma_tile<false>(acc[2], A[1], LO(5));
        SEGS(4, 5);
        ok = probe_n<6, 1>();
        SEGS(5, 6);
        settle_n<6, 1>(ok);
        mma_tile<false>(acc[2], A[2], LO(6));
        SEGS(6, 8);
        WG_WAIT(2); pin(acc[1]);
        RELEASE(2, 4);
        ok = probe_n<7, 1>();
        SEGS(8, 9);
        settle_n<7, 1>(ok);
        mma_tile_fold<2 * CS_FF2 + 4>(acc[2], A[3], LO(7), mu);
        SEGS(9, 12);
        mma_tile<false>(acc[3], A[1], HI(5));
        SEGS(12, 14);
        mma_tile<false>(acc[3], A[2], HI(6));
        SEGS(14, 16);
        WG_WAIT(2); pin(acc[2]);
        SEGS(16, 17);
        mma_tile_fold<2 * CS_FF2 + 6>(acc[3], A[3], HI(7), mu);
        SEGS(17, 19);
        ok = probe_n<8, 2>();
        SEGS(19, 20);
        settle_n<8, 2>(ok);
        mma_tile_reuse(acc[1], H[0], LO(8));
        SEGS(20, 22);
        mma_tile<false>(acc[1], H[1], HI(8));
        SEGS(22, 24);
        WG_WAIT(2); pin(acc[3]);
        RELEASE(5, 7);
        SEGS(24, 26);
        mma_tile<false>(acc[1], H[2], LO(9));
        SEGS(26, 27);
        ok = probe_n<10, 2>();
        SEGS(27, 28);
        settle_n<10, 2>(ok);
        mma_tile_reuse(acc[2], H[0], LO(10));
        SEGS(28, 31);
        mma_tile<false>(acc[2], H[1], HI(10));
        SEGS(31, 34);
#undef SEGS
        PROF_MARK2(3, 19);
        const uint32_t rtag = here(pass ^ 1);
        const uint4* rs_in = xp + X_RS;
        mma_tile<false>(acc[1], H[3], HI(9));
        mma_tile<false>(acc[2], H[2], LO(11));
        ok = probe_n<12, 2>();
        uint4* rs_out = peer<1>(xp) + X_RS;
        mma_tile<false>(acc[2], H[3], HI(11));
        settle_n<12, 2>(ok);
        if (!pass) bar_sync(BAR_RST, 192);
        WG_WAIT(2); pin(acc[1]);
        RELEASE(8, 9);
        send_half<0>(rs_out, acc[1], rtag);
        mma_tile_reuse(acc[3], H[0], LO(12));
        SCHED();
        send_half<1>(rs_out, acc[1], rtag);
        mma_tile<false>(acc[3], H[1], HI(12));
        rs_out = peer<2>(xp) + X_RS + 512;
        WG_WAIT(2); pin(acc[2]);
        send_half<0>(rs_out, acc[2], rtag);
        mma_tile<false>(acc[3], H[2], LO(13));
        SCHED();
        ok = probe_n<14, 2>();
        send_half<1>(rs_out, acc[2], rtag);
        mma_tile<false>(acc[3], H[3], HI(13));
        settle_n<14, 2>(ok);
        mma_tile_reuse(acc[1], H[0], LO(14));
        rs_out = peer<3>(xp) + X_RS + 1024;
        if (!pass) bar_sync(BAR_GO, 160);
        announce(sc, tid == 0);
        fetch(rs_in, A[1]);
        SCHED();
        mma_tile<false>(acc[1], H[1], HI(14));
        WG_WAIT(2); pin(acc[3]);
        send_half<0>(rs_out, acc[3], rtag);
        send_half<1>(rs_out, acc[3], rtag);
        if (TIMED) sent = clock_now();
        mma_tile<false>(acc[1], H[2], LO(15)); mma_tile<false>(acc[1], H[3], HI(15));
        SCHED();
        fetch(rs_in + 512, A[2]);
        SCHED();
        res_load(maddr, acc[2]);
        if (TIMED) { while (clock_now() - sent < RD) {} } else bar_sync(BAR_GO, 160);
        fetch(rs_in + 1024, A[3]);
        if (!pass) acquire_n<F_QKV, 3>();
        {
          uint32_t spin = 0;
          while (__builtin_expect(stale(miss(A[1], rtag) | miss(A[2], rtag) | miss(A[3], rtag)), 0) && ++spin < SPIN_LIMIT) {
            if (stale(miss(A[1], rtag) | miss(A[2], rtag))) { fetch(rs_in, A[1]); fetch(rs_in + 512, A[2]); }
            fetch(rs_in + 1024, A[3]);
          }
        }
        announce(sc, tid == 0 && !pass);
        mma_add_half(acc[2], A[1]);
        mma_add_half(acc[2], A[2]);
        mma_add_half(acc[2], A[3]);
        PROF_MARK2(4, 20);
        WG_WAIT(0); pin(acc[2]); pin(acc[1]);
#pragma unroll
        for (int i = 0; i < 16; i++) A[0][i] = pack2(fmaf(acc[1][2 * i], 0.5f, acc[2][2 * i]), fmaf(acc[1][2 * i + 1], 0.5f, acc[2][2 * i + 1]));
        if (pass) {
          PROF_MARK(21);
          stat_publish(A[0], sc, here(th), 0);
          stat_fetch(sc, st);
          const RowNorm fn = stat_finish(sc, st, 0, 1.f);
          const float nm0 = -fn.m0 * fn.rs0, nm1 = -fn.m1 * fn.rs1;
#pragma unroll
          for (int i = 0; i < 16; i++) {
            const float rs = (i & 1) ? fn.rs1 : fn.rs0, nm = (i & 1) ? nm1 : nm0;
            A[0][i] = pack2(fmaf(bf_lo(A[0][i]), rs, nm), fmaf(bf_hi(A[0][i]), rs, nm));
          }
          tile_store(here(maddr), A[0]);
          __syncwarp();
          const int row = 16 * w + (lane >> 3);
          uint4* dst = (uint4*)(out + ((size_t)batch * T_SEQ + t * 64 + row) * DM + 64 * r) + (lane & 7);
          const uint32_t src = stg + row * 128 + (((lane & 7) ^ (lane >> 3)) << 4);
#pragma unroll
          for (int i = 0; i < 4; i++) {
            uint4 v;
            lds128((src ^ ((i & 1) << 6)) + i * 512, v.x, v.y, v.z, v.w);
            if (row + 4 * i < nvalid) dst[i * 4 * (DM / 8)] = v;
          }
          PROF_MARK(22);
          PROF_TIME(31);
          break;
        }
        send_residual(A[0], sc, xp, maddr, 1, sent);
        PROF_MARK(5);
        mma_tile<true>(acc[0], A[0], LO(F_QKV)); mma_tile<true>(acc[1], A[0], HI(F_QKV));
        mma_tile<true>(acc[2], A[0], LO(F_QKV + 1));
        gather_first<1, X_AG0>(A, st, sc, xp, 1, sent);
        mma_tile<false>(acc[0], A[1], LO(F_QKV + 2)); mma_tile<false>(acc[1], A[1], HI(F_QKV + 2));
        acquire_n<F_QKV + 3, 3>();
        bar_sync(BAR_CS, 256);
        gather_rest<1, X_AG0>(A, xp, 1);
        PROF_MARK(6);
        mma_tile<false>(acc[0], A[2], LO(F_QKV + 3)); mma_tile<false>(acc[0], A[3], LO(F_QKV + 4));
        SCHED();
        {
          const RowNorm n = stat_finish(sc, st, 1, 1.f);
          rs0 = row0 < nvalid ? n.rs0 : 0.f; rs1 = row0 + 8 < nvalid ? n.rs1 : 0.f;
          mean_frag(mu, n, q == 3);
        }
        mma_fold<2 * CS_QKV - 6>(acc[0], mu);
        RELEASE(10, 15);
        WG_WAIT(0); pin(acc[0]);
        scale_pack(acc[0], A[0], rs0, rs1);
        tile_store(here(maddr), A[0]);
        SCHED();
        mma_tile<false>(acc[1], A[2], HI(F_QKV + 3));
        fence_async_smem();
        bar_arrive(BAR_K, 160);
        mma_tile_fold<2 * CS_QKV - 4>(acc[1], A[3], HI(F_QKV + 4), mu);
        mma_tile<false>(acc[2], A[1], HI(F_QKV + 1)); mma_tile<false>(acc[2], A[2], LO(F_QKV + 5));
        WG_WAIT(2); pin(acc[1]);
        scale_pack(acc[1], Q, rs0, rs1);
        tile_store(here(maddr) + TILE_BYTES, Q);
        fence_async_smem();
        bar_arrive(BAR_V, 160);
        mma_tile_fold<2 * CS_QKV - 2>(acc[2], A[3], HI(F_QKV + 5), mu);
        WG_WAIT(0); pin(acc[2]);
        scale_pack(acc[2], Q, rs0 * SM_SCALE_LOG2, rs1 * SM_SCALE_LOG2);
        frag_store(here(qslot), Q);
        {
          uint32_t d[4] = {0u, 0u, 0u, 0u};
#pragma unroll
          for (int i = 0; i < 16; i++) asm("fma.rn.bf16x2 %0, %1, %2, %0;" : "+r"(d[i & 3]) : "r"(Q[i]), "r"(A[0][i]));
          float s0 = (bf_lo(d[0]) + bf_hi(d[0])) + (bf_lo(d[2]) + bf_hi(d[2])), s1 = (bf_lo(d[1]) + bf_hi(d[1])) + (bf_lo(d[3]) + bf_hi(d[3]));
          shift = pack2(-s0, -s1);
          sts32(SM_BASE + SM_CS + 2 * CS_QKV * 128 + here(th) * 4, shift);
        }
        bar_arrive(BAR_Q, 256);
        RELEASE(F_QKV, F_QKV + 5);
      } else {
        bar_sync(BAR_Q, 256);
#pragma unroll
        for (int s = 0; s < 4; s++) lds128(qslot + s * 512, Q[4 * s], Q[4 * s + 1], Q[4 * s + 2], Q[4 * s + 3]);
        shift = lds32(SM_BASE + SM_CS + 2 * CS_QKV * 128 + th * 4);
        if (w < 2) {
          const uint32_t v = w ? 0u : 0x3F803F80u;
#pragma unroll
          for (int s = 0; s < 4; s++) sts128(qslot + s * 512, v, v, v, v);
          fence_async_smem();
        }
      }
      PROF_MARK(7);

      float O[36];
      {
        float S[2][32];
        uint32_t P[2][16], nm[4] = {shift & 0xFFFFu, shift >> 16, 0u, 0u};
        pin(Q); pin(nm);
        uint32_t sk = wg, sv = F_SPARE % NSTAGE + wg;
        mbar_wait(SM_BASE + SM_FULL + sv * 8, 1);
        if (wg == 1) bar_sync(BAR_ATT, 256);
        mbar_wait(SM_BASE + SM_FULL + sk * 8, 0);
        PROF_MARK(8);
        WG_FENCE();
        wgmma64_set<0>(S[0], nm, (uint64_t)((SM_BASE + SM_ONE) >> 4));
#pragma unroll
        for (int s = 0; s < 4; s++) wgmma64_acc<0>(S[0], &Q[4 * s], ring_desc(RING_K + sk * 1024 + s * 2));
        WG_COMMIT();
        SCHED();
#pragma unroll
        for (int i = 0; i < 36; i++) O[i] = 0.f;
#pragma unroll
        for (int i = 0; i < 32; i++) S[1][i] = 0.f;
#pragma unroll
        for (int i = 0; i < 16; i++) P[1][i] = 0u;
        pin(O); pin(S[1]); pin(P[1]);
        SCHED();
        WG_WAIT(0); pin(S[0]);
        if (wg == 0) bar_sync(BAR_ATT, 256);
#pragma unroll 1
        for (int it = 0; it < 4; it++) {
          const uint32_t sn = it >= 2 ? wg : sk + 4;
          uint32_t ok = 1;
          mbar_probe(ok, SM_BASE + SM_FULL + sn * 8, it >= 2);
          mbar_probe(ok, SM_BASE + SM_FULL + (sk + 2) * 8, it == 3);
          attn_step(S[0], S[1], P[0], P[1], O, Q, nm, RING_K + sk * 1024 + 512, RING_V + (sv * 1024 + 512) * V_STEP, true, it > 0);
          PROF_MARK(24 + it * 3);
          if (__builtin_expect(!ok, 0)) {
            mbar_wait(SM_BASE + SM_FULL + sn * 8, it >= 2);
            mbar_wait(SM_BASE + SM_FULL + (sk + 2) * 8, it == 3);
          }
          WG_WAIT(0); pin(O); pin(S[1]); pin(P[1]);
          asm volatile("{\n.reg .pred p;\nsetp.eq.u32 p, %2, 0;\n@p mbarrier.arrive.shared::cta.b64 _, [%0];\n@p mbarrier.arrive.shared::cta.b64 _, [%1];\n}"
                       :: "r"(SM_BASE + SM_EMPTY + sk * 8), "r"(SM_BASE + SM_EMPTY + sv * 8), "r"(lane) : "memory");
          PROF_MARK(25 + it * 3);
          sv = sk + 2; sk = sn;
          attn_step(S[1], S[0], P[1], P[0], O, Q, nm, RING_K + sk * 1024, RING_V + (sv * 1024) * V_STEP, it < 3, true);
          WG_WAIT(0); pin(O); pin(S[0]); pin(P[0]);
          PROF_MARK(26 + it * 3);
        }
        WG_FENCE();
        pv_tile(O, P[1], RING_V + (sv * 1024 + 512) * V_STEP, wg << 22);
        WG_COMMIT();
        announce<1>(sc, th == 0);
        WG_WAIT(0); pin(O);
      }
      PROF_MARK(9);

      {
        const uint32_t mo = stg + here(th) * 16;
        sts64(mo + 5 * 4096 + wg * 8, __float_as_uint(O[32]), __float_as_uint(O[34]));
        if (wg == 0) {
#pragma unroll
          for (int i = 4; i < 8; i++)
            sts128(mo + i * 2048, __float_as_uint(O[4 * i]), __float_as_uint(O[4 * i + 1]), __float_as_uint(O[4 * i + 2]), __float_as_uint(O[4 * i + 3]));
        } else {
#pragma unroll
          for (int i = 0; i < 4; i++)
            sts128(mo + i * 2048, __float_as_uint(O[4 * i]), __float_as_uint(O[4 * i + 1]), __float_as_uint(O[4 * i + 2]), __float_as_uint(O[4 * i + 3]));
#pragma unroll
          for (int i = 0; i < 16; i++) O[i] = O[16 + i];
        }
        bar_sync(BAR_MERGE, 256);
        uint32_t e[4];
        lds128(mo + 5 * 4096, e[0], e[1], e[2], e[3]);
        O[32] = __uint_as_float(e[0]) + __uint_as_float(e[2]); O[34] = __uint_as_float(e[1]) + __uint_as_float(e[3]);
#pragma unroll
        for (int i = 0; i < 4; i++) {
          lds128(mo + wg * TILE_BYTES + i * 2048, e[0], e[1], e[2], e[3]);
#pragma unroll
          for (int k = 0; k < 4; k++) O[4 * i + k] += __uint_as_float(e[k]);
        }
        const bool safe = O[32] > 0x1p-60f && O[32] < 0x1p60f && O[34] > 0x1p-60f && O[34] < 0x1p60f;
        if (__builtin_expect(__any_sync(0xffffffffu, !safe), 0)) attention_exact(O, Q, sc, batch * 4 + r, lane, wg);
        const float i0 = rcp_hw(O[32]), i1 = rcp_hw(O[34]);
#pragma unroll
        for (int i = 0; i < 8; i++) { const float v = (i & 1) ? i1 : i0; A[0][i] = pack2(O[2 * i] * v, O[2 * i + 1] * v); }
        A[0][0] &= ~1u; A[0][4] &= ~1u;
        uint4* dst = xp + X_AG1 + wg * 256;
        SCHED();
        st_vec(dst, A[0][0], A[0][1], A[0][2], A[0][3]);
        st_vec(dst + 128, A[0][4], A[0][5], A[0][6], A[0][7]);
        SCHED();
        if (TIMED) sent = clock_now();
      }
      const int dir = cw == 0 ? -1 : 1;
      uint32_t tap[15];
      if (wg == 1) {
        const uint32_t mo = stg + TILE_BYTES + here(th) * 16;
        sts128(mo, A[0][0], A[0][1], A[0][2], A[0][3]);
        sts128(mo + 2048, A[0][4], A[0][5], A[0][6], A[0][7]);
        bar_arrive(BAR_HALF, 256);
        load_taps(tap, dw, 1);
        halve_taps(tap);
      } else {
        PROF_MARK(10);
        const uint32_t mo = stg + TILE_BYTES + here(th) * 16;
        bar_sync(BAR_HALF, 256);
        lds128(mo, A[0][8], A[0][9], A[0][10], A[0][11]);
        lds128(mo + 2048, A[0][12], A[0][13], A[0][14], A[0][15]);
        proj_residual<F_WO, 6>(A, sc, xp, maddr, 0, sent);
        PROF_MARK(12);
        float acc[2][32];
        mma_tile<true>(acc[0], A[0], LO(F_PW1)); mma_tile<true>(acc[1], A[0], HI(F_PW1));
        load_taps(tap, dw, dir);
        gather_first<1, X_AG0>(A, st, sc, xp, 0, sent);
        mma_tile<false>(acc[1], A[1], HI(F_PW1 + 1)); mma_tile<false>(acc[0], A[1], LO(F_PW1 + 1));
        gather_rest<1, X_AG0>(A, xp, 0);
        RELEASE(F_WO - 2, F_WO + 1);
        PROF_MARK(13);
        mma_tile<false>(acc[1], A[2], HI(F_PW1 + 2)); mma_tile<false>(acc[1], A[3], HI(F_PW1 + 3));
        WG_WAIT(2);
        RELEASE(F_WO + 2, F_WO - 3 + NREL);
        SCHED();
        uint32_t mu[4];
        const RowNorm n = stat_finish(sc, st, 0, 0.5f);
        const float rs0 = row0 < nvalid ? n.rs0 : 0.f, rs1 = row0 + 8 < nvalid ? n.rs1 : 0.f;
        mean_frag(mu, n, q == 0);
        mma_fold<2 * CS_PW1 + 2>(acc[1], mu);
        mma_tile<false>(acc[0], A[2], LO(F_PW1 + 2));
        halve_taps(tap);
        mma_tile_fold<2 * CS_PW1>(acc[0], A[3], LO(F_PW1 + 3), mu);
        WG_WAIT(2); pin(acc[1]);
#pragma unroll
        for (int i = 0; i < 32; i++) acc[1][i] = tanh_hw(acc[1][i] * ((i & 2) ? rs1 : rs0));
#pragma unroll
        for (int i = 0; i < 32; i++) { const float rs = (i & 2) ? rs1 : rs0; acc[1][i] = fmaf(acc[1][i], rs, rs); }
        pin(acc[1]);
        SCHED();
        WG_WAIT(0); pin(acc[0]);
#pragma unroll
        for (int i = 0; i < 16; i++) A[0][i] = pack2(acc[0][2 * i] * acc[1][2 * i], acc[0][2 * i + 1] * acc[1][2 * i + 1]);
        const uint32_t ga = stg + TILE_BYTES + here(mrow) * G_PITCH + (lane >> 4) * 16;
#pragma unroll
        for (int s = 0; s < 4; s++) stsm4(ga + s * 32, &A[0][4 * s]);
      }
      {
        const uint32_t gsrc = stg + TILE_BYTES + (8 * cw - 7) * G_PITCH + lane * 4;
        const bool edge = cw == 0 || cw == 7;
        const bool nbr = cw == 0 ? t > 0 : t < 15;
        uint4* const hdst = &sc->x[b + 4 * dir][X_HALO + (cw == 0 ? 96 : 0) + lane];
        uint32_t in[22];
        bar_sync(BAR_G, 256);
        PROF_MARK(14);
        if (cw == 0) {
#pragma unroll
          for (int i = 14; i >= 0; i--) in[i] = lds32(gsrc + (21 - i) * G_PITCH);
        } else {
#pragma unroll
          for (int i = 14; i >= 0; i--) in[i] = lds32(gsrc + i * G_PITCH);
        }
        if (edge) {
          if (nbr) {
            st_vec(hdst, HALO_TAG, in[14], in[13], in[12]);
            st_vec(hdst + 32, HALO_TAG, in[11], in[10], in[9]);
            st_vec(hdst + 64, HALO_TAG, in[8], 0u, 0u);
          }
        } else {
#pragma unroll
          for (int i = 15; i < 22; i++) in[i] = lds32(gsrc + i * G_PITCH);
        }
        if (cw == 0) PROF_MARK0(40);
        uint32_t cv[8];
#pragma unroll
        for (int i = 0; i < 15; i++)
#pragma unroll
          for (int o = 0; o < 8; o++) {
            if (i == o) asm("mul.rn.bf16x2 %0, %1, %2;" : "=r"(cv[o]) : "r"(in[i]), "r"(tap[0]));
            if (i > o) asm("fma.rn.bf16x2 %0, %1, %2, %0;" : "+r"(cv[o]) : "r"(in[i]), "r"(tap[i - o]));
          }
        pin(cv);
        if (cw == 0) PROF_MARK0(41);
        if (edge) {
#pragma unroll
          for (int i = 15; i < 22; i++) in[i] = 0u;
          if (nbr) {
            const uint4* src = &sc->x[b][X_HALO + (cw == 0 ? 0 : 96) + lane];
            uint32_t e0, e1, e2, u0, u1, spin = 0;
#pragma unroll 1
            do {
              ld_vec(src, e0, in[15], in[16], in[17]);
              ld_vec(src + 32, e1, in[18], in[19], in[20]);
              ld_vec(src + 64, e2, in[21], u0, u1);
            } while (__any_sync(0xffffffffu, ((e0 ^ HALO_TAG) | (e1 ^ HALO_TAG) | (e2 ^ HALO_TAG)) != 0) && ++spin < SPIN_LIMIT);
          }
          announce<1>(sc, lane == 0);
        }
#pragma unroll
        for (int i = 15; i < 22; i++)
#pragma unroll
          for (int o = 0; o < 8; o++)
            if (i - o <= 14) asm("fma.rn.bf16x2 %0, %1, %2, %0;" : "+r"(cv[o]) : "r"(in[i]), "r"(tap[i - o]));
        if (cw == 0) PROF_MARK0(42);
        if (cw == 7) PROF_MARK0(43);
        const uint32_t fl = cw == 0 ? 7 : 0;
        const uint32_t cdst = (stg + cw * 1024 + lane * 4) ^ (fl * 144);
#pragma unroll
        for (int o = 0; o < 8; o++) {
          const float a = bf_lo(cv[o]), c = bf_hi(cv[o]);
          sts32(cdst ^ (o * 144), pack2(fmaf(a, tanh_hw(a), a), fmaf(c, tanh_hw(c), c)));
        }
      }
      if (wg == 1) {
        bar_arrive(BAR_C, 256);
        break;
      }
      bar_sync(BAR_C, 256);
      tile_load(here(maddr), A[0]);
      PROF_MARK(15);
      publish(xp + X_AG1, A[0], 1);
      proj_residual<F_PW2, 2>(A, sc, xp, maddr, 1, sent);
      PROF_MARK(17);
    }
  }
}

typedef CUresult (*EncodeFn)(CUtensorMap*, CUtensorMapDataType, cuuint32_t, void*, const cuuint64_t*, const cuuint64_t*,
                             const cuuint32_t*, const cuuint32_t*, CUtensorMapInterleave, CUtensorMapSwizzle,
                             CUtensorMapL2promotion, CUtensorMapFloatOOBfill);

void make_map(EncodeFn fn, CUtensorMap* m, const void* w, int rows, int cols, CUtensorMapSwizzle swz) {
  const cuuint64_t dims[2] = {(cuuint64_t)cols, (cuuint64_t)rows}, strides[1] = {(cuuint64_t)cols * 2};
  const cuuint32_t box[2] = {64, 64}, es[2] = {1, 1};
  fn(m, CU_TENSOR_MAP_DATA_TYPE_BFLOAT16, 2, const_cast<void*>(w), dims, strides, box, es, CU_TENSOR_MAP_INTERLEAVE_NONE,
     swz, CU_TENSOR_MAP_L2_PROMOTION_L2_128B, CU_TENSOR_MAP_FLOAT_OOB_FILL_NONE);
}

}

extern "C" void kernel_launch(void* const* d_in, const int* in_sizes, int n_in, void* d_out, int out_size) {
  static EncodeFn fn = nullptr;
  static Scratch* sc = nullptr;
  if (!fn) {
    void* f = nullptr;
    cudaDriverEntryPointQueryResult st;
    cudaGetDriverEntryPoint("cuTensorMapEncodeTiled", &f, cudaEnableDefault, &st);
    fn = (EncodeFn)f;
    void* raw = nullptr;
    cudaGetSymbolAddress(&raw, g_scratch);
    sc = (Scratch*)(((uintptr_t)raw + X_ALIGN - 1) & ~(uintptr_t)(X_ALIGN - 1));
    cudaFuncSetAttribute(conformer_kernel, cudaFuncAttributeMaxDynamicSharedMemorySize, SM_TOTAL);
  }
  typedef const __nv_bfloat16* W;
  const CUtensorMapSwizzle S = CU_TENSOR_MAP_SWIZZLE_128B;
  Params p;
  make_map(fn, &p.map[M_FF1A], d_in[1], 256, 1024, S);
  make_map(fn, &p.map[M_FF1B], d_in[2], 1024, 256, S);
  make_map(fn, &p.map[M_QKV], d_in[3], 256, 768, S);
  make_map(fn, &p.map[M_WO], d_in[4], 256, 256, S);
  make_map(fn, &p.map[M_PW1], d_in[5], 256, 512, S);
  make_map(fn, &p.map[M_PW2], d_in[7], 256, 256, S);
  make_map(fn, &p.map[M_FF2A], d_in[8], 256, 1024, S);
  make_map(fn, &p.map[M_FF2B], d_in[9], 1024, 256, S);
  p.w_ff1b = (W)d_in[2]; p.w_qkv = (W)d_in[3]; p.w_o = (W)d_in[4]; p.w_pw1 = (W)d_in[5];
  p.w_pw2 = (W)d_in[7]; p.w_ff2a = (W)d_in[8]; p.w_ff2b = (W)d_in[9];

  cudaLaunchConfig_t cfg = {};
  cfg.gridDim = dim3(NCTA);
  cfg.blockDim = dim3(384);
  cfg.dynamicSmemBytes = SM_TOTAL;
  cfg.stream = cudaStreamPerThread;
  cudaLaunchAttribute at[1];
  at[0].id = cudaLaunchAttributeCooperative;
  at[0].val.cooperative = 1;
  cfg.attrs = at;
  cfg.numAttrs = 1;
  cudaLaunchKernelEx(&cfg, conformer_kernel, sc, (__nv_bfloat16*)d_out, (W)d_in[6], (W)d_in[0], (W)d_in[1], p);
}
```

```cpp
#include <cuda_runtime.h>
#include <cuda_bf16.h>
#include <cuda.h>
#include <stdint.h>

namespace {

constexpr int T_SEQ = 1000;
constexpr int DM = 256;
constexpr int NCTA = 128;
constexpr int NSTAGE = 12;
constexpr uint32_t STAGE_BYTES = 16384;
constexpr uint32_t TILE_BYTES = 8192;
constexpr uint32_t SM_BASE = 1024;
constexpr uint32_t SM_STG = NSTAGE * STAGE_BYTES;
constexpr uint32_t SM_FULL = SM_STG + 32768;
constexpr uint32_t SM_EMPTY = SM_FULL + 96;
constexpr uint32_t SM_KVRDY = SM_FULL + 192;
constexpr uint32_t SM_EYE = SM_FULL + 256;
constexpr uint32_t SM_ONE = SM_FULL + 640;
constexpr uint32_t SM_CS = SM_FULL + 768;
constexpr uint32_t SM_TOTAL = SM_FULL + 3072;
constexpr int CS_FF2 = 0, CS_PW1 = 4, CS_QKV = 6;
constexpr uint32_t SPIN_LIMIT = 1u << 16;
constexpr float LN_EPS = 1e-5f;
constexpr float SM_SCALE_LOG2 = 0.125f * 1.4426950408889634f;
constexpr uint32_t G_PITCH = 144;
#define FSTR 8
#define TIMED 0
#define GD 400
#define RD 550
#define NREL 5
#define PF0 1
#define TF 1
#define TC 1
#define PF1 1400
#define PF2 2000
#define PF3 3500
#define CLR_PACE 150

constexpr int F_QKV = 16, F_SPARE = 22, F_KV = 24, F_WO = 40, F_PW1 = 42, F_PW2 = 46, F_TOTAL = 64;
enum { M_FF1A, M_FF1B, M_QKV, M_WO, M_PW1, M_PW2, M_FF2A, M_FF2B, M_COUNT };
enum { BAR_K = 1, BAR_V, BAR_Q, BAR_MERGE, BAR_G, BAR_C, BAR_WG1, BAR_GO, BAR_CS, BAR_ATT, BAR_INIT, BAR_HALF, BAR_RST };

struct Params {
  CUtensorMap map[M_COUNT];
  const __nv_bfloat16 *w_ff1b, *w_qkv, *w_o, *w_pw1, *w_pw2, *w_ff2a, *w_ff2b;
};

constexpr int X_RS = 0, X_AG1 = X_RS, X_HALO = X_RS + 512, X_AG0 = 1536, X_ST = 2048, X_SIZE = 4096;
constexpr uint32_t HALO_TAG = 0xFFFF0001u;
struct Scratch {
  uint4 x[NCTA][X_SIZE];
  uint4 kv[8][2][16][512];
  uint4 cs[576];
  uint32_t flag[8][32][FSTR];
  uint32_t step[NCTA][32];
};
constexpr size_t X_ALIGN = 4 * X_SIZE * sizeof(uint4);
__device__ uint8_t g_scratch[sizeof(Scratch) + X_ALIGN];
#define PROF_TIME(i)
#define PROF_MARK(i)
#define PROF_MARK2(i, j)
#define PROF_MARK0(i)
#define PROF_AT(a)

__device__ __forceinline__ void mbar_init(uint32_t bar, uint32_t cnt) {
  asm volatile("mbarrier.init.shared::cta.b64 [%0], %1;" :: "r"(bar), "r"(cnt) : "memory");
}
__device__ __forceinline__ void mbar_wait(uint32_t bar, uint32_t parity) {
  asm volatile("{\n.reg .pred p;\n.reg .u32 c;\nmov.u32 c, 0;\n"
               "WAIT_LOOP:\nmbarrier.try_wait.parity.shared::cta.b64 p, [%0], %1;\n@p bra WAIT_DONE;\n"
               "add.u32 c, c, 1;\nsetp.lt.u32 p, c, %2;\n@p bra WAIT_LOOP;\nWAIT_DONE:\n}"
               :: "r"(bar), "r"(parity), "n"(SPIN_LIMIT) : "memory");
}
__device__ __forceinline__ void mbar_arrive(uint32_t bar) {
  asm volatile("mbarrier.arrive.shared::cta.b64 _, [%0];" :: "r"(bar) : "memory");
}
#define bar_sync(id, n) asm volatile("bar.sync %0, %1;" :: "n"((int)(id)), "n"(n) : "memory")
#define bar_arrive(id, n) asm volatile("bar.arrive %0, %1;" :: "n"((int)(id)), "n"(n) : "memory")
__device__ __forceinline__ void fence_async_smem() { asm volatile("fence.proxy.async.shared::cta;" ::: "memory"); }

__device__ __forceinline__ void st_vec(uint4* p, uint32_t a, uint32_t b, uint32_t c, uint32_t d) {
  asm volatile("{\n.reg .b128 v;\n.reg .b64 lo, hi;\nmov.b64 lo, {%1, %2};\nmov.b64 hi, {%3, %4};\nmov.b128 v, {lo, hi};\n"
               "st.relaxed.gpu.global.b128 [%0], v;\n}" :: "l"(p), "r"(a), "r"(b), "r"(c), "r"(d) : "memory");
}
__device__ __forceinline__ void ld_vec(const uint4* p, uint32_t& a, uint32_t& b, uint32_t& c, uint32_t& d) {
  asm volatile("{\n.reg .b128 v;\n.reg .b64 lo, hi;\nld.relaxed.gpu.global.b128 v, [%4];\nmov.b128 {lo, hi}, v;\n"
               "mov.b64 {%0, %1}, lo;\nmov.b64 {%2, %3}, hi;\n}" : "=r"(a), "=r"(b), "=r"(c), "=r"(d) : "l"(p) : "memory");
}
__device__ __forceinline__ void sts128(uint32_t a, uint32_t x, uint32_t y, uint32_t z, uint32_t w) {
  asm volatile("st.shared.v4.u32 [%0], {%1, %2, %3, %4};" :: "r"(a), "r"(x), "r"(y), "r"(z), "r"(w) : "memory");
}
__device__ __forceinline__ void lds128(uint32_t a, uint32_t& x, uint32_t& y, uint32_t& z, uint32_t& w) {
  asm volatile("ld.shared.v4.u32 {%0, %1, %2, %3}, [%4];" : "=r"(x), "=r"(y), "=r"(z), "=r"(w) : "r"(a) : "memory");
}
__device__ __forceinline__ uint32_t lds32(uint32_t a) {
  uint32_t x; asm volatile("ld.shared.u32 %0, [%1];" : "=r"(x) : "r"(a) : "memory"); return x;
}
__device__ __forceinline__ void sts32(uint32_t a, uint32_t x) { asm volatile("st.shared.u32 [%0], %1;" :: "r"(a), "r"(x) : "memory"); }
__device__ __forceinline__ void sts64(uint32_t a, uint32_t x, uint32_t y) {
  asm volatile("st.shared.v2.u32 [%0], {%1, %2};" :: "r"(a), "r"(x), "r"(y) : "memory");
}
__device__ __forceinline__ void stsm4(uint32_t a, const uint32_t* r) {
  asm volatile("stmatrix.sync.aligned.m8n8.x4.shared.b16 [%0], {%1, %2, %3, %4};" :: "r"(a), "r"(r[0]), "r"(r[1]), "r"(r[2]), "r"(r[3]) : "memory");
}
__device__ __forceinline__ void ldsm4(uint32_t a, uint32_t* r) {
  asm volatile("ldmatrix.sync.aligned.m8n8.x4.shared.b16 {%0, %1, %2, %3}, [%4];" : "=r"(r[0]), "=r"(r[1]), "=r"(r[2]), "=r"(r[3]) : "r"(a) : "memory");
}
__device__ __forceinline__ uint32_t pack2(float lo, float hi) {
  uint32_t r; asm("cvt.rn.bf16x2.f32 %0, %1, %2;" : "=r"(r) : "f"(hi), "f"(lo)); return r;
}
__device__ __forceinline__ float bf_lo(uint32_t w) { return __uint_as_float(w << 16); }
__device__ __forceinline__ float bf_hi(uint32_t w) { return __uint_as_float(w & 0xffff0000u); }
__device__ __forceinline__ float tanh_hw(float x) { float y; asm volatile("tanh.approx.f32 %0, %1;" : "=f"(y) : "f"(x)); return y; }
__device__ __forceinline__ float rcp_hw(float x) { float y; asm("rcp.approx.ftz.f32 %0, %1;" : "=f"(y) : "f"(x)); return y; }
__device__ __forceinline__ float rsqrt_hw(float x) { float y; asm("rsqrt.approx.ftz.f32 %0, %1;" : "=f"(y) : "f"(x)); return y; }
__device__ __forceinline__ float ex2_hw(float x) { float y; asm("ex2.approx.ftz.f32 %0, %1;" : "=f"(y) : "f"(x)); return y; }

__device__ __forceinline__ uint32_t here(uint32_t v) { asm volatile("" : "+r"(v)); return v; }

#define SCHED() asm volatile("pmevent 1;" ::: "memory")
__device__ __forceinline__ void cp_async16(uint32_t dst, const void* src) {
  asm volatile("cp.async.cg.shared.global [%0], [%1], 16;" :: "r"(dst), "l"(src) : "memory");
}
__device__ __forceinline__ void cp_async_wait(int n) {
  if (n == 0) asm volatile("cp.async.wait_group 0;" ::: "memory");
  if (n == 1) asm volatile("cp.async.wait_group 1;" ::: "memory");
  if (n == 2) asm volatile("cp.async.wait_group 2;" ::: "memory");
  if (n == 3) asm volatile("cp.async.wait_group 3;" ::: "memory");
}
#define WG_FENCE() asm volatile("wgmma.fence.sync.aligned;" ::: "memory")
#define WG_COMMIT() asm volatile("wgmma.commit_group.sync.aligned;" ::: "memory")
#define WG_WAIT(n) asm volatile("wgmma.wait_group.sync.aligned %0;" :: "n"(n) : "memory")

template <int N> __device__ __forceinline__ void pin(float (&d)[N]) {
#pragma unroll
  for (int i = 0; i < N; i++) asm volatile("" : "+f"(d[i]) :: "memory");
}
template <int N> __device__ __forceinline__ void pin(uint32_t (&d)[N]) {
#pragma unroll
  for (int i = 0; i < N; i++) asm volatile("" : "+r"(d[i]) :: "memory");
}

#define WG_D32 "{%0, %1, %2, %3, %4, %5, %6, %7, %8, %9, %10, %11, %12, %13, %14, %15, %16, %17, %18, %19, %20, %21, %22, %23, %24, %25, %26, %27, %28, %29, %30, %31}"
template <int TB> __device__ __forceinline__ void wgmma64_acc(float (&d)[32], const uint32_t* a, uint64_t db) {
  asm volatile("wgmma.mma_async.sync.aligned.m64n64k16.f32.bf16.bf16 " WG_D32 ", {%32, %33, %34, %35}, %36, 1, 1, 1, %37;"
    : "+f"(d[0]), "+f"(d[1]), "+f"(d[2]), "+f"(d[3]), "+f"(d[4]), "+f"(d[5]), "+f"(d[6]), "+f"(d[7]),
      "+f"(d[8]), "+f"(d[9]), "+f"(d[10]), "+f"(d[11]), "+f"(d[12]), "+f"(d[13]), "+f"(d[14]), "+f"(d[15]),
      "+f"(d[16]), "+f"(d[17]), "+f"(d[18]), "+f"(d[19]), "+f"(d[20]), "+f"(d[21]), "+f"(d[22]), "+f"(d[23]),
      "+f"(d[24]), "+f"(d[25]), "+f"(d[26]), "+f"(d[27]), "+f"(d[28]), "+f"(d[29]), "+f"(d[30]), "+f"(d[31])
    : "r"(a[0]), "r"(a[1]), "r"(a[2]), "r"(a[3]), "l"(db), "n"(TB));
}
template <int TB> __device__ __forceinline__ void wgmma64_reuse(float (&d)[32], const uint32_t* a, uint64_t db, uint32_t zero) {
  asm volatile("{\n.reg .pred p;\nsetp.ne.u32 p, %37, 0;\nwgmma.mma_async.sync.aligned.m64n64k16.f32.bf16.bf16 " WG_D32 ", {%32, %33, %34, %35}, %36, p, 1, 1, %38;\n}"
    : "+f"(d[0]), "+f"(d[1]), "+f"(d[2]), "+f"(d[3]), "+f"(d[4]), "+f"(d[5]), "+f"(d[6]), "+f"(d[7]),
      "+f"(d[8]), "+f"(d[9]), "+f"(d[10]), "+f"(d[11]), "+f"(d[12]), "+f"(d[13]), "+f"(d[14]), "+f"(d[15]),
      "+f"(d[16]), "+f"(d[17]), "+f"(d[18]), "+f"(d[19]), "+f"(d[20]), "+f"(d[21]), "+f"(d[22]), "+f"(d[23]),
      "+f"(d[24]), "+f"(d[25]), "+f"(d[26]), "+f"(d[27]), "+f"(d[28]), "+f"(d[29]), "+f"(d[30]), "+f"(d[31])
    : "r"(a[0]), "r"(a[1]), "r"(a[2]), "r"(a[3]), "l"(db), "r"(zero), "n"(TB));
}
template <int TB> __device__ __forceinline__ void wgmma64_set(float (&d)[32], const uint32_t* a, uint64_t db) {
  asm volatile("wgmma.mma_async.sync.aligned.m64n64k16.f32.bf16.bf16 " WG_D32 ", {%32, %33, %34, %35}, %36, 0, 1, 1, %37;"
    : "=f"(d[0]), "=f"(d[1]), "=f"(d[2]), "=f"(d[3]), "=f"(d[4]), "=f"(d[5]), "=f"(d[6]), "=f"(d[7]),
      "=f"(d[8]), "=f"(d[9]), "=f"(d[10]), "=f"(d[11]), "=f"(d[12]), "=f"(d[13]), "=f"(d[14]), "=f"(d[15]),
      "=f"(d[16]), "=f"(d[17]), "=f"(d[18]), "=f"(d[19]), "=f"(d[20]), "=f"(d[21]), "=f"(d[22]), "=f"(d[23]),
      "=f"(d[24]), "=f"(d[25]), "=f"(d[26]), "=f"(d[27]), "=f"(d[28]), "=f"(d[29]), "=f"(d[30]), "=f"(d[31])
    : "r"(a[0]), "r"(a[1]), "r"(a[2]), "r"(a[3]), "l"(db), "n"(TB));
}

__device__ __forceinline__ void wgmma72_acc(float (&d)[36], const uint32_t* a, uint64_t db) {
  asm volatile("wgmma.mma_async.sync.aligned.m64n72k16.f32.bf16.bf16 {%0, %1, %2, %3, %4, %5, %6, %7, %8, %9, %10, %11, %12, %13, %14, %15, %16, %17, %18, %19, %20, %21, %22, %23, %24, %25, %26, %27, %28, %29, %30, %31, %32, %33, %34, %35}, {%36, %37, %38, %39}, %40, 1, 1, 1, 1;"
    : "+f"(d[0]), "+f"(d[1]), "+f"(d[2]), "+f"(d[3]), "+f"(d[4]), "+f"(d[5]), "+f"(d[6]), "+f"(d[7]), "+f"(d[8]),
      "+f"(d[9]), "+f"(d[10]), "+f"(d[11]), "+f"(d[12]), "+f"(d[13]), "+f"(d[14]), "+f"(d[15]), "+f"(d[16]), "+f"(d[17]),
      "+f"(d[18]), "+f"(d[19]), "+f"(d[20]), "+f"(d[21]), "+f"(d[22]), "+f"(d[23]), "+f"(d[24]), "+f"(d[25]), "+f"(d[26]),
      "+f"(d[27]), "+f"(d[28]), "+f"(d[29]), "+f"(d[30]), "+f"(d[31]), "+f"(d[32]), "+f"(d[33]), "+f"(d[34]), "+f"(d[35])
    : "r"(a[0]), "r"(a[1]), "r"(a[2]), "r"(a[3]), "l"(db));
}
__device__ __forceinline__ void wgmma16_acc(float* d, const uint32_t* a, uint64_t db) {
  asm volatile("wgmma.mma_async.sync.aligned.m64n16k16.f32.bf16.bf16 {%0, %1, %2, %3, %4, %5, %6, %7}, {%8, %9, %10, %11}, %12, 1, 1, 1, 0;"
    : "+f"(d[0]), "+f"(d[1]), "+f"(d[2]), "+f"(d[3]), "+f"(d[4]), "+f"(d[5]), "+f"(d[6]), "+f"(d[7])
    : "r"(a[0]), "r"(a[1]), "r"(a[2]), "r"(a[3]), "l"(db));
}
__device__ __forceinline__ void hmma(float (&d)[4], const uint32_t* a, uint32_t b0, uint32_t b1) {
  asm("mma.sync.aligned.m16n8k16.row.col.f32.bf16.bf16.f32 {%0, %1, %2, %3}, {%4, %5, %6, %7}, {%8, %9}, {%0, %1, %2, %3};"
    : "+f"(d[0]), "+f"(d[1]), "+f"(d[2]), "+f"(d[3]) : "r"(a[0]), "r"(a[1]), "r"(a[2]), "r"(a[3]), "r"(b0), "r"(b1));
}

__device__ __forceinline__ void hmma8(float (&d)[4], const uint32_t* a, uint32_t b0) {
  asm("mma.sync.aligned.m16n8k8.row.col.f32.bf16.bf16.f32 {%0, %1, %2, %3}, {%4, %5}, {%6}, {%0, %1, %2, %3};"
    : "+f"(d[0]), "+f"(d[1]), "+f"(d[2]), "+f"(d[3]) : "r"(a[0]), "r"(a[1]), "r"(b0));
}

template <bool FIRST> __device__ __forceinline__ void mma_tile(float (&d)[32], const uint32_t (&a)[16], uint64_t db) {
  WG_FENCE();
#pragma unroll
  for (int s = 0; s < 4; s++) {
    if (FIRST && s == 0) wgmma64_set<1>(d, &a[0], db); else wgmma64_acc<1>(d, &a[4 * s], db + s * 128);
  }
  WG_COMMIT();
}
__device__ __forceinline__ void mma_tile_reuse(float (&d)[32], const uint32_t (&a)[16], uint64_t db) {
  WG_FENCE();
  wgmma64_reuse<1>(d, &a[0], db, blockIdx.y);
#pragma unroll
  for (int s = 1; s < 4; s++) wgmma64_acc<1>(d, &a[4 * s], db + s * 128);
  WG_COMMIT();
}
template <int ROW> __device__ __forceinline__ void fold_step(float (&d)[32], const uint32_t (&mu)[4]) {
  wgmma64_acc<1>(d, mu, (uint64_t)((SM_BASE + SM_CS + ROW * 128) >> 4) | (uint64_t(1) << 16) | (uint64_t(1) << 62));
}
template <int ROW> __device__ __forceinline__ void mma_fold(float (&d)[32], const uint32_t (&mu)[4]) {
  WG_FENCE();
  fold_step<ROW>(d, mu);
  WG_COMMIT();
}
template <int ROW> __device__ __forceinline__ void mma_tile_fold(float (&d)[32], const uint32_t (&a)[16], uint64_t db, const uint32_t (&mu)[4]) {
  WG_FENCE();
#pragma unroll
  for (int s = 0; s < 4; s++) wgmma64_acc<1>(d, &a[4 * s], db + s * 128);
  fold_step<ROW>(d, mu);
  WG_COMMIT();
}
__device__ __forceinline__ void mma_add_half(float (&d)[32], const uint32_t (&a)[16]) {
  const uint64_t db = (uint64_t)((SM_BASE + SM_EYE) >> 4) | (uint64_t(8) << 16) | (uint64_t(8) << 32);
  WG_FENCE();
#pragma unroll
  for (int s = 0; s < 4; s++) wgmma16_acc(&d[8 * s], &a[4 * s], db);
  WG_COMMIT();
}
#define ACQUIRE(f) mbar_wait(SM_BASE + SM_FULL + ((f) % NSTAGE) * 8, ((f) / NSTAGE) & 1)
__device__ __forceinline__ void mbar_probe(uint32_t& ok, uint32_t bar, uint32_t parity) {
  asm volatile("{\n.reg .pred p;\nmbarrier.test_wait.parity.shared::cta.b64 p, [%1], %2;\nselp.u32 %0, %0, 0, p;\n}"
               : "+r"(ok) : "r"(bar), "r"(parity) : "memory");
}
template <int F, int N> __device__ __forceinline__ uint32_t probe_n() {
  static_assert(F % NSTAGE + N <= NSTAGE, "stages must not wrap");
  uint32_t ok = 1;
#pragma unroll
  for (int i = 0; i < N; i++) mbar_probe(ok, SM_BASE + SM_FULL + (F % NSTAGE + i) * 8, (F / NSTAGE) & 1);
  return ok;
}
template <int F, int N> __device__ __forceinline__ void settle_n(uint32_t ok) {
  if (__builtin_expect(!ok, 0)) {
#pragma unroll 1
    for (int i = 0; i < N; i++) mbar_wait(SM_BASE + SM_FULL + (F % NSTAGE + i) * 8, (F / NSTAGE) & 1);
  }
}
template <int F, int N> __device__ __forceinline__ void acquire_n() { settle_n<F, N>(probe_n<F, N>()); }
#define RELEASE(f0, f1) do { if (lane == 0) { _Pragma("unroll") for (int f_ = (f0); f_ <= (f1); f_++) mbar_arrive(SM_BASE + SM_EMPTY + (f_ % NSTAGE) * 8); } } while (0)
constexpr uint64_t RING = (uint64_t)(SM_BASE >> 4) | (uint64_t(1) << 16) | (uint64_t(64) << 32) | (uint64_t(1) << 62);
#define LO(f) (RING + ((f) % NSTAGE) * 1024)
#define HI(f) (RING + ((f) % NSTAGE) * 1024 + 512)

template <int C> __device__ __forceinline__ uint4* peer(uint4* p) {
  asm volatile("" : "+l"(p));
  return (uint4*)((uintptr_t)p ^ (C * X_SIZE * sizeof(uint4)));
}
__device__ __forceinline__ uint32_t clock_now() { uint32_t c; asm volatile("mov.u32 %0, %%clock;" : "=r"(c) :: "memory"); return c; }
__device__ __forceinline__ void publish(uint4* dst, uint32_t (&a)[16], uint32_t tag) {
#pragma unroll
  for (int s = 0; s < 4; s++) a[4 * s] = (a[4 * s] & ~1u) | tag;
  pin(a);
  SCHED();
#pragma unroll
  for (int s = 0; s < 4; s++) st_vec(dst + s * 128, a[4 * s], a[4 * s + 1], a[4 * s + 2], a[4 * s + 3]);
  SCHED();
}
__device__ __forceinline__ void fetch(const uint4* src, uint32_t (&a)[16]) {
#pragma unroll
  for (int s = 0; s < 4; s++) ld_vec(src + s * 128, a[4 * s], a[4 * s + 1], a[4 * s + 2], a[4 * s + 3]);
}
__device__ __forceinline__ uint32_t miss(const uint32_t (&a)[16], uint32_t tag) {
  return (a[0] ^ tag) | (a[4] ^ tag) | (a[8] ^ tag) | (a[12] ^ tag);
}
__device__ __forceinline__ bool stale(uint32_t v) { return __any_sync(0xffffffffu, here(v) & 1u); }
template <int N = 2> __device__ __forceinline__ void announce(Scratch* sc, bool leader) {
  asm volatile("{\n.reg .pred p;\nsetp.ne.u32 p, %1, 0;\n@p red.relaxed.gpu.global.add.u32 [%0], %2;\n}"
               :: "l"(sc->step[blockIdx.x]), "r"((uint32_t)leader), "n"(N) : "memory");
}
__device__ __forceinline__ uint32_t launch_index(const Scratch* sc) { return *(const volatile uint32_t*)sc->step[blockIdx.x] >> 4; }
__device__ __forceinline__ void stat_fetch(const Scratch* sc, uint32_t (&st)[4]) {
  const uint32_t th = here(threadIdx.x);
  ld_vec(&sc->x[(blockIdx.x & ~3u) + (th & 3)][X_ST + (th >> 2)], st[0], st[1], st[2], st[3]);
}
template <int C, int SLOT> __device__ __forceinline__ void gather_first(uint32_t (&A)[4][16], uint32_t (&st)[4], const Scratch* sc, uint4* xp, uint32_t tag, uint32_t sent) {
  if (TIMED) { while (clock_now() - sent < GD) {} } else bar_sync(BAR_GO, 160);
  fetch(peer<1>(xp) + SLOT, A[1]); fetch(peer<2>(xp) + SLOT, A[2]); fetch(peer<3>(xp) + SLOT, A[3]);
  if (SLOT == X_AG0) stat_fetch(sc, st);
  uint32_t spin = 0;
  while (__builtin_expect(stale(miss(A[1], tag) | miss(A[C], tag)), 0) && ++spin < SPIN_LIMIT) {
    fetch(peer<1>(xp) + SLOT, A[1]);
    if (C == 2) fetch(peer<2>(xp) + SLOT, A[2]);
  }
}
template <int C, int SLOT> __device__ __forceinline__ void gather_rest(uint32_t (&A)[4][16], uint4* xp, uint32_t tag) {
  SCHED();
  uint32_t spin = 0;
  while (__builtin_expect(stale(miss(A[C + 1], tag) | miss(A[3], tag)), 0) && ++spin < SPIN_LIMIT) {
    if (C == 1) fetch(peer<2>(xp) + SLOT, A[2]);
    fetch(peer<3>(xp) + SLOT, A[3]);
  }
}
__device__ __forceinline__ void pack_acc(const float (&d)[32], uint32_t (&a)[16]) {
#pragma unroll
  for (int i = 0; i < 16; i++) a[i] = pack2(d[2 * i], d[2 * i + 1]);
}
__device__ __forceinline__ void frag_store(uint32_t slot, const uint32_t (&a)[16]) {
#pragma unroll
  for (int s = 0; s < 4; s++) sts128(slot + s * 512, a[4 * s], a[4 * s + 1], a[4 * s + 2], a[4 * s + 3]);
}
__device__ __forceinline__ void tile_store(uint32_t maddr, const uint32_t (&a)[16]) {
#pragma unroll
  for (int s = 0; s < 4; s++) stsm4(maddr ^ (s << 5), &a[4 * s]);
}
__device__ __forceinline__ void tile_load(uint32_t maddr, uint32_t (&a)[16]) {
#pragma unroll
  for (int s = 0; s < 4; s++) ldsm4(maddr ^ (s << 5), &a[4 * s]);
}

__device__ __forceinline__ void res_load(uint32_t maddr, float (&d)[32]) {
  uint32_t a[16];
  tile_load(here(maddr) + 3 * TILE_BYTES, a);
#pragma unroll
  for (int i = 0; i < 16; i++) { d[2 * i] = bf_lo(a[i]); d[2 * i + 1] = bf_hi(a[i]); }
  pin(d);
}

struct RowAcc { float s[2][4], u[2][4], v[2][4]; };
__device__ __forceinline__ void row_sums(RowAcc& t, const uint32_t (&a)[16]) {
#pragma unroll
  for (int s = 0; s < 4; s++) hmma(t.s[s & 1], &a[4 * s], 0x3F803F80u, 0x3F803F80u);
}
__device__ __forceinline__ void row_gram(RowAcc& t, const uint32_t (&a)[16]) {
#pragma unroll
  for (int s = 0; s < 8; s++) {
    hmma8(t.u[s & 1], &a[2 * s], a[2 * s]);
    hmma8(t.v[s & 1], &a[2 * s], a[2 * s + 1]);
  }
}
__device__ __forceinline__ float2 row_squares(const RowAcc& t, bool odd) {
  return make_float2(odd ? t.u[0][1] + t.u[1][1] : t.u[0][0] + t.u[1][0], odd ? t.v[0][3] + t.v[1][3] : t.v[0][2] + t.v[1][2]);
}
__device__ __forceinline__ void stat_publish(const uint32_t (&a)[16], Scratch* sc, uint32_t th, uint32_t tag) {
  RowAcc t = {};
  row_sums(t, a);
  row_gram(t, a);
  const float2 q = row_squares(t, th & 4);
  if ((th & 3) == ((th >> 3) & 3))
    st_vec(&sc->x[blockIdx.x][X_ST + (th >> 2)], (__float_as_uint(t.s[0][0] + t.s[1][0]) & ~1u) | tag, __float_as_uint(q.x),
           __float_as_uint(t.s[0][2] + t.s[1][2]), __float_as_uint(q.y));
}
struct RowNorm { float m0, rs0, m1, rs1; };
__device__ __forceinline__ RowNorm row_norm(float s0, float q0, float s1, float q1, float scale) {
  RowNorm n;
  n.m0 = s0 * (1.f / DM); n.m1 = s1 * (1.f / DM);
  n.rs0 = scale * rsqrt_hw(fmaxf(fmaf(-n.m0, n.m0, q0 * (1.f / DM)), 0.f) + LN_EPS);
  n.rs1 = scale * rsqrt_hw(fmaxf(fmaf(-n.m1, n.m1, q1 * (1.f / DM)), 0.f) + LN_EPS);
  return n;
}
__device__ __forceinline__ RowNorm stat_finish(const Scratch* sc, uint32_t (&st)[4], uint32_t tag, float scale) {
  uint32_t spin = 0;
  while (__builtin_expect(stale(st[0] ^ tag), 0) && ++spin < SPIN_LIMIT) stat_fetch(sc, st);
  float f[4];
#pragma unroll
  for (int i = 0; i < 4; i++) {
    f[i] = __uint_as_float(st[i]);
    f[i] += __shfl_xor_sync(0xffffffffu, f[i], 1);
    f[i] += __shfl_xor_sync(0xffffffffu, f[i], 2);
  }
  return row_norm(f[0], f[1], f[2], f[3], scale);
}
__device__ __forceinline__ void mean_frag(uint32_t (&mu)[4], const RowNorm& n, bool sel) {
  const float a = sel ? -n.m0 : 0.f, c = sel ? -n.m1 : 0.f;
  mu[0] = pack2(a, a); mu[1] = pack2(c, c);
  const float al = a - bf_lo(mu[0]), cl = c - bf_lo(mu[1]);
  mu[2] = pack2(al, al); mu[3] = pack2(cl, cl);
  pin(mu);
}
__device__ __forceinline__ void centre(uint32_t (&a)[16], uint32_t m0, uint32_t m1) {
#pragma unroll
  for (int i = 0; i < 16; i++) asm("sub.rn.bf16x2 %0, %0, %1;" : "+r"(a[i]) : "r"((i & 1) ? m1 : m0));
  pin(a);
}
__device__ __forceinline__ void scale_pack(const float (&d)[32], uint32_t (&a)[16], float rs0, float rs1) {
#pragma unroll
  for (int i = 0; i < 16; i++) { const float rs = (i & 1) ? rs1 : rs0; a[i] = pack2(d[2 * i] * rs, d[2 * i + 1] * rs); }
}
template <int S> __device__ __forceinline__ void silu_seg(float (&acc)[4][32], float (&tn)[2][4], uint32_t (&H)[4][16], float rs0, float rs1) {
  if (S >= 2) {
    const float* h = &acc[(S - 2) >> 3][4 * ((S - 2) & 7)];
    const float* v = tn[S & 1];
    uint32_t* o = &H[(S - 2) >> 3][2 * ((S - 2) & 7)];
    o[0] = pack2(fmaf(h[0], v[0], h[0]), fmaf(h[1], v[1], h[1]));
    o[1] = pack2(fmaf(h[2], v[2], h[2]), fmaf(h[3], v[3], h[3]));
    asm volatile("" : "+r"(o[0]), "+r"(o[1]));
  }
  if (S >= 1 && S <= 32) {
#pragma unroll
    for (int k = 0; k < 4; k++) tn[(S - 1) & 1][k] = tanh_hw(acc[((S - 1) >> 3) & 3][4 * ((S - 1) & 7) + k]);
  }
  if (S < 32) {
    float* h = &acc[(S >> 3) & 3][4 * (S & 7)];
    h[0] *= rs0; h[1] *= rs0; h[2] *= rs1; h[3] *= rs1;
    asm volatile("" : "+f"(h[0]), "+f"(h[1]), "+f"(h[2]), "+f"(h[3]));
  }
  SCHED();
}
template <int S0, int S1> __device__ __forceinline__ void silu_segs(float (&acc)[4][32], float (&tn)[2][4], uint32_t (&H)[4][16], float rs0, float rs1) {
  silu_seg<S0>(acc, tn, H, rs0, rs1);
  if constexpr (S0 + 1 < S1) silu_segs<S0 + 1, S1>(acc, tn, H, rs0, rs1);
}
template <int HALF> __device__ __forceinline__ void send_half(uint4* dst, const float (&d)[32], uint32_t tag) {
  uint32_t o[8];
#pragma unroll
  for (int i = 0; i < 8; i++) o[i] = pack2(d[16 * HALF + 2 * i], d[16 * HALF + 2 * i + 1]);
  o[0] = (o[0] & ~1u) | tag; o[4] = (o[4] & ~1u) | tag;
  pin(o);
  SCHED();
  st_vec(dst + HALF * 256, o[0], o[1], o[2], o[3]);
  st_vec(dst + HALF * 256 + 128, o[4], o[5], o[6], o[7]);
  SCHED();
}
__device__ __forceinline__ void send_residual(uint32_t (&a)[16], Scratch* sc, uint4* xp, uint32_t maddr, uint32_t tag, uint32_t& sent) {
  const uint32_t exact[4] = {a[0], a[4], a[8], a[12]};
  publish(xp + X_AG0, a, tag);
  if (TIMED) sent = clock_now();
  const uint32_t th = here(threadIdx.x);
  stat_publish(a, sc, th, tag);
  tile_store(here(maddr) + 3 * TILE_BYTES, a);
  stsm4(SM_BASE + SM_STG + 3 * TILE_BYTES + (th >> 5) * 2048 + (th & 7) * 128 + ((((th >> 2) & 6) ^ (th & 7)) << 4), exact);
}
template <int F, int N> __device__ __forceinline__ void proj_residual(uint32_t (&A)[4][16], Scratch* sc, uint4* xp, uint32_t maddr,
                                                                      uint32_t tag, uint32_t& sent) {
  float acc[32];
  if (TIMED && F == F_PW2) sent = clock_now();
  uint32_t st[4];
  acquire_n<F, N>();
  if (F == F_PW2) acquire_n<0, 5>();
  res_load(maddr, acc);
  mma_tile<false>(acc, A[0], LO(F));
  gather_first<2, X_AG1>(A, st, sc, xp, tag, sent);
  announce(sc, threadIdx.x == 0);
  mma_tile<false>(acc, A[1], HI(F));
  mma_tile<false>(acc, A[2], LO(F + 1));
  gather_rest<2, X_AG1>(A, xp, tag);
  PROF_MARK0(F == F_WO ? 11 : 16);
  mma_tile<false>(acc, A[3], HI(F + 1));
  WG_WAIT(0); pin(acc);
  pack_acc(acc, A[0]);
  send_residual(A[0], sc, xp, maddr, tag, sent);
}

__device__ __forceinline__ uint64_t ring_desc(uint32_t lo) { return (RING & ~uint64_t(0xFFFFFFFFu)) | lo; }
__device__ __forceinline__ void qk_tile(float (&S)[32], const uint32_t (&Q)[16], uint32_t dk) {
  wgmma64_reuse<0>(S, &Q[0], ring_desc(dk), blockIdx.y);
#pragma unroll
  for (int s = 1; s < 4; s++) wgmma64_acc<0>(S, &Q[4 * s], ring_desc(dk + s * 2));
}
__device__ __forceinline__ void qk_shift(float (&S)[32], const uint32_t (&nm)[4]) { wgmma64_acc<0>(S, nm, (uint64_t)((SM_BASE + SM_ONE) >> 4)); }
constexpr uint32_t RING_K = (uint32_t)RING, V_STEP = 1u - (1u << 16);
constexpr uint32_t RING_V = (SM_BASE >> 4) | (((SM_STG + 2 * TILE_BYTES) >> 4) << 16);
__device__ __forceinline__ void pv_tile(float (&O)[36], const uint32_t (&P)[16], uint32_t dv, uint32_t pad) {
#pragma unroll
  for (int s = 0; s < 4; s++) wgmma72_acc(O, &P[4 * s], ring_desc(dv + s * 128 * V_STEP + (s < 2 ? 0 : (s - 1) * pad)));
}
__device__ __forceinline__ void attn_step(const float (&Sc)[32], float (&Sn)[32], uint32_t (&Pc)[16], uint32_t (&Pp)[16], float (&O)[36],
                                          const uint32_t (&Q)[16], const uint32_t (&nm)[4], uint32_t dk, uint32_t dv, bool next, bool prev) {
  if (next) {
    WG_FENCE();
    qk_tile(Sn, Q, dk);
    qk_shift(Sn, nm);
  }
  if (prev) {
    WG_FENCE();
    pv_tile(O, Pp, dv, 0);
  }
  WG_COMMIT();
  SCHED();
#pragma unroll
  for (int i = 0; i < 16; i++) Pc[i] = pack2(ex2_hw(Sc[2 * i]), ex2_hw(Sc[2 * i + 1]));
  pin(Pc);
  SCHED();
}
__device__ __forceinline__ void load_taps(uint32_t (&tap)[15], const __nv_bfloat16* dw, int dir) {
  const uint32_t* src = (const uint32_t*)(dw + 64 * (blockIdx.x & 3)) + (here(threadIdx.x) & 31) + 7 * (DM / 2);
#pragma unroll
  for (int k = 0; k < 15; k++) tap[k] = __ldg(src + dir * (k - 7) * (DM / 2));
}
__device__ __forceinline__ void halve_taps(uint32_t (&tap)[15]) {
#pragma unroll
  for (int k = 0; k < 15; k++) asm("mul.rn.bf16x2 %0, %0, %1;" : "+r"(tap[k]) : "r"(0x3F003F00u));
  pin(tap);
}
__device__ __forceinline__ void attention_exact(float (&O)[36], const uint32_t (&Q)[16], const Scratch* sc, int bh, int lane, int half) {
  const char* kb = (const char*)&sc->kv[bh][0][0][0];
  const char* vb = (const char*)&sc->kv[bh][1][0][0];
  const int g = lane >> 2, q = lane & 3;
  float m0 = -INFINITY, m1 = -INFINITY, l0 = 0.f, l1 = 0.f;
  float o[4][4] = {};
#pragma unroll 1
  for (int k0 = 0; k0 < T_SEQ; k0 += 8) {
    float s[4] = {0.f, 0.f, 0.f, 0.f};
#pragma unroll
    for (int c = 0; c < 8; c++) hmma8(s, &Q[2 * c], __ldcg((const uint32_t*)(kb + (k0 + g) * 128 + ((c ^ g) << 4) + q * 4)));
    float n0 = fmaxf(s[0], s[1]), n1 = fmaxf(s[2], s[3]);
    n0 = fmaxf(n0, __shfl_xor_sync(0xffffffffu, n0, 1)); n1 = fmaxf(n1, __shfl_xor_sync(0xffffffffu, n1, 1));
    n0 = fmaxf(m0, fmaxf(n0, __shfl_xor_sync(0xffffffffu, n0, 2))); n1 = fmaxf(m1, fmaxf(n1, __shfl_xor_sync(0xffffffffu, n1, 2)));
    const float a0 = ex2_hw(m0 - n0), a1 = ex2_hw(m1 - n1);
    m0 = n0; m1 = n1;
    const uint32_t pp[2] = {pack2(ex2_hw(s[0] - n0), ex2_hw(s[1] - n0)), pack2(ex2_hw(s[2] - n1), ex2_hw(s[3] - n1))};
    l0 = fmaf(l0, a0, bf_lo(pp[0]) + bf_hi(pp[0])); l1 = fmaf(l1, a1, bf_lo(pp[1]) + bf_hi(pp[1]));
#pragma unroll
    for (int j = 0; j < 4; j++) {
      const int c = 4 * half + j;
      const uint32_t v0 = __ldcg((const uint16_t*)(vb + (k0 + 2 * q) * 128 + ((c ^ (2 * q)) << 4) + g * 2));
      const uint32_t v1 = __ldcg((const uint16_t*)(vb + (k0 + 2 * q + 1) * 128 + ((c ^ (2 * q + 1)) << 4) + g * 2));
      o[j][0] *= a0; o[j][1] *= a0; o[j][2] *= a1; o[j][3] *= a1;
      hmma8(o[j], pp, v0 | (v1 << 16));
    }
  }
  l0 += __shfl_xor_sync(0xffffffffu, l0, 1); l1 += __shfl_xor_sync(0xffffffffu, l1, 1);
  O[32] = l0 + __shfl_xor_sync(0xffffffffu, l0, 2); O[34] = l1 + __shfl_xor_sync(0xffffffffu, l1, 2);
#pragma unroll
  for (int i = 0; i < 16; i++) O[i] = o[i >> 2][i & 3];
}

__device__ __forceinline__ uint32_t fill_entry(int f, int r) {
  int m, x = r, y, dx = 0;
  if (f < F_QKV || f >= 48) {
    const int i = f & 15;
    m = f < F_QKV ? M_FF1A : M_FF2A;
    if (i < 8) { x = 4 * r + ((0xE2u >> i) & 1) * 2; y = r ^ ((0xE790u >> (2 * i)) & 3); dx = 1; }
    else { m++; x = r ^ (((i >> 1) - 3) & 3); y = 4 * r + 2 * (i & 1); }
  } else if (f < F_KV) {
    const int i = f - F_QKV;
    m = M_QKV;
    if (i == 1 || i >= 5) { y = r ^ (i == 1 ? 0 : 2); }
    else { x = 4 + r; y = r ^ (i ? i - 1 : 0); dx = 4; }
  } else if (f >= F_PW1 && f < F_PW2) {
    m = M_PW1; y = r ^ (f - F_PW1); dx = 4;
  } else {
    m = f < F_PW1 ? M_WO : M_PW2; y = r ^ ((f & 1) * 2);
  }
  return m | (x << 4) | (y << 8) | (dx << 16);
}
__device__ __forceinline__ void tma_fill(uint32_t st, const CUtensorMap* map, uint32_t x, uint32_t y, uint32_t x2, uint32_t y2) {
  asm volatile("{\n.reg .pred p;\nelect.sync _|p, 0xffffffff;\n"
               "@p mbarrier.arrive.expect_tx.shared::cta.b64 _, [%1], 16384;\n"
               "@p cp.async.bulk.tensor.2d.shared::cluster.global.mbarrier::complete_tx::bytes [%0], [%2, {%3, %4}], [%1];\n"
               "@p cp.async.bulk.tensor.2d.shared::cluster.global.mbarrier::complete_tx::bytes [%0 + 8192], [%2, {%5, %6}], [%1];\n}"
               :: "r"(SM_BASE + st * STAGE_BYTES), "r"(SM_BASE + SM_FULL + st * 8), "l"(map), "r"(x), "r"(y), "r"(x2), "r"(y2) : "memory");
}
template <int F0, int N> __device__ __forceinline__ void weight_fills(const Params& p, uint32_t entry) {
  uint32_t st = F0 % NSTAGE, parity = ((F0 / NSTAGE) & 1) ^ 1, e = __shfl_sync(0xffffffffu, entry, 0);
#pragma unroll 1
  for (int i = 1; i <= N; i++) {
    const uint32_t x = (e << 2) & 0x3C0, y = (e >> 2) & 0x3FC0, dx = (e >> 16) << 6;
    const CUtensorMap* map = &p.map[e & 15];
    e = __shfl_sync(0xffffffffu, entry, i);
    mbar_wait(SM_BASE + SM_EMPTY + st * 8, parity);
    tma_fill(st, map, x, y, x + dx, dx ? y : y ^ 64);
    if (++st == NSTAGE) { st = 0; parity ^= 1; }
  }
}
template <int KIND, int J> __device__ __forceinline__ uint32_t kv_fill(const uint4* kv, uint32_t want) {
  constexpr uint32_t st = (J < 6 ? 4 * (J >> 1) : 0) + (J & 1) + 2 * KIND;
  mbar_wait(SM_BASE + SM_EMPTY + st * 8, J < 6);
  uint32_t have, spin = 0;
#pragma unroll 1
  do {
    asm volatile("ld.volatile.shared.u32 %0, [%1];" : "=r"(have) : "r"(SM_BASE + SM_KVRDY + KIND * 4) : "memory");
    have &= want;
  } while (!have && ++spin < (SPIN_LIMIT << 4));
  const uint32_t tile = (__ffs(KIND ? want : have) - 1) & 15;
  asm volatile("{\n.reg .pred p;\nelect.sync _|p, 0xffffffff;\n"
               "@p mbarrier.arrive.expect_tx.shared::cta.b64 _, [%1], 16384;\n"
               "@p cp.async.bulk.shared::cluster.global.mbarrier::complete_tx::bytes [%0], [%2], 16384, [%1];\n}"
               :: "r"(SM_BASE + st * STAGE_BYTES), "r"(SM_BASE + SM_FULL + st * 8), "l"(kv + (KIND * 16 + tile) * 512) : "memory");
  PROF_AT(256 + 512 + (10 + KIND * 8 + J) * 4);
  return 1u << tile;
}
template <int J> __device__ __forceinline__ void kv_fills(const uint4* kv, uint32_t todo, uint32_t b1, uint32_t b2) {
  if constexpr (J >= 2) kv_fill<1, J - 2>(kv, b2);
  uint32_t b0 = 0;
  if constexpr (J < 8) b0 = kv_fill<0, J>(kv, J == 7 ? 0x4000u : todo);
  if constexpr (J < 9) kv_fills<J + 1>(kv, todo & ~b0, b0, b1);
}
__device__ __forceinline__ void reset_mailboxes(Scratch* sc, int half, int lane, uint32_t t_start) {
  while (clock_now() - t_start < TC) {}
#pragma unroll 1
  for (int i = half * 8; i < half * 9 + 8; i++) {
    const uint32_t t0 = clock_now();
    uint4* dst = &sc->x[blockIdx.x ^ (i < 12 ? (i >> 2) + 1 : 0)][i * 128 + lane];
#pragma unroll
    for (int k = 0; k < 4; k++) st_vec(dst + 32 * k, 0u, 0u, 0u, 0u);
    while (clock_now() - t0 < CLR_PACE) {}
  }
  bar_arrive(BAR_RST, 192);
  PROF_AT(256 + 512 + 28 * 4);
  asm volatile("fence.acq_rel.gpu;" ::: "memory");
  __syncwarp();
  announce<1>(sc, lane == 0);
  PROF_AT(256 + 512 + 2 * 4);
}
__device__ __forceinline__ void l2_prefetch(const void* p, uint32_t total, int b) {
  const uint32_t part = total / NCTA;
  asm volatile("cp.async.bulk.prefetch.L2.global [%0], %1;" :: "l"((const char*)p + (size_t)b * part), "r"(part) : "memory");
}

__global__ void __launch_bounds__(384, 1) conformer_kernel(Scratch* __restrict__ sc, __nv_bfloat16* __restrict__ out,
                                                           const __nv_bfloat16* __restrict__ dw, const __nv_bfloat16* __restrict__ xin,
                                                           const __nv_bfloat16* __restrict__ w_ff1a, const __grid_constant__ Params p) {
  extern __shared__ __align__(1024) uint8_t smem[];
  const int tid = threadIdx.x, lane = tid & 31;
  const uint32_t t_start = clock_now();
  const int b = blockIdx.x, r = b & 3, batch = b >> 6, t = (b >> 2) & 15;
  if ((uint32_t)__cvta_generic_to_shared(smem) != SM_BASE) return;
  PROF_AT(256 + (tid >> 7) * 256);
  PROF_TIME(30);
  const uint32_t crow = ((tid >> 1) & 48) + (lane >> 3);
  const uint32_t cdst = SM_BASE + crow * 128 + (((lane & 7) ^ (lane >> 3)) << 4);
  if (tid < 128) {
    const uint32_t g0 = batch * T_SEQ + t * 64 + crow, o = r * 128 + (lane & 7) * 16;
    const uint32_t lo = min(g0, 2 * T_SEQ - 5) * 512 + o, hi = min(g0 + 8, 2 * T_SEQ - 5) * 512 + o;
#pragma unroll
    for (int c = 0; c < 4; c++) {
#pragma unroll
      for (int i = 0; i < 4; i++)
        cp_async16((cdst ^ ((i & 1) << 6)) + SM_STG + (3 - c) * TILE_BYTES + i * 512, (const char*)xin + (((i & 2) ? hi : lo) ^ (c << 7)) + (i & 1) * 2048);
      asm volatile("cp.async.commit_group;" ::: "memory");
    }
  } else if (tid < 256) {
    const char* src = (const char*)w_ff1a + (64 * r + crow) * 2048 + r * 512 + (lane & 7) * 16;
#pragma unroll
    for (int c = 0; c < 4; c++) {
#pragma unroll
      for (int i = 0; i < 4; i++) cp_async16((cdst ^ ((i & 1) << 6)) + c * TILE_BYTES + i * 512, src + i * 8192 + c * 128);
      asm volatile("cp.async.commit_group;" ::: "memory");
    }
  }
  const int cw = __shfl_sync(0xffffffffu, tid >> 5, 0), wg = cw >> 2, w = cw & 3;

  if (wg == 2) {
    asm volatile("setmaxnreg.dec.sync.aligned.u32 40;");
    if (cw == 8) {
      if (lane == 0) {
        asm volatile("prefetch.tensormap [%0];" :: "l"(&p.map[M_FF1A]) : "memory");
#pragma unroll
        for (int i = 0; i < NSTAGE; i++) mbar_init(SM_BASE + SM_FULL + i * 8, 1);
        fence_async_smem();
      }
      __syncwarp();
      bar_arrive(0, 320);
      while (clock_now() - t_start < TF) {}
      PROF_MARK(9);
#pragma unroll
      for (int f = 2; f < 8; f++) {
        const uint32_t x = 256 * r + ((0xE2u >> f) & 1) * 128, y = (r ^ ((0xE790u >> (2 * f)) & 3)) * 64;
        tma_fill(f, &p.map[M_FF1A], x, y, x + 64, y);
      }
      PROF_MARK(1);
      uint32_t entry[2];
#pragma unroll 1
      for (int i = 0; i < 2; i++) { entry[1] = fill_entry(8 + i * 32 + lane, r); if (i == 0) entry[0] = entry[1]; }
      bar_sync(BAR_INIT, 64);
      weight_fills<8, F_KV - 8>(p, entry[0]);
      kv_fills<0>(sc->kv[batch * 4 + r][0][0], 0x1555u, 0u, 0u);
      weight_fills<F_WO, F_TOTAL - F_WO>(p, entry[1]);
    } else if (here(cw) != 11) {
      const int kind = w - 1;
      const uint32_t prev = launch_index(sc);
      if (kind == 0) {
        if (lane == 0) {
#pragma unroll
            for (int i = 0; i < NSTAGE; i++) mbar_init(SM_BASE + SM_EMPTY + i * 8, 4);
          sts64(SM_BASE + SM_KVRDY, 0u, 0u);
        }
        __syncwarp();
        bar_arrive(0, 320);
        bar_arrive(BAR_INIT, 64);
        if (lane == 0) {
          const uint32_t t0 = t_start;
          while (clock_now() - t0 < PF0) {}
          while (clock_now() - t0 < PF1) {}
          asm volatile("prefetch.tensormap [%0];" :: "l"(&p.map[M_FF1B]) : "memory");
          l2_prefetch(p.w_ff1b, 1024 * 256 * 2, b);
          while (clock_now() - t0 < PF2) {}
          l2_prefetch(p.w_qkv, 256 * 768 * 2, b);
          l2_prefetch(p.w_pw1, 256 * 512 * 2, b);
          l2_prefetch(p.w_ff2a, 256 * 1024 * 2, b);
          while (clock_now() - t0 < PF3) {}
          if (b < 15) l2_prefetch(dw, 512 * NCTA, b);
          l2_prefetch(p.w_o, 256 * 256 * 2, b);
          l2_prefetch(p.w_pw2, 256 * 256 * 2, b);
          l2_prefetch(p.w_ff2b, 1024 * 256 * 2, b);
#pragma unroll
          for (int i = M_QKV; i < M_COUNT; i++) asm volatile("prefetch.tensormap [%0];" :: "l"(&p.map[i]) : "memory");
        }
        __syncwarp();
      } else {
        reset_mailboxes(sc, 1, lane, t_start);
      }
      const uint32_t* flag = sc->flag[batch * 4 + r][kind * 16 + (lane & 15)];
      uint32_t spin = 0, ready;
#pragma unroll 1
      do {
        uint32_t v;
        asm volatile("ld.relaxed.gpu.global.u32 %0, [%1];" : "=r"(v) : "l"(flag) : "memory");
        ready = __ballot_sync(0xffffffffu, v - 1 == prev);
        asm volatile("st.volatile.shared.u32 [%0], %1;" :: "r"(SM_BASE + SM_KVRDY + kind * 4), "r"(ready & (ready >> 1)) : "memory");
        if (spin == 0) {
          if (kind == 0) bar_sync(BAR_K, 160); else bar_sync(BAR_V, 160);
          if (lane == 0) {
            PROF_MARK(4 + kind * 2);
            asm volatile("cp.async.bulk.global.shared::cta.bulk_group [%0], [%1], %2;"
                         :: "l"(sc->kv[batch * 4 + r][kind][t]), "r"(SM_BASE + SM_STG + kind * TILE_BYTES), "r"(TILE_BYTES) : "memory");
            asm volatile("cp.async.bulk.commit_group;\ncp.async.bulk.wait_group 0;" ::: "memory");
            asm volatile("st.relaxed.gpu.global.u32 [%0], %1;" :: "l"(sc->flag[batch * 4 + r][kind * 16 + t]), "r"(prev + 1) : "memory");
            PROF_MARK(5 + kind * 2);
          }
          __syncwarp();
        }
      } while (ready != 0xffffffffu && ++spin < SPIN_LIMIT);
    } else {
      const uint32_t* watch = sc->step[(b & ~3) + (lane & 3)];
      uint32_t seen;
      asm volatile("ld.relaxed.gpu.global.u32 %0, [%1];" : "=r"(seen) : "l"(watch) : "memory");
      reset_mailboxes(sc, 0, lane, t_start);
      uint32_t want = seen & ~15u;
#pragma unroll 1
      for (int k = 0; k < (TIMED ? 1 : 8); k++) {
        want += 2;
        uint32_t spin = 0;
#pragma unroll 1
        while (__any_sync(0xffffffffu, (int)(seen - want) < 0) && ++spin < SPIN_LIMIT)
          asm volatile("ld.relaxed.gpu.global.u32 %0, [%1];" : "=r"(seen) : "l"(watch) : "memory");
        bar_arrive(BAR_GO, 160);
        PROF_MARK(32 + k);
      }
    }
  } else {
    asm volatile("setmaxnreg.inc.sync.aligned.u32 232;");
    const int q = lane & 3, th = tid & 127;
    constexpr uint32_t stg = SM_BASE + SM_STG;
    const uint32_t mrow = 16 * w + (lane & 15);
    const uint32_t maddr = stg + mrow * 128 + (((lane >> 4) ^ (lane & 7)) << 4);
    const uint32_t qslot = stg + 2 * TILE_BYTES + w * 2048 + lane * 16;
    uint4* const xp = &sc->x[b][th];
    const int nvalid = T_SEQ - t * 64, row0 = 16 * w + (lane >> 2);

    uint32_t A[4][16];
    uint32_t st[4], sent = 0;
    bar_sync(0, 320);
    if (wg == 0) {
      RowAcc ra = {};
      cp_async_wait(0);
      __syncwarp();
      PROF_MARK0(45);
#pragma unroll
      for (int c = 0; c < 4; c++) tile_load(maddr + (3 - c) * TILE_BYTES, A[c]);
      row_sums(ra, A[0]); row_gram(ra, A[0]); row_sums(ra, A[1]); row_gram(ra, A[1]);
      pin(ra.s[0]); pin(ra.s[1]); pin(ra.u[0]); pin(ra.u[1]); pin(ra.v[0]); pin(ra.v[1]);
      SCHED();
      row_sums(ra, A[2]); row_sums(ra, A[3]); row_gram(ra, A[2]); row_gram(ra, A[3]);
      const float m0 = (ra.s[0][0] + ra.s[1][0]) * (1.f / DM), m1 = (ra.s[0][2] + ra.s[1][2]) * (1.f / DM);
      st[0] = pack2(m0, m0); st[1] = pack2(m1, m1);
      centre(A[0], st[0], st[1]);
      const float2 sq = row_squares(ra, lane & 4);
      st[2] = __float_as_uint(fmaf(-m0, m0, sq.x * (1.f / DM))); st[3] = __float_as_uint(fmaf(-m1, m1, sq.y * (1.f / DM)));
    } else {
      if (th < 112) sts128(SM_BASE + SM_CS + th * 16, 0, 0, 0, 0);
      sts32(SM_BASE + SM_EYE + th * 4, th >= 96 ? 0x3F803F80u : ((th & 32) == 0 && (th & 3) == ((th >> 3) & 3)) ? (0x3F00u << ((th & 4) * 4)) : 0u);
#pragma unroll
      for (int i = 0; i < 2; i++) {
        cp_async_wait(2 - 2 * i);
        fence_async_smem();
        bar_sync(BAR_WG1, 128);
        if (th == 0) mbar_arrive(SM_BASE + SM_FULL + i * 8);
      }
      PROF_MARK(6);
      const uint32_t tag = ~launch_index(sc) & 1;
      mbar_wait(SM_BASE + SM_FULL + 4 * 8, 0);
      PROF_MARK(5);
      if (b < 72) {
        const __nv_bfloat16* wp; int ld, col;
        if (b < 24) { wp = p.w_qkv; ld = 768; col = b * 32; }
        else if (b < 40) { wp = p.w_pw1; ld = 512; col = (b - 24) * 32; }
        else { wp = p.w_ff2a; ld = 1024; col = (b - 40) * 32; }
        const uint4* src = (const uint4*)(wp + (size_t)(th >> 2) * ld + col + q * 8);
        float c[8] = {0.f, 0.f, 0.f, 0.f, 0.f, 0.f, 0.f, 0.f};
#pragma unroll 1
        for (int h = 0; h < 2; h++, src += 16 * ld) {
#pragma unroll
          for (int i = 0; i < 4; i++) {
            const uint4 v = __ldg(src + i * 4 * ld);
            c[0] += bf_lo(v.x); c[1] += bf_hi(v.x); c[2] += bf_lo(v.y); c[3] += bf_hi(v.y);
            c[4] += bf_lo(v.z); c[5] += bf_hi(v.z); c[6] += bf_lo(v.w); c[7] += bf_hi(v.w);
          }
        }
#pragma unroll 1
        for (int m = 4; m <= 16; m <<= 1)
#pragma unroll
          for (int k = 0; k < 8; k++) c[k] += __shfl_xor_sync(0xffffffffu, c[k], m);
        if (lane < 4) {
          const uint32_t a = SM_BASE + SM_CS + 1792 + w * 128 + lane * 32;
          sts128(a, __float_as_uint(c[0]), __float_as_uint(c[1]), __float_as_uint(c[2]), __float_as_uint(c[3]));
          sts128(a + 16, __float_as_uint(c[4]), __float_as_uint(c[5]), __float_as_uint(c[6]), __float_as_uint(c[7]));
        }
        bar_sync(BAR_WG1, 128);
        if (th < 8) {
          float o[4] = {0.f, 0.f, 0.f, 0.f};
#pragma unroll 1
          for (int k = 0; k < 4; k++) {
            uint32_t e[4];
            lds128(SM_BASE + SM_CS + 1792 + k * 128 + th * 16, e[0], e[1], e[2], e[3]);
#pragma unroll
            for (int i = 0; i < 4; i++) o[i] += __uint_as_float(e[i]);
          }
          st_vec(&sc->cs[b * 8 + th], (__float_as_uint(o[0]) & ~1u) | tag, __float_as_uint(o[1]), __float_as_uint(o[2]), __float_as_uint(o[3]));
        }
      }
      bar_sync(BAR_WG1, 128);
      PROF_MARK(2);
      if (th < 72) {
        const int j = th >> 3, i = (th & 7) * 2;
        int src;
        if (j < CS_PW1) src = 320 + 64 * r + 16 * j;
        else if (j < CS_QKV) src = 192 + (j - CS_PW1) * 64 + 16 * r;
        else src = ((j - CS_QKV + 1) % 3) * 64 + 16 * r;
        uint32_t e[8], hi[4], lo[4], spin = 0;
#pragma unroll 1
        do {
          ld_vec(&sc->cs[src + i], e[0], e[1], e[2], e[3]);
          ld_vec(&sc->cs[src + i + 1], e[4], e[5], e[6], e[7]);
        } while ((((e[0] ^ tag) | (e[4] ^ tag)) & 1u) && ++spin < SPIN_LIMIT);
        e[0] &= ~1u; e[4] &= ~1u;
#pragma unroll
        for (int k = 0; k < 4; k++) {
          const float c0 = __uint_as_float(e[2 * k]), c1 = __uint_as_float(e[2 * k + 1]);
          hi[k] = pack2(c0, c1);
          lo[k] = pack2(c0 - bf_lo(hi[k]), c1 - bf_hi(hi[k]));
        }
        const uint32_t a = SM_BASE + SM_CS + j * 256 + i * 8;
        sts128(a ^ ((a >> 3) & 0x70), hi[0], hi[1], hi[2], hi[3]);
        sts128((a + 128) ^ (((a + 128) >> 3) & 0x70), lo[0], lo[1], lo[2], lo[3]);
      }
      fence_async_smem();
      PROF_MARK(4);
      bar_arrive(BAR_CS, 256);
    }

#pragma unroll 1
    for (uint32_t pass = 0; pass < 2; pass++) {
      uint32_t Q[16], shift;
      if (wg == 0) {
        float acc[4][32];
        uint32_t H[4][16];
        if (!pass) { PROF_MARK(47); ACQUIRE(0); }
        mma_tile<true>(acc[0], A[0], LO(0)); mma_tile<true>(acc[1], A[0], HI(0));
        if (!pass) ACQUIRE(1);
        mma_tile<true>(acc[2], A[0], LO(1)); mma_tile<true>(acc[3], A[0], HI(1));
        if (pass) {
          gather_first<1, X_AG0>(A, st, sc, xp, 1, sent);
        } else {
          centre(A[1], st[0], st[1]);
          acquire_n<2, 3>();
        }
        mma_tile<false>(acc[0], A[1], LO(2)); mma_tile<false>(acc[1], A[1], HI(2));
        if (pass) {
          gather_rest<1, X_AG0>(A, xp, 1);
          RELEASE(F_WO - 2 + NREL, F_PW2 + 1);
        } else {
          centre(A[2], st[0], st[1]); centre(A[3], st[0], st[1]);
        }
        PROF_MARK2(2, 18);
        mma_tile<false>(acc[0], A[2], LO(3)); mma_tile<false>(acc[0], A[3], LO(4));
        WG_WAIT(4);
        RELEASE(0, 1);
        uint32_t mu[4] = {0u, 0u, 0u, 0u};
        float rs0, rs1, tn[2][4];
        if (pass) {
          const RowNorm n = stat_finish(sc, st, 1, 0.5f);
          rs0 = n.rs0; rs1 = n.rs1;
          mean_frag(mu, n, q == 0);
        } else {
          const int src = (lane & 28) | (lane >> 3);
          rs0 = 0.5f * rsqrt_hw(fmaxf(__uint_as_float(__shfl_sync(0xffffffffu, st[2], src)), 0.f) + LN_EPS);
          rs1 = 0.5f * rsqrt_hw(fmaxf(__uint_as_float(__shfl_sync(0xffffffffu, st[3], src)), 0.f) + LN_EPS);
        }
        pin(mu);
        mma_fold<2 * CS_FF2>(acc[0], mu);
        mma_tile<false>(acc[1], A[2], HI(3));
#define SEGS(a, b) silu_segs<a, b>(acc, tn, H, rs0, rs1)
        WG_WAIT(1); pin(acc[0]);
        SEGS(0, 1);
        mma_tile_fold<2 * CS_FF2 + 2>(acc[1], A[3], HI(4), mu);
        SEGS(1, 3);
        uint32_t ok = probe_n<5, 1>();
        SEGS(3, 4);
        settle_n<5, 1>(ok);
        mma_tile<false>(acc[2], A[1], LO(5));
        SEGS(4, 5);
        ok = probe_n<6, 1>();
        SEGS(5, 6);
        settle_n<6, 1>(ok);
        mma_tile<false>(acc[2], A[2], LO(6));
        SEGS(6, 8);
        WG_WAIT(2); pin(acc[1]);
        RELEASE(2, 4);
        ok = probe_n<7, 1>();
        SEGS(8, 9);
        settle_n<7, 1>(ok);
        mma_tile_fold<2 * CS_FF2 + 4>(acc[2], A[3], LO(7), mu);
        SEGS(9, 12);
        mma_tile<false>(acc[3], A[1], HI(5));
        SEGS(12, 14);
        mma_tile<false>(acc[3], A[2], HI(6));
        SEGS(14, 16);
        WG_WAIT(2); pin(acc[2]);
        SEGS(16, 17);
        mma_tile_fold<2 * CS_FF2 + 6>(acc[3], A[3], HI(7), mu);
        SEGS(17, 19);
        ok = probe_n<8, 2>();
        SEGS(19, 20);
        settle_n<8, 2>(ok);
        mma_tile_reuse(acc[1], H[0], LO(8));
        SEGS(20, 22);
        mma_tile<false>(acc[1], H[1], HI(8));
        SEGS(22, 24);
        WG_WAIT(2); pin(acc[3]);
        RELEASE(5, 7);
        SEGS(24, 26);
        mma_tile<false>(acc[1], H[2], LO(9));
        SEGS(26, 27);
        ok = probe_n<10, 2>();
        SEGS(27, 28);
        settle_n<10, 2>(ok);
        mma_tile_reuse(acc[2], H[0], LO(10));
        SEGS(28, 31);
        mma_tile<false>(acc[2], H[1], HI(10));
        SEGS(31, 34);
#undef SEGS
        PROF_MARK2(3, 19);
        const uint32_t rtag = here(pass ^ 1);
        const uint4* rs_in = xp + X_RS;
        mma_tile<false>(acc[1], H[3], HI(9));
        mma_tile<false>(acc[2], H[2], LO(11));
        ok = probe_n<12, 2>();
        uint4* rs_out = peer<1>(xp) + X_RS;
        mma_tile<false>(acc[2], H[3], HI(11));
        settle_n<12, 2>(ok);
        if (!pass) bar_sync(BAR_RST, 192);
        WG_WAIT(2); pin(acc[1]);
        RELEASE(8, 9);
        send_half<0>(rs_out, acc[1], rtag);
        mma_tile_reuse(acc[3], H[0], LO(12));
        SCHED();
        send_half<1>(rs_out, acc[1], rtag);
        mma_tile<false>(acc[3], H[1], HI(12));
        rs_out = peer<2>(xp) + X_RS + 512;
        WG_WAIT(2); pin(acc[2]);
        send_half<0>(rs_out, acc[2], rtag);
        mma_tile<false>(acc[3], H[2], LO(13));
        SCHED();
        ok = probe_n<14, 2>();
        send_half<1>(rs_out, acc[2], rtag);
        mma_tile<false>(acc[3], H[3], HI(13));
        settle_n<14, 2>(ok);
        mma_tile_reuse(acc[1], H[0], LO(14));
        rs_out = peer<3>(xp) + X_RS + 1024;
        if (!pass) bar_sync(BAR_GO, 160);
        announce(sc, tid == 0);
        fetch(rs_in, A[1]);
        SCHED();
        mma_tile<false>(acc[1], H[1], HI(14));
        WG_WAIT(2); pin(acc[3]);
        send_half<0>(rs_out, acc[3], rtag);
        send_half<1>(rs_out, acc[3], rtag);
        if (TIMED) sent = clock_now();
        mma_tile<false>(acc[1], H[2], LO(15)); mma_tile<false>(acc[1], H[3], HI(15));
        SCHED();
        fetch(rs_in + 512, A[2]);
        SCHED();
        res_load(maddr, acc[2]);
        if (TIMED) { while (clock_now() - sent < RD) {} } else bar_sync(BAR_GO, 160);
        fetch(rs_in + 1024, A[3]);
        if (!pass) acquire_n<F_QKV, 3>();
        {
          uint32_t spin = 0;
          while (__builtin_expect(stale(miss(A[1], rtag) | miss(A[2], rtag) | miss(A[3], rtag)), 0) && ++spin < SPIN_LIMIT) {
            if (stale(miss(A[1], rtag) | miss(A[2], rtag))) { fetch(rs_in, A[1]); fetch(rs_in + 512, A[2]); }
            fetch(rs_in + 1024, A[3]);
          }
        }
        announce(sc, tid == 0 && !pass);
        mma_add_half(acc[2], A[1]);
        mma_add_half(acc[2], A[2]);
        mma_add_half(acc[2], A[3]);
        PROF_MARK2(4, 20);
        WG_WAIT(0); pin(acc[2]); pin(acc[1]);
#pragma unroll
        for (int i = 0; i < 16; i++) A[0][i] = pack2(fmaf(acc[1][2 * i], 0.5f, acc[2][2 * i]), fmaf(acc[1][2 * i + 1], 0.5f, acc[2][2 * i + 1]));
        if (pass) {
          PROF_MARK(21);
          stat_publish(A[0], sc, here(th), 0);
          stat_fetch(sc, st);
          const RowNorm fn = stat_finish(sc, st, 0, 1.f);
          const float nm0 = -fn.m0 * fn.rs0, nm1 = -fn.m1 * fn.rs1;
#pragma unroll
          for (int i = 0; i < 16; i++) {
            const float rs = (i & 1) ? fn.rs1 : fn.rs0, nm = (i & 1) ? nm1 : nm0;
            A[0][i] = pack2(fmaf(bf_lo(A[0][i]), rs, nm), fmaf(bf_hi(A[0][i]), rs, nm));
          }
          tile_store(here(maddr), A[0]);
          __syncwarp();
          const int row = 16 * w + (lane >> 3);
          uint4* dst = (uint4*)(out + ((size_t)batch * T_SEQ + t * 64 + row) * DM + 64 * r) + (lane & 7);
          const uint32_t src = stg + row * 128 + (((lane & 7) ^ (lane >> 3)) << 4);
#pragma unroll
          for (int i = 0; i < 4; i++) {
            uint4 v;
            lds128((src ^ ((i & 1) << 6)) + i * 512, v.x, v.y, v.z, v.w);
            if (row + 4 * i < nvalid) dst[i * 4 * (DM / 8)] = v;
          }
          PROF_MARK(22);
          PROF_TIME(31);
          break;
        }
        send_residual(A[0], sc, xp, maddr, 1, sent);
        PROF_MARK(5);
        mma_tile<true>(acc[0], A[0], LO(F_QKV)); mma_tile<true>(acc[1], A[0], HI(F_QKV));
        mma_tile<true>(acc[2], A[0], LO(F_QKV + 1));
        gather_first<1, X_AG0>(A, st, sc, xp, 1, sent);
        mma_tile<false>(acc[0], A[1], LO(F_QKV + 2)); mma_tile<false>(acc[1], A[1], HI(F_QKV + 2));
        acquire_n<F_QKV + 3, 3>();
        bar_sync(BAR_CS, 256);
        gather_rest<1, X_AG0>(A, xp, 1);
        PROF_MARK(6);
        mma_tile<false>(acc[0], A[2], LO(F_QKV + 3)); mma_tile<false>(acc[0], A[3], LO(F_QKV + 4));
        SCHED();
        {
          const RowNorm n = stat_finish(sc, st, 1, 1.f);
          rs0 = row0 < nvalid ? n.rs0 : 0.f; rs1 = row0 + 8 < nvalid ? n.rs1 : 0.f;
          mean_frag(mu, n, q == 3);
        }
        mma_fold<2 * CS_QKV - 6>(acc[0], mu);
        RELEASE(10, 15);
        WG_WAIT(0); pin(acc[0]);
        scale_pack(acc[0], A[0], rs0, rs1);
        tile_store(here(maddr), A[0]);
        SCHED();
        mma_tile<false>(acc[1], A[2], HI(F_QKV + 3));
        fence_async_smem();
        bar_arrive(BAR_K, 160);
        mma_tile_fold<2 * CS_QKV - 4>(acc[1], A[3], HI(F_QKV + 4), mu);
        mma_tile<false>(acc[2], A[1], HI(F_QKV + 1)); mma_tile<false>(acc[2], A[2], LO(F_QKV + 5));
        WG_WAIT(2); pin(acc[1]);
        scale_pack(acc[1], Q, rs0, rs1);
        tile_store(here(maddr) + TILE_BYTES, Q);
        fence_async_smem();
        bar_arrive(BAR_V, 160);
        mma_tile_fold<2 * CS_QKV - 2>(acc[2], A[3], HI(F_QKV + 5), mu);
        WG_WAIT(0); pin(acc[2]);
        scale_pack(acc[2], Q, rs0 * SM_SCALE_LOG2, rs1 * SM_SCALE_LOG2);
        frag_store(here(qslot), Q);
        {
          uint32_t d[4] = {0u, 0u, 0u, 0u};
#pragma unroll
          for (int i = 0; i < 16; i++) asm("fma.rn.bf16x2 %0, %1, %2, %0;" : "+r"(d[i & 3]) : "r"(Q[i]), "r"(A[0][i]));
          float s0 = (bf_lo(d[0]) + bf_hi(d[0])) + (bf_lo(d[2]) + bf_hi(d[2])), s1 = (bf_lo(d[1]) + bf_hi(d[1])) + (bf_lo(d[3]) + bf_hi(d[3]));
          shift = pack2(-s0, -s1);
          sts32(SM_BASE + SM_CS + 2 * CS_QKV * 128 + here(th) * 4, shift);
        }
        bar_arrive(BAR_Q, 256);
        RELEASE(F_QKV, F_QKV + 5);
      } else {
        bar_sync(BAR_Q, 256);
#pragma unroll
        for (int s = 0; s < 4; s++) lds128(qslot + s * 512, Q[4 * s], Q[4 * s + 1], Q[4 * s + 2], Q[4 * s + 3]);
        shift = lds32(SM_BASE + SM_CS + 2 * CS_QKV * 128 + th * 4);
        if (w < 2) {
          const uint32_t v = w ? 0u : 0x3F803F80u;
#pragma unroll
          for (int s = 0; s < 4; s++) sts128(qslot + s * 512, v, v, v, v);
          fence_async_smem();
        }
      }
      PROF_MARK(7);

      float O[36];
      {
        float S[2][32];
        uint32_t P[2][16], nm[4] = {shift & 0xFFFFu, shift >> 16, 0u, 0u};
        pin(Q); pin(nm);
        uint32_t sk = wg, sv = F_SPARE % NSTAGE + wg;
        mbar_wait(SM_BASE + SM_FULL + sv * 8, 1);
        if (wg == 1) bar_sync(BAR_ATT, 256);
        mbar_wait(SM_BASE + SM_FULL + sk * 8, 0);
        PROF_MARK(8);
        WG_FENCE();
        wgmma64_set<0>(S[0], nm, (uint64_t)((SM_BASE + SM_ONE) >> 4));
#pragma unroll
        for (int s = 0; s < 4; s++) wgmma64_acc<0>(S[0], &Q[4 * s], ring_desc(RING_K + sk * 1024 + s * 2));
        WG_COMMIT();
        SCHED();
#pragma unroll
        for (int i = 0; i < 36; i++) O[i] = 0.f;
#pragma unroll
        for (int i = 0; i < 32; i++) S[1][i] = 0.f;
#pragma unroll
        for (int i = 0; i < 16; i++) P[1][i] = 0u;
        pin(O); pin(S[1]); pin(P[1]);
        SCHED();
        WG_WAIT(0); pin(S[0]);
        if (wg == 0) bar_sync(BAR_ATT, 256);
#pragma unroll 1
        for (int it = 0; it < 4; it++) {
          const uint32_t sn = it >= 2 ? wg : sk + 4;
          uint32_t ok = 1;
          mbar_probe(ok, SM_BASE + SM_FULL + sn * 8, it >= 2);
          mbar_probe(ok, SM_BASE + SM_FULL + (sk + 2) * 8, it == 3);
          attn_step(S[0], S[1], P[0], P[1], O, Q, nm, RING_K + sk * 1024 + 512, RING_V + (sv * 1024 + 512) * V_STEP, true, it > 0);
          PROF_MARK(24 + it * 3);
          if (__builtin_expect(!ok, 0)) {
            mbar_wait(SM_BASE + SM_FULL + sn * 8, it >= 2);
            mbar_wait(SM_BASE + SM_FULL + (sk + 2) * 8, it == 3);
          }
          WG_WAIT(0); pin(O); pin(S[1]); pin(P[1]);
          asm volatile("{\n.reg .pred p;\nsetp.eq.u32 p, %2, 0;\n@p mbarrier.arrive.shared::cta.b64 _, [%0];\n@p mbarrier.arrive.shared::cta.b64 _, [%1];\n}"
                       :: "r"(SM_BASE + SM_EMPTY + sk * 8), "r"(SM_BASE + SM_EMPTY + sv * 8), "r"(lane) : "memory");
          PROF_MARK(25 + it * 3);
          sv = sk + 2; sk = sn;
          attn_step(S[1], S[0], P[1], P[0], O, Q, nm, RING_K + sk * 1024, RING_V + (sv * 1024) * V_STEP, it < 3, true);
          WG_WAIT(0); pin(O); pin(S[0]); pin(P[0]);
          PROF_MARK(26 + it * 3);
        }
        WG_FENCE();
        pv_tile(O, P[1], RING_V + (sv * 1024 + 512) * V_STEP, wg << 22);
        WG_COMMIT();
        announce<1>(sc, th == 0);
        WG_WAIT(0); pin(O);
      }
      PROF_MARK(9);

      {
        const uint32_t mo = stg + here(th) * 16;
        sts64(mo + 5 * 4096 + wg * 8, __float_as_uint(O[32]), __float_as_uint(O[34]));
        if (wg == 0) {
#pragma unroll
          for (int i = 4; i < 8; i++)
            sts128(mo + i * 2048, __float_as_uint(O[4 * i]), __float_as_uint(O[4 * i + 1]), __float_as_uint(O[4 * i + 2]), __float_as_uint(O[4 * i + 3]));
        } else {
#pragma unroll
          for (int i = 0; i < 4; i++)
            sts128(mo + i * 2048, __float_as_uint(O[4 * i]), __float_as_uint(O[4 * i + 1]), __float_as_uint(O[4 * i + 2]), __float_as_uint(O[4 * i + 3]));
#pragma unroll
          for (int i = 0; i < 16; i++) O[i] = O[16 + i];
        }
        bar_sync(BAR_MERGE, 256);
        uint32_t e[4];
        lds128(mo + 5 * 4096, e[0], e[1], e[2], e[3]);
        O[32] = __uint_as_float(e[0]) + __uint_as_float(e[2]); O[34] = __uint_as_float(e[1]) + __uint_as_float(e[3]);
#pragma unroll
        for (int i = 0; i < 4; i++) {
          lds128(mo + wg * TILE_BYTES + i * 2048, e[0], e[1], e[2], e[3]);
#pragma unroll
          for (int k = 0; k < 4; k++) O[4 * i + k] += __uint_as_float(e[k]);
        }
        const bool safe = O[32] > 0x1p-60f && O[32] < 0x1p60f && O[34] > 0x1p-60f && O[34] < 0x1p60f;
        if (__builtin_expect(__any_sync(0xffffffffu, !safe), 0)) attention_exact(O, Q, sc, batch * 4 + r, lane, wg);
        const float i0 = rcp_hw(O[32]), i1 = rcp_hw(O[34]);
#pragma unroll
        for (int i = 0; i < 8; i++) { const float v = (i & 1) ? i1 : i0; A[0][i] = pack2(O[2 * i] * v, O[2 * i + 1] * v); }
        A[0][0] &= ~1u; A[0][4] &= ~1u;
        uint4* dst = xp + X_AG1 + wg * 256;
        SCHED();
        st_vec(dst, A[0][0], A[0][1], A[0][2], A[0][3]);
        st_vec(dst + 128, A[0][4], A[0][5], A[0][6], A[0][7]);
        SCHED();
        if (TIMED) sent = clock_now();
      }
      const int dir = cw == 0 ? -1 : 1;
      uint32_t tap[15];
      if (wg == 1) {
        const uint32_t mo = stg + TILE_BYTES + here(th) * 16;
        sts128(mo, A[0][0], A[0][1], A[0][2], A[0][3]);
        sts128(mo + 2048, A[0][4], A[0][5], A[0][6], A[0][7]);
        bar_arrive(BAR_HALF, 256);
        load_taps(tap, dw, 1);
        halve_taps(tap);
      } else {
        PROF_MARK(10);
        const uint32_t mo = stg + TILE_BYTES + here(th) * 16;
        bar_sync(BAR_HALF, 256);
        lds128(mo, A[0][8], A[0][9], A[0][10], A[0][11]);
        lds128(mo + 2048, A[0][12], A[0][13], A[0][14], A[0][15]);
        proj_residual<F_WO, 6>(A, sc, xp, maddr, 0, sent);
        PROF_MARK(12);
        float acc[2][32];
        mma_tile<true>(acc[0], A[0], LO(F_PW1)); mma_tile<true>(acc[1], A[0], HI(F_PW1));
        load_taps(tap, dw, dir);
        gather_first<1, X_AG0>(A, st, sc, xp, 0, sent);
        mma_tile<false>(acc[1], A[1], HI(F_PW1 + 1)); mma_tile<false>(acc[0], A[1], LO(F_PW1 + 1));
        gather_rest<1, X_AG0>(A, xp, 0);
        RELEASE(F_WO - 2, F_WO + 1);
        PROF_MARK(13);
        mma_tile<false>(acc[1], A[2], HI(F_PW1 + 2)); mma_tile<false>(acc[1], A[3], HI(F_PW1 + 3));
        WG_WAIT(2);
        RELEASE(F_WO + 2, F_WO - 3 + NREL);
        SCHED();
        uint32_t mu[4];
        const RowNorm n = stat_finish(sc, st, 0, 0.5f);
        const float rs0 = row0 < nvalid ? n.rs0 : 0.f, rs1 = row0 + 8 < nvalid ? n.rs1 : 0.f;
        mean_frag(mu, n, q == 0);
        mma_fold<2 * CS_PW1 + 2>(acc[1], mu);
        mma_tile<false>(acc[0], A[2], LO(F_PW1 + 2));
        halve_taps(tap);
        mma_tile_fold<2 * CS_PW1>(acc[0], A[3], LO(F_PW1 + 3), mu);
        WG_WAIT(2); pin(acc[1]);
#pragma unroll
        for (int i = 0; i < 32; i++) acc[1][i] = tanh_hw(acc[1][i] * ((i & 2) ? rs1 : rs0));
#pragma unroll
        for (int i = 0; i < 32; i++) { const float rs = (i & 2) ? rs1 : rs0; acc[1][i] = fmaf(acc[1][i], rs, rs); }
        pin(acc[1]);
        SCHED();
        WG_WAIT(0); pin(acc[0]);
#pragma unroll
        for (int i = 0; i < 16; i++) A[0][i] = pack2(acc[0][2 * i] * acc[1][2 * i], acc[0][2 * i + 1] * acc[1][2 * i + 1]);
        const uint32_t ga = stg + TILE_BYTES + here(mrow) * G_PITCH + (lane >> 4) * 16;
#pragma unroll
        for (int s = 0; s < 4; s++) stsm4(ga + s * 32, &A[0][4 * s]);
      }
      {
        const uint32_t gsrc = stg + TILE_BYTES + (8 * cw - 7) * G_PITCH + lane * 4;
        const bool edge = cw == 0 || cw == 7;
        const bool nbr = cw == 0 ? t > 0 : t < 15;
        uint4* const hdst = &sc->x[b + 4 * dir][X_HALO + (cw == 0 ? 96 : 0) + lane];
        uint32_t in[22];
        bar_sync(BAR_G, 256);
        PROF_MARK(14);
        if (cw == 0) {
#pragma unroll
          for (int i = 14; i >= 0; i--) in[i] = lds32(gsrc + (21 - i) * G_PITCH);
        } else {
#pragma unroll
          for (int i = 14; i >= 0; i--) in[i] = lds32(gsrc + i * G_PITCH);
        }
        if (edge) {
          if (nbr) {
            st_vec(hdst, HALO_TAG, in[14], in[13], in[12]);
            st_vec(hdst + 32, HALO_TAG, in[11], in[10], in[9]);
            st_vec(hdst + 64, HALO_TAG, in[8], 0u, 0u);
          }
        } else {
#pragma unroll
          for (int i = 15; i < 22; i++) in[i] = lds32(gsrc + i * G_PITCH);
        }
        if (cw == 0) PROF_MARK0(40);
        uint32_t cv[8];
#pragma unroll
        for (int i = 0; i < 15; i++)
#pragma unroll
          for (int o = 0; o < 8; o++) {
            if (i == o) asm("mul.rn.bf16x2 %0, %1, %2;" : "=r"(cv[o]) : "r"(in[i]), "r"(tap[0]));
            if (i > o) asm("fma.rn.bf16x2 %0, %1, %2, %0;" : "+r"(cv[o]) : "r"(in[i]), "r"(tap[i - o]));
          }
        pin(cv);
        if (cw == 0) PROF_MARK0(41);
        if (edge) {
#pragma unroll
          for (int i = 15; i < 22; i++) in[i] = 0u;
          if (nbr) {
            const uint4* src = &sc->x[b][X_HALO + (cw == 0 ? 0 : 96) + lane];
            uint32_t e0, e1, e2, u0, u1, spin = 0;
#pragma unroll 1
            do {
              ld_vec(src, e0, in[15], in[16], in[17]);
              ld_vec(src + 32, e1, in[18], in[19], in[20]);
              ld_vec(src + 64, e2, in[21], u0, u1);
            } while (__any_sync(0xffffffffu, ((e0 ^ HALO_TAG) | (e1 ^ HALO_TAG) | (e2 ^ HALO_TAG)) != 0) && ++spin < SPIN_LIMIT);
          }
          announce<1>(sc, lane == 0);
        }
#pragma unroll
        for (int i = 15; i < 22; i++)
#pragma unroll
          for (int o = 0; o < 8; o++)
            if (i - o <= 14) asm("fma.rn.bf16x2 %0, %1, %2, %0;" : "+r"(cv[o]) : "r"(in[i]), "r"(tap[i - o]));
        if (cw == 0) PROF_MARK0(42);
        if (cw == 7) PROF_MARK0(43);
        const uint32_t fl = cw == 0 ? 7 : 0;
        const uint32_t cdst = (stg + cw * 1024 + lane * 4) ^ (fl * 144);
#pragma unroll
        for (int o = 0; o < 8; o++) {
          const float a = bf_lo(cv[o]), c = bf_hi(cv[o]);
          sts32(cdst ^ (o * 144), pack2(fmaf(a, tanh_hw(a), a), fmaf(c, tanh_hw(c), c)));
        }
      }
      if (wg == 1) {
        bar_arrive(BAR_C, 256);
        break;
      }
      bar_sync(BAR_C, 256);
      tile_load(here(maddr), A[0]);
      PROF_MARK(15);
      publish(xp + X_AG1, A[0], 1);
      proj_residual<F_PW2, 2>(A, sc, xp, maddr, 1, sent);
      PROF_MARK(17);
    }
  }
}

typedef CUresult (*EncodeFn)(CUtensorMap*, CUtensorMapDataType, cuuint32_t, void*, const cuuint64_t*, const cuuint64_t*,
                             const cuuint32_t*, const cuuint32_t*, CUtensorMapInterleave, CUtensorMapSwizzle,
                             CUtensorMapL2promotion, CUtensorMapFloatOOBfill);

void make_map(EncodeFn fn, CUtensorMap* m, const void* w, int rows, int cols, CUtensorMapSwizzle swz) {
  const cuuint64_t dims[2] = {(cuuint64_t)cols, (cuuint64_t)rows}, strides[1] = {(cuuint64_t)cols * 2};
  const cuuint32_t box[2] = {64, 64}, es[2] = {1, 1};
  fn(m, CU_TENSOR_MAP_DATA_TYPE_BFLOAT16, 2, const_cast<void*>(w), dims, strides, box, es, CU_TENSOR_MAP_INTERLEAVE_NONE,
     swz, CU_TENSOR_MAP_L2_PROMOTION_L2_128B, CU_TENSOR_MAP_FLOAT_OOB_FILL_NONE);
}

}

extern "C" void kernel_launch(void* const* d_in, const int* in_sizes, int n_in, void* d_out, int out_size) {
  static EncodeFn fn = nullptr;
  static Scratch* sc = nullptr;
  if (!fn) {
    void* f = nullptr;
    cudaDriverEntryPointQueryResult st;
    cudaGetDriverEntryPoint("cuTensorMapEncodeTiled", &f, cudaEnableDefault, &st);
    fn = (EncodeFn)f;
    void* raw = nullptr;
    cudaGetSymbolAddress(&raw, g_scratch);
    sc = (Scratch*)(((uintptr_t)raw + X_ALIGN - 1) & ~(uintptr_t)(X_ALIGN - 1));
    cudaFuncSetAttribute(conformer_kernel, cudaFuncAttributeMaxDynamicSharedMemorySize, SM_TOTAL);
  }
  typedef const __nv_bfloat16* W;
  const CUtensorMapSwizzle S = CU_TENSOR_MAP_SWIZZLE_128B;
  Params p;
  make_map(fn, &p.map[M_FF1A], d_in[1], 256, 1024, S);
  make_map(fn, &p.map[M_FF1B], d_in[2], 1024, 256, S);
  make_map(fn, &p.map[M_QKV], d_in[3], 256, 768, S);
  make_map(fn, &p.map[M_WO], d_in[4], 256, 256, S);
  make_map(fn, &p.map[M_PW1], d_in[5], 256, 512, S);
  make_map(fn, &p.map[M_PW2], d_in[7], 256, 256, S);
  make_map(fn, &p.map[M_FF2A], d_in[8], 256, 1024, S);
  make_map(fn, &p.map[M_FF2B], d_in[9], 1024, 256, S);
  p.w_ff1b = (W)d_in[2]; p.w_qkv = (W)d_in[3]; p.w_o = (W)d_in[4]; p.w_pw1 = (W)d_in[5];
  p.w_pw2 = (W)d_in[7]; p.w_ff2a = (W)d_in[8]; p.w_ff2b = (W)d_in[9];

  cudaLaunchConfig_t cfg = {};
  cfg.gridDim = dim3(NCTA);
  cfg.blockDim = dim3(384);
  cfg.dynamicSmemBytes = SM_TOTAL;
  cfg.stream = cudaStreamPerThread;
  cudaLaunchAttribute at[1];
  at[0].id = cudaLaunchAttributeCooperative;
  at[0].val.cooperative = 1;
  cfg.attrs = at;
  cfg.numAttrs = 1;
  cudaLaunchKernelEx(&cfg, conformer_kernel, sc, (__nv_bfloat16*)d_out, (W)d_in[6], (W)d_in[0], (W)d_in[1], p);
}
```

```cpp
#include <cuda_runtime.h>
#include <cuda_bf16.h>
#include <cuda.h>
#include <stdint.h>

namespace {

constexpr int T_SEQ = 1000;
constexpr int DM = 256;
constexpr int NCTA = 128;
constexpr int NSTAGE = 12;
constexpr uint32_t STAGE_BYTES = 16384;
constexpr uint32_t TILE_BYTES = 8192;
constexpr uint32_t SM_BASE = 1024;
constexpr uint32_t SM_STG = NSTAGE * STAGE_BYTES;
constexpr uint32_t SM_FULL = SM_STG + 32768;
constexpr uint32_t SM_EMPTY = SM_FULL + 96;
constexpr uint32_t SM_KVRDY = SM_FULL + 192;
constexpr uint32_t SM_EYE = SM_FULL + 256;
constexpr uint32_t SM_ONE = SM_FULL + 640;
constexpr uint32_t SM_CS = SM_FULL + 768;
constexpr uint32_t SM_TOTAL = SM_FULL + 3072;
constexpr int CS_FF2 = 0, CS_PW1 = 4, CS_QKV = 6;
constexpr uint32_t SPIN_LIMIT = 1u << 16;
constexpr float LN_EPS = 1e-5f;
constexpr float SM_SCALE_LOG2 = 0.125f * 1.4426950408889634f;
constexpr uint32_t G_PITCH = 144;
#define FSTR 8
#define TIMED 0
#define GD 400
#define RD 550
#define NREL 5
#define PF0 1
#define TF 1
#define TC 1
#define PF1 1400
#define PF2 2000
#define PF3 3500
#define CLR_PACE 150

constexpr int F_QKV = 16, F_SPARE = 22, F_KV = 24, F_WO = 40, F_PW1 = 42, F_PW2 = 46, F_TOTAL = 64;
enum { M_FF1A, M_FF1B, M_QKV, M_WO, M_PW1, M_PW2, M_FF2A, M_FF2B, M_COUNT };
enum { BAR_K = 1, BAR_V, BAR_Q, BAR_MERGE, BAR_G, BAR_C, BAR_WG1, BAR_GO, BAR_CS, BAR_ATT, BAR_INIT, BAR_HALF, BAR_RST };

struct Params {
  CUtensorMap map[M_COUNT];
  const __nv_bfloat16 *w_ff1b, *w_qkv, *w_o, *w_pw1, *w_pw2, *w_ff2a, *w_ff2b;
};

constexpr int X_RS = 0, X_AG1 = X_RS, X_HALO = X_RS + 512, X_AG0 = 1536, X_ST = 2048, X_SIZE = 4096;
constexpr uint32_t HALO_TAG = 0xFFFF0001u;
struct Scratch {
  uint4 x[NCTA][X_SIZE];
  uint4 kv[8][2][16][512];
  uint4 cs[576];
  uint32_t flag[8][32][FSTR];
  uint32_t step[NCTA][32];
};
constexpr size_t X_ALIGN = 4 * X_SIZE * sizeof(uint4);
__device__ uint8_t g_scratch[sizeof(Scratch) + X_ALIGN];
#define PROF_TIME(i)
#define PROF_MARK(i)
#define PROF_MARK2(i, j)
#define PROF_MARK0(i)
#define PROF_AT(a)

__device__ __forceinline__ void mbar_init(uint32_t bar, uint32_t cnt) {
  asm volatile("mbarrier.init.shared::cta.b64 [%0], %1;" :: "r"(bar), "r"(cnt) : "memory");
}
__device__ __forceinline__ void mbar_wait(uint32_t bar, uint32_t parity) {
  asm volatile("{\n.reg .pred p;\n.reg .u32 c;\nmov.u32 c, 0;\n"
               "WAIT_LOOP:\nmbarrier.try_wait.parity.shared::cta.b64 p, [%0], %1;\n@p bra WAIT_DONE;\n"
               "add.u32 c, c, 1;\nsetp.lt.u32 p, c, %2;\n@p bra WAIT_LOOP;\nWAIT_DONE:\n}"
               :: "r"(bar), "r"(parity), "n"(SPIN_LIMIT) : "memory");
}
__device__ __forceinline__ void mbar_arrive(uint32_t bar) {
  asm volatile("mbarrier.arrive.shared::cta.b64 _, [%0];" :: "r"(bar) : "memory");
}
#define bar_sync(id, n) asm volatile("bar.sync %0, %1;" :: "n"((int)(id)), "n"(n) : "memory")
#define bar_arrive(id, n) asm volatile("bar.arrive %0, %1;" :: "n"((int)(id)), "n"(n) : "memory")
__device__ __forceinline__ void fence_async_smem() { asm volatile("fence.proxy.async.shared::cta;" ::: "memory"); }

__device__ __forceinline__ void st_vec(uint4* p, uint32_t a, uint32_t b, uint32_t c, uint32_t d) {
  asm volatile("{\n.reg .b128 v;\n.reg .b64 lo, hi;\nmov.b64 lo, {%1, %2};\nmov.b64 hi, {%3, %4};\nmov.b128 v, {lo, hi};\n"
               "st.relaxed.gpu.global.b128 [%0], v;\n}" :: "l"(p), "r"(a), "r"(b), "r"(c), "r"(d) : "memory");
}
__device__ __forceinline__ void ld_vec(const uint4* p, uint32_t& a, uint32_t& b, uint32_t& c, uint32_t& d) {
  asm volatile("{\n.reg .b128 v;\n.reg .b64 lo, hi;\nld.relaxed.gpu.global.b128 v, [%4];\nmov.b128 {lo, hi}, v;\n"
               "mov.b64 {%0, %1}, lo;\nmov.b64 {%2, %3}, hi;\n}" : "=r"(a), "=r"(b), "=r"(c), "=r"(d) : "l"(p) : "memory");
}
__device__ __forceinline__ void sts128(uint32_t a, uint32_t x, uint32_t y, uint32_t z, uint32_t w) {
  asm volatile("st.shared.v4.u32 [%0], {%1, %2, %3, %4};" :: "r"(a), "r"(x), "r"(y), "r"(z), "r"(w) : "memory");
}
__device__ __forceinline__ void lds128(uint32_t a, uint32_t& x, uint32_t& y, uint32_t& z, uint32_t& w) {
  asm volatile("ld.shared.v4.u32 {%0, %1, %2, %3}, [%4];" : "=r"(x), "=r"(y), "=r"(z), "=r"(w) : "r"(a) : "memory");
}
__device__ __forceinline__ uint32_t lds32(uint32_t a) {
  uint32_t x; asm volatile("ld.shared.u32 %0, [%1];" : "=r"(x) : "r"(a) : "memory"); return x;
}
__device__ __forceinline__ void sts32(uint32_t a, uint32_t x) { asm volatile("st.shared.u32 [%0], %1;" :: "r"(a), "r"(x) : "memory"); }
__device__ __forceinline__ void sts64(uint32_t a, uint32_t x, uint32_t y) {
  asm volatile("st.shared.v2.u32 [%0], {%1, %2};" :: "r"(a), "r"(x), "r"(y) : "memory");
}
__device__ __forceinline__ void stsm4(uint32_t a, const uint32_t* r) {
  asm volatile("stmatrix.sync.aligned.m8n8.x4.shared.b16 [%0], {%1, %2, %3, %4};" :: "r"(a), "r"(r[0]), "r"(r[1]), "r"(r[2]), "r"(r[3]) : "memory");
}
__device__ __forceinline__ void ldsm4(uint32_t a, uint32_t* r) {
  asm volatile("ldmatrix.sync.aligned.m8n8.x4.shared.b16 {%0, %1, %2, %3}, [%4];" : "=r"(r[0]), "=r"(r[1]), "=r"(r[2]), "=r"(r[3]) : "r"(a) : "memory");
}
__device__ __forceinline__ uint32_t pack2(float lo, float hi) {
  uint32_t r; asm("cvt.rn.bf16x2.f32 %0, %1, %2;" : "=r"(r) : "f"(hi), "f"(lo)); return r;
}
__device__ __forceinline__ float bf_lo(uint32_t w) { return __uint_as_float(w << 16); }
__device__ __forceinline__ float bf_hi(uint32_t w) { return __uint_as_float(w & 0xffff0000u); }
__device__ __forceinline__ float tanh_hw(float x) { float y; asm volatile("tanh.approx.f32 %0, %1;" : "=f"(y) : "f"(x)); return y; }
__device__ __forceinline__ float rcp_hw(float x) { float y; asm("rcp.approx.ftz.f32 %0, %1;" : "=f"(y) : "f"(x)); return y; }
__device__ __forceinline__ float rsqrt_hw(float x) { float y; asm("rsqrt.approx.ftz.f32 %0, %1;" : "=f"(y) : "f"(x)); return y; }
__device__ __forceinline__ float ex2_hw(float x) { float y; asm("ex2.approx.ftz.f32 %0, %1;" : "=f"(y) : "f"(x)); return y; }

__device__ __forceinline__ uint32_t here(uint32_t v) { asm volatile("" : "+r"(v)); return v; }

#define SCHED() asm volatile("pmevent 1;" ::: "memory")
__device__ __forceinline__ void cp_async16(uint32_t dst, const void* src) {
  asm volatile("cp.async.cg.shared.global [%0], [%1], 16;" :: "r"(dst), "l"(src) : "memory");
}
__device__ __forceinline__ void cp_async_wait(int n) {
  if (n == 0) asm volatile("cp.async.wait_group 0;" ::: "memory");
  if (n == 1) asm volatile("cp.async.wait_group 1;" ::: "memory");
  if (n == 2) asm volatile("cp.async.wait_group 2;" ::: "memory");
  if (n == 3) asm volatile("cp.async.wait_group 3;" ::: "memory");
}
#define WG_FENCE() asm volatile("wgmma.fence.sync.aligned;" ::: "memory")
#define WG_COMMIT() asm volatile("wgmma.commit_group.sync.aligned;" ::: "memory")
#define WG_WAIT(n) asm volatile("wgmma.wait_group.sync.aligned %0;" :: "n"(n) : "memory")

template <int N> __device__ __forceinline__ void pin(float (&d)[N]) {
#pragma unroll
  for (int i = 0; i < N; i++) asm volatile("" : "+f"(d[i]) :: "memory");
}
template <int N> __device__ __forceinline__ void pin(uint32_t (&d)[N]) {
#pragma unroll
  for (int i = 0; i < N; i++) asm volatile("" : "+r"(d[i]) :: "memory");
}

#define WG_D32 "{%0, %1, %2, %3, %4, %5, %6, %7, %8, %9, %10, %11, %12, %13, %14, %15, %16, %17, %18, %19, %20, %21, %22, %23, %24, %25, %26, %27, %28, %29, %30, %31}"
template <int TB> __device__ __forceinline__ void wgmma64_acc(float (&d)[32], const uint32_t* a, uint64_t db) {
  asm volatile("wgmma.mma_async.sync.aligned.m64n64k16.f32.bf16.bf16 " WG_D32 ", {%32, %33, %34, %35}, %36, 1, 1, 1, %37;"
    : "+f"(d[0]), "+f"(d[1]), "+f"(d[2]), "+f"(d[3]), "+f"(d[4]), "+f"(d[5]), "+f"(d[6]), "+f"(d[7]),
      "+f"(d[8]), "+f"(d[9]), "+f"(d[10]), "+f"(d[11]), "+f"(d[12]), "+f"(d[13]), "+f"(d[14]), "+f"(d[15]),
      "+f"(d[16]), "+f"(d[17]), "+f"(d[18]), "+f"(d[19]), "+f"(d[20]), "+f"(d[21]), "+f"(d[22]), "+f"(d[23]),
      "+f"(d[24]), "+f"(d[25]), "+f"(d[26]), "+f"(d[27]), "+f"(d[28]), "+f"(d[29]), "+f"(d[30]), "+f"(d[31])
    : "r"(a[0]), "r"(a[1]), "r"(a[2]), "r"(a[3]), "l"(db), "n"(TB));
}
template <int TB> __device__ __forceinline__ void wgmma64_reuse(float (&d)[32], const uint32_t* a, uint64_t db, uint32_t zero) {
  asm volatile("{\n.reg .pred p;\nsetp.ne.u32 p, %37, 0;\nwgmma.mma_async.sync.aligned.m64n64k16.f32.bf16.bf16 " WG_D32 ", {%32, %33, %34, %35}, %36, p, 1, 1, %38;\n}"
    : "+f"(d[0]), "+f"(d[1]), "+f"(d[2]), "+f"(d[3]), "+f"(d[4]), "+f"(d[5]), "+f"(d[6]), "+f"(d[7]),
      "+f"(d[8]), "+f"(d[9]), "+f"(d[10]), "+f"(d[11]), "+f"(d[12]), "+f"(d[13]), "+f"(d[14]), "+f"(d[15]),
      "+f"(d[16]), "+f"(d[17]), "+f"(d[18]), "+f"(d[19]), "+f"(d[20]), "+f"(d[21]), "+f"(d[22]), "+f"(d[23]),
      "+f"(d[24]), "+f"(d[25]), "+f"(d[26]), "+f"(d[27]), "+f"(d[28]), "+f"(d[29]), "+f"(d[30]), "+f"(d[31])
    : "r"(a[0]), "r"(a[1]), "r"(a[2]), "r"(a[3]), "l"(db), "r"(zero), "n"(TB));
}
template <int TB> __device__ __forceinline__ void wgmma64_set(float (&d)[32], const uint32_t* a, uint64_t db) {
  asm volatile("wgmma.mma_async.sync.aligned.m64n64k16.f32.bf16.bf16 " WG_D32 ", {%32, %33, %34, %35}, %36, 0, 1, 1, %37;"
    : "=f"(d[0]), "=f"(d[1]), "=f"(d[2]), "=f"(d[3]), "=f"(d[4]), "=f"(d[5]), "=f"(d[6]), "=f"(d[7]),
      "=f"(d[8]), "=f"(d[9]), "=f"(d[10]), "=f"(d[11]), "=f"(d[12]), "=f"(d[13]), "=f"(d[14]), "=f"(d[15]),
      "=f"(d[16]), "=f"(d[17]), "=f"(d[18]), "=f"(d[19]), "=f"(d[20]), "=f"(d[21]), "=f"(d[22]), "=f"(d[23]),
      "=f"(d[24]), "=f"(d[25]), "=f"(d[26]), "=f"(d[27]), "=f"(d[28]), "=f"(d[29]), "=f"(d[30]), "=f"(d[31])
    : "r"(a[0]), "r"(a[1]), "r"(a[2]), "r"(a[3]), "l"(db), "n"(TB));
}

__device__ __forceinline__ void wgmma72_acc(float (&d)[36], const uint32_t* a, uint64_t db) {
  asm volatile("wgmma.mma_async.sync.aligned.m64n72k16.f32.bf16.bf16 {%0, %1, %2, %3, %4, %5, %6, %7, %8, %9, %10, %11, %12, %13, %14, %15, %16, %17, %18, %19, %20, %21, %22, %23, %24, %25, %26, %27, %28, %29, %30, %31, %32, %33, %34, %35}, {%36, %37, %38, %39}, %40, 1, 1, 1, 1;"
    : "+f"(d[0]), "+f"(d[1]), "+f"(d[2]), "+f"(d[3]), "+f"(d[4]), "+f"(d[5]), "+f"(d[6]), "+f"(d[7]), "+f"(d[8]),
      "+f"(d[9]), "+f"(d[10]), "+f"(d[11]), "+f"(d[12]), "+f"(d[13]), "+f"(d[14]), "+f"(d[15]), "+f"(d[16]), "+f"(d[17]),
      "+f"(d[18]), "+f"(d[19]), "+f"(d[20]), "+f"(d[21]), "+f"(d[22]), "+f"(d[23]), "+f"(d[24]), "+f"(d[25]), "+f"(d[26]),
      "+f"(d[27]), "+f"(d[28]), "+f"(d[29]), "+f"(d[30]), "+f"(d[31]), "+f"(d[32]), "+f"(d[33]), "+f"(d[34]), "+f"(d[35])
    : "r"(a[0]), "r"(a[1]), "r"(a[2]), "r"(a[3]), "l"(db));
}
__device__ __forceinline__ void wgmma16_acc(float* d, const uint32_t* a, uint64_t db) {
  asm volatile("wgmma.mma_async.sync.aligned.m64n16k16.f32.bf16.bf16 {%0, %1, %2, %3, %4, %5, %6, %7}, {%8, %9, %10, %11}, %12, 1, 1, 1, 0;"
    : "+f"(d[0]), "+f"(d[1]), "+f"(d[2]), "+f"(d[3]), "+f"(d[4]), "+f"(d[5]), "+f"(d[6]), "+f"(d[7])
    : "r"(a[0]), "r"(a[1]), "r"(a[2]), "r"(a[3]), "l"(db));
}
__device__ __forceinline__ void hmma(float (&d)[4], const uint32_t* a, uint32_t b0, uint32_t b1) {
  asm("mma.sync.aligned.m16n8k16.row.col.f32.bf16.bf16.f32 {%0, %1, %2, %3}, {%4, %5, %6, %7}, {%8, %9}, {%0, %1, %2, %3};"
    : "+f"(d[0]), "+f"(d[1]), "+f"(d[2]), "+f"(d[3]) : "r"(a[0]), "r"(a[1]), "r"(a[2]), "r"(a[3]), "r"(b0), "r"(b1));
}

__device__ __forceinline__ void hmma8(float (&d)[4], const uint32_t* a, uint32_t b0) {
  asm("mma.sync.aligned.m16n8k8.row.col.f32.bf16.bf16.f32 {%0, %1, %2, %3}, {%4, %5}, {%6}, {%0, %1, %2, %3};"
    : "+f"(d[0]), "+f"(d[1]), "+f"(d[2]), "+f"(d[3]) : "r"(a[0]), "r"(a[1]), "r"(b0));
}

template <bool FIRST> __device__ __forceinline__ void mma_tile(float (&d)[32], const uint32_t (&a)[16], uint64_t db) {
  WG_FENCE();
#pragma unroll
  for (int s = 0; s < 4; s++) {
    if (FIRST && s == 0) wgmma64_set<1>(d, &a[0], db); else wgmma64_acc<1>(d, &a[4 * s], db + s * 128);
  }
  WG_COMMIT();
}
__device__ __forceinline__ void mma_tile_reuse(float (&d)[32], const uint32_t (&a)[16], uint64_t db) {
  WG_FENCE();
  wgmma64_reuse<1>(d, &a[0], db, blockIdx.y);
#pragma unroll
  for (int s = 1; s < 4; s++) wgmma64_acc<1>(d, &a[4 * s], db + s * 128);
  WG_COMMIT();
}
template <int ROW> __device__ __forceinline__ void fold_step(float (&d)[32], const uint32_t (&mu)[4]) {
  wgmma64_acc<1>(d, mu, (uint64_t)((SM_BASE + SM_CS + ROW * 128) >> 4) | (uint64_t(1) << 16) | (uint64_t(1) << 62));
}
template <int ROW> __device__ __forceinline__ void mma_fold(float (&d)[32], const uint32_t (&mu)[4]) {
  WG_FENCE();
  fold_step<ROW>(d, mu);
  WG_COMMIT();
}
template <int ROW> __device__ __forceinline__ void mma_tile_fold(float (&d)[32], const uint32_t (&a)[16], uint64_t db, const uint32_t (&mu)[4]) {
  WG_FENCE();
#pragma unroll
  for (int s = 0; s < 4; s++) wgmma64_acc<1>(d, &a[4 * s], db + s * 128);
  fold_step<ROW>(d, mu);
  WG_COMMIT();
}
__device__ __forceinline__ void mma_add_half(float (&d)[32], const uint32_t (&a)[16]) {
  const uint64_t db = (uint64_t)((SM_BASE + SM_EYE) >> 4) | (uint64_t(8) << 16) | (uint64_t(8) << 32);
  WG_FENCE();
#pragma unroll
  for (int s = 0; s < 4; s++) wgmma16_acc(&d[8 * s], &a[4 * s], db);
  WG_COMMIT();
}
#define ACQUIRE(f) mbar_wait(SM_BASE + SM_FULL + ((f) % NSTAGE) * 8, ((f) / NSTAGE) & 1)
__device__ __forceinline__ void mbar_probe(uint32_t& ok, uint32_t bar, uint32_t parity) {
  asm volatile("{\n.reg .pred p;\nmbarrier.test_wait.parity.shared::cta.b64 p, [%1], %2;\nselp.u32 %0, %0, 0, p;\n}"
               : "+r"(ok) : "r"(bar), "r"(parity) : "memory");
}
template <int F, int N> __device__ __forceinline__ uint32_t probe_n() {
  static_assert(F % NSTAGE + N <= NSTAGE, "stages must not wrap");
  uint32_t ok = 1;
#pragma unroll
  for (int i = 0; i < N; i++) mbar_probe(ok, SM_BASE + SM_FULL + (F % NSTAGE + i) * 8, (F / NSTAGE) & 1);
  return ok;
}
template <int F, int N> __device__ __forceinline__ void settle_n(uint32_t ok) {
  if (__builtin_expect(!ok, 0)) {
#pragma unroll 1
    for (int i = 0; i < N; i++) mbar_wait(SM_BASE + SM_FULL + (F % NSTAGE + i) * 8, (F / NSTAGE) & 1);
  }
}
template <int F, int N> __device__ __forceinline__ void acquire_n() { settle_n<F, N>(probe_n<F, N>()); }
#define RELEASE(f0, f1) do { if (lane == 0) { _Pragma("unroll") for (int f_ = (f0); f_ <= (f1); f_++) mbar_arrive(SM_BASE + SM_EMPTY + (f_ % NSTAGE) * 8); } } while (0)
constexpr uint64_t RING = (uint64_t)(SM_BASE >> 4) | (uint64_t(1) << 16) | (uint64_t(64) << 32) | (uint64_t(1) << 62);
#define LO(f) (RING + ((f) % NSTAGE) * 1024)
#define HI(f) (RING + ((f) % NSTAGE) * 1024 + 512)

template <int C> __device__ __forceinline__ uint4* peer(uint4* p) {
  asm volatile("" : "+l"(p));
  return (uint4*)((uintptr_t)p ^ (C * X_SIZE * sizeof(uint4)));
}
__device__ __forceinline__ uint32_t clock_now() { uint32_t c; asm volatile("mov.u32 %0, %%clock;" : "=r"(c) :: "memory"); return c; }
__device__ __forceinline__ void publish(uint4* dst, uint32_t (&a)[16], uint32_t tag) {
#pragma unroll
  for (int s = 0; s < 4; s++) a[4 * s] = (a[4 * s] & ~1u) | tag;
  pin(a);
  SCHED();
#pragma unroll
  for (int s = 0; s < 4; s++) st_vec(dst + s * 128, a[4 * s], a[4 * s + 1], a[4 * s + 2], a[4 * s + 3]);
  SCHED();
}
__device__ __forceinline__ void fetch(const uint4* src, uint32_t (&a)[16]) {
#pragma unroll
  for (int s = 0; s < 4; s++) ld_vec(src + s * 128, a[4 * s], a[4 * s + 1], a[4 * s + 2], a[4 * s + 3]);
}
__device__ __forceinline__ uint32_t miss(const uint32_t (&a)[16], uint32_t tag) {
  return (a[0] ^ tag) | (a[4] ^ tag) | (a[8] ^ tag) | (a[12] ^ tag);
}
__device__ __forceinline__ bool stale(uint32_t v) { return __any_sync(0xffffffffu, here(v) & 1u); }
template <int N = 2> __device__ __forceinline__ void announce(Scratch* sc, bool leader) {
  asm volatile("{\n.reg .pred p;\nsetp.ne.u32 p, %1, 0;\n@p red.relaxed.gpu.global.add.u32 [%0], %2;\n}"
               :: "l"(sc->step[blockIdx.x]), "r"((uint32_t)leader), "n"(N) : "memory");
}
__device__ __forceinline__ uint32_t launch_index(const Scratch* sc) { return *(const volatile uint32_t*)sc->step[blockIdx.x] >> 4; }
__device__ __forceinline__ void stat_fetch(const Scratch* sc, uint32_t (&st)[4]) {
  const uint32_t th = here(threadIdx.x);
  ld_vec(&sc->x[(blockIdx.x & ~3u) + (th & 3)][X_ST + (th >> 2)], st[0], st[1], st[2], st[3]);
}
struct Nothing { __device__ __forceinline__ void operator()() const {} };
template <int C, int SLOT, class F = Nothing>
__device__ __forceinline__ void gather_first(uint32_t (&A)[4][16], uint32_t (&st)[4], const Scratch* sc, uint4* xp, uint32_t tag, uint32_t sent, F meanwhile = F()) {
  if (TIMED) { while (clock_now() - sent < GD) {} } else bar_sync(BAR_GO, 160);
  fetch(peer<1>(xp) + SLOT, A[1]); fetch(peer<2>(xp) + SLOT, A[2]); fetch(peer<3>(xp) + SLOT, A[3]);
  if (SLOT == X_AG0) stat_fetch(sc, st);
  meanwhile();
  uint32_t spin = 0;
  while (__builtin_expect(stale(miss(A[1], tag) | miss(A[C], tag)), 0) && ++spin < SPIN_LIMIT) {
    fetch(peer<1>(xp) + SLOT, A[1]);
    if (C == 2) fetch(peer<2>(xp) + SLOT, A[2]);
  }
}
template <int C, int SLOT> __device__ __forceinline__ void gather_rest(uint32_t (&A)[4][16], uint4* xp, uint32_t tag) {
  SCHED();
  uint32_t spin = 0;
  while (__builtin_expect(stale(miss(A[C + 1], tag) | miss(A[3], tag)), 0) && ++spin < SPIN_LIMIT) {
    if (C == 1) fetch(peer<2>(xp) + SLOT, A[2]);
    fetch(peer<3>(xp) + SLOT, A[3]);
  }
}
__device__ __forceinline__ void pack_acc(const float (&d)[32], uint32_t (&a)[16]) {
#pragma unroll
  for (int i = 0; i < 16; i++) a[i] = pack2(d[2 * i], d[2 * i + 1]);
}
__device__ __forceinline__ void frag_store(uint32_t slot, const uint32_t (&a)[16]) {
#pragma unroll
  for (int s = 0; s < 4; s++) sts128(slot + s * 512, a[4 * s], a[4 * s + 1], a[4 * s + 2], a[4 * s + 3]);
}
__device__ __forceinline__ void tile_store(uint32_t maddr, const uint32_t (&a)[16]) {
#pragma unroll
  for (int s = 0; s < 4; s++) stsm4(maddr ^ (s << 5), &a[4 * s]);
}
__device__ __forceinline__ void tile_load(uint32_t maddr, uint32_t (&a)[16]) {
#pragma unroll
  for (int s = 0; s < 4; s++) ldsm4(maddr ^ (s << 5), &a[4 * s]);
}

__device__ __forceinline__ void res_load(uint32_t maddr, float (&d)[32]) {
  uint32_t a[16];
  tile_load(here(maddr) + 3 * TILE_BYTES, a);
#pragma unroll
  for (int i = 0; i < 16; i++) { d[2 * i] = bf_lo(a[i]); d[2 * i + 1] = bf_hi(a[i]); }
  pin(d);
}

struct RowAcc { float s[2][4], u[2][4], v[2][4]; };
__device__ __forceinline__ void row_sums(RowAcc& t, const uint32_t (&a)[16]) {
#pragma unroll
  for (int s = 0; s < 4; s++) hmma(t.s[s & 1], &a[4 * s], 0x3F803F80u, 0x3F803F80u);
}
__device__ __forceinline__ void row_gram(RowAcc& t, const uint32_t (&a)[16]) {
#pragma unroll
  for (int s = 0; s < 8; s++) {
    hmma8(t.u[s & 1], &a[2 * s], a[2 * s]);
    hmma8(t.v[s & 1], &a[2 * s], a[2 * s + 1]);
  }
}
__device__ __forceinline__ float2 row_squares(const RowAcc& t, bool odd) {
  return make_float2(odd ? t.u[0][1] + t.u[1][1] : t.u[0][0] + t.u[1][0], odd ? t.v[0][3] + t.v[1][3] : t.v[0][2] + t.v[1][2]);
}
__device__ __forceinline__ void stat_publish(const uint32_t (&a)[16], Scratch* sc, uint32_t th, uint32_t tag) {
  RowAcc t = {};
  row_sums(t, a);
  row_gram(t, a);
  const float2 q = row_squares(t, th & 4);
  if ((th & 3) == ((th >> 3) & 3))
    st_vec(&sc->x[blockIdx.x][X_ST + (th >> 2)], (__float_as_uint(t.s[0][0] + t.s[1][0]) & ~1u) | tag, __float_as_uint(q.x),
           __float_as_uint(t.s[0][2] + t.s[1][2]), __float_as_uint(q.y));
}
struct RowNorm { float m0, rs0, m1, rs1; };
__device__ __forceinline__ RowNorm row_norm(float s0, float q0, float s1, float q1, float scale) {
  RowNorm n;
  n.m0 = s0 * (1.f / DM); n.m1 = s1 * (1.f / DM);
  n.rs0 = scale * rsqrt_hw(fmaxf(fmaf(-n.m0, n.m0, q0 * (1.f / DM)), 0.f) + LN_EPS);
  n.rs1 = scale * rsqrt_hw(fmaxf(fmaf(-n.m1, n.m1, q1 * (1.f / DM)), 0.f) + LN_EPS);
  return n;
}
__device__ __forceinline__ RowNorm stat_finish(const Scratch* sc, uint32_t (&st)[4], uint32_t tag, float scale) {
  uint32_t spin = 0;
  while (__builtin_expect(stale(st[0] ^ tag), 0) && ++spin < SPIN_LIMIT) stat_fetch(sc, st);
  float f[4];
#pragma unroll
  for (int i = 0; i < 4; i++) {
    f[i] = __uint_as_float(st[i]);
    f[i] += __shfl_xor_sync(0xffffffffu, f[i], 1);
    f[i] += __shfl_xor_sync(0xffffffffu, f[i], 2);
  }
  return row_norm(f[0], f[1], f[2], f[3], scale);
}
__device__ __forceinline__ void mean_frag(uint32_t (&mu)[4], const RowNorm& n, bool sel) {
  const float a = sel ? -n.m0 : 0.f, c = sel ? -n.m1 : 0.f;
  mu[0] = pack2(a, a); mu[1] = pack2(c, c);
  const float al = a - bf_lo(mu[0]), cl = c - bf_lo(mu[1]);
  mu[2] = pack2(al, al); mu[3] = pack2(cl, cl);
  pin(mu);
}
__device__ __forceinline__ void centre(uint32_t (&a)[16], uint32_t m0, uint32_t m1) {
#pragma unroll
  for (int i = 0; i < 16; i++) asm("sub.rn.bf16x2 %0, %0, %1;" : "+r"(a[i]) : "r"((i & 1) ? m1 : m0));
  pin(a);
}
__device__ __forceinline__ void scale_pack(const float (&d)[32], uint32_t (&a)[16], float rs0, float rs1) {
#pragma unroll
  for (int i = 0; i < 16; i++) { const float rs = (i & 1) ? rs1 : rs0; a[i] = pack2(d[2 * i] * rs, d[2 * i + 1] * rs); }
}
template <int S> __device__ __forceinline__ void silu_seg(float (&acc)[4][32], float (&tn)[2][4], uint32_t (&H)[4][16], float rs0, float rs1) {
  if (S >= 2) {
    const float* h = &acc[(S - 2) >> 3][4 * ((S - 2) & 7)];
    const float* v = tn[S & 1];
    uint32_t* o = &H[(S - 2) >> 3][2 * ((S - 2) & 7)];
    o[0] = pack2(fmaf(h[0], v[0], h[0]), fmaf(h[1], v[1], h[1]));
    o[1] = pack2(fmaf(h[2], v[2], h[2]), fmaf(h[3], v[3], h[3]));
    asm volatile("" : "+r"(o[0]), "+r"(o[1]));
  }
  if (S >= 1 && S <= 32) {
#pragma unroll
    for (int k = 0; k < 4; k++) tn[(S - 1) & 1][k] = tanh_hw(acc[((S - 1) >> 3) & 3][4 * ((S - 1) & 7) + k]);
  }
  if (S < 32) {
    float* h = &acc[(S >> 3) & 3][4 * (S & 7)];
    h[0] *= rs0; h[1] *= rs0; h[2] *= rs1; h[3] *= rs1;
    asm volatile("" : "+f"(h[0]), "+f"(h[1]), "+f"(h[2]), "+f"(h[3]));
  }
  SCHED();
}
template <int S0, int S1> __device__ __forceinline__ void silu_segs(float (&acc)[4][32], float (&tn)[2][4], uint32_t (&H)[4][16], float rs0, float rs1) {
  silu_seg<S0>(acc, tn, H, rs0, rs1);
  if constexpr (S0 + 1 < S1) silu_segs<S0 + 1, S1>(acc, tn, H, rs0, rs1);
}
template <int HALF> __device__ __forceinline__ void send_half(uint4* dst, const float (&d)[32], uint32_t tag) {
  uint32_t o[8];
#pragma unroll
  for (int i = 0; i < 8; i++) o[i] = pack2(d[16 * HALF + 2 * i], d[16 * HALF + 2 * i + 1]);
  o[0] = (o[0] & ~1u) | tag; o[4] = (o[4] & ~1u) | tag;
  pin(o);
  SCHED();
  st_vec(dst + HALF * 256, o[0], o[1], o[2], o[3]);
  st_vec(dst + HALF * 256 + 128, o[4], o[5], o[6], o[7]);
  SCHED();
}
__device__ __forceinline__ void send_residual(uint32_t (&a)[16], Scratch* sc, uint4* xp, uint32_t maddr, uint32_t tag, uint32_t& sent) {
  const uint32_t exact[4] = {a[0], a[4], a[8], a[12]};
  publish(xp + X_AG0, a, tag);
  if (TIMED) sent = clock_now();
  const uint32_t th = here(threadIdx.x);
  stat_publish(a, sc, th, tag);
  tile_store(here(maddr) + 3 * TILE_BYTES, a);
  stsm4(SM_BASE + SM_STG + 3 * TILE_BYTES + (th >> 5) * 2048 + (th & 7) * 128 + ((((th >> 2) & 6) ^ (th & 7)) << 4), exact);
}
template <int F, int N> __device__ __forceinline__ void proj_residual(uint32_t (&A)[4][16], Scratch* sc, uint4* xp, uint32_t maddr,
                                                                      uint32_t tag, uint32_t& sent) {
  float acc[32];
  if (TIMED && F == F_PW2) sent = clock_now();
  uint32_t st[4];
  acquire_n<F, N>();
  if (F == F_PW2) acquire_n<0, 5>();
  res_load(maddr, acc);
  mma_tile<false>(acc, A[0], LO(F));
  gather_first<2, X_AG1>(A, st, sc, xp, tag, sent);
  announce(sc, threadIdx.x == 0);
  mma_tile<false>(acc, A[1], HI(F));
  mma_tile<false>(acc, A[2], LO(F + 1));
  gather_rest<2, X_AG1>(A, xp, tag);
  PROF_MARK0(F == F_WO ? 11 : 16);
  mma_tile<false>(acc, A[3], HI(F + 1));
  WG_WAIT(0); pin(acc);
  pack_acc(acc, A[0]);
  send_residual(A[0], sc, xp, maddr, tag, sent);
}

__device__ __forceinline__ uint64_t ring_desc(uint32_t lo) { return (RING & ~uint64_t(0xFFFFFFFFu)) | lo; }
__device__ __forceinline__ void qk_tile(float (&S)[32], const uint32_t (&Q)[16], uint32_t dk) {
  wgmma64_reuse<0>(S, &Q[0], ring_desc(dk), blockIdx.y);
#pragma unroll
  for (int s = 1; s < 4; s++) wgmma64_acc<0>(S, &Q[4 * s], ring_desc(dk + s * 2));
}
__device__ __forceinline__ void qk_shift(float (&S)[32], const uint32_t (&nm)[4]) { wgmma64_acc<0>(S, nm, (uint64_t)((SM_BASE + SM_ONE) >> 4)); }
constexpr uint32_t RING_K = (uint32_t)RING, V_STEP = 1u - (1u << 16);
constexpr uint32_t RING_V = (SM_BASE >> 4) | (((SM_STG + 2 * TILE_BYTES) >> 4) << 16);
__device__ __forceinline__ void pv_tile(float (&O)[36], const uint32_t (&P)[16], uint32_t dv, uint32_t pad) {
#pragma unroll
  for (int s = 0; s < 4; s++) wgmma72_acc(O, &P[4 * s], ring_desc(dv + s * 128 * V_STEP + (s < 2 ? 0 : (s - 1) * pad)));
}
template <class F = Nothing>
__device__ __forceinline__ void attn_step(const float (&Sc)[32], float (&Sn)[32], uint32_t (&Pc)[16], uint32_t (&Pp)[16], float (&O)[36],
                                          const uint32_t (&Q)[16], const uint32_t (&nm)[4], uint32_t dk, uint32_t dv, bool next, bool prev, F late = F()) {
  if (next) {
    WG_FENCE();
    qk_tile(Sn, Q, dk);
    qk_shift(Sn, nm);
  }
  if (prev) {
    WG_FENCE();
    pv_tile(O, Pp, dv, 0);
  }
  WG_COMMIT();
  SCHED();
#pragma unroll
  for (int i = 0; i < 16; i++) {
    if (i == 12) late();
    Pc[i] = pack2(ex2_hw(Sc[2 * i]), ex2_hw(Sc[2 * i + 1]));
    asm volatile("" : "+r"(Pc[i]));
  }
  SCHED();
}
__device__ __forceinline__ void load_taps(uint32_t (&tap)[15], const __nv_bfloat16* dw, int dir) {
  const uint32_t* src = (const uint32_t*)(dw + 64 * (blockIdx.x & 3)) + (here(threadIdx.x) & 31) + 7 * (DM / 2);
#pragma unroll
  for (int k = 0; k < 15; k++) tap[k] = __ldg(src + dir * (k - 7) * (DM / 2));
}
__device__ __forceinline__ void halve_taps(uint32_t (&tap)[15]) {
#pragma unroll
  for (int k = 0; k < 15; k++) asm("mul.rn.bf16x2 %0, %0, %1;" : "+r"(tap[k]) : "r"(0x3F003F00u));
  pin(tap);
}
__device__ __forceinline__ void attention_exact(float (&O)[36], const uint32_t (&Q)[16], const Scratch* sc, int bh, int lane, int half) {
  const char* kb = (const char*)&sc->kv[bh][0][0][0];
  const char* vb = (const char*)&sc->kv[bh][1][0][0];
  const int g = lane >> 2, q = lane & 3;
  float m0 = -INFINITY, m1 = -INFINITY, l0 = 0.f, l1 = 0.f;
  float o[4][4] = {};
#pragma unroll 1
  for (int k0 = 0; k0 < T_SEQ; k0 += 8) {
    float s[4] = {0.f, 0.f, 0.f, 0.f};
#pragma unroll
    for (int c = 0; c < 8; c++) hmma8(s, &Q[2 * c], __ldcg((const uint32_t*)(kb + (k0 + g) * 128 + ((c ^ g) << 4) + q * 4)));
    float n0 = fmaxf(s[0], s[1]), n1 = fmaxf(s[2], s[3]);
    n0 = fmaxf(n0, __shfl_xor_sync(0xffffffffu, n0, 1)); n1 = fmaxf(n1, __shfl_xor_sync(0xffffffffu, n1, 1));
    n0 = fmaxf(m0, fmaxf(n0, __shfl_xor_sync(0xffffffffu, n0, 2))); n1 = fmaxf(m1, fmaxf(n1, __shfl_xor_sync(0xffffffffu, n1, 2)));
    const float a0 = ex2_hw(m0 - n0), a1 = ex2_hw(m1 - n1);
    m0 = n0; m1 = n1;
    const uint32_t pp[2] = {pack2(ex2_hw(s[0] - n0), ex2_hw(s[1] - n0)), pack2(ex2_hw(s[2] - n1), ex2_hw(s[3] - n1))};
    l0 = fmaf(l0, a0, bf_lo(pp[0]) + bf_hi(pp[0])); l1 = fmaf(l1, a1, bf_lo(pp[1]) + bf_hi(pp[1]));
#pragma unroll
    for (int j = 0; j < 4; j++) {
      const int c = 4 * half + j;
      const uint32_t v0 = __ldcg((const uint16_t*)(vb + (k0 + 2 * q) * 128 + ((c ^ (2 * q)) << 4) + g * 2));
      const uint32_t v1 = __ldcg((const uint16_t*)(vb + (k0 + 2 * q + 1) * 128 + ((c ^ (2 * q + 1)) << 4) + g * 2));
      o[j][0] *= a0; o[j][1] *= a0; o[j][2] *= a1; o[j][3] *= a1;
      hmma8(o[j], pp, v0 | (v1 << 16));
    }
  }
  l0 += __shfl_xor_sync(0xffffffffu, l0, 1); l1 += __shfl_xor_sync(0xffffffffu, l1, 1);
  O[32] = l0 + __shfl_xor_sync(0xffffffffu, l0, 2); O[34] = l1 + __shfl_xor_sync(0xffffffffu, l1, 2);
#pragma unroll
  for (int i = 0; i < 16; i++) O[i] = o[i >> 2][i & 3];
}

__device__ __forceinline__ uint32_t fill_entry(int f, int r) {
  int m, x = r, y, dx = 0;
  if (f < F_QKV || f >= 48) {
    const int i = f & 15;
    m = f < F_QKV ? M_FF1A : M_FF2A;
    if (i < 8) { x = 4 * r + ((0xE2u >> i) & 1) * 2; y = r ^ ((0xE790u >> (2 * i)) & 3); dx = 1; }
    else { m++; x = r ^ (((i >> 1) - 3) & 3); y = 4 * r + 2 * (i & 1); }
  } else if (f < F_KV) {
    const int i = f - F_QKV;
    m = M_QKV;
    if (i == 1 || i >= 5) { y = r ^ (i == 1 ? 0 : 2); }
    else { x = 4 + r; y = r ^ (i ? i - 1 : 0); dx = 4; }
  } else if (f >= F_PW1 && f < F_PW2) {
    m = M_PW1; y = r ^ (f - F_PW1); dx = 4;
  } else {
    m = f < F_PW1 ? M_WO : M_PW2; y = r ^ ((f & 1) * 2);
  }
  return m | (x << 4) | (y << 8) | (dx << 16);
}
__device__ __forceinline__ void tma_fill(uint32_t st, const CUtensorMap* map, uint32_t x, uint32_t y, uint32_t x2, uint32_t y2) {
  asm volatile("{\n.reg .pred p;\nelect.sync _|p, 0xffffffff;\n"
               "@p mbarrier.arrive.expect_tx.shared::cta.b64 _, [%1], 16384;\n"
               "@p cp.async.bulk.tensor.2d.shared::cluster.global.mbarrier::complete_tx::bytes [%0], [%2, {%3, %4}], [%1];\n"
               "@p cp.async.bulk.tensor.2d.shared::cluster.global.mbarrier::complete_tx::bytes [%0 + 8192], [%2, {%5, %6}], [%1];\n}"
               :: "r"(SM_BASE + st * STAGE_BYTES), "r"(SM_BASE + SM_FULL + st * 8), "l"(map), "r"(x), "r"(y), "r"(x2), "r"(y2) : "memory");
}
template <int F0, int N> __device__ __forceinline__ void weight_fills(const Params& p, uint32_t entry) {
  uint32_t st = F0 % NSTAGE, parity = ((F0 / NSTAGE) & 1) ^ 1, e = __shfl_sync(0xffffffffu, entry, 0);
#pragma unroll 1
  for (int i = 1; i <= N; i++) {
    const uint32_t x = (e << 2) & 0x3C0, y = (e >> 2) & 0x3FC0, dx = (e >> 16) << 6;
    const CUtensorMap* map = &p.map[e & 15];
    e = __shfl_sync(0xffffffffu, entry, i);
    mbar_wait(SM_BASE + SM_EMPTY + st * 8, parity);
    tma_fill(st, map, x, y, x + dx, dx ? y : y ^ 64);
    if (++st == NSTAGE) { st = 0; parity ^= 1; }
  }
}
template <int KIND, int J> __device__ __forceinline__ uint32_t kv_fill(const uint4* kv, uint32_t want) {
  constexpr uint32_t st = (J < 6 ? 4 * (J >> 1) : 0) + (J & 1) + 2 * KIND;
  mbar_wait(SM_BASE + SM_EMPTY + st * 8, J < 6);
  uint32_t have, spin = 0;
#pragma unroll 1
  do {
    asm volatile("ld.volatile.shared.u32 %0, [%1];" : "=r"(have) : "r"(SM_BASE + SM_KVRDY + KIND * 4) : "memory");
    have &= want;
  } while (!have && ++spin < (SPIN_LIMIT << 4));
  const uint32_t tile = (__ffs(KIND ? want : have) - 1) & 15;
  asm volatile("{\n.reg .pred p;\nelect.sync _|p, 0xffffffff;\n"
               "@p mbarrier.arrive.expect_tx.shared::cta.b64 _, [%1], 16384;\n"
               "@p cp.async.bulk.shared::cluster.global.mbarrier::complete_tx::bytes [%0], [%2], 16384, [%1];\n}"
               :: "r"(SM_BASE + st * STAGE_BYTES), "r"(SM_BASE + SM_FULL + st * 8), "l"(kv + (KIND * 16 + tile) * 512) : "memory");
  PROF_AT(256 + 512 + (10 + KIND * 8 + J) * 4);
  return 1u << tile;
}
template <int J> __device__ __forceinline__ void kv_fills(const uint4* kv, uint32_t todo, uint32_t b1, uint32_t b2) {
  if constexpr (J >= 2) kv_fill<1, J - 2>(kv, b2);
  uint32_t b0 = 0;
  if constexpr (J < 8) b0 = kv_fill<0, J>(kv, J == 7 ? 0x4000u : todo);
  if constexpr (J < 9) kv_fills<J + 1>(kv, todo & ~b0, b0, b1);
}
__device__ __forceinline__ void reset_mailboxes(Scratch* sc, int half, int lane, uint32_t t_start) {
  while (clock_now() - t_start < TC) {}
#pragma unroll 1
  for (int i = half * 8; i < half * 9 + 8; i++) {
    const uint32_t t0 = clock_now();
    uint4* dst = &sc->x[blockIdx.x ^ (i < 12 ? (i >> 2) + 1 : 0)][i * 128 + lane];
#pragma unroll
    for (int k = 0; k < 4; k++) st_vec(dst + 32 * k, 0u, 0u, 0u, 0u);
    while (clock_now() - t0 < CLR_PACE) {}
  }
  bar_arrive(BAR_RST, 192);
  PROF_AT(256 + 512 + 28 * 4);
  asm volatile("fence.acq_rel.gpu;" ::: "memory");
  __syncwarp();
  announce<1>(sc, lane == 0);
  PROF_AT(256 + 512 + 2 * 4);
}
__device__ __forceinline__ void l2_prefetch(const void* p, uint32_t total, int b) {
  const uint32_t part = total / NCTA;
  asm volatile("cp.async.bulk.prefetch.L2.global [%0], %1;" :: "l"((const char*)p + (size_t)b * part), "r"(part) : "memory");
}

__global__ void __launch_bounds__(384, 1) conformer_kernel(Scratch* __restrict__ sc, __nv_bfloat16* __restrict__ out,
                                                           const __nv_bfloat16* __restrict__ dw, const __nv_bfloat16* __restrict__ xin,
                                                           const __nv_bfloat16* __restrict__ w_ff1a, const __grid_constant__ Params p) {
  extern __shared__ __align__(1024) uint8_t smem[];
  const int tid = threadIdx.x, lane = tid & 31;
  const uint32_t t_start = clock_now();
  const int b = blockIdx.x, r = b & 3, batch = b >> 6, t = (b >> 2) & 15;
  if ((uint32_t)__cvta_generic_to_shared(smem) != SM_BASE) return;
  PROF_AT(256 + (tid >> 7) * 256);
  PROF_TIME(30);
  const uint32_t crow = ((tid >> 1) & 48) + (lane >> 3);
  const uint32_t cdst = SM_BASE + crow * 128 + (((lane & 7) ^ (lane >> 3)) << 4);
  if (tid < 128) {
    const uint32_t g0 = batch * T_SEQ + t * 64 + crow, o = r * 128 + (lane & 7) * 16;
    const uint32_t lo = min(g0, 2 * T_SEQ - 5) * 512 + o, hi = min(g0 + 8, 2 * T_SEQ - 5) * 512 + o;
#pragma unroll
    for (int c = 0; c < 4; c++) {
#pragma unroll
      for (int i = 0; i < 4; i++)
        cp_async16((cdst ^ ((i & 1) << 6)) + SM_STG + (3 - c) * TILE_BYTES + i * 512, (const char*)xin + (((i & 2) ? hi : lo) ^ (c << 7)) + (i & 1) * 2048);
      asm volatile("cp.async.commit_group;" ::: "memory");
    }
  } else if (tid < 256) {
    const char* src = (const char*)w_ff1a + (64 * r + crow) * 2048 + r * 512 + (lane & 7) * 16;
#pragma unroll
    for (int c = 0; c < 4; c++) {
#pragma unroll
      for (int i = 0; i < 4; i++) cp_async16((cdst ^ ((i & 1) << 6)) + c * TILE_BYTES + i * 512, src + i * 8192 + c * 128);
      asm volatile("cp.async.commit_group;" ::: "memory");
    }
  }
  const int cw = __shfl_sync(0xffffffffu, tid >> 5, 0), wg = cw >> 2, w = cw & 3;

  if (wg == 2) {
    asm volatile("setmaxnreg.dec.sync.aligned.u32 40;");
    if (cw == 8) {
      if (lane == 0) {
        asm volatile("prefetch.tensormap [%0];" :: "l"(&p.map[M_FF1A]) : "memory");
#pragma unroll
        for (int i = 0; i < NSTAGE; i++) mbar_init(SM_BASE + SM_FULL + i * 8, 1);
        fence_async_smem();
      }
      __syncwarp();
      bar_arrive(0, 320);
      while (clock_now() - t_start < TF) {}
      PROF_MARK(9);
#pragma unroll
      for (int f = 2; f < 8; f++) {
        const uint32_t x = 256 * r + ((0xE2u >> f) & 1) * 128, y = (r ^ ((0xE790u >> (2 * f)) & 3)) * 64;
        tma_fill(f, &p.map[M_FF1A], x, y, x + 64, y);
      }
      PROF_MARK(1);
      uint32_t entry[2];
#pragma unroll 1
      for (int i = 0; i < 2; i++) { entry[1] = fill_entry(8 + i * 32 + lane, r); if (i == 0) entry[0] = entry[1]; }
      bar_sync(BAR_INIT, 64);
      weight_fills<8, F_KV - 8>(p, entry[0]);
      kv_fills<0>(sc->kv[batch * 4 + r][0][0], 0x1555u, 0u, 0u);
      weight_fills<F_WO, F_TOTAL - F_WO>(p, entry[1]);
    } else if (here(cw) != 11) {
      const int kind = w - 1;
      const uint32_t prev = launch_index(sc);
      if (kind == 0) {
        if (lane == 0) {
#pragma unroll
            for (int i = 0; i < NSTAGE; i++) mbar_init(SM_BASE + SM_EMPTY + i * 8, 4);
          sts64(SM_BASE + SM_KVRDY, 0u, 0u);
        }
        __syncwarp();
        bar_arrive(0, 320);
        bar_arrive(BAR_INIT, 64);
        if (lane == 0) {
          const uint32_t t0 = t_start;
          while (clock_now() - t0 < PF0) {}
          while (clock_now() - t0 < PF1) {}
          asm volatile("prefetch.tensormap [%0];" :: "l"(&p.map[M_FF1B]) : "memory");
          l2_prefetch(p.w_ff1b, 1024 * 256 * 2, b);
          while (clock_now() - t0 < PF2) {}
          l2_prefetch(p.w_qkv, 256 * 768 * 2, b);
          l2_prefetch(p.w_pw1, 256 * 512 * 2, b);
          l2_prefetch(p.w_ff2a, 256 * 1024 * 2, b);
          while (clock_now() - t0 < PF3) {}
          if (b < 15) l2_prefetch(dw, 512 * NCTA, b);
          l2_prefetch(p.w_o, 256 * 256 * 2, b);
          l2_prefetch(p.w_pw2, 256 * 256 * 2, b);
          l2_prefetch(p.w_ff2b, 1024 * 256 * 2, b);
#pragma unroll
          for (int i = M_QKV; i < M_COUNT; i++) asm volatile("prefetch.tensormap [%0];" :: "l"(&p.map[i]) : "memory");
        }
        __syncwarp();
      } else {
        reset_mailboxes(sc, 1, lane, t_start);
      }
      const uint32_t* flag = sc->flag[batch * 4 + r][kind * 16 + (lane & 15)];
      uint32_t spin = 0, ready;
#pragma unroll 1
      do {
        uint32_t v;
        asm volatile("ld.relaxed.gpu.global.u32 %0, [%1];" : "=r"(v) : "l"(flag) : "memory");
        ready = __ballot_sync(0xffffffffu, v - 1 == prev);
        asm volatile("st.volatile.shared.u32 [%0], %1;" :: "r"(SM_BASE + SM_KVRDY + kind * 4), "r"(ready & (ready >> 1)) : "memory");
        if (spin == 0) {
          if (kind == 0) bar_sync(BAR_K, 160); else bar_sync(BAR_V, 160);
          if (lane == 0) {
            PROF_MARK(4 + kind * 2);
            asm volatile("cp.async.bulk.global.shared::cta.bulk_group [%0], [%1], %2;"
                         :: "l"(sc->kv[batch * 4 + r][kind][t]), "r"(SM_BASE + SM_STG + kind * TILE_BYTES), "r"(TILE_BYTES) : "memory");
            asm volatile("cp.async.bulk.commit_group;\ncp.async.bulk.wait_group 0;" ::: "memory");
            asm volatile("st.relaxed.gpu.global.u32 [%0], %1;" :: "l"(sc->flag[batch * 4 + r][kind * 16 + t]), "r"(prev + 1) : "memory");
            PROF_MARK(5 + kind * 2);
          }
          __syncwarp();
        }
      } while (ready != 0xffffffffu && ++spin < SPIN_LIMIT);
    } else {
      const uint32_t* watch = sc->step[(b & ~3) + (lane & 3)];
      uint32_t seen;
      asm volatile("ld.relaxed.gpu.global.u32 %0, [%1];" : "=r"(seen) : "l"(watch) : "memory");
      reset_mailboxes(sc, 0, lane, t_start);
      uint32_t want = seen & ~15u;
#pragma unroll 1
      for (int k = 0; k < (TIMED ? 1 : 8); k++) {
        want += 2;
        uint32_t spin = 0;
#pragma unroll 1
        while (__any_sync(0xffffffffu, (int)(seen - want) < 0) && ++spin < SPIN_LIMIT)
          asm volatile("ld.relaxed.gpu.global.u32 %0, [%1];" : "=r"(seen) : "l"(watch) : "memory");
        bar_arrive(BAR_GO, 160);
        PROF_MARK(32 + k);
      }
    }
  } else {
    asm volatile("setmaxnreg.inc.sync.aligned.u32 232;");
    const int q = lane & 3, th = tid & 127;
    constexpr uint32_t stg = SM_BASE + SM_STG;
    const uint32_t mrow = 16 * w + (lane & 15);
    const uint32_t maddr = stg + mrow * 128 + (((lane >> 4) ^ (lane & 7)) << 4);
    const uint32_t qslot = stg + 2 * TILE_BYTES + w * 2048 + lane * 16;
    uint4* const xp = &sc->x[b][th];
    const int nvalid = T_SEQ - t * 64, row0 = 16 * w + (lane >> 2);

    uint32_t A[4][16];
    uint32_t st[4], sent = 0;
    bar_sync(0, 320);
    if (wg == 0) {
      RowAcc ra = {};
      cp_async_wait(0);
      __syncwarp();
      PROF_MARK0(45);
#pragma unroll
      for (int c = 0; c < 4; c++) tile_load(maddr + (3 - c) * TILE_BYTES, A[c]);
      row_sums(ra, A[0]); row_gram(ra, A[0]); row_sums(ra, A[1]); row_gram(ra, A[1]);
      pin(ra.s[0]); pin(ra.s[1]); pin(ra.u[0]); pin(ra.u[1]); pin(ra.v[0]); pin(ra.v[1]);
      SCHED();
      row_sums(ra, A[2]); row_sums(ra, A[3]); row_gram(ra, A[2]); row_gram(ra, A[3]);
      const float m0 = (ra.s[0][0] + ra.s[1][0]) * (1.f / DM), m1 = (ra.s[0][2] + ra.s[1][2]) * (1.f / DM);
      st[0] = pack2(m0, m0); st[1] = pack2(m1, m1);
      centre(A[0], st[0], st[1]);
      const float2 sq = row_squares(ra, lane & 4);
      st[2] = __float_as_uint(fmaf(-m0, m0, sq.x * (1.f / DM))); st[3] = __float_as_uint(fmaf(-m1, m1, sq.y * (1.f / DM)));
    } else {
      if (th < 112) sts128(SM_BASE + SM_CS + th * 16, 0, 0, 0, 0);
      sts32(SM_BASE + SM_EYE + th * 4, th >= 96 ? 0x3F803F80u : ((th & 32) == 0 && (th & 3) == ((th >> 3) & 3)) ? (0x3F00u << ((th & 4) * 4)) : 0u);
#pragma unroll
      for (int i = 0; i < 2; i++) {
        cp_async_wait(2 - 2 * i);
        fence_async_smem();
        bar_sync(BAR_WG1, 128);
        if (th == 0) mbar_arrive(SM_BASE + SM_FULL + i * 8);
      }
      PROF_MARK(6);
      const uint32_t tag = ~launch_index(sc) & 1;
      mbar_wait(SM_BASE + SM_FULL + 4 * 8, 0);
      PROF_MARK(5);
      if (b < 72) {
        const __nv_bfloat16* wp; int ld, col;
        if (b < 24) { wp = p.w_qkv; ld = 768; col = b * 32; }
        else if (b < 40) { wp = p.w_pw1; ld = 512; col = (b - 24) * 32; }
        else { wp = p.w_ff2a; ld = 1024; col = (b - 40) * 32; }
        const uint4* src = (const uint4*)(wp + (size_t)(th >> 2) * ld + col + q * 8);
        float c[8] = {0.f, 0.f, 0.f, 0.f, 0.f, 0.f, 0.f, 0.f};
#pragma unroll 1
        for (int h = 0; h < 2; h++, src += 16 * ld) {
#pragma unroll
          for (int i = 0; i < 4; i++) {
            const uint4 v = __ldg(src + i * 4 * ld);
            c[0] += bf_lo(v.x); c[1] += bf_hi(v.x); c[2] += bf_lo(v.y); c[3] += bf_hi(v.y);
            c[4] += bf_lo(v.z); c[5] += bf_hi(v.z); c[6] += bf_lo(v.w); c[7] += bf_hi(v.w);
          }
        }
#pragma unroll 1
        for (int m = 4; m <= 16; m <<= 1)
#pragma unroll
          for (int k = 0; k < 8; k++) c[k] += __shfl_xor_sync(0xffffffffu, c[k], m);
        if (lane < 4) {
          const uint32_t a = SM_BASE + SM_CS + 1792 + w * 128 + lane * 32;
          sts128(a, __float_as_uint(c[0]), __float_as_uint(c[1]), __float_as_uint(c[2]), __float_as_uint(c[3]));
          sts128(a + 16, __float_as_uint(c[4]), __float_as_uint(c[5]), __float_as_uint(c[6]), __float_as_uint(c[7]));
        }
        bar_sync(BAR_WG1, 128);
        if (th < 8) {
          float o[4] = {0.f, 0.f, 0.f, 0.f};
#pragma unroll 1
          for (int k = 0; k < 4; k++) {
            uint32_t e[4];
            lds128(SM_BASE + SM_CS + 1792 + k * 128 + th * 16, e[0], e[1], e[2], e[3]);
#pragma unroll
            for (int i = 0; i < 4; i++) o[i] += __uint_as_float(e[i]);
          }
          st_vec(&sc->cs[b * 8 + th], (__float_as_uint(o[0]) & ~1u) | tag, __float_as_uint(o[1]), __float_as_uint(o[2]), __float_as_uint(o[3]));
        }
      }
      bar_sync(BAR_WG1, 128);
      PROF_MARK(2);
      if (th < 72) {
        const int j = th >> 3, i = (th & 7) * 2;
        int src;
        if (j < CS_PW1) src = 320 + 64 * r + 16 * j;
        else if (j < CS_QKV) src = 192 + (j - CS_PW1) * 64 + 16 * r;
        else src = ((j - CS_QKV + 1) % 3) * 64 + 16 * r;
        uint32_t e[8], hi[4], lo[4], spin = 0;
#pragma unroll 1
        do {
          ld_vec(&sc->cs[src + i], e[0], e[1], e[2], e[3]);
          ld_vec(&sc->cs[src + i + 1], e[4], e[5], e[6], e[7]);
        } while ((((e[0] ^ tag) | (e[4] ^ tag)) & 1u) && ++spin < SPIN_LIMIT);
        e[0] &= ~1u; e[4] &= ~1u;
#pragma unroll
        for (int k = 0; k < 4; k++) {
          const float c0 = __uint_as_float(e[2 * k]), c1 = __uint_as_float(e[2 * k + 1]);
          hi[k] = pack2(c0, c1);
          lo[k] = pack2(c0 - bf_lo(hi[k]), c1 - bf_hi(hi[k]));
        }
        const uint32_t a = SM_BASE + SM_CS + j * 256 + i * 8;
        sts128(a ^ ((a >> 3) & 0x70), hi[0], hi[1], hi[2], hi[3]);
        sts128((a + 128) ^ (((a + 128) >> 3) & 0x70), lo[0], lo[1], lo[2], lo[3]);
      }
      fence_async_smem();
      PROF_MARK(4);
      bar_arrive(BAR_CS, 256);
    }

#pragma unroll 1
    for (uint32_t pass = 0; pass < 2; pass++) {
      uint32_t Q[16], shift;
      if (wg == 0) {
        float acc[4][32];
        uint32_t H[4][16];
        if (!pass) { PROF_MARK(47); ACQUIRE(0); }
        mma_tile<true>(acc[0], A[0], LO(0)); mma_tile<true>(acc[1], A[0], HI(0));
        if (pass) {
          gather_first<1, X_AG0>(A, st, sc, xp, 1, sent, [&] { mma_tile<true>(acc[2], A[0], LO(1)); mma_tile<true>(acc[3], A[0], HI(1)); });
        } else {
          ACQUIRE(1);
          mma_tile<true>(acc[2], A[0], LO(1)); mma_tile<true>(acc[3], A[0], HI(1));
          centre(A[1], st[0], st[1]);
          acquire_n<2, 3>();
        }
        mma_tile<false>(acc[0], A[1], LO(2)); mma_tile<false>(acc[1], A[1], HI(2));
        if (pass) {
          gather_rest<1, X_AG0>(A, xp, 1);
          RELEASE(F_WO - 2 + NREL, F_PW2 + 1);
        } else {
          centre(A[2], st[0], st[1]); centre(A[3], st[0], st[1]);
        }
        PROF_MARK2(2, 18);
        mma_tile<false>(acc[0], A[2], LO(3)); mma_tile<false>(acc[0], A[3], LO(4));
        WG_WAIT(4);
        RELEASE(0, 1);
        uint32_t mu[4] = {0u, 0u, 0u, 0u};
        float rs0, rs1, tn[2][4];
        if (pass) {
          const RowNorm n = stat_finish(sc, st, 1, 0.5f);
          rs0 = n.rs0; rs1 = n.rs1;
          mean_frag(mu, n, q == 0);
        } else {
          const int src = (lane & 28) | (lane >> 3);
          rs0 = 0.5f * rsqrt_hw(fmaxf(__uint_as_float(__shfl_sync(0xffffffffu, st[2], src)), 0.f) + LN_EPS);
          rs1 = 0.5f * rsqrt_hw(fmaxf(__uint_as_float(__shfl_sync(0xffffffffu, st[3], src)), 0.f) + LN_EPS);
        }
        pin(mu);
        mma_fold<2 * CS_FF2>(acc[0], mu);
        mma_tile<false>(acc[1], A[2], HI(3));
#define SEGS(a, b) silu_segs<a, b>(acc, tn, H, rs0, rs1)
        WG_WAIT(1); pin(acc[0]);
        SEGS(0, 1);
        mma_tile_fold<2 * CS_FF2 + 2>(acc[1], A[3], HI(4), mu);
        SEGS(1, 3);
        uint32_t ok = probe_n<5, 1>();
        SEGS(3, 4);
        settle_n<5, 1>(ok);
        mma_tile<false>(acc[2], A[1], LO(5));
        SEGS(4, 5);
        ok = probe_n<6, 1>();
        SEGS(5, 6);
        settle_n<6, 1>(ok);
        mma_tile<false>(acc[2], A[2], LO(6));
        SEGS(6, 8);
        WG_WAIT(2); pin(acc[1]);
        RELEASE(2, 4);
        ok = probe_n<7, 1>();
        SEGS(8, 9);
        settle_n<7, 1>(ok);
        mma_tile_fold<2 * CS_FF2 + 4>(acc[2], A[3], LO(7), mu);
        SEGS(9, 12);
        mma_tile<false>(acc[3], A[1], HI(5));
        SEGS(12, 14);
        mma_tile<false>(acc[3], A[2], HI(6));
        SEGS(14, 16);
        WG_WAIT(2); pin(acc[2]);
        SEGS(16, 17);
        mma_tile_fold<2 * CS_FF2 + 6>(acc[3], A[3], HI(7), mu);
        SEGS(17, 19);
        ok = probe_n<8, 2>();
        SEGS(19, 20);
        settle_n<8, 2>(ok);
        mma_tile_reuse(acc[1], H[0], LO(8));
        SEGS(20, 22);
        mma_tile<false>(acc[1], H[1], HI(8));
        SEGS(22, 24);
        WG_WAIT(2); pin(acc[3]);
        RELEASE(5, 7);
        SEGS(24, 26);
        mma_tile<false>(acc[1], H[2], LO(9));
        SEGS(26, 27);
        ok = probe_n<10, 2>();
        SEGS(27, 28);
        settle_n<10, 2>(ok);
        mma_tile_reuse(acc[2], H[0], LO(10));
        SEGS(28, 31);
        mma_tile<false>(acc[2], H[1], HI(10));
        SEGS(31, 34);
#undef SEGS
        PROF_MARK2(3, 19);
        const uint32_t rtag = here(pass ^ 1);
        const uint4* rs_in = xp + X_RS;
        mma_tile<false>(acc[1], H[3], HI(9));
        mma_tile<false>(acc[2], H[2], LO(11));
        ok = probe_n<12, 2>();
        uint4* rs_out = peer<1>(xp) + X_RS;
        mma_tile<false>(acc[2], H[3], HI(11));
        settle_n<12, 2>(ok);
        if (!pass) bar_sync(BAR_RST, 192);
        WG_WAIT(2); pin(acc[1]);
        RELEASE(8, 9);
        send_half<0>(rs_out, acc[1], rtag);
        mma_tile_reuse(acc[3], H[0], LO(12));
        SCHED();
        send_half<1>(rs_out, acc[1], rtag);
        mma_tile<false>(acc[3], H[1], HI(12));
        rs_out = peer<2>(xp) + X_RS + 512;
        WG_WAIT(2); pin(acc[2]);
        send_half<0>(rs_out, acc[2], rtag);
        mma_tile<false>(acc[3], H[2], LO(13));
        SCHED();
        ok = probe_n<14, 2>();
        send_half<1>(rs_out, acc[2], rtag);
        mma_tile<false>(acc[3], H[3], HI(13));
        settle_n<14, 2>(ok);
        mma_tile_reuse(acc[1], H[0], LO(14));
        rs_out = peer<3>(xp) + X_RS + 1024;
        if (!pass) bar_sync(BAR_GO, 160);
        announce(sc, tid == 0);
        fetch(rs_in, A[1]);
        SCHED();
        mma_tile<false>(acc[1], H[1], HI(14));
        WG_WAIT(2); pin(acc[3]);
        send_half<0>(rs_out, acc[3], rtag);
        send_half<1>(rs_out, acc[3], rtag);
        if (TIMED) sent = clock_now();
        mma_tile<false>(acc[1], H[2], LO(15)); mma_tile<false>(acc[1], H[3], HI(15));
        SCHED();
        fetch(rs_in + 512, A[2]);
        SCHED();
        res_load(maddr, acc[2]);
        if (TIMED) { while (clock_now() - sent < RD) {} } else bar_sync(BAR_GO, 160);
        fetch(rs_in + 1024, A[3]);
        if (!pass) acquire_n<F_QKV, 3>();
        {
          uint32_t spin = 0;
          while (__builtin_expect(stale(miss(A[1], rtag) | miss(A[2], rtag) | miss(A[3], rtag)), 0) && ++spin < SPIN_LIMIT) {
            if (stale(miss(A[1], rtag) | miss(A[2], rtag))) { fetch(rs_in, A[1]); fetch(rs_in + 512, A[2]); }
            fetch(rs_in + 1024, A[3]);
          }
        }
        announce(sc, tid == 0 && !pass);
        mma_add_half(acc[2], A[1]);
        mma_add_half(acc[2], A[2]);
        mma_add_half(acc[2], A[3]);
        PROF_MARK2(4, 20);
        WG_WAIT(0); pin(acc[2]); pin(acc[1]);
#pragma unroll
        for (int i = 0; i < 16; i++) A[0][i] = pack2(fmaf(acc[1][2 * i], 0.5f, acc[2][2 * i]), fmaf(acc[1][2 * i + 1], 0.5f, acc[2][2 * i + 1]));
        if (pass) {
          PROF_MARK(21);
          stat_publish(A[0], sc, here(th), 0);
          stat_fetch(sc, st);
          const RowNorm fn = stat_finish(sc, st, 0, 1.f);
          const float nm0 = -fn.m0 * fn.rs0, nm1 = -fn.m1 * fn.rs1;
#pragma unroll
          for (int i = 0; i < 16; i++) {
            const float rs = (i & 1) ? fn.rs1 : fn.rs0, nm = (i & 1) ? nm1 : nm0;
            A[0][i] = pack2(fmaf(bf_lo(A[0][i]), rs, nm), fmaf(bf_hi(A[0][i]), rs, nm));
          }
          tile_store(here(maddr), A[0]);
          __syncwarp();
          const int row = 16 * w + (lane >> 3);
          uint4* dst = (uint4*)(out + ((size_t)batch * T_SEQ + t * 64 + row) * DM + 64 * r) + (lane & 7);
          const uint32_t src = stg + row * 128 + (((lane & 7) ^ (lane >> 3)) << 4);
#pragma unroll
          for (int i = 0; i < 4; i++) {
            uint4 v;
            lds128((src ^ ((i & 1) << 6)) + i * 512, v.x, v.y, v.z, v.w);
            if (row + 4 * i < nvalid) dst[i * 4 * (DM / 8)] = v;
          }
          PROF_MARK(22);
          PROF_TIME(31);
          break;
        }
        send_residual(A[0], sc, xp, maddr, 1, sent);
        PROF_MARK(5);
        mma_tile<true>(acc[0], A[0], LO(F_QKV)); mma_tile<true>(acc[1], A[0], HI(F_QKV));
        gather_first<1, X_AG0>(A, st, sc, xp, 1, sent, [&] { mma_tile<true>(acc[2], A[0], LO(F_QKV + 1)); });
        mma_tile<false>(acc[0], A[1], LO(F_QKV + 2)); mma_tile<false>(acc[1], A[1], HI(F_QKV + 2));
        acquire_n<F_QKV + 3, 3>();
        bar_sync(BAR_CS, 256);
        gather_rest<1, X_AG0>(A, xp, 1);
        PROF_MARK(6);
        mma_tile<false>(acc[0], A[2], LO(F_QKV + 3)); mma_tile<false>(acc[0], A[3], LO(F_QKV + 4));
        SCHED();
        {
          const RowNorm n = stat_finish(sc, st, 1, 1.f);
          rs0 = row0 < nvalid ? n.rs0 : 0.f; rs1 = row0 + 8 < nvalid ? n.rs1 : 0.f;
          mean_frag(mu, n, q == 3);
        }
        mma_fold<2 * CS_QKV - 6>(acc[0], mu);
        RELEASE(10, 15);
        WG_WAIT(0); pin(acc[0]);
        scale_pack(acc[0], A[0], rs0, rs1);
        tile_store(here(maddr), A[0]);
        SCHED();
        mma_tile<false>(acc[1], A[2], HI(F_QKV + 3));
        fence_async_smem();
        bar_arrive(BAR_K, 160);
        mma_tile_fold<2 * CS_QKV - 4>(acc[1], A[3], HI(F_QKV + 4), mu);
        mma_tile<false>(acc[2], A[1], HI(F_QKV + 1)); mma_tile<false>(acc[2], A[2], LO(F_QKV + 5));
        WG_WAIT(2); pin(acc[1]);
        scale_pack(acc[1], Q, rs0, rs1);
        tile_store(here(maddr) + TILE_BYTES, Q);
        fence_async_smem();
        bar_arrive(BAR_V, 160);
        mma_tile_fold<2 * CS_QKV - 2>(acc[2], A[3], HI(F_QKV + 5), mu);
        WG_WAIT(0); pin(acc[2]);
        scale_pack(acc[2], Q, rs0 * SM_SCALE_LOG2, rs1 * SM_SCALE_LOG2);
        frag_store(here(qslot), Q);
        {
          uint32_t d[4] = {0u, 0u, 0u, 0u};
#pragma unroll
          for (int i = 0; i < 16; i++) asm("fma.rn.bf16x2 %0, %1, %2, %0;" : "+r"(d[i & 3]) : "r"(Q[i]), "r"(A[0][i]));
          float s0 = (bf_lo(d[0]) + bf_hi(d[0])) + (bf_lo(d[2]) + bf_hi(d[2])), s1 = (bf_lo(d[1]) + bf_hi(d[1])) + (bf_lo(d[3]) + bf_hi(d[3]));
          shift = pack2(-s0, -s1);
          sts32(SM_BASE + SM_CS + 2 * CS_QKV * 128 + here(th) * 4, shift);
        }
        bar_arrive(BAR_Q, 256);
        RELEASE(F_QKV, F_QKV + 5);
      } else {
        bar_sync(BAR_Q, 256);
#pragma unroll
        for (int s = 0; s < 4; s++) lds128(qslot + s * 512, Q[4 * s], Q[4 * s + 1], Q[4 * s + 2], Q[4 * s + 3]);
        shift = lds32(SM_BASE + SM_CS + 2 * CS_QKV * 128 + th * 4);
        if (w < 2) {
          const uint32_t v = w ? 0u : 0x3F803F80u;
#pragma unroll
          for (int s = 0; s < 4; s++) sts128(qslot + s * 512, v, v, v, v);
          fence_async_smem();
        }
      }
      PROF_MARK(7);

      float O[36];
      {
        float S[2][32];
        uint32_t P[2][16], nm[4] = {shift & 0xFFFFu, shift >> 16, 0u, 0u};
        pin(Q); pin(nm);
        uint32_t sk = wg, sv = F_SPARE % NSTAGE + wg;
        mbar_wait(SM_BASE + SM_FULL + sv * 8, 1);
        if (wg == 1) bar_sync(BAR_ATT, 256);
        mbar_wait(SM_BASE + SM_FULL + sk * 8, 0);
        PROF_MARK(8);
        WG_FENCE();
        wgmma64_set<0>(S[0], nm, (uint64_t)((SM_BASE + SM_ONE) >> 4));
#pragma unroll
        for (int s = 0; s < 4; s++) wgmma64_acc<0>(S[0], &Q[4 * s], ring_desc(RING_K + sk * 1024 + s * 2));
        WG_COMMIT();
        SCHED();
#pragma unroll
        for (int i = 0; i < 36; i++) O[i] = 0.f;
#pragma unroll
        for (int i = 0; i < 32; i++) S[1][i] = 0.f;
#pragma unroll
        for (int i = 0; i < 16; i++) P[1][i] = 0u;
        pin(O); pin(S[1]); pin(P[1]);
        SCHED();
        WG_WAIT(0); pin(S[0]);
        if (wg == 0) bar_sync(BAR_ATT, 256);
#pragma unroll 1
        for (int it = 0; it < 4; it++) {
          const uint32_t sn = it >= 2 ? wg : sk + 4;
          uint32_t ok = 1;
          attn_step(S[0], S[1], P[0], P[1], O, Q, nm, RING_K + sk * 1024 + 512, RING_V + (sv * 1024 + 512) * V_STEP, true, it > 0, [&] {
            SCHED();
            mbar_probe(ok, SM_BASE + SM_FULL + sn * 8, it >= 2);
            mbar_probe(ok, SM_BASE + SM_FULL + (sk + 2) * 8, it == 3);
          });
          PROF_MARK(24 + it * 3);
          if (__builtin_expect(!ok, 0)) {
            mbar_wait(SM_BASE + SM_FULL + sn * 8, it >= 2);
            mbar_wait(SM_BASE + SM_FULL + (sk + 2) * 8, it == 3);
          }
          WG_WAIT(0); pin(O); pin(S[1]); pin(P[1]);
          asm volatile("{\n.reg .pred p;\nsetp.eq.u32 p, %2, 0;\n@p mbarrier.arrive.shared::cta.b64 _, [%0];\n@p mbarrier.arrive.shared::cta.b64 _, [%1];\n}"
                       :: "r"(SM_BASE + SM_EMPTY + sk * 8), "r"(SM_BASE + SM_EMPTY + sv * 8), "r"(lane) : "memory");
          PROF_MARK(25 + it * 3);
          sv = sk + 2; sk = sn;
          attn_step(S[1], S[0], P[1], P[0], O, Q, nm, RING_K + sk * 1024, RING_V + (sv * 1024) * V_STEP, it < 3, true);
          WG_WAIT(0); pin(O); pin(S[0]); pin(P[0]);
          PROF_MARK(26 + it * 3);
        }
        WG_FENCE();
        pv_tile(O, P[1], RING_V + (sv * 1024 + 512) * V_STEP, wg << 22);
        WG_COMMIT();
        announce<1>(sc, th == 0);
        WG_WAIT(0); pin(O);
      }
      PROF_MARK(9);

      {
        const uint32_t mo = stg + here(th) * 16;
        sts64(mo + 5 * 4096 + wg * 8, __float_as_uint(O[32]), __float_as_uint(O[34]));
        if (wg == 0) {
#pragma unroll
          for (int i = 4; i < 8; i++)
            sts128(mo + i * 2048, __float_as_uint(O[4 * i]), __float_as_uint(O[4 * i + 1]), __float_as_uint(O[4 * i + 2]), __float_as_uint(O[4 * i + 3]));
        } else {
#pragma unroll
          for (int i = 0; i < 4; i++)
            sts128(mo + i * 2048, __float_as_uint(O[4 * i]), __float_as_uint(O[4 * i + 1]), __float_as_uint(O[4 * i + 2]), __float_as_uint(O[4 * i + 3]));
#pragma unroll
          for (int i = 0; i < 16; i++) O[i] = O[16 + i];
        }
        bar_sync(BAR_MERGE, 256);
        uint32_t e[4];
        lds128(mo + 5 * 4096, e[0], e[1], e[2], e[3]);
        O[32] = __uint_as_float(e[0]) + __uint_as_float(e[2]); O[34] = __uint_as_float(e[1]) + __uint_as_float(e[3]);
#pragma unroll
        for (int i = 0; i < 4; i++) {
          lds128(mo + wg * TILE_BYTES + i * 2048, e[0], e[1], e[2], e[3]);
#pragma unroll
          for (int k = 0; k < 4; k++) O[4 * i + k] += __uint_as_float(e[k]);
        }
        const bool safe = O[32] > 0x1p-60f && O[32] < 0x1p60f && O[34] > 0x1p-60f && O[34] < 0x1p60f;
        if (__builtin_expect(__any_sync(0xffffffffu, !safe), 0)) attention_exact(O, Q, sc, batch * 4 + r, lane, wg);
        const float i0 = rcp_hw(O[32]), i1 = rcp_hw(O[34]);
#pragma unroll
        for (int i = 0; i < 8; i++) { const float v = (i & 1) ? i1 : i0; A[0][i] = pack2(O[2 * i] * v, O[2 * i + 1] * v); }
        A[0][0] &= ~1u; A[0][4] &= ~1u;
        uint4* dst = xp + X_AG1 + wg * 256;
        SCHED();
        st_vec(dst, A[0][0], A[0][1], A[0][2], A[0][3]);
        st_vec(dst + 128, A[0][4], A[0][5], A[0][6], A[0][7]);
        SCHED();
        if (TIMED) sent = clock_now();
      }
      const int dir = cw == 0 ? -1 : 1;
      uint32_t tap[15];
      if (wg == 1) {
        const uint32_t mo = stg + TILE_BYTES + here(th) * 16;
        sts128(mo, A[0][0], A[0][1], A[0][2], A[0][3]);
        sts128(mo + 2048, A[0][4], A[0][5], A[0][6], A[0][7]);
        bar_arrive(BAR_HALF, 256);
        load_taps(tap, dw, 1);
        halve_taps(tap);
      } else {
        PROF_MARK(10);
        const uint32_t mo = stg + TILE_BYTES + here(th) * 16;
        bar_sync(BAR_HALF, 256);
        lds128(mo, A[0][8], A[0][9], A[0][10], A[0][11]);
        lds128(mo + 2048, A[0][12], A[0][13], A[0][14], A[0][15]);
        proj_residual<F_WO, 6>(A, sc, xp, maddr, 0, sent);
        PROF_MARK(12);
        float acc[2][32];
        mma_tile<true>(acc[0], A[0], LO(F_PW1)); mma_tile<true>(acc[1], A[0], HI(F_PW1));
        gather_first<1, X_AG0>(A, st, sc, xp, 0, sent, [&] { load_taps(tap, dw, dir); });
        mma_tile<false>(acc[1], A[1], HI(F_PW1 + 1)); mma_tile<false>(acc[0], A[1], LO(F_PW1 + 1));
        gather_rest<1, X_AG0>(A, xp, 0);
        RELEASE(F_WO - 2, F_WO + 1);
        PROF_MARK(13);
        mma_tile<false>(acc[1], A[2], HI(F_PW1 + 2)); mma_tile<false>(acc[1], A[3], HI(F_PW1 + 3));
        WG_WAIT(2);
        RELEASE(F_WO + 2, F_WO - 3 + NREL);
        SCHED();
        uint32_t mu[4];
        const RowNorm n = stat_finish(sc, st, 0, 0.5f);
        const float rs0 = row0 < nvalid ? n.rs0 : 0.f, rs1 = row0 + 8 < nvalid ? n.rs1 : 0.f;
        mean_frag(mu, n, q == 0);
        mma_fold<2 * CS_PW1 + 2>(acc[1], mu);
        mma_tile<false>(acc[0], A[2], LO(F_PW1 + 2));
        halve_taps(tap);
        mma_tile_fold<2 * CS_PW1>(acc[0], A[3], LO(F_PW1 + 3), mu);
        WG_WAIT(2); pin(acc[1]);
#pragma unroll
        for (int i = 0; i < 32; i++) acc[1][i] = tanh_hw(acc[1][i] * ((i & 2) ? rs1 : rs0));
#pragma unroll
        for (int i = 0; i < 32; i++) { const float rs = (i & 2) ? rs1 : rs0; acc[1][i] = fmaf(acc[1][i], rs, rs); }
        pin(acc[1]);
        SCHED();
        WG_WAIT(0); pin(acc[0]);
#pragma unroll
        for (int i = 0; i < 16; i++) A[0][i] = pack2(acc[0][2 * i] * acc[1][2 * i], acc[0][2 * i + 1] * acc[1][2 * i + 1]);
        const uint32_t ga = stg + TILE_BYTES + here(mrow) * G_PITCH + (lane >> 4) * 16;
#pragma unroll
        for (int s = 0; s < 4; s++) stsm4(ga + s * 32, &A[0][4 * s]);
      }
      {
        const uint32_t gsrc = stg + TILE_BYTES + (8 * cw - 7) * G_PITCH + lane * 4;
        const bool edge = cw == 0 || cw == 7;
        const bool nbr = cw == 0 ? t > 0 : t < 15;
        uint4* const hdst = &sc->x[b + 4 * dir][X_HALO + (cw == 0 ? 96 : 0) + lane];
        uint32_t in[22];
        bar_sync(BAR_G, 256);
        PROF_MARK(14);
        if (cw == 0) {
#pragma unroll
          for (int i = 14; i >= 0; i--) in[i] = lds32(gsrc + (21 - i) * G_PITCH);
        } else {
#pragma unroll
          for (int i = 14; i >= 0; i--) in[i] = lds32(gsrc + i * G_PITCH);
        }
        if (edge) {
          if (nbr) {
            st_vec(hdst, HALO_TAG, in[14], in[13], in[12]);
            st_vec(hdst + 32, HALO_TAG, in[11], in[10], in[9]);
            st_vec(hdst + 64, HALO_TAG, in[8], 0u, 0u);
          }
        } else {
#pragma unroll
          for (int i = 15; i < 22; i++) in[i] = lds32(gsrc + i * G_PITCH);
        }
        if (cw == 0) PROF_MARK0(40);
        uint32_t cv[8];
#pragma unroll
        for (int i = 0; i < 15; i++)
#pragma unroll
          for (int o = 0; o < 8; o++) {
            if (i == o) asm("mul.rn.bf16x2 %0, %1, %2;" : "=r"(cv[o]) : "r"(in[i]), "r"(tap[0]));
            if (i > o) asm("fma.rn.bf16x2 %0, %1, %2, %0;" : "+r"(cv[o]) : "r"(in[i]), "r"(tap[i - o]));
          }
        pin(cv);
        if (cw == 0) PROF_MARK0(41);
        if (edge) {
#pragma unroll
          for (int i = 15; i < 22; i++) in[i] = 0u;
          if (nbr) {
            const uint4* src = &sc->x[b][X_HALO + (cw == 0 ? 0 : 96) + lane];
            uint32_t e0, e1, e2, u0, u1, spin = 0;
#pragma unroll 1
            do {
              ld_vec(src, e0, in[15], in[16], in[17]);
              ld_vec(src + 32, e1, in[18], in[19], in[20]);
              ld_vec(src + 64, e2, in[21], u0, u1);
            } while (__any_sync(0xffffffffu, ((e0 ^ HALO_TAG) | (e1 ^ HALO_TAG) | (e2 ^ HALO_TAG)) != 0) && ++spin < SPIN_LIMIT);
          }
          announce<1>(sc, lane == 0);
        }
#pragma unroll
        for (int i = 15; i < 22; i++)
#pragma unroll
          for (int o = 0; o < 8; o++)
            if (i - o <= 14) asm("fma.rn.bf16x2 %0, %1, %2, %0;" : "+r"(cv[o]) : "r"(in[i]), "r"(tap[i - o]));
        if (cw == 0) PROF_MARK0(42);
        if (cw == 7) PROF_MARK0(43);
        const uint32_t fl = cw == 0 ? 7 : 0;
        const uint32_t cdst = (stg + cw * 1024 + lane * 4) ^ (fl * 144);
#pragma unroll
        for (int o = 0; o < 8; o++) {
          const float a = bf_lo(cv[o]), c = bf_hi(cv[o]);
          sts32(cdst ^ (o * 144), pack2(fmaf(a, tanh_hw(a), a), fmaf(c, tanh_hw(c), c)));
        }
      }
      if (wg == 1) {
        bar_arrive(BAR_C, 256);
        break;
      }
      bar_sync(BAR_C, 256);
      tile_load(here(maddr), A[0]);
      PROF_MARK(15);
      publish(xp + X_AG1, A[0], 1);
      proj_residual<F_PW2, 2>(A, sc, xp, maddr, 1, sent);
      PROF_MARK(17);
    }
  }
}

typedef CUresult (*EncodeFn)(CUtensorMap*, CUtensorMapDataType, cuuint32_t, void*, const cuuint64_t*, const cuuint64_t*,
                             const cuuint32_t*, const cuuint32_t*, CUtensorMapInterleave, CUtensorMapSwizzle,
                             CUtensorMapL2promotion, CUtensorMapFloatOOBfill);

void make_map(EncodeFn fn, CUtensorMap* m, const void* w, int rows, int cols, CUtensorMapSwizzle swz) {
  const cuuint64_t dims[2] = {(cuuint64_t)cols, (cuuint64_t)rows}, strides[1] = {(cuuint64_t)cols * 2};
  const cuuint32_t box[2] = {64, 64}, es[2] = {1, 1};
  fn(m, CU_TENSOR_MAP_DATA_TYPE_BFLOAT16, 2, const_cast<void*>(w), dims, strides, box, es, CU_TENSOR_MAP_INTERLEAVE_NONE,
     swz, CU_TENSOR_MAP_L2_PROMOTION_L2_128B, CU_TENSOR_MAP_FLOAT_OOB_FILL_NONE);
}

}

extern "C" void kernel_launch(void* const* d_in, const int* in_sizes, int n_in, void* d_out, int out_size) {
  static EncodeFn fn = nullptr;
  static Scratch* sc = nullptr;
  if (!fn) {
    void* f = nullptr;
    cudaDriverEntryPointQueryResult st;
    cudaGetDriverEntryPoint("cuTensorMapEncodeTiled", &f, cudaEnableDefault, &st);
    fn = (EncodeFn)f;
    void* raw = nullptr;
    cudaGetSymbolAddress(&raw, g_scratch);
    sc = (Scratch*)(((uintptr_t)raw + X_ALIGN - 1) & ~(uintptr_t)(X_ALIGN - 1));
    cudaFuncSetAttribute(conformer_kernel, cudaFuncAttributeMaxDynamicSharedMemorySize, SM_TOTAL);
  }
  typedef const __nv_bfloat16* W;
  const CUtensorMapSwizzle S = CU_TENSOR_MAP_SWIZZLE_128B;
  Params p;
  make_map(fn, &p.map[M_FF1A], d_in[1], 256, 1024, S);
  make_map(fn, &p.map[M_FF1B], d_in[2], 1024, 256, S);
  make_map(fn, &p.map[M_QKV], d_in[3], 256, 768, S);
  make_map(fn, &p.map[M_WO], d_in[4], 256, 256, S);
  make_map(fn, &p.map[M_PW1], d_in[5], 256, 512, S);
  make_map(fn, &p.map[M_PW2], d_in[7], 256, 256, S);
  make_map(fn, &p.map[M_FF2A], d_in[8], 256, 1024, S);
  make_map(fn, &p.map[M_FF2B], d_in[9], 1024, 256, S);
  p.w_ff1b = (W)d_in[2]; p.w_qkv = (W)d_in[3]; p.w_o = (W)d_in[4]; p.w_pw1 = (W)d_in[5];
  p.w_pw2 = (W)d_in[7]; p.w_ff2a = (W)d_in[8]; p.w_ff2b = (W)d_in[9];

  cudaLaunchConfig_t cfg = {};
  cfg.gridDim = dim3(NCTA);
  cfg.blockDim = dim3(384);
  cfg.dynamicSmemBytes = SM_TOTAL;
  cfg.stream = cudaStreamPerThread;
  cudaLaunchAttribute at[1];
  at[0].id = cudaLaunchAttributeCooperative;
  at[0].val.cooperative = 1;
  cfg.attrs = at;
  cfg.numAttrs = 1;
  cudaLaunchKernelEx(&cfg, conformer_kernel, sc, (__nv_bfloat16*)d_out, (W)d_in[6], (W)d_in[0], (W)d_in[1], p);
}
```

```cpp
#include <cuda_runtime.h>
#include <cuda_bf16.h>
#include <cuda.h>
#include <stdint.h>

namespace {

constexpr int T_SEQ = 1000;
constexpr int DM = 256;
constexpr int NCTA = 128;
constexpr int NSTAGE = 12;
constexpr uint32_t STAGE_BYTES = 16384;
constexpr uint32_t TILE_BYTES = 8192;
constexpr uint32_t SM_BASE = 1024;
constexpr uint32_t SM_STG = NSTAGE * STAGE_BYTES;
constexpr uint32_t SM_FULL = SM_STG + 32768;
constexpr uint32_t SM_EMPTY = SM_FULL + 96;
constexpr uint32_t SM_KVRDY = SM_FULL + 192;
constexpr uint32_t SM_EYE = SM_FULL + 256;
constexpr uint32_t SM_ONE = SM_FULL + 640;
constexpr uint32_t SM_CS = SM_FULL + 768;
constexpr uint32_t SM_TOTAL = SM_FULL + 3072;
constexpr int CS_FF2 = 0, CS_PW1 = 4, CS_QKV = 6;
constexpr uint32_t SPIN_LIMIT = 1u << 16;
constexpr float LN_EPS = 1e-5f;
constexpr float SM_SCALE_LOG2 = 0.125f * 1.4426950408889634f;
constexpr uint32_t G_PITCH = 144;
#define FSTR 8
#define CS_AFTER 8
#define TIMED 0
#define GD 400
#define RD 550
#define NREL 5
#define PF0 1
#define TF 1
#define TC 1
#define PF1 1400
#define PF2 2000
#define PF3 3500
#define CLR_PACE 150

constexpr int F_QKV = 16, F_SPARE = 22, F_KV = 24, F_WO = 40, F_PW1 = 42, F_PW2 = 46, F_TOTAL = 64;
enum { M_FF1A, M_FF1B, M_QKV, M_WO, M_PW1, M_PW2, M_FF2A, M_FF2B, M_COUNT };
enum { BAR_K = 1, BAR_V, BAR_Q, BAR_MERGE, BAR_G, BAR_C, BAR_WG1, BAR_GO, BAR_CS, BAR_ATT, BAR_INIT, BAR_HALF, BAR_RST, BAR_TAP };

struct Params {
  CUtensorMap map[M_COUNT];
  const __nv_bfloat16 *w_ff1b, *w_qkv, *w_o, *w_pw1, *w_pw2, *w_ff2a, *w_ff2b;
};

constexpr int X_RS = 0, X_AG1 = X_RS, X_HALO = X_RS + 512, X_AG0 = 1536, X_ST = 2048, X_SIZE = 4096;
constexpr uint32_t HALO_TAG = 0xFFFF0001u;
struct Scratch {
  uint4 x[NCTA][X_SIZE];
  uint4 kv[8][2][16][512];
  uint4 cs[2][576];
  uint32_t flag[8][32][FSTR];
  uint32_t step[NCTA][32];
};
constexpr size_t X_ALIGN = 4 * X_SIZE * sizeof(uint4);
__device__ uint8_t g_scratch[sizeof(Scratch) + X_ALIGN];
#define PROF_TIME(i)
#define PROF_MARK(i)
#define PROF_MARK2(i, j)
#define PROF_MARK0(i)
#define PROF_AT(a)

__device__ __forceinline__ void mbar_init(uint32_t bar, uint32_t cnt) {
  asm volatile("mbarrier.init.shared::cta.b64 [%0], %1;" :: "r"(bar), "r"(cnt) : "memory");
}
__device__ __forceinline__ void mbar_wait(uint32_t bar, uint32_t parity) {
  asm volatile("{\n.reg .pred p;\n.reg .u32 c;\nmov.u32 c, 0;\n"
               "WAIT_LOOP:\nmbarrier.try_wait.parity.shared::cta.b64 p, [%0], %1;\n@p bra WAIT_DONE;\n"
               "add.u32 c, c, 1;\nsetp.lt.u32 p, c, %2;\n@p bra WAIT_LOOP;\nWAIT_DONE:\n}"
               :: "r"(bar), "r"(parity), "n"(SPIN_LIMIT) : "memory");
}
__device__ __forceinline__ void mbar_arrive(uint32_t bar) {
  asm volatile("mbarrier.arrive.shared::cta.b64 _, [%0];" :: "r"(bar) : "memory");
}
#define bar_sync(id, n) asm volatile("bar.sync %0, %1;" :: "n"((int)(id)), "n"(n) : "memory")
#define bar_arrive(id, n) asm volatile("bar.arrive %0, %1;" :: "n"((int)(id)), "n"(n) : "memory")
__device__ __forceinline__ void fence_async_smem() { asm volatile("fence.proxy.async.shared::cta;" ::: "memory"); }

__device__ __forceinline__ void st_vec(uint4* p, uint32_t a, uint32_t b, uint32_t c, uint32_t d) {
  asm volatile("{\n.reg .b128 v;\n.reg .b64 lo, hi;\nmov.b64 lo, {%1, %2};\nmov.b64 hi, {%3, %4};\nmov.b128 v, {lo, hi};\n"
               "st.relaxed.gpu.global.b128 [%0], v;\n}" :: "l"(p), "r"(a), "r"(b), "r"(c), "r"(d) : "memory");
}
__device__ __forceinline__ void ld_vec(const uint4* p, uint32_t& a, uint32_t& b, uint32_t& c, uint32_t& d) {
  asm volatile("{\n.reg .b128 v;\n.reg .b64 lo, hi;\nld.relaxed.gpu.global.b128 v, [%4];\nmov.b128 {lo, hi}, v;\n"
               "mov.b64 {%0, %1}, lo;\nmov.b64 {%2, %3}, hi;\n}" : "=r"(a), "=r"(b), "=r"(c), "=r"(d) : "l"(p) : "memory");
}
__device__ __forceinline__ void sts128(uint32_t a, uint32_t x, uint32_t y, uint32_t z, uint32_t w) {
  asm volatile("st.shared.v4.u32 [%0], {%1, %2, %3, %4};" :: "r"(a), "r"(x), "r"(y), "r"(z), "r"(w) : "memory");
}
__device__ __forceinline__ void lds128(uint32_t a, uint32_t& x, uint32_t& y, uint32_t& z, uint32_t& w) {
  asm volatile("ld.shared.v4.u32 {%0, %1, %2, %3}, [%4];" : "=r"(x), "=r"(y), "=r"(z), "=r"(w) : "r"(a) : "memory");
}
__device__ __forceinline__ uint32_t lds32(uint32_t a) {
  uint32_t x; asm volatile("ld.shared.u32 %0, [%1];" : "=r"(x) : "r"(a) : "memory"); return x;
}
__device__ __forceinline__ void sts32(uint32_t a, uint32_t x) { asm volatile("st.shared.u32 [%0], %1;" :: "r"(a), "r"(x) : "memory"); }
__device__ __forceinline__ void sts64(uint32_t a, uint32_t x, uint32_t y) {
  asm volatile("st.shared.v2.u32 [%0], {%1, %2};" :: "r"(a), "r"(x), "r"(y) : "memory");
}
__device__ __forceinline__ void stsm4(uint32_t a, const uint32_t* r) {
  asm volatile("stmatrix.sync.aligned.m8n8.x4.shared.b16 [%0], {%1, %2, %3, %4};" :: "r"(a), "r"(r[0]), "r"(r[1]), "r"(r[2]), "r"(r[3]) : "memory");
}
__device__ __forceinline__ void ldsm4(uint32_t a, uint32_t* r) {
  asm volatile("ldmatrix.sync.aligned.m8n8.x4.shared.b16 {%0, %1, %2, %3}, [%4];" : "=r"(r[0]), "=r"(r[1]), "=r"(r[2]), "=r"(r[3]) : "r"(a) : "memory");
}
__device__ __forceinline__ uint32_t pack2(float lo, float hi) {
  uint32_t r; asm("cvt.rn.bf16x2.f32 %0, %1, %2;" : "=r"(r) : "f"(hi), "f"(lo)); return r;
}
__device__ __forceinline__ float bf_lo(uint32_t w) { return __uint_as_float(w << 16); }
__device__ __forceinline__ float bf_hi(uint32_t w) { return __uint_as_float(w & 0xffff0000u); }
__device__ __forceinline__ float tanh_hw(float x) { float y; asm volatile("tanh.approx.f32 %0, %1;" : "=f"(y) : "f"(x)); return y; }
__device__ __forceinline__ float rcp_hw(float x) { float y; asm("rcp.approx.ftz.f32 %0, %1;" : "=f"(y) : "f"(x)); return y; }
__device__ __forceinline__ float rsqrt_hw(float x) { float y; asm("rsqrt.approx.ftz.f32 %0, %1;" : "=f"(y) : "f"(x)); return y; }
__device__ __forceinline__ float ex2_hw(float x) { float y; asm("ex2.approx.ftz.f32 %0, %1;" : "=f"(y) : "f"(x)); return y; }

__device__ __forceinline__ uint32_t here(uint32_t v) { asm volatile("" : "+r"(v)); return v; }

#define SCHED() asm volatile("pmevent 1;" ::: "memory")
__device__ __forceinline__ void cp_async16(uint32_t dst, const void* src) {
  asm volatile("cp.async.cg.shared.global [%0], [%1], 16;" :: "r"(dst), "l"(src) : "memory");
}
__device__ __forceinline__ void cp_async_wait(int n) {
  if (n == 0) asm volatile("cp.async.wait_group 0;" ::: "memory");
  if (n == 1) asm volatile("cp.async.wait_group 1;" ::: "memory");
  if (n == 2) asm volatile("cp.async.wait_group 2;" ::: "memory");
  if (n == 3) asm volatile("cp.async.wait_group 3;" ::: "memory");
}
#define WG_FENCE() asm volatile("wgmma.fence.sync.aligned;" ::: "memory")
#define WG_COMMIT() asm volatile("wgmma.commit_group.sync.aligned;" ::: "memory")
#define WG_WAIT(n) asm volatile("wgmma.wait_group.sync.aligned %0;" :: "n"(n) : "memory")

template <int N> __device__ __forceinline__ void pin(float (&d)[N]) {
#pragma unroll
  for (int i = 0; i < N; i++) asm volatile("" : "+f"(d[i]) :: "memory");
}
template <int N> __device__ __forceinline__ void pin(uint32_t (&d)[N]) {
#pragma unroll
  for (int i = 0; i < N; i++) asm volatile("" : "+r"(d[i]) :: "memory");
}

#define WG_D32 "{%0, %1, %2, %3, %4, %5, %6, %7, %8, %9, %10, %11, %12, %13, %14, %15, %16, %17, %18, %19, %20, %21, %22, %23, %24, %25, %26, %27, %28, %29, %30, %31}"
template <int TB> __device__ __forceinline__ void wgmma64_acc(float (&d)[32], const uint32_t* a, uint64_t db) {
  asm volatile("wgmma.mma_async.sync.aligned.m64n64k16.f32.bf16.bf16 " WG_D32 ", {%32, %33, %34, %35}, %36, 1, 1, 1, %37;"
    : "+f"(d[0]), "+f"(d[1]), "+f"(d[2]), "+f"(d[3]), "+f"(d[4]), "+f"(d[5]), "+f"(d[6]), "+f"(d[7]),
      "+f"(d[8]), "+f"(d[9]), "+f"(d[10]), "+f"(d[11]), "+f"(d[12]), "+f"(d[13]), "+f"(d[14]), "+f"(d[15]),
      "+f"(d[16]), "+f"(d[17]), "+f"(d[18]), "+f"(d[19]), "+f"(d[20]), "+f"(d[21]), "+f"(d[22]), "+f"(d[23]),
      "+f"(d[24]), "+f"(d[25]), "+f"(d[26]), "+f"(d[27]), "+f"(d[28]), "+f"(d[29]), "+f"(d[30]), "+f"(d[31])
    : "r"(a[0]), "r"(a[1]), "r"(a[2]), "r"(a[3]), "l"(db), "n"(TB));
}
template <int TB> __device__ __forceinline__ void wgmma64_reuse(float (&d)[32], const uint32_t* a, uint64_t db, uint32_t zero) {
  asm volatile("{\n.reg .pred p;\nsetp.ne.u32 p, %37, 0;\nwgmma.mma_async.sync.aligned.m64n64k16.f32.bf16.bf16 " WG_D32 ", {%32, %33, %34, %35}, %36, p, 1, 1, %38;\n}"
    : "+f"(d[0]), "+f"(d[1]), "+f"(d[2]), "+f"(d[3]), "+f"(d[4]), "+f"(d[5]), "+f"(d[6]), "+f"(d[7]),
      "+f"(d[8]), "+f"(d[9]), "+f"(d[10]), "+f"(d[11]), "+f"(d[12]), "+f"(d[13]), "+f"(d[14]), "+f"(d[15]),
      "+f"(d[16]), "+f"(d[17]), "+f"(d[18]), "+f"(d[19]), "+f"(d[20]), "+f"(d[21]), "+f"(d[22]), "+f"(d[23]),
      "+f"(d[24]), "+f"(d[25]), "+f"(d[26]), "+f"(d[27]), "+f"(d[28]), "+f"(d[29]), "+f"(d[30]), "+f"(d[31])
    : "r"(a[0]), "r"(a[1]), "r"(a[2]), "r"(a[3]), "l"(db), "r"(zero), "n"(TB));
}
template <int TB> __device__ __forceinline__ void wgmma64_set(float (&d)[32], const uint32_t* a, uint64_t db) {
  asm volatile("wgmma.mma_async.sync.aligned.m64n64k16.f32.bf16.bf16 " WG_D32 ", {%32, %33, %34, %35}, %36, 0, 1, 1, %37;"
    : "=f"(d[0]), "=f"(d[1]), "=f"(d[2]), "=f"(d[3]), "=f"(d[4]), "=f"(d[5]), "=f"(d[6]), "=f"(d[7]),
      "=f"(d[8]), "=f"(d[9]), "=f"(d[10]), "=f"(d[11]), "=f"(d[12]), "=f"(d[13]), "=f"(d[14]), "=f"(d[15]),
      "=f"(d[16]), "=f"(d[17]), "=f"(d[18]), "=f"(d[19]), "=f"(d[20]), "=f"(d[21]), "=f"(d[22]), "=f"(d[23]),
      "=f"(d[24]), "=f"(d[25]), "=f"(d[26]), "=f"(d[27]), "=f"(d[28]), "=f"(d[29]), "=f"(d[30]), "=f"(d[31])
    : "r"(a[0]), "r"(a[1]), "r"(a[2]), "r"(a[3]), "l"(db), "n"(TB));
}

__device__ __forceinline__ void wgmma72_acc(float (&d)[36], const uint32_t* a, uint64_t db) {
  asm volatile("wgmma.mma_async.sync.aligned.m64n72k16.f32.bf16.bf16 {%0, %1, %2, %3, %4, %5, %6, %7, %8, %9, %10, %11, %12, %13, %14, %15, %16, %17, %18, %19, %20, %21, %22, %23, %24, %25, %26, %27, %28, %29, %30, %31, %32, %33, %34, %35}, {%36, %37, %38, %39}, %40, 1, 1, 1, 1;"
    : "+f"(d[0]), "+f"(d[1]), "+f"(d[2]), "+f"(d[3]), "+f"(d[4]), "+f"(d[5]), "+f"(d[6]), "+f"(d[7]), "+f"(d[8]),
      "+f"(d[9]), "+f"(d[10]), "+f"(d[11]), "+f"(d[12]), "+f"(d[13]), "+f"(d[14]), "+f"(d[15]), "+f"(d[16]), "+f"(d[17]),
      "+f"(d[18]), "+f"(d[19]), "+f"(d[20]), "+f"(d[21]), "+f"(d[22]), "+f"(d[23]), "+f"(d[24]), "+f"(d[25]), "+f"(d[26]),
      "+f"(d[27]), "+f"(d[28]), "+f"(d[29]), "+f"(d[30]), "+f"(d[31]), "+f"(d[32]), "+f"(d[33]), "+f"(d[34]), "+f"(d[35])
    : "r"(a[0]), "r"(a[1]), "r"(a[2]), "r"(a[3]), "l"(db));
}
__device__ __forceinline__ void wgmma16_acc(float* d, const uint32_t* a, uint64_t db) {
  asm volatile("wgmma.mma_async.sync.aligned.m64n16k16.f32.bf16.bf16 {%0, %1, %2, %3, %4, %5, %6, %7}, {%8, %9, %10, %11}, %12, 1, 1, 1, 0;"
    : "+f"(d[0]), "+f"(d[1]), "+f"(d[2]), "+f"(d[3]), "+f"(d[4]), "+f"(d[5]), "+f"(d[6]), "+f"(d[7])
    : "r"(a[0]), "r"(a[1]), "r"(a[2]), "r"(a[3]), "l"(db));
}
__device__ __forceinline__ void hmma(float (&d)[4], const uint32_t* a, uint32_t b0, uint32_t b1) {
  asm("mma.sync.aligned.m16n8k16.row.col.f32.bf16.bf16.f32 {%0, %1, %2, %3}, {%4, %5, %6, %7}, {%8, %9}, {%0, %1, %2, %3};"
    : "+f"(d[0]), "+f"(d[1]), "+f"(d[2]), "+f"(d[3]) : "r"(a[0]), "r"(a[1]), "r"(a[2]), "r"(a[3]), "r"(b0), "r"(b1));
}

__device__ __forceinline__ void hmma8(float (&d)[4], const uint32_t* a, uint32_t b0) {
  asm("mma.sync.aligned.m16n8k8.row.col.f32.bf16.bf16.f32 {%0, %1, %2, %3}, {%4, %5}, {%6}, {%0, %1, %2, %3};"
    : "+f"(d[0]), "+f"(d[1]), "+f"(d[2]), "+f"(d[3]) : "r"(a[0]), "r"(a[1]), "r"(b0));
}

template <bool FIRST> __device__ __forceinline__ void mma_tile(float (&d)[32], const uint32_t (&a)[16], uint64_t db) {
  WG_FENCE();
#pragma unroll
  for (int s = 0; s < 4; s++) {
    if (FIRST && s == 0) wgmma64_set<1>(d, &a[0], db); else wgmma64_acc<1>(d, &a[4 * s], db + s * 128);
  }
  WG_COMMIT();
}
__device__ __forceinline__ void mma_tile_reuse(float (&d)[32], const uint32_t (&a)[16], uint64_t db) {
  WG_FENCE();
  wgmma64_reuse<1>(d, &a[0], db, blockIdx.y);
#pragma unroll
  for (int s = 1; s < 4; s++) wgmma64_acc<1>(d, &a[4 * s], db + s * 128);
  WG_COMMIT();
}
template <int ROW> __device__ __forceinline__ void fold_step(float (&d)[32], const uint32_t (&mu)[4]) {
  wgmma64_acc<1>(d, mu, (uint64_t)((SM_BASE + SM_CS + ROW * 128) >> 4) | (uint64_t(1) << 16) | (uint64_t(1) << 62));
}
template <int ROW> __device__ __forceinline__ void mma_fold(float (&d)[32], const uint32_t (&mu)[4]) {
  WG_FENCE();
  fold_step<ROW>(d, mu);
  WG_COMMIT();
}
template <int ROW> __device__ __forceinline__ void mma_tile_fold(float (&d)[32], const uint32_t (&a)[16], uint64_t db, const uint32_t (&mu)[4]) {
  WG_FENCE();
#pragma unroll
  for (int s = 0; s < 4; s++) wgmma64_acc<1>(d, &a[4 * s], db + s * 128);
  fold_step<ROW>(d, mu);
  WG_COMMIT();
}
__device__ __forceinline__ void mma_add_half(float (&d)[32], const uint32_t (&a)[16]) {
  const uint64_t db = (uint64_t)((SM_BASE + SM_EYE) >> 4) | (uint64_t(8) << 16) | (uint64_t(8) << 32);
  WG_FENCE();
#pragma unroll
  for (int s = 0; s < 4; s++) wgmma16_acc(&d[8 * s], &a[4 * s], db);
  WG_COMMIT();
}
#define ACQUIRE(f) mbar_wait(SM_BASE + SM_FULL + ((f) % NSTAGE) * 8, ((f) / NSTAGE) & 1)
__device__ __forceinline__ void mbar_probe(uint32_t& ok, uint32_t bar, uint32_t parity) {
  asm volatile("{\n.reg .pred p;\nmbarrier.test_wait.parity.shared::cta.b64 p, [%1], %2;\nselp.u32 %0, %0, 0, p;\n}"
               : "+r"(ok) : "r"(bar), "r"(parity) : "memory");
}
template <int F, int N> __device__ __forceinline__ uint32_t probe_n() {
  static_assert(F % NSTAGE + N <= NSTAGE, "stages must not wrap");
  uint32_t ok = 1;
#pragma unroll
  for (int i = 0; i < N; i++) mbar_probe(ok, SM_BASE + SM_FULL + (F % NSTAGE + i) * 8, (F / NSTAGE) & 1);
  return ok;
}
template <int F, int N> __device__ __forceinline__ void settle_n(uint32_t ok) {
  if (__builtin_expect(!ok, 0)) {
#pragma unroll 1
    for (int i = 0; i < N; i++) mbar_wait(SM_BASE + SM_FULL + (F % NSTAGE + i) * 8, (F / NSTAGE) & 1);
  }
}
template <int F, int N> __device__ __forceinline__ void acquire_n() { settle_n<F, N>(probe_n<F, N>()); }
#define RELEASE(f0, f1) do { if (lane == 0) { _Pragma("unroll") for (int f_ = (f0); f_ <= (f1); f_++) mbar_arrive(SM_BASE + SM_EMPTY + (f_ % NSTAGE) * 8); } } while (0)
constexpr uint64_t RING = (uint64_t)(SM_BASE >> 4) | (uint64_t(1) << 16) | (uint64_t(64) << 32) | (uint64_t(1) << 62);
#define LO(f) (RING + ((f) % NSTAGE) * 1024)
#define HI(f) (RING + ((f) % NSTAGE) * 1024 + 512)

template <int C> __device__ __forceinline__ uint4* peer(uint4* p) {
  asm volatile("" : "+l"(p));
  return (uint4*)((uintptr_t)p ^ (C * X_SIZE * sizeof(uint4)));
}
__device__ __forceinline__ uint32_t clock_now() { uint32_t c; asm volatile("mov.u32 %0, %%clock;" : "=r"(c) :: "memory"); return c; }
__device__ __forceinline__ void publish(uint4* dst, uint32_t (&a)[16], uint32_t tag) {
#pragma unroll
  for (int s = 0; s < 4; s++) a[4 * s] = (a[4 * s] & ~1u) | tag;
  pin(a);
  SCHED();
#pragma unroll
  for (int s = 0; s < 4; s++) st_vec(dst + s * 128, a[4 * s], a[4 * s + 1], a[4 * s + 2], a[4 * s + 3]);
  SCHED();
}
__device__ __forceinline__ void fetch(const uint4* src, uint32_t (&a)[16]) {
#pragma unroll
  for (int s = 0; s < 4; s++) ld_vec(src + s * 128, a[4 * s], a[4 * s + 1], a[4 * s + 2], a[4 * s + 3]);
}
__device__ __forceinline__ uint32_t miss(const uint32_t (&a)[16], uint32_t tag) {
  return (a[0] ^ tag) | (a[4] ^ tag) | (a[8] ^ tag) | (a[12] ^ tag);
}
__device__ __forceinline__ bool stale(uint32_t v) { return __any_sync(0xffffffffu, here(v) & 1u); }
template <int N = 2> __device__ __forceinline__ void announce(Scratch* sc, bool leader) {
  asm volatile("{\n.reg .pred p;\nsetp.ne.u32 p, %1, 0;\n@p red.relaxed.gpu.global.add.u32 [%0], %2;\n}"
               :: "l"(sc->step[blockIdx.x]), "r"((uint32_t)leader), "n"(N) : "memory");
}
__device__ __forceinline__ uint32_t launch_index(const Scratch* sc) { return *(const volatile uint32_t*)sc->step[blockIdx.x] >> 4; }
__device__ __forceinline__ void stat_fetch(const Scratch* sc, uint32_t (&st)[4]) {
  const uint32_t th = here(threadIdx.x);
  ld_vec(&sc->x[(blockIdx.x & ~3u) + (th & 3)][X_ST + (th >> 2)], st[0], st[1], st[2], st[3]);
}
struct Nothing { __device__ __forceinline__ void operator()() const {} };
template <int C, int SLOT, class F = Nothing>
__device__ __forceinline__ void gather_first(uint32_t (&A)[4][16], uint32_t (&st)[4], const Scratch* sc, uint4* xp, uint32_t tag, uint32_t sent, F meanwhile = F()) {
  if (TIMED) { while (clock_now() - sent < GD) {} } else bar_sync(BAR_GO, 160);
  fetch(peer<1>(xp) + SLOT, A[1]); fetch(peer<2>(xp) + SLOT, A[2]); fetch(peer<3>(xp) + SLOT, A[3]);
  if (SLOT == X_AG0) stat_fetch(sc, st);
  meanwhile();
  uint32_t spin = 0;
  while (__builtin_expect(stale(miss(A[1], tag) | miss(A[C], tag)), 0) && ++spin < SPIN_LIMIT) {
    fetch(peer<1>(xp) + SLOT, A[1]);
    if (C == 2) fetch(peer<2>(xp) + SLOT, A[2]);
  }
}
template <int C, int SLOT> __device__ __forceinline__ void gather_rest(uint32_t (&A)[4][16], uint4* xp, uint32_t tag) {
  SCHED();
  uint32_t spin = 0;
  while (__builtin_expect(stale(miss(A[C + 1], tag) | miss(A[3], tag)), 0) && ++spin < SPIN_LIMIT) {
    if (C == 1) fetch(peer<2>(xp) + SLOT, A[2]);
    fetch(peer<3>(xp) + SLOT, A[3]);
  }
}
__device__ __forceinline__ void pack_acc(const float (&d)[32], uint32_t (&a)[16]) {
#pragma unroll
  for (int i = 0; i < 16; i++) a[i] = pack2(d[2 * i], d[2 * i + 1]);
}
__device__ __forceinline__ void frag_store(uint32_t slot, const uint32_t (&a)[16]) {
#pragma unroll
  for (int s = 0; s < 4; s++) sts128(slot + s * 512, a[4 * s], a[4 * s + 1], a[4 * s + 2], a[4 * s + 3]);
}
__device__ __forceinline__ void tile_store(uint32_t maddr, const uint32_t (&a)[16]) {
#pragma unroll
  for (int s = 0; s < 4; s++) stsm4(maddr ^ (s << 5), &a[4 * s]);
}
__device__ __forceinline__ void tile_load(uint32_t maddr, uint32_t (&a)[16]) {
#pragma unroll
  for (int s = 0; s < 4; s++) ldsm4(maddr ^ (s << 5), &a[4 * s]);
}

__device__ __forceinline__ void res_load(uint32_t maddr, float (&d)[32]) {
  uint32_t a[16];
  tile_load(here(maddr) + 3 * TILE_BYTES, a);
#pragma unroll
  for (int i = 0; i < 16; i++) { d[2 * i] = bf_lo(a[i]); d[2 * i + 1] = bf_hi(a[i]); }
  pin(d);
}

struct RowAcc { float s[2][4], u[2][4], v[2][4]; };
__device__ __forceinline__ void row_sums(RowAcc& t, const uint32_t (&a)[16]) {
#pragma unroll
  for (int s = 0; s < 4; s++) hmma(t.s[s & 1], &a[4 * s], 0x3F803F80u, 0x3F803F80u);
}
__device__ __forceinline__ void row_gram(RowAcc& t, const uint32_t (&a)[16]) {
#pragma unroll
  for (int s = 0; s < 8; s++) {
    hmma8(t.u[s & 1], &a[2 * s], a[2 * s]);
    hmma8(t.v[s & 1], &a[2 * s], a[2 * s + 1]);
  }
}
__device__ __forceinline__ float2 row_squares(const RowAcc& t, bool odd) {
  return make_float2(odd ? t.u[0][1] + t.u[1][1] : t.u[0][0] + t.u[1][0], odd ? t.v[0][3] + t.v[1][3] : t.v[0][2] + t.v[1][2]);
}
__device__ __forceinline__ void stat_publish(const uint32_t (&a)[16], Scratch* sc, uint32_t th, uint32_t tag) {
  RowAcc t = {};
  row_sums(t, a);
  row_gram(t, a);
  const float2 q = row_squares(t, th & 4);
  if ((th & 3) == ((th >> 3) & 3))
    st_vec(&sc->x[blockIdx.x][X_ST + (th >> 2)], (__float_as_uint(t.s[0][0] + t.s[1][0]) & ~1u) | tag, __float_as_uint(q.x),
           __float_as_uint(t.s[0][2] + t.s[1][2]), __float_as_uint(q.y));
}
struct RowNorm { float m0, rs0, m1, rs1; };
__device__ __forceinline__ RowNorm row_norm(float s0, float q0, float s1, float q1, float scale) {
  RowNorm n;
  n.m0 = s0 * (1.f / DM); n.m1 = s1 * (1.f / DM);
  n.rs0 = scale * rsqrt_hw(fmaxf(fmaf(-n.m0, n.m0, q0 * (1.f / DM)), 0.f) + LN_EPS);
  n.rs1 = scale * rsqrt_hw(fmaxf(fmaf(-n.m1, n.m1, q1 * (1.f / DM)), 0.f) + LN_EPS);
  return n;
}
__device__ __forceinline__ RowNorm stat_finish(const Scratch* sc, uint32_t (&st)[4], uint32_t tag, float scale) {
  uint32_t spin = 0;
  while (__builtin_expect(stale(st[0] ^ tag), 0) && ++spin < SPIN_LIMIT) stat_fetch(sc, st);
  float f[4];
#pragma unroll
  for (int i = 0; i < 4; i++) {
    f[i] = __uint_as_float(st[i]);
    f[i] += __shfl_xor_sync(0xffffffffu, f[i], 1);
    f[i] += __shfl_xor_sync(0xffffffffu, f[i], 2);
  }
  return row_norm(f[0], f[1], f[2], f[3], scale);
}
__device__ __forceinline__ void mean_frag(uint32_t (&mu)[4], const RowNorm& n, bool sel) {
  const float a = sel ? -n.m0 : 0.f, c = sel ? -n.m1 : 0.f;
  mu[0] = pack2(a, a); mu[1] = pack2(c, c);
  const float al = a - bf_lo(mu[0]), cl = c - bf_lo(mu[1]);
  mu[2] = pack2(al, al); mu[3] = pack2(cl, cl);
  pin(mu);
}
__device__ __forceinline__ void centre(uint32_t (&a)[16], uint32_t m0, uint32_t m1) {
#pragma unroll
  for (int i = 0; i < 16; i++) asm("sub.rn.bf16x2 %0, %0, %1;" : "+r"(a[i]) : "r"((i & 1) ? m1 : m0));
  pin(a);
}
__device__ __forceinline__ void scale_pack(const float (&d)[32], uint32_t (&a)[16], float rs0, float rs1) {
#pragma unroll
  for (int i = 0; i < 16; i++) { const float rs = (i & 1) ? rs1 : rs0; a[i] = pack2(d[2 * i] * rs, d[2 * i + 1] * rs); }
}
template <int S> __device__ __forceinline__ void silu_seg(float (&acc)[4][32], float (&tn)[2][4], uint32_t (&H)[4][16], float rs0, float rs1) {
  if (S >= 2) {
    const float* h = &acc[(S - 2) >> 3][4 * ((S - 2) & 7)];
    const float* v = tn[S & 1];
    uint32_t* o = &H[(S - 2) >> 3][2 * ((S - 2) & 7)];
    o[0] = pack2(fmaf(h[0], v[0], h[0]), fmaf(h[1], v[1], h[1]));
    o[1] = pack2(fmaf(h[2], v[2], h[2]), fmaf(h[3], v[3], h[3]));
    asm volatile("" : "+r"(o[0]), "+r"(o[1]));
  }
  if (S >= 1 && S <= 32) {
#pragma unroll
    for (int k = 0; k < 4; k++) tn[(S - 1) & 1][k] = tanh_hw(acc[((S - 1) >> 3) & 3][4 * ((S - 1) & 7) + k]);
  }
  if (S < 32) {
    float* h = &acc[(S >> 3) & 3][4 * (S & 7)];
    h[0] *= rs0; h[1] *= rs0; h[2] *= rs1; h[3] *= rs1;
    asm volatile("" : "+f"(h[0]), "+f"(h[1]), "+f"(h[2]), "+f"(h[3]));
  }
  SCHED();
}
template <int S0, int S1> __device__ __forceinline__ void silu_segs(float (&acc)[4][32], float (&tn)[2][4], uint32_t (&H)[4][16], float rs0, float rs1) {
  silu_seg<S0>(acc, tn, H, rs0, rs1);
  if constexpr (S0 + 1 < S1) silu_segs<S0 + 1, S1>(acc, tn, H, rs0, rs1);
}
template <int HALF> __device__ __forceinline__ void send_half(uint4* dst, const float (&d)[32], uint32_t tag) {
  uint32_t o[8];
#pragma unroll
  for (int i = 0; i < 8; i++) o[i] = pack2(d[16 * HALF + 2 * i], d[16 * HALF + 2 * i + 1]);
  o[0] = (o[0] & ~1u) | tag; o[4] = (o[4] & ~1u) | tag;
  pin(o);
  SCHED();
  st_vec(dst + HALF * 256, o[0], o[1], o[2], o[3]);
  st_vec(dst + HALF * 256 + 128, o[4], o[5], o[6], o[7]);
  SCHED();
}
__device__ __forceinline__ void send_residual(uint32_t (&a)[16], Scratch* sc, uint4* xp, uint32_t maddr, uint32_t tag, uint32_t& sent) {
  const uint32_t exact[4] = {a[0], a[4], a[8], a[12]};
  publish(xp + X_AG0, a, tag);
  if (TIMED) sent = clock_now();
  const uint32_t th = here(threadIdx.x);
  stat_publish(a, sc, th, tag);
  tile_store(here(maddr) + 3 * TILE_BYTES, a);
  stsm4(SM_BASE + SM_STG + 3 * TILE_BYTES + (th >> 5) * 2048 + (th & 7) * 128 + ((((th >> 2) & 6) ^ (th & 7)) << 4), exact);
}
template <int F, int N> __device__ __forceinline__ void proj_residual(uint32_t (&A)[4][16], Scratch* sc, uint4* xp, uint32_t maddr,
                                                                      uint32_t tag, uint32_t& sent) {
  float acc[32];
  if (TIMED && F == F_PW2) sent = clock_now();
  uint32_t st[4];
  acquire_n<F, N>();
  if (F == F_PW2) acquire_n<0, 5>();
  res_load(maddr, acc);
  mma_tile<false>(acc, A[0], LO(F));
  gather_first<2, X_AG1>(A, st, sc, xp, tag, sent);
  announce(sc, threadIdx.x == 0);
  mma_tile<false>(acc, A[1], HI(F));
  mma_tile<false>(acc, A[2], LO(F + 1));
  gather_rest<2, X_AG1>(A, xp, tag);
  PROF_MARK0(F == F_WO ? 11 : 16);
  mma_tile<false>(acc, A[3], HI(F + 1));
  WG_WAIT(0); pin(acc);
  pack_acc(acc, A[0]);
  send_residual(A[0], sc, xp, maddr, tag, sent);
}

__device__ __forceinline__ uint64_t ring_desc(uint32_t lo) { return (RING & ~uint64_t(0xFFFFFFFFu)) | lo; }
__device__ __forceinline__ void qk_tile(float (&S)[32], const uint32_t (&Q)[16], uint32_t dk) {
  wgmma64_reuse<0>(S, &Q[0], ring_desc(dk), blockIdx.y);
#pragma unroll
  for (int s = 1; s < 4; s++) wgmma64_acc<0>(S, &Q[4 * s], ring_desc(dk + s * 2));
}
__device__ __forceinline__ void qk_shift(float (&S)[32], const uint32_t (&nm)[4]) { wgmma64_acc<0>(S, nm, (uint64_t)((SM_BASE + SM_ONE) >> 4)); }
constexpr uint32_t RING_K = (uint32_t)RING, V_STEP = 1u - (1u << 16);
constexpr uint32_t RING_V = (SM_BASE >> 4) | (((SM_STG + 2 * TILE_BYTES) >> 4) << 16);
__device__ __forceinline__ void pv_tile(float (&O)[36], const uint32_t (&P)[16], uint32_t dv, uint32_t pad) {
#pragma unroll
  for (int s = 0; s < 4; s++) wgmma72_acc(O, &P[4 * s], ring_desc(dv + s * 128 * V_STEP + (s < 2 ? 0 : (s - 1) * pad)));
}
template <class F = Nothing>
__device__ __forceinline__ void attn_step(const float (&Sc)[32], float (&Sn)[32], uint32_t (&Pc)[16], uint32_t (&Pp)[16], float (&O)[36],
                                          const uint32_t (&Q)[16], const uint32_t (&nm)[4], uint32_t dk, uint32_t dv, bool next, bool prev, F late = F()) {
  if (next) {
    WG_FENCE();
    qk_tile(Sn, Q, dk);
    qk_shift(Sn, nm);
  }
  if (prev) {
    WG_FENCE();
    pv_tile(O, Pp, dv, 0);
  }
  WG_COMMIT();
  SCHED();
#pragma unroll
  for (int i = 0; i < 16; i++) {
    if (i == 0) late();
    Pc[i] = pack2(ex2_hw(Sc[2 * i]), ex2_hw(Sc[2 * i + 1]));
    asm volatile("" : "+r"(Pc[i]));
  }
  SCHED();
}
constexpr uint32_t SM_TAPS = SM_BASE + SM_STG + 2 * TILE_BYTES + 6144;
__device__ __forceinline__ void load_taps(uint32_t (&tap)[15], int dir) {
  const uint32_t src = SM_TAPS + 7 * 128 + (here(threadIdx.x) & 31) * 4;
#pragma unroll
  for (int k = 0; k < 15; k++) tap[k] = lds32(src + dir * (k - 7) * 128);
}
__device__ __forceinline__ void attention_exact(float (&O)[36], const uint32_t (&Q)[16], const Scratch* sc, int bh, int lane, int half) {
  const char* kb = (const char*)&sc->kv[bh][0][0][0];
  const char* vb = (const char*)&sc->kv[bh][1][0][0];
  const int g = lane >> 2, q = lane & 3;
  float m0 = -INFINITY, m1 = -INFINITY, l0 = 0.f, l1 = 0.f;
  float o[4][4] = {};
#pragma unroll 1
  for (int k0 = 0; k0 < T_SEQ; k0 += 8) {
    float s[4] = {0.f, 0.f, 0.f, 0.f};
#pragma unroll
    for (int c = 0; c < 8; c++) hmma8(s, &Q[2 * c], __ldcg((const uint32_t*)(kb + (k0 + g) * 128 + ((c ^ g) << 4) + q * 4)));
    float n0 = fmaxf(s[0], s[1]), n1 = fmaxf(s[2], s[3]);
    n0 = fmaxf(n0, __shfl_xor_sync(0xffffffffu, n0, 1)); n1 = fmaxf(n1, __shfl_xor_sync(0xffffffffu, n1, 1));
    n0 = fmaxf(m0, fmaxf(n0, __shfl_xor_sync(0xffffffffu, n0, 2))); n1 = fmaxf(m1, fmaxf(n1, __shfl_xor_sync(0xffffffffu, n1, 2)));
    const float a0 = ex2_hw(m0 - n0), a1 = ex2_hw(m1 - n1);
    m0 = n0; m1 = n1;
    const uint32_t pp[2] = {pack2(ex2_hw(s[0] - n0), ex2_hw(s[1] - n0)), pack2(ex2_hw(s[2] - n1), ex2_hw(s[3] - n1))};
    l0 = fmaf(l0, a0, bf_lo(pp[0]) + bf_hi(pp[0])); l1 = fmaf(l1, a1, bf_lo(pp[1]) + bf_hi(pp[1]));
#pragma unroll
    for (int j = 0; j < 4; j++) {
      const int c = 4 * half + j;
      const uint32_t v0 = __ldcg((const uint16_t*)(vb + (k0 + 2 * q) * 128 + ((c ^ (2 * q)) << 4) + g * 2));
      const uint32_t v1 = __ldcg((const uint16_t*)(vb + (k0 + 2 * q + 1) * 128 + ((c ^ (2 * q + 1)) << 4) + g * 2));
      o[j][0] *= a0; o[j][1] *= a0; o[j][2] *= a1; o[j][3] *= a1;
      hmma8(o[j], pp, v0 | (v1 << 16));
    }
  }
  l0 += __shfl_xor_sync(0xffffffffu, l0, 1); l1 += __shfl_xor_sync(0xffffffffu, l1, 1);
  O[32] = l0 + __shfl_xor_sync(0xffffffffu, l0, 2); O[34] = l1 + __shfl_xor_sync(0xffffffffu, l1, 2);
#pragma unroll
  for (int i = 0; i < 16; i++) O[i] = o[i >> 2][i & 3];
}

__device__ __forceinline__ uint32_t fill_entry(int f, int r) {
  int m, x = r, y, dx = 0;
  if (f < F_QKV || f >= 48) {
    const int i = f & 15;
    m = f < F_QKV ? M_FF1A : M_FF2A;
    if (i < 8) { x = 4 * r + ((0xE2u >> i) & 1) * 2; y = r ^ ((0xE790u >> (2 * i)) & 3); dx = 1; }
    else { m++; x = r ^ (((i >> 1) - 3) & 3); y = 4 * r + 2 * (i & 1); }
  } else if (f < F_KV) {
    const int i = f - F_QKV;
    m = M_QKV;
    if (i == 1 || i >= 5) { y = r ^ (i == 1 ? 0 : 2); }
    else { x = 4 + r; y = r ^ (i ? i - 1 : 0); dx = 4; }
  } else if (f >= F_PW1 && f < F_PW2) {
    m = M_PW1; y = r ^ (f - F_PW1); dx = 4;
  } else {
    m = f < F_PW1 ? M_WO : M_PW2; y = r ^ ((f & 1) * 2);
  }
  return m | (x << 4) | (y << 8) | (dx << 16);
}
__device__ __forceinline__ void tma_fill(uint32_t st, const CUtensorMap* map, uint32_t x, uint32_t y, uint32_t x2, uint32_t y2) {
  asm volatile("{\n.reg .pred p;\nelect.sync _|p, 0xffffffff;\n"
               "@p mbarrier.arrive.expect_tx.shared::cta.b64 _, [%1], 16384;\n"
               "@p cp.async.bulk.tensor.2d.shared::cluster.global.mbarrier::complete_tx::bytes [%0], [%2, {%3, %4}], [%1];\n"
               "@p cp.async.bulk.tensor.2d.shared::cluster.global.mbarrier::complete_tx::bytes [%0 + 8192], [%2, {%5, %6}], [%1];\n}"
               :: "r"(SM_BASE + st * STAGE_BYTES), "r"(SM_BASE + SM_FULL + st * 8), "l"(map), "r"(x), "r"(y), "r"(x2), "r"(y2) : "memory");
}
template <int F0, int N> __device__ __forceinline__ void weight_fills(const Params& p, uint32_t entry) {
  uint32_t st = F0 % NSTAGE, parity = ((F0 / NSTAGE) & 1) ^ 1, e = __shfl_sync(0xffffffffu, entry, 0);
#pragma unroll 1
  for (int i = 1; i <= N; i++) {
    const uint32_t x = (e << 2) & 0x3C0, y = (e >> 2) & 0x3FC0, dx = (e >> 16) << 6;
    const CUtensorMap* map = &p.map[e & 15];
    e = __shfl_sync(0xffffffffu, entry, i);
    mbar_wait(SM_BASE + SM_EMPTY + st * 8, parity);
    tma_fill(st, map, x, y, x + dx, dx ? y : y ^ 64);
    if (++st == NSTAGE) { st = 0; parity ^= 1; }
  }
}
template <int KIND, int J> __device__ __forceinline__ uint32_t kv_fill(const uint4* kv, uint32_t want) {
  constexpr uint32_t st = (J < 6 ? 4 * (J >> 1) : 0) + (J & 1) + 2 * KIND;
  mbar_wait(SM_BASE + SM_EMPTY + st * 8, J < 6);
  uint32_t have, spin = 0;
#pragma unroll 1
  do {
    asm volatile("ld.volatile.shared.u32 %0, [%1];" : "=r"(have) : "r"(SM_BASE + SM_KVRDY + KIND * 4) : "memory");
    have &= want;
  } while (!have && ++spin < (SPIN_LIMIT << 4));
  const uint32_t tile = (__ffs(KIND ? want : have) - 1) & 15;
  asm volatile("{\n.reg .pred p;\nelect.sync _|p, 0xffffffff;\n"
               "@p mbarrier.arrive.expect_tx.shared::cta.b64 _, [%1], 16384;\n"
               "@p cp.async.bulk.shared::cluster.global.mbarrier::complete_tx::bytes [%0], [%2], 16384, [%1];\n}"
               :: "r"(SM_BASE + st * STAGE_BYTES), "r"(SM_BASE + SM_FULL + st * 8), "l"(kv + (KIND * 16 + tile) * 512) : "memory");
  PROF_AT(256 + 512 + (10 + KIND * 8 + J) * 4);
  return 1u << tile;
}
template <int J> __device__ __forceinline__ void kv_fills(const uint4* kv, uint32_t todo, uint32_t b1, uint32_t b2) {
  if constexpr (J >= 2) kv_fill<1, J - 2>(kv, b2);
  uint32_t b0 = 0;
  if constexpr (J < 8) b0 = kv_fill<0, J>(kv, J == 7 ? 0x4000u : todo);
  if constexpr (J < 9) kv_fills<J + 1>(kv, todo & ~b0, b0, b1);
}
__device__ __forceinline__ void reset_mailboxes(Scratch* sc, int half, int lane, uint32_t t_start) {
  while (clock_now() - t_start < TC) {}
#pragma unroll 1
  for (int i = half * 8; i < half * 9 + 8; i++) {
    const uint32_t t0 = clock_now();
    uint4* dst = &sc->x[blockIdx.x ^ (i < 12 ? (i >> 2) + 1 : 0)][i * 128 + lane];
#pragma unroll
    for (int k = 0; k < 4; k++) st_vec(dst + 32 * k, 0u, 0u, 0u, 0u);
    while (clock_now() - t0 < CLR_PACE) {}
  }
  bar_arrive(BAR_RST, 192);
  PROF_AT(256 + 512 + 28 * 4);
  asm volatile("fence.acq_rel.gpu;" ::: "memory");
  __syncwarp();
  announce<1>(sc, lane == 0);
  PROF_AT(256 + 512 + 2 * 4);
}
__device__ __forceinline__ void l2_prefetch(const void* p, uint32_t total, int b) {
  const uint32_t part = total / NCTA;
  asm volatile("cp.async.bulk.prefetch.L2.global [%0], %1;" :: "l"((const char*)p + (size_t)b * part), "r"(part) : "memory");
}

__global__ void __launch_bounds__(384, 1) conformer_kernel(Scratch* __restrict__ sc, __nv_bfloat16* __restrict__ out,
                                                           const __nv_bfloat16* __restrict__ dw, const __nv_bfloat16* __restrict__ xin,
                                                           const __nv_bfloat16* __restrict__ w_ff1a, const __grid_constant__ Params p) {
  extern __shared__ __align__(1024) uint8_t smem[];
  const int tid = threadIdx.x, lane = tid & 31;
  const uint32_t t_start = clock_now();
  const int b = blockIdx.x, r = b & 3, batch = b >> 6, t = (b >> 2) & 15;
  if ((uint32_t)__cvta_generic_to_shared(smem) != SM_BASE) return;
  PROF_AT(256 + (tid >> 7) * 256);
  PROF_TIME(30);
  const uint32_t crow = ((tid >> 1) & 48) + (lane >> 3);
  const uint32_t cdst = SM_BASE + crow * 128 + (((lane & 7) ^ (lane >> 3)) << 4);
  if (tid < 128) {
    const uint32_t g0 = batch * T_SEQ + t * 64 + crow, o = r * 128 + (lane & 7) * 16;
    const uint32_t lo = min(g0, 2 * T_SEQ - 5) * 512 + o, hi = min(g0 + 8, 2 * T_SEQ - 5) * 512 + o;
#pragma unroll
    for (int c = 0; c < 4; c++) {
#pragma unroll
      for (int i = 0; i < 4; i++)
        cp_async16((cdst ^ ((i & 1) << 6)) + SM_STG + (3 - c) * TILE_BYTES + i * 512, (const char*)xin + (((i & 2) ? hi : lo) ^ (c << 7)) + (i & 1) * 2048);
      asm volatile("cp.async.commit_group;" ::: "memory");
    }
  } else if (tid < 256) {
    const char* src = (const char*)w_ff1a + (64 * r + crow) * 2048 + r * 512 + (lane & 7) * 16;
#pragma unroll
    for (int c = 0; c < 4; c++) {
#pragma unroll
      for (int i = 0; i < 4; i++) cp_async16((cdst ^ ((i & 1) << 6)) + c * TILE_BYTES + i * 512, src + i * 8192 + c * 128);
      asm volatile("cp.async.commit_group;" ::: "memory");
    }
  }
  const int cw = __shfl_sync(0xffffffffu, tid >> 5, 0), wg = cw >> 2, w = cw & 3;

  if (wg == 2) {
    asm volatile("setmaxnreg.dec.sync.aligned.u32 40;");
    if (cw == 8) {
      if (lane == 0) {
        asm volatile("prefetch.tensormap [%0];" :: "l"(&p.map[M_FF1A]) : "memory");
#pragma unroll
        for (int i = 0; i < NSTAGE; i++) mbar_init(SM_BASE + SM_FULL + i * 8, 1);
        fence_async_smem();
      }
      __syncwarp();
      bar_arrive(0, 320);
      while (clock_now() - t_start < TF) {}
      PROF_MARK(9);
#pragma unroll
      for (int f = 2; f < 8; f++) {
        const uint32_t x = 256 * r + ((0xE2u >> f) & 1) * 128, y = (r ^ ((0xE790u >> (2 * f)) & 3)) * 64;
        tma_fill(f, &p.map[M_FF1A], x, y, x + 64, y);
      }
      PROF_MARK(1);
      uint32_t entry[2];
#pragma unroll 1
      for (int i = 0; i < 2; i++) { entry[1] = fill_entry(8 + i * 32 + lane, r); if (i == 0) entry[0] = entry[1]; }
      bar_sync(BAR_INIT, 64);
      weight_fills<8, F_KV - 8>(p, entry[0]);
      kv_fills<0>(sc->kv[batch * 4 + r][0][0], 0x1555u, 0u, 0u);
      weight_fills<F_WO, F_TOTAL - F_WO>(p, entry[1]);
    } else if (here(cw) != 11) {
      const int kind = w - 1;
      const uint32_t prev = launch_index(sc);
      if (kind == 0) {
        if (lane == 0) {
#pragma unroll
            for (int i = 0; i < NSTAGE; i++) mbar_init(SM_BASE + SM_EMPTY + i * 8, 4);
          sts64(SM_BASE + SM_KVRDY, 0u, 0u);
        }
        __syncwarp();
        bar_arrive(0, 320);
        bar_arrive(BAR_INIT, 64);
        if (lane == 0) {
          const uint32_t t0 = t_start;
          while (clock_now() - t0 < PF0) {}
          while (clock_now() - t0 < PF1) {}
          asm volatile("prefetch.tensormap [%0];" :: "l"(&p.map[M_FF1B]) : "memory");
          l2_prefetch(p.w_ff1b, 1024 * 256 * 2, b);
          while (clock_now() - t0 < PF2) {}
          l2_prefetch(p.w_qkv, 256 * 768 * 2, b);
          l2_prefetch(p.w_pw1, 256 * 512 * 2, b);
          l2_prefetch(p.w_ff2a, 256 * 1024 * 2, b);
          while (clock_now() - t0 < PF3) {}
          if (b < 15) l2_prefetch(dw, 512 * NCTA, b);
          l2_prefetch(p.w_o, 256 * 256 * 2, b);
          l2_prefetch(p.w_pw2, 256 * 256 * 2, b);
          l2_prefetch(p.w_ff2b, 1024 * 256 * 2, b);
#pragma unroll
          for (int i = M_QKV; i < M_COUNT; i++) asm volatile("prefetch.tensormap [%0];" :: "l"(&p.map[i]) : "memory");
        }
        __syncwarp();
      } else {
        reset_mailboxes(sc, 1, lane, t_start);
      }
      const uint32_t* flag = sc->flag[batch * 4 + r][kind * 16 + (lane & 15)];
      uint32_t spin = 0, ready;
#pragma unroll 1
      do {
        uint32_t v;
        asm volatile("ld.relaxed.gpu.global.u32 %0, [%1];" : "=r"(v) : "l"(flag) : "memory");
        ready = __ballot_sync(0xffffffffu, v - 1 == prev);
        asm volatile("st.volatile.shared.u32 [%0], %1;" :: "r"(SM_BASE + SM_KVRDY + kind * 4), "r"(ready & (ready >> 1)) : "memory");
        if (spin == 0) {
          if (kind == 0) bar_sync(BAR_K, 160); else bar_sync(BAR_V, 160);
          if (lane == 0) {
            PROF_MARK(4 + kind * 2);
            asm volatile("cp.async.bulk.global.shared::cta.bulk_group [%0], [%1], %2;"
                         :: "l"(sc->kv[batch * 4 + r][kind][t]), "r"(SM_BASE + SM_STG + kind * TILE_BYTES), "r"(TILE_BYTES) : "memory");
            asm volatile("cp.async.bulk.commit_group;\ncp.async.bulk.wait_group 0;" ::: "memory");
            asm volatile("st.relaxed.gpu.global.u32 [%0], %1;" :: "l"(sc->flag[batch * 4 + r][kind * 16 + t]), "r"(prev + 1) : "memory");
            PROF_MARK(5 + kind * 2);
          }
          __syncwarp();
        }
      } while (ready != 0xffffffffu && ++spin < SPIN_LIMIT);
      if (kind) {
        bar_sync(BAR_TAP, 64);
#pragma unroll 5
        for (int k = 0; k < 15; k++) {
          uint32_t v = __ldg((const uint32_t*)(dw + k * DM + 64 * r) + lane);
          asm("mul.rn.bf16x2 %0, %0, %1;" : "+r"(v) : "r"(0x3F003F00u));
          sts32(SM_TAPS + k * 128 + lane * 4, v);
        }
        bar_arrive(BAR_MERGE, 288);
      }
    } else {
      const uint32_t* watch = sc->step[(b & ~3) + (lane & 3)];
      uint32_t seen;
      asm volatile("ld.relaxed.gpu.global.u32 %0, [%1];" : "=r"(seen) : "l"(watch) : "memory");
      reset_mailboxes(sc, 0, lane, t_start);
      uint32_t want = seen & ~15u;
#pragma unroll 1
      for (int k = 0; k < (TIMED ? 1 : 8); k++) {
        want += 2;
        uint32_t spin = 0;
#pragma unroll 1
        while (__any_sync(0xffffffffu, (int)(seen - want) < 0) && ++spin < SPIN_LIMIT)
          asm volatile("ld.relaxed.gpu.global.u32 %0, [%1];" : "=r"(seen) : "l"(watch) : "memory");
        bar_arrive(BAR_GO, 160);
        PROF_MARK(32 + k);
      }
    }
  } else {
    asm volatile("setmaxnreg.inc.sync.aligned.u32 232;");
    const int q = lane & 3, th = tid & 127;
    constexpr uint32_t stg = SM_BASE + SM_STG;
    const uint32_t mrow = 16 * w + (lane & 15);
    const uint32_t maddr = stg + mrow * 128 + (((lane >> 4) ^ (lane & 7)) << 4);
    const uint32_t qslot = stg + 2 * TILE_BYTES + w * 2048 + lane * 16;
    uint4* const xp = &sc->x[b][th];
    const int nvalid = T_SEQ - t * 64, row0 = 16 * w + (lane >> 2);

    uint32_t A[4][16];
    uint32_t st[4], sent = 0;
    bar_sync(0, 320);
    if (wg == 0) {
      RowAcc ra = {};
      cp_async_wait(0);
      __syncwarp();
      PROF_MARK0(45);
#pragma unroll
      for (int c = 0; c < 4; c++) tile_load(maddr + (3 - c) * TILE_BYTES, A[c]);
      row_sums(ra, A[0]); row_gram(ra, A[0]); row_sums(ra, A[1]); row_gram(ra, A[1]);
      pin(ra.s[0]); pin(ra.s[1]); pin(ra.u[0]); pin(ra.u[1]); pin(ra.v[0]); pin(ra.v[1]);
      SCHED();
      row_sums(ra, A[2]); row_sums(ra, A[3]); row_gram(ra, A[2]); row_gram(ra, A[3]);
      const float m0 = (ra.s[0][0] + ra.s[1][0]) * (1.f / DM), m1 = (ra.s[0][2] + ra.s[1][2]) * (1.f / DM);
      st[0] = pack2(m0, m0); st[1] = pack2(m1, m1);
      centre(A[0], st[0], st[1]);
      const float2 sq = row_squares(ra, lane & 4);
      st[2] = __float_as_uint(fmaf(-m0, m0, sq.x * (1.f / DM))); st[3] = __float_as_uint(fmaf(-m1, m1, sq.y * (1.f / DM)));
    } else {
      if (th < 112) sts128(SM_BASE + SM_CS + th * 16, 0, 0, 0, 0);
      sts32(SM_BASE + SM_EYE + th * 4, th >= 96 ? 0x3F803F80u : ((th & 32) == 0 && (th & 3) == ((th >> 3) & 3)) ? (0x3F00u << ((th & 4) * 4)) : 0u);
#pragma unroll
      for (int i = 0; i < 2; i++) {
        cp_async_wait(2 - 2 * i);
        fence_async_smem();
        bar_sync(BAR_WG1, 128);
        if (th == 0) mbar_arrive(SM_BASE + SM_FULL + i * 8);
      }
      PROF_MARK(6);
      const uint32_t tag = ~launch_index(sc) & 1;
      mbar_wait(SM_BASE + SM_FULL + 4 * 8, 0);
      PROF_MARK(5);
      if (b < 72) {
        const int strip = b >> 1;
        const __nv_bfloat16* wp; int ld;
        if (strip < 12) { wp = p.w_qkv + strip * 64; ld = 768; }
        else if (strip < 20) { wp = p.w_pw1 + (strip - 12) * 64; ld = 512; }
        else { wp = p.w_ff2a + (strip - 20) * 64; ld = 1024; }
        const uint4* src = (const uint4*)(wp + (size_t)((b & 1) * 128 + (th >> 3)) * ld) + (th & 7);
        uint4 v[8];
#pragma unroll
        for (int i = 0; i < 8; i++) v[i] = __ldg(src + i * 2 * ld);
        mbar_wait(SM_BASE + SM_EMPTY + CS_AFTER * 8, 0);
        float c[8] = {0.f, 0.f, 0.f, 0.f, 0.f, 0.f, 0.f, 0.f};
#pragma unroll
        for (int i = 0; i < 8; i++) {
          c[0] += bf_lo(v[i].x); c[1] += bf_hi(v[i].x); c[2] += bf_lo(v[i].y); c[3] += bf_hi(v[i].y);
          c[4] += bf_lo(v[i].z); c[5] += bf_hi(v[i].z); c[6] += bf_lo(v[i].w); c[7] += bf_hi(v[i].w);
        }
#pragma unroll 1
        for (int m = 8; m <= 16; m <<= 1)
#pragma unroll
          for (int k = 0; k < 8; k++) c[k] += __shfl_xor_sync(0xffffffffu, c[k], m);
        if (lane < 8) {
          const uint32_t a = SM_BASE + SM_CS + w * 256 + lane * 32;
          sts128(a, __float_as_uint(c[0]), __float_as_uint(c[1]), __float_as_uint(c[2]), __float_as_uint(c[3]));
          sts128(a + 16, __float_as_uint(c[4]), __float_as_uint(c[5]), __float_as_uint(c[6]), __float_as_uint(c[7]));
        }
        bar_sync(BAR_WG1, 128);
        if (th < 16) {
          float o[4] = {0.f, 0.f, 0.f, 0.f};
#pragma unroll
          for (int k = 0; k < 4; k++) {
            uint32_t e[4];
            lds128(SM_BASE + SM_CS + k * 256 + th * 16, e[0], e[1], e[2], e[3]);
#pragma unroll
            for (int i = 0; i < 4; i++) o[i] += __uint_as_float(e[i]);
          }
          st_vec(&sc->cs[b & 1][strip * 16 + th], (__float_as_uint(o[0]) & ~1u) | tag, __float_as_uint(o[1]), __float_as_uint(o[2]), __float_as_uint(o[3]));
        }
      } else {
        mbar_wait(SM_BASE + SM_EMPTY + CS_AFTER * 8, 0);
      }
      bar_sync(BAR_WG1, 128);
      PROF_MARK(2);
      if (th < 72) {
        const int j = th >> 3, i = (th & 7) * 2;
        int src;
        if (j < CS_PW1) src = 320 + 64 * r + 16 * j;
        else if (j < CS_QKV) src = 192 + (j - CS_PW1) * 64 + 16 * r;
        else src = ((j - CS_QKV + 1) % 3) * 64 + 16 * r;
        uint32_t e[16], hi[4], lo[4], spin = 0;
#pragma unroll 1
        do {
#pragma unroll
          for (int k = 0; k < 4; k++) ld_vec(&sc->cs[k >> 1][src + i + (k & 1)], e[4 * k], e[4 * k + 1], e[4 * k + 2], e[4 * k + 3]);
        } while ((miss(e, tag) & 1u) && ++spin < SPIN_LIMIT);
#pragma unroll
        for (int k = 0; k < 4; k++) e[4 * k] &= ~1u;
#pragma unroll
        for (int k = 0; k < 4; k++) {
          const float c0 = __uint_as_float(e[2 * k]) + __uint_as_float(e[8 + 2 * k]), c1 = __uint_as_float(e[2 * k + 1]) + __uint_as_float(e[9 + 2 * k]);
          hi[k] = pack2(c0, c1);
          lo[k] = pack2(c0 - bf_lo(hi[k]), c1 - bf_hi(hi[k]));
        }
        const uint32_t a = SM_BASE + SM_CS + j * 256 + i * 8;
        sts128(a ^ ((a >> 3) & 0x70), hi[0], hi[1], hi[2], hi[3]);
        sts128((a + 128) ^ (((a + 128) >> 3) & 0x70), lo[0], lo[1], lo[2], lo[3]);
      }
      fence_async_smem();
      PROF_MARK(4);
      bar_arrive(BAR_CS, 256);
    }

#pragma unroll 1
    for (uint32_t pass = 0; pass < 2; pass++) {
      uint32_t Q[16], shift;
      if (wg == 0) {
        float acc[4][32];
        uint32_t H[4][16];
        if (!pass) { PROF_MARK(47); ACQUIRE(0); }
        mma_tile<true>(acc[0], A[0], LO(0)); mma_tile<true>(acc[1], A[0], HI(0));
        if (pass) {
          gather_first<1, X_AG0>(A, st, sc, xp, 1, sent, [&] { mma_tile<true>(acc[2], A[0], LO(1)); mma_tile<true>(acc[3], A[0], HI(1)); });
        } else {
          ACQUIRE(1);
          mma_tile<true>(acc[2], A[0], LO(1)); mma_tile<true>(acc[3], A[0], HI(1));
          centre(A[1], st[0], st[1]);
          acquire_n<2, 3>();
        }
        mma_tile<false>(acc[0], A[1], LO(2)); mma_tile<false>(acc[1], A[1], HI(2));
        if (pass) {
          gather_rest<1, X_AG0>(A, xp, 1);
          RELEASE(F_WO - 2 + NREL, F_PW2 + 1);
        } else {
          centre(A[2], st[0], st[1]); centre(A[3], st[0], st[1]);
        }
        PROF_MARK2(2, 18);
        mma_tile<false>(acc[0], A[2], LO(3)); mma_tile<false>(acc[0], A[3], LO(4));
        WG_WAIT(4);
        RELEASE(0, 1);
        uint32_t mu[4] = {0u, 0u, 0u, 0u};
        float rs0, rs1, tn[2][4];
        if (pass) {
          const RowNorm n = stat_finish(sc, st, 1, 0.5f);
          rs0 = n.rs0; rs1 = n.rs1;
          mean_frag(mu, n, q == 0);
        } else {
          const int src = (lane & 28) | (lane >> 3);
          rs0 = 0.5f * rsqrt_hw(fmaxf(__uint_as_float(__shfl_sync(0xffffffffu, st[2], src)), 0.f) + LN_EPS);
          rs1 = 0.5f * rsqrt_hw(fmaxf(__uint_as_float(__shfl_sync(0xffffffffu, st[3], src)), 0.f) + LN_EPS);
        }
        pin(mu);
        mma_fold<2 * CS_FF2>(acc[0], mu);
        mma_tile<false>(acc[1], A[2], HI(3));
#define SEGS(a, b) silu_segs<a, b>(acc, tn, H, rs0, rs1)
        WG_WAIT(1); pin(acc[0]);
        SEGS(0, 1);
        mma_tile_fold<2 * CS_FF2 + 2>(acc[1], A[3], HI(4), mu);
        SEGS(1, 3);
        uint32_t ok = probe_n<5, 1>();
        SEGS(3, 4);
        settle_n<5, 1>(ok);
        mma_tile<false>(acc[2], A[1], LO(5));
        SEGS(4, 5);
        ok = probe_n<6, 1>();
        SEGS(5, 6);
        settle_n<6, 1>(ok);
        mma_tile<false>(acc[2], A[2], LO(6));
        SEGS(6, 8);
        WG_WAIT(2); pin(acc[1]);
        RELEASE(2, 4);
        ok = probe_n<7, 1>();
        SEGS(8, 9);
        settle_n<7, 1>(ok);
        mma_tile_fold<2 * CS_FF2 + 4>(acc[2], A[3], LO(7), mu);
        SEGS(9, 12);
        mma_tile<false>(acc[3], A[1], HI(5));
        SEGS(12, 14);
        mma_tile<false>(acc[3], A[2], HI(6));
        SEGS(14, 16);
        WG_WAIT(2); pin(acc[2]);
        SEGS(16, 17);
        mma_tile_fold<2 * CS_FF2 + 6>(acc[3], A[3], HI(7), mu);
        SEGS(17, 19);
        ok = probe_n<8, 2>();
        SEGS(19, 20);
        settle_n<8, 2>(ok);
        mma_tile_reuse(acc[1], H[0], LO(8));
        SEGS(20, 22);
        mma_tile<false>(acc[1], H[1], HI(8));
        SEGS(22, 24);
        WG_WAIT(2); pin(acc[3]);
        RELEASE(5, 7);
        SEGS(24, 26);
        mma_tile<false>(acc[1], H[2], LO(9));
        SEGS(26, 27);
        ok = probe_n<10, 2>();
        SEGS(27, 28);
        settle_n<10, 2>(ok);
        mma_tile_reuse(acc[2], H[0], LO(10));
        SEGS(28, 31);
        mma_tile<false>(acc[2], H[1], HI(10));
        SEGS(31, 34);
#undef SEGS
        PROF_MARK2(3, 19);
        const uint32_t rtag = here(pass ^ 1);
        const uint4* rs_in = xp + X_RS;
        mma_tile<false>(acc[1], H[3], HI(9));
        mma_tile<false>(acc[2], H[2], LO(11));
        ok = probe_n<12, 2>();
        uint4* rs_out = peer<1>(xp) + X_RS;
        mma_tile<false>(acc[2], H[3], HI(11));
        settle_n<12, 2>(ok);
        if (!pass) bar_sync(BAR_RST, 192);
        WG_WAIT(2); pin(acc[1]);
        RELEASE(8, 9);
        send_half<0>(rs_out, acc[1], rtag);
        mma_tile_reuse(acc[3], H[0], LO(12));
        SCHED();
        send_half<1>(rs_out, acc[1], rtag);
        mma_tile<false>(acc[3], H[1], HI(12));
        rs_out = peer<2>(xp) + X_RS + 512;
        WG_WAIT(2); pin(acc[2]);
        send_half<0>(rs_out, acc[2], rtag);
        mma_tile<false>(acc[3], H[2], LO(13));
        SCHED();
        ok = probe_n<14, 2>();
        send_half<1>(rs_out, acc[2], rtag);
        mma_tile<false>(acc[3], H[3], HI(13));
        settle_n<14, 2>(ok);
        mma_tile_reuse(acc[1], H[0], LO(14));
        rs_out = peer<3>(xp) + X_RS + 1024;
        if (!pass) bar_sync(BAR_GO, 160);
        announce(sc, tid == 0);
        fetch(rs_in, A[1]);
        SCHED();
        mma_tile<false>(acc[1], H[1], HI(14));
        WG_WAIT(2); pin(acc[3]);
        send_half<0>(rs_out, acc[3], rtag);
        send_half<1>(rs_out, acc[3], rtag);
        if (TIMED) sent = clock_now();
        mma_tile<false>(acc[1], H[2], LO(15)); mma_tile<false>(acc[1], H[3], HI(15));
        SCHED();
        fetch(rs_in + 512, A[2]);
        SCHED();
        res_load(maddr, acc[2]);
        if (TIMED) { while (clock_now() - sent < RD) {} } else bar_sync(BAR_GO, 160);
        fetch(rs_in + 1024, A[3]);
        if (!pass) acquire_n<F_QKV, 3>();
        {
          uint32_t spin = 0;
          while (__builtin_expect(stale(miss(A[1], rtag) | miss(A[2], rtag) | miss(A[3], rtag)), 0) && ++spin < SPIN_LIMIT) {
            if (stale(miss(A[1], rtag) | miss(A[2], rtag))) { fetch(rs_in, A[1]); fetch(rs_in + 512, A[2]); }
            fetch(rs_in + 1024, A[3]);
          }
        }
        announce(sc, tid == 0 && !pass);
        mma_add_half(acc[2], A[1]);
        mma_add_half(acc[2], A[2]);
        mma_add_half(acc[2], A[3]);
        PROF_MARK2(4, 20);
        WG_WAIT(0); pin(acc[2]); pin(acc[1]);
#pragma unroll
        for (int i = 0; i < 16; i++) A[0][i] = pack2(fmaf(acc[1][2 * i], 0.5f, acc[2][2 * i]), fmaf(acc[1][2 * i + 1], 0.5f, acc[2][2 * i + 1]));
        if (pass) {
          PROF_MARK(21);
          stat_publish(A[0], sc, here(th), 0);
          stat_fetch(sc, st);
          const RowNorm fn = stat_finish(sc, st, 0, 1.f);
          const float nm0 = -fn.m0 * fn.rs0, nm1 = -fn.m1 * fn.rs1;
#pragma unroll
          for (int i = 0; i < 16; i++) {
            const float rs = (i & 1) ? fn.rs1 : fn.rs0, nm = (i & 1) ? nm1 : nm0;
            A[0][i] = pack2(fmaf(bf_lo(A[0][i]), rs, nm), fmaf(bf_hi(A[0][i]), rs, nm));
          }
          tile_store(here(maddr), A[0]);
          __syncwarp();
          const int row = 16 * w + (lane >> 3);
          uint4* dst = (uint4*)(out + ((size_t)batch * T_SEQ + t * 64 + row) * DM + 64 * r) + (lane & 7);
          const uint32_t src = stg + row * 128 + (((lane & 7) ^ (lane >> 3)) << 4);
#pragma unroll
          for (int i = 0; i < 4; i++) {
            uint4 v;
            lds128((src ^ ((i & 1) << 6)) + i * 512, v.x, v.y, v.z, v.w);
            if (row + 4 * i < nvalid) dst[i * 4 * (DM / 8)] = v;
          }
          PROF_MARK(22);
          PROF_TIME(31);
          break;
        }
        send_residual(A[0], sc, xp, maddr, 1, sent);
        PROF_MARK(5);
        mma_tile<true>(acc[0], A[0], LO(F_QKV)); mma_tile<true>(acc[1], A[0], HI(F_QKV));
        gather_first<1, X_AG0>(A, st, sc, xp, 1, sent, [&] { mma_tile<true>(acc[2], A[0], LO(F_QKV + 1)); });
        mma_tile<false>(acc[0], A[1], LO(F_QKV + 2)); mma_tile<false>(acc[1], A[1], HI(F_QKV + 2));
        acquire_n<F_QKV + 3, 3>();
        bar_sync(BAR_CS, 256);
        gather_rest<1, X_AG0>(A, xp, 1);
        PROF_MARK(6);
        mma_tile<false>(acc[0], A[2], LO(F_QKV + 3)); mma_tile<false>(acc[0], A[3], LO(F_QKV + 4));
        SCHED();
        {
          const RowNorm n = stat_finish(sc, st, 1, 1.f);
          rs0 = row0 < nvalid ? n.rs0 : 0.f; rs1 = row0 + 8 < nvalid ? n.rs1 : 0.f;
          mean_frag(mu, n, q == 3);
        }
        mma_fold<2 * CS_QKV - 6>(acc[0], mu);
        RELEASE(10, 15);
        WG_WAIT(0); pin(acc[0]);
        scale_pack(acc[0], A[0], rs0, rs1);
        tile_store(here(maddr), A[0]);
        SCHED();
        mma_tile<false>(acc[1], A[2], HI(F_QKV + 3));
        fence_async_smem();
        bar_arrive(BAR_K, 160);
        mma_tile_fold<2 * CS_QKV - 4>(acc[1], A[3], HI(F_QKV + 4), mu);
        mma_tile<false>(acc[2], A[1], HI(F_QKV + 1)); mma_tile<false>(acc[2], A[2], LO(F_QKV + 5));
        WG_WAIT(2); pin(acc[1]);
        scale_pack(acc[1], Q, rs0, rs1);
        tile_store(here(maddr) + TILE_BYTES, Q);
        fence_async_smem();
        bar_arrive(BAR_V, 160);
        mma_tile_fold<2 * CS_QKV - 2>(acc[2], A[3], HI(F_QKV + 5), mu);
        WG_WAIT(0); pin(acc[2]);
        scale_pack(acc[2], Q, rs0 * SM_SCALE_LOG2, rs1 * SM_SCALE_LOG2);
        frag_store(here(qslot), Q);
        {
          uint32_t d[4] = {0u, 0u, 0u, 0u};
#pragma unroll
          for (int i = 0; i < 16; i++) asm("fma.rn.bf16x2 %0, %1, %2, %0;" : "+r"(d[i & 3]) : "r"(Q[i]), "r"(A[0][i]));
          float s0 = (bf_lo(d[0]) + bf_hi(d[0])) + (bf_lo(d[2]) + bf_hi(d[2])), s1 = (bf_lo(d[1]) + bf_hi(d[1])) + (bf_lo(d[3]) + bf_hi(d[3]));
          shift = pack2(-s0, -s1);
          sts32(SM_BASE + SM_CS + 2 * CS_QKV * 128 + here(th) * 4, shift);
        }
        bar_arrive(BAR_Q, 256);
        RELEASE(F_QKV, F_QKV + 5);
      } else {
        bar_sync(BAR_Q, 256);
#pragma unroll
        for (int s = 0; s < 4; s++) lds128(qslot + s * 512, Q[4 * s], Q[4 * s + 1], Q[4 * s + 2], Q[4 * s + 3]);
        shift = lds32(SM_BASE + SM_CS + 2 * CS_QKV * 128 + th * 4);
        if (w < 2) {
          const uint32_t v = w ? 0u : 0x3F803F80u;
#pragma unroll
          for (int s = 0; s < 4; s++) sts128(qslot + s * 512, v, v, v, v);
          fence_async_smem();
        }
        if (w == 3) bar_arrive(BAR_TAP, 64);
      }
      PROF_MARK(7);

      float O[36];
      {
        float S[2][32];
        uint32_t P[2][16], nm[4] = {shift & 0xFFFFu, shift >> 16, 0u, 0u};
        pin(Q); pin(nm);
        uint32_t sk = wg, sv = F_SPARE % NSTAGE + wg;
        mbar_wait(SM_BASE + SM_FULL + sv * 8, 1);
        if (wg == 1) bar_sync(BAR_ATT, 256);
        mbar_wait(SM_BASE + SM_FULL + sk * 8, 0);
        PROF_MARK(8);
        WG_FENCE();
        wgmma64_set<0>(S[0], nm, (uint64_t)((SM_BASE + SM_ONE) >> 4));
#pragma unroll
        for (int s = 0; s < 4; s++) wgmma64_acc<0>(S[0], &Q[4 * s], ring_desc(RING_K + sk * 1024 + s * 2));
        WG_COMMIT();
        SCHED();
#pragma unroll
        for (int i = 0; i < 36; i++) O[i] = 0.f;
#pragma unroll
        for (int i = 0; i < 32; i++) S[1][i] = 0.f;
#pragma unroll
        for (int i = 0; i < 16; i++) P[1][i] = 0u;
        pin(O); pin(S[1]); pin(P[1]);
        SCHED();
        WG_WAIT(0); pin(S[0]);
        if (wg == 0) bar_sync(BAR_ATT, 256);
#pragma unroll 1
        for (int it = 0; it < 4; it++) {
          const uint32_t sn = it >= 2 ? wg : sk + 4;
          uint32_t ok = 1;
          attn_step(S[0], S[1], P[0], P[1], O, Q, nm, RING_K + sk * 1024 + 512, RING_V + (sv * 1024 + 512) * V_STEP, true, it > 0, [&] {
            mbar_probe(ok, SM_BASE + SM_FULL + sn * 8, it >= 2);
            mbar_probe(ok, SM_BASE + SM_FULL + (sk + 2) * 8, it == 3);
          });
          PROF_MARK(24 + it * 3);
          if (__builtin_expect(!ok, 0)) {
            mbar_wait(SM_BASE + SM_FULL + sn * 8, it >= 2);
            mbar_wait(SM_BASE + SM_FULL + (sk + 2) * 8, it == 3);
          }
          WG_WAIT(0); pin(O); pin(S[1]); pin(P[1]);
          asm volatile("{\n.reg .pred p;\nsetp.eq.u32 p, %2, 0;\n@p mbarrier.arrive.shared::cta.b64 _, [%0];\n@p mbarrier.arrive.shared::cta.b64 _, [%1];\n}"
                       :: "r"(SM_BASE + SM_EMPTY + sk * 8), "r"(SM_BASE + SM_EMPTY + sv * 8), "r"(lane) : "memory");
          PROF_MARK(25 + it * 3);
          sv = sk + 2; sk = sn;
          attn_step(S[1], S[0], P[1], P[0], O, Q, nm, RING_K + sk * 1024, RING_V + (sv * 1024) * V_STEP, it < 3, true);
          WG_WAIT(0); pin(O); pin(S[0]); pin(P[0]);
          PROF_MARK(26 + it * 3);
        }
        WG_FENCE();
        pv_tile(O, P[1], RING_V + (sv * 1024 + 512) * V_STEP, wg << 22);
        WG_COMMIT();
        announce<1>(sc, th == 0);
        WG_WAIT(0); pin(O);
      }
      PROF_MARK(9);

      {
        const uint32_t mo = stg + here(th) * 16;
        sts64(mo + 5 * 4096 + wg * 8, __float_as_uint(O[32]), __float_as_uint(O[34]));
        if (wg == 0) {
#pragma unroll
          for (int i = 4; i < 8; i++)
            sts128(mo + i * 2048, __float_as_uint(O[4 * i]), __float_as_uint(O[4 * i + 1]), __float_as_uint(O[4 * i + 2]), __float_as_uint(O[4 * i + 3]));
        } else {
#pragma unroll
          for (int i = 0; i < 4; i++)
            sts128(mo + i * 2048, __float_as_uint(O[4 * i]), __float_as_uint(O[4 * i + 1]), __float_as_uint(O[4 * i + 2]), __float_as_uint(O[4 * i + 3]));
#pragma unroll
          for (int i = 0; i < 16; i++) O[i] = O[16 + i];
        }
        bar_sync(BAR_MERGE, 288);
        uint32_t e[4];
        lds128(mo + 5 * 4096, e[0], e[1], e[2], e[3]);
        O[32] = __uint_as_float(e[0]) + __uint_as_float(e[2]); O[34] = __uint_as_float(e[1]) + __uint_as_float(e[3]);
#pragma unroll
        for (int i = 0; i < 4; i++) {
          lds128(mo + wg * TILE_BYTES + i * 2048, e[0], e[1], e[2], e[3]);
#pragma unroll
          for (int k = 0; k < 4; k++) O[4 * i + k] += __uint_as_float(e[k]);
        }
        const bool safe = O[32] > 0x1p-60f && O[32] < 0x1p60f && O[34] > 0x1p-60f && O[34] < 0x1p60f;
        if (__builtin_expect(__any_sync(0xffffffffu, !safe), 0)) attention_exact(O, Q, sc, batch * 4 + r, lane, wg);
        const float i0 = rcp_hw(O[32]), i1 = rcp_hw(O[34]);
#pragma unroll
        for (int i = 0; i < 8; i++) { const float v = (i & 1) ? i1 : i0; A[0][i] = pack2(O[2 * i] * v, O[2 * i + 1] * v); }
        A[0][0] &= ~1u; A[0][4] &= ~1u;
        uint4* dst = xp + X_AG1 + wg * 256;
        SCHED();
        st_vec(dst, A[0][0], A[0][1], A[0][2], A[0][3]);
        st_vec(dst + 128, A[0][4], A[0][5], A[0][6], A[0][7]);
        SCHED();
        if (TIMED) sent = clock_now();
      }
      const int dir = cw == 0 ? -1 : 1;
      uint32_t tap[15];
      if (wg == 1) {
        const uint32_t mo = stg + TILE_BYTES + here(th) * 16;
        sts128(mo, A[0][0], A[0][1], A[0][2], A[0][3]);
        sts128(mo + 2048, A[0][4], A[0][5], A[0][6], A[0][7]);
        bar_arrive(BAR_HALF, 256);
        load_taps(tap, 1);
      } else {
        PROF_MARK(10);
        const uint32_t mo = stg + TILE_BYTES + here(th) * 16;
        bar_sync(BAR_HALF, 256);
        lds128(mo, A[0][8], A[0][9], A[0][10], A[0][11]);
        lds128(mo + 2048, A[0][12], A[0][13], A[0][14], A[0][15]);
        proj_residual<F_WO, 6>(A, sc, xp, maddr, 0, sent);
        PROF_MARK(12);
        float acc[2][32];
        mma_tile<true>(acc[0], A[0], LO(F_PW1)); mma_tile<true>(acc[1], A[0], HI(F_PW1));
        gather_first<1, X_AG0>(A, st, sc, xp, 0, sent, [&] { load_taps(tap, dir); });
        mma_tile<false>(acc[1], A[1], HI(F_PW1 + 1)); mma_tile<false>(acc[0], A[1], LO(F_PW1 + 1));
        gather_rest<1, X_AG0>(A, xp, 0);
        RELEASE(F_WO - 2, F_WO + 1);
        PROF_MARK(13);
        mma_tile<false>(acc[1], A[2], HI(F_PW1 + 2)); mma_tile<false>(acc[1], A[3], HI(F_PW1 + 3));
        WG_WAIT(2);
        RELEASE(F_WO + 2, F_WO - 3 + NREL);
        SCHED();
        uint32_t mu[4];
        const RowNorm n = stat_finish(sc, st, 0, 0.5f);
        const float rs0 = row0 < nvalid ? n.rs0 : 0.f, rs1 = row0 + 8 < nvalid ? n.rs1 : 0.f;
        mean_frag(mu, n, q == 0);
        mma_fold<2 * CS_PW1 + 2>(acc[1], mu);
        mma_tile<false>(acc[0], A[2], LO(F_PW1 + 2));
        mma_tile_fold<2 * CS_PW1>(acc[0], A[3], LO(F_PW1 + 3), mu);
        WG_WAIT(2); pin(acc[1]);
#pragma unroll
        for (int i = 0; i < 32; i++) acc[1][i] = tanh_hw(acc[1][i] * ((i & 2) ? rs1 : rs0));
#pragma unroll
        for (int i = 0; i < 32; i++) { const float rs = (i & 2) ? rs1 : rs0; acc[1][i] = fmaf(acc[1][i], rs, rs); }
        pin(acc[1]);
        SCHED();
        WG_WAIT(0); pin(acc[0]);
#pragma unroll
        for (int i = 0; i < 16; i++) A[0][i] = pack2(acc[0][2 * i] * acc[1][2 * i], acc[0][2 * i + 1] * acc[1][2 * i + 1]);
        const uint32_t ga = stg + TILE_BYTES + here(mrow) * G_PITCH + (lane >> 4) * 16;
#pragma unroll
        for (int s = 0; s < 4; s++) stsm4(ga + s * 32, &A[0][4 * s]);
      }
      {
        const uint32_t gsrc = stg + TILE_BYTES + (8 * cw - 7) * G_PITCH + lane * 4;
        const bool edge = cw == 0 || cw == 7;
        const bool nbr = cw == 0 ? t > 0 : t < 15;
        uint4* const hdst = &sc->x[b + 4 * dir][X_HALO + (cw == 0 ? 96 : 0) + lane];
        uint32_t in[22];
        bar_sync(BAR_G, 256);
        PROF_MARK(14);
        if (cw == 0) {
#pragma unroll
          for (int i = 14; i >= 0; i--) in[i] = lds32(gsrc + (21 - i) * G_PITCH);
        } else {
#pragma unroll
          for (int i = 14; i >= 0; i--) in[i] = lds32(gsrc + i * G_PITCH);
        }
        if (edge) {
          if (nbr) {
            st_vec(hdst, HALO_TAG, in[14], in[13], in[12]);
            st_vec(hdst + 32, HALO_TAG, in[11], in[10], in[9]);
            st_vec(hdst + 64, HALO_TAG, in[8], 0u, 0u);
          }
        } else {
#pragma unroll
          for (int i = 15; i < 22; i++) in[i] = lds32(gsrc + i * G_PITCH);
        }
        if (cw == 0) PROF_MARK0(40);
        uint32_t cv[8];
#pragma unroll
        for (int i = 0; i < 15; i++)
#pragma unroll
          for (int o = 0; o < 8; o++) {
            if (i == o) asm("mul.rn.bf16x2 %0, %1, %2;" : "=r"(cv[o]) : "r"(in[i]), "r"(tap[0]));
            if (i > o) asm("fma.rn.bf16x2 %0, %1, %2, %0;" : "+r"(cv[o]) : "r"(in[i]), "r"(tap[i - o]));
          }
        pin(cv);
        if (cw == 0) PROF_MARK0(41);
        if (edge) {
#pragma unroll
          for (int i = 15; i < 22; i++) in[i] = 0u;
          if (nbr) {
            const uint4* src = &sc->x[b][X_HALO + (cw == 0 ? 0 : 96) + lane];
            uint32_t e0, e1, e2, u0, u1, spin = 0;
#pragma unroll 1
            do {
              ld_vec(src, e0, in[15], in[16], in[17]);
              ld_vec(src + 32, e1, in[18], in[19], in[20]);
              ld_vec(src + 64, e2, in[21], u0, u1);
            } while (__any_sync(0xffffffffu, ((e0 ^ HALO_TAG) | (e1 ^ HALO_TAG) | (e2 ^ HALO_TAG)) != 0) && ++spin < SPIN_LIMIT);
          }
          announce<1>(sc, lane == 0);
        }
#pragma unroll
        for (int i = 15; i < 22; i++)
#pragma unroll
          for (int o = 0; o < 8; o++)
            if (i - o <= 14) asm("fma.rn.bf16x2 %0, %1, %2, %0;" : "+r"(cv[o]) : "r"(in[i]), "r"(tap[i - o]));
        if (cw == 0) PROF_MARK0(42);
        if (cw == 7) PROF_MARK0(43);
        const uint32_t fl = cw == 0 ? 7 : 0;
        const uint32_t cdst = (stg + cw * 1024 + lane * 4) ^ (fl * 144);
#pragma unroll
        for (int o = 0; o < 8; o++) {
          const float a = bf_lo(cv[o]), c = bf_hi(cv[o]);
          sts32(cdst ^ (o * 144), pack2(fmaf(a, tanh_hw(a), a), fmaf(c, tanh_hw(c), c)));
        }
      }
      if (wg == 1) {
        bar_arrive(BAR_C, 256);
        break;
      }
      bar_sync(BAR_C, 256);
      tile_load(here(maddr), A[0]);
      PROF_MARK(15);
      publish(xp + X_AG1, A[0], 1);
      proj_residual<F_PW2, 2>(A, sc, xp, maddr, 1, sent);
      PROF_MARK(17);
    }
  }
}

typedef CUresult (*EncodeFn)(CUtensorMap*, CUtensorMapDataType, cuuint32_t, void*, const cuuint64_t*, const cuuint64_t*,
                             const cuuint32_t*, const cuuint32_t*, CUtensorMapInterleave, CUtensorMapSwizzle,
                             CUtensorMapL2promotion, CUtensorMapFloatOOBfill);

void make_map(EncodeFn fn, CUtensorMap* m, const void* w, int rows, int cols, CUtensorMapSwizzle swz) {
  const cuuint64_t dims[2] = {(cuuint64_t)cols, (cuuint64_t)rows}, strides[1] = {(cuuint64_t)cols * 2};
  const cuuint32_t box[2] = {64, 64}, es[2] = {1, 1};
  fn(m, CU_TENSOR_MAP_DATA_TYPE_BFLOAT16, 2, const_cast<void*>(w), dims, strides, box, es, CU_TENSOR_MAP_INTERLEAVE_NONE,
     swz, CU_TENSOR_MAP_L2_PROMOTION_L2_128B, CU_TENSOR_MAP_FLOAT_OOB_FILL_NONE);
}

}

extern "C" void kernel_launch(void* const* d_in, const int* in_sizes, int n_in, void* d_out, int out_size) {
  static EncodeFn fn = nullptr;
  static Scratch* sc = nullptr;
  if (!fn) {
    void* f = nullptr;
    cudaDriverEntryPointQueryResult st;
    cudaGetDriverEntryPoint("cuTensorMapEncodeTiled", &f, cudaEnableDefault, &st);
    fn = (EncodeFn)f;
    void* raw = nullptr;
    cudaGetSymbolAddress(&raw, g_scratch);
    sc = (Scratch*)(((uintptr_t)raw + X_ALIGN - 1) & ~(uintptr_t)(X_ALIGN - 1));
    cudaFuncSetAttribute(conformer_kernel, cudaFuncAttributeMaxDynamicSharedMemorySize, SM_TOTAL);
  }
  typedef const __nv_bfloat16* W;
  const CUtensorMapSwizzle S = CU_TENSOR_MAP_SWIZZLE_128B;
  Params p;
  make_map(fn, &p.map[M_FF1A], d_in[1], 256, 1024, S);
  make_map(fn, &p.map[M_FF1B], d_in[2], 1024, 256, S);
  make_map(fn, &p.map[M_QKV], d_in[3], 256, 768, S);
  make_map(fn, &p.map[M_WO], d_in[4], 256, 256, S);
  make_map(fn, &p.map[M_PW1], d_in[5], 256, 512, S);
  make_map(fn, &p.map[M_PW2], d_in[7], 256, 256, S);
  make_map(fn, &p.map[M_FF2A], d_in[8], 256, 1024, S);
  make_map(fn, &p.map[M_FF2B], d_in[9], 1024, 256, S);
  p.w_ff1b = (W)d_in[2]; p.w_qkv = (W)d_in[3]; p.w_o = (W)d_in[4]; p.w_pw1 = (W)d_in[5];
  p.w_pw2 = (W)d_in[7]; p.w_ff2a = (W)d_in[8]; p.w_ff2b = (W)d_in[9];

  cudaLaunchConfig_t cfg = {};
  cfg.gridDim = dim3(NCTA);
  cfg.blockDim = dim3(384);
  cfg.dynamicSmemBytes = SM_TOTAL;
  cfg.stream = cudaStreamPerThread;
  cudaLaunchAttribute at[1];
  at[0].id = cudaLaunchAttributeCooperative;
  at[0].val.cooperative = 1;
  cfg.attrs = at;
  cfg.numAttrs = 1;
  cudaLaunchKernelEx(&cfg, conformer_kernel, sc, (__nv_bfloat16*)d_out, (W)d_in[6], (W)d_in[0], (W)d_in[1], p);
}
```

```cpp
#include <cuda_runtime.h>
#include <cuda_bf16.h>
#include <cuda.h>
#include <stdint.h>

namespace {

constexpr int T_SEQ = 1000;
constexpr int DM = 256;
constexpr int NCTA = 128;
constexpr int NSTAGE = 12;
constexpr uint32_t STAGE_BYTES = 16384;
constexpr uint32_t TILE_BYTES = 8192;
constexpr uint32_t SM_BASE = 1024;
constexpr uint32_t SM_STG = NSTAGE * STAGE_BYTES;
constexpr uint32_t SM_FULL = SM_STG + 32768;
constexpr uint32_t SM_EMPTY = SM_FULL + 96;
constexpr uint32_t SM_KVRDY = SM_FULL + 192;
constexpr uint32_t SM_EYE = SM_FULL + 256;
constexpr uint32_t SM_ONE = SM_FULL + 640;
constexpr uint32_t SM_CS = SM_FULL + 768;
constexpr uint32_t SM_TOTAL = SM_FULL + 3072;
constexpr int CS_FF2 = 0, CS_PW1 = 4, CS_QKV = 6;
constexpr uint32_t SPIN_LIMIT = 1u << 16;
constexpr float LN_EPS = 1e-5f;
constexpr float SM_SCALE_LOG2 = 0.125f * 1.4426950408889634f;
constexpr uint32_t G_PITCH = 144;
#define FSTR 8
#define CS_AFTER 8
#define WD 0
#define TIMED 1
#define GD 480
#define RD 400
#define NREL 5
#define PF0 1
#define TF 1
#define TC 1
#define PF1 1400
#define PF2 2000
#define PF3 3500
#define CLR_PACE 150

constexpr int F_QKV = 16, F_SPARE = 22, F_KV = 24, F_WO = 40, F_PW1 = 42, F_PW2 = 46, F_TOTAL = 64;
enum { M_FF1A, M_FF1B, M_QKV, M_WO, M_PW1, M_PW2, M_FF2A, M_FF2B, M_COUNT };
enum { BAR_K = 1, BAR_V, BAR_Q, BAR_MERGE, BAR_G, BAR_C, BAR_WG1, BAR_GO, BAR_CS, BAR_ATT, BAR_INIT, BAR_HALF, BAR_RST, BAR_TAP };

struct Params {
  CUtensorMap map[M_COUNT];
  const __nv_bfloat16 *w_ff1b, *w_qkv, *w_o, *w_pw1, *w_pw2, *w_ff2a, *w_ff2b;
};

constexpr int X_RS = 0, X_AG1 = X_RS, X_HALO = X_RS + 512, X_AG0 = 1536, X_ST = 2048, X_SIZE = 4096;
constexpr uint32_t HALO_TAG = 0xFFFF0001u;
struct Scratch {
  uint4 x[NCTA][X_SIZE];
  uint4 kv[8][2][16][512];
  uint4 cs[2][576];
  uint32_t flag[8][32][FSTR];
  uint32_t step[NCTA][32];
};
constexpr size_t X_ALIGN = 4 * X_SIZE * sizeof(uint4);
__device__ uint8_t g_scratch[sizeof(Scratch) + X_ALIGN];
#define PROF_TIME(i)
#define PROF_MARK(i)
#define PROF_MARK2(i, j)
#define PROF_MARK0(i)
#define PROF_AT(a)

__device__ __forceinline__ void mbar_init(uint32_t bar, uint32_t cnt) {
  asm volatile("mbarrier.init.shared::cta.b64 [%0], %1;" :: "r"(bar), "r"(cnt) : "memory");
}
__device__ __forceinline__ void mbar_wait(uint32_t bar, uint32_t parity) {
  asm volatile("{\n.reg .pred p;\n.reg .u32 c;\nmov.u32 c, 0;\n"
               "WAIT_LOOP:\nmbarrier.try_wait.parity.shared::cta.b64 p, [%0], %1;\n@p bra WAIT_DONE;\n"
               "add.u32 c, c, 1;\nsetp.lt.u32 p, c, %2;\n@p bra WAIT_LOOP;\nWAIT_DONE:\n}"
               :: "r"(bar), "r"(parity), "n"(SPIN_LIMIT) : "memory");
}
__device__ __forceinline__ void mbar_arrive(uint32_t bar) {
  asm volatile("mbarrier.arrive.shared::cta.b64 _, [%0];" :: "r"(bar) : "memory");
}
#define bar_sync(id, n) asm volatile("bar.sync %0, %1;" :: "n"((int)(id)), "n"(n) : "memory")
#define bar_arrive(id, n) asm volatile("bar.arrive %0, %1;" :: "n"((int)(id)), "n"(n) : "memory")
__device__ __forceinline__ void fence_async_smem() { asm volatile("fence.proxy.async.shared::cta;" ::: "memory"); }

__device__ __forceinline__ void st_vec(uint4* p, uint32_t a, uint32_t b, uint32_t c, uint32_t d) {
  asm volatile("{\n.reg .b128 v;\n.reg .b64 lo, hi;\nmov.b64 lo, {%1, %2};\nmov.b64 hi, {%3, %4};\nmov.b128 v, {lo, hi};\n"
               "st.relaxed.gpu.global.b128 [%0], v;\n}" :: "l"(p), "r"(a), "r"(b), "r"(c), "r"(d) : "memory");
}
__device__ __forceinline__ void ld_vec(const uint4* p, uint32_t& a, uint32_t& b, uint32_t& c, uint32_t& d) {
  asm volatile("{\n.reg .b128 v;\n.reg .b64 lo, hi;\nld.relaxed.gpu.global.b128 v, [%4];\nmov.b128 {lo, hi}, v;\n"
               "mov.b64 {%0, %1}, lo;\nmov.b64 {%2, %3}, hi;\n}" : "=r"(a), "=r"(b), "=r"(c), "=r"(d) : "l"(p) : "memory");
}
__device__ __forceinline__ void sts128(uint32_t a, uint32_t x, uint32_t y, uint32_t z, uint32_t w) {
  asm volatile("st.shared.v4.u32 [%0], {%1, %2, %3, %4};" :: "r"(a), "r"(x), "r"(y), "r"(z), "r"(w) : "memory");
}
__device__ __forceinline__ void lds128(uint32_t a, uint32_t& x, uint32_t& y, uint32_t& z, uint32_t& w) {
  asm volatile("ld.shared.v4.u32 {%0, %1, %2, %3}, [%4];" : "=r"(x), "=r"(y), "=r"(z), "=r"(w) : "r"(a) : "memory");
}
__device__ __forceinline__ uint32_t lds32(uint32_t a) {
  uint32_t x; asm volatile("ld.shared.u32 %0, [%1];" : "=r"(x) : "r"(a) : "memory"); return x;
}
__device__ __forceinline__ void sts32(uint32_t a, uint32_t x) { asm volatile("st.shared.u32 [%0], %1;" :: "r"(a), "r"(x) : "memory"); }
__device__ __forceinline__ void sts64(uint32_t a, uint32_t x, uint32_t y) {
  asm volatile("st.shared.v2.u32 [%0], {%1, %2};" :: "r"(a), "r"(x), "r"(y) : "memory");
}
__device__ __forceinline__ void stsm4(uint32_t a, const uint32_t* r) {
  asm volatile("stmatrix.sync.aligned.m8n8.x4.shared.b16 [%0], {%1, %2, %3, %4};" :: "r"(a), "r"(r[0]), "r"(r[1]), "r"(r[2]), "r"(r[3]) : "memory");
}
__device__ __forceinline__ void ldsm4(uint32_t a, uint32_t* r) {
  asm volatile("ldmatrix.sync.aligned.m8n8.x4.shared.b16 {%0, %1, %2, %3}, [%4];" : "=r"(r[0]), "=r"(r[1]), "=r"(r[2]), "=r"(r[3]) : "r"(a) : "memory");
}
__device__ __forceinline__ uint32_t pack2(float lo, float hi) {
  uint32_t r; asm("cvt.rn.bf16x2.f32 %0, %1, %2;" : "=r"(r) : "f"(hi), "f"(lo)); return r;
}
__device__ __forceinline__ float bf_lo(uint32_t w) { return __uint_as_float(w << 16); }
__device__ __forceinline__ float bf_hi(uint32_t w) { return __uint_as_float(w & 0xffff0000u); }
__device__ __forceinline__ float tanh_hw(float x) { float y; asm volatile("tanh.approx.f32 %0, %1;" : "=f"(y) : "f"(x)); return y; }
__device__ __forceinline__ float rcp_hw(float x) { float y; asm("rcp.approx.ftz.f32 %0, %1;" : "=f"(y) : "f"(x)); return y; }
__device__ __forceinline__ float rsqrt_hw(float x) { float y; asm("rsqrt.approx.ftz.f32 %0, %1;" : "=f"(y) : "f"(x)); return y; }
__device__ __forceinline__ float ex2_hw(float x) { float y; asm("ex2.approx.ftz.f32 %0, %1;" : "=f"(y) : "f"(x)); return y; }

__device__ __forceinline__ uint32_t here(uint32_t v) { asm volatile("" : "+r"(v)); return v; }

#define SCHED() asm volatile("pmevent 1;" ::: "memory")
__device__ __forceinline__ void cp_async16(uint32_t dst, const void* src) {
  asm volatile("cp.async.cg.shared.global [%0], [%1], 16;" :: "r"(dst), "l"(src) : "memory");
}
__device__ __forceinline__ void cp_async_wait(int n) {
  if (n == 0) asm volatile("cp.async.wait_group 0;" ::: "memory");
  if (n == 1) asm volatile("cp.async.wait_group 1;" ::: "memory");
  if (n == 2) asm volatile("cp.async.wait_group 2;" ::: "memory");
  if (n == 3) asm volatile("cp.async.wait_group 3;" ::: "memory");
}
#define WG_FENCE() asm volatile("wgmma.fence.sync.aligned;" ::: "memory")
#define WG_COMMIT() asm volatile("wgmma.commit_group.sync.aligned;" ::: "memory")
#define WG_WAIT(n) asm volatile("wgmma.wait_group.sync.aligned %0;" :: "n"(n) : "memory")

template <int N> __device__ __forceinline__ void pin(float (&d)[N]) {
#pragma unroll
  for (int i = 0; i < N; i++) asm volatile("" : "+f"(d[i]) :: "memory");
}
template <int N> __device__ __forceinline__ void pin(uint32_t (&d)[N]) {
#pragma unroll
  for (int i = 0; i < N; i++) asm volatile("" : "+r"(d[i]) :: "memory");
}

#define WG_D32 "{%0, %1, %2, %3, %4, %5, %6, %7, %8, %9, %10, %11, %12, %13, %14, %15, %16, %17, %18, %19, %20, %21, %22, %23, %24, %25, %26, %27, %28, %29, %30, %31}"
template <int TB> __device__ __forceinline__ void wgmma64_acc(float (&d)[32], const uint32_t* a, uint64_t db) {
  asm volatile("wgmma.mma_async.sync.aligned.m64n64k16.f32.bf16.bf16 " WG_D32 ", {%32, %33, %34, %35}, %36, 1, 1, 1, %37;"
    : "+f"(d[0]), "+f"(d[1]), "+f"(d[2]), "+f"(d[3]), "+f"(d[4]), "+f"(d[5]), "+f"(d[6]), "+f"(d[7]),
      "+f"(d[8]), "+f"(d[9]), "+f"(d[10]), "+f"(d[11]), "+f"(d[12]), "+f"(d[13]), "+f"(d[14]), "+f"(d[15]),
      "+f"(d[16]), "+f"(d[17]), "+f"(d[18]), "+f"(d[19]), "+f"(d[20]), "+f"(d[21]), "+f"(d[22]), "+f"(d[23]),
      "+f"(d[24]), "+f"(d[25]), "+f"(d[26]), "+f"(d[27]), "+f"(d[28]), "+f"(d[29]), "+f"(d[30]), "+f"(d[31])
    : "r"(a[0]), "r"(a[1]), "r"(a[2]), "r"(a[3]), "l"(db), "n"(TB));
}
template <int TB> __device__ __forceinline__ void wgmma64_reuse(float (&d)[32], const uint32_t* a, uint64_t db, uint32_t zero) {
  asm volatile("{\n.reg .pred p;\nsetp.ne.u32 p, %37, 0;\nwgmma.mma_async.sync.aligned.m64n64k16.f32.bf16.bf16 " WG_D32 ", {%32, %33, %34, %35}, %36, p, 1, 1, %38;\n}"
    : "+f"(d[0]), "+f"(d[1]), "+f"(d[2]), "+f"(d[3]), "+f"(d[4]), "+f"(d[5]), "+f"(d[6]), "+f"(d[7]),
      "+f"(d[8]), "+f"(d[9]), "+f"(d[10]), "+f"(d[11]), "+f"(d[12]), "+f"(d[13]), "+f"(d[14]), "+f"(d[15]),
      "+f"(d[16]), "+f"(d[17]), "+f"(d[18]), "+f"(d[19]), "+f"(d[20]), "+f"(d[21]), "+f"(d[22]), "+f"(d[23]),
      "+f"(d[24]), "+f"(d[25]), "+f"(d[26]), "+f"(d[27]), "+f"(d[28]), "+f"(d[29]), "+f"(d[30]), "+f"(d[31])
    : "r"(a[0]), "r"(a[1]), "r"(a[2]), "r"(a[3]), "l"(db), "r"(zero), "n"(TB));
}
template <int TB> __device__ __forceinline__ void wgmma64_set(float (&d)[32], const uint32_t* a, uint64_t db) {
  asm volatile("wgmma.mma_async.sync.aligned.m64n64k16.f32.bf16.bf16 " WG_D32 ", {%32, %33, %34, %35}, %36, 0, 1, 1, %37;"
    : "=f"(d[0]), "=f"(d[1]), "=f"(d[2]), "=f"(d[3]), "=f"(d[4]), "=f"(d[5]), "=f"(d[6]), "=f"(d[7]),
      "=f"(d[8]), "=f"(d[9]), "=f"(d[10]), "=f"(d[11]), "=f"(d[12]), "=f"(d[13]), "=f"(d[14]), "=f"(d[15]),
      "=f"(d[16]), "=f"(d[17]), "=f"(d[18]), "=f"(d[19]), "=f"(d[20]), "=f"(d[21]), "=f"(d[22]), "=f"(d[23]),
      "=f"(d[24]), "=f"(d[25]), "=f"(d[26]), "=f"(d[27]), "=f"(d[28]), "=f"(d[29]), "=f"(d[30]), "=f"(d[31])
    : "r"(a[0]), "r"(a[1]), "r"(a[2]), "r"(a[3]), "l"(db), "n"(TB));
}

__device__ __forceinline__ void wgmma72_acc(float (&d)[36], const uint32_t* a, uint64_t db) {
  asm volatile("wgmma.mma_async.sync.aligned.m64n72k16.f32.bf16.bf16 {%0, %1, %2, %3, %4, %5, %6, %7, %8, %9, %10, %11, %12, %13, %14, %15, %16, %17, %18, %19, %20, %21, %22, %23, %24, %25, %26, %27, %28, %29, %30, %31, %32, %33, %34, %35}, {%36, %37, %38, %39}, %40, 1, 1, 1, 1;"
    : "+f"(d[0]), "+f"(d[1]), "+f"(d[2]), "+f"(d[3]), "+f"(d[4]), "+f"(d[5]), "+f"(d[6]), "+f"(d[7]), "+f"(d[8]),
      "+f"(d[9]), "+f"(d[10]), "+f"(d[11]), "+f"(d[12]), "+f"(d[13]), "+f"(d[14]), "+f"(d[15]), "+f"(d[16]), "+f"(d[17]),
      "+f"(d[18]), "+f"(d[19]), "+f"(d[20]), "+f"(d[21]), "+f"(d[22]), "+f"(d[23]), "+f"(d[24]), "+f"(d[25]), "+f"(d[26]),
      "+f"(d[27]), "+f"(d[28]), "+f"(d[29]), "+f"(d[30]), "+f"(d[31]), "+f"(d[32]), "+f"(d[33]), "+f"(d[34]), "+f"(d[35])
    : "r"(a[0]), "r"(a[1]), "r"(a[2]), "r"(a[3]), "l"(db));
}
__device__ __forceinline__ void wgmma16_acc(float* d, const uint32_t* a, uint64_t db) {
  asm volatile("wgmma.mma_async.sync.aligned.m64n16k16.f32.bf16.bf16 {%0, %1, %2, %3, %4, %5, %6, %7}, {%8, %9, %10, %11}, %12, 1, 1, 1, 0;"
    : "+f"(d[0]), "+f"(d[1]), "+f"(d[2]), "+f"(d[3]), "+f"(d[4]), "+f"(d[5]), "+f"(d[6]), "+f"(d[7])
    : "r"(a[0]), "r"(a[1]), "r"(a[2]), "r"(a[3]), "l"(db));
}
__device__ __forceinline__ void hmma(float (&d)[4], const uint32_t* a, uint32_t b0, uint32_t b1) {
  asm("mma.sync.aligned.m16n8k16.row.col.f32.bf16.bf16.f32 {%0, %1, %2, %3}, {%4, %5, %6, %7}, {%8, %9}, {%0, %1, %2, %3};"
    : "+f"(d[0]), "+f"(d[1]), "+f"(d[2]), "+f"(d[3]) : "r"(a[0]), "r"(a[1]), "r"(a[2]), "r"(a[3]), "r"(b0), "r"(b1));
}

__device__ __forceinline__ void hmma8(float (&d)[4], const uint32_t* a, uint32_t b0) {
  asm("mma.sync.aligned.m16n8k8.row.col.f32.bf16.bf16.f32 {%0, %1, %2, %3}, {%4, %5}, {%6}, {%0, %1, %2, %3};"
    : "+f"(d[0]), "+f"(d[1]), "+f"(d[2]), "+f"(d[3]) : "r"(a[0]), "r"(a[1]), "r"(b0));
}

template <bool FIRST> __device__ __forceinline__ void mma_tile(float (&d)[32], const uint32_t (&a)[16], uint64_t db) {
  WG_FENCE();
#pragma unroll
  for (int s = 0; s < 4; s++) {
    if (FIRST && s == 0) wgmma64_set<1>(d, &a[0], db); else wgmma64_acc<1>(d, &a[4 * s], db + s * 128);
  }
  WG_COMMIT();
}
__device__ __forceinline__ void mma_tile_reuse(float (&d)[32], const uint32_t (&a)[16], uint64_t db) {
  WG_FENCE();
  wgmma64_reuse<1>(d, &a[0], db, blockIdx.y);
#pragma unroll
  for (int s = 1; s < 4; s++) wgmma64_acc<1>(d, &a[4 * s], db + s * 128);
  WG_COMMIT();
}
template <int ROW> __device__ __forceinline__ void fold_step(float (&d)[32], const uint32_t (&mu)[4]) {
  wgmma64_acc<1>(d, mu, (uint64_t)((SM_BASE + SM_CS + ROW * 128) >> 4) | (uint64_t(1) << 16) | (uint64_t(1) << 62));
}
template <int ROW> __device__ __forceinline__ void mma_fold(float (&d)[32], const uint32_t (&mu)[4]) {
  WG_FENCE();
  fold_step<ROW>(d, mu);
  WG_COMMIT();
}
template <int ROW> __device__ __forceinline__ void mma_tile_fold(float (&d)[32], const uint32_t (&a)[16], uint64_t db, const uint32_t (&mu)[4]) {
  WG_FENCE();
#pragma unroll
  for (int s = 0; s < 4; s++) wgmma64_acc<1>(d, &a[4 * s], db + s * 128);
  fold_step<ROW>(d, mu);
  WG_COMMIT();
}
__device__ __forceinline__ void mma_add_half(float (&d)[32], const uint32_t (&a)[16]) {
  const uint64_t db = (uint64_t)((SM_BASE + SM_EYE) >> 4) | (uint64_t(8) << 16) | (uint64_t(8) << 32);
  WG_FENCE();
#pragma unroll
  for (int s = 0; s < 4; s++) wgmma16_acc(&d[8 * s], &a[4 * s], db);
  WG_COMMIT();
}
#define ACQUIRE(f) mbar_wait(SM_BASE + SM_FULL + ((f) % NSTAGE) * 8, ((f) / NSTAGE) & 1)
__device__ __forceinline__ void mbar_probe(uint32_t& ok, uint32_t bar, uint32_t parity) {
  asm volatile("{\n.reg .pred p;\nmbarrier.test_wait.parity.shared::cta.b64 p, [%1], %2;\nselp.u32 %0, %0, 0, p;\n}"
               : "+r"(ok) : "r"(bar), "r"(parity) : "memory");
}
template <int F, int N> __device__ __forceinline__ uint32_t probe_n() {
  static_assert(F % NSTAGE + N <= NSTAGE, "stages must not wrap");
  uint32_t ok = 1;
#pragma unroll
  for (int i = 0; i < N; i++) mbar_probe(ok, SM_BASE + SM_FULL + (F % NSTAGE + i) * 8, (F / NSTAGE) & 1);
  return ok;
}
template <int F, int N> __device__ __forceinline__ void settle_n(uint32_t ok) {
  if (__builtin_expect(!ok, 0)) {
#pragma unroll 1
    for (int i = 0; i < N; i++) mbar_wait(SM_BASE + SM_FULL + (F % NSTAGE + i) * 8, (F / NSTAGE) & 1);
  }
}
template <int F, int N> __device__ __forceinline__ void acquire_n() { settle_n<F, N>(probe_n<F, N>()); }
#define RELEASE(f0, f1) do { if (lane == 0) { _Pragma("unroll") for (int f_ = (f0); f_ <= (f1); f_++) mbar_arrive(SM_BASE + SM_EMPTY + (f_ % NSTAGE) * 8); } } while (0)
constexpr uint64_t RING = (uint64_t)(SM_BASE >> 4) | (uint64_t(1) << 16) | (uint64_t(64) << 32) | (uint64_t(1) << 62);
#define LO(f) (RING + ((f) % NSTAGE) * 1024)
#define HI(f) (RING + ((f) % NSTAGE) * 1024 + 512)

template <int C> __device__ __forceinline__ uint4* peer(uint4* p) {
  asm volatile("" : "+l"(p));
  return (uint4*)((uintptr_t)p ^ (C * X_SIZE * sizeof(uint4)));
}
__device__ __forceinline__ uint32_t clock_now() { uint32_t c; asm volatile("mov.u32 %0, %%clock;" : "=r"(c) :: "memory"); return c; }
__device__ __forceinline__ void publish(uint4* dst, uint32_t (&a)[16], uint32_t tag) {
#pragma unroll
  for (int s = 0; s < 4; s++) a[4 * s] = (a[4 * s] & ~1u) | tag;
  pin(a);
  SCHED();
#pragma unroll
  for (int s = 0; s < 4; s++) st_vec(dst + s * 128, a[4 * s], a[4 * s + 1], a[4 * s + 2], a[4 * s + 3]);
  SCHED();
}
__device__ __forceinline__ void fetch(const uint4* src, uint32_t (&a)[16]) {
#pragma unroll
  for (int s = 0; s < 4; s++) ld_vec(src + s * 128, a[4 * s], a[4 * s + 1], a[4 * s + 2], a[4 * s + 3]);
}
__device__ __forceinline__ uint32_t miss(const uint32_t (&a)[16], uint32_t tag) {
  return (a[0] ^ tag) | (a[4] ^ tag) | (a[8] ^ tag) | (a[12] ^ tag);
}
__device__ __forceinline__ bool stale(uint32_t v) { return __any_sync(0xffffffffu, here(v) & 1u); }
template <int N = 2> __device__ __forceinline__ void announce(Scratch* sc, bool leader) {
  asm volatile("{\n.reg .pred p;\nsetp.ne.u32 p, %1, 0;\n@p red.relaxed.gpu.global.add.u32 [%0], %2;\n}"
               :: "l"(sc->step[blockIdx.x]), "r"((uint32_t)leader), "n"(N) : "memory");
}
__device__ __forceinline__ uint32_t launch_index(const Scratch* sc) { return *(const volatile uint32_t*)sc->step[blockIdx.x] >> 4; }
__device__ __forceinline__ void stat_fetch(const Scratch* sc, uint32_t (&st)[4]) {
  const uint32_t th = here(threadIdx.x);
  ld_vec(&sc->x[(blockIdx.x & ~3u) + (th & 3)][X_ST + (th >> 2)], st[0], st[1], st[2], st[3]);
}
struct Nothing { __device__ __forceinline__ void operator()() const {} };
template <int C, int SLOT, class F = Nothing>
__device__ __forceinline__ void gather_first(uint32_t (&A)[4][16], uint32_t (&st)[4], const Scratch* sc, uint4* xp, uint32_t tag, uint32_t sent, F meanwhile = F()) {
  if (TIMED) { while (clock_now() - sent < GD) {} }
  bar_sync(BAR_GO, 160);
  fetch(peer<1>(xp) + SLOT, A[1]); fetch(peer<2>(xp) + SLOT, A[2]); fetch(peer<3>(xp) + SLOT, A[3]);
  if (SLOT == X_AG0) stat_fetch(sc, st);
  meanwhile();
  uint32_t spin = 0;
  while (__builtin_expect(stale(miss(A[1], tag) | miss(A[C], tag)), 0) && ++spin < SPIN_LIMIT) {
    fetch(peer<1>(xp) + SLOT, A[1]);
    if (C == 2) fetch(peer<2>(xp) + SLOT, A[2]);
  }
}
template <int C, int SLOT> __device__ __forceinline__ void gather_rest(uint32_t (&A)[4][16], uint4* xp, uint32_t tag) {
  SCHED();
  uint32_t spin = 0;
  while (__builtin_expect(stale(miss(A[C + 1], tag) | miss(A[3], tag)), 0) && ++spin < SPIN_LIMIT) {
    if (C == 1) fetch(peer<2>(xp) + SLOT, A[2]);
    fetch(peer<3>(xp) + SLOT, A[3]);
  }
}
__device__ __forceinline__ void pack_acc(const float (&d)[32], uint32_t (&a)[16]) {
#pragma unroll
  for (int i = 0; i < 16; i++) a[i] = pack2(d[2 * i], d[2 * i + 1]);
}
__device__ __forceinline__ void frag_store(uint32_t slot, const uint32_t (&a)[16]) {
#pragma unroll
  for (int s = 0; s < 4; s++) sts128(slot + s * 512, a[4 * s], a[4 * s + 1], a[4 * s + 2], a[4 * s + 3]);
}
__device__ __forceinline__ void tile_store(uint32_t maddr, const uint32_t (&a)[16]) {
#pragma unroll
  for (int s = 0; s < 4; s++) stsm4(maddr ^ (s << 5), &a[4 * s]);
}
__device__ __forceinline__ void tile_load(uint32_t maddr, uint32_t (&a)[16]) {
#pragma unroll
  for (int s = 0; s < 4; s++) ldsm4(maddr ^ (s << 5), &a[4 * s]);
}

__device__ __forceinline__ void res_load(uint32_t maddr, float (&d)[32]) {
  uint32_t a[16];
  tile_load(here(maddr) + 3 * TILE_BYTES, a);
#pragma unroll
  for (int i = 0; i < 16; i++) { d[2 * i] = bf_lo(a[i]); d[2 * i + 1] = bf_hi(a[i]); }
  pin(d);
}

struct RowAcc { float s[2][4], u[2][4], v[2][4]; };
__device__ __forceinline__ void row_sums(RowAcc& t, const uint32_t (&a)[16]) {
#pragma unroll
  for (int s = 0; s < 4; s++) hmma(t.s[s & 1], &a[4 * s], 0x3F803F80u, 0x3F803F80u);
}
__device__ __forceinline__ void row_gram(RowAcc& t, const uint32_t (&a)[16]) {
#pragma unroll
  for (int s = 0; s < 8; s++) {
    hmma8(t.u[s & 1], &a[2 * s], a[2 * s]);
    hmma8(t.v[s & 1], &a[2 * s], a[2 * s + 1]);
  }
}
__device__ __forceinline__ float2 row_squares(const RowAcc& t, bool odd) {
  return make_float2(odd ? t.u[0][1] + t.u[1][1] : t.u[0][0] + t.u[1][0], odd ? t.v[0][3] + t.v[1][3] : t.v[0][2] + t.v[1][2]);
}
__device__ __forceinline__ void stat_publish(const uint32_t (&a)[16], Scratch* sc, uint32_t th, uint32_t tag) {
  RowAcc t = {};
  row_sums(t, a);
  row_gram(t, a);
  const float2 q = row_squares(t, th & 4);
  if ((th & 3) == ((th >> 3) & 3))
    st_vec(&sc->x[blockIdx.x][X_ST + (th >> 2)], (__float_as_uint(t.s[0][0] + t.s[1][0]) & ~1u) | tag, __float_as_uint(q.x),
           __float_as_uint(t.s[0][2] + t.s[1][2]), __float_as_uint(q.y));
}
struct RowNorm { float m0, rs0, m1, rs1; };
__device__ __forceinline__ RowNorm row_norm(float s0, float q0, float s1, float q1, float scale) {
  RowNorm n;
  n.m0 = s0 * (1.f / DM); n.m1 = s1 * (1.f / DM);
  n.rs0 = scale * rsqrt_hw(fmaxf(fmaf(-n.m0, n.m0, q0 * (1.f / DM)), 0.f) + LN_EPS);
  n.rs1 = scale * rsqrt_hw(fmaxf(fmaf(-n.m1, n.m1, q1 * (1.f / DM)), 0.f) + LN_EPS);
  return n;
}
__device__ __forceinline__ RowNorm stat_finish(const Scratch* sc, uint32_t (&st)[4], uint32_t tag, float scale) {
  uint32_t spin = 0;
  while (__builtin_expect(stale(st[0] ^ tag), 0) && ++spin < SPIN_LIMIT) stat_fetch(sc, st);
  float f[4];
#pragma unroll
  for (int i = 0; i < 4; i++) {
    f[i] = __uint_as_float(st[i]);
    f[i] += __shfl_xor_sync(0xffffffffu, f[i], 1);
    f[i] += __shfl_xor_sync(0xffffffffu, f[i], 2);
  }
  return row_norm(f[0], f[1], f[2], f[3], scale);
}
__device__ __forceinline__ void mean_frag(uint32_t (&mu)[4], const RowNorm& n, bool sel) {
  const float a = sel ? -n.m0 : 0.f, c = sel ? -n.m1 : 0.f;
  mu[0] = pack2(a, a); mu[1] = pack2(c, c);
  const float al = a - bf_lo(mu[0]), cl = c - bf_lo(mu[1]);
  mu[2] = pack2(al, al); mu[3] = pack2(cl, cl);
  pin(mu);
}
__device__ __forceinline__ void centre(uint32_t (&a)[16], uint32_t m0, uint32_t m1) {
#pragma unroll
  for (int i = 0; i < 16; i++) asm("sub.rn.bf16x2 %0, %0, %1;" : "+r"(a[i]) : "r"((i & 1) ? m1 : m0));
  pin(a);
}
__device__ __forceinline__ void scale_pack(const float (&d)[32], uint32_t (&a)[16], float rs0, float rs1) {
#pragma unroll
  for (int i = 0; i < 16; i++) { const float rs = (i & 1) ? rs1 : rs0; a[i] = pack2(d[2 * i] * rs, d[2 * i + 1] * rs); }
}
template <int S> __device__ __forceinline__ void silu_seg(float (&acc)[4][32], float (&tn)[2][4], uint32_t (&H)[4][16], float rs0, float rs1) {
  if (S >= 2) {
    const float* h = &acc[(S - 2) >> 3][4 * ((S - 2) & 7)];
    const float* v = tn[S & 1];
    uint32_t* o = &H[(S - 2) >> 3][2 * ((S - 2) & 7)];
    o[0] = pack2(fmaf(h[0], v[0], h[0]), fmaf(h[1], v[1], h[1]));
    o[1] = pack2(fmaf(h[2], v[2], h[2]), fmaf(h[3], v[3], h[3]));
    asm volatile("" : "+r"(o[0]), "+r"(o[1]));
  }
  if (S >= 1 && S <= 32) {
#pragma unroll
    for (int k = 0; k < 4; k++) tn[(S - 1) & 1][k] = tanh_hw(acc[((S - 1) >> 3) & 3][4 * ((S - 1) & 7) + k]);
  }
  if (S < 32) {
    float* h = &acc[(S >> 3) & 3][4 * (S & 7)];
    h[0] *= rs0; h[1] *= rs0; h[2] *= rs1; h[3] *= rs1;
    asm volatile("" : "+f"(h[0]), "+f"(h[1]), "+f"(h[2]), "+f"(h[3]));
  }
  SCHED();
}
template <int S0, int S1> __device__ __forceinline__ void silu_segs(float (&acc)[4][32], float (&tn)[2][4], uint32_t (&H)[4][16], float rs0, float rs1) {
  silu_seg<S0>(acc, tn, H, rs0, rs1);
  if constexpr (S0 + 1 < S1) silu_segs<S0 + 1, S1>(acc, tn, H, rs0, rs1);
}
template <int HALF> __device__ __forceinline__ void send_half(uint4* dst, const float (&d)[32], uint32_t tag) {
  uint32_t o[8];
#pragma unroll
  for (int i = 0; i < 8; i++) o[i] = pack2(d[16 * HALF + 2 * i], d[16 * HALF + 2 * i + 1]);
  o[0] = (o[0] & ~1u) | tag; o[4] = (o[4] & ~1u) | tag;
  pin(o);
  SCHED();
  st_vec(dst + HALF * 256, o[0], o[1], o[2], o[3]);
  st_vec(dst + HALF * 256 + 128, o[4], o[5], o[6], o[7]);
  SCHED();
}
__device__ __forceinline__ void send_residual(uint32_t (&a)[16], Scratch* sc, uint4* xp, uint32_t maddr, uint32_t tag, uint32_t& sent) {
  const uint32_t exact[4] = {a[0], a[4], a[8], a[12]};
  publish(xp + X_AG0, a, tag);
  if (TIMED) sent = clock_now();
  const uint32_t th = here(threadIdx.x);
  stat_publish(a, sc, th, tag);
  tile_store(here(maddr) + 3 * TILE_BYTES, a);
  stsm4(SM_BASE + SM_STG + 3 * TILE_BYTES + (th >> 5) * 2048 + (th & 7) * 128 + ((((th >> 2) & 6) ^ (th & 7)) << 4), exact);
}
template <int F, int N, class G> __device__ __forceinline__ void proj_residual(uint32_t (&A)[4][16], Scratch* sc, uint4* xp, uint32_t maddr,
                                                                      uint32_t tag, uint32_t& sent, G own_chunk, uint32_t sent_early = 0) {
  float acc[32];
  uint32_t st[4];
  acquire_n<F, N>();
  if (F == F_PW2) acquire_n<0, 5>();
  res_load(maddr, acc);
  own_chunk();
  sent = F == F_PW2 ? sent_early : clock_now() - 60;
  mma_tile<false>(acc, A[0], LO(F));
  gather_first<2, X_AG1>(A, st, sc, xp, tag, sent);
  announce(sc, threadIdx.x == 0);
  mma_tile<false>(acc, A[1], HI(F));
  mma_tile<false>(acc, A[2], LO(F + 1));
  gather_rest<2, X_AG1>(A, xp, tag);
  PROF_MARK0(F == F_WO ? 11 : 16);
  mma_tile<false>(acc, A[3], HI(F + 1));
  WG_WAIT(0); pin(acc);
  pack_acc(acc, A[0]);
  send_residual(A[0], sc, xp, maddr, tag, sent);
}

__device__ __forceinline__ uint64_t ring_desc(uint32_t lo) { return (RING & ~uint64_t(0xFFFFFFFFu)) | lo; }
__device__ __forceinline__ void qk_tile(float (&S)[32], const uint32_t (&Q)[16], uint32_t dk) {
  wgmma64_reuse<0>(S, &Q[0], ring_desc(dk), blockIdx.y);
#pragma unroll
  for (int s = 1; s < 4; s++) wgmma64_acc<0>(S, &Q[4 * s], ring_desc(dk + s * 2));
}
__device__ __forceinline__ void qk_shift(float (&S)[32], const uint32_t (&nm)[4]) { wgmma64_acc<0>(S, nm, (uint64_t)((SM_BASE + SM_ONE) >> 4)); }
constexpr uint32_t RING_K = (uint32_t)RING, V_STEP = 1u - (1u << 16);
constexpr uint32_t RING_V = (SM_BASE >> 4) | (((SM_STG + 2 * TILE_BYTES) >> 4) << 16);
__device__ __forceinline__ void pv_tile(float (&O)[36], const uint32_t (&P)[16], uint32_t dv, uint32_t pad) {
#pragma unroll
  for (int s = 0; s < 4; s++) wgmma72_acc(O, &P[4 * s], ring_desc(dv + s * 128 * V_STEP + (s < 2 ? 0 : (s - 1) * pad)));
}
template <class F = Nothing>
__device__ __forceinline__ void attn_step(const float (&Sc)[32], float (&Sn)[32], uint32_t (&Pc)[16], uint32_t (&Pp)[16], float (&O)[36],
                                          const uint32_t (&Q)[16], const uint32_t (&nm)[4], uint32_t dk, uint32_t dv, bool next, bool prev, F late = F()) {
  if (next) {
    WG_FENCE();
    qk_tile(Sn, Q, dk);
    qk_shift(Sn, nm);
  }
  if (prev) {
    WG_FENCE();
    pv_tile(O, Pp, dv, 0);
  }
  WG_COMMIT();
  SCHED();
#pragma unroll
  for (int i = 0; i < 16; i++) {
    if (i == 0) late();
    Pc[i] = pack2(ex2_hw(Sc[2 * i]), ex2_hw(Sc[2 * i + 1]));
    asm volatile("" : "+r"(Pc[i]));
  }
  SCHED();
}
constexpr uint32_t SM_TAPS = SM_BASE + SM_STG + 2 * TILE_BYTES + 6144;
__device__ __forceinline__ void load_taps(uint32_t (&tap)[15], int dir) {
  const uint32_t src = SM_TAPS + 7 * 128 + (here(threadIdx.x) & 31) * 4;
#pragma unroll
  for (int k = 0; k < 15; k++) tap[k] = lds32(src + dir * (k - 7) * 128);
}
__device__ __forceinline__ void attention_exact(float (&O)[36], const uint32_t (&Q)[16], const Scratch* sc, int bh, int lane) {
  const char* kb = (const char*)&sc->kv[bh][0][0][0];
  const char* vb = (const char*)&sc->kv[bh][1][0][0];
  const int g = lane >> 2, q = lane & 3;
  float m0 = -INFINITY, m1 = -INFINITY, l0 = 0.f, l1 = 0.f;
  float o[8][4] = {};
#pragma unroll 1
  for (int k0 = 0; k0 < T_SEQ; k0 += 8) {
    float s[4] = {0.f, 0.f, 0.f, 0.f};
#pragma unroll
    for (int c = 0; c < 8; c++) hmma8(s, &Q[2 * c], __ldcg((const uint32_t*)(kb + (k0 + g) * 128 + ((c ^ g) << 4) + q * 4)));
    float n0 = fmaxf(s[0], s[1]), n1 = fmaxf(s[2], s[3]);
    n0 = fmaxf(n0, __shfl_xor_sync(0xffffffffu, n0, 1)); n1 = fmaxf(n1, __shfl_xor_sync(0xffffffffu, n1, 1));
    n0 = fmaxf(m0, fmaxf(n0, __shfl_xor_sync(0xffffffffu, n0, 2))); n1 = fmaxf(m1, fmaxf(n1, __shfl_xor_sync(0xffffffffu, n1, 2)));
    const float a0 = ex2_hw(m0 - n0), a1 = ex2_hw(m1 - n1);
    m0 = n0; m1 = n1;
    const uint32_t pp[2] = {pack2(ex2_hw(s[0] - n0), ex2_hw(s[1] - n0)), pack2(ex2_hw(s[2] - n1), ex2_hw(s[3] - n1))};
    l0 = fmaf(l0, a0, bf_lo(pp[0]) + bf_hi(pp[0])); l1 = fmaf(l1, a1, bf_lo(pp[1]) + bf_hi(pp[1]));
#pragma unroll
    for (int j = 0; j < 8; j++) {
      const uint32_t v0 = __ldcg((const uint16_t*)(vb + (k0 + 2 * q) * 128 + ((j ^ (2 * q)) << 4) + g * 2));
      const uint32_t v1 = __ldcg((const uint16_t*)(vb + (k0 + 2 * q + 1) * 128 + ((j ^ (2 * q + 1)) << 4) + g * 2));
      o[j][0] *= a0; o[j][1] *= a0; o[j][2] *= a1; o[j][3] *= a1;
      hmma8(o[j], pp, v0 | (v1 << 16));
    }
  }
  l0 += __shfl_xor_sync(0xffffffffu, l0, 1); l1 += __shfl_xor_sync(0xffffffffu, l1, 1);
  O[32] = l0 + __shfl_xor_sync(0xffffffffu, l0, 2); O[34] = l1 + __shfl_xor_sync(0xffffffffu, l1, 2);
#pragma unroll
  for (int i = 0; i < 32; i++) O[i] = o[i >> 2][i & 3];
}

__device__ __forceinline__ uint32_t fill_entry(int f, int r) {
  int m, x = r, y, dx = 0;
  if (f < F_QKV || f >= 48) {
    const int i = f & 15;
    m = f < F_QKV ? M_FF1A : M_FF2A;
    if (i < 8) { x = 4 * r + ((0xE2u >> i) & 1) * 2; y = r ^ ((0xE790u >> (2 * i)) & 3); dx = 1; }
    else { m++; x = r ^ (((i >> 1) - 3) & 3); y = 4 * r + 2 * (i & 1); }
  } else if (f < F_KV) {
    const int i = f - F_QKV;
    m = M_QKV;
    if (i == 1 || i >= 5) { y = r ^ (i == 1 ? 0 : 2); }
    else { x = 4 + r; y = r ^ (i ? i - 1 : 0); dx = 4; }
  } else if (f >= F_PW1 && f < F_PW2) {
    m = M_PW1; y = r ^ (f - F_PW1); dx = 4;
  } else {
    m = f < F_PW1 ? M_WO : M_PW2; y = r ^ ((f & 1) * 2);
  }
  return m | (x << 4) | (y << 8) | (dx << 16);
}
__device__ __forceinline__ void tma_fill(uint32_t st, const CUtensorMap* map, uint32_t x, uint32_t y, uint32_t x2, uint32_t y2) {
  asm volatile("{\n.reg .pred p;\nelect.sync _|p, 0xffffffff;\n"
               "@p mbarrier.arrive.expect_tx.shared::cta.b64 _, [%1], 16384;\n"
               "@p cp.async.bulk.tensor.2d.shared::cluster.global.mbarrier::complete_tx::bytes [%0], [%2, {%3, %4}], [%1];\n"
               "@p cp.async.bulk.tensor.2d.shared::cluster.global.mbarrier::complete_tx::bytes [%0 + 8192], [%2, {%5, %6}], [%1];\n}"
               :: "r"(SM_BASE + st * STAGE_BYTES), "r"(SM_BASE + SM_FULL + st * 8), "l"(map), "r"(x), "r"(y), "r"(x2), "r"(y2) : "memory");
}
template <int F0, int N> __device__ __forceinline__ void weight_fills(const Params& p, uint32_t entry) {
  uint32_t st = F0 % NSTAGE, parity = ((F0 / NSTAGE) & 1) ^ 1, e = __shfl_sync(0xffffffffu, entry, 0);
#pragma unroll 1
  for (int i = 1; i <= N; i++) {
    const uint32_t x = (e << 2) & 0x3C0, y = (e >> 2) & 0x3FC0, dx = (e >> 16) << 6;
    const CUtensorMap* map = &p.map[e & 15];
    e = __shfl_sync(0xffffffffu, entry, i);
    mbar_wait(SM_BASE + SM_EMPTY + st * 8, parity);
    tma_fill(st, map, x, y, x + dx, dx ? y : y ^ 64);
    if (++st == NSTAGE) { st = 0; parity ^= 1; }
  }
}
template <int KIND, int J> __device__ __forceinline__ uint32_t kv_fill(const uint4* kv, uint32_t want) {
  constexpr uint32_t st = (J < 6 ? 4 * (J >> 1) : 0) + (J & 1) + 2 * KIND;
  mbar_wait(SM_BASE + SM_EMPTY + st * 8, J < 6);
  uint32_t have, spin = 0;
#pragma unroll 1
  do {
    asm volatile("ld.volatile.shared.u32 %0, [%1];" : "=r"(have) : "r"(SM_BASE + SM_KVRDY + KIND * 4) : "memory");
    have &= want;
  } while (!have && ++spin < (SPIN_LIMIT << 4));
  const uint32_t tile = (__ffs(KIND ? want : have) - 1) & 15;
  asm volatile("{\n.reg .pred p;\nelect.sync _|p, 0xffffffff;\n"
               "@p mbarrier.arrive.expect_tx.shared::cta.b64 _, [%1], 16384;\n"
               "@p cp.async.bulk.shared::cluster.global.mbarrier::complete_tx::bytes [%0], [%2], 16384, [%1];\n}"
               :: "r"(SM_BASE + st * STAGE_BYTES), "r"(SM_BASE + SM_FULL + st * 8), "l"(kv + (KIND * 16 + tile) * 512) : "memory");
  PROF_AT(256 + 512 + (10 + KIND * 8 + J) * 4);
  return 1u << tile;
}
template <int J> __device__ __forceinline__ void kv_fills(const uint4* kv, uint32_t todo, uint32_t b1, uint32_t b2) {
  if constexpr (J >= 2) kv_fill<1, J - 2>(kv, b2);
  uint32_t b0 = 0;
  if constexpr (J < 8) b0 = kv_fill<0, J>(kv, J == 7 ? 0x4000u : todo);
  if constexpr (J < 9) kv_fills<J + 1>(kv, todo & ~b0, b0, b1);
}
__device__ __forceinline__ void reset_mailboxes(Scratch* sc, int half, int lane, uint32_t t_start) {
  while (clock_now() - t_start < TC) {}
#pragma unroll 1
  for (int i = half * 8; i < half * 9 + 8; i++) {
    const uint32_t t0 = clock_now();
    uint4* dst = &sc->x[blockIdx.x ^ (i < 12 ? (i >> 2) + 1 : 0)][i * 128 + lane];
#pragma unroll
    for (int k = 0; k < 4; k++) st_vec(dst + 32 * k, 0u, 0u, 0u, 0u);
    while (clock_now() - t0 < CLR_PACE) {}
  }
  bar_arrive(BAR_RST, 192);
  PROF_AT(256 + 512 + 28 * 4);
  asm volatile("fence.acq_rel.gpu;" ::: "memory");
  __syncwarp();
  announce<1>(sc, lane == 0);
  PROF_AT(256 + 512 + 2 * 4);
}
__device__ __forceinline__ void l2_prefetch(const void* p, uint32_t total, int b) {
  const uint32_t part = total / NCTA;
  asm volatile("cp.async.bulk.prefetch.L2.global [%0], %1;" :: "l"((const char*)p + (size_t)b * part), "r"(part) : "memory");
}

__global__ void __launch_bounds__(384, 1) conformer_kernel(Scratch* __restrict__ sc, __nv_bfloat16* __restrict__ out,
                                                           const __nv_bfloat16* __restrict__ dw, const __nv_bfloat16* __restrict__ xin,
                                                           const __nv_bfloat16* __restrict__ w_ff1a, const __grid_constant__ Params p) {
  extern __shared__ __align__(1024) uint8_t smem[];
  const int tid = threadIdx.x, lane = tid & 31;
  const uint32_t t_start = clock_now();
  const int b = blockIdx.x, r = b & 3, batch = b >> 6, t = (b >> 2) & 15;
  if ((uint32_t)__cvta_generic_to_shared(smem) != SM_BASE) return;
  PROF_AT(256 + (tid >> 7) * 256);
  PROF_TIME(30);
  const uint32_t crow = ((tid >> 1) & 48) + (lane >> 3);
  const uint32_t cdst = SM_BASE + crow * 128 + (((lane & 7) ^ (lane >> 3)) << 4);
  if (tid < 128) {
    const uint32_t g0 = batch * T_SEQ + t * 64 + crow, o = r * 128 + (lane & 7) * 16;
    const uint32_t lo = min(g0, 2 * T_SEQ - 5) * 512 + o, hi = min(g0 + 8, 2 * T_SEQ - 5) * 512 + o;
#pragma unroll
    for (int c = 0; c < 4; c++) {
#pragma unroll
      for (int i = 0; i < 4; i++)
        cp_async16((cdst ^ ((i & 1) << 6)) + SM_STG + (3 - c) * TILE_BYTES + i * 512, (const char*)xin + (((i & 2) ? hi : lo) ^ (c << 7)) + (i & 1) * 2048);
      asm volatile("cp.async.commit_group;" ::: "memory");
    }
  } else if (tid < 256) {
    const char* src = (const char*)w_ff1a + (64 * r + crow) * 2048 + r * 512 + (lane & 7) * 16;
#pragma unroll
    for (int c = 0; c < 4; c++) {
#pragma unroll
      for (int i = 0; i < 4; i++) cp_async16((cdst ^ ((i & 1) << 6)) + c * TILE_BYTES + i * 512, src + i * 8192 + c * 128);
      asm volatile("cp.async.commit_group;" ::: "memory");
    }
  }
  const int cw = __shfl_sync(0xffffffffu, tid >> 5, 0), wg = cw >> 2, w = cw & 3;

  if (wg == 2) {
    asm volatile("setmaxnreg.dec.sync.aligned.u32 40;");
    if (cw == 8) {
      if (lane == 0) {
        asm volatile("prefetch.tensormap [%0];" :: "l"(&p.map[M_FF1A]) : "memory");
#pragma unroll
        for (int i = 0; i < NSTAGE; i++) mbar_init(SM_BASE + SM_FULL + i * 8, 1);
        fence_async_smem();
      }
      __syncwarp();
      bar_arrive(0, 320);
      while (clock_now() - t_start < TF) {}
      PROF_MARK(9);
#pragma unroll
      for (int f = 2; f < 8; f++) {
        const uint32_t x = 256 * r + ((0xE2u >> f) & 1) * 128, y = (r ^ ((0xE790u >> (2 * f)) & 3)) * 64;
        tma_fill(f, &p.map[M_FF1A], x, y, x + 64, y);
      }
      PROF_MARK(1);
      uint32_t entry[2];
#pragma unroll 1
      for (int i = 0; i < 2; i++) { entry[1] = fill_entry(8 + i * 32 + lane, r); if (i == 0) entry[0] = entry[1]; }
      bar_sync(BAR_INIT, 64);
      weight_fills<8, F_KV - 8>(p, entry[0]);
      kv_fills<0>(sc->kv[batch * 4 + r][0][0], 0x1555u, 0u, 0u);
      weight_fills<F_WO, F_TOTAL - F_WO>(p, entry[1]);
    } else if (here(cw) != 11) {
      const int kind = w - 1;
      const uint32_t prev = launch_index(sc);
      if (kind == 0) {
        if (lane == 0) {
#pragma unroll
            for (int i = 0; i < NSTAGE; i++) mbar_init(SM_BASE + SM_EMPTY + i * 8, 4);
          sts64(SM_BASE + SM_KVRDY, 0u, 0u);
        }
        __syncwarp();
        bar_arrive(0, 320);
        bar_arrive(BAR_INIT, 64);
        if (lane == 0) {
          const uint32_t t0 = t_start;
          while (clock_now() - t0 < PF0) {}
          while (clock_now() - t0 < PF1) {}
          asm volatile("prefetch.tensormap [%0];" :: "l"(&p.map[M_FF1B]) : "memory");
          l2_prefetch(p.w_ff1b, 1024 * 256 * 2, b);
          while (clock_now() - t0 < PF2) {}
          l2_prefetch(p.w_qkv, 256 * 768 * 2, b);
          l2_prefetch(p.w_pw1, 256 * 512 * 2, b);
          l2_prefetch(p.w_ff2a, 256 * 1024 * 2, b);
          while (clock_now() - t0 < PF3) {}
          if (b < 15) l2_prefetch(dw, 512 * NCTA, b);
          l2_prefetch(p.w_o, 256 * 256 * 2, b);
          l2_prefetch(p.w_pw2, 256 * 256 * 2, b);
          l2_prefetch(p.w_ff2b, 1024 * 256 * 2, b);
#pragma unroll
          for (int i = M_QKV; i < M_COUNT; i++) asm volatile("prefetch.tensormap [%0];" :: "l"(&p.map[i]) : "memory");
        }
        __syncwarp();
      } else {
        reset_mailboxes(sc, 1, lane, t_start);
      }
      const uint32_t* flag = sc->flag[batch * 4 + r][kind * 16 + (lane & 15)];
      uint32_t spin = 0, ready;
#pragma unroll 1
      do {
        uint32_t v;
        asm volatile("ld.relaxed.gpu.global.u32 %0, [%1];" : "=r"(v) : "l"(flag) : "memory");
        ready = __ballot_sync(0xffffffffu, v - 1 == prev);
        asm volatile("st.volatile.shared.u32 [%0], %1;" :: "r"(SM_BASE + SM_KVRDY + kind * 4), "r"(ready & (ready >> 1)) : "memory");
        if (spin == 0) {
          if (kind == 0) bar_sync(BAR_K, 160); else bar_sync(BAR_V, 160);
          if (lane == 0) {
            PROF_MARK(4 + kind * 2);
            asm volatile("cp.async.bulk.global.shared::cta.bulk_group [%0], [%1], %2;"
                         :: "l"(sc->kv[batch * 4 + r][kind][t]), "r"(SM_BASE + SM_STG + kind * TILE_BYTES), "r"(TILE_BYTES) : "memory");
            asm volatile("cp.async.bulk.commit_group;\ncp.async.bulk.wait_group 0;" ::: "memory");
            asm volatile("st.relaxed.gpu.global.u32 [%0], %1;" :: "l"(sc->flag[batch * 4 + r][kind * 16 + t]), "r"(prev + 1) : "memory");
            PROF_MARK(5 + kind * 2);
          }
          __syncwarp();
        }
      } while (ready != 0xffffffffu && ++spin < SPIN_LIMIT);
      if (kind) {
        bar_sync(BAR_TAP, 64);
#pragma unroll 5
        for (int k = 0; k < 15; k++) {
          uint32_t v = __ldg((const uint32_t*)(dw + k * DM + 64 * r) + lane);
          asm("mul.rn.bf16x2 %0, %0, %1;" : "+r"(v) : "r"(0x3F003F00u));
          sts32(SM_TAPS + k * 128 + lane * 4, v);
        }
        bar_arrive(BAR_MERGE, 288);
      }
    } else {
      const uint32_t* watch = sc->step[(b & ~3) + (lane & 3)];
      uint32_t seen;
      asm volatile("ld.relaxed.gpu.global.u32 %0, [%1];" : "=r"(seen) : "l"(watch) : "memory");
      reset_mailboxes(sc, 0, lane, t_start);
      uint32_t want = (seen & ~15u) + 2;
#pragma unroll 1
      for (int k = 1; k < 8; k++) {
        want += 2;
        uint32_t spin = 0;
#pragma unroll 1
        while (__any_sync(0xffffffffu, (int)(seen - want) < 0) && ++spin < SPIN_LIMIT)
          asm volatile("ld.relaxed.gpu.global.u32 %0, [%1];" : "=r"(seen) : "l"(watch) : "memory");
        bar_arrive(BAR_GO, 160);
        PROF_MARK(32 + k);
      }
    }
  } else {
    asm volatile("setmaxnreg.inc.sync.aligned.u32 232;");
    const int q = lane & 3, th = tid & 127;
    constexpr uint32_t stg = SM_BASE + SM_STG;
    const uint32_t mrow = 16 * w + (lane & 15);
    const uint32_t maddr = stg + mrow * 128 + (((lane >> 4) ^ (lane & 7)) << 4);
    const uint32_t qslot = stg + 2 * TILE_BYTES + w * 2048 + lane * 16;
    uint4* const xp = &sc->x[b][th];
    const int nvalid = T_SEQ - t * 64, row0 = 16 * w + (lane >> 2);

    uint32_t A[4][16];
    uint32_t st[4], sent = 0;
    bar_sync(0, 320);
    if (wg == 0) {
      RowAcc ra = {};
      cp_async_wait(0);
      __syncwarp();
      PROF_MARK0(45);
#pragma unroll
      for (int c = 0; c < 4; c++) tile_load(maddr + (3 - c) * TILE_BYTES, A[c]);
      row_sums(ra, A[0]); row_gram(ra, A[0]); row_sums(ra, A[1]); row_gram(ra, A[1]);
      pin(ra.s[0]); pin(ra.s[1]); pin(ra.u[0]); pin(ra.u[1]); pin(ra.v[0]); pin(ra.v[1]);
      SCHED();
      row_sums(ra, A[2]); row_sums(ra, A[3]); row_gram(ra, A[2]); row_gram(ra, A[3]);
      const float m0 = (ra.s[0][0] + ra.s[1][0]) * (1.f / DM), m1 = (ra.s[0][2] + ra.s[1][2]) * (1.f / DM);
      st[0] = pack2(m0, m0); st[1] = pack2(m1, m1);
      centre(A[0], st[0], st[1]);
      const float2 sq = row_squares(ra, lane & 4);
      st[2] = __float_as_uint(fmaf(-m0, m0, sq.x * (1.f / DM))); st[3] = __float_as_uint(fmaf(-m1, m1, sq.y * (1.f / DM)));
    } else {
      if (th < 112) sts128(SM_BASE + SM_CS + th * 16, 0, 0, 0, 0);
      sts32(SM_BASE + SM_EYE + th * 4, th >= 96 ? 0x3F803F80u : ((th & 32) == 0 && (th & 3) == ((th >> 3) & 3)) ? (0x3F00u << ((th & 4) * 4)) : 0u);
#pragma unroll
      for (int i = 0; i < 2; i++) {
        cp_async_wait(2 - 2 * i);
        fence_async_smem();
        bar_sync(BAR_WG1, 128);
        if (th == 0) mbar_arrive(SM_BASE + SM_FULL + i * 8);
      }
      PROF_MARK(6);
      const uint32_t tag = ~launch_index(sc) & 1;
      mbar_wait(SM_BASE + SM_FULL + 4 * 8, 0);
      PROF_MARK(5);
      if (b < 72) {
        const int strip = b >> 1;
        const __nv_bfloat16* wp; int ld;
        if (strip < 12) { wp = p.w_qkv + strip * 64; ld = 768; }
        else if (strip < 20) { wp = p.w_pw1 + (strip - 12) * 64; ld = 512; }
        else { wp = p.w_ff2a + (strip - 20) * 64; ld = 1024; }
        const uint4* src = (const uint4*)(wp + (size_t)((b & 1) * 128 + (th >> 3)) * ld) + (th & 7);
        uint4 v[8];
#pragma unroll
        for (int i = 0; i < 8; i++) v[i] = __ldg(src + i * 2 * ld);
        mbar_wait(SM_BASE + SM_EMPTY + CS_AFTER * 8, 0);
        float c[8] = {0.f, 0.f, 0.f, 0.f, 0.f, 0.f, 0.f, 0.f};
#pragma unroll
        for (int i = 0; i < 8; i++) {
          c[0] += bf_lo(v[i].x); c[1] += bf_hi(v[i].x); c[2] += bf_lo(v[i].y); c[3] += bf_hi(v[i].y);
          c[4] += bf_lo(v[i].z); c[5] += bf_hi(v[i].z); c[6] += bf_lo(v[i].w); c[7] += bf_hi(v[i].w);
        }
#pragma unroll 1
        for (int m = 8; m <= 16; m <<= 1)
#pragma unroll
          for (int k = 0; k < 8; k++) c[k] += __shfl_xor_sync(0xffffffffu, c[k], m);
        if (lane < 8) {
          const uint32_t a = SM_BASE + SM_CS + w * 256 + lane * 32;
          sts128(a, __float_as_uint(c[0]), __float_as_uint(c[1]), __float_as_uint(c[2]), __float_as_uint(c[3]));
          sts128(a + 16, __float_as_uint(c[4]), __float_as_uint(c[5]), __float_as_uint(c[6]), __float_as_uint(c[7]));
        }
        bar_sync(BAR_WG1, 128);
        if (th < 16) {
          float o[4] = {0.f, 0.f, 0.f, 0.f};
#pragma unroll
          for (int k = 0; k < 4; k++) {
            uint32_t e[4];
            lds128(SM_BASE + SM_CS + k * 256 + th * 16, e[0], e[1], e[2], e[3]);
#pragma unroll
            for (int i = 0; i < 4; i++) o[i] += __uint_as_float(e[i]);
          }
          st_vec(&sc->cs[b & 1][strip * 16 + th], (__float_as_uint(o[0]) & ~1u) | tag, __float_as_uint(o[1]), __float_as_uint(o[2]), __float_as_uint(o[3]));
        }
      } else {
        mbar_wait(SM_BASE + SM_EMPTY + CS_AFTER * 8, 0);
      }
      bar_sync(BAR_WG1, 128);
      PROF_MARK(2);
      if (th < 72) {
        const int j = th >> 3, i = (th & 7) * 2;
        int src;
        if (j < CS_PW1) src = 320 + 64 * r + 16 * j;
        else if (j < CS_QKV) src = 192 + (j - CS_PW1) * 64 + 16 * r;
        else src = ((j - CS_QKV + 1) % 3) * 64 + 16 * r;
        uint32_t e[16], hi[4], lo[4], spin = 0;
#pragma unroll 1
        do {
#pragma unroll
          for (int k = 0; k < 4; k++) ld_vec(&sc->cs[k >> 1][src + i + (k & 1)], e[4 * k], e[4 * k + 1], e[4 * k + 2], e[4 * k + 3]);
        } while ((miss(e, tag) & 1u) && ++spin < SPIN_LIMIT);
#pragma unroll
        for (int k = 0; k < 4; k++) e[4 * k] &= ~1u;
#pragma unroll
        for (int k = 0; k < 4; k++) {
          const float c0 = __uint_as_float(e[2 * k]) + __uint_as_float(e[8 + 2 * k]), c1 = __uint_as_float(e[2 * k + 1]) + __uint_as_float(e[9 + 2 * k]);
          hi[k] = pack2(c0, c1);
          lo[k] = pack2(c0 - bf_lo(hi[k]), c1 - bf_hi(hi[k]));
        }
        const uint32_t a = SM_BASE + SM_CS + j * 256 + i * 8;
        sts128(a ^ ((a >> 3) & 0x70), hi[0], hi[1], hi[2], hi[3]);
        sts128((a + 128) ^ (((a + 128) >> 3) & 0x70), lo[0], lo[1], lo[2], lo[3]);
      }
      fence_async_smem();
      PROF_MARK(4);
      bar_arrive(BAR_CS, 256);
    }

#pragma unroll 1
    for (uint32_t pass = 0; pass < 2; pass++) {
      uint32_t Q[16], shift;
      if (wg == 0) {
        float acc[4][32];
        uint32_t H[4][16];
        if (!pass) { PROF_MARK(47); ACQUIRE(0); }
        mma_tile<true>(acc[0], A[0], LO(0)); mma_tile<true>(acc[1], A[0], HI(0));
        if (pass) {
          gather_first<1, X_AG0>(A, st, sc, xp, 1, sent, [&] { mma_tile<true>(acc[2], A[0], LO(1)); mma_tile<true>(acc[3], A[0], HI(1)); });
        } else {
          ACQUIRE(1);
          mma_tile<true>(acc[2], A[0], LO(1)); mma_tile<true>(acc[3], A[0], HI(1));
          centre(A[1], st[0], st[1]);
          acquire_n<2, 3>();
        }
        mma_tile<false>(acc[0], A[1], LO(2)); mma_tile<false>(acc[1], A[1], HI(2));
        if (pass) {
          gather_rest<1, X_AG0>(A, xp, 1);
          RELEASE(F_WO - 2 + NREL, F_PW2 + 1);
        } else {
          centre(A[2], st[0], st[1]); centre(A[3], st[0], st[1]);
        }
        PROF_MARK2(2, 18);
        mma_tile<false>(acc[0], A[2], LO(3)); mma_tile<false>(acc[0], A[3], LO(4));
        WG_WAIT(4);
        RELEASE(0, 1);
        uint32_t mu[4] = {0u, 0u, 0u, 0u};
        float rs0, rs1, tn[2][4];
        if (pass) {
          const RowNorm n = stat_finish(sc, st, 1, 0.5f);
          rs0 = n.rs0; rs1 = n.rs1;
          mean_frag(mu, n, q == 0);
        } else {
          const int src = (lane & 28) | (lane >> 3);
          rs0 = 0.5f * rsqrt_hw(fmaxf(__uint_as_float(__shfl_sync(0xffffffffu, st[2], src)), 0.f) + LN_EPS);
          rs1 = 0.5f * rsqrt_hw(fmaxf(__uint_as_float(__shfl_sync(0xffffffffu, st[3], src)), 0.f) + LN_EPS);
        }
        pin(mu);
        mma_fold<2 * CS_FF2>(acc[0], mu);
        mma_tile<false>(acc[1], A[2], HI(3));
#define SEGS(a, b) silu_segs<a, b>(acc, tn, H, rs0, rs1)
        WG_WAIT(1); pin(acc[0]);
        SEGS(0, 1);
        mma_tile_fold<2 * CS_FF2 + 2>(acc[1], A[3], HI(4), mu);
        SEGS(1, 3);
        uint32_t ok = probe_n<5, 1>();
        SEGS(3, 4);
        settle_n<5, 1>(ok);
        mma_tile<false>(acc[2], A[1], LO(5));
        SEGS(4, 5);
        ok = probe_n<6, 1>();
        SEGS(5, 6);
        settle_n<6, 1>(ok);
        mma_tile<false>(acc[2], A[2], LO(6));
        SEGS(6, 8);
        WG_WAIT(2); pin(acc[1]);
        RELEASE(2, 4);
        ok = probe_n<7, 1>();
        SEGS(8, 9);
        settle_n<7, 1>(ok);
        mma_tile_fold<2 * CS_FF2 + 4>(acc[2], A[3], LO(7), mu);
        SEGS(9, 12);
        mma_tile<false>(acc[3], A[1], HI(5));
        SEGS(12, 14);
        mma_tile<false>(acc[3], A[2], HI(6));
        SEGS(14, 16);
        WG_WAIT(2); pin(acc[2]);
        SEGS(16, 17);
        mma_tile_fold<2 * CS_FF2 + 6>(acc[3], A[3], HI(7), mu);
        SEGS(17, 19);
        ok = probe_n<8, 2>();
        SEGS(19, 20);
        settle_n<8, 2>(ok);
        mma_tile_reuse(acc[1], H[0], LO(8));
        SEGS(20, 22);
        mma_tile<false>(acc[1], H[1], HI(8));
        SEGS(22, 24);
        WG_WAIT(2); pin(acc[3]);
        RELEASE(5, 7);
        SEGS(24, 26);
        mma_tile<false>(acc[1], H[2], LO(9));
        SEGS(26, 27);
        ok = probe_n<10, 2>();
        SEGS(27, 28);
        settle_n<10, 2>(ok);
        mma_tile_reuse(acc[2], H[0], LO(10));
        SEGS(28, 31);
        mma_tile<false>(acc[2], H[1], HI(10));
        SEGS(31, 34);
#undef SEGS
        PROF_MARK2(3, 19);
        const uint32_t rtag = here(pass ^ 1);
        const uint4* rs_in = xp + X_RS;
        mma_tile<false>(acc[1], H[3], HI(9));
        mma_tile<false>(acc[2], H[2], LO(11));
        ok = probe_n<12, 2>();
        uint4* rs_out = peer<1>(xp) + X_RS;
        mma_tile<false>(acc[2], H[3], HI(11));
        settle_n<12, 2>(ok);
        if (!pass) bar_sync(BAR_RST, 192);
        WG_WAIT(2); pin(acc[1]);
        RELEASE(8, 9);
        send_half<0>(rs_out, acc[1], rtag);
        mma_tile_reuse(acc[3], H[0], LO(12));
        SCHED();
        send_half<1>(rs_out, acc[1], rtag);
        mma_tile<false>(acc[3], H[1], HI(12));
        rs_out = peer<2>(xp) + X_RS + 512;
        WG_WAIT(2); pin(acc[2]);
        send_half<0>(rs_out, acc[2], rtag);
        mma_tile<false>(acc[3], H[2], LO(13));
        SCHED();
        ok = probe_n<14, 2>();
        send_half<1>(rs_out, acc[2], rtag);
        mma_tile<false>(acc[3], H[3], HI(13));
        settle_n<14, 2>(ok);
        mma_tile_reuse(acc[1], H[0], LO(14));
        rs_out = peer<3>(xp) + X_RS + 1024;
        announce(sc, tid == 0);
        fetch(rs_in, A[1]);
        SCHED();
        mma_tile<false>(acc[1], H[1], HI(14));
        WG_WAIT(2); pin(acc[3]);
        send_half<0>(rs_out, acc[3], rtag);
        send_half<1>(rs_out, acc[3], rtag);
        if (TIMED) sent = clock_now();
        mma_tile<false>(acc[1], H[2], LO(15)); mma_tile<false>(acc[1], H[3], HI(15));
        SCHED();
        fetch(rs_in + 512, A[2]);
        SCHED();
        res_load(maddr, acc[2]);
        if (TIMED) { while (clock_now() - sent < RD) {} }
        bar_sync(BAR_GO, 160);
        fetch(rs_in + 1024, A[3]);
        if (!pass) acquire_n<F_QKV, 3>();
        {
          uint32_t spin = 0;
          while (__builtin_expect(stale(miss(A[1], rtag) | miss(A[2], rtag) | miss(A[3], rtag)), 0) && ++spin < SPIN_LIMIT) {
            if (stale(miss(A[1], rtag) | miss(A[2], rtag))) { fetch(rs_in, A[1]); fetch(rs_in + 512, A[2]); }
            fetch(rs_in + 1024, A[3]);
          }
        }
        announce(sc, tid == 0 && !pass);
        mma_add_half(acc[2], A[1]);
        mma_add_half(acc[2], A[2]);
        mma_add_half(acc[2], A[3]);
        PROF_MARK2(4, 20);
        WG_WAIT(0); pin(acc[2]); pin(acc[1]);
#pragma unroll
        for (int i = 0; i < 16; i++) A[0][i] = pack2(fmaf(acc[1][2 * i], 0.5f, acc[2][2 * i]), fmaf(acc[1][2 * i + 1], 0.5f, acc[2][2 * i + 1]));
        if (pass) {
          PROF_MARK(21);
          stat_publish(A[0], sc, here(th), 0);
          stat_fetch(sc, st);
          const RowNorm fn = stat_finish(sc, st, 0, 1.f);
          const float nm0 = -fn.m0 * fn.rs0, nm1 = -fn.m1 * fn.rs1;
#pragma unroll
          for (int i = 0; i < 16; i++) {
            const float rs = (i & 1) ? fn.rs1 : fn.rs0, nm = (i & 1) ? nm1 : nm0;
            A[0][i] = pack2(fmaf(bf_lo(A[0][i]), rs, nm), fmaf(bf_hi(A[0][i]), rs, nm));
          }
          tile_store(here(maddr), A[0]);
          __syncwarp();
          const int row = 16 * w + (lane >> 3);
          uint4* dst = (uint4*)(out + ((size_t)batch * T_SEQ + t * 64 + row) * DM + 64 * r) + (lane & 7);
          const uint32_t src = stg + row * 128 + (((lane & 7) ^ (lane >> 3)) << 4);
#pragma unroll
          for (int i = 0; i < 4; i++) {
            uint4 v;
            lds128((src ^ ((i & 1) << 6)) + i * 512, v.x, v.y, v.z, v.w);
            if (row + 4 * i < nvalid) dst[i * 4 * (DM / 8)] = v;
          }
          PROF_MARK(22);
          PROF_TIME(31);
          break;
        }
        send_residual(A[0], sc, xp, maddr, 1, sent);
        PROF_MARK(5);
        mma_tile<true>(acc[0], A[0], LO(F_QKV)); mma_tile<true>(acc[1], A[0], HI(F_QKV));
        gather_first<1, X_AG0>(A, st, sc, xp, 1, sent, [&] { mma_tile<true>(acc[2], A[0], LO(F_QKV + 1)); });
        mma_tile<false>(acc[0], A[1], LO(F_QKV + 2)); mma_tile<false>(acc[1], A[1], HI(F_QKV + 2));
        acquire_n<F_QKV + 3, 3>();
        bar_sync(BAR_CS, 256);
        gather_rest<1, X_AG0>(A, xp, 1);
        PROF_MARK(6);
        mma_tile<false>(acc[0], A[2], LO(F_QKV + 3)); mma_tile<false>(acc[0], A[3], LO(F_QKV + 4));
        SCHED();
        {
          const RowNorm n = stat_finish(sc, st, 1, 1.f);
          rs0 = row0 < nvalid ? n.rs0 : 0.f; rs1 = row0 + 8 < nvalid ? n.rs1 : 0.f;
          mean_frag(mu, n, q == 3);
        }
        mma_fold<2 * CS_QKV - 6>(acc[0], mu);
        RELEASE(10, 15);
        WG_WAIT(0); pin(acc[0]);
        scale_pack(acc[0], A[0], rs0, rs1);
        tile_store(here(maddr), A[0]);
        SCHED();
        mma_tile<false>(acc[1], A[2], HI(F_QKV + 3));
        fence_async_smem();
        bar_arrive(BAR_K, 160);
        mma_tile_fold<2 * CS_QKV - 4>(acc[1], A[3], HI(F_QKV + 4), mu);
        mma_tile<false>(acc[2], A[1], HI(F_QKV + 1)); mma_tile<false>(acc[2], A[2], LO(F_QKV + 5));
        WG_WAIT(2); pin(acc[1]);
        scale_pack(acc[1], Q, rs0, rs1);
        tile_store(here(maddr) + TILE_BYTES, Q);
        fence_async_smem();
        bar_arrive(BAR_V, 160);
        mma_tile_fold<2 * CS_QKV - 2>(acc[2], A[3], HI(F_QKV + 5), mu);
        WG_WAIT(0); pin(acc[2]);
        scale_pack(acc[2], Q, rs0 * SM_SCALE_LOG2, rs1 * SM_SCALE_LOG2);
        frag_store(here(qslot), Q);
        {
          uint32_t d[4] = {0u, 0u, 0u, 0u};
#pragma unroll
          for (int i = 0; i < 16; i++) asm("fma.rn.bf16x2 %0, %1, %2, %0;" : "+r"(d[i & 3]) : "r"(Q[i]), "r"(A[0][i]));
          float s0 = (bf_lo(d[0]) + bf_hi(d[0])) + (bf_lo(d[2]) + bf_hi(d[2])), s1 = (bf_lo(d[1]) + bf_hi(d[1])) + (bf_lo(d[3]) + bf_hi(d[3]));
          shift = pack2(-s0, -s1);
          sts32(SM_BASE + SM_CS + 2 * CS_QKV * 128 + here(th) * 4, shift);
        }
        bar_arrive(BAR_Q, 256);
        RELEASE(F_QKV, F_QKV + 5);
      } else {
        bar_sync(BAR_Q, 256);
#pragma unroll
        for (int s = 0; s < 4; s++) lds128(qslot + s * 512, Q[4 * s], Q[4 * s + 1], Q[4 * s + 2], Q[4 * s + 3]);
        shift = lds32(SM_BASE + SM_CS + 2 * CS_QKV * 128 + th * 4);
        if (w < 2) {
          const uint32_t v = w ? 0u : 0x3F803F80u;
#pragma unroll
          for (int s = 0; s < 4; s++) sts128(qslot + s * 512, v, v, v, v);
          fence_async_smem();
        }
        if (w == 3) bar_arrive(BAR_TAP, 64);
      }
      PROF_MARK(7);

      float O[36];
      {
        float S[2][32];
        uint32_t P[2][16], nm[4] = {shift & 0xFFFFu, shift >> 16, 0u, 0u};
        pin(Q); pin(nm);
        uint32_t sk = wg, sv = F_SPARE % NSTAGE + wg;
        mbar_wait(SM_BASE + SM_FULL + sv * 8, 1);
        if (wg == 1) bar_sync(BAR_ATT, 256);
        mbar_wait(SM_BASE + SM_FULL + sk * 8, 0);
        PROF_MARK(8);
        WG_FENCE();
        wgmma64_set<0>(S[0], nm, (uint64_t)((SM_BASE + SM_ONE) >> 4));
#pragma unroll
        for (int s = 0; s < 4; s++) wgmma64_acc<0>(S[0], &Q[4 * s], ring_desc(RING_K + sk * 1024 + s * 2));
        WG_COMMIT();
        SCHED();
#pragma unroll
        for (int i = 0; i < 36; i++) O[i] = 0.f;
#pragma unroll
        for (int i = 0; i < 32; i++) S[1][i] = 0.f;
#pragma unroll
        for (int i = 0; i < 16; i++) P[1][i] = 0u;
        pin(O); pin(S[1]); pin(P[1]);
        SCHED();
        WG_WAIT(0); pin(S[0]);
        if (wg == 0) bar_sync(BAR_ATT, 256);
#pragma unroll 1
        for (int it = 0; it < 4; it++) {
          const uint32_t sn = it >= 2 ? wg : sk + 4;
          uint32_t ok = 1;
          attn_step(S[0], S[1], P[0], P[1], O, Q, nm, RING_K + sk * 1024 + 512, RING_V + (sv * 1024 + 512) * V_STEP, true, it > 0, [&] {
            mbar_probe(ok, SM_BASE + SM_FULL + sn * 8, it >= 2);
            mbar_probe(ok, SM_BASE + SM_FULL + (sk + 2) * 8, it == 3);
          });
          PROF_MARK(24 + it * 3);
          if (__builtin_expect(!ok, 0)) {
            mbar_wait(SM_BASE + SM_FULL + sn * 8, it >= 2);
            mbar_wait(SM_BASE + SM_FULL + (sk + 2) * 8, it == 3);
          }
          WG_WAIT(0); pin(O); pin(S[1]); pin(P[1]);
          asm volatile("{\n.reg .pred p;\nsetp.eq.u32 p, %2, 0;\n@p mbarrier.arrive.shared::cta.b64 _, [%0];\n@p mbarrier.arrive.shared::cta.b64 _, [%1];\n}"
                       :: "r"(SM_BASE + SM_EMPTY + sk * 8), "r"(SM_BASE + SM_EMPTY + sv * 8), "r"(lane) : "memory");
          PROF_MARK(25 + it * 3);
          sv = sk + 2; sk = sn;
          attn_step(S[1], S[0], P[1], P[0], O, Q, nm, RING_K + sk * 1024, RING_V + (sv * 1024) * V_STEP, it < 3, true);
          WG_WAIT(0); pin(O); pin(S[0]); pin(P[0]);
          PROF_MARK(26 + it * 3);
        }
        WG_FENCE();
        pv_tile(O, P[1], RING_V + (sv * 1024 + 512) * V_STEP, wg << 22);
        WG_COMMIT();
        announce<1>(sc, th == 0);
      }

      const int dir = cw == 0 ? -1 : 1;
      uint32_t tap[15];
      if (wg == 1) {
        const uint32_t mo = stg + here(th) * 16;
        uint32_t other[36];
        bar_sync(BAR_MERGE, 288);
#pragma unroll
        for (int i = 0; i < 9; i++) lds128(mo + i * 2048 + (i >> 3) * 4096, other[4 * i], other[4 * i + 1], other[4 * i + 2], other[4 * i + 3]);
        SCHED();
        WG_WAIT(0); pin(O);
        PROF_MARK(9);
#pragma unroll
        for (int i = 0; i < 36; i++) O[i] += __uint_as_float(other[i]);
        const bool safe = O[32] > 0x1p-60f && O[32] < 0x1p60f && O[34] > 0x1p-60f && O[34] < 0x1p60f;
        if (__builtin_expect(__any_sync(0xffffffffu, !safe), 0)) attention_exact(O, Q, sc, batch * 4 + r, lane);
        const float i0 = rcp_hw(O[32]), i1 = rcp_hw(O[34]);
#pragma unroll
        for (int i = 0; i < 16; i++) { const float v = (i & 1) ? i1 : i0; A[0][i] = pack2(O[2 * i] * v, O[2 * i + 1] * v); }
        publish(xp + X_AG1, A[0], 0);
#pragma unroll
        for (int s = 0; s < 4; s++) sts128(mo + s * 2048, A[0][4 * s], A[0][4 * s + 1], A[0][4 * s + 2], A[0][4 * s + 3]);
        bar_arrive(BAR_HALF, 256);
        load_taps(tap, 1);
      } else {
        const uint32_t mo = stg + here(th) * 16;
        WG_WAIT(0); pin(O);
        PROF_MARK(9);
#pragma unroll
        for (int i = 0; i < 9; i++)
          sts128(mo + i * 2048 + (i >> 3) * 4096, __float_as_uint(O[4 * i]), __float_as_uint(O[4 * i + 1]), __float_as_uint(O[4 * i + 2]), __float_as_uint(O[4 * i + 3]));
        bar_arrive(BAR_MERGE, 288);
        proj_residual<F_WO, 6>(A, sc, xp, maddr, 0, sent, [&] {
          bar_sync(BAR_HALF, 256);
#pragma unroll
          for (int s = 0; s < 4; s++) lds128(mo + s * 2048, A[0][4 * s], A[0][4 * s + 1], A[0][4 * s + 2], A[0][4 * s + 3]);
          PROF_MARK(10);
        });
        PROF_MARK(12);
        float acc[2][32];
        mma_tile<true>(acc[0], A[0], LO(F_PW1)); mma_tile<true>(acc[1], A[0], HI(F_PW1));
        gather_first<1, X_AG0>(A, st, sc, xp, 0, sent, [&] { load_taps(tap, dir); });
        mma_tile<false>(acc[1], A[1], HI(F_PW1 + 1)); mma_tile<false>(acc[0], A[1], LO(F_PW1 + 1));
        gather_rest<1, X_AG0>(A, xp, 0);
        RELEASE(F_WO - 2, F_WO + 1);
        PROF_MARK(13);
        mma_tile<false>(acc[1], A[2], HI(F_PW1 + 2)); mma_tile<false>(acc[1], A[3], HI(F_PW1 + 3));
        WG_WAIT(2);
        RELEASE(F_WO + 2, F_WO - 3 + NREL);
        SCHED();
        uint32_t mu[4];
        const RowNorm n = stat_finish(sc, st, 0, 0.5f);
        const float rs0 = row0 < nvalid ? n.rs0 : 0.f, rs1 = row0 + 8 < nvalid ? n.rs1 : 0.f;
        mean_frag(mu, n, q == 0);
        mma_fold<2 * CS_PW1 + 2>(acc[1], mu);
        mma_tile<false>(acc[0], A[2], LO(F_PW1 + 2));
        mma_tile_fold<2 * CS_PW1>(acc[0], A[3], LO(F_PW1 + 3), mu);
        WG_WAIT(2); pin(acc[1]);
#pragma unroll
        for (int i = 0; i < 32; i++) acc[1][i] = tanh_hw(acc[1][i] * ((i & 2) ? rs1 : rs0));
#pragma unroll
        for (int i = 0; i < 32; i++) { const float rs = (i & 2) ? rs1 : rs0; acc[1][i] = fmaf(acc[1][i], rs, rs); }
        pin(acc[1]);
        SCHED();
        WG_WAIT(0); pin(acc[0]);
#pragma unroll
        for (int i = 0; i < 16; i++) A[0][i] = pack2(acc[0][2 * i] * acc[1][2 * i], acc[0][2 * i + 1] * acc[1][2 * i + 1]);
        const uint32_t ga = stg + TILE_BYTES + here(mrow) * G_PITCH + (lane >> 4) * 16;
#pragma unroll
        for (int s = 0; s < 4; s++) stsm4(ga + s * 32, &A[0][4 * s]);
      }
      {
        const uint32_t gsrc = stg + TILE_BYTES + (8 * cw - 7) * G_PITCH + lane * 4;
        const bool edge = cw == 0 || cw == 7;
        const bool nbr = cw == 0 ? t > 0 : t < 15;
        uint4* const hdst = &sc->x[b + 4 * dir][X_HALO + (cw == 0 ? 96 : 0) + lane];
        uint32_t in[22];
        bar_sync(BAR_G, 256);
        PROF_MARK(14);
        if (cw == 0) {
#pragma unroll
          for (int i = 14; i >= 0; i--) in[i] = lds32(gsrc + (21 - i) * G_PITCH);
        } else {
#pragma unroll
          for (int i = 14; i >= 0; i--) in[i] = lds32(gsrc + i * G_PITCH);
        }
        if (edge) {
          if (nbr) {
            st_vec(hdst, HALO_TAG, in[14], in[13], in[12]);
            st_vec(hdst + 32, HALO_TAG, in[11], in[10], in[9]);
            st_vec(hdst + 64, HALO_TAG, in[8], 0u, 0u);
          }
        } else {
#pragma unroll
          for (int i = 15; i < 22; i++) in[i] = lds32(gsrc + i * G_PITCH);
        }
        if (cw == 0) PROF_MARK0(40);
        uint32_t cv[8];
#pragma unroll
        for (int i = 0; i < 15; i++)
#pragma unroll
          for (int o = 0; o < 8; o++) {
            if (i == o) asm("mul.rn.bf16x2 %0, %1, %2;" : "=r"(cv[o]) : "r"(in[i]), "r"(tap[0]));
            if (i > o) asm("fma.rn.bf16x2 %0, %1, %2, %0;" : "+r"(cv[o]) : "r"(in[i]), "r"(tap[i - o]));
          }
        pin(cv);
        if (cw == 0) PROF_MARK0(41);
        if (edge) {
#pragma unroll
          for (int i = 15; i < 22; i++) in[i] = 0u;
          if (nbr) {
            const uint4* src = &sc->x[b][X_HALO + (cw == 0 ? 0 : 96) + lane];
            uint32_t e0, e1, e2, u0, u1, spin = 0;
#pragma unroll 1
            do {
              ld_vec(src, e0, in[15], in[16], in[17]);
              ld_vec(src + 32, e1, in[18], in[19], in[20]);
              ld_vec(src + 64, e2, in[21], u0, u1);
            } while (__any_sync(0xffffffffu, ((e0 ^ HALO_TAG) | (e1 ^ HALO_TAG) | (e2 ^ HALO_TAG)) != 0) && ++spin < SPIN_LIMIT);
          }
          announce<1>(sc, lane == 0);
        }
#pragma unroll
        for (int i = 15; i < 22; i++)
#pragma unroll
          for (int o = 0; o < 8; o++)
            if (i - o <= 14) asm("fma.rn.bf16x2 %0, %1, %2, %0;" : "+r"(cv[o]) : "r"(in[i]), "r"(tap[i - o]));
        if (cw == 0) PROF_MARK0(42);
        if (cw == 7) PROF_MARK0(43);
        const uint32_t fl = cw == 0 ? 7 : 0;
        const uint32_t cdst = (stg + cw * 1024 + lane * 4) ^ (fl * 144);
#pragma unroll
        for (int o = 0; o < 8; o++) {
          const float a = bf_lo(cv[o]), c = bf_hi(cv[o]);
          sts32(cdst ^ (o * 144), pack2(fmaf(a, tanh_hw(a), a), fmaf(c, tanh_hw(c), c)));
        }
      }
      if (wg == 1) {
        bar_arrive(BAR_C, 256);
        break;
      }
      bar_sync(BAR_C, 256);
      tile_load(here(maddr), A[0]);
      PROF_MARK(15);
      publish(xp + X_AG1, A[0], 1);
      const uint32_t sent_c = clock_now();
      proj_residual<F_PW2, 2>(A, sc, xp, maddr, 1, sent, Nothing(), sent_c);
      PROF_MARK(17);
    }
  }
}

typedef CUresult (*EncodeFn)(CUtensorMap*, CUtensorMapDataType, cuuint32_t, void*, const cuuint64_t*, const cuuint64_t*,
                             const cuuint32_t*, const cuuint32_t*, CUtensorMapInterleave, CUtensorMapSwizzle,
                             CUtensorMapL2promotion, CUtensorMapFloatOOBfill);

void make_map(EncodeFn fn, CUtensorMap* m, const void* w, int rows, int cols, CUtensorMapSwizzle swz) {
  const cuuint64_t dims[2] = {(cuuint64_t)cols, (cuuint64_t)rows}, strides[1] = {(cuuint64_t)cols * 2};
  const cuuint32_t box[2] = {64, 64}, es[2] = {1, 1};
  fn(m, CU_TENSOR_MAP_DATA_TYPE_BFLOAT16, 2, const_cast<void*>(w), dims, strides, box, es, CU_TENSOR_MAP_INTERLEAVE_NONE,
     swz, CU_TENSOR_MAP_L2_PROMOTION_L2_128B, CU_TENSOR_MAP_FLOAT_OOB_FILL_NONE);
}

}

extern "C" void kernel_launch(void* const* d_in, const int* in_sizes, int n_in, void* d_out, int out_size) {
  static EncodeFn fn = nullptr;
  static Scratch* sc = nullptr;
  if (!fn) {
    void* f = nullptr;
    cudaDriverEntryPointQueryResult st;
    cudaGetDriverEntryPoint("cuTensorMapEncodeTiled", &f, cudaEnableDefault, &st);
    fn = (EncodeFn)f;
    void* raw = nullptr;
    cudaGetSymbolAddress(&raw, g_scratch);
    sc = (Scratch*)(((uintptr_t)raw + X_ALIGN - 1) & ~(uintptr_t)(X_ALIGN - 1));
    cudaFuncSetAttribute(conformer_kernel, cudaFuncAttributeMaxDynamicSharedMemorySize, SM_TOTAL);
  }
  typedef const __nv_bfloat16* W;
  const CUtensorMapSwizzle S = CU_TENSOR_MAP_SWIZZLE_128B;
  Params p;
  make_map(fn, &p.map[M_FF1A], d_in[1], 256, 1024, S);
  make_map(fn, &p.map[M_FF1B], d_in[2], 1024, 256, S);
  make_map(fn, &p.map[M_QKV], d_in[3], 256, 768, S);
  make_map(fn, &p.map[M_WO], d_in[4], 256, 256, S);
  make_map(fn, &p.map[M_PW1], d_in[5], 256, 512, S);
  make_map(fn, &p.map[M_PW2], d_in[7], 256, 256, S);
  make_map(fn, &p.map[M_FF2A], d_in[8], 256, 1024, S);
  make_map(fn, &p.map[M_FF2B], d_in[9], 1024, 256, S);
  p.w_ff1b = (W)d_in[2]; p.w_qkv = (W)d_in[3]; p.w_o = (W)d_in[4]; p.w_pw1 = (W)d_in[5];
  p.w_pw2 = (W)d_in[7]; p.w_ff2a = (W)d_in[8]; p.w_ff2b = (W)d_in[9];

  cudaLaunchConfig_t cfg = {};
  cfg.gridDim = dim3(NCTA);
  cfg.blockDim = dim3(384);
  cfg.dynamicSmemBytes = SM_TOTAL;
  cfg.stream = cudaStreamPerThread;
  cudaLaunchAttribute at[1];
  at[0].id = cudaLaunchAttributeCooperative;
  at[0].val.cooperative = 1;
  cfg.attrs = at;
  cfg.numAttrs = 1;
  cudaLaunchKernelEx(&cfg, conformer_kernel, sc, (__nv_bfloat16*)d_out, (W)d_in[6], (W)d_in[0], (W)d_in[1], p);
}
```

```cpp
#include <cuda_runtime.h>
#include <cuda_bf16.h>
#include <cuda.h>
#include <stdint.h>

namespace {

constexpr int T_SEQ = 1000;
constexpr int DM = 256;
constexpr int NCTA = 128;
constexpr int NSTAGE = 12;
constexpr uint32_t STAGE_BYTES = 16384;
constexpr uint32_t TILE_BYTES = 8192;
constexpr uint32_t SM_BASE = 1024;
constexpr uint32_t SM_STG = NSTAGE * STAGE_BYTES;
constexpr uint32_t SM_FULL = SM_STG + 32768;
constexpr uint32_t SM_EMPTY = SM_FULL + 96;
constexpr uint32_t SM_KVRDY = SM_FULL + 192;
constexpr uint32_t SM_LAND = SM_FULL + 208;
constexpr uint32_t SM_EYE = SM_FULL + 256;
constexpr uint32_t SM_ONE = SM_FULL + 640;
constexpr uint32_t SM_CS = SM_FULL + 768;
constexpr uint32_t SM_TOTAL = SM_FULL + 3072;
constexpr int CS_FF2 = 0, CS_PW1 = 4, CS_QKV = 6;
constexpr uint32_t SPIN_LIMIT = 1u << 16;
constexpr float LN_EPS = 1e-5f;
constexpr float SM_SCALE_LOG2 = 0.125f * 1.4426950408889634f;
constexpr uint32_t G_PITCH = 144;
#define FSTR 8
#define CS_AFTER 8
#define WD 0
#define SEG_FENCE 0
#define STAT_LATE 1
#define QT 7
#define ATT_EARLY 1
#define FD 100
#define HD 0
#define KV_ORDER 0xFED7C6B5A4983210ull
#define PV_LATE 1
#define HOLD 5
#define CSAT 4
#define CSNAP 100
#define TIMED 0
#define GD 480
#define GD1 380
#define RD 400
#define NREL 6
#define PF0 1
#define TF 1
#define TC 1600
#define PF1 500
#define PF2 1200
#define PF3 2600
#define CLR_PACE 150

constexpr int F_QKV = 16, F_SPARE = 22, F_KV = 24, F_WO = 40, F_PW1 = 42, F_PW2 = 46, F_TOTAL = 64;
enum { M_FF1A, M_FF1B, M_QKV, M_WO, M_PW1, M_PW2, M_FF2A, M_FF2B, M_COUNT };
enum { BAR_K = 1, BAR_V, BAR_Q, BAR_MERGE, BAR_G, BAR_C, BAR_WG1, BAR_GO, BAR_CS, BAR_ATT, BAR_INIT, BAR_HALF, BAR_RST, BAR_TAP, BAR_PUSH };

struct Params {
  CUtensorMap map[M_COUNT];
  const __nv_bfloat16 *w_ff1b, *w_qkv, *w_o, *w_pw1, *w_pw2, *w_ff2a, *w_ff2b;
  uint16_t fill[4][F_TOTAL];
};

constexpr int X_RS = 0, X_AG1 = X_RS, X_HALO = X_RS + 512, X_AG0 = 1024, X_ST = 1536, X_SIZE = 4096;
constexpr uint32_t HALO_TAG = 0xFFFF0001u;
struct Scratch {
  uint4 x[NCTA][X_SIZE];
  uint4 kv[8][2][16][512];
  uint4 cs[576];
  uint32_t flag[8][32][FSTR];
  uint32_t step[NCTA][32];
};
constexpr size_t X_ALIGN = 4 * X_SIZE * sizeof(uint4);
__device__ uint8_t g_scratch[sizeof(Scratch) + X_ALIGN];
#define PROF_TIME(i)
#define PROF_MARK(i)
#define PROF_MARK2(i, j)
#define PROF_MARK0(i)
#define PROF_AT(a)

__device__ __forceinline__ uint32_t cta_id() {
  const uint32_t c = blockIdx.x >> 1;
  const bool late = c >= 36;
  const uint32_t j = c - (late ? 36 : 4), q = (j * (late ? 37 : 32)) >> 8, g = j - q * (late ? 7 : 8);
  const uint32_t pair = ((late ? 0xFEDC654u : c < 4 ? 0x77777777u : 0xBA983210u) >> (4 * g & 31)) & 15, k = min(c, q);
  return pair * 8 + k * 2 + (blockIdx.x & 1);
}
extern __shared__ __align__(1024) uint8_t smem[];
__device__ __forceinline__ uint32_t own_cta(uint32_t a) { return (uint32_t)__cvta_generic_to_shared(smem) + (a - SM_BASE); }
__device__ __forceinline__ void mbar_init(uint32_t bar, uint32_t cnt) {
  asm volatile("mbarrier.init.shared::cta.b64 [%0], %1;" :: "r"(own_cta(bar)), "r"(cnt) : "memory");
}
__device__ __forceinline__ void mbar_wait(uint32_t bar, uint32_t parity) {
  asm volatile("{\n.reg .pred p;\n.reg .u32 c;\nmov.u32 c, 0;\n"
               "WAIT_LOOP:\nmbarrier.try_wait.parity.shared::cta.b64 p, [%0], %1;\n@p bra WAIT_DONE;\n"
               "add.u32 c, c, 1;\nsetp.lt.u32 p, c, %2;\n@p bra WAIT_LOOP;\nWAIT_DONE:\n}"
               :: "r"(own_cta(bar)), "r"(parity), "n"(SPIN_LIMIT) : "memory");
}
__device__ __forceinline__ void mbar_arrive(uint32_t bar) {
  asm volatile("mbarrier.arrive.shared::cta.b64 _, [%0];" :: "r"(own_cta(bar)) : "memory");
}
#define bar_sync(id, n) asm volatile("bar.sync %0, %1;" :: "n"((int)(id)), "n"(n) : "memory")
#define bar_arrive(id, n) asm volatile("bar.arrive %0, %1;" :: "n"((int)(id)), "n"(n) : "memory")
__device__ __forceinline__ void fence_async_smem() { asm volatile("fence.proxy.async.shared::cta;" ::: "memory"); }

__device__ __forceinline__ void st_vec(uint4* p, uint32_t a, uint32_t b, uint32_t c, uint32_t d) {
  asm volatile("{\n.reg .b128 v;\n.reg .b64 lo, hi;\nmov.b64 lo, {%1, %2};\nmov.b64 hi, {%3, %4};\nmov.b128 v, {lo, hi};\n"
               "st.relaxed.gpu.global.b128 [%0], v;\n}" :: "l"(p), "r"(a), "r"(b), "r"(c), "r"(d) : "memory");
}
__device__ __forceinline__ void ld_vec(const uint4* p, uint32_t& a, uint32_t& b, uint32_t& c, uint32_t& d) {
  asm volatile("{\n.reg .b128 v;\n.reg .b64 lo, hi;\nld.relaxed.gpu.global.b128 v, [%4];\nmov.b128 {lo, hi}, v;\n"
               "mov.b64 {%0, %1}, lo;\nmov.b64 {%2, %3}, hi;\n}" : "=r"(a), "=r"(b), "=r"(c), "=r"(d) : "l"(p) : "memory");
}
__device__ __forceinline__ void sts128(uint32_t a, uint32_t x, uint32_t y, uint32_t z, uint32_t w) {
  asm volatile("st.shared.v4.u32 [%0], {%1, %2, %3, %4};" :: "r"(own_cta(a)), "r"(x), "r"(y), "r"(z), "r"(w) : "memory");
}
__device__ __forceinline__ void lds128(uint32_t a, uint32_t& x, uint32_t& y, uint32_t& z, uint32_t& w) {
  asm volatile("ld.shared.v4.u32 {%0, %1, %2, %3}, [%4];" : "=r"(x), "=r"(y), "=r"(z), "=r"(w) : "r"(own_cta(a)) : "memory");
}
__device__ __forceinline__ uint32_t lds32(uint32_t a) {
  uint32_t x; asm volatile("ld.shared.u32 %0, [%1];" : "=r"(x) : "r"(own_cta(a)) : "memory"); return x;
}
__device__ __forceinline__ void sts32(uint32_t a, uint32_t x) { asm volatile("st.shared.u32 [%0], %1;" :: "r"(own_cta(a)), "r"(x) : "memory"); }
__device__ __forceinline__ void sts64(uint32_t a, uint32_t x, uint32_t y) {
  asm volatile("st.shared.v2.u32 [%0], {%1, %2};" :: "r"(own_cta(a)), "r"(x), "r"(y) : "memory");
}
__device__ __forceinline__ void stsm4(uint32_t a, const uint32_t* r) {
  asm volatile("stmatrix.sync.aligned.m8n8.x4.shared.b16 [%0], {%1, %2, %3, %4};" :: "r"(own_cta(a)), "r"(r[0]), "r"(r[1]), "r"(r[2]), "r"(r[3]) : "memory");
}
__device__ __forceinline__ void ldsm4(uint32_t a, uint32_t* r) {
  asm volatile("ldmatrix.sync.aligned.m8n8.x4.shared.b16 {%0, %1, %2, %3}, [%4];" : "=r"(r[0]), "=r"(r[1]), "=r"(r[2]), "=r"(r[3]) : "r"(own_cta(a)) : "memory");
}
__device__ __forceinline__ uint32_t pack2(float lo, float hi) {
  uint32_t r; asm("cvt.rn.bf16x2.f32 %0, %1, %2;" : "=r"(r) : "f"(hi), "f"(lo)); return r;
}
__device__ __forceinline__ float bf_lo(uint32_t w) { return __uint_as_float(w << 16); }
__device__ __forceinline__ float bf_hi(uint32_t w) { return __uint_as_float(w & 0xffff0000u); }
__device__ __forceinline__ float tanh_hw(float x) { float y; asm volatile("tanh.approx.f32 %0, %1;" : "=f"(y) : "f"(x)); return y; }
__device__ __forceinline__ float rcp_hw(float x) { float y; asm("rcp.approx.ftz.f32 %0, %1;" : "=f"(y) : "f"(x)); return y; }
__device__ __forceinline__ float rsqrt_hw(float x) { float y; asm("rsqrt.approx.ftz.f32 %0, %1;" : "=f"(y) : "f"(x)); return y; }
__device__ __forceinline__ float ex2_hw(float x) { float y; asm("ex2.approx.ftz.f32 %0, %1;" : "=f"(y) : "f"(x)); return y; }

__device__ __forceinline__ uint32_t here(uint32_t v) { asm volatile("" : "+r"(v)); return v; }

#define SCHED() asm volatile("pmevent 1;" ::: "memory")
__device__ __forceinline__ void cp_async16(uint32_t dst, const void* src) {
  asm volatile("cp.async.cg.shared.global [%0], [%1], 16;" :: "r"(own_cta(dst)), "l"(src) : "memory");
}
#define CLUSTER_ARRIVE() asm volatile("barrier.cluster.arrive.relaxed.aligned;" ::: "memory")
#define WG_FENCE() asm volatile("wgmma.fence.sync.aligned;" ::: "memory")
#define WG_COMMIT() asm volatile("wgmma.commit_group.sync.aligned;" ::: "memory")
#define WG_WAIT(n) asm volatile("wgmma.wait_group.sync.aligned %0;" :: "n"(n) : "memory")

template <int N> __device__ __forceinline__ void pin(float (&d)[N]) {
#pragma unroll
  for (int i = 0; i < N; i++) asm volatile("" : "+f"(d[i]) :: "memory");
}
template <int N> __device__ __forceinline__ void pin(uint32_t (&d)[N]) {
#pragma unroll
  for (int i = 0; i < N; i++) asm volatile("" : "+r"(d[i]) :: "memory");
}

#define WG_D32 "{%0, %1, %2, %3, %4, %5, %6, %7, %8, %9, %10, %11, %12, %13, %14, %15, %16, %17, %18, %19, %20, %21, %22, %23, %24, %25, %26, %27, %28, %29, %30, %31}"
template <int TB> __device__ __forceinline__ void wgmma64_acc(float (&d)[32], const uint32_t* a, uint64_t db) {
  asm volatile("wgmma.mma_async.sync.aligned.m64n64k16.f32.bf16.bf16 " WG_D32 ", {%32, %33, %34, %35}, %36, 1, 1, 1, %37;"
    : "+f"(d[0]), "+f"(d[1]), "+f"(d[2]), "+f"(d[3]), "+f"(d[4]), "+f"(d[5]), "+f"(d[6]), "+f"(d[7]),
      "+f"(d[8]), "+f"(d[9]), "+f"(d[10]), "+f"(d[11]), "+f"(d[12]), "+f"(d[13]), "+f"(d[14]), "+f"(d[15]),
      "+f"(d[16]), "+f"(d[17]), "+f"(d[18]), "+f"(d[19]), "+f"(d[20]), "+f"(d[21]), "+f"(d[22]), "+f"(d[23]),
      "+f"(d[24]), "+f"(d[25]), "+f"(d[26]), "+f"(d[27]), "+f"(d[28]), "+f"(d[29]), "+f"(d[30]), "+f"(d[31])
    : "r"(a[0]), "r"(a[1]), "r"(a[2]), "r"(a[3]), "l"(db), "n"(TB));
}
template <int TB> __device__ __forceinline__ void wgmma64_reuse(float (&d)[32], const uint32_t* a, uint64_t db, uint32_t zero) {
  asm volatile("{\n.reg .pred p;\nsetp.ne.u32 p, %37, 0;\nwgmma.mma_async.sync.aligned.m64n64k16.f32.bf16.bf16 " WG_D32 ", {%32, %33, %34, %35}, %36, p, 1, 1, %38;\n}"
    : "+f"(d[0]), "+f"(d[1]), "+f"(d[2]), "+f"(d[3]), "+f"(d[4]), "+f"(d[5]), "+f"(d[6]), "+f"(d[7]),
      "+f"(d[8]), "+f"(d[9]), "+f"(d[10]), "+f"(d[11]), "+f"(d[12]), "+f"(d[13]), "+f"(d[14]), "+f"(d[15]),
      "+f"(d[16]), "+f"(d[17]), "+f"(d[18]), "+f"(d[19]), "+f"(d[20]), "+f"(d[21]), "+f"(d[22]), "+f"(d[23]),
      "+f"(d[24]), "+f"(d[25]), "+f"(d[26]), "+f"(d[27]), "+f"(d[28]), "+f"(d[29]), "+f"(d[30]), "+f"(d[31])
    : "r"(a[0]), "r"(a[1]), "r"(a[2]), "r"(a[3]), "l"(db), "r"(zero), "n"(TB));
}
template <int TB> __device__ __forceinline__ void wgmma64_set(float (&d)[32], const uint32_t* a, uint64_t db) {
  asm volatile("wgmma.mma_async.sync.aligned.m64n64k16.f32.bf16.bf16 " WG_D32 ", {%32, %33, %34, %35}, %36, 0, 1, 1, %37;"
    : "=f"(d[0]), "=f"(d[1]), "=f"(d[2]), "=f"(d[3]), "=f"(d[4]), "=f"(d[5]), "=f"(d[6]), "=f"(d[7]),
      "=f"(d[8]), "=f"(d[9]), "=f"(d[10]), "=f"(d[11]), "=f"(d[12]), "=f"(d[13]), "=f"(d[14]), "=f"(d[15]),
      "=f"(d[16]), "=f"(d[17]), "=f"(d[18]), "=f"(d[19]), "=f"(d[20]), "=f"(d[21]), "=f"(d[22]), "=f"(d[23]),
      "=f"(d[24]), "=f"(d[25]), "=f"(d[26]), "=f"(d[27]), "=f"(d[28]), "=f"(d[29]), "=f"(d[30]), "=f"(d[31])
    : "r"(a[0]), "r"(a[1]), "r"(a[2]), "r"(a[3]), "l"(db), "n"(TB));
}

template <int ACC> __device__ __forceinline__ void wgmma72(float (&d)[36], const uint32_t* a, uint64_t db) {
  if constexpr (ACC)
  asm volatile("wgmma.mma_async.sync.aligned.m64n72k16.f32.bf16.bf16 {%0, %1, %2, %3, %4, %5, %6, %7, %8, %9, %10, %11, %12, %13, %14, %15, %16, %17, %18, %19, %20, %21, %22, %23, %24, %25, %26, %27, %28, %29, %30, %31, %32, %33, %34, %35}, {%36, %37, %38, %39}, %40, 1, 1, 1, 1;"
    : "+f"(d[0]), "+f"(d[1]), "+f"(d[2]), "+f"(d[3]), "+f"(d[4]), "+f"(d[5]), "+f"(d[6]), "+f"(d[7]), "+f"(d[8]),
      "+f"(d[9]), "+f"(d[10]), "+f"(d[11]), "+f"(d[12]), "+f"(d[13]), "+f"(d[14]), "+f"(d[15]), "+f"(d[16]), "+f"(d[17]),
      "+f"(d[18]), "+f"(d[19]), "+f"(d[20]), "+f"(d[21]), "+f"(d[22]), "+f"(d[23]), "+f"(d[24]), "+f"(d[25]), "+f"(d[26]),
      "+f"(d[27]), "+f"(d[28]), "+f"(d[29]), "+f"(d[30]), "+f"(d[31]), "+f"(d[32]), "+f"(d[33]), "+f"(d[34]), "+f"(d[35])
    : "r"(a[0]), "r"(a[1]), "r"(a[2]), "r"(a[3]), "l"(db));
  else
  asm volatile("wgmma.mma_async.sync.aligned.m64n72k16.f32.bf16.bf16 {%0, %1, %2, %3, %4, %5, %6, %7, %8, %9, %10, %11, %12, %13, %14, %15, %16, %17, %18, %19, %20, %21, %22, %23, %24, %25, %26, %27, %28, %29, %30, %31, %32, %33, %34, %35}, {%36, %37, %38, %39}, %40, 0, 1, 1, 1;"
    : "=f"(d[0]), "=f"(d[1]), "=f"(d[2]), "=f"(d[3]), "=f"(d[4]), "=f"(d[5]), "=f"(d[6]), "=f"(d[7]), "=f"(d[8]),
      "=f"(d[9]), "=f"(d[10]), "=f"(d[11]), "=f"(d[12]), "=f"(d[13]), "=f"(d[14]), "=f"(d[15]), "=f"(d[16]), "=f"(d[17]),
      "=f"(d[18]), "=f"(d[19]), "=f"(d[20]), "=f"(d[21]), "=f"(d[22]), "=f"(d[23]), "=f"(d[24]), "=f"(d[25]), "=f"(d[26]),
      "=f"(d[27]), "=f"(d[28]), "=f"(d[29]), "=f"(d[30]), "=f"(d[31]), "=f"(d[32]), "=f"(d[33]), "=f"(d[34]), "=f"(d[35])
    : "r"(a[0]), "r"(a[1]), "r"(a[2]), "r"(a[3]), "l"(db));
}
__device__ __forceinline__ void wgmma16_acc(float* d, const uint32_t* a, uint64_t db) {
  asm volatile("wgmma.mma_async.sync.aligned.m64n16k16.f32.bf16.bf16 {%0, %1, %2, %3, %4, %5, %6, %7}, {%8, %9, %10, %11}, %12, 1, 1, 1, 0;"
    : "+f"(d[0]), "+f"(d[1]), "+f"(d[2]), "+f"(d[3]), "+f"(d[4]), "+f"(d[5]), "+f"(d[6]), "+f"(d[7])
    : "r"(a[0]), "r"(a[1]), "r"(a[2]), "r"(a[3]), "l"(db));
}
__device__ __forceinline__ void hmma(float (&d)[4], const uint32_t* a, uint32_t b0, uint32_t b1) {
  asm("mma.sync.aligned.m16n8k16.row.col.f32.bf16.bf16.f32 {%0, %1, %2, %3}, {%4, %5, %6, %7}, {%8, %9}, {%0, %1, %2, %3};"
    : "+f"(d[0]), "+f"(d[1]), "+f"(d[2]), "+f"(d[3]) : "r"(a[0]), "r"(a[1]), "r"(a[2]), "r"(a[3]), "r"(b0), "r"(b1));
}

__device__ __forceinline__ void hmma8(float (&d)[4], const uint32_t* a, uint32_t b0) {
  asm("mma.sync.aligned.m16n8k8.row.col.f32.bf16.bf16.f32 {%0, %1, %2, %3}, {%4, %5}, {%6}, {%0, %1, %2, %3};"
    : "+f"(d[0]), "+f"(d[1]), "+f"(d[2]), "+f"(d[3]) : "r"(a[0]), "r"(a[1]), "r"(b0));
}

template <bool FIRST> __device__ __forceinline__ void mma_tile(float (&d)[32], const uint32_t (&a)[16], uint64_t db) {
  WG_FENCE();
#pragma unroll
  for (int s = 0; s < 4; s++) {
    if (FIRST && s == 0) wgmma64_set<1>(d, &a[0], db); else wgmma64_acc<1>(d, &a[4 * s], db + s * 128);
  }
  WG_COMMIT();
}
__device__ __forceinline__ void mma_tile_reuse(float (&d)[32], const uint32_t (&a)[16], uint64_t db) {
  WG_FENCE();
  wgmma64_reuse<1>(d, &a[0], db, blockIdx.y);
#pragma unroll
  for (int s = 1; s < 4; s++) wgmma64_acc<1>(d, &a[4 * s], db + s * 128);
  WG_COMMIT();
}
template <int ROW> __device__ __forceinline__ void fold_step(float (&d)[32], const uint32_t (&mu)[4]) {
  wgmma64_acc<1>(d, mu, (uint64_t)((SM_BASE + SM_CS + ROW * 128) >> 4) | (uint64_t(1) << 16) | (uint64_t(1) << 62));
}
template <int ROW> __device__ __forceinline__ void mma_fold(float (&d)[32], const uint32_t (&mu)[4]) {
  WG_FENCE();
  fold_step<ROW>(d, mu);
  WG_COMMIT();
}
template <int ROW> __device__ __forceinline__ void mma_tile_fold(float (&d)[32], const uint32_t (&a)[16], uint64_t db, const uint32_t (&mu)[4]) {
  WG_FENCE();
#pragma unroll
  for (int s = 0; s < 4; s++) wgmma64_acc<1>(d, &a[4 * s], db + s * 128);
  fold_step<ROW>(d, mu);
  WG_COMMIT();
}
__device__ __forceinline__ void mma_add_half(float (&d)[32], const uint32_t (&a)[16]) {
  const uint64_t db = (uint64_t)((SM_BASE + SM_EYE) >> 4) | (uint64_t(8) << 16) | (uint64_t(8) << 32);
  WG_FENCE();
#pragma unroll
  for (int s = 0; s < 4; s++) wgmma16_acc(&d[8 * s], &a[4 * s], db);
  WG_COMMIT();
}
#define ACQUIRE(f) mbar_wait(SM_BASE + SM_FULL + ((f) % NSTAGE) * 8, ((f) / NSTAGE) & 1)
__device__ __forceinline__ void mbar_probe(uint32_t& ok, uint32_t bar, uint32_t parity) {
  asm volatile("{\n.reg .pred p;\nmbarrier.test_wait.parity.shared::cta.b64 p, [%1], %2;\nselp.u32 %0, %0, 0, p;\n}"
               : "+r"(ok) : "r"(own_cta(bar)), "r"(parity) : "memory");
}
template <int F, int N> __device__ __forceinline__ void acquire_n() {
  uint32_t spin = 0, ok;
#pragma unroll 1
  do {
    ok = 1;
#pragma unroll
    for (int i = F; i < F + N; i++)
      asm volatile("{\n.reg .pred p;\nmbarrier.try_wait.parity.shared::cta.b64 p, [%1], %2;\nselp.u32 %0, %0, 0, p;\n}"
                   : "+r"(ok) : "r"(own_cta(SM_BASE + SM_FULL + i % NSTAGE * 8)), "r"((i / NSTAGE) & 1) : "memory");
  } while (!ok && ++spin < SPIN_LIMIT);
}
#define GO() bar_sync(BAR_GO, 160)
#define RELEASE(f0, f1) do { if (lane == 0) { _Pragma("unroll") for (int f_ = (f0); f_ <= (f1); f_++) mbar_arrive(SM_BASE + SM_EMPTY + (f_ % NSTAGE) * 8); } } while (0)
constexpr uint64_t RING = (uint64_t)(SM_BASE >> 4) | (uint64_t(1) << 16) | (uint64_t(64) << 32) | (uint64_t(1) << 62);
#define LO(f) (RING + ((f) % NSTAGE) * 1024)
#define HI(f) (RING + ((f) % NSTAGE) * 1024 + 512)

template <int C> __device__ __forceinline__ uint4* peer(uint4* p) {
  asm volatile("" : "+l"(p));
  return (uint4*)((uintptr_t)p ^ (C * X_SIZE * sizeof(uint4)));
}
__device__ __forceinline__ uint32_t clock_now() { uint32_t c; asm volatile("mov.u32 %0, %%clock;" : "=r"(c) :: "memory"); return c; }
__device__ __forceinline__ void publish(uint4* dst, uint32_t (&a)[16], uint32_t tag) {
#pragma unroll
  for (int s = 0; s < 4; s++) a[4 * s] = (a[4 * s] & ~1u) | tag;
  pin(a);
  SCHED();
#pragma unroll
  for (int s = 0; s < 4; s++) st_vec(dst + s * 128, a[4 * s], a[4 * s + 1], a[4 * s + 2], a[4 * s + 3]);
  SCHED();
}
__device__ __forceinline__ uint32_t partner(uint32_t a) {
  uint32_t d; asm("mapa.shared::cluster.u32 %0, %1, %2;" : "=r"(d) : "r"(a), "r"(~blockIdx.x & 1)); return d;
}
__device__ __forceinline__ void push(uint32_t tile, uint32_t buf) {
  fence_async_smem();
  asm volatile("{\n.reg .pred p;\nelect.sync _|p, 0xffffffff;\n"
               "@p cp.async.bulk.shared::cluster.shared::cta.mbarrier::complete_tx::bytes [%0], [%1], 8192, [%2];\n"
               "@p mbarrier.arrive.expect_tx.shared::cta.b64 _, [%3], 8192;\n}"
               :: "r"(partner(SM_BASE + SM_STG + buf * TILE_BYTES)), "r"(own_cta(tile)),
                  "r"(partner(SM_BASE + SM_LAND + buf * 8)), "r"(own_cta(SM_BASE + SM_LAND + buf * 8)) : "memory");
}
__device__ __forceinline__ void fetch(const uint4* src, uint32_t (&a)[16]) {
#pragma unroll
  for (int s = 0; s < 4; s++) ld_vec(src + s * 128, a[4 * s], a[4 * s + 1], a[4 * s + 2], a[4 * s + 3]);
}
__device__ __forceinline__ uint32_t miss(const uint32_t (&a)[16], uint32_t tag) {
  return (a[0] ^ tag) | (a[4] ^ tag) | (a[8] ^ tag) | (a[12] ^ tag);
}
__device__ __forceinline__ bool stale(uint32_t v) { return __any_sync(0xffffffffu, here(v) & 1u); }
template <int N = 2> __device__ __forceinline__ void announce(Scratch* sc, bool leader) {
  asm volatile("{\n.reg .pred p;\nsetp.ne.u32 p, %1, 0;\n@p red.relaxed.gpu.global.add.u32 [%0], %2;\n}"
               :: "l"(&sc->step[cta_id()][here(threadIdx.x) & 31]), "r"((uint32_t)leader), "n"(N) : "memory");
}
__device__ __forceinline__ uint32_t launch_index(const Scratch* sc) { return *(const volatile uint32_t*)sc->step[cta_id()] >> 4; }
__device__ __forceinline__ void stat_fetch(const Scratch* sc, uint32_t (&st)[4]) {
  const uint32_t th = here(threadIdx.x);
  ld_vec(&sc->x[(cta_id() & ~3u) + (th & 3)][X_ST + (th >> 2)], st[0], st[1], st[2], st[3]);
}
__device__ __forceinline__ void tile_store(uint32_t maddr, const uint32_t (&a)[16]) {
#pragma unroll
  for (int s = 0; s < 4; s++) stsm4(maddr ^ (s << 5), &a[4 * s]);
}
__device__ __forceinline__ void tile_load(uint32_t maddr, uint32_t (&a)[16]) {
#pragma unroll
  for (int s = 0; s < 4; s++) ldsm4(maddr ^ (s << 5), &a[4 * s]);
}
template <int BUF> __device__ __forceinline__ void land(uint32_t (&a)[16], uint32_t maddr, uint32_t parity) {
  mbar_wait(SM_BASE + SM_LAND + BUF * 8, parity);
  tile_load(here(maddr) + BUF * TILE_BYTES, a);
}
template <int SLOT, class F>
__device__ __forceinline__ void gather_first(uint32_t (&A)[4][16], uint32_t (&st)[4], const Scratch* sc, uint4* xp, uint32_t maddr, uint32_t parity,
                                             uint32_t sent, F meanwhile) {
  if (TIMED) { while (clock_now() - sent < (SLOT == X_AG0 ? GD : GD1)) {} }
  GO();
  fetch(peer<2>(xp) + SLOT, A[2]); fetch(peer<3>(xp) + SLOT, A[3]);
  if (SLOT == X_AG0 && !STAT_LATE) stat_fetch(sc, st);
  SCHED();
  meanwhile();
  if (SLOT == X_AG0 && STAT_LATE) { SCHED(); stat_fetch(sc, st); }
  land<SLOT == X_AG0>(A[1], maddr, parity);
}
__device__ __forceinline__ void confirm2(uint32_t (&A)[4][16], const uint4* p2, const uint4* p3, uint32_t tag) {
  SCHED();
  uint32_t spin = 0;
  while (__builtin_expect(stale(miss(A[2], tag) | miss(A[3], tag)), 0) && ++spin < SPIN_LIMIT) {
    fetch(p2, A[2]);
    fetch(p3, A[3]);
  }
}
template <int SLOT> __device__ __forceinline__ void gather_rest(uint32_t (&A)[4][16], uint4* xp, uint32_t tag) {
  confirm2(A, peer<2>(xp) + SLOT, peer<3>(xp) + SLOT, tag);
}
__device__ __forceinline__ void stat_confirm(const Scratch* sc, uint32_t (&st)[4], uint32_t tag) {
  uint32_t spin = 0;
  while (__builtin_expect(stale(st[0] ^ tag), 0) && ++spin < SPIN_LIMIT) stat_fetch(sc, st);
}
__device__ __forceinline__ void pack_acc(const float (&d)[32], uint32_t (&a)[16]) {
#pragma unroll
  for (int i = 0; i < 16; i++) a[i] = pack2(d[2 * i], d[2 * i + 1]);
}
__device__ __forceinline__ void frag_store(uint32_t slot, const uint32_t (&a)[16]) {
#pragma unroll
  for (int s = 0; s < 4; s++) sts128(slot + s * 512, a[4 * s], a[4 * s + 1], a[4 * s + 2], a[4 * s + 3]);
}
__device__ __forceinline__ void res_load(uint32_t maddr, float (&d)[32]) {
  uint32_t a[16];
  tile_load(here(maddr) + 3 * TILE_BYTES, a);
#pragma unroll
  for (int i = 0; i < 16; i++) { d[2 * i] = bf_lo(a[i]); d[2 * i + 1] = bf_hi(a[i]); }
  pin(d);
}

struct RowAcc { float s[2][4], u[2][4], v[2][4]; };
__device__ __forceinline__ void row_sums(RowAcc& t, const uint32_t (&a)[16]) {
#pragma unroll
  for (int s = 0; s < 4; s++) hmma(t.s[s & 1], &a[4 * s], 0x3F803F80u, 0x3F803F80u);
}
__device__ __forceinline__ void row_gram(RowAcc& t, const uint32_t (&a)[16]) {
#pragma unroll
  for (int s = 0; s < 8; s++) {
    hmma8(t.u[s & 1], &a[2 * s], a[2 * s]);
    hmma8(t.v[s & 1], &a[2 * s], a[2 * s + 1]);
  }
}
__device__ __forceinline__ float2 row_squares(const RowAcc& t, bool odd) {
  return make_float2(odd ? t.u[0][1] + t.u[1][1] : t.u[0][0] + t.u[1][0], odd ? t.v[0][3] + t.v[1][3] : t.v[0][2] + t.v[1][2]);
}
__device__ __forceinline__ void stat_publish(const uint32_t (&a)[16], Scratch* sc, uint32_t th, uint32_t tag) {
  RowAcc t = {};
  row_sums(t, a);
  row_gram(t, a);
  const float2 q = row_squares(t, th & 4);
  asm volatile("{\n.reg .pred p;\n.reg .b128 v;\n.reg .b64 lo, hi;\nsetp.eq.u32 p, %5, 0;\nmov.b64 lo, {%1, %2};\nmov.b64 hi, {%3, %4};\n"
               "mov.b128 v, {lo, hi};\n@p st.relaxed.gpu.global.b128 [%0], v;\n}"
               :: "l"(&sc->x[cta_id()][X_ST + (th >> 2)]), "r"((__float_as_uint(t.s[0][0] + t.s[1][0]) & ~1u) | tag), "r"(__float_as_uint(q.x)),
                  "r"(__float_as_uint(t.s[0][2] + t.s[1][2])), "r"(__float_as_uint(q.y)), "r"((th ^ (th >> 3)) & 3) : "memory");
}
struct RowNorm { float m0, rs0, m1, rs1; };
__device__ __forceinline__ RowNorm row_norm(float s0, float q0, float s1, float q1, float scale) {
  RowNorm n;
  n.m0 = s0 * (1.f / DM); n.m1 = s1 * (1.f / DM);
  n.rs0 = scale * rsqrt_hw(fmaxf(fmaf(-n.m0, n.m0, q0 * (1.f / DM)), 0.f) + LN_EPS);
  n.rs1 = scale * rsqrt_hw(fmaxf(fmaf(-n.m1, n.m1, q1 * (1.f / DM)), 0.f) + LN_EPS);
  return n;
}
__device__ __forceinline__ RowNorm stat_finish(const uint32_t (&st)[4], float scale) {
  float f[4];
#pragma unroll
  for (int i = 0; i < 4; i++) {
    f[i] = __uint_as_float(st[i]);
    f[i] += __shfl_xor_sync(0xffffffffu, f[i], 1);
    f[i] += __shfl_xor_sync(0xffffffffu, f[i], 2);
  }
  return row_norm(f[0], f[1], f[2], f[3], scale);
}
__device__ __forceinline__ void mean_frag(uint32_t (&mu)[4], const RowNorm& n, bool sel) {
  const float a = sel ? -n.m0 : 0.f, c = sel ? -n.m1 : 0.f;
  mu[0] = pack2(a, a); mu[1] = pack2(c, c);
  const float al = a - bf_lo(mu[0]), cl = c - bf_lo(mu[1]);
  mu[2] = pack2(al, al); mu[3] = pack2(cl, cl);
  pin(mu);
}
__device__ __forceinline__ void centre(uint32_t (&a)[16], uint32_t m0, uint32_t m1) {
#pragma unroll
  for (int i = 0; i < 16; i++) asm("sub.rn.bf16x2 %0, %0, %1;" : "+r"(a[i]) : "r"((i & 1) ? m1 : m0));
  pin(a);
}
__device__ __forceinline__ void scale_pack(const float (&d)[32], uint32_t (&a)[16], float rs0, float rs1) {
#pragma unroll
  for (int i = 0; i < 16; i++) { const float rs = (i & 1) ? rs1 : rs0; a[i] = pack2(d[2 * i] * rs, d[2 * i + 1] * rs); }
}
template <int S> __device__ __forceinline__ void silu_seg(float (&acc)[4][32], float (&tn)[2][4], uint32_t (&H)[4][16], float rs0, float rs1) {
  if (S >= 2) {
    const float* h = &acc[(S - 2) >> 3][4 * ((S - 2) & 7)];
    const float* v = tn[S & 1];
    uint32_t* o = &H[(S - 2) >> 3][2 * ((S - 2) & 7)];
    o[0] = pack2(fmaf(h[0], v[0], h[0]), fmaf(h[1], v[1], h[1]));
    o[1] = pack2(fmaf(h[2], v[2], h[2]), fmaf(h[3], v[3], h[3]));
    asm volatile("" : "+r"(o[0]), "+r"(o[1]));
  }
  if (S >= 1 && S <= 32) {
#pragma unroll
    for (int k = 0; k < 4; k++) tn[(S - 1) & 1][k] = tanh_hw(acc[((S - 1) >> 3) & 3][4 * ((S - 1) & 7) + k]);
  }
  if (S < 32) {
    float* h = &acc[(S >> 3) & 3][4 * (S & 7)];
    h[0] *= rs0; h[1] *= rs0; h[2] *= rs1; h[3] *= rs1;
    asm volatile("" : "+f"(h[0]), "+f"(h[1]), "+f"(h[2]), "+f"(h[3]));
  }
}
template <int S0, int S1> __device__ __forceinline__ void silu_segs(float (&acc)[4][32], float (&tn)[2][4], uint32_t (&H)[4][16], float rs0, float rs1) {
  silu_seg<S0>(acc, tn, H, rs0, rs1);
  if (SEG_FENCE || S0 + 1 == S1) SCHED();
  if constexpr (S0 + 1 < S1) silu_segs<S0 + 1, S1>(acc, tn, H, rs0, rs1);
}
template <int HALF> __device__ __forceinline__ void send_half(uint4* dst, const float (&d)[32], uint32_t tag) {
  uint32_t o[8];
#pragma unroll
  for (int i = 0; i < 8; i++) o[i] = pack2(d[16 * HALF + 2 * i], d[16 * HALF + 2 * i + 1]);
  o[0] = (o[0] & ~1u) | tag; o[4] = (o[4] & ~1u) | tag;
  pin(o);
  SCHED();
  st_vec(dst + HALF * 256, o[0], o[1], o[2], o[3]);
  st_vec(dst + HALF * 256 + 128, o[4], o[5], o[6], o[7]);
  SCHED();
}
__device__ __forceinline__ void send_residual(uint32_t (&a)[16], Scratch* sc, uint4* xp, uint32_t maddr, uint32_t tag, uint32_t& sent) {
  const uint32_t exact[4] = {a[0], a[4], a[8], a[12]};
  publish(xp + X_AG0, a, tag);
  if (TIMED) sent = clock_now();
  const uint32_t th = here(threadIdx.x);
  tile_store(here(maddr) + 3 * TILE_BYTES, a);
  stsm4(SM_BASE + SM_STG + 3 * TILE_BYTES + (th >> 5) * 2048 + (th & 7) * 128 + ((((th >> 2) & 6) ^ (th & 7)) << 4), exact);
  bar_arrive(BAR_PUSH, 160);
  stat_publish(a, sc, th, tag);
}
__device__ __forceinline__ void proj_residual(uint32_t (&A)[4][16], Scratch* sc, uint4* xp, uint32_t maddr,
                                                                      uint32_t tag, uint32_t& sent) {
  float acc[32];
  uint32_t st[4];
  const uint64_t db = LO(F_WO) + tag * ((F_PW2 - F_WO) * 1024);
  res_load(maddr, acc);
  gather_first<X_AG1>(A, st, sc, xp, maddr, tag ^ 1, sent, [&] { mma_tile<false>(acc, A[0], db); });
  mma_tile<false>(acc, A[1], db + 512);
  gather_rest<X_AG1>(A, xp, tag);
  announce(sc, threadIdx.x == 0);
  PROF_MARK0(11 + 5 * tag);
  mma_tile<false>(acc, A[2], db + 1024);
  mma_tile<false>(acc, A[3], db + 1536);
  WG_WAIT(0); pin(acc);
  pack_acc(acc, A[0]);
  send_residual(A[0], sc, xp, maddr, tag, sent);
}

__device__ __forceinline__ void qk_tile(float (&S)[32], const uint32_t (&Q)[16], const uint32_t (&nm)[4], uint64_t dk) {
  wgmma64_set<0>(S, nm, (uint64_t)((SM_BASE + SM_ONE) >> 4));
#pragma unroll
  for (int s = 0; s < 4; s++) wgmma64_acc<0>(S, &Q[4 * s], dk + s * 2);
}
constexpr int64_t V_STEP = 1 - 65536;
constexpr uint64_t RING_V = RING - (uint64_t(1) << 16) + ((uint64_t)((SM_STG + 2 * TILE_BYTES) >> 4) << 16);
template <bool FIRST> __device__ __forceinline__ void pv_tile(float (&O)[36], const uint32_t (&P)[16], uint64_t dv, uint32_t pad) {
#pragma unroll
  for (int s = 0; s < 4; s++) {
    if (FIRST && s == 0) wgmma72<0>(O, &P[0], dv); else wgmma72<1>(O, &P[4 * s], dv + s * 128 * V_STEP + (s < 2 ? 0 : (s - 1) * pad));
  }
}
constexpr uint32_t SM_GLU = SM_BASE + (F_PW1 + 2) % NSTAGE * STAGE_BYTES;
constexpr uint32_t SM_ATT = SM_BASE + 2 * STAGE_BYTES + TILE_BYTES;
constexpr uint32_t SM_TAPS = SM_BASE + SM_STG + 2 * TILE_BYTES + 6144;
__device__ __forceinline__ void load_taps(uint32_t (&tap)[15], int dir) {
  const uint32_t src = SM_TAPS + 7 * 128 + (here(threadIdx.x) & 31) * 4;
#pragma unroll
  for (int k = 0; k < 15; k++) tap[k] = lds32(src + dir * (k - 7) * 128);
}
__device__ __forceinline__ void attention_exact(float (&O)[36], const uint32_t (&Q)[16], const Scratch* sc, int bh, int lane, int half) {
  const char* kb = (const char*)&sc->kv[bh][0][0][0];
  const char* vb = (const char*)&sc->kv[bh][1][0][0];
  const int g = lane >> 2, q = lane & 3;
  float m0 = -INFINITY, m1 = -INFINITY, l0 = 0.f, l1 = 0.f;
  float o[4][4] = {};
#pragma unroll 1
  for (int k0 = 0; k0 < T_SEQ; k0 += 8) {
    float s[4] = {0.f, 0.f, 0.f, 0.f};
#pragma unroll
    for (int c = 0; c < 8; c++) hmma8(s, &Q[2 * c], __ldcg((const uint32_t*)(kb + (k0 + g) * 128 + ((c ^ g) << 4) + q * 4)));
    float n0 = fmaxf(s[0], s[1]), n1 = fmaxf(s[2], s[3]);
    n0 = fmaxf(n0, __shfl_xor_sync(0xffffffffu, n0, 1)); n1 = fmaxf(n1, __shfl_xor_sync(0xffffffffu, n1, 1));
    n0 = fmaxf(m0, fmaxf(n0, __shfl_xor_sync(0xffffffffu, n0, 2))); n1 = fmaxf(m1, fmaxf(n1, __shfl_xor_sync(0xffffffffu, n1, 2)));
    const float a0 = ex2_hw(m0 - n0), a1 = ex2_hw(m1 - n1);
    m0 = n0; m1 = n1;
    const uint32_t pp[2] = {pack2(ex2_hw(s[0] - n0), ex2_hw(s[1] - n0)), pack2(ex2_hw(s[2] - n1), ex2_hw(s[3] - n1))};
    l0 = fmaf(l0, a0, bf_lo(pp[0]) + bf_hi(pp[0])); l1 = fmaf(l1, a1, bf_lo(pp[1]) + bf_hi(pp[1]));
#pragma unroll
    for (int j = 0; j < 4; j++) {
      const int c = 4 * half + j;
      const uint32_t v0 = __ldcg((const uint16_t*)(vb + (k0 + 2 * q) * 128 + ((c ^ (2 * q)) << 4) + g * 2));
      const uint32_t v1 = __ldcg((const uint16_t*)(vb + (k0 + 2 * q + 1) * 128 + ((c ^ (2 * q + 1)) << 4) + g * 2));
      o[j][0] *= a0; o[j][1] *= a0; o[j][2] *= a1; o[j][3] *= a1;
      hmma8(o[j], pp, v0 | (v1 << 16));
    }
  }
  l0 += __shfl_xor_sync(0xffffffffu, l0, 1); l1 += __shfl_xor_sync(0xffffffffu, l1, 1);
  O[32] = l0 + __shfl_xor_sync(0xffffffffu, l0, 2); O[34] = l1 + __shfl_xor_sync(0xffffffffu, l1, 2);
#pragma unroll
  for (int i = 0; i < 16; i++) O[i] = o[i >> 2][i & 3];
}

constexpr uint16_t fill_entry(int f, int r) {
  int m = 0, x = r, y = 0, dx = 0;
  if (f < F_QKV || f >= 48) {
    const int i = f & 15;
    m = f < F_QKV ? M_FF1A : M_FF2A;
    if (i < 8) { x = 4 * r + ((0xE2u >> i) & 1) * 2; y = r ^ ((0xE790u >> (2 * i)) & 3); dx = 1; }
    else { m++; x = r ^ (7 - (i >> 1)); y = 4 * r + 2 * (i & 1); }
  } else if (f < F_KV) {
    const int i = f - F_QKV;
    m = M_QKV;
    if (i >= 4) { y = r ^ ((i & 1) * 2); }
    else { x = 4 + r; y = r ^ i; dx = 4; }
  } else if (f >= F_PW1 && f < F_PW2) {
    m = M_PW1; y = r ^ (f - F_PW1); dx = 4;
  } else {
    m = f < F_PW1 ? M_WO : M_PW2; y = r ^ ((f & 1) * 2);
  }
  return (uint16_t)(m | (x << 4) | (y << 8) | (dx << 12));
}
__device__ __forceinline__ void tma_fill(uint32_t st, const CUtensorMap* map, uint32_t x, uint32_t y, uint32_t x2, uint32_t y2) {
  asm volatile("{\n.reg .pred p;\nelect.sync _|p, 0xffffffff;\n"
               "@p mbarrier.arrive.expect_tx.shared::cta.b64 _, [%1], 16384;\n"
               "@p cp.async.bulk.tensor.2d.shared::cluster.global.mbarrier::complete_tx::bytes [%0], [%2, {%3, %4}], [%1];\n"
               "@p cp.async.bulk.tensor.2d.shared::cluster.global.mbarrier::complete_tx::bytes [%0 + 8192], [%2, {%5, %6}], [%1];\n}"
               :: "r"(own_cta(SM_BASE + st * STAGE_BYTES)), "r"(own_cta(SM_BASE + SM_FULL + st * 8)), "l"(map), "r"(x), "r"(y), "r"(x2), "r"(y2) : "memory");
}
__device__ __forceinline__ void weight_fills(const Params& p, uint32_t r, uint32_t f, uint32_t step, uint32_t end, uint32_t st, uint32_t parity) {
#pragma unroll 1
  do {
    const uint32_t e = p.fill[r][f];
    const uint32_t x = (e << 2) & 0x3C0, y = (e >> 2) & 0x3C0, dx = (e >> 6) & 0x3C0;
    mbar_wait(SM_BASE + SM_EMPTY + st * 8, parity);
    tma_fill(st, &p.map[e & 15], x, y, x + dx, dx ? y : y ^ 64);
    st += step;
    if (st >= NSTAGE) { st -= NSTAGE; parity ^= 1; }
    f += step;
  } while (f < end);
}
__device__ __forceinline__ void kv_fills(const uint4* kv) {
  uint64_t blocks = KV_ORDER;
#pragma unroll 1
  for (int i = 0; i < 16; i++, blocks >>= 4) {
    const uint32_t e = (uint32_t)blocks & 15, j = e & 7, st = ((0x10985410u >> (4 * j)) & 15) + (e >> 3) * 2;
    mbar_wait(SM_BASE + SM_EMPTY + st * 8, j < 6);
    uint32_t have, spin = 0;
#pragma unroll 1
    do {
      asm volatile("ld.volatile.shared.u32 %0, [%1];" : "=r"(have) : "r"(own_cta(SM_BASE + SM_KVRDY)) : "memory");
    } while (!((have >> (2 * e)) & 1) && ++spin < (SPIN_LIMIT << 4));
    asm volatile("{\n.reg .pred p;\nelect.sync _|p, 0xffffffff;\n"
                 "@p mbarrier.arrive.expect_tx.shared::cta.b64 _, [%1], 16384;\n"
                 "@p cp.async.bulk.shared::cluster.global.mbarrier::complete_tx::bytes [%0], [%2], 16384, [%1];\n}"
                 :: "r"(own_cta(SM_BASE + st * STAGE_BYTES)), "r"(own_cta(SM_BASE + SM_FULL + st * 8)), "l"(kv + e * 1024) : "memory");
    PROF_AT(256 + 512 + (10 + e) * 4);
  }
}
__device__ __forceinline__ uint32_t kv_poll(const uint32_t* flag, uint32_t prev) {
  uint32_t v;
  asm volatile("ld.relaxed.gpu.global.u32 %0, [%1];" : "=r"(v) : "l"(flag) : "memory");
  v = __ballot_sync(0xffffffffu, v - 1 == prev);
  asm volatile("st.volatile.shared.u32 [%0], %1;" :: "r"(own_cta(SM_BASE + SM_KVRDY)), "r"(v & (v >> 1)) : "memory");
  return v;
}
__device__ __forceinline__ void reset_mailboxes(Scratch* sc, int half, int lane, uint32_t t_start) {
  while (clock_now() - t_start < TC) {}
#pragma unroll 1
  for (int i = half * 6; i < half * 7 + 6; i++) {
    const uint32_t t0 = clock_now();
    uint4* dst = &sc->x[cta_id() ^ (i < 8 ? 3 - (i >> 2) : 0)][i * 128 + lane];
#pragma unroll
    for (int k = 0; k < 4; k++) st_vec(dst + 32 * k, 0u, 0u, 0u, 0u);
    while (clock_now() - t0 < CLR_PACE) {}
  }
  asm volatile("barrier.cluster.wait.aligned;" ::: "memory");
  bar_arrive(BAR_RST, 192);
  PROF_AT(256 + 512 + 28 * 4);
  asm volatile("fence.acq_rel.gpu;" ::: "memory");
  __syncwarp();
  announce<3>(sc, lane == 0);
  PROF_AT(256 + 512 + 2 * 4);
}
__device__ __forceinline__ void l2_prefetch(const void* p, uint32_t total, uint32_t b) {
  const uint32_t part = total / NCTA;
  asm volatile("{\n.reg .pred p;\nelect.sync _|p, 0xffffffff;\n@p cp.async.bulk.prefetch.L2.global [%0], %1;\n}"
               :: "l"((const char*)p + b * part), "r"(part) : "memory");
}

__global__ void __cluster_dims__(2, 1, 1) __launch_bounds__(384, 1) conformer_kernel(Scratch* __restrict__ sc, __nv_bfloat16* __restrict__ out,
                                                           const __nv_bfloat16* __restrict__ dw, const __nv_bfloat16* __restrict__ xin,
                                                           const __grid_constant__ Params p) {
  const int tid = threadIdx.x, lane = tid & 31;
  PROF_AT(256 + (tid >> 7) * 256);
  PROF_TIME(30);
  const int b = cta_id(), r = b & 3, batch = b >> 6, t = (b >> 2) & 15;
  if (tid < 128) {
    const uint32_t crow = (tid >> 1 & 48) + (lane >> 3), g0 = batch * T_SEQ + t * 64 + crow;
    const char* lo = (const char*)xin + (min(g0, 2 * T_SEQ - 5) * 512 + (lane & 7) * 16 + 1024);
    const char* hi = (const char*)xin + (min(g0 + 8, 2 * T_SEQ - 5) * 512 + (lane & 7) * 16 + 1024);
    asm volatile("" : "+l"(lo), "+l"(hi));
    const uint32_t dst = (3 ^ r) * TILE_BYTES + crow * 128 + (((lane & 7) ^ (lane >> 3)) << 4);
#pragma unroll
    for (int c = 0; c < 4; c++)
#pragma unroll
      for (int i = 0; i < 4; i++)
        cp_async16(SM_BASE + SM_STG + (dst ^ (c * TILE_BYTES + ((i & 1) << 6))) + i * 512, ((i & 2) ? hi : lo) + c * 128 + (i & 1) * 2048 - 1024);
  }
  PROF_AT(256 + (tid >> 7) * 256 + 44 * 4);
  if ((own_cta(SM_BASE) & 0xFFFFFFu) != SM_BASE) return;
  const int cw = __shfl_sync(0xffffffffu, tid >> 5, 0), wg = cw >> 2, w = cw & 3;

  if (wg == 2) {
    asm volatile("setmaxnreg.dec.sync.aligned.u32 40;");
    const uint32_t t_start = clock_now();
    if (cw != 9) CLUSTER_ARRIVE();
    if (cw == 8) {
      if (lane == 0) {
        asm volatile("prefetch.tensormap [%0];" :: "l"(&p.map[M_FF1A]) : "memory");
#pragma unroll
        for (int i = 0; i < NSTAGE; i++) mbar_init(SM_BASE + SM_FULL + i * 8, 1);
        fence_async_smem();
      }
      __syncwarp();
      bar_arrive(0, 320);
      PROF_MARK(9);
#pragma unroll
      for (int f = 0; f < 8; f++) {
        const uint32_t x = 256 * r + ((0xE2u >> f) & 1) * 128, y = (r ^ ((0xE790u >> (2 * f)) & 3)) * 64;
        tma_fill(f, &p.map[M_FF1A], x, y, x + 64, y);
      }
      PROF_MARK(1);
      l2_prefetch(p.w_ff1b, 1024 * 256 * 2, b);
      l2_prefetch(p.w_qkv, 256 * 768 * 2, b);
      l2_prefetch(p.w_pw1, 256 * 512 * 2, b);
      l2_prefetch(p.w_ff2a, 256 * 1024 * 2, b);
      mbar_wait(SM_BASE + SM_FULL + HOLD * 8, 0);
      l2_prefetch(p.w_o, 256 * 256 * 2, b);
      l2_prefetch(p.w_pw2, 256 * 256 * 2, b);
      l2_prefetch(p.w_ff2b, 1024 * 256 * 2, b);
      if (b < 15) l2_prefetch(dw, 512 * NCTA, b);
      bar_sync(BAR_INIT, 64);
    } else if (here(cw) != 11) {
      const int kind = w - 1;
      const uint32_t prev = launch_index(sc);
      if (kind == 0) {
        if (lane == 0) {
#pragma unroll
            for (int i = 0; i < NSTAGE; i++) mbar_init(SM_BASE + SM_EMPTY + i * 8, 4);
          sts32(SM_BASE + SM_KVRDY, 0u);
#pragma unroll
          for (int i = 0; i < 3; i++) mbar_init(SM_BASE + SM_LAND + i * 8, 1);
          asm volatile("fence.mbarrier_init.release.cluster;" ::: "memory");
        }
        __syncwarp();
        CLUSTER_ARRIVE();
        bar_arrive(0, 320);
        bar_arrive(BAR_INIT, 64);
      }
      reset_mailboxes(sc, kind, lane, t_start);
      if (kind) {
        const uint32_t* flag = sc->flag[batch * 4 + r][lane];
        kv_poll(flag, prev);
        bar_sync(BAR_K, 192);
        uint32_t spin = 0;
#pragma unroll 1
        while (kv_poll(flag, prev) != 0xffffffffu && ++spin < SPIN_LIMIT) {}
        bar_sync(BAR_TAP, 96);
      } else {
#pragma unroll 1
        for (int m = here(0); m < 7; m++) {
          if (m == 2) {
#pragma unroll 1
            for (int k = 0; k < 2; k++) {
              if (k == 0) bar_sync(BAR_K, 192); else bar_sync(BAR_V, 160);
              fence_async_smem();
              PROF_MARK(4 + k * 2);
              asm volatile("{\n.reg .pred p;\nelect.sync _|p, 0xffffffff;\n"
                           "@p cp.async.bulk.global.shared::cta.bulk_group [%0], [%1], 8192;\n"
                           "cp.async.bulk.commit_group;\ncp.async.bulk.wait_group 0;\n"
                           "@p st.relaxed.gpu.global.u32 [%2], %3;\n}"
                           :: "l"(sc->kv[batch * 4 + r][k][t]), "r"(own_cta(SM_BASE + SM_STG + k * TILE_BYTES)),
                              "l"(sc->flag[batch * 4 + r][k * 16 + t]), "r"(prev + 1) : "memory");
              PROF_MARK(5 + k * 2);
            }
            if (lane == 0) asm volatile("mbarrier.arrive.shared::cluster.b64 _, [%0];" :: "r"(partner(SM_BASE + SM_LAND + 16)) : "memory");
            mbar_wait(SM_BASE + SM_LAND + 16, 0);
            bar_sync(BAR_HALF, 288);
          } else {
            bar_sync(BAR_PUSH, 160);
          }
          push(m == 2 ? SM_ATT : SM_BASE + SM_STG + (2 + (m & 1)) * TILE_BYTES, m & 1);
        }
      }
    } else {
      const uint32_t* watch = sc->step[(b & ~3) + (lane & 3)];
      uint32_t seen;
      asm volatile("ld.relaxed.gpu.global.u32 %0, [%1];" : "=r"(seen) : "l"(watch) : "memory");
      if (lane == 0) {
#pragma unroll
        for (int i = M_FF1B; i < M_COUNT; i++) asm volatile("prefetch.tensormap [%0];" :: "l"(&p.map[i]) : "memory");
      }
      asm volatile("barrier.cluster.wait.aligned;" ::: "memory");
      uint32_t want = (seen & ~15u) + 6;
      acquire_n<2, 3>(); GO();
#pragma unroll 1
      for (int pass = 0;; pass++) {
        acquire_n<5, 2>(); GO();
        acquire_n<7, 1>(); GO();
        acquire_n<8, 2>(); GO();
        acquire_n<10, 2>(); GO();
        acquire_n<12, 2>(); GO();
        acquire_n<14, 2>(); GO();
        if (pass) break;
        acquire_n<F_QKV, 4>(); GO();
#pragma unroll 1
        for (int k = here(0); k < 5; k++) {
          if (k == 1) {
            acquire_n<F_QKV + 4, 1>(); GO();
            acquire_n<F_QKV + 5, 1>(); GO();
            bar_sync(BAR_TAP, 96);
#pragma unroll 5
            for (int i = 0; i < 15; i++) {
              uint32_t v = __ldg((const uint32_t*)(dw + i * DM + 64 * r) + lane);
              asm("mul.rn.bf16x2 %0, %0, %1;" : "+r"(v) : "r"(0x3F003F00u));
              sts32(SM_TAPS + i * 128 + lane * 4, v);
            }
            bar_arrive(BAR_MERGE, 288);
          }
          if (k == 3) acquire_n<F_PW2, 7>();
          want += 2;
          uint32_t spin = 0;
#pragma unroll 1
          do {
            asm volatile("ld.relaxed.gpu.global.u32 %0, [%1];" : "=r"(seen) : "l"(watch) : "memory");
          } while (__any_sync(0xffffffffu, (int)(seen - want) < 0) && ++spin < SPIN_LIMIT);
          if (k == 1) acquire_n<F_WO, 6>();
          GO();
        }
      }
    }
    if ((cw & 1) == 0) {
#pragma unroll 1
      for (uint32_t late = w >> 1;; late++) {
        weight_fills(p, r, late ? F_WO + (w >> 1) : 8, late + 1, late ? F_TOTAL : F_SPARE, late ? F_WO % NSTAGE + (w >> 1) : 8, late ^ 1);
        if (late) break;
#pragma unroll
        for (int i = F_SPARE % NSTAGE; i < NSTAGE; i++) {
          mbar_wait(SM_BASE + SM_EMPTY + i * 8, 0);
          asm volatile("{\n.reg .pred p;\nelect.sync _|p, 0xffffffff;\n@p mbarrier.arrive.shared::cta.b64 _, [%0];\n}"
                       :: "r"(own_cta(SM_BASE + SM_FULL + i * 8)) : "memory");
        }
        kv_fills(sc->kv[batch * 4 + r][0][0]);
      }
    }
  } else {
    asm volatile("setmaxnreg.inc.sync.aligned.u32 232;");
    const int q = lane & 3, th = tid & 127;
    constexpr uint32_t stg = SM_BASE + SM_STG;
    const uint32_t mrow = 16 * w + (lane & 15);
    const uint32_t maddr = stg + mrow * 128 + (((lane >> 4) ^ (lane & 7)) << 4);
    const uint32_t qslot = stg + 2 * TILE_BYTES + w * 2048 + lane * 16;
    uint4* const xp = &sc->x[b][th];
    const int nvalid = T_SEQ - t * 64, row0 = 16 * w + (lane >> 2);

    uint32_t A[4][16];
    uint32_t st[4], sent = 0;
    if (wg == 1) {
      if (th < 112) sts128(SM_BASE + SM_CS + th * 16, 0, 0, 0, 0);
      sts32(SM_BASE + SM_EYE + th * 4, th >= 96 ? 0x3F803F80u : ((th & 32) == 0 && (th & 3) == ((th >> 3) & 3)) ? (0x3F00u << ((th & 4) * 4)) : 0u);
      fence_async_smem();
    }
    bar_sync(0, 320);
    if (wg == 0) {
      RowAcc ra = {};
      asm volatile("cp.async.wait_all;" ::: "memory");
      __syncwarp();
      PROF_MARK0(45);
#pragma unroll
      for (int c = 0; c < 4; c++) tile_load(maddr + (3 - c) * TILE_BYTES, A[c]);
      row_sums(ra, A[0]); row_gram(ra, A[0]); row_sums(ra, A[1]); row_gram(ra, A[1]);
      pin(ra.s[0]); pin(ra.s[1]); pin(ra.u[0]); pin(ra.u[1]); pin(ra.v[0]); pin(ra.v[1]);
      SCHED();
      row_sums(ra, A[2]); row_sums(ra, A[3]); row_gram(ra, A[2]); row_gram(ra, A[3]);
      const float m0 = (ra.s[0][0] + ra.s[1][0]) * (1.f / DM), m1 = (ra.s[0][2] + ra.s[1][2]) * (1.f / DM);
      st[0] = pack2(m0, m0); st[1] = pack2(m1, m1);
      centre(A[0], st[0], st[1]);
      const float2 sq = row_squares(ra, lane & 4);
      st[2] = __float_as_uint(fmaf(-m0, m0, sq.x * (1.f / DM))); st[3] = __float_as_uint(fmaf(-m1, m1, sq.y * (1.f / DM)));
    } else {
      CLUSTER_ARRIVE();
      const uint32_t tag = ~launch_index(sc) & 1;
      mbar_wait(SM_BASE + SM_FULL + CSAT * 8, 0);
      PROF_MARK(5);
      if (t >= 7) {
        const int job = b - 28 * (batch + 1);
        const __nv_bfloat16* wp; int ld, col;
        if (job < 24) { wp = p.w_qkv; ld = 768; col = job * 32; }
        else if (job < 40) { wp = p.w_pw1; ld = 512; col = (job - 24) * 32; }
        else { wp = p.w_ff2a; ld = 1024; col = (job - 40) * 32; }
        const uint4* src = (const uint4*)(wp + (size_t)(th >> 2) * ld + col + q * 8);
        float c[8] = {0.f, 0.f, 0.f, 0.f, 0.f, 0.f, 0.f, 0.f};
#pragma unroll 1
        for (int h = here(0); h < 2; h++, src += 16 * ld) {
#pragma unroll
          for (int i = 0; i < 4; i++) {
            const uint4 v = __ldg(src + i * 4 * ld);
            c[0] += bf_lo(v.x); c[1] += bf_hi(v.x); c[2] += bf_lo(v.y); c[3] += bf_hi(v.y);
            c[4] += bf_lo(v.z); c[5] += bf_hi(v.z); c[6] += bf_lo(v.w); c[7] += bf_hi(v.w);
          }
        }
#pragma unroll 1
        for (int m = 4; m <= 16; m <<= 1)
#pragma unroll
          for (int k = 0; k < 8; k++) c[k] += __shfl_xor_sync(0xffffffffu, c[k], m);
        if (lane < 4) {
          const uint32_t a = SM_BASE + SM_CS + 1792 + w * 128 + lane * 32;
          sts128(a, __float_as_uint(c[0]), __float_as_uint(c[1]), __float_as_uint(c[2]), __float_as_uint(c[3]));
          sts128(a + 16, __float_as_uint(c[4]), __float_as_uint(c[5]), __float_as_uint(c[6]), __float_as_uint(c[7]));
        }
        bar_sync(BAR_WG1, 128);
        if (th < 8) {
          float o[4] = {0.f, 0.f, 0.f, 0.f};
#pragma unroll 1
          for (int k = 0; k < 4; k++) {
            uint32_t e[4];
            lds128(SM_BASE + SM_CS + 1792 + k * 128 + th * 16, e[0], e[1], e[2], e[3]);
#pragma unroll
            for (int i = 0; i < 4; i++) o[i] += __uint_as_float(e[i]);
          }
          st_vec(&sc->cs[job * 8 + th], (__float_as_uint(o[0]) & ~1u) | tag, __float_as_uint(o[1]), __float_as_uint(o[2]), __float_as_uint(o[3]));
        }
      }
      bar_sync(BAR_WG1, 128);
      PROF_MARK(2);
      if (th < 72) {
        const int j = th >> 3, i = (th & 7) * 2;
        int src;
        if (j < CS_PW1) src = 320 + 64 * r + 16 * j;
        else if (j < CS_QKV) src = 192 + (j - CS_PW1) * 64 + 16 * r;
        else src = ((j - CS_QKV + 1) % 3) * 64 + 16 * r;
        uint32_t e[8], hi[4], lo[4], spin = 0;
#pragma unroll 1
        do {
          if (spin) __nanosleep(CSNAP);
          ld_vec(&sc->cs[src + i], e[0], e[1], e[2], e[3]);
          ld_vec(&sc->cs[src + i + 1], e[4], e[5], e[6], e[7]);
        } while ((((e[0] ^ tag) | (e[4] ^ tag)) & 1u) && ++spin < SPIN_LIMIT);
        e[0] &= ~1u; e[4] &= ~1u;
#pragma unroll
        for (int k = 0; k < 4; k++) {
          const float c0 = __uint_as_float(e[2 * k]), c1 = __uint_as_float(e[2 * k + 1]);
          hi[k] = pack2(c0, c1);
          lo[k] = pack2(c0 - bf_lo(hi[k]), c1 - bf_hi(hi[k]));
        }
        const uint32_t a = SM_BASE + SM_CS + j * 256 + i * 8;
        sts128(a ^ ((a >> 3) & 0x70), hi[0], hi[1], hi[2], hi[3]);
        sts128((a + 128) ^ (((a + 128) >> 3) & 0x70), lo[0], lo[1], lo[2], lo[3]);
      }
      fence_async_smem();
      PROF_MARK(4);
      bar_arrive(BAR_CS, 256);
    }

#pragma unroll 1
    for (uint32_t pass = 0; pass < 2; pass++) {
      uint32_t Q[16], shift;
      if (wg == 0) {
        float acc[4][32];
        uint32_t H[4][16];
        if (!pass) { PROF_MARK(47); ACQUIRE(0); }
        mma_tile<true>(acc[0], A[0], LO(0)); mma_tile<true>(acc[1], A[0], HI(0));
        if (pass) {
          gather_first<X_AG0>(A, st, sc, xp, maddr, 0, sent, [&] { mma_tile<true>(acc[2], A[0], LO(1)); mma_tile<true>(acc[3], A[0], HI(1)); });
        } else {
          CLUSTER_ARRIVE();
          centre(A[1], st[0], st[1]);
          ACQUIRE(1);
          mma_tile<true>(acc[2], A[0], LO(1)); mma_tile<true>(acc[3], A[0], HI(1));
          SCHED();
          centre(A[2], st[0], st[1]);
          GO();
        }
        mma_tile<false>(acc[0], A[1], LO(2)); mma_tile<false>(acc[1], A[1], HI(2));
        if (pass) {
          gather_rest<X_AG0>(A, xp, 1);
        } else {
          centre(A[3], st[0], st[1]);
        }
        PROF_MARK2(2, 18);
        mma_tile<false>(acc[0], A[2], LO(3)); mma_tile<false>(acc[0], A[3], LO(4));
        WG_WAIT(4);
        uint32_t mu[4] = {0u, 0u, 0u, 0u};
        float rs0, rs1, tn[2][4];
        if (pass) {
          stat_confirm(sc, st, 1);
          fence_async_smem();
          RELEASE(F_WO - 2 + NREL, F_PW2 + 1);
          const RowNorm n = stat_finish(st, 0.5f);
          rs0 = n.rs0; rs1 = n.rs1;
          mean_frag(mu, n, q == 0);
        } else {
          const int src = (lane & 28) | (lane >> 3);
          rs0 = 0.5f * rsqrt_hw(fmaxf(__uint_as_float(__shfl_sync(0xffffffffu, st[2], src)), 0.f) + LN_EPS);
          rs1 = 0.5f * rsqrt_hw(fmaxf(__uint_as_float(__shfl_sync(0xffffffffu, st[3], src)), 0.f) + LN_EPS);
        }
        pin(mu);
        mma_fold<2 * CS_FF2>(acc[0], mu);
        RELEASE(0, 1);
        mma_tile<false>(acc[1], A[2], HI(3));
#define SEGS(a, b) silu_segs<a, b>(acc, tn, H, rs0, rs1)
        WG_WAIT(1); pin(acc[0]);
        PROF_MARK2(49, 55);
        SEGS(0, 1);
        mma_tile_fold<2 * CS_FF2 + 2>(acc[1], A[3], HI(4), mu);
        SEGS(1, 4);
        GO();
        mma_tile<false>(acc[2], A[1], LO(5));
        SEGS(4, 6);
        mma_tile<false>(acc[2], A[2], LO(6));
        SEGS(6, 8);
        WG_WAIT(2); pin(acc[1]);
        RELEASE(2, 4);
        SEGS(8, 9);
        GO();
        mma_tile_fold<2 * CS_FF2 + 4>(acc[2], A[3], LO(7), mu);
        SEGS(9, 12);
        mma_tile<false>(acc[3], A[1], HI(5));
        SEGS(12, 14);
        mma_tile<false>(acc[3], A[2], HI(6));
        SEGS(14, 16);
        WG_WAIT(2); pin(acc[2]);
        SEGS(16, 17);
        mma_tile_fold<2 * CS_FF2 + 6>(acc[3], A[3], HI(7), mu);
        SEGS(17, 20);
        GO();
        mma_tile_reuse(acc[1], H[0], LO(8));
        SEGS(20, 22);
        mma_tile<false>(acc[1], H[1], HI(8));
        SEGS(22, 24);
        WG_WAIT(2); pin(acc[3]);
        RELEASE(5, 7);
        SEGS(24, 26);
        mma_tile<false>(acc[1], H[2], LO(9));
        SEGS(26, 28);
        GO();
        mma_tile_reuse(acc[2], H[0], LO(10));
        SEGS(28, 31);
        mma_tile<false>(acc[2], H[1], HI(10));
        SEGS(31, 34);
#undef SEGS
        PROF_MARK2(3, 19);
        const uint32_t rtag = here(pass ^ 1);
        const uint4* rs_in = xp + X_RS;
        mma_tile<false>(acc[1], H[3], HI(9));
        mma_tile<false>(acc[2], H[2], LO(11));
        uint4* rs_out = peer<3>(xp) + X_RS;
        mma_tile<false>(acc[2], H[3], HI(11));
        GO();
        if (!pass) bar_sync(BAR_RST, 192);
        WG_WAIT(2); pin(acc[1]);
        send_half<0>(rs_out, acc[1], rtag);
        mma_tile_reuse(acc[3], H[0], LO(12));
        SCHED();
        send_half<1>(rs_out, acc[1], rtag);
        mma_tile<false>(acc[3], H[1], HI(12));
        rs_out = peer<2>(xp) + X_RS + 512;
        WG_WAIT(2); pin(acc[2]);
        send_half<0>(rs_out, acc[2], rtag);
        mma_tile<false>(acc[3], H[2], LO(13));
        SCHED();
        send_half<1>(rs_out, acc[2], rtag);
        mma_tile<false>(acc[3], H[3], HI(13));
        GO();
        mma_tile_reuse(acc[1], H[0], LO(14));
        fetch(rs_in, A[3]);
        SCHED();
        mma_tile<false>(acc[1], H[1], HI(14));
        WG_WAIT(2); pin(acc[3]);
        pack_acc(acc[3], A[1]);
        tile_store(here(maddr) + 2 * TILE_BYTES, A[1]);
        bar_arrive(BAR_PUSH, 160);
        SCHED();
        mma_tile<false>(acc[1], H[2], LO(15));
        SCHED();
        fetch(rs_in + 512, A[2]);
        SCHED();
        mma_tile<false>(acc[1], H[3], HI(15));
        SCHED();
        res_load(maddr, acc[2]);
        if (!pass) GO();
        confirm2(A, rs_in + 512, rs_in, rtag);
        mma_add_half(acc[2], A[3]);
        mma_add_half(acc[2], A[2]);
        announce(sc, tid == 0 && !pass);
        land<0>(A[1], maddr, pass);
        mma_add_half(acc[2], A[1]);
        PROF_MARK2(4, 20);
        WG_WAIT(0); pin(acc[2]); pin(acc[1]);
#pragma unroll
        for (int i = 0; i < 16; i++) A[0][i] = pack2(fmaf(acc[1][2 * i], 0.5f, acc[2][2 * i]), fmaf(acc[1][2 * i + 1], 0.5f, acc[2][2 * i + 1]));
        if (pass) {
          PROF_MARK(21);
          stat_publish(A[0], sc, here(th), 0);
          SCHED();
          sent = clock_now();
#pragma unroll
          for (int i = 0; i < 16; i++) { acc[2][2 * i] = bf_lo(A[0][i]); acc[2][2 * i + 1] = bf_hi(A[0][i]); }
          pin(acc[2]);
          const int row = 16 * w + (lane >> 3);
          uint4* dst = (uint4*)(out + ((size_t)batch * T_SEQ + t * 64 + row) * DM + 64 * r) + (lane & 7);
          asm volatile("" : "+l"(dst));
          while (clock_now() - sent < FD) {}
          stat_fetch(sc, st);
          stat_confirm(sc, st, 0);
          const RowNorm fn = stat_finish(st, 1.f);
          const float nm0 = -fn.m0 * fn.rs0, nm1 = -fn.m1 * fn.rs1;
#pragma unroll
          for (int i = 0; i < 16; i++) {
            const float rs = (i & 1) ? fn.rs1 : fn.rs0, nm = (i & 1) ? nm1 : nm0;
            A[0][i] = pack2(fmaf(acc[2][2 * i], rs, nm), fmaf(acc[2][2 * i + 1], rs, nm));
          }
          tile_store(here(maddr) + TILE_BYTES, A[0]);
          __syncwarp();
          const uint32_t src = stg + TILE_BYTES + row * 128 + (((lane & 7) ^ (lane >> 3)) << 4);
#pragma unroll
          for (int i = 0; i < 4; i++) {
            uint4 v;
            lds128((src ^ ((i & 1) << 6)) + i * 512, v.x, v.y, v.z, v.w);
            if (row + 4 * i < nvalid) dst[i * 4 * (DM / 8)] = v;
          }
          PROF_MARK(22);
          PROF_TIME(31);
          break;
        }
        send_residual(A[0], sc, xp, maddr, 1, sent);
        PROF_MARK(5);
        mma_tile<true>(acc[0], A[0], LO(F_QKV)); mma_tile<true>(acc[1], A[0], HI(F_QKV));
        gather_first<X_AG0>(A, st, sc, xp, maddr, 0, sent, [] {});
        mma_tile<false>(acc[0], A[1], LO(F_QKV + 1)); mma_tile<false>(acc[1], A[1], HI(F_QKV + 1));
        gather_rest<X_AG0>(A, xp, 1);
        PROF_MARK(6);
        mma_tile<false>(acc[0], A[2], LO(F_QKV + 2)); mma_tile<false>(acc[0], A[3], LO(F_QKV + 3));
        bar_sync(BAR_CS, 256);
        SCHED();
        {
          stat_confirm(sc, st, 1);
          if (t >= QT) RELEASE(8, 15);
          const RowNorm n = stat_finish(st, 1.f);
          rs0 = row0 < nvalid ? n.rs0 : 0.f; rs1 = row0 + 8 < nvalid ? n.rs1 : 0.f;
          mean_frag(mu, n, q == 3);
        }
        mma_fold<2 * CS_QKV - 6>(acc[0], mu);
        WG_WAIT(0); pin(acc[0]);
        uint32_t K[16];
        scale_pack(acc[0], K, rs0, rs1);
        tile_store(here(maddr), K);
        bar_arrive(BAR_K, 192);
        if (t < QT) RELEASE(8, 15);
        SCHED();
        mma_tile<false>(acc[1], A[2], HI(F_QKV + 2));
        mma_tile_fold<2 * CS_QKV - 4>(acc[1], A[3], HI(F_QKV + 3), mu);
        WG_WAIT(0); pin(acc[1]);
        scale_pack(acc[1], Q, rs0, rs1);
        tile_store(here(maddr) + TILE_BYTES, Q);
        bar_arrive(BAR_V, 160);
        GO();
        mma_tile<true>(acc[2], A[0], LO(F_QKV + 4)); mma_tile<false>(acc[2], A[1], HI(F_QKV + 4));
        GO();
        mma_tile<false>(acc[2], A[2], LO(F_QKV + 5));
        mma_tile_fold<2 * CS_QKV - 2>(acc[2], A[3], HI(F_QKV + 5), mu);
        RELEASE(F_QKV, F_QKV + 3);
        WG_WAIT(0); pin(acc[2]);
        scale_pack(acc[2], Q, rs0 * SM_SCALE_LOG2, rs1 * SM_SCALE_LOG2);
        frag_store(here(qslot), Q);
        {
          uint32_t d[4] = {0u, 0u, 0u, 0u};
#pragma unroll
          for (int i = 0; i < 16; i++) asm("fma.rn.bf16x2 %0, %1, %2, %0;" : "+r"(d[i & 3]) : "r"(Q[i]), "r"(K[i]));
          float s0 = (bf_lo(d[0]) + bf_hi(d[0])) + (bf_lo(d[2]) + bf_hi(d[2])), s1 = (bf_lo(d[1]) + bf_hi(d[1])) + (bf_lo(d[3]) + bf_hi(d[3]));
          shift = pack2(-s0, -s1);
          sts32(SM_BASE + SM_CS + 2 * CS_QKV * 128 + here(th) * 4, shift);
        }
        RELEASE(F_QKV + 4, F_QKV + 5);
        bar_arrive(BAR_Q, 256);
      } else {
        bar_sync(BAR_Q, 256);
#pragma unroll
        for (int s = 0; s < 4; s++) lds128(qslot + s * 512, Q[4 * s], Q[4 * s + 1], Q[4 * s + 2], Q[4 * s + 3]);
        shift = lds32(SM_BASE + SM_CS + 2 * CS_QKV * 128 + th * 4);
        if (w < 2) {
          const uint32_t v = w ? 0u : 0x3F803F80u;
#pragma unroll
          for (int s = 0; s < 4; s++) sts128(qslot + s * 512, v, v, v, v);
          fence_async_smem();
        }
        if (w == 3) bar_arrive(BAR_TAP, 96);
      }
      PROF_MARK(7);

      float O[36];
      {
        float S[2][32];
        uint32_t P[3][16], nm[4] = {shift & 0xFFFFu, shift >> 16, 0u, 0u};
        pin(Q); pin(nm);
        const uint64_t kb = RING + wg * 1024, vb = RING_V + wg * 1024 * V_STEP;
        const uint32_t full = SM_BASE + SM_FULL + wg * 8, empty = SM_BASE + SM_EMPTY + wg * 8;
        mbar_wait(full + F_SPARE % NSTAGE * 8, 1);
        if (wg == 1) bar_sync(BAR_ATT, 256);
        mbar_wait(full, 0);
        PROF_MARK(8);
        WG_FENCE();
        qk_tile(S[0], Q, nm, kb);
        WG_COMMIT();
        if (ATT_EARLY && wg == 0) bar_sync(BAR_ATT, 256);
        WG_WAIT(0); pin(S[0]);
        if (!ATT_EARLY && wg == 0) bar_sync(BAR_ATT, 256);
#pragma unroll
        for (int h = 0; h < 8; h++) {
          const int it = h >> 1, c = h & 1;
          const int sk = it == 3 ? 0 : 4 * it, sn = it >= 2 ? 0 : 4 * it + 4, sv = sk + 2, sp = it ? 4 * it - 2 : F_SPARE % NSTAGE;
          WG_FENCE();
          if (h < 7) qk_tile(S[c ^ 1], Q, nm, kb + (c ? sn * 1024 : sk * 1024 + 512));
          if (h == 1 + PV_LATE) pv_tile<true>(O, P[0], vb + (uint64_t)(2 * 1024 * V_STEP), 0);
          if (h > 1) pv_tile<false>(O, P[(h - 1) % 3], vb + (c ? sv * 1024 : sp * 1024 + 512) * V_STEP, 0);
          WG_COMMIT();
          SCHED();
          const bool nk = !c && it < 3, nv = h == PV_LATE || (!c && it);
          uint32_t ok = 1;
          if (nk) mbar_probe(ok, full + sn * 8, it == 2);
          if (nv) mbar_probe(ok, full + sv * 8, it == 3);
#pragma unroll
          for (int i = 0; i < 16; i++) {
            P[h % 3][i] = pack2(ex2_hw(S[c][2 * i]), ex2_hw(S[c][2 * i + 1]));
            asm volatile("" : "+r"(P[h % 3][i]));
          }
          SCHED();
          if (h == 0) PROF_MARK(24);
          if ((nk || nv) && __builtin_expect(!ok, 0)) {
            if (nk) mbar_wait(full + sn * 8, it == 2);
            if (nv) mbar_wait(full + sv * 8, it == 3);
          }
          WG_WAIT(0);
          if (h > PV_LATE) pin(O);
          if (h < 7) pin(S[c ^ 1]);
          if (!c && lane == 0) { mbar_arrive(empty + sk * 8); mbar_arrive(empty + sp * 8); }
          if (h == 0) PROF_MARK(25);
        }
        WG_FENCE();
        pv_tile<false>(O, P[7 % 3], vb + (uint64_t)((2 * 1024 + 512) * V_STEP), wg << 22);
        WG_COMMIT();
        announce<1>(sc, th == 0);
        WG_WAIT(0); pin(O);
      }
      PROF_MARK(9);

      {
        const uint32_t mo = SM_BASE + (2 + wg) * STAGE_BYTES + here(th) * 16;
        sts64(stg + 5 * 4096 + th * 16 + wg * 8, __float_as_uint(O[32]), __float_as_uint(O[34]));
        if (wg == 0) {
#pragma unroll
          for (int i = 4; i < 8; i++)
            sts128(mo + (i - 4) * 2048, __float_as_uint(O[4 * i]), __float_as_uint(O[4 * i + 1]), __float_as_uint(O[4 * i + 2]), __float_as_uint(O[4 * i + 3]));
        } else {
#pragma unroll
          for (int i = 0; i < 4; i++)
            sts128(mo + i * 2048, __float_as_uint(O[4 * i]), __float_as_uint(O[4 * i + 1]), __float_as_uint(O[4 * i + 2]), __float_as_uint(O[4 * i + 3]));
#pragma unroll
          for (int i = 0; i < 16; i++) O[i] = O[16 + i];
        }
        bar_sync(BAR_MERGE, 288);
        const uint32_t mi = SM_BASE + (3 - wg) * STAGE_BYTES + here(th) * 16;
        uint32_t e[4];
        asm volatile("ld.shared.v2.u32 {%0, %1}, [%2];" : "=r"(e[0]), "=r"(e[1]) : "r"(own_cta(stg + 5 * 4096 + th * 16 + 8 - wg * 8)) : "memory");
        O[32] += __uint_as_float(e[0]); O[34] += __uint_as_float(e[1]);
#pragma unroll
        for (int i = 0; i < 4; i++) {
          lds128(mi + i * 2048, e[0], e[1], e[2], e[3]);
#pragma unroll
          for (int k = 0; k < 4; k++) O[4 * i + k] += __uint_as_float(e[k]);
        }
        const bool safe = O[32] > 0x1p-60f && O[32] < 0x1p60f && O[34] > 0x1p-60f && O[34] < 0x1p60f;
        if (__builtin_expect(__any_sync(0xffffffffu, !safe), 0)) attention_exact(O, Q, sc, batch * 4 + r, lane, wg);
        const float i0 = rcp_hw(O[32]), i1 = rcp_hw(O[34]);
#pragma unroll
        for (int i = 0; i < 8; i++) { const float v = (i & 1) ? i1 : i0; A[0][i] = pack2(O[2 * i] * v, O[2 * i + 1] * v); }
        A[0][0] &= ~1u; A[0][4] &= ~1u;
        uint4* dst = xp + X_AG1 + wg * 256;
        SCHED();
        st_vec(dst, A[0][0], A[0][1], A[0][2], A[0][3]);
        st_vec(dst + 128, A[0][4], A[0][5], A[0][6], A[0][7]);
        SCHED();
        sent = clock_now();
        const uint32_t ta = (here(maddr) - stg + SM_ATT) ^ (wg << 6);
        stsm4(ta, &A[0][0]); stsm4(ta ^ 32, &A[0][4]);
      }
      const int dir = cw == 0 ? -1 : 1;
      if (wg == 1) {
        bar_arrive(BAR_HALF, 288);
      } else {
        PROF_MARK(10);
        bar_sync(BAR_HALF, 288);
        ldsm4((here(maddr) - stg + SM_ATT) ^ 64, &A[0][8]); ldsm4((here(maddr) - stg + SM_ATT) ^ 96, &A[0][12]);
      }
#pragma unroll 1
      for (uint32_t second = here(0);; second++) {
      uint32_t tap[15];
      if (wg == 1) {
        load_taps(tap, 1);
      } else {
        proj_residual(A, sc, xp, maddr, second, sent);
        PROF_MARK0(12 + 5 * second);
        if (second) break;
        float acc[2][32];
        mma_tile<true>(acc[0], A[0], LO(F_PW1)); mma_tile<true>(acc[1], A[0], HI(F_PW1));
        gather_first<X_AG0>(A, st, sc, xp, maddr, 1, sent, [&] { load_taps(tap, dir); });
        mma_tile<false>(acc[1], A[1], HI(F_PW1 + 1)); mma_tile<false>(acc[0], A[1], LO(F_PW1 + 1));
        gather_rest<X_AG0>(A, xp, 0);
        PROF_MARK(13);
        mma_tile<false>(acc[1], A[2], HI(F_PW1 + 2)); mma_tile<false>(acc[1], A[3], HI(F_PW1 + 3));
        WG_WAIT(2);
        SCHED();
        uint32_t mu[4];
        stat_confirm(sc, st, 0);
        fence_async_smem();
        RELEASE(F_WO - 2, F_WO - 3 + NREL);
        const RowNorm n = stat_finish(st, 0.5f);
        const float rs0 = row0 < nvalid ? n.rs0 : 0.f, rs1 = row0 + 8 < nvalid ? n.rs1 : 0.f;
        mean_frag(mu, n, q == 0);
        mma_fold<2 * CS_PW1 + 2>(acc[1], mu);
        mma_tile<false>(acc[0], A[2], LO(F_PW1 + 2));
        mma_tile_fold<2 * CS_PW1>(acc[0], A[3], LO(F_PW1 + 3), mu);
        WG_WAIT(2); pin(acc[1]);
#pragma unroll
        for (int i = 0; i < 32; i++) acc[1][i] = tanh_hw(acc[1][i] * ((i & 2) ? rs1 : rs0));
#pragma unroll
        for (int i = 0; i < 32; i++) { const float rs = (i & 2) ? rs1 : rs0; acc[1][i] = fmaf(acc[1][i], rs, rs); }
        pin(acc[1]);
        SCHED();
        WG_WAIT(0); pin(acc[0]);
#pragma unroll
        for (int i = 0; i < 16; i++) A[0][i] = pack2(acc[0][2 * i] * acc[1][2 * i], acc[0][2 * i + 1] * acc[1][2 * i + 1]);
        const uint32_t ga = SM_GLU + here(mrow) * G_PITCH + (lane >> 4) * 16;
#pragma unroll
        for (int s = 0; s < 4; s++) stsm4(ga + s * 32, &A[0][4 * s]);
      }
      {
        const uint32_t gsrc = SM_GLU + (8 * cw - 7) * G_PITCH + lane * 4;
        const bool edge = cw == 0 || cw == 7;
        const bool nbr = cw == 0 ? t > 0 : t < 15;
        uint4* const hdst = &sc->x[b + 4 * dir][X_HALO + (cw == 0 ? 96 : 0) + lane];
        uint32_t in[22];
        bar_sync(BAR_G, 256);
        PROF_MARK(14);
        if (cw == 0) {
#pragma unroll
          for (int i = 14; i >= 0; i--) in[i] = lds32(gsrc + (21 - i) * G_PITCH);
        } else {
#pragma unroll
          for (int i = 14; i >= 0; i--) in[i] = lds32(gsrc + i * G_PITCH);
        }
        if (edge) {
          if (nbr) {
            st_vec(hdst, HALO_TAG, in[14], in[13], in[12]);
            st_vec(hdst + 32, HALO_TAG, in[11], in[10], in[9]);
            st_vec(hdst + 64, HALO_TAG, in[8], 0u, 0u);
          }
        } else {
#pragma unroll
          for (int i = 15; i < 22; i++) in[i] = lds32(gsrc + i * G_PITCH);
        }
        if (cw == 0) PROF_MARK0(40);
        uint32_t cv[8];
#pragma unroll
        for (int i = 0; i < 15; i++)
#pragma unroll
          for (int o = 0; o < 8; o++) {
            if (i == o) asm("mul.rn.bf16x2 %0, %1, %2;" : "=r"(cv[o]) : "r"(in[i]), "r"(tap[0]));
            if (i > o) asm("fma.rn.bf16x2 %0, %1, %2, %0;" : "+r"(cv[o]) : "r"(in[i]), "r"(tap[i - o]));
          }
        pin(cv);
        if (cw == 0) PROF_MARK0(41);
        if (edge) {
#pragma unroll
          for (int i = 15; i < 22; i++) in[i] = 0u;
          if (nbr) {
            const uint4* src = &sc->x[b][X_HALO + (cw == 0 ? 0 : 96) + lane];
            uint32_t e0, e1, e2, u0, u1, spin = 0;
#pragma unroll 1
            do {
              ld_vec(src, e0, in[15], in[16], in[17]);
              ld_vec(src + 32, e1, in[18], in[19], in[20]);
              ld_vec(src + 64, e2, in[21], u0, u1);
            } while (__any_sync(0xffffffffu, ((e0 ^ HALO_TAG) | (e1 ^ HALO_TAG) | (e2 ^ HALO_TAG)) != 0) && ++spin < SPIN_LIMIT);
          }
          announce<1>(sc, lane == 0);
        }
#pragma unroll
        for (int i = 15; i < 22; i++)
#pragma unroll
          for (int o = 0; o < 8; o++)
            if (i - o <= 14) asm("fma.rn.bf16x2 %0, %1, %2, %0;" : "+r"(cv[o]) : "r"(in[i]), "r"(tap[i - o]));
        if (cw == 0) PROF_MARK0(42);
        if (cw == 7) PROF_MARK0(43);
        const uint32_t fl = cw == 0 ? 7 : 0;
        const uint32_t cdst = (stg + 2 * TILE_BYTES + cw * 1024 + lane * 4) ^ (fl * 144);
#pragma unroll
        for (int o = 0; o < 8; o++) {
          const float a = bf_lo(cv[o]), c = bf_hi(cv[o]);
          sts32(cdst ^ (o * 144), pack2(fmaf(a, tanh_hw(a), a), fmaf(c, tanh_hw(c), c)));
        }
      }
      if (wg == 1) {
        bar_arrive(BAR_C, 256);
        return;
      }
      bar_sync(BAR_C, 256);
      tile_load(here(maddr) + 2 * TILE_BYTES, A[0]);
      PROF_MARK(15);
      publish(xp + X_AG1, A[0], 1);
      bar_arrive(BAR_PUSH, 160);
      }
    }
  }
}

typedef CUresult (*EncodeFn)(CUtensorMap*, CUtensorMapDataType, cuuint32_t, void*, const cuuint64_t*, const cuuint64_t*,
                             const cuuint32_t*, const cuuint32_t*, CUtensorMapInterleave, CUtensorMapSwizzle,
                             CUtensorMapL2promotion, CUtensorMapFloatOOBfill);

void make_map(EncodeFn fn, CUtensorMap* m, const void* w, int rows, int cols, CUtensorMapSwizzle swz) {
  const cuuint64_t dims[2] = {(cuuint64_t)cols, (cuuint64_t)rows}, strides[1] = {(cuuint64_t)cols * 2};
  const cuuint32_t box[2] = {64, 64}, es[2] = {1, 1};
  fn(m, CU_TENSOR_MAP_DATA_TYPE_BFLOAT16, 2, const_cast<void*>(w), dims, strides, box, es, CU_TENSOR_MAP_INTERLEAVE_NONE,
     swz, CU_TENSOR_MAP_L2_PROMOTION_L2_128B, CU_TENSOR_MAP_FLOAT_OOB_FILL_NONE);
}

}

extern "C" void kernel_launch(void* const* d_in, const int* in_sizes, int n_in, void* d_out, int out_size) {
  static EncodeFn fn = nullptr;
  static Scratch* sc = nullptr;
  if (!fn) {
    void* f = nullptr;
    cudaDriverEntryPointQueryResult st;
    cudaGetDriverEntryPoint("cuTensorMapEncodeTiled", &f, cudaEnableDefault, &st);
    fn = (EncodeFn)f;
    void* raw = nullptr;
    cudaGetSymbolAddress(&raw, g_scratch);
    sc = (Scratch*)(((uintptr_t)raw + X_ALIGN - 1) & ~(uintptr_t)(X_ALIGN - 1));
    cudaFuncSetAttribute(conformer_kernel, cudaFuncAttributeMaxDynamicSharedMemorySize, SM_TOTAL);
  }
  typedef const __nv_bfloat16* W;
  const CUtensorMapSwizzle S = CU_TENSOR_MAP_SWIZZLE_128B;
  Params p;
  make_map(fn, &p.map[M_FF1A], d_in[1], 256, 1024, S);
  make_map(fn, &p.map[M_FF1B], d_in[2], 1024, 256, S);
  make_map(fn, &p.map[M_QKV], d_in[3], 256, 768, S);
  make_map(fn, &p.map[M_WO], d_in[4], 256, 256, S);
  make_map(fn, &p.map[M_PW1], d_in[5], 256, 512, S);
  make_map(fn, &p.map[M_PW2], d_in[7], 256, 256, S);
  make_map(fn, &p.map[M_FF2A], d_in[8], 256, 1024, S);
  make_map(fn, &p.map[M_FF2B], d_in[9], 1024, 256, S);
  for (int i = 0; i < 4 * F_TOTAL; i++) p.fill[i / F_TOTAL][i % F_TOTAL] = fill_entry(i % F_TOTAL, i / F_TOTAL);
  p.w_ff1b = (W)d_in[2]; p.w_qkv = (W)d_in[3]; p.w_o = (W)d_in[4]; p.w_pw1 = (W)d_in[5];
  p.w_pw2 = (W)d_in[7]; p.w_ff2a = (W)d_in[8]; p.w_ff2b = (W)d_in[9];

  cudaLaunchConfig_t cfg = {};
  cfg.gridDim = dim3(NCTA);
  cfg.blockDim = dim3(384);
  cfg.dynamicSmemBytes = SM_TOTAL;
  cfg.stream = cudaStreamPerThread;
  cudaLaunchKernelEx(&cfg, conformer_kernel, sc, (__nv_bfloat16*)d_out, (W)d_in[6], (W)d_in[0], p);
}
```
